```python
import torch

def _softmax(x, axis=-1):
    return torch.softmax(x, dim=axis)
def _gelu(x):
    return torch.nn.functional.gelu(x, approximate="tanh")
def _silu(x):
    return torch.nn.functional.silu(x)
def _sigmoid(x):
    return torch.sigmoid(x)
def _layernorm(x, axis=-1, eps=1e-5):
    m = x.mean(dim=axis, keepdim=True)
    v = x.var(dim=axis, keepdim=True, unbiased=False)
    return (x - m) / torch.sqrt(v + eps)
def _scatter_add(tgt, idx, src, axis=0):
    return tgt.clone().index_add_(axis, idx, src)
def _segment_sum(src, seg, n):
    out = torch.zeros((n,) + src.shape[1:], dtype=src.dtype)
    return out.index_add_(0, seg, src)
def _pad(x, pw):
    flat = tuple(v for pair in reversed(pw) for v in pair)
    return torch.nn.functional.pad(x, flat)

kernel_name = 'interleave_layers__sliding_local_dilated__glu_gated_geglu__prompt'

def setup_inputs():

    _w = (lambda a: (lambda t: t.to(torch.bfloat16) if t.is_floating_point() else t)(torch.as_tensor(a)))
    def _A_setup():
        B, S, D = 1, 2048, 576
        return {
            "x": _w((lambda *s: torch.randn(*s, dtype=torch.bfloat16) * 0.05)(B, S, D)),
            "wqkv": _w((lambda *s: torch.randn(*s, dtype=torch.bfloat16) * 0.05)(D, 3 * D)),
            "wo": _w((lambda *s: torch.randn(*s, dtype=torch.bfloat16) * 0.05)(D, D)),
        }
    _A_in = _A_setup()

    def _B_setup():
        B, S, Dm, Df = 1, 2048, 576, 4608
        return {
            "x": _w((lambda *s: torch.randn(*s, dtype=torch.bfloat16) * 0.05)(B, S, Dm)),
            "w_gate": _w((lambda *s: torch.randn(*s, dtype=torch.bfloat16) * 0.8)(Dm, Df) * (Dm ** -0.5)),
            "w_up": _w((lambda *s: torch.randn(*s, dtype=torch.bfloat16) * 0.8)(Dm, Df) * (Dm ** -0.5)),
            "w_down": _w((lambda *s: torch.randn(*s, dtype=torch.bfloat16) * 0.8)(Df, Dm) * (Df ** -0.5)),
        }
    _B_in = _B_setup()

    return {
        "A_x": _A_in["x"],
        "A_wqkv": _A_in["wqkv"],
        "A_wo": _A_in["wo"],
        "B_x": _B_in["x"],
        "B_w_gate": _B_in["w_gate"],
        "B_w_up": _B_in["w_up"],
        "B_w_down": _B_in["w_down"],
    }

def reference(A_x, A_wqkv, A_wo, B_x, B_w_gate, B_w_up, B_w_down):
    def _A_ref(x, wqkv, wo):
        B, S, D = x.shape
        H = 32; Dh = D // H
        W, dil = 8, 2
        qkv = (lambda x, *d: x.permute(*d))((x @ wqkv).reshape(B, S, 3, H, Dh), 2, 0, 3, 1, 4)
        q, k, v = qkv[0], qkv[1], qkv[2]
        scale = Dh ** -0.5
        pos = torch.arange(S)
        off = torch.arange(W) * dil
        idx = pos[:, None] - off[None, :]
        mask = idx >= 0
        idx_c = torch.where(mask, idx, 0).reshape(-1)
        kg = k[:, :, idx_c, :].reshape(B, H, S, W, Dh)
        vg = v[:, :, idx_c, :].reshape(B, H, S, W, Dh)
        logits = torch.einsum("bhsd,bhswd->bhsw", q, kg) * scale
        logits = torch.where(mask[None, None, :, :], logits, -1e9)
        attn = _softmax(logits, axis=-1)
        o = torch.einsum("bhsw,bhswd->bhsd", attn, vg)
        return (lambda x, *d: x.permute(*d))(o, 0, 2, 1, 3).reshape(B, S, D) @ wo

    def _B_ref(x, w_gate, w_up, w_down):
        g = torch.einsum("bsd,df->bsf", x, w_gate)
        u = torch.einsum("bsd,df->bsf", x, w_up)
        h = _gelu(g) * u
        return torch.einsum("bsf,fd->bsd", h, w_down)

    x = A_x
    x = x + _A_ref(_layernorm(x, axis=-1), A_wqkv, A_wo)
    x = x + _B_ref(_layernorm(x, axis=-1), B_w_gate, B_w_up, B_w_down)
    x = x + _A_ref(_layernorm(x, axis=-1), A_wqkv, A_wo)
    x = x + _B_ref(_layernorm(x, axis=-1), B_w_gate, B_w_up, B_w_down)
    return x
```

```cpp
#include <cuda_runtime.h>
#include <cuda.h>
#include <cuda_bf16.h>
#include <stdint.h>

#define TRACE 0

namespace {

constexpr int NST = 6;
constexpr int STAGE = 16384;
constexpr int PARK = NST * STAGE;
constexpr int REM = PARK + 49152;
constexpr int KVS = REM + 40960;
constexpr int BARS = KVS + 41472;
constexpr int SMEM_BYTES = BARS + 256;
static_assert(BARS >= PARK + 131072, "barriers overlap park");
static_assert(SMEM_BYTES <= 232448, "smem");

constexpr int SLAB = 36 * 32;
constexpr int SPIN_MAX = 1 << 22;

}

__device__ uint4 g_XA[2][128 * SLAB];
__device__ uint4 g_XB[2][128 * SLAB];
__device__ uint4 g_O[2][128 * SLAB];
__device__ uint4 g_P[8 * 128 * SLAB];
__device__ uint4 g_SA[128 * 12 * 8];
__device__ uint4 g_SB[128 * 8 * 8];
__device__ uint4 g_H[2][128 * 2 * 5 * 32];

namespace {

__device__ __forceinline__ void wgmma_rs_n64(float (&d)[32], const uint32_t* a, uint64_t desc, int scale_d) {
  asm volatile("{\n.reg .pred p;\nsetp.ne.b32 p, %37, 0;\n"
    "wgmma.mma_async.sync.aligned.m64n64k16.f32.bf16.bf16 "
    "{%0, %1, %2, %3, %4, %5, %6, %7, %8, %9, %10, %11, %12, %13, %14, %15, %16, %17, %18, %19, %20, %21, %22, %23, %24, %25, %26, %27, %28, %29, %30, %31}, "
    "{%32, %33, %34, %35}, %36, p, 1, 1, 1;\n}\n"
    : "+f"(d[0]), "+f"(d[1]), "+f"(d[2]), "+f"(d[3]), "+f"(d[4]), "+f"(d[5]), "+f"(d[6]), "+f"(d[7]), "+f"(d[8]), "+f"(d[9]), "+f"(d[10]), "+f"(d[11]), "+f"(d[12]), "+f"(d[13]), "+f"(d[14]), "+f"(d[15]), "+f"(d[16]), "+f"(d[17]), "+f"(d[18]), "+f"(d[19]), "+f"(d[20]), "+f"(d[21]), "+f"(d[22]), "+f"(d[23]), "+f"(d[24]), "+f"(d[25]), "+f"(d[26]), "+f"(d[27]), "+f"(d[28]), "+f"(d[29]), "+f"(d[30]), "+f"(d[31])
    : "r"(a[0]), "r"(a[1]), "r"(a[2]), "r"(a[3]), "l"(desc), "r"(scale_d));
}
__device__ __forceinline__ void wgmma_rs_n72(float (&d)[36], const uint32_t* a, uint64_t desc, int scale_d) {
  asm volatile("{\n.reg .pred p;\nsetp.ne.b32 p, %41, 0;\n"
    "wgmma.mma_async.sync.aligned.m64n72k16.f32.bf16.bf16 "
    "{%0, %1, %2, %3, %4, %5, %6, %7, %8, %9, %10, %11, %12, %13, %14, %15, %16, %17, %18, %19, %20, %21, %22, %23, %24, %25, %26, %27, %28, %29, %30, %31, %32, %33, %34, %35}, "
    "{%36, %37, %38, %39}, %40, p, 1, 1, 1;\n}\n"
    : "+f"(d[0]), "+f"(d[1]), "+f"(d[2]), "+f"(d[3]), "+f"(d[4]), "+f"(d[5]), "+f"(d[6]), "+f"(d[7]), "+f"(d[8]), "+f"(d[9]), "+f"(d[10]), "+f"(d[11]), "+f"(d[12]), "+f"(d[13]), "+f"(d[14]), "+f"(d[15]), "+f"(d[16]), "+f"(d[17]), "+f"(d[18]), "+f"(d[19]), "+f"(d[20]), "+f"(d[21]), "+f"(d[22]), "+f"(d[23]), "+f"(d[24]), "+f"(d[25]), "+f"(d[26]), "+f"(d[27]), "+f"(d[28]), "+f"(d[29]), "+f"(d[30]), "+f"(d[31]), "+f"(d[32]), "+f"(d[33]), "+f"(d[34]), "+f"(d[35])
    : "r"(a[0]), "r"(a[1]), "r"(a[2]), "r"(a[3]), "l"(desc), "r"(scale_d));
}

__device__ __forceinline__ void mbar_init(uint32_t a, uint32_t c) { asm volatile("mbarrier.init.shared::cta.b64 [%0], %1;" :: "r"(a), "r"(c)); }
__device__ __forceinline__ void mbar_expect(uint32_t a, uint32_t b) { asm volatile("mbarrier.arrive.expect_tx.shared::cta.b64 _, [%0], %1;" :: "r"(a), "r"(b) : "memory"); }
__device__ __forceinline__ void mbar_arrive(uint32_t a) { asm volatile("mbarrier.arrive.shared::cta.b64 _, [%0];" :: "r"(a) : "memory"); }
__device__ __forceinline__ void mbar_wait(uint32_t a, uint32_t ph) {
  asm volatile("{\n.reg .pred p;\n.reg .u32 n;\n"
               "mbarrier.try_wait.parity.shared::cta.b64 p, [%0], %1;\n@p bra D;\n"
               "mov.u32 n, 0;\n"
               "W: mbarrier.try_wait.parity.shared::cta.b64 p, [%0], %1;\n@p bra D;\n"
               "add.u32 n, n, 1;\nsetp.lt.u32 p, n, 4194304;\n@p bra W;\ntrap;\nD:\n}" :: "r"(a), "r"(ph) : "memory");
}
__device__ __forceinline__ void tma2d(uint32_t dst, const CUtensorMap* m, int c0, int c1, uint32_t bar) {
  asm volatile("cp.async.bulk.tensor.2d.shared::cluster.global.mbarrier::complete_tx::bytes [%0], [%1, {%3, %4}], [%2];"
    :: "r"(dst), "l"(m), "r"(bar), "r"(c0), "r"(c1) : "memory");
}
__device__ __forceinline__ void wg_fence() { asm volatile("wgmma.fence.sync.aligned;" ::: "memory"); }
__device__ __forceinline__ void wg_commit() { asm volatile("wgmma.commit_group.sync.aligned;" ::: "memory"); }
template <int N> __device__ __forceinline__ void wg_wait() { asm volatile("wgmma.wait_group.sync.aligned %0;" :: "n"(N) : "memory"); }
__device__ __forceinline__ uint64_t mk_desc(uint32_t addr, uint32_t lbo, uint32_t sbo) {
  return (uint64_t)((addr & 0x3FFFF) >> 4) | ((uint64_t)(lbo >> 4) << 16) | ((uint64_t)(sbo >> 4) << 32) | (1ull << 62);
}
__device__ __forceinline__ float tanh_ap(float x) { float y; asm("tanh.approx.f32 %0, %1;" : "=f"(y) : "f"(x)); return y; }
__device__ __forceinline__ float ex2(float x) { float y; asm("ex2.approx.ftz.f32 %0, %1;" : "=f"(y) : "f"(x)); return y; }
__device__ __forceinline__ uint32_t pack_bf16(float lo, float hi) { uint32_t r; asm("cvt.rn.bf16x2.f32 %0, %1, %2;" : "=r"(r) : "f"(hi), "f"(lo)); return r; }
__device__ __forceinline__ float bf_lo(uint32_t v) { return __uint_as_float(v << 16); }
__device__ __forceinline__ float bf_hi(uint32_t v) { return __uint_as_float(v & 0xffff0000u); }
__device__ __forceinline__ uint32_t sub_bf16x2(uint32_t a, uint32_t b) { uint32_t r; asm("sub.rn.bf16x2 %0, %1, %2;" : "=r"(r) : "r"(a), "r"(b)); return r; }
__device__ __forceinline__ uint32_t nz(uint32_t w) { return w == 0u ? 0x8000u : w; }

__device__ __forceinline__ void ldg4(uint32_t* d, const uint4* p) {
  asm volatile("ld.relaxed.gpu.global.v4.b32 {%0,%1,%2,%3}, [%4];" : "=r"(d[0]), "=r"(d[1]), "=r"(d[2]), "=r"(d[3]) : "l"(p) : "memory");
}
__device__ __forceinline__ void ldg2(uint32_t* d, const void* p) {
  asm volatile("ld.relaxed.gpu.global.v2.b32 {%0,%1}, [%2];" : "=r"(d[0]), "=r"(d[1]) : "l"(p) : "memory");
}
__device__ __forceinline__ void stg4(uint4* p, uint32_t a, uint32_t b, uint32_t c, uint32_t d) {
  asm volatile("st.relaxed.gpu.global.v4.b32 [%0], {%1,%2,%3,%4};" :: "l"(p), "r"(a), "r"(b), "r"(c), "r"(d) : "memory");
}
__device__ __forceinline__ void stg2(void* p, uint32_t a, uint32_t b) {
  asm volatile("st.relaxed.gpu.global.v2.b32 [%0], {%1,%2};" :: "l"(p), "r"(a), "r"(b) : "memory");
}
__device__ __forceinline__ void sts4(uint32_t a, const uint32_t* o) { asm volatile("st.shared.v4.b32 [%0], {%1,%2,%3,%4};" :: "r"(a), "r"(o[0]), "r"(o[1]), "r"(o[2]), "r"(o[3]) : "memory"); }
__device__ __forceinline__ void lds4(uint32_t a, uint32_t* o) { asm volatile("ld.shared.v4.b32 {%0,%1,%2,%3}, [%4];" : "=r"(o[0]), "=r"(o[1]), "=r"(o[2]), "=r"(o[3]) : "r"(a) : "memory"); }
__device__ __forceinline__ void sts1(uint32_t a, uint32_t v) { asm volatile("st.shared.b32 [%0], %1;" :: "r"(a), "r"(v) : "memory"); }
__device__ __forceinline__ void ldsm4(uint32_t a, uint32_t& r0, uint32_t& r1, uint32_t& r2, uint32_t& r3) {
  asm volatile("ldmatrix.sync.aligned.m8n8.x4.shared.b16 {%0,%1,%2,%3}, [%4];" : "=r"(r0), "=r"(r1), "=r"(r2), "=r"(r3) : "r"(a) : "memory");
}
__device__ __forceinline__ void ldsm4t(uint32_t a, uint32_t& r0, uint32_t& r1, uint32_t& r2, uint32_t& r3) {
  asm volatile("ldmatrix.sync.aligned.m8n8.x4.trans.shared.b16 {%0,%1,%2,%3}, [%4];" : "=r"(r0), "=r"(r1), "=r"(r2), "=r"(r3) : "r"(a) : "memory");
}
__device__ __forceinline__ void mma16(float* c, uint32_t a0, uint32_t a1, uint32_t a2, uint32_t a3, uint32_t b0, uint32_t b1) {
  asm("mma.sync.aligned.m16n8k16.row.col.f32.bf16.bf16.f32 {%0,%1,%2,%3}, {%4,%5,%6,%7}, {%8,%9}, {%0,%1,%2,%3};"
    : "+f"(c[0]), "+f"(c[1]), "+f"(c[2]), "+f"(c[3]) : "r"(a0), "r"(a1), "r"(a2), "r"(a3), "r"(b0), "r"(b1));
}
__device__ __forceinline__ void mma8(float* c, uint32_t a0, uint32_t a1, uint32_t b0) {
  asm("mma.sync.aligned.m16n8k8.row.col.f32.bf16.bf16.f32 {%0,%1,%2,%3}, {%4,%5}, {%6}, {%0,%1,%2,%3};"
    : "+f"(c[0]), "+f"(c[1]), "+f"(c[2]), "+f"(c[3]) : "r"(a0), "r"(a1), "r"(b0));
}
__device__ __forceinline__ float quad_sum(float v) { v += __shfl_xor_sync(~0u, v, 1); v += __shfl_xor_sync(~0u, v, 2); return v; }
__device__ __forceinline__ float quad_max(float v) { v = fmaxf(v, __shfl_xor_sync(~0u, v, 1)); v = fmaxf(v, __shfl_xor_sync(~0u, v, 2)); return v; }
template <int N> __device__ __forceinline__ void pin(float (&d)[N]) {
#pragma unroll
  for (int i = 0; i < N; i++) asm volatile("" : "+f"(d[i]) :: "memory");
}
__device__ __forceinline__ void spin_guard(int& n) { if (++n > SPIN_MAX) __trap(); }

template <int NW> __device__ __forceinline__ void publish_stats(uint4* dst, const uint32_t* v, uint32_t tag, int lane) {
  float s0 = 0.f, s1 = 0.f;
#pragma unroll
  for (int g = 0; g < NW / 2; g++) { s0 += bf_lo(v[2 * g]) + bf_hi(v[2 * g]); s1 += bf_lo(v[2 * g + 1]) + bf_hi(v[2 * g + 1]); }
  s0 = quad_sum(s0); s1 = quad_sum(s1);
  const float m0 = s0 * (1.f / (4 * NW)), m1 = s1 * (1.f / (4 * NW));
  float q0 = 0.f, q1 = 0.f;
#pragma unroll
  for (int g = 0; g < NW / 2; g++) {
    float a = bf_lo(v[2 * g]) - m0, b = bf_hi(v[2 * g]) - m0, c = bf_lo(v[2 * g + 1]) - m1, d = bf_hi(v[2 * g + 1]) - m1;
    q0 = fmaf(a, a, q0); q0 = fmaf(b, b, q0); q1 = fmaf(c, c, q1); q1 = fmaf(d, d, q1);
  }
  q0 = quad_sum(q0); q1 = quad_sum(q1);
  if ((lane & 3) == 0)
    stg4(dst + (lane >> 2), (__float_as_uint(s0) & ~1u) | tag, __float_as_uint(q0), __float_as_uint(s1), __float_as_uint(q1));
}

template <bool A> __device__ __forceinline__ void gather_stats(const uint4* src, uint32_t tag, int lane, uint32_t& mean0, uint32_t& mean1, float& rs0, float& rs1) {
  constexpr int NV = A ? 3 : 2;
  uint32_t s[NV][4];
  const uint4* p = src + (lane & 3) * 8 + (lane >> 2);
  int n = 0;
  while (true) {
#pragma unroll
    for (int i = 0; i < NV; i++) ldg4(s[i], p + i * 32);
    bool ok = true;
#pragma unroll
    for (int i = 0; i < NV; i++) ok = ok && ((s[i][0] & 1u) == tag);
    if (__all_sync(~0u, ok)) break;
    spin_guard(n);
  }
  float t0 = 0.f, t1 = 0.f;
#pragma unroll
  for (int i = 0; i < NV; i++) { t0 += __uint_as_float(s[i][0]); t1 += __uint_as_float(s[i][2]); }
  const float m0 = quad_sum(t0) * (1.f / 576), m1 = quad_sum(t1) * (1.f / 576);
  float v0 = 0.f, v1 = 0.f;
#pragma unroll
  for (int i = 0; i < NV; i++) {
    const float cnt = A ? (i < 2 ? 64.f : 16.f) : 72.f;
    float d0 = fmaf(__uint_as_float(s[i][0]), 1.f / cnt, -m0), d1 = fmaf(__uint_as_float(s[i][2]), 1.f / cnt, -m1);
    v0 += fmaf(d0 * d0, cnt, __uint_as_float(s[i][1])); v1 += fmaf(d1 * d1, cnt, __uint_as_float(s[i][3]));
  }
  rs0 = rsqrtf(fmaf(quad_sum(v0), 1.f / 576, 1e-5f)); rs1 = rsqrtf(fmaf(quad_sum(v1), 1.f / 576, 1e-5f));
  mean0 = pack_bf16(m0, m0); mean1 = pack_bf16(m1, m1);
}

template <bool SPLIT> __device__ __forceinline__ void gather_slab(uint32_t (&X)[144], const uint4* src) {
  int n = 0;
  while (true) {
#pragma unroll
    for (int s = 0; s < 36; s++) ldg4(X + 4 * s, src + s * 32);
    bool ok = true;
#pragma unroll
    for (int s = 0; s < 36; s++) { ok = ok && X[4 * s] != 0u; if (SPLIT && s % 9 == 4) ok = ok && X[4 * s + 2] != 0u; }
    if (__all_sync(~0u, ok)) break;
    spin_guard(n);
  }
}

__device__ __forceinline__ void put72(uint4* slab, int j, const uint32_t* v) {
  uint4* p = slab + ((9 * j + 1) >> 1) * 32;
  if (j & 1) {
    stg2((char*)(p - 32) + 8, nz(v[0]), v[1]);
#pragma unroll
    for (int i = 0; i < 4; i++) stg4(p + i * 32, nz(v[4 * i + 2]), v[4 * i + 3], v[4 * i + 4], v[4 * i + 5]);
  } else {
#pragma unroll
    for (int i = 0; i < 4; i++) stg4(p + i * 32, nz(v[4 * i]), v[4 * i + 1], v[4 * i + 2], v[4 * i + 3]);
    stg2(p + 4 * 32, nz(v[16]), v[17]);
  }
}
__device__ __forceinline__ void get72(const uint4* slab, int j, uint32_t* v) {
  const uint4* p = slab + ((9 * j + 1) >> 1) * 32;
  if (j & 1) {
    ldg2(v, (const char*)(p - 32) + 8);
#pragma unroll
    for (int i = 0; i < 4; i++) ldg4(v + 2 + 4 * i, p + i * 32);
  } else {
#pragma unroll
    for (int i = 0; i < 4; i++) ldg4(v + 4 * i, p + i * 32);
    ldg2(v + 16, p + 4 * 32);
  }
}
__device__ __forceinline__ void zero72(uint4* slab, int j) {
  uint4* p = slab + ((9 * j + 1) >> 1) * 32;
#pragma unroll
  for (int i = 0; i < 4; i++) stg4(p + i * 32, 0u, 0u, 0u, 0u);
  stg2((j & 1) ? (char*)(p - 32) + 8 : (char*)(p + 4 * 32), 0u, 0u);
}

struct Ring {
  uint32_t st, ph;
  __device__ __forceinline__ void next() { if (++st == NST) { st = 0; ph ^= 1; } }
};

#define STAMP(i) do {} while (0)

__global__ void __launch_bounds__(384, 1) mega_kernel(
    const __grid_constant__ CUtensorMap m_qkv, const __grid_constant__ CUtensorMap m_wo,
    const __grid_constant__ CUtensorMap m_g, const __grid_constant__ CUtensorMap m_u, const __grid_constant__ CUtensorMap m_d,
    const __nv_bfloat16* __restrict__ x_in, const __nv_bfloat16* __restrict__ wqkv, const __nv_bfloat16* __restrict__ wo,
    __nv_bfloat16* __restrict__ out) {
  extern __shared__ __align__(1024) uint8_t smem[];
  const uint32_t sb = (uint32_t)__cvta_generic_to_shared(smem);
  const uint32_t full0 = sb + BARS, empty0 = full0 + 8 * NST, rem_full = empty0 + 8 * NST, park_free = rem_full + 8;
  const int w = threadIdx.x >> 5, lane = threadIdx.x & 31;
  const int t = blockIdx.x >> 3, j = blockIdx.x & 7;
  if (threadIdx.x == 0) {
    for (int i = 0; i < NST; i++) { mbar_init(full0 + 8 * i, 1); mbar_init(empty0 + 8 * i, 8); }
    mbar_init(rem_full, 64); mbar_init(park_free, 8);
    asm volatile("fence.mbarrier_init.release.cluster;" ::: "memory");
  }
  __syncthreads();

  if (w >= 8) {
    asm volatile("setmaxnreg.dec.sync.aligned.u32 24;");
    if (w == 8) {
      if (lane == 0) {
        Ring r{0, 1};
        auto stage = [&](const CUtensorMap* ma, int a0, int a1, const CUtensorMap* mb, int b0, int b1, bool two) {
          mbar_wait(empty0 + r.st * 8, r.ph);
          const uint32_t d = sb + r.st * STAGE, fb = full0 + r.st * 8;
          mbar_expect(fb, two ? STAGE : STAGE / 2);
          tma2d(d, ma, a0, a1, fb);
          if (two) tma2d(d + 8192, mb, b0, b1, fb);
          r.next();
        };
        auto pair = [&](const CUtensorMap* ma, int ca, int ra, const CUtensorMap* mb, int cb, int rb) {
          for (int st = 0; st < 9; st++) {
            const int b0 = 2 * st, b1 = 2 * st + 1;
            stage(b0 < 9 ? ma : mb, b0 < 9 ? ca : cb, b0 < 9 ? ra + b0 * 64 : rb + (b0 - 9) * 64,
                  b1 < 9 ? ma : mb, b1 < 9 ? ca : cb, b1 < 9 ? ra + b1 * 64 : rb + (b1 - 9) * 64, true);
          }
        };
        for (int layer = 0; layer < 2; layer++) {
          pair(&m_qkv, 576 + 72 * j, 0, &m_qkv, 1152 + 72 * j, 0);
          pair(&m_qkv, 72 * j, 0, &m_wo, 72 * j, 0);
          for (int c = 0; c < 9; c++) pair(&m_g, 576 * j + 64 * c, 0, &m_u, 576 * j + 64 * c, 0);
          for (int sp = 0; sp < 4; sp++)
            pair(&m_d, (sp == 0 ? 8 : ((j + 2 * sp) & 7)) * 64, 576 * j, &m_d, ((j + 2 * sp + 1) & 7) * 64, 576 * j);
          for (int st = 0; st < 5; st++)
            stage(&m_d, 64 * j, 576 * j + 128 * st, &m_d, 64 * j, 576 * j + 128 * st + 64, st < 4);
        }
      }
    } else if (w == 9) {
      const int r = lane >> 2, q = lane & 3;
      const int row = 128 * t + 32 * (j >> 1) + 2 * r + (j & 1);
      const int slab = (t * 8 + j) * SLAB + 32 * 32 + lane;
      uint4* sa = g_SA + ((t * 8 + j) * 12 + 8) * 8;
      {
        const uint32_t* xr = (const uint32_t*)(x_in + row * 576 + 512 + 2 * q);
        uint32_t v[16];
#pragma unroll
        for (int g = 0; g < 8; g++) { v[2 * g] = __ldg(xr + 4 * g); v[2 * g + 1] = __ldg(xr + 8 * 576 + 4 * g); }
#pragma unroll
        for (int i = 0; i < 4; i++) stg4(g_XA[0] + slab + i * 32, nz(v[4 * i]), v[4 * i + 1], v[4 * i + 2], v[4 * i + 3]);
#pragma unroll
        for (int i = 0; i < 4; i++) publish_stats<4>(sa + i * 8, v + 4 * i, 1u, lane);
      }
      for (int layer = 0; layer < 2; layer++) {
        const uint32_t tag = 1 - layer;
#pragma unroll 1
        for (int i = 0; i < 4; i++) {
          float a[8];
#pragma unroll
          for (int e = 0; e < 8; e++) a[e] = 0.f;
#pragma unroll 1
          for (int s = 0; s < 8; s += 2) {
            const uint4* p = g_P + ((t * 8 + s) * 8 + j) * SLAB + (32 + i) * 32 + lane;
            uint32_t u[4], v[4];
            int n = 0;
            while (true) {
              ldg4(u, p); ldg4(v, p + 8 * SLAB);
              if (__all_sync(~0u, (u[0] & 1u) == tag && (v[0] & 1u) == tag)) break;
              __nanosleep(256);
              spin_guard(n);
            }
#pragma unroll
            for (int e = 0; e < 4; e++) { a[2 * e] += bf_lo(u[e]) + bf_lo(v[e]); a[2 * e + 1] += bf_hi(u[e]) + bf_hi(v[e]); }
          }
          uint32_t x[4];
          uint4* xb = g_XB[layer] + slab + i * 32;
          ldg4(x, xb);
#pragma unroll
          for (int e = 0; e < 4; e++) x[e] = pack_bf16(bf_lo(x[e]) + a[2 * e], bf_hi(x[e]) + a[2 * e + 1]);
          stg4(xb, 0u, 0u, 0u, 0u);
          if (layer == 0) {
            stg4(g_XA[1] + slab + i * 32, nz(x[0]), x[1], x[2], x[3]);
            publish_stats<4>(sa + i * 8, x, 0u, lane);
          } else {
            uint32_t* o = (uint32_t*)(out + row * 576 + 512 + 16 * i + 2 * q);
            o[0] = x[0]; o[8 * 576] = x[1]; o[4] = x[2]; o[8 * 576 + 4] = x[3];
          }
        }
      }
    } else {
      const int tid = threadIdx.x - 320;
      for (int layer = 0; layer < 2; layer++) {
        if (layer) mbar_wait(park_free, 0);
#pragma unroll 1
        for (int p = 0; p < 4; p++) {
          const __nv_bfloat16* src = (p == 3 ? wo : wqkv + (p == 2 ? 0 : 576 * (p + 1))) + 72 * j + 64;
          const int pitch = p == 3 ? 576 : 1728;
#pragma unroll
          for (int i = 0; i < 9; i++) {
            const int k = tid + 64 * i, s = k >> 4, rr = k & 7;
            const uint32_t dst = sb + REM + p * 10240 + (s >> 3) * 2048 + ((k >> 3) & 1) * 1024 + rr * 128 + (((s & 7) ^ rr) << 4);
            asm volatile("cp.async.cg.shared.global [%0], [%1], 16;" :: "r"(dst), "l"(src + k * pitch) : "memory");
          }
        }
        asm volatile("cp.async.wait_all;\nfence.proxy.async.shared::cta;" ::: "memory");
        mbar_arrive(rem_full);
      }
    }
  } else {
    asm volatile("setmaxnreg.inc.sync.aligned.u32 240;");
    const int r = lane >> 2, q = lane & 3;
    const int slab = (t * 8 + w) * SLAB + lane;
    Ring rg{0, 0};
    uint32_t prev = 0;
    uint32_t X[144];
    auto release = [&](uint32_t st) { if (lane == 0) mbar_arrive(empty0 + st * 8); };
    auto publishA = [&](int layer, const uint32_t* v) {
      uint4* p = g_XA[layer] + slab + 4 * j * 32;
#pragma unroll
      for (int i = 0; i < 4; i++) stg4(p + i * 32, nz(v[4 * i]), v[4 * i + 1], v[4 * i + 2], v[4 * i + 3]);
      publish_stats<16>(g_SA + ((t * 8 + w) * 12 + j) * 8, v, 1 - layer, lane);
    };
    {
      const int row = 128 * t + 32 * (w >> 1) + 2 * r + (w & 1);
      const uint32_t* xr = (const uint32_t*)(x_in + row * 576 + 64 * j + 2 * q);
      uint32_t v[16];
#pragma unroll
      for (int g = 0; g < 8; g++) { v[2 * g] = __ldg(xr + 4 * g); v[2 * g + 1] = __ldg(xr + 8 * 576 + 4 * g); }
      publishA(0, v);
    }
#pragma unroll 1
    for (int layer = 0; layer < 2; layer++) {
      const uint32_t tag = 1 - layer;
      float rs0, rs1;
      STAMP(0);
      auto part72 = [&](float (&acc)[36], int part) {
        const int B0 = 9 * part;
#pragma unroll
        for (int kb = 0; kb < 9; kb++) {
          const int b = B0 + kb;
          if ((b & 1) == 0) mbar_wait(full0 + rg.st * 8, rg.ph);
          const uint32_t base = sb + rg.st * STAGE + (b & 1) * 8192;
          wg_fence();
#pragma unroll
          for (int i = 0; i < 4; i++) {
            const int s = kb * 4 + i;
            const uint32_t a = base + i * 2048, rem = sb + REM + part * 10240 + (s >> 3) * 2048 + (s & 7) * 16;
            wgmma_rs_n72(acc, X + 4 * s, mk_desc(a, rem - a, 1024), s != 0);
          }
          wg_commit();
          wg_wait<1>();
          if ((b & 1) == 0 && kb > 0) release(prev);
          if (b & 1) { prev = rg.st; rg.next(); }
        }
        wg_wait<0>();
        if ((B0 + 8) & 1) release(prev);
        pin(acc);
      };
      {
        uint32_t mean0, mean1;
        gather_stats<true>(g_SA + (t * 8 + w) * 12 * 8, tag, lane, mean0, mean1, rs0, rs1);
        STAMP(1);
        gather_slab<false>(X, g_XA[layer] + slab);
#pragma unroll
        for (int i = 0; i < 144; i++) X[i] = sub_bf16x2(X[i], (i & 1) ? mean1 : mean0);
      }
      STAMP(2);
      mbar_wait(rem_full, layer);
      const uint32_t kvrow = sb + KVS + (w & 1) * 10368 + (16 * (w >> 1)) * 144;
      uint32_t Q[18];
      {
        float acc[36];
        uint32_t hl[20];
        part72(acc, 0);
#pragma unroll
        for (int g = 0; g < 9; g++) {
          const uint32_t lo = pack_bf16(acc[4 * g] * rs0, acc[4 * g + 1] * rs0), hi = pack_bf16(acc[4 * g + 2] * rs1, acc[4 * g + 3] * rs1);
          sts1(kvrow + (8 + r) * 144 + g * 16 + q * 4, lo); sts1(kvrow + (16 + r) * 144 + g * 16 + q * 4, hi);
          hl[g] = hi;
        }
        part72(acc, 1);
#pragma unroll
        for (int g = 0; g < 9; g++) {
          const uint32_t lo = pack_bf16(acc[4 * g] * rs0, acc[4 * g + 1] * rs0), hi = pack_bf16(acc[4 * g + 2] * rs1, acc[4 * g + 3] * rs1);
          sts1(kvrow + 20736 + (8 + r) * 144 + g * 16 + q * 4, lo); sts1(kvrow + 20736 + (16 + r) * 144 + g * 16 + q * 4, hi);
          hl[9 + g] = hi;
        }
        if (w >= 6 && t < 15) {
          hl[18] = hl[19] = 0u;
          uint4* hp = g_H[layer] + (((t + 1) * 8 + j) * 2 + (w & 1)) * 160 + lane;
#pragma unroll
          for (int i = 0; i < 5; i++) stg4(hp + i * 32, nz(hl[4 * i]), hl[4 * i + 1], hl[4 * i + 2], hl[4 * i + 3]);
        }
        if (w < 4) asm volatile("bar.arrive 2, 256;" ::: "memory");
        part72(acc, 2);
#pragma unroll
        for (int g = 0; g < 9; g++) {
          Q[2 * g] = pack_bf16(acc[4 * g] * rs0, acc[4 * g + 1] * rs0); Q[2 * g + 1] = pack_bf16(acc[4 * g + 2] * rs1, acc[4 * g + 3] * rs1);
        }
      }
      STAMP(3);
      if (w < 2 && t > 0) {
        uint4* hp = g_H[layer] + ((t * 8 + j) * 2 + w) * 160 + lane;
        uint32_t hl[20];
        int n = 0;
        while (true) {
#pragma unroll
          for (int i = 0; i < 5; i++) ldg4(hl + 4 * i, hp + i * 32);
          if (__all_sync(~0u, hl[0] != 0u && hl[4] != 0u && hl[8] != 0u && hl[12] != 0u && hl[16] != 0u)) break;
          spin_guard(n);
        }
#pragma unroll
        for (int i = 0; i < 5; i++) stg4(hp + i * 32, 0u, 0u, 0u, 0u);
#pragma unroll
        for (int g = 0; g < 9; g++) {
          sts1(kvrow + r * 144 + g * 16 + q * 4, hl[g]); sts1(kvrow + 20736 + r * 144 + g * 16 + q * 4, hl[9 + g]);
        }
      }
      if (w < 4) asm volatile("bar.sync 1, 128;" ::: "memory");
      else asm volatile("bar.sync 2, 256;" ::: "memory");
      STAMP(4);
      uint32_t O[18];
      {
        const bool edge = (t == 0 && w < 2);
        uint32_t row[3];
#pragma unroll
        for (int nt = 0; nt < 3; nt++) row[nt] = kvrow + (8 * nt + (lane & 7)) * 144;
        if (edge) row[0] = sb + KVS + 8 * 144;
        const uint32_t rlast = ((lane >> 3) == 0 ? row[0] : (lane >> 3) == 1 ? row[1] : row[2]) + 128;
        uint32_t K[3][9], V[3][9], dummy;
#pragma unroll
        for (int nt = 0; nt < 3; nt++) {
          ldsm4(row[nt] + (lane >> 3) * 16, K[nt][0], K[nt][1], K[nt][2], K[nt][3]);
          ldsm4(row[nt] + 64 + (lane >> 3) * 16, K[nt][4], K[nt][5], K[nt][6], K[nt][7]);
        }
        ldsm4(rlast, K[0][8], K[1][8], K[2][8], dummy);
#pragma unroll
        for (int nt = 0; nt < 3; nt++) {
          ldsm4t(row[nt] + 20736 + (lane >> 3) * 16, V[nt][0], V[nt][1], V[nt][2], V[nt][3]);
          ldsm4t(row[nt] + 20736 + 64 + (lane >> 3) * 16, V[nt][4], V[nt][5], V[nt][6], V[nt][7]);
        }
        ldsm4t(rlast + 20736, V[0][8], V[1][8], V[2][8], dummy);
        const bool up0 = 2 * q > r, up1 = 2 * q + 1 > r;
        const float sc = 0.23570226039551584f * 1.4426950408889634f;
        const float neg = -1e9f * 1.4426950408889634f;
        float Of[9][4];
#pragma unroll
        for (int h = 0; h < 4; h++) {
          const uint32_t a0 = q >= h ? Q[4 * h] : 0u, a1 = q >= h ? Q[4 * h + 1] : 0u;
          const uint32_t a4 = q <= h ? Q[4 * h + 4] : 0u, a5 = q <= h ? Q[4 * h + 5] : 0u;
          float S[3][4];
#pragma unroll
          for (int nt = 0; nt < 3; nt++) {
            S[nt][0] = S[nt][1] = S[nt][2] = S[nt][3] = 0.f;
            mma16(S[nt], a0, a1, Q[4 * h + 2], Q[4 * h + 3], K[nt][2 * h], K[nt][2 * h + 1]);
            mma8(S[nt], a4, a5, K[nt][2 * h + 2]);
          }
          float s00 = (up0 ? S[0][0] : S[1][0]) * sc, s01 = (up1 ? S[0][1] : S[1][1]) * sc;
          const float s10 = (up0 ? S[1][2] : S[2][2]) * sc, s11 = (up1 ? S[1][3] : S[2][3]) * sc;
          if (edge && up0) s00 = neg;
          if (edge && up1) s01 = neg;
          const float m0 = quad_max(fmaxf(s00, s01)), m1 = quad_max(fmaxf(s10, s11));
          float p00 = ex2(s00 - m0), p01 = ex2(s01 - m0), p10 = ex2(s10 - m1), p11 = ex2(s11 - m1);
          const float i0 = __frcp_rn(quad_sum(p00 + p01)), i1 = __frcp_rn(quad_sum(p10 + p11));
          p00 *= i0; p01 *= i0; p10 *= i1; p11 *= i1;
          const uint32_t pa = pack_bf16(up0 ? p00 : 0.f, up1 ? p01 : 0.f), pb = pack_bf16(up0 ? 0.f : p00, up1 ? 0.f : p01);
          const uint32_t pc = pack_bf16(up0 ? p10 : 0.f, up1 ? p11 : 0.f), pd = pack_bf16(up0 ? 0.f : p10, up1 ? 0.f : p11);
#pragma unroll
          for (int gi = 0; gi < 3; gi++) {
            const int g = 2 * h + gi;
            float o[4] = {0.f, 0.f, 0.f, 0.f};
            mma16(o, pa, 0u, pb, pc, V[0][g], V[1][g]);
            mma8(o, 0u, pd, V[2][g]);
#pragma unroll
            for (int e = 0; e < 4; e++) Of[g][e] = (gi == 0 && h > 0 && q < h) ? Of[g][e] : o[e];
          }
        }
#pragma unroll
        for (int g = 0; g < 9; g++) { O[2 * g] = pack_bf16(Of[g][0], Of[g][1]); O[2 * g + 1] = pack_bf16(Of[g][2], Of[g][3]); }
      }
      put72(g_O[layer] + slab, j, O);
      STAMP(5);
      {
        const uint4* p = g_O[layer] + slab + (((9 * (lane & 7) + 1) >> 1) + 3) * 32;
        uint32_t v[4];
        int n = 0;
        while (true) { ldg4(v, p); if (__all_sync(~0u, v[0] != 0u)) break; spin_guard(n); }
      }
      STAMP(6);
      gather_slab<true>(X, g_O[layer] + slab);
      STAMP(7);
      {
        uint32_t res[18];
        get72(g_XA[layer] + slab, j, res);
        float acc[36];
        part72(acc, 3);
        STAMP(8);
#pragma unroll
        for (int i = 0; i < 18; i++) res[i] = pack_bf16(bf_lo(res[i]) + acc[2 * i], bf_hi(res[i]) + acc[2 * i + 1]);
        put72(g_XB[layer] + slab, j, res);
        publish_stats<18>(g_SB + ((t * 8 + w) * 8 + j) * 8, res, tag, lane);
        zero72(g_XA[layer] + slab, j);
      }
      STAMP(9);
      {
        uint32_t mean0, mean1;
        gather_stats<false>(g_SB + (t * 8 + w) * 8 * 8, tag, lane, mean0, mean1, rs0, rs1);
        STAMP(10);
        gather_slab<true>(X, g_XB[layer] + slab);
#pragma unroll
        for (int i = 0; i < 144; i++) X[i] = sub_bf16x2(X[i], (i & 1) ? mean1 : mean0);
        zero72(g_O[layer] + slab, j);
      }
      STAMP(11);
      float aG[32], aU[32];
      const uint32_t hp = sb + PARK + w * 512 + lane * 16;
      auto gelu8 = [&](int p, uint32_t* o) {
#pragma unroll
        for (int e = 0; e < 8; e++) asm volatile("" : "+f"(aG[8 * p + e]) :: "memory");
        float h[8];
#pragma unroll
        for (int e = 0; e < 8; e++) {
          const float rs = (e & 2) ? rs1 : rs0;
          const float g = aG[8 * p + e] * rs;
          const float th = tanh_ap(g * fmaf(g * g, 0.7978845608028654f * 0.044715f, 0.7978845608028654f));
          const float gs = g * (0.5f * rs);
          h[e] = fmaf(gs, th, gs);
        }
#pragma unroll
        for (int e = 0; e < 4; e++) o[e] = pack_bf16(h[2 * e], h[2 * e + 1]);
      };
      auto mul8 = [&](int p, uint32_t* g) {
#pragma unroll
        for (int e = 0; e < 8; e++) asm volatile("" : "+f"(aU[8 * p + e]) :: "memory");
#pragma unroll
        for (int e = 0; e < 4; e++) g[e] = pack_bf16(bf_lo(g[e]) * aU[8 * p + 2 * e], bf_hi(g[e]) * aU[8 * p + 2 * e + 1]);
      };
      auto step = [&](int st, bool rel, auto&& filler) {
        mbar_wait(full0 + rg.st * 8, rg.ph);
        const uint64_t desc = mk_desc(sb + rg.st * STAGE, 8192, 1024);
        wg_fence();
#pragma unroll
        for (int i = 0; i < 8; i++) {
          const int b = 2 * st + (i >> 2), s = (b < 9 ? b : b - 9) * 4 + (i & 3);
          if (b < 9) wgmma_rs_n64(aG, X + 4 * s, desc + i * 128, s != 0);
          else wgmma_rs_n64(aU, X + 4 * s, desc + i * 128, s != 0);
          if (i == 7) wg_commit();
          if (st == 4 && i == 3) { wg_commit(); wg_wait<1>(); wg_fence(); }
          if (i == 3) filler();
        }
        wg_wait<1>();
        if (rel) release(prev);
        prev = rg.st; rg.next();
      };
      auto nop = [] {};
#pragma unroll
      for (int st = 0; st < 4; st++) step(st, st > 0, nop);
#pragma unroll 1
      for (int c = 0; c < 8; c++) {
        const uint32_t hc = hp + c * 4 * 4096;
#pragma unroll
        for (int st = 4; st < 9; st++) step(st, true, [&] { if (st >= 5) { uint32_t o[4]; gelu8(st - 5, o); sts4(hc + (st - 5) * 4096, o); } });
#pragma unroll
        for (int st = 0; st < 4; st++) step(st, true, [&] {
          if (st >= 1) { uint32_t o[4]; lds4(hc + st * 4096, o); mul8(st, o); sts4(hc + st * 4096, o); }
          if (st == 1) { uint32_t o[4]; lds4(hc, o); mul8(0, o); sts4(hc, o); } });
      }
      {
        uint32_t G[16];
#pragma unroll
        for (int st = 4; st < 9; st++) step(st, true, [&] { if (st >= 5) gelu8(st - 5, G + 4 * (st - 5)); });
        wg_wait<0>(); release(prev);
        STAMP(12);
#pragma unroll
        for (int s = 0; s < 32; s++) lds4(hp + s * 4096, X + 4 * s);
#pragma unroll
        for (int p = 0; p < 4; p++) mul8(p, G + 4 * p);
#pragma unroll
        for (int i = 0; i < 16; i++) X[128 + i] = G[i];
      }
      STAMP(13);
      uint4* pw = g_P + ((t * 8 + j) * 8 + w) * SLAB + lane;
      auto put_part = [&](float (&a)[32], int p, int chunk) {
#pragma unroll
        for (int e = 0; e < 8; e++) asm volatile("" : "+f"(a[8 * p + e]) :: "memory");
        stg4(pw + (chunk * 4 + p) * 32, (pack_bf16(a[8 * p], a[8 * p + 1]) & ~1u) | tag, pack_bf16(a[8 * p + 2], a[8 * p + 3]),
             pack_bf16(a[8 * p + 4], a[8 * p + 5]), pack_bf16(a[8 * p + 6], a[8 * p + 7]));
      };
#pragma unroll
      for (int st = 0; st < 4; st++) step(st, st > 0, nop);
      if (layer == 0 && lane == 0) mbar_arrive(park_free);
#pragma unroll 1
      for (int sp = 0; sp < 4; sp++) {
        const int ca = sp == 0 ? 8 : ((j + 2 * sp) & 7), cb = (j + 2 * sp + 1) & 7;
#pragma unroll
        for (int st = 4; st < 9; st++) step(st, true, [&] { if (st == 5 || st == 6) { put_part(aG, 2 * (st - 5), ca); put_part(aG, 2 * (st - 5) + 1, ca); } });
#pragma unroll
        for (int st = 0; st < 4; st++) step(st, true, [&] { if (st == 1) { put_part(aU, 0, cb); put_part(aU, 1, cb); put_part(aU, 2, cb); put_part(aU, 3, cb); } });
      }
      {
        mbar_wait(full0 + rg.st * 8, rg.ph);
        const uint64_t desc = mk_desc(sb + rg.st * STAGE, 8192, 1024);
        wg_fence();
#pragma unroll
        for (int i = 0; i < 4; i++) wgmma_rs_n64(aG, X + 4 * (32 + i), desc + i * 128, 1);
        wg_commit();
        wg_wait<1>(); release(prev);
        prev = rg.st; rg.next();
        wg_wait<0>(); release(prev);
        pin(aG);
      }
      STAMP(14);
      {
        uint4* xb = g_XB[layer] + slab + 4 * j * 32;
        const uint4* pr = g_P + (t * 64 + w) * SLAB + 4 * j * 32 + lane;
        uint32_t res[16];
#pragma unroll
        for (int i = 0; i < 4; i++) ldg4(res + 4 * i, xb + i * 32);
        int n = 0;
        while (true) {
#pragma unroll
          for (int s = 1; s < 8; s++)
#pragma unroll
            for (int i = 0; i < 4; i++) ldg4(X + 16 * s + 4 * i, pr + ((j + s) & 7) * 8 * SLAB + i * 32);
          bool ok = true;
#pragma unroll
          for (int s = 4; s < 32; s++) ok = ok && (X[4 * s] & 1u) == tag;
          if (__all_sync(~0u, ok)) break;
          spin_guard(n);
        }
#pragma unroll
        for (int s = 1; s < 8; s++)
#pragma unroll
          for (int i = 0; i < 16; i++) { aG[2 * i] += bf_lo(X[16 * s + i]); aG[2 * i + 1] += bf_hi(X[16 * s + i]); }
#pragma unroll
        for (int i = 0; i < 16; i++) res[i] = pack_bf16(bf_lo(res[i]) + aG[2 * i], bf_hi(res[i]) + aG[2 * i + 1]);
        if (layer == 0) {
          publishA(1, res);
        } else {
          const int row = 128 * t + 32 * (w >> 1) + 2 * r + (w & 1);
          uint32_t* o = (uint32_t*)(out + row * 576 + 64 * j + 2 * q);
#pragma unroll
          for (int g = 0; g < 8; g++) { o[4 * g] = res[2 * g]; o[8 * 576 + 4 * g] = res[2 * g + 1]; }
        }
#pragma unroll
        for (int i = 0; i < 4; i++) stg4(xb + i * 32, 0u, 0u, 0u, 0u);
      }
      STAMP(15);
    }
  }
}

typedef CUresult (*EncodeFn)(CUtensorMap*, CUtensorMapDataType, cuuint32_t, void*, const cuuint64_t*, const cuuint64_t*,
                             const cuuint32_t*, const cuuint32_t*, CUtensorMapInterleave, CUtensorMapSwizzle,
                             CUtensorMapL2promotion, CUtensorMapFloatOOBfill);

CUtensorMap make_map(EncodeFn f, const void* p, uint64_t cols, uint64_t rows) {
  CUtensorMap m;
  cuuint64_t dims[2] = {cols, rows};
  cuuint64_t str[1] = {cols * 2};
  cuuint32_t box[2] = {64, 64};
  cuuint32_t es[2] = {1, 1};
  f(&m, CU_TENSOR_MAP_DATA_TYPE_BFLOAT16, 2, const_cast<void*>(p), dims, str, box, es, CU_TENSOR_MAP_INTERLEAVE_NONE,
    CU_TENSOR_MAP_SWIZZLE_128B, CU_TENSOR_MAP_L2_PROMOTION_NONE, CU_TENSOR_MAP_FLOAT_OOB_FILL_NONE);
  return m;
}

}

extern "C" void kernel_launch(void* const* d_in, const int* in_sizes, int n_in, void* d_out, int out_size) {
  void* fn = nullptr;
  cudaDriverEntryPointQueryResult qr;
  cudaGetDriverEntryPoint("cuTensorMapEncodeTiled", &fn, cudaEnableDefault, &qr);
  EncodeFn enc = (EncodeFn)fn;
  const CUtensorMap m_qkv = make_map(enc, d_in[1], 1728, 576), m_wo = make_map(enc, d_in[2], 576, 576);
  const CUtensorMap m_g = make_map(enc, d_in[4], 4608, 576), m_u = make_map(enc, d_in[5], 4608, 576), m_d = make_map(enc, d_in[6], 576, 4608);
  cudaFuncSetAttribute(mega_kernel, cudaFuncAttributeMaxDynamicSharedMemorySize, SMEM_BYTES);
  mega_kernel<<<128, 384, SMEM_BYTES>>>(m_qkv, m_wo, m_g, m_u, m_d, (const __nv_bfloat16*)d_in[0], (const __nv_bfloat16*)d_in[1],
                                        (const __nv_bfloat16*)d_in[2], (__nv_bfloat16*)d_out);
}
```

```cpp
#include <cuda_runtime.h>
#include <cuda.h>
#include <cuda_bf16.h>
#include <stdint.h>

#define TRACE 0

namespace {

constexpr int NST = 6;
constexpr int STAGE = 16384;
constexpr int PARK = NST * STAGE;
constexpr int REM = PARK + 49152;
constexpr int KVS = REM + 40960;
constexpr int BARS = KVS + 41472;
constexpr int SMEM_BYTES = BARS + 256;
static_assert(BARS >= PARK + 131072, "barriers overlap park");
static_assert(SMEM_BYTES <= 232448, "smem");

constexpr int SLAB = 36 * 32;
constexpr int SPIN_MAX = 1 << 22;

}

__device__ uint4 g_X[3][2][128 * SLAB];
__device__ uint4 g_P[8 * 128 * SLAB];
__device__ uint4 g_S[3][128 * 12 * 8];
__device__ uint4 g_H[2][128 * 2 * 6 * 32];

namespace {

constexpr uint64_t DESC_HI = 0x4000004000000000ull;
__device__ __forceinline__ void wgmma_rs_n64(float (&d)[32], const uint32_t* a, uint64_t desc, int scale_d) {
  asm volatile("{\n.reg .pred p;\nsetp.ne.b32 p, %37, 0;\n"
    "wgmma.mma_async.sync.aligned.m64n64k16.f32.bf16.bf16 "
    "{%0, %1, %2, %3, %4, %5, %6, %7, %8, %9, %10, %11, %12, %13, %14, %15, %16, %17, %18, %19, %20, %21, %22, %23, %24, %25, %26, %27, %28, %29, %30, %31}, "
    "{%32, %33, %34, %35}, %36, p, 1, 1, 1;\n}\n"
    : "+f"(d[0]), "+f"(d[1]), "+f"(d[2]), "+f"(d[3]), "+f"(d[4]), "+f"(d[5]), "+f"(d[6]), "+f"(d[7]), "+f"(d[8]), "+f"(d[9]), "+f"(d[10]), "+f"(d[11]), "+f"(d[12]), "+f"(d[13]), "+f"(d[14]), "+f"(d[15]), "+f"(d[16]), "+f"(d[17]), "+f"(d[18]), "+f"(d[19]), "+f"(d[20]), "+f"(d[21]), "+f"(d[22]), "+f"(d[23]), "+f"(d[24]), "+f"(d[25]), "+f"(d[26]), "+f"(d[27]), "+f"(d[28]), "+f"(d[29]), "+f"(d[30]), "+f"(d[31])
    : "r"(a[0]), "r"(a[1]), "r"(a[2]), "r"(a[3]), "l"(desc), "r"(scale_d));
}
__device__ __forceinline__ void wgmma_rs_n72(float (&d)[36], const uint32_t* a, uint64_t desc, int scale_d) {
  asm volatile("{\n.reg .pred p;\nsetp.ne.b32 p, %41, 0;\n"
    "wgmma.mma_async.sync.aligned.m64n72k16.f32.bf16.bf16 "
    "{%0, %1, %2, %3, %4, %5, %6, %7, %8, %9, %10, %11, %12, %13, %14, %15, %16, %17, %18, %19, %20, %21, %22, %23, %24, %25, %26, %27, %28, %29, %30, %31, %32, %33, %34, %35}, "
    "{%36, %37, %38, %39}, %40, p, 1, 1, 1;\n}\n"
    : "+f"(d[0]), "+f"(d[1]), "+f"(d[2]), "+f"(d[3]), "+f"(d[4]), "+f"(d[5]), "+f"(d[6]), "+f"(d[7]), "+f"(d[8]), "+f"(d[9]), "+f"(d[10]), "+f"(d[11]), "+f"(d[12]), "+f"(d[13]), "+f"(d[14]), "+f"(d[15]), "+f"(d[16]), "+f"(d[17]), "+f"(d[18]), "+f"(d[19]), "+f"(d[20]), "+f"(d[21]), "+f"(d[22]), "+f"(d[23]), "+f"(d[24]), "+f"(d[25]), "+f"(d[26]), "+f"(d[27]), "+f"(d[28]), "+f"(d[29]), "+f"(d[30]), "+f"(d[31]), "+f"(d[32]), "+f"(d[33]), "+f"(d[34]), "+f"(d[35])
    : "r"(a[0]), "r"(a[1]), "r"(a[2]), "r"(a[3]), "l"(desc), "r"(scale_d));
}

__device__ __forceinline__ void mbar_init(uint32_t a, uint32_t c) { asm volatile("mbarrier.init.shared::cta.b64 [%0], %1;" :: "r"(a), "r"(c)); }
__device__ __forceinline__ void mbar_expect(uint32_t a, uint32_t b) { asm volatile("mbarrier.arrive.expect_tx.shared::cta.b64 _, [%0], %1;" :: "r"(a), "r"(b) : "memory"); }
__device__ __forceinline__ void mbar_arrive(uint32_t a) { asm volatile("mbarrier.arrive.shared::cta.b64 _, [%0];" :: "r"(a) : "memory"); }
__device__ __forceinline__ void mbar_wait(uint32_t a, uint32_t ph) {
  asm volatile("{\n.reg .pred p;\n.reg .u32 n;\n"
               "mbarrier.try_wait.parity.shared::cta.b64 p, [%0], %1;\n@p bra D;\n"
               "mov.u32 n, 0;\n"
               "W: mbarrier.try_wait.parity.shared::cta.b64 p, [%0], %1;\n@p bra D;\n"
               "add.u32 n, n, 1;\nsetp.lt.u32 p, n, 4194304;\n@p bra W;\ntrap;\nD:\n}" :: "r"(a), "r"(ph) : "memory");
}
__device__ __forceinline__ void tma2d(uint32_t dst, const CUtensorMap* m, int c0, int c1, uint32_t bar) {
  asm volatile("cp.async.bulk.tensor.2d.shared::cluster.global.mbarrier::complete_tx::bytes [%0], [%1, {%3, %4}], [%2];"
    :: "r"(dst), "l"(m), "r"(bar), "r"(c0), "r"(c1) : "memory");
}
__device__ __forceinline__ void wg_fence() { asm volatile("wgmma.fence.sync.aligned;" ::: "memory"); }
__device__ __forceinline__ void wg_commit() { asm volatile("wgmma.commit_group.sync.aligned;" ::: "memory"); }
template <int N> __device__ __forceinline__ void wg_wait() { asm volatile("wgmma.wait_group.sync.aligned %0;" :: "n"(N) : "memory"); }
__device__ __forceinline__ float tanh_ap(float x) { float y; asm("tanh.approx.f32 %0, %1;" : "=f"(y) : "f"(x)); return y; }
__device__ __forceinline__ float ex2(float x) { float y; asm("ex2.approx.ftz.f32 %0, %1;" : "=f"(y) : "f"(x)); return y; }
__device__ __forceinline__ uint32_t pack_bf16(float lo, float hi) { uint32_t r; asm("cvt.rn.bf16x2.f32 %0, %1, %2;" : "=r"(r) : "f"(hi), "f"(lo)); return r; }
__device__ __forceinline__ float bf_lo(uint32_t v) { return __uint_as_float(v << 16); }
__device__ __forceinline__ float bf_hi(uint32_t v) { return __uint_as_float(v & 0xffff0000u); }
__device__ __forceinline__ uint32_t sub_bf16x2(uint32_t a, uint32_t b) { uint32_t r; asm("sub.rn.bf16x2 %0, %1, %2;" : "=r"(r) : "r"(a), "r"(b)); return r; }
__device__ __forceinline__ uint32_t nz(uint32_t w) { return w == 0u ? 0x8000u : w; }

__device__ __forceinline__ void ldg4(uint32_t* d, const uint4* p) {
  asm volatile("ld.relaxed.gpu.global.v4.b32 {%0,%1,%2,%3}, [%4];" : "=r"(d[0]), "=r"(d[1]), "=r"(d[2]), "=r"(d[3]) : "l"(p) : "memory");
}
__device__ __forceinline__ void ldg2(uint32_t* d, const void* p) {
  asm volatile("ld.relaxed.gpu.global.v2.b32 {%0,%1}, [%2];" : "=r"(d[0]), "=r"(d[1]) : "l"(p) : "memory");
}
__device__ __forceinline__ void stg4(uint4* p, uint32_t a, uint32_t b, uint32_t c, uint32_t d) {
  asm volatile("st.relaxed.gpu.global.v4.b32 [%0], {%1,%2,%3,%4};" :: "l"(p), "r"(a), "r"(b), "r"(c), "r"(d) : "memory");
}
__device__ __forceinline__ void stg2(void* p, uint32_t a, uint32_t b) {
  asm volatile("st.relaxed.gpu.global.v2.b32 [%0], {%1,%2};" :: "l"(p), "r"(a), "r"(b) : "memory");
}
__device__ __forceinline__ void sts4(uint32_t a, const uint32_t* o) { asm volatile("st.shared.v4.b32 [%0], {%1,%2,%3,%4};" :: "r"(a), "r"(o[0]), "r"(o[1]), "r"(o[2]), "r"(o[3]) : "memory"); }
__device__ __forceinline__ void lds4(uint32_t a, uint32_t* o) { asm volatile("ld.shared.v4.b32 {%0,%1,%2,%3}, [%4];" : "=r"(o[0]), "=r"(o[1]), "=r"(o[2]), "=r"(o[3]) : "r"(a) : "memory"); }
__device__ __forceinline__ void sts1(uint32_t a, uint32_t v) { asm volatile("st.shared.b32 [%0], %1;" :: "r"(a), "r"(v) : "memory"); }
__device__ __forceinline__ void ldsm4(uint32_t a, uint32_t& r0, uint32_t& r1, uint32_t& r2, uint32_t& r3) {
  asm volatile("ldmatrix.sync.aligned.m8n8.x4.shared.b16 {%0,%1,%2,%3}, [%4];" : "=r"(r0), "=r"(r1), "=r"(r2), "=r"(r3) : "r"(a) : "memory");
}
__device__ __forceinline__ void ldsm4t(uint32_t a, uint32_t& r0, uint32_t& r1, uint32_t& r2, uint32_t& r3) {
  asm volatile("ldmatrix.sync.aligned.m8n8.x4.trans.shared.b16 {%0,%1,%2,%3}, [%4];" : "=r"(r0), "=r"(r1), "=r"(r2), "=r"(r3) : "r"(a) : "memory");
}
__device__ __forceinline__ void mma16(float* c, uint32_t a0, uint32_t a1, uint32_t a2, uint32_t a3, uint32_t b0, uint32_t b1) {
  asm("mma.sync.aligned.m16n8k16.row.col.f32.bf16.bf16.f32 {%0,%1,%2,%3}, {%4,%5,%6,%7}, {%8,%9}, {%0,%1,%2,%3};"
    : "+f"(c[0]), "+f"(c[1]), "+f"(c[2]), "+f"(c[3]) : "r"(a0), "r"(a1), "r"(a2), "r"(a3), "r"(b0), "r"(b1));
}
__device__ __forceinline__ void mma8(float* c, uint32_t a0, uint32_t a1, uint32_t b0) {
  asm("mma.sync.aligned.m16n8k8.row.col.f32.bf16.bf16.f32 {%0,%1,%2,%3}, {%4,%5}, {%6}, {%0,%1,%2,%3};"
    : "+f"(c[0]), "+f"(c[1]), "+f"(c[2]), "+f"(c[3]) : "r"(a0), "r"(a1), "r"(b0));
}
__device__ __forceinline__ float quad_sum(float v) { v += __shfl_xor_sync(~0u, v, 1); v += __shfl_xor_sync(~0u, v, 2); return v; }
__device__ __forceinline__ float quad_max(float v) { v = fmaxf(v, __shfl_xor_sync(~0u, v, 1)); v = fmaxf(v, __shfl_xor_sync(~0u, v, 2)); return v; }
template <int N> __device__ __forceinline__ void pin(float (&d)[N]) {
#pragma unroll
  for (int i = 0; i < N; i++) asm volatile("" : "+f"(d[i]) :: "memory");
}
__device__ __forceinline__ void spin_guard(int& n) { if (++n > SPIN_MAX) __trap(); }

template <int NW> __device__ __forceinline__ void publish_stats(uint4* dst, const uint32_t* v, uint32_t tag, int lane) {
  float s0 = 0.f, s1 = 0.f;
#pragma unroll
  for (int g = 0; g < NW / 2; g++) { s0 += bf_lo(v[2 * g]) + bf_hi(v[2 * g]); s1 += bf_lo(v[2 * g + 1]) + bf_hi(v[2 * g + 1]); }
  s0 = quad_sum(s0); s1 = quad_sum(s1);
  const float m0 = s0 * (1.f / (4 * NW)), m1 = s1 * (1.f / (4 * NW));
  float q0 = 0.f, q1 = 0.f;
#pragma unroll
  for (int g = 0; g < NW / 2; g++) {
    float a = bf_lo(v[2 * g]) - m0, b = bf_hi(v[2 * g]) - m0, c = bf_lo(v[2 * g + 1]) - m1, d = bf_hi(v[2 * g + 1]) - m1;
    q0 = fmaf(a, a, q0); q0 = fmaf(b, b, q0); q1 = fmaf(c, c, q1); q1 = fmaf(d, d, q1);
  }
  q0 = quad_sum(q0); q1 = quad_sum(q1);
  if ((lane & 3) == 0)
    stg4(dst + (lane >> 2), (__float_as_uint(s0) & ~1u) | tag, __float_as_uint(q0), __float_as_uint(s1), __float_as_uint(q1));
}

__device__ __forceinline__ void put72(uint4* slab, int j, int lane, const uint32_t* v) {
  uint4* p = slab + ((9 * j + 1) >> 1) * 32;
  if (j & 1) {
    stg2((char*)(p - 16) + lane * 8, nz(v[0]), v[1]);
#pragma unroll
    for (int i = 0; i < 4; i++) stg4(p + lane + i * 32, nz(v[4 * i + 2]), v[4 * i + 3], v[4 * i + 4], v[4 * i + 5]);
  } else {
#pragma unroll
    for (int i = 0; i < 4; i++) stg4(p + lane + i * 32, nz(v[4 * i]), v[4 * i + 1], v[4 * i + 2], v[4 * i + 3]);
    stg2((char*)(p + 4 * 32) + lane * 8, nz(v[16]), v[17]);
  }
}
__device__ __forceinline__ void get72_unsplit(const uint4* slab, int j, int lane, uint32_t* v) {
  const uint4* p = slab + ((9 * j + 1) >> 1) * 32 + lane;
  if (j & 1) {
    ldg2(v, (const char*)(p - 32) + 8);
#pragma unroll
    for (int i = 0; i < 4; i++) ldg4(v + 2 + 4 * i, p + i * 32);
  } else {
#pragma unroll
    for (int i = 0; i < 4; i++) ldg4(v + 4 * i, p + i * 32);
    ldg2(v + 16, p + 4 * 32);
  }
}
__device__ __forceinline__ void zero_share(uint4* slab, int j, int lane) {
  uint4* p = slab + j * 144 + lane;
#pragma unroll
  for (int i = 0; i < 4; i++) stg4(p + i * 32, 0u, 0u, 0u, 0u);
  if (lane < 16) stg4(p + 128, 0u, 0u, 0u, 0u);
}

struct Ring {
  uint32_t st, ph;
  __device__ __forceinline__ void next() { if (++st == NST) { st = 0; ph ^= 1; } }
};

#define STAMP(i) do {} while (0)

__global__ void __launch_bounds__(384, 1) mega_kernel(
    const __grid_constant__ CUtensorMap m_qkv, const __grid_constant__ CUtensorMap m_wo,
    const __grid_constant__ CUtensorMap m_g, const __grid_constant__ CUtensorMap m_u, const __grid_constant__ CUtensorMap m_d,
    const __nv_bfloat16* __restrict__ x_in, const __nv_bfloat16* __restrict__ wqkv, const __nv_bfloat16* __restrict__ wo,
    __nv_bfloat16* __restrict__ out) {
  extern __shared__ __align__(1024) uint8_t smem[];
  const uint32_t sb = (uint32_t)__cvta_generic_to_shared(smem);
  const uint32_t full0 = sb + BARS, empty0 = full0 + 8 * NST, rem_full = empty0 + 8 * NST, park_free = rem_full + 8;
  const int w = threadIdx.x >> 5, lane = threadIdx.x & 31;
  const int t = blockIdx.x >> 3, j = blockIdx.x & 7;
  if (threadIdx.x == 0) {
    for (int i = 0; i < NST; i++) { mbar_init(full0 + 8 * i, 1); mbar_init(empty0 + 8 * i, 8); }
    mbar_init(rem_full, 64); mbar_init(park_free, 8);
    asm volatile("fence.mbarrier_init.release.cluster;" ::: "memory");
  }
  __syncthreads();

  if (w >= 8) {
    asm volatile("setmaxnreg.dec.sync.aligned.u32 24;");
    if (w == 8) {
      if (lane == 0) {
        Ring r{0, 1};
        uint32_t half = 0;
#pragma unroll 1
        for (int run = 0; run < 62; run++) {
          const int n = run >= 31 ? run - 31 : run;
          const CUtensorMap* m;
          int col, row = 0;
          if (n < 4) { m = n == 3 ? &m_wo : &m_qkv; col = 72 * j + (n < 2 ? 576 * (n + 1) : 0); }
          else if (n < 22) { m = (n & 1) ? &m_u : &m_g; col = 576 * j + 32 * ((n - 4) & ~1); }
          else { m = &m_d; col = n == 22 ? 512 : ((j + n - 22) & 7) * 64; row = 576 * j; }
          const bool padded = n < 4 || n == 30;
#pragma unroll 1
          for (int b = 0; b < 9; b++) {
            const bool solo = padded && b == 8;
            const uint32_t fb = full0 + r.st * 8;
            if (!half) { mbar_wait(empty0 + r.st * 8, r.ph); mbar_expect(fb, solo ? STAGE / 2 : STAGE); }
            tma2d(sb + r.st * STAGE + half * 8192, m, col, row + 64 * b, fb);
            if (half || solo) { half = 0; r.next(); } else half = 1;
          }
        }
      }
    } else if (w == 9) {
      const int r = lane >> 2, q = lane & 3;
      const int row = 128 * t + 32 * (j >> 1) + 2 * r + (j & 1);
      const int slab = (t * 8 + j) * SLAB + 32 * 32 + lane;
      uint4* sa = g_S[0] + ((t * 8 + j) * 12 + 8) * 8;
      {
        const uint32_t* xr = (const uint32_t*)(x_in + row * 576 + 512 + 2 * q);
        uint32_t v[16];
#pragma unroll
        for (int g = 0; g < 8; g++) { v[2 * g] = __ldg(xr + 4 * g); v[2 * g + 1] = __ldg(xr + 8 * 576 + 4 * g); }
#pragma unroll
        for (int i = 0; i < 4; i++) stg4(g_X[0][0] + slab + i * 32, nz(v[4 * i]), v[4 * i + 1], v[4 * i + 2], v[4 * i + 3]);
#pragma unroll
        for (int i = 0; i < 4; i++) publish_stats<4>(sa + i * 8, v + 4 * i, 1u, lane);
      }
#pragma unroll 1
      for (int layer = 0; layer < 2; layer++) {
        const uint32_t tag = 1 - layer;
#pragma unroll 1
        for (int i = 0; i < 4; i++) {
          float a[8];
#pragma unroll
          for (int e = 0; e < 8; e++) a[e] = 0.f;
#pragma unroll 1
          for (int s = 0; s < 8; s += 2) {
            const uint4* p = g_P + ((t * 8 + s) * 8 + j) * SLAB + (32 + i) * 32 + lane;
            uint32_t u[4], v[4];
            int n = 0;
            while (true) {
              ldg4(u, p); ldg4(v, p + 8 * SLAB);
              if (__all_sync(~0u, (u[0] & 1u) == tag && (v[0] & 1u) == tag)) break;
              __nanosleep(256);
              spin_guard(n);
            }
#pragma unroll
            for (int e = 0; e < 4; e++) { a[2 * e] += bf_lo(u[e]) + bf_lo(v[e]); a[2 * e + 1] += bf_hi(u[e]) + bf_hi(v[e]); }
          }
          uint32_t x[4];
          uint4* xb = g_X[2][layer] + slab + i * 32;
          ldg4(x, xb);
#pragma unroll
          for (int e = 0; e < 4; e++) x[e] = pack_bf16(bf_lo(x[e]) + a[2 * e], bf_hi(x[e]) + a[2 * e + 1]);
          stg4(xb, 0u, 0u, 0u, 0u);
          if (layer == 0) {
            stg4(g_X[0][1] + slab + i * 32, nz(x[0]), x[1], x[2], x[3]);
            publish_stats<4>(sa + i * 8, x, 0u, lane);
          } else {
            uint32_t* o = (uint32_t*)(out + row * 576 + 512 + 16 * i + 2 * q);
            o[0] = x[0]; o[8 * 576] = x[1]; o[4] = x[2]; o[8 * 576 + 4] = x[3];
          }
        }
      }
    } else {
      const int tid = threadIdx.x - 320;
#pragma unroll 1
      for (int layer = 0; layer < 2; layer++) {
        if (layer) mbar_wait(park_free, 0);
#pragma unroll 1
        for (int p = 0; p < 4; p++) {
          const __nv_bfloat16* src = (p == 3 ? wo : wqkv + (p == 2 ? 0 : 576 * (p + 1))) + 72 * j + 64;
          const int pitch = p == 3 ? 576 : 1728;
#pragma unroll 1
          for (int i = 0; i < 9; i++) {
            const int k = tid + 64 * i, s = k >> 4, rr = k & 7;
            const uint32_t dst = sb + REM + p * 10240 + (s >> 3) * 2048 + ((k >> 3) & 1) * 1024 + rr * 128 + (((s & 7) ^ rr) << 4);
            asm volatile("cp.async.cg.shared.global [%0], [%1], 16;" :: "r"(dst), "l"(src + k * pitch) : "memory");
          }
        }
        asm volatile("cp.async.wait_all;\nfence.proxy.async.shared::cta;" ::: "memory");
        mbar_arrive(rem_full);
      }
    }
  } else {
    asm volatile("setmaxnreg.inc.sync.aligned.u32 240;");
    const int r = lane >> 2, q = lane & 3;
    const int slab = (t * 8 + w) * SLAB;
    Ring rg{0, 0};
    uint32_t prev = 0;
    uint32_t X[144];
    auto release = [&](uint32_t st) { if (lane == 0) mbar_arrive(empty0 + st * 8); };
    auto publishA = [&](int layer, const uint32_t* v) {
      uint4* p = g_X[0][layer] + slab + 4 * j * 32 + lane;
#pragma unroll
      for (int i = 0; i < 4; i++) stg4(p + i * 32, nz(v[4 * i]), v[4 * i + 1], nz(v[4 * i + 2]), v[4 * i + 3]);
      publish_stats<16>(g_S[0] + ((t * 8 + w) * 12 + j) * 8, v, 1 - layer, lane);
    };
    {
      const int row = 128 * t + 32 * (w >> 1) + 2 * r + (w & 1);
      const uint32_t* xr = (const uint32_t*)(x_in + row * 576 + 64 * j + 2 * q);
      uint32_t v[16];
#pragma unroll
      for (int g = 0; g < 8; g++) { v[2 * g] = __ldg(xr + 4 * g); v[2 * g + 1] = __ldg(xr + 8 * 576 + 4 * g); }
      publishA(0, v);
    }
#pragma unroll 1
    for (int ph = 0; ph < 6; ph++) {
      const int layer = ph >= 3, kind = ph - 3 * layer;
      const uint32_t tag = 1 - layer;
      float rs0, rs1;
      STAMP(kind * 8 + 0);
      {
        uint32_t s[3][4];
        const uint4* p = g_S[kind] + (t * 8 + w) * 96 + q * 8 + r;
        int n = 0;
        s[2][0] = tag; s[2][1] = s[2][2] = s[2][3] = 0u;
        while (true) {
          ldg4(s[0], p); ldg4(s[1], p + 32);
          if (kind == 0) ldg4(s[2], p + 64);
          if (__all_sync(~0u, ((s[0][0] ^ tag) | (s[1][0] ^ tag) | (s[2][0] ^ tag)) % 2u == 0u)) break;
          spin_guard(n);
        }
        STAMP(kind * 8 + 1);
        const uint4* src = g_X[kind][layer] + slab;
        const char* lo = (const char*)src + (kind == 0 ? lane * 16 : lane * 8);
        const char* hi = lo + (kind == 0 ? 8 : 256);
        n = 0;
        while (true) {
#pragma unroll
          for (int k = 0; k < 36; k++) {
            if (k % 9 == 4) { ldg2(X + 4 * k, lo + k * 512); ldg2(X + 4 * k + 2, hi + k * 512); }
            else ldg4(X + 4 * k, src + lane + k * 32);
          }
          bool ok = true;
#pragma unroll
          for (int k = 0; k < 36; k++) { ok = ok && X[4 * k] != 0u; if (k % 9 == 4) ok = ok && X[4 * k + 2] != 0u; }
          if (__all_sync(~0u, ok)) break;
          spin_guard(n);
        }
        if (kind != 1) {
          float t0 = 0.f, t1 = 0.f;
#pragma unroll
          for (int i = 0; i < 3; i++) { t0 += __uint_as_float(s[i][0]); t1 += __uint_as_float(s[i][2]); }
          const float m0 = quad_sum(t0) * (1.f / 576), m1 = quad_sum(t1) * (1.f / 576);
          float v0 = 0.f, v1 = 0.f;
#pragma unroll
          for (int i = 0; i < 3; i++) {
            const float cnt = i < 2 ? (kind == 0 ? 64.f : 72.f) : (kind == 0 ? 16.f : 0.f);
            const float inv = i < 2 ? (kind == 0 ? 1.f / 64 : 1.f / 72) : 1.f / 16;
            const float d0 = fmaf(__uint_as_float(s[i][0]), inv, -m0), d1 = fmaf(__uint_as_float(s[i][2]), inv, -m1);
            v0 += fmaf(d0 * d0, cnt, __uint_as_float(s[i][1])); v1 += fmaf(d1 * d1, cnt, __uint_as_float(s[i][3]));
          }
          rs0 = rsqrtf(fmaf(quad_sum(v0), 1.f / 576, 1e-5f)); rs1 = rsqrtf(fmaf(quad_sum(v1), 1.f / 576, 1e-5f));
          const uint32_t mean0 = pack_bf16(m0, m0), mean1 = pack_bf16(m1, m1);
#pragma unroll
          for (int i = 0; i < 144; i++) X[i] = sub_bf16x2(X[i], (i & 1) ? mean1 : mean0);
        }
      }
      STAMP(kind * 8 + 2);
      if (kind != 2) {
      const uint32_t kvrow = sb + KVS + (w & 1) * 10368 + (16 * (w >> 1)) * 144;
      uint32_t res[18];
      float acc[36];
      if (kind == 0) mbar_wait(rem_full, layer);
      else get72_unsplit(g_X[0][layer] + slab, j, lane, res);
#pragma unroll 1
      for (int part = kind == 0 ? 0 : 3;; part++) {
#pragma unroll
        for (int st = 0; st < 5; st++) {
          mbar_wait(full0 + rg.st * 8, rg.ph);
          const uint32_t base = sb + rg.st * STAGE;
          const uint64_t d0 = DESC_HI | ((base >> 4) + (((sb + REM + part * 10240 + st * 2048 - base) >> 4) << 16));
          wg_fence();
#pragma unroll
          for (int i = 0; i < (st < 4 ? 8 : 4); i++) wgmma_rs_n72(acc, X + 4 * (8 * st + i), d0 - (uint64_t)(i * ((127u << 16) - 128u)), st + i != 0);
          wg_commit();
          wg_wait<1>();
          if (st > 0) release(prev);
          prev = rg.st; rg.next();
        }
        wg_wait<0>();
        release(prev);
        pin(acc);
        if (part >= 2) break;
        uint32_t hl[12];
        const uint32_t dst = kvrow + part * 20736 + (8 + r) * 144 + q * 4;
#pragma unroll
        for (int g = 0; g < 9; g++) {
          const uint32_t lo = pack_bf16(acc[4 * g] * rs0, acc[4 * g + 1] * rs0), hi = pack_bf16(acc[4 * g + 2] * rs1, acc[4 * g + 3] * rs1);
          sts1(dst + g * 16, lo); sts1(dst + 8 * 144 + g * 16, hi);
          hl[g] = hi;
        }
        if (w >= 6 && t < 15) {
          uint4* hp = g_H[layer] + ((((t + 1) * 8 + j) * 2 + (w & 1)) * 2 + part) * 96 + lane;
          stg4(hp, nz(hl[0]), hl[1], hl[2], hl[3]); stg4(hp + 32, nz(hl[4]), hl[5], hl[6], hl[7]); stg4(hp + 64, nz(hl[8]), 0u, 0u, 0u);
        }
        if (part == 1 && w < 4) asm volatile("bar.arrive 2, 256;" ::: "memory");
      }
      STAMP(kind * 8 + 3);
      if (kind == 1) {
#pragma unroll
        for (int i = 0; i < 18; i++) res[i] = pack_bf16(bf_lo(res[i]) + acc[2 * i], bf_hi(res[i]) + acc[2 * i + 1]);
        put72(g_X[2][layer] + slab, j, lane, res);
        publish_stats<18>(g_S[2] + ((t * 8 + w) * 12 + j) * 8, res, tag, lane);
        STAMP(kind * 8 + 4);
        continue;
      }
      uint32_t Q[18];
#pragma unroll
      for (int g = 0; g < 9; g++) {
        Q[2 * g] = pack_bf16(acc[4 * g] * rs0, acc[4 * g + 1] * rs0); Q[2 * g + 1] = pack_bf16(acc[4 * g + 2] * rs1, acc[4 * g + 3] * rs1);
      }
      if (w < 2 && t > 0) {
        uint4* hp = g_H[layer] + ((t * 8 + j) * 2 + w) * 192 + lane;
        uint32_t hl[24];
        int n = 0;
        while (true) {
#pragma unroll
          for (int i = 0; i < 6; i++) ldg4(hl + 4 * i, hp + i * 32);
          if (__all_sync(~0u, hl[0] != 0u && hl[4] != 0u && hl[8] != 0u && hl[12] != 0u && hl[16] != 0u && hl[20] != 0u)) break;
          spin_guard(n);
        }
#pragma unroll
        for (int i = 0; i < 6; i++) stg4(hp + i * 32, 0u, 0u, 0u, 0u);
#pragma unroll
        for (int g = 0; g < 9; g++) {
          sts1(kvrow + r * 144 + g * 16 + q * 4, hl[g]); sts1(kvrow + 20736 + r * 144 + g * 16 + q * 4, hl[12 + g]);
        }
      }
      if (w < 4) asm volatile("bar.sync 1, 128;" ::: "memory");
      else asm volatile("bar.sync 2, 256;" ::: "memory");
      STAMP(4);
      uint32_t O[18];
      {
        const bool edge = (t == 0 && w < 2);
        uint32_t row[3];
#pragma unroll
        for (int nt = 0; nt < 3; nt++) row[nt] = kvrow + (8 * nt + (lane & 7)) * 144;
        if (edge) row[0] = sb + KVS + 8 * 144;
        const uint32_t rlast = ((lane >> 3) == 0 ? row[0] : (lane >> 3) == 1 ? row[1] : row[2]) + 128;
        uint32_t K[3][9], V[3][9], dummy;
#pragma unroll
        for (int nt = 0; nt < 3; nt++) {
          ldsm4(row[nt] + (lane >> 3) * 16, K[nt][0], K[nt][1], K[nt][2], K[nt][3]);
          ldsm4(row[nt] + 64 + (lane >> 3) * 16, K[nt][4], K[nt][5], K[nt][6], K[nt][7]);
        }
        ldsm4(rlast, K[0][8], K[1][8], K[2][8], dummy);
#pragma unroll
        for (int nt = 0; nt < 3; nt++) {
          ldsm4t(row[nt] + 20736 + (lane >> 3) * 16, V[nt][0], V[nt][1], V[nt][2], V[nt][3]);
          ldsm4t(row[nt] + 20736 + 64 + (lane >> 3) * 16, V[nt][4], V[nt][5], V[nt][6], V[nt][7]);
        }
        ldsm4t(rlast + 20736, V[0][8], V[1][8], V[2][8], dummy);
        const bool up0 = 2 * q > r, up1 = 2 * q + 1 > r;
        const float sc = 0.23570226039551584f * 1.4426950408889634f;
        const float neg = -1e9f * 1.4426950408889634f;
        float Of[9][4];
#pragma unroll
        for (int h = 0; h < 4; h++) {
          const uint32_t a0 = q >= h ? Q[4 * h] : 0u, a1 = q >= h ? Q[4 * h + 1] : 0u;
          const uint32_t a4 = q <= h ? Q[4 * h + 4] : 0u, a5 = q <= h ? Q[4 * h + 5] : 0u;
          float S[3][4];
#pragma unroll
          for (int nt = 0; nt < 3; nt++) {
            S[nt][0] = S[nt][1] = S[nt][2] = S[nt][3] = 0.f;
            mma16(S[nt], a0, a1, Q[4 * h + 2], Q[4 * h + 3], K[nt][2 * h], K[nt][2 * h + 1]);
            mma8(S[nt], a4, a5, K[nt][2 * h + 2]);
          }
          float s00 = (up0 ? S[0][0] : S[1][0]) * sc, s01 = (up1 ? S[0][1] : S[1][1]) * sc;
          const float s10 = (up0 ? S[1][2] : S[2][2]) * sc, s11 = (up1 ? S[1][3] : S[2][3]) * sc;
          if (edge && up0) s00 = neg;
          if (edge && up1) s01 = neg;
          const float m0 = quad_max(fmaxf(s00, s01)), m1 = quad_max(fmaxf(s10, s11));
          float p00 = ex2(s00 - m0), p01 = ex2(s01 - m0), p10 = ex2(s10 - m1), p11 = ex2(s11 - m1);
          const float i0 = __frcp_rn(quad_sum(p00 + p01)), i1 = __frcp_rn(quad_sum(p10 + p11));
          p00 *= i0; p01 *= i0; p10 *= i1; p11 *= i1;
          const uint32_t pa = pack_bf16(up0 ? p00 : 0.f, up1 ? p01 : 0.f), pb = pack_bf16(up0 ? 0.f : p00, up1 ? 0.f : p01);
          const uint32_t pc = pack_bf16(up0 ? p10 : 0.f, up1 ? p11 : 0.f), pd = pack_bf16(up0 ? 0.f : p10, up1 ? 0.f : p11);
#pragma unroll
          for (int gi = 0; gi < 3; gi++) {
            const int g = 2 * h + gi;
            float o[4] = {0.f, 0.f, 0.f, 0.f};
            mma16(o, pa, 0u, pb, pc, V[0][g], V[1][g]);
            mma8(o, 0u, pd, V[2][g]);
#pragma unroll
            for (int e = 0; e < 4; e++) Of[g][e] = (gi == 0 && h > 0 && q < h) ? Of[g][e] : o[e];
          }
        }
#pragma unroll
        for (int g = 0; g < 9; g++) { O[2 * g] = pack_bf16(Of[g][0], Of[g][1]); O[2 * g + 1] = pack_bf16(Of[g][2], Of[g][3]); }
      }
      put72(g_X[1][layer] + slab, j, lane, O);
      if (q == 0) stg4(g_S[1] + ((t * 8 + w) * 12 + j) * 8 + r, tag, 0u, 0u, 0u);
      STAMP(5);
      continue;
      }
      zero_share(g_X[0][layer] + slab, j, lane);
      zero_share(g_X[1][layer] + slab, j, lane);
      float aG[32], aU[32];
      const uint32_t hp = sb + PARK + w * 512 + lane * 16;
      auto gelu8 = [&](int p, uint32_t* o) {
#pragma unroll
        for (int e = 0; e < 8; e++) asm volatile("" : "+f"(aG[8 * p + e]) :: "memory");
        float h[8];
#pragma unroll
        for (int e = 0; e < 8; e++) {
          const float rs = (e & 2) ? rs1 : rs0;
          const float g = aG[8 * p + e] * rs;
          const float th = tanh_ap(g * fmaf(g * g, 0.7978845608028654f * 0.044715f, 0.7978845608028654f));
          const float gs = g * (0.5f * rs);
          h[e] = fmaf(gs, th, gs);
        }
#pragma unroll
        for (int e = 0; e < 4; e++) o[e] = pack_bf16(h[2 * e], h[2 * e + 1]);
      };
      auto mul8 = [&](int p, uint32_t* g) {
#pragma unroll
        for (int e = 0; e < 8; e++) asm volatile("" : "+f"(aU[8 * p + e]) :: "memory");
#pragma unroll
        for (int e = 0; e < 4; e++) g[e] = pack_bf16(bf_lo(g[e]) * aU[8 * p + 2 * e], bf_hi(g[e]) * aU[8 * p + 2 * e + 1]);
      };
      auto step = [&](int st, bool rel, auto&& filler) {
        mbar_wait(full0 + rg.st * 8, rg.ph);
        const uint64_t desc = DESC_HI | ((sb + rg.st * STAGE) >> 4);
        wg_fence();
#pragma unroll
        for (int i = 0; i < 8; i++) {
          const int b = 2 * st + (i >> 2), s = (b < 9 ? b : b - 9) * 4 + (i & 3);
          if (b < 9) wgmma_rs_n64(aG, X + 4 * s, desc + i * 128, s != 0);
          else wgmma_rs_n64(aU, X + 4 * s, desc + i * 128, s != 0);
          if (i == 7) wg_commit();
          if (st == 4 && i == 3) { wg_commit(); wg_wait<1>(); wg_fence(); }
          if (i == 3) filler();
        }
        wg_wait<1>();
        if (rel) release(prev);
        prev = rg.st; rg.next();
      };
      auto nop = [] {};
#pragma unroll
      for (int st = 0; st < 4; st++) step(st, st > 0, nop);
#pragma unroll 1
      for (int c = 0; c < 8; c++) {
        const uint32_t hc = hp + c * 4 * 4096;
#pragma unroll
        for (int st = 4; st < 9; st++) step(st, true, [&] { if (st >= 5) { uint32_t o[4]; gelu8(st - 5, o); sts4(hc + (st - 5) * 4096, o); } });
#pragma unroll
        for (int st = 0; st < 4; st++) step(st, true, [&] {
          if (st >= 1) { uint32_t o[4]; lds4(hc + st * 4096, o); mul8(st, o); sts4(hc + st * 4096, o); }
          if (st == 1) { uint32_t o[4]; lds4(hc, o); mul8(0, o); sts4(hc, o); } });
      }
      {
        uint32_t G[16];
#pragma unroll
        for (int st = 4; st < 9; st++) step(st, true, [&] { if (st >= 5) gelu8(st - 5, G + 4 * (st - 5)); });
        wg_wait<0>(); release(prev);
        STAMP(19);
#pragma unroll
        for (int s = 0; s < 32; s++) lds4(hp + s * 4096, X + 4 * s);
#pragma unroll
        for (int p = 0; p < 4; p++) mul8(p, G + 4 * p);
#pragma unroll
        for (int i = 0; i < 16; i++) X[128 + i] = G[i];
      }
      STAMP(20);
      uint4* pw = g_P + ((t * 8 + j) * 8 + w) * SLAB + lane;
      auto put_part = [&](float (&a)[32], int p, int chunk) {
#pragma unroll
        for (int e = 0; e < 8; e++) asm volatile("" : "+f"(a[8 * p + e]) :: "memory");
        stg4(pw + (chunk * 4 + p) * 32, (pack_bf16(a[8 * p], a[8 * p + 1]) & ~1u) | tag, pack_bf16(a[8 * p + 2], a[8 * p + 3]),
             pack_bf16(a[8 * p + 4], a[8 * p + 5]), pack_bf16(a[8 * p + 6], a[8 * p + 7]));
      };
#pragma unroll
      for (int st = 0; st < 4; st++) step(st, st > 0, nop);
      if (layer == 0 && lane == 0) mbar_arrive(park_free);
#pragma unroll 1
      for (int sp = 0; sp < 4; sp++) {
        const int ca = sp == 0 ? 8 : ((j + 2 * sp) & 7), cb = (j + 2 * sp + 1) & 7;
#pragma unroll
        for (int st = 4; st < 9; st++) step(st, true, [&] { if (st == 5 || st == 6) { put_part(aG, 2 * (st - 5), ca); put_part(aG, 2 * (st - 5) + 1, ca); } });
#pragma unroll
        for (int st = 0; st < 4; st++) step(st, true, [&] { if (st == 1) { put_part(aU, 0, cb); put_part(aU, 1, cb); put_part(aU, 2, cb); put_part(aU, 3, cb); } });
      }
      {
        mbar_wait(full0 + rg.st * 8, rg.ph);
        const uint64_t desc = DESC_HI | ((sb + rg.st * STAGE) >> 4);
        wg_fence();
#pragma unroll
        for (int i = 0; i < 4; i++) wgmma_rs_n64(aG, X + 4 * (32 + i), desc + i * 128, 1);
        wg_commit();
        wg_wait<1>(); release(prev);
        prev = rg.st; rg.next();
        wg_wait<0>(); release(prev);
        pin(aG);
      }
      STAMP(21);
      {
        uint4* xb = g_X[2][layer] + slab + 4 * j * 32;
        const uint4* pr = g_P + (t * 64 + w) * SLAB + 4 * j * 32 + lane;
#pragma unroll
        for (int i = 0; i < 4; i++) {
          const bool split = j == 2 * i + 1;
          const char* lo = (const char*)(xb + i * 32) + (split ? lane * 8 : lane * 16);
          ldg2(X + 4 * i, lo); ldg2(X + 4 * i + 2, lo + (split ? 256 : 8));
        }
        int n = 0;
        while (true) {
#pragma unroll
          for (int s = 1; s < 8; s++)
#pragma unroll
            for (int i = 0; i < 4; i++) ldg4(X + 16 * s + 4 * i, pr + ((j + s) & 7) * 8 * SLAB + i * 32);
          uint32_t bad = 0;
#pragma unroll
          for (int s = 4; s < 32; s++) bad |= X[4 * s] ^ tag;
          if (__all_sync(~0u, (bad & 1u) == 0u)) break;
          spin_guard(n);
        }
        const uint32_t eye = r == 2 * q ? 0x3f80u : r == 2 * q + 1 ? 0x3f800000u : 0u;
#pragma unroll
        for (int s = 0; s < 8; s++)
#pragma unroll
          for (int g = 0; g < 8; g++) mma8(aG + 4 * g, X[16 * s + 2 * g], X[16 * s + 2 * g + 1], eye);
        uint32_t res[16];
#pragma unroll
        for (int i = 0; i < 16; i++) res[i] = pack_bf16(aG[2 * i], aG[2 * i + 1]);
        if (layer == 0) {
          publishA(1, res);
        } else {
          const int row = 128 * t + 32 * (w >> 1) + 2 * r + (w & 1);
          uint32_t* o = (uint32_t*)(out + row * 576 + 64 * j + 2 * q);
#pragma unroll
          for (int g = 0; g < 8; g++) { o[4 * g] = res[2 * g]; o[8 * 576 + 4 * g] = res[2 * g + 1]; }
        }
#pragma unroll
        for (int i = 0; i < 4; i++) stg4(xb + lane + i * 32, 0u, 0u, 0u, 0u);
      }
      STAMP(22);
    }
  }
}

typedef CUresult (*EncodeFn)(CUtensorMap*, CUtensorMapDataType, cuuint32_t, void*, const cuuint64_t*, const cuuint64_t*,
                             const cuuint32_t*, const cuuint32_t*, CUtensorMapInterleave, CUtensorMapSwizzle,
                             CUtensorMapL2promotion, CUtensorMapFloatOOBfill);

CUtensorMap make_map(EncodeFn f, const void* p, uint64_t cols, uint64_t rows) {
  CUtensorMap m;
  cuuint64_t dims[2] = {cols, rows};
  cuuint64_t str[1] = {cols * 2};
  cuuint32_t box[2] = {64, 64};
  cuuint32_t es[2] = {1, 1};
  f(&m, CU_TENSOR_MAP_DATA_TYPE_BFLOAT16, 2, const_cast<void*>(p), dims, str, box, es, CU_TENSOR_MAP_INTERLEAVE_NONE,
    CU_TENSOR_MAP_SWIZZLE_128B, CU_TENSOR_MAP_L2_PROMOTION_NONE, CU_TENSOR_MAP_FLOAT_OOB_FILL_NONE);
  return m;
}

}

extern "C" void kernel_launch(void* const* d_in, const int* in_sizes, int n_in, void* d_out, int out_size) {
  void* fn = nullptr;
  cudaDriverEntryPointQueryResult qr;
  cudaGetDriverEntryPoint("cuTensorMapEncodeTiled", &fn, cudaEnableDefault, &qr);
  EncodeFn enc = (EncodeFn)fn;
  const CUtensorMap m_qkv = make_map(enc, d_in[1], 1728, 576), m_wo = make_map(enc, d_in[2], 576, 576);
  const CUtensorMap m_g = make_map(enc, d_in[4], 4608, 576), m_u = make_map(enc, d_in[5], 4608, 576), m_d = make_map(enc, d_in[6], 576, 4608);
  cudaFuncSetAttribute(mega_kernel, cudaFuncAttributeMaxDynamicSharedMemorySize, SMEM_BYTES);
  mega_kernel<<<128, 384, SMEM_BYTES>>>(m_qkv, m_wo, m_g, m_u, m_d, (const __nv_bfloat16*)d_in[0], (const __nv_bfloat16*)d_in[1],
                                        (const __nv_bfloat16*)d_in[2], (__nv_bfloat16*)d_out);
}
```

```cpp
#include <cuda_runtime.h>
#include <cuda.h>
#include <cuda_bf16.h>
#include <stdint.h>

#define TRACE 0

namespace {

constexpr int NST = 6;
constexpr int STAGE = 16384;
constexpr int PARK = NST * STAGE;
constexpr int REM = PARK + 49152;
constexpr int KVS = REM + 40960;
constexpr int BARS = KVS + 41472;
constexpr int SMEM_BYTES = BARS + 256;
static_assert(BARS >= PARK + 131072, "barriers overlap park");
static_assert(SMEM_BYTES <= 232448, "smem");

constexpr int SLAB = 36 * 32;
constexpr int SPIN_MAX = 1 << 22;

}

__device__ uint4 g_X[3][2][128 * SLAB];
__device__ uint4 g_P[8 * 128 * SLAB];
__device__ uint4 g_S[3][128 * 12 * 8];
__device__ uint4 g_H[2][128 * 2 * 6 * 32];

namespace {

constexpr uint64_t DESC_HI = 0x4000004000000000ull;
__device__ __forceinline__ void wgmma_rs_n64(float (&d)[32], const uint32_t* a, uint64_t desc, int scale_d) {
  asm volatile("{\n.reg .pred p;\nsetp.ne.b32 p, %37, 0;\n"
    "wgmma.mma_async.sync.aligned.m64n64k16.f32.bf16.bf16 "
    "{%0, %1, %2, %3, %4, %5, %6, %7, %8, %9, %10, %11, %12, %13, %14, %15, %16, %17, %18, %19, %20, %21, %22, %23, %24, %25, %26, %27, %28, %29, %30, %31}, "
    "{%32, %33, %34, %35}, %36, p, 1, 1, 1;\n}\n"
    : "+f"(d[0]), "+f"(d[1]), "+f"(d[2]), "+f"(d[3]), "+f"(d[4]), "+f"(d[5]), "+f"(d[6]), "+f"(d[7]), "+f"(d[8]), "+f"(d[9]), "+f"(d[10]), "+f"(d[11]), "+f"(d[12]), "+f"(d[13]), "+f"(d[14]), "+f"(d[15]), "+f"(d[16]), "+f"(d[17]), "+f"(d[18]), "+f"(d[19]), "+f"(d[20]), "+f"(d[21]), "+f"(d[22]), "+f"(d[23]), "+f"(d[24]), "+f"(d[25]), "+f"(d[26]), "+f"(d[27]), "+f"(d[28]), "+f"(d[29]), "+f"(d[30]), "+f"(d[31])
    : "r"(a[0]), "r"(a[1]), "r"(a[2]), "r"(a[3]), "l"(desc), "r"(scale_d));
}
__device__ __forceinline__ void wgmma_rs_n72(float (&d)[36], const uint32_t* a, uint64_t desc, int scale_d) {
  asm volatile("{\n.reg .pred p;\nsetp.ne.b32 p, %41, 0;\n"
    "wgmma.mma_async.sync.aligned.m64n72k16.f32.bf16.bf16 "
    "{%0, %1, %2, %3, %4, %5, %6, %7, %8, %9, %10, %11, %12, %13, %14, %15, %16, %17, %18, %19, %20, %21, %22, %23, %24, %25, %26, %27, %28, %29, %30, %31, %32, %33, %34, %35}, "
    "{%36, %37, %38, %39}, %40, p, 1, 1, 1;\n}\n"
    : "+f"(d[0]), "+f"(d[1]), "+f"(d[2]), "+f"(d[3]), "+f"(d[4]), "+f"(d[5]), "+f"(d[6]), "+f"(d[7]), "+f"(d[8]), "+f"(d[9]), "+f"(d[10]), "+f"(d[11]), "+f"(d[12]), "+f"(d[13]), "+f"(d[14]), "+f"(d[15]), "+f"(d[16]), "+f"(d[17]), "+f"(d[18]), "+f"(d[19]), "+f"(d[20]), "+f"(d[21]), "+f"(d[22]), "+f"(d[23]), "+f"(d[24]), "+f"(d[25]), "+f"(d[26]), "+f"(d[27]), "+f"(d[28]), "+f"(d[29]), "+f"(d[30]), "+f"(d[31]), "+f"(d[32]), "+f"(d[33]), "+f"(d[34]), "+f"(d[35])
    : "r"(a[0]), "r"(a[1]), "r"(a[2]), "r"(a[3]), "l"(desc), "r"(scale_d));
}

__device__ __forceinline__ void mbar_init(uint32_t a, uint32_t c) { asm volatile("mbarrier.init.shared::cta.b64 [%0], %1;" :: "r"(a), "r"(c)); }
__device__ __forceinline__ void mbar_arrive(uint32_t a) { asm volatile("mbarrier.arrive.shared::cta.b64 _, [%0];" :: "r"(a) : "memory"); }
__device__ __forceinline__ void mbar_wait(uint32_t a, uint32_t ph) {
  asm volatile("{\n.reg .pred p;\n.reg .u32 n;\n"
               "mbarrier.try_wait.parity.shared::cta.b64 p, [%0], %1;\n@p bra D;\n"
               "mov.u32 n, 0;\n"
               "W: mbarrier.try_wait.parity.shared::cta.b64 p, [%0], %1;\n@p bra D;\n"
               "add.u32 n, n, 1;\nsetp.lt.u32 p, n, 4194304;\n@p bra W;\ntrap;\nD:\n}" :: "r"(a), "r"(ph) : "memory");
}
__device__ __forceinline__ void wg_fence() { asm volatile("wgmma.fence.sync.aligned;" ::: "memory"); }
__device__ __forceinline__ void wg_commit() { asm volatile("wgmma.commit_group.sync.aligned;" ::: "memory"); }
template <int N> __device__ __forceinline__ void wg_wait() { asm volatile("wgmma.wait_group.sync.aligned %0;" :: "n"(N) : "memory"); }
__device__ __forceinline__ float tanh_ap(float x) { float y; asm("tanh.approx.f32 %0, %1;" : "=f"(y) : "f"(x)); return y; }
__device__ __forceinline__ float ex2(float x) { float y; asm("ex2.approx.ftz.f32 %0, %1;" : "=f"(y) : "f"(x)); return y; }
__device__ __forceinline__ uint32_t pack_bf16(float lo, float hi) { uint32_t r; asm("cvt.rn.bf16x2.f32 %0, %1, %2;" : "=r"(r) : "f"(hi), "f"(lo)); return r; }
__device__ __forceinline__ float bf_lo(uint32_t v) { return __uint_as_float(v << 16); }
__device__ __forceinline__ float bf_hi(uint32_t v) { return __uint_as_float(v & 0xffff0000u); }
__device__ __forceinline__ uint32_t sub_bf16x2(uint32_t a, uint32_t b) { uint32_t r; asm("sub.rn.bf16x2 %0, %1, %2;" : "=r"(r) : "r"(a), "r"(b)); return r; }
__device__ __forceinline__ uint32_t nz(uint32_t w) { return w == 0u ? 0x8000u : w; }

__device__ __forceinline__ void ldg4(uint32_t* d, const uint4* p) {
  asm volatile("ld.relaxed.gpu.global.v4.b32 {%0,%1,%2,%3}, [%4];" : "=r"(d[0]), "=r"(d[1]), "=r"(d[2]), "=r"(d[3]) : "l"(p) : "memory");
}
__device__ __forceinline__ void ldg2(uint32_t* d, const void* p) {
  asm volatile("ld.relaxed.gpu.global.v2.b32 {%0,%1}, [%2];" : "=r"(d[0]), "=r"(d[1]) : "l"(p) : "memory");
}
__device__ __forceinline__ void stg4(uint4* p, uint32_t a, uint32_t b, uint32_t c, uint32_t d) {
  asm volatile("st.relaxed.gpu.global.v4.b32 [%0], {%1,%2,%3,%4};" :: "l"(p), "r"(a), "r"(b), "r"(c), "r"(d) : "memory");
}
__device__ __forceinline__ void stg2(void* p, uint32_t a, uint32_t b) {
  asm volatile("st.relaxed.gpu.global.v2.b32 [%0], {%1,%2};" :: "l"(p), "r"(a), "r"(b) : "memory");
}
__device__ __forceinline__ void sts4(uint32_t a, const uint32_t* o) { asm volatile("st.shared.v4.b32 [%0], {%1,%2,%3,%4};" :: "r"(a), "r"(o[0]), "r"(o[1]), "r"(o[2]), "r"(o[3]) : "memory"); }
__device__ __forceinline__ void lds4(uint32_t a, uint32_t* o) { asm volatile("ld.shared.v4.b32 {%0,%1,%2,%3}, [%4];" : "=r"(o[0]), "=r"(o[1]), "=r"(o[2]), "=r"(o[3]) : "r"(a) : "memory"); }
__device__ __forceinline__ void sts1(uint32_t a, uint32_t v) { asm volatile("st.shared.b32 [%0], %1;" :: "r"(a), "r"(v) : "memory"); }
__device__ __forceinline__ void ldsm4(uint32_t a, uint32_t& r0, uint32_t& r1, uint32_t& r2, uint32_t& r3) {
  asm volatile("ldmatrix.sync.aligned.m8n8.x4.shared.b16 {%0,%1,%2,%3}, [%4];" : "=r"(r0), "=r"(r1), "=r"(r2), "=r"(r3) : "r"(a) : "memory");
}
__device__ __forceinline__ void ldsm4t(uint32_t a, uint32_t& r0, uint32_t& r1, uint32_t& r2, uint32_t& r3) {
  asm volatile("ldmatrix.sync.aligned.m8n8.x4.trans.shared.b16 {%0,%1,%2,%3}, [%4];" : "=r"(r0), "=r"(r1), "=r"(r2), "=r"(r3) : "r"(a) : "memory");
}
__device__ __forceinline__ void mma16(float* c, uint32_t a0, uint32_t a1, uint32_t a2, uint32_t a3, uint32_t b0, uint32_t b1) {
  asm("mma.sync.aligned.m16n8k16.row.col.f32.bf16.bf16.f32 {%0,%1,%2,%3}, {%4,%5,%6,%7}, {%8,%9}, {%0,%1,%2,%3};"
    : "+f"(c[0]), "+f"(c[1]), "+f"(c[2]), "+f"(c[3]) : "r"(a0), "r"(a1), "r"(a2), "r"(a3), "r"(b0), "r"(b1));
}
__device__ __forceinline__ void mma8(float* c, uint32_t a0, uint32_t a1, uint32_t b0) {
  asm("mma.sync.aligned.m16n8k8.row.col.f32.bf16.bf16.f32 {%0,%1,%2,%3}, {%4,%5}, {%6}, {%0,%1,%2,%3};"
    : "+f"(c[0]), "+f"(c[1]), "+f"(c[2]), "+f"(c[3]) : "r"(a0), "r"(a1), "r"(b0));
}
__device__ __forceinline__ float quad_sum(float v) { v += __shfl_xor_sync(~0u, v, 1); v += __shfl_xor_sync(~0u, v, 2); return v; }
__device__ __forceinline__ float quad_max(float v) { v = fmaxf(v, __shfl_xor_sync(~0u, v, 1)); v = fmaxf(v, __shfl_xor_sync(~0u, v, 2)); return v; }
template <int N> __device__ __forceinline__ void pin(float (&d)[N]) {
#pragma unroll
  for (int i = 0; i < N; i++) asm volatile("" : "+f"(d[i]) :: "memory");
}
__device__ __forceinline__ void spin_guard(int& n) { if (++n > SPIN_MAX) __trap(); }

template <int NW> __device__ __forceinline__ void publish_stats(uint4* dst, const uint32_t* v, uint32_t tag, int lane) {
  float s0 = 0.f, s1 = 0.f;
#pragma unroll
  for (int g = 0; g < NW / 2; g++) { s0 += bf_lo(v[2 * g]) + bf_hi(v[2 * g]); s1 += bf_lo(v[2 * g + 1]) + bf_hi(v[2 * g + 1]); }
  s0 = quad_sum(s0); s1 = quad_sum(s1);
  const float m0 = s0 * (1.f / (4 * NW)), m1 = s1 * (1.f / (4 * NW));
  float q0 = 0.f, q1 = 0.f;
#pragma unroll
  for (int g = 0; g < NW / 2; g++) {
    float a = bf_lo(v[2 * g]) - m0, b = bf_hi(v[2 * g]) - m0, c = bf_lo(v[2 * g + 1]) - m1, d = bf_hi(v[2 * g + 1]) - m1;
    q0 = fmaf(a, a, q0); q0 = fmaf(b, b, q0); q1 = fmaf(c, c, q1); q1 = fmaf(d, d, q1);
  }
  q0 = quad_sum(q0); q1 = quad_sum(q1);
  if ((lane & 3) == 0)
    stg4(dst + (lane >> 2), (__float_as_uint(s0) & ~1u) | tag, __float_as_uint(q0), __float_as_uint(s1), __float_as_uint(q1));
}

__device__ __forceinline__ void put72(uint4* slab, int j, int lane, const uint32_t* v) {
  uint4* p = slab + ((9 * j + 1) >> 1) * 32;
  if (j & 1) {
    stg2((char*)(p - 16) + lane * 8, nz(v[0]), v[1]);
#pragma unroll
    for (int i = 0; i < 4; i++) stg4(p + lane + i * 32, nz(v[4 * i + 2]), v[4 * i + 3], v[4 * i + 4], v[4 * i + 5]);
  } else {
#pragma unroll
    for (int i = 0; i < 4; i++) stg4(p + lane + i * 32, nz(v[4 * i]), v[4 * i + 1], v[4 * i + 2], v[4 * i + 3]);
    stg2((char*)(p + 4 * 32) + lane * 8, nz(v[16]), v[17]);
  }
}
__device__ __forceinline__ void get72_unsplit(const uint4* slab, int j, int lane, uint32_t* v) {
  const uint4* p = slab + ((9 * j + 1) >> 1) * 32 + lane;
  if (j & 1) {
    ldg2(v, (const char*)(p - 32) + 8);
#pragma unroll
    for (int i = 0; i < 4; i++) ldg4(v + 2 + 4 * i, p + i * 32);
  } else {
#pragma unroll
    for (int i = 0; i < 4; i++) ldg4(v + 4 * i, p + i * 32);
    ldg2(v + 16, p + 4 * 32);
  }
}
__device__ __forceinline__ void zero_share(uint4* slab, int j, int lane) {
  uint4* p = slab + j * 144 + lane;
#pragma unroll
  for (int i = 0; i < 4; i++) stg4(p + i * 32, 0u, 0u, 0u, 0u);
  if (lane < 16) stg4(p + 128, 0u, 0u, 0u, 0u);
}

struct Maps { CUtensorMap m[5]; };

struct Ring {
  uint32_t st, ph;
  __device__ __forceinline__ void next() { if (++st == NST) { st = 0; ph ^= 1; } }
};

#define STAMP(i) do {} while (0)

__global__ void __launch_bounds__(384, 1) mega_kernel(
    const __grid_constant__ Maps maps,
    const __nv_bfloat16* __restrict__ x_in, const __nv_bfloat16* __restrict__ wqkv, const __nv_bfloat16* __restrict__ wo,
    __nv_bfloat16* __restrict__ out) {
  extern __shared__ __align__(1024) uint8_t smem[];
  const uint32_t sb = (uint32_t)__cvta_generic_to_shared(smem);
  const uint32_t full0 = sb + BARS, empty0 = full0 + 8 * NST, rem_full = empty0 + 8 * NST, park_free = rem_full + 8;
  const int w = __shfl_sync(~0u, threadIdx.x >> 5, 0), lane = threadIdx.x & 31;
  const int t = blockIdx.x >> 3, j = blockIdx.x & 7;
  if (threadIdx.x == 0) {
    for (int i = 0; i < NST; i++) { mbar_init(full0 + 8 * i, 1); mbar_init(empty0 + 8 * i, 8); }
    mbar_init(rem_full, 64); mbar_init(park_free, 8);
    asm volatile("fence.mbarrier_init.release.cluster;" ::: "memory");
  }
  __syncthreads();

  if (w >= 8) {
    asm volatile("setmaxnreg.dec.sync.aligned.u32 24;");
    if (w == 8) {
      Ring r{0, 1};
      uint32_t half = 0;
#pragma unroll 1
      for (int run = 0; run < 62; run++) {
        const int n = run >= 31 ? run - 31 : run;
        int mi, col, row = 0;
        if (n < 4) { mi = n == 3; col = 72 * j + (n < 2 ? 576 * (n + 1) : 0); }
        else if (n < 22) { mi = 2 + (n & 1); col = 576 * j + 32 * ((n - 4) & ~1); }
        else { mi = 4; col = n == 22 ? 512 : ((j + n - 22) & 7) * 64; row = 576 * j; }
        const CUtensorMap* m = &maps.m[mi];
        const bool padded = n < 4 || n == 30;
#pragma unroll 1
        for (int b = 0; b < 9; b++) {
          const bool solo = padded && b == 8;
          const uint32_t fb = full0 + r.st * 8;
          if (!half) mbar_wait(empty0 + r.st * 8, r.ph);
          asm volatile("{\n.reg .pred e, h;\nelect.sync _|e, 0xffffffff;\nsetp.eq.and.u32 h, %6, 0, e;\n"
                       "@h mbarrier.arrive.expect_tx.shared::cta.b64 _, [%2], %5;\n"
                       "@e cp.async.bulk.tensor.2d.shared::cluster.global.mbarrier::complete_tx::bytes [%0], [%1, {%3, %4}], [%2];\n}"
                       :: "r"(sb + r.st * STAGE + half * 8192), "l"(m), "r"(fb), "r"(col), "r"(row + 64 * b),
                          "r"(solo ? STAGE / 2 : STAGE), "r"(half) : "memory");
          if (half || solo) { half = 0; r.next(); } else half = 1;
        }
      }
    } else if (w == 9) {
      const int r = lane >> 2, q = lane & 3;
      const int row = 128 * t + 32 * (j >> 1) + 2 * r + (j & 1);
      const int slab = (t * 8 + j) * SLAB + 32 * 32 + lane;
      uint4* sa = g_S[0] + ((t * 8 + j) * 12 + 8) * 8;
      {
        const uint32_t* xr = (const uint32_t*)(x_in + row * 576 + 512 + 2 * q);
        uint32_t v[16];
#pragma unroll
        for (int g = 0; g < 8; g++) { v[2 * g] = __ldg(xr + 4 * g); v[2 * g + 1] = __ldg(xr + 8 * 576 + 4 * g); }
#pragma unroll
        for (int i = 0; i < 4; i++) stg4(g_X[0][0] + slab + i * 32, nz(v[4 * i]), v[4 * i + 1], v[4 * i + 2], v[4 * i + 3]);
#pragma unroll
        for (int i = 0; i < 4; i++) publish_stats<4>(sa + i * 8, v + 4 * i, 1u, lane);
      }
#pragma unroll 1
      for (int layer = 0; layer < 2; layer++) {
        const uint32_t tag = 1 - layer;
#pragma unroll 1
        for (int i = 0; i < 4; i++) {
          float a[8];
#pragma unroll
          for (int e = 0; e < 8; e++) a[e] = 0.f;
#pragma unroll 1
          for (int s = 0; s < 8; s += 2) {
            const uint4* p = g_P + ((t * 8 + s) * 8 + j) * SLAB + (32 + i) * 32 + lane;
            uint32_t u[4], v[4];
            int n = 0;
            while (true) {
              ldg4(u, p); ldg4(v, p + 8 * SLAB);
              if (__all_sync(~0u, (u[0] & 1u) == tag && (v[0] & 1u) == tag)) break;
              __nanosleep(256);
              spin_guard(n);
            }
#pragma unroll
            for (int e = 0; e < 4; e++) { a[2 * e] += bf_lo(u[e]) + bf_lo(v[e]); a[2 * e + 1] += bf_hi(u[e]) + bf_hi(v[e]); }
          }
          uint32_t x[4];
          uint4* xb = g_X[2][layer] + slab + i * 32;
          ldg4(x, xb);
#pragma unroll
          for (int e = 0; e < 4; e++) x[e] = pack_bf16(bf_lo(x[e]) + a[2 * e], bf_hi(x[e]) + a[2 * e + 1]);
          stg4(xb, 0u, 0u, 0u, 0u);
          if (layer == 0) {
            stg4(g_X[0][1] + slab + i * 32, nz(x[0]), x[1], x[2], x[3]);
            publish_stats<4>(sa + i * 8, x, 0u, lane);
          } else {
            uint32_t* o = (uint32_t*)(out + row * 576 + 512 + 16 * i + 2 * q);
            o[0] = x[0]; o[8 * 576] = x[1]; o[4] = x[2]; o[8 * 576 + 4] = x[3];
          }
        }
      }
    } else {
      const int tid = threadIdx.x - 320;
#pragma unroll 1
      for (int layer = 0; layer < 2; layer++) {
        if (layer) mbar_wait(park_free, 0);
#pragma unroll 1
        for (int p = 0; p < 4; p++) {
          const __nv_bfloat16* src = (p == 3 ? wo : wqkv + (p == 2 ? 0 : 576 * (p + 1))) + 72 * j + 64;
          const int pitch = p == 3 ? 576 : 1728;
#pragma unroll 1
          for (int i = 0; i < 9; i++) {
            const int k = tid + 64 * i, s = k >> 4, rr = k & 7;
            const uint32_t dst = sb + REM + p * 10240 + (s >> 3) * 2048 + ((k >> 3) & 1) * 1024 + rr * 128 + (((s & 7) ^ rr) << 4);
            asm volatile("cp.async.cg.shared.global [%0], [%1], 16;" :: "r"(dst), "l"(src + k * pitch) : "memory");
          }
        }
        asm volatile("cp.async.wait_all;\nfence.proxy.async.shared::cta;" ::: "memory");
        mbar_arrive(rem_full);
      }
    }
  } else {
    asm volatile("setmaxnreg.inc.sync.aligned.u32 240;");
    const int r = lane >> 2, q = lane & 3;
    const int slab = (t * 8 + w) * SLAB;
    Ring rg{0, 0};
    uint32_t prev = 0;
    uint32_t X[144];
    auto release = [&](uint32_t st) { if (lane == 0) mbar_arrive(empty0 + st * 8); };
    auto publishA = [&](int layer, const uint32_t* v) {
      uint4* p = g_X[0][layer] + slab + 4 * j * 32 + lane;
#pragma unroll
      for (int i = 0; i < 4; i++) stg4(p + i * 32, nz(v[4 * i]), v[4 * i + 1], nz(v[4 * i + 2]), v[4 * i + 3]);
      publish_stats<16>(g_S[0] + ((t * 8 + w) * 12 + j) * 8, v, 1 - layer, lane);
    };
    {
      const int row = 128 * t + 32 * (w >> 1) + 2 * r + (w & 1);
      const uint32_t* xr = (const uint32_t*)(x_in + row * 576 + 64 * j + 2 * q);
      uint32_t v[16];
#pragma unroll
      for (int g = 0; g < 8; g++) { v[2 * g] = __ldg(xr + 4 * g); v[2 * g + 1] = __ldg(xr + 8 * 576 + 4 * g); }
      publishA(0, v);
    }
#pragma unroll 1
    for (int ph = 0; ph < 6; ph++) {
      const int layer = ph >= 3, kind = ph - 3 * layer;
      const uint32_t tag = 1 - layer;
      float rs0, rs1;
      STAMP(kind * 8 + 0);
      {
        uint32_t s[3][4];
        const uint4* p = g_S[kind] + (t * 8 + w) * 96 + q * 8 + r;
        int n = 0;
        s[2][0] = tag; s[2][1] = s[2][2] = s[2][3] = 0u;
        while (true) {
          ldg4(s[0], p); ldg4(s[1], p + 32);
          if (kind == 0) ldg4(s[2], p + 64);
          if (__all_sync(~0u, ((s[0][0] ^ tag) | (s[1][0] ^ tag) | (s[2][0] ^ tag)) % 2u == 0u)) break;
          spin_guard(n);
        }
        STAMP(kind * 8 + 1);
        const uint4* src = g_X[kind][layer] + slab;
        const char* lo = (const char*)src + (kind == 0 ? lane * 16 : lane * 8);
        const char* hi = lo + (kind == 0 ? 8 : 256);
        n = 0;
        while (true) {
#pragma unroll
          for (int k = 0; k < 36; k++) {
            if (k % 9 == 4) { ldg2(X + 4 * k, lo + k * 512); ldg2(X + 4 * k + 2, hi + k * 512); }
            else ldg4(X + 4 * k, src + lane + k * 32);
          }
          bool ok = true;
#pragma unroll
          for (int k = 0; k < 36; k++) { ok = ok && X[4 * k] != 0u; if (k % 9 == 4) ok = ok && X[4 * k + 2] != 0u; }
          if (__all_sync(~0u, ok)) break;
          spin_guard(n);
        }
        if (kind != 1) {
          float t0 = 0.f, t1 = 0.f;
#pragma unroll
          for (int i = 0; i < 3; i++) { t0 += __uint_as_float(s[i][0]); t1 += __uint_as_float(s[i][2]); }
          const float m0 = quad_sum(t0) * (1.f / 576), m1 = quad_sum(t1) * (1.f / 576);
          float v0 = 0.f, v1 = 0.f;
#pragma unroll
          for (int i = 0; i < 3; i++) {
            const float cnt = i < 2 ? (kind == 0 ? 64.f : 72.f) : (kind == 0 ? 16.f : 0.f);
            const float inv = i < 2 ? (kind == 0 ? 1.f / 64 : 1.f / 72) : 1.f / 16;
            const float d0 = fmaf(__uint_as_float(s[i][0]), inv, -m0), d1 = fmaf(__uint_as_float(s[i][2]), inv, -m1);
            v0 += fmaf(d0 * d0, cnt, __uint_as_float(s[i][1])); v1 += fmaf(d1 * d1, cnt, __uint_as_float(s[i][3]));
          }
          rs0 = rsqrtf(fmaf(quad_sum(v0), 1.f / 576, 1e-5f)); rs1 = rsqrtf(fmaf(quad_sum(v1), 1.f / 576, 1e-5f));
          const uint32_t mean0 = pack_bf16(m0, m0), mean1 = pack_bf16(m1, m1);
#pragma unroll
          for (int i = 0; i < 144; i++) X[i] = sub_bf16x2(X[i], (i & 1) ? mean1 : mean0);
        }
      }
      STAMP(kind * 8 + 2);
      if (kind != 2) {
      const uint32_t kvrow = sb + KVS + (w & 1) * 10368 + (16 * (w >> 1)) * 144;
      uint32_t res[18];
      float acc[36];
      if (kind == 0) mbar_wait(rem_full, layer);
      else get72_unsplit(g_X[0][layer] + slab, j, lane, res);
#pragma unroll 1
      for (int part = kind == 0 ? 0 : 3;; part++) {
#pragma unroll
        for (int st = 0; st < 5; st++) {
          mbar_wait(full0 + rg.st * 8, rg.ph);
          const uint32_t base = sb + rg.st * STAGE;
          const uint64_t d0 = DESC_HI | ((base >> 4) + (((sb + REM + part * 10240 + st * 2048 - base) >> 4) << 16));
          wg_fence();
#pragma unroll
          for (int i = 0; i < (st < 4 ? 8 : 4); i++) wgmma_rs_n72(acc, X + 4 * (8 * st + i), d0 - (uint64_t)(i * ((127u << 16) - 128u)), st + i != 0);
          wg_commit();
          wg_wait<1>();
          if (st > 0) release(prev);
          prev = rg.st; rg.next();
        }
        wg_wait<0>();
        release(prev);
        pin(acc);
        if (part >= 2) break;
        uint32_t hl[12];
        const uint32_t dst = kvrow + part * 20736 + (8 + r) * 144 + q * 4;
#pragma unroll
        for (int g = 0; g < 9; g++) {
          const uint32_t lo = pack_bf16(acc[4 * g] * rs0, acc[4 * g + 1] * rs0), hi = pack_bf16(acc[4 * g + 2] * rs1, acc[4 * g + 3] * rs1);
          sts1(dst + g * 16, lo); sts1(dst + 8 * 144 + g * 16, hi);
          hl[g] = hi;
        }
        if (w >= 6 && t < 15) {
          uint4* hp = g_H[layer] + ((((t + 1) * 8 + j) * 2 + (w & 1)) * 2 + part) * 96 + lane;
          stg4(hp, nz(hl[0]), hl[1], hl[2], hl[3]); stg4(hp + 32, nz(hl[4]), hl[5], hl[6], hl[7]); stg4(hp + 64, nz(hl[8]), 0u, 0u, 0u);
        }
        if (part == 1 && w < 4) asm volatile("bar.arrive 2, 256;" ::: "memory");
      }
      STAMP(kind * 8 + 3);
      if (kind == 1) {
#pragma unroll
        for (int i = 0; i < 18; i++) res[i] = pack_bf16(bf_lo(res[i]) + acc[2 * i], bf_hi(res[i]) + acc[2 * i + 1]);
        put72(g_X[2][layer] + slab, j, lane, res);
        publish_stats<18>(g_S[2] + ((t * 8 + w) * 12 + j) * 8, res, tag, lane);
        STAMP(kind * 8 + 4);
        continue;
      }
      uint32_t Q[18];
#pragma unroll
      for (int g = 0; g < 9; g++) {
        Q[2 * g] = pack_bf16(acc[4 * g] * rs0, acc[4 * g + 1] * rs0); Q[2 * g + 1] = pack_bf16(acc[4 * g + 2] * rs1, acc[4 * g + 3] * rs1);
      }
      if (w < 2 && t > 0) {
        uint4* hp = g_H[layer] + ((t * 8 + j) * 2 + w) * 192 + lane;
        uint32_t hl[24];
        int n = 0;
        while (true) {
#pragma unroll
          for (int i = 0; i < 6; i++) ldg4(hl + 4 * i, hp + i * 32);
          if (__all_sync(~0u, hl[0] != 0u && hl[4] != 0u && hl[8] != 0u && hl[12] != 0u && hl[16] != 0u && hl[20] != 0u)) break;
          spin_guard(n);
        }
#pragma unroll
        for (int i = 0; i < 6; i++) stg4(hp + i * 32, 0u, 0u, 0u, 0u);
#pragma unroll
        for (int g = 0; g < 9; g++) {
          sts1(kvrow + r * 144 + g * 16 + q * 4, hl[g]); sts1(kvrow + 20736 + r * 144 + g * 16 + q * 4, hl[12 + g]);
        }
      }
      if (w < 4) asm volatile("bar.sync 1, 128;" ::: "memory");
      else asm volatile("bar.sync 2, 256;" ::: "memory");
      STAMP(4);
      uint32_t O[18];
      {
        const bool edge = (t == 0 && w < 2);
        uint32_t row[3];
#pragma unroll
        for (int nt = 0; nt < 3; nt++) row[nt] = kvrow + (8 * nt + (lane & 7)) * 144;
        if (edge) row[0] = sb + KVS + 8 * 144;
        const uint32_t rlast = ((lane >> 3) == 0 ? row[0] : (lane >> 3) == 1 ? row[1] : row[2]) + 128;
        uint32_t K[3][9], V[3][9], dummy;
#pragma unroll
        for (int nt = 0; nt < 3; nt++) {
          ldsm4(row[nt] + (lane >> 3) * 16, K[nt][0], K[nt][1], K[nt][2], K[nt][3]);
          ldsm4(row[nt] + 64 + (lane >> 3) * 16, K[nt][4], K[nt][5], K[nt][6], K[nt][7]);
        }
        ldsm4(rlast, K[0][8], K[1][8], K[2][8], dummy);
#pragma unroll
        for (int nt = 0; nt < 3; nt++) {
          ldsm4t(row[nt] + 20736 + (lane >> 3) * 16, V[nt][0], V[nt][1], V[nt][2], V[nt][3]);
          ldsm4t(row[nt] + 20736 + 64 + (lane >> 3) * 16, V[nt][4], V[nt][5], V[nt][6], V[nt][7]);
        }
        ldsm4t(rlast + 20736, V[0][8], V[1][8], V[2][8], dummy);
        const bool up0 = 2 * q > r, up1 = 2 * q + 1 > r;
        const float sc = 0.23570226039551584f * 1.4426950408889634f;
        const float neg = -1e9f * 1.4426950408889634f;
        float Of[9][4];
#pragma unroll
        for (int h = 0; h < 4; h++) {
          const uint32_t a0 = q >= h ? Q[4 * h] : 0u, a1 = q >= h ? Q[4 * h + 1] : 0u;
          const uint32_t a4 = q <= h ? Q[4 * h + 4] : 0u, a5 = q <= h ? Q[4 * h + 5] : 0u;
          float S[3][4];
#pragma unroll
          for (int nt = 0; nt < 3; nt++) {
            S[nt][0] = S[nt][1] = S[nt][2] = S[nt][3] = 0.f;
            mma16(S[nt], a0, a1, Q[4 * h + 2], Q[4 * h + 3], K[nt][2 * h], K[nt][2 * h + 1]);
            mma8(S[nt], a4, a5, K[nt][2 * h + 2]);
          }
          float s00 = (up0 ? S[0][0] : S[1][0]) * sc, s01 = (up1 ? S[0][1] : S[1][1]) * sc;
          const float s10 = (up0 ? S[1][2] : S[2][2]) * sc, s11 = (up1 ? S[1][3] : S[2][3]) * sc;
          if (edge && up0) s00 = neg;
          if (edge && up1) s01 = neg;
          const float m0 = quad_max(fmaxf(s00, s01)), m1 = quad_max(fmaxf(s10, s11));
          float p00 = ex2(s00 - m0), p01 = ex2(s01 - m0), p10 = ex2(s10 - m1), p11 = ex2(s11 - m1);
          const float i0 = __frcp_rn(quad_sum(p00 + p01)), i1 = __frcp_rn(quad_sum(p10 + p11));
          p00 *= i0; p01 *= i0; p10 *= i1; p11 *= i1;
          const uint32_t pa = pack_bf16(up0 ? p00 : 0.f, up1 ? p01 : 0.f), pb = pack_bf16(up0 ? 0.f : p00, up1 ? 0.f : p01);
          const uint32_t pc = pack_bf16(up0 ? p10 : 0.f, up1 ? p11 : 0.f), pd = pack_bf16(up0 ? 0.f : p10, up1 ? 0.f : p11);
#pragma unroll
          for (int gi = 0; gi < 3; gi++) {
            const int g = 2 * h + gi;
            float o[4] = {0.f, 0.f, 0.f, 0.f};
            mma16(o, pa, 0u, pb, pc, V[0][g], V[1][g]);
            mma8(o, 0u, pd, V[2][g]);
#pragma unroll
            for (int e = 0; e < 4; e++) Of[g][e] = (gi == 0 && h > 0 && q < h) ? Of[g][e] : o[e];
          }
        }
#pragma unroll
        for (int g = 0; g < 9; g++) { O[2 * g] = pack_bf16(Of[g][0], Of[g][1]); O[2 * g + 1] = pack_bf16(Of[g][2], Of[g][3]); }
      }
      put72(g_X[1][layer] + slab, j, lane, O);
      if (q == 0) stg4(g_S[1] + ((t * 8 + w) * 12 + j) * 8 + r, tag, 0u, 0u, 0u);
      STAMP(5);
      continue;
      }
      zero_share(g_X[0][layer] + slab, j, lane);
      zero_share(g_X[1][layer] + slab, j, lane);
      float aG[32], aU[32];
      const uint32_t hp = sb + PARK + w * 512 + lane * 16;
      auto gelu8 = [&](int p, uint32_t* o) {
#pragma unroll
        for (int e = 0; e < 8; e++) asm volatile("" : "+f"(aG[8 * p + e]) :: "memory");
        float h[8];
#pragma unroll
        for (int e = 0; e < 8; e++) {
          const float rs = (e & 2) ? rs1 : rs0;
          const float g = aG[8 * p + e] * rs;
          const float th = tanh_ap(g * fmaf(g * g, 0.7978845608028654f * 0.044715f, 0.7978845608028654f));
          const float gs = g * (0.5f * rs);
          h[e] = fmaf(gs, th, gs);
        }
#pragma unroll
        for (int e = 0; e < 4; e++) o[e] = pack_bf16(h[2 * e], h[2 * e + 1]);
      };
      auto mul8 = [&](int p, uint32_t* g) {
#pragma unroll
        for (int e = 0; e < 8; e++) asm volatile("" : "+f"(aU[8 * p + e]) :: "memory");
#pragma unroll
        for (int e = 0; e < 4; e++) g[e] = pack_bf16(bf_lo(g[e]) * aU[8 * p + 2 * e], bf_hi(g[e]) * aU[8 * p + 2 * e + 1]);
      };
      auto step = [&](int st, bool rel, auto&& filler) {
        mbar_wait(full0 + rg.st * 8, rg.ph);
        const uint64_t desc = DESC_HI | ((sb + rg.st * STAGE) >> 4);
        wg_fence();
#pragma unroll
        for (int i = 0; i < 8; i++) {
          const int b = 2 * st + (i >> 2), s = (b < 9 ? b : b - 9) * 4 + (i & 3);
          if (b < 9) wgmma_rs_n64(aG, X + 4 * s, desc + i * 128, s != 0);
          else wgmma_rs_n64(aU, X + 4 * s, desc + i * 128, s != 0);
          if (i == 7) wg_commit();
          if (st == 4 && i == 3) { wg_commit(); wg_wait<1>(); wg_fence(); }
          if (i == 3) filler();
        }
        wg_wait<1>();
        if (rel) release(prev);
        prev = rg.st; rg.next();
      };
      auto nop = [] {};
#pragma unroll
      for (int st = 0; st < 4; st++) step(st, st > 0, nop);
#pragma unroll 1
      for (int c = 0; c < 8; c++) {
        const uint32_t hc = hp + c * 4 * 4096;
#pragma unroll
        for (int st = 4; st < 9; st++) step(st, true, [&] { if (st >= 5) { uint32_t o[4]; gelu8(st - 5, o); sts4(hc + (st - 5) * 4096, o); } });
#pragma unroll
        for (int st = 0; st < 4; st++) step(st, true, [&] {
          if (st >= 1) { uint32_t o[4]; lds4(hc + st * 4096, o); mul8(st, o); sts4(hc + st * 4096, o); }
          if (st == 1) { uint32_t o[4]; lds4(hc, o); mul8(0, o); sts4(hc, o); } });
      }
      {
        uint32_t G[16];
#pragma unroll
        for (int st = 4; st < 9; st++) step(st, true, [&] { if (st >= 5) gelu8(st - 5, G + 4 * (st - 5)); });
        wg_wait<0>(); release(prev);
        STAMP(19);
#pragma unroll
        for (int s = 0; s < 32; s++) lds4(hp + s * 4096, X + 4 * s);
#pragma unroll
        for (int p = 0; p < 4; p++) mul8(p, G + 4 * p);
#pragma unroll
        for (int i = 0; i < 16; i++) X[128 + i] = G[i];
      }
      STAMP(20);
      uint4* pw = g_P + ((t * 8 + j) * 8 + w) * SLAB + lane;
      auto put_part = [&](float (&a)[32], int p, int chunk) {
#pragma unroll
        for (int e = 0; e < 8; e++) asm volatile("" : "+f"(a[8 * p + e]) :: "memory");
        stg4(pw + (chunk * 4 + p) * 32, (pack_bf16(a[8 * p], a[8 * p + 1]) & ~1u) | tag, pack_bf16(a[8 * p + 2], a[8 * p + 3]),
             pack_bf16(a[8 * p + 4], a[8 * p + 5]), pack_bf16(a[8 * p + 6], a[8 * p + 7]));
      };
#pragma unroll
      for (int st = 0; st < 4; st++) step(st, st > 0, nop);
      if (layer == 0 && lane == 0) mbar_arrive(park_free);
#pragma unroll 1
      for (int sp = 0; sp < 4; sp++) {
        const int ca = sp == 0 ? 8 : ((j + 2 * sp) & 7), cb = (j + 2 * sp + 1) & 7;
#pragma unroll
        for (int st = 4; st < 9; st++) step(st, true, [&] { if (st == 5 || st == 6) { put_part(aG, 2 * (st - 5), ca); put_part(aG, 2 * (st - 5) + 1, ca); } });
#pragma unroll
        for (int st = 0; st < 4; st++) step(st, true, [&] { if (st == 1) { put_part(aU, 0, cb); put_part(aU, 1, cb); put_part(aU, 2, cb); put_part(aU, 3, cb); } });
      }
      {
        mbar_wait(full0 + rg.st * 8, rg.ph);
        const uint64_t desc = DESC_HI | ((sb + rg.st * STAGE) >> 4);
        wg_fence();
#pragma unroll
        for (int i = 0; i < 4; i++) wgmma_rs_n64(aG, X + 4 * (32 + i), desc + i * 128, 1);
        wg_commit();
        wg_wait<1>(); release(prev);
        prev = rg.st; rg.next();
        wg_wait<0>(); release(prev);
        pin(aG);
      }
      STAMP(21);
      {
        uint4* xb = g_X[2][layer] + slab + 4 * j * 32;
        const uint4* pr = g_P + (t * 64 + w) * SLAB + 4 * j * 32 + lane;
#pragma unroll
        for (int i = 0; i < 4; i++) {
          const bool split = j == 2 * i + 1;
          const char* lo = (const char*)(xb + i * 32) + (split ? lane * 8 : lane * 16);
          ldg2(X + 4 * i, lo); ldg2(X + 4 * i + 2, lo + (split ? 256 : 8));
        }
        int n = 0;
        while (true) {
#pragma unroll
          for (int s = 1; s < 8; s++)
#pragma unroll
            for (int i = 0; i < 4; i++) ldg4(X + 16 * s + 4 * i, pr + ((j + s) & 7) * 8 * SLAB + i * 32);
          uint32_t bad = 0;
#pragma unroll
          for (int s = 4; s < 32; s++) bad |= X[4 * s] ^ tag;
          if (__all_sync(~0u, (bad & 1u) == 0u)) break;
          spin_guard(n);
        }
        const uint32_t eye = r == 2 * q ? 0x3f80u : r == 2 * q + 1 ? 0x3f800000u : 0u;
#pragma unroll
        for (int s = 0; s < 8; s++)
#pragma unroll
          for (int g = 0; g < 8; g++) mma8(aG + 4 * g, X[16 * s + 2 * g], X[16 * s + 2 * g + 1], eye);
        uint32_t res[16];
#pragma unroll
        for (int i = 0; i < 16; i++) res[i] = pack_bf16(aG[2 * i], aG[2 * i + 1]);
        if (layer == 0) {
          publishA(1, res);
        } else {
          const int row = 128 * t + 32 * (w >> 1) + 2 * r + (w & 1);
          uint32_t* o = (uint32_t*)(out + row * 576 + 64 * j + 2 * q);
#pragma unroll
          for (int g = 0; g < 8; g++) { o[4 * g] = res[2 * g]; o[8 * 576 + 4 * g] = res[2 * g + 1]; }
        }
#pragma unroll
        for (int i = 0; i < 4; i++) stg4(xb + lane + i * 32, 0u, 0u, 0u, 0u);
      }
      STAMP(22);
    }
  }
}

typedef CUresult (*EncodeFn)(CUtensorMap*, CUtensorMapDataType, cuuint32_t, void*, const cuuint64_t*, const cuuint64_t*,
                             const cuuint32_t*, const cuuint32_t*, CUtensorMapInterleave, CUtensorMapSwizzle,
                             CUtensorMapL2promotion, CUtensorMapFloatOOBfill);

CUtensorMap make_map(EncodeFn f, const void* p, uint64_t cols, uint64_t rows) {
  CUtensorMap m;
  cuuint64_t dims[2] = {cols, rows};
  cuuint64_t str[1] = {cols * 2};
  cuuint32_t box[2] = {64, 64};
  cuuint32_t es[2] = {1, 1};
  f(&m, CU_TENSOR_MAP_DATA_TYPE_BFLOAT16, 2, const_cast<void*>(p), dims, str, box, es, CU_TENSOR_MAP_INTERLEAVE_NONE,
    CU_TENSOR_MAP_SWIZZLE_128B, CU_TENSOR_MAP_L2_PROMOTION_NONE, CU_TENSOR_MAP_FLOAT_OOB_FILL_NONE);
  return m;
}

}

extern "C" void kernel_launch(void* const* d_in, const int* in_sizes, int n_in, void* d_out, int out_size) {
  void* fn = nullptr;
  cudaDriverEntryPointQueryResult qr;
  cudaGetDriverEntryPoint("cuTensorMapEncodeTiled", &fn, cudaEnableDefault, &qr);
  EncodeFn enc = (EncodeFn)fn;
  Maps maps;
  maps.m[0] = make_map(enc, d_in[1], 1728, 576); maps.m[1] = make_map(enc, d_in[2], 576, 576);
  maps.m[2] = make_map(enc, d_in[4], 4608, 576); maps.m[3] = make_map(enc, d_in[5], 4608, 576); maps.m[4] = make_map(enc, d_in[6], 576, 4608);
  cudaFuncSetAttribute(mega_kernel, cudaFuncAttributeMaxDynamicSharedMemorySize, SMEM_BYTES);
  mega_kernel<<<128, 384, SMEM_BYTES>>>(maps, (const __nv_bfloat16*)d_in[0], (const __nv_bfloat16*)d_in[1],
                                        (const __nv_bfloat16*)d_in[2], (__nv_bfloat16*)d_out);
}
```

```cpp
#include <cuda_runtime.h>
#include <cuda.h>
#include <cuda_bf16.h>
#include <stdint.h>

#define TRACE 0

namespace {

constexpr int NST = 6;
constexpr int STAGE = 16384;
constexpr int PARK = NST * STAGE;
constexpr int REM = PARK + 49152;
constexpr int KVS = REM + 40960;
constexpr int HSTG = KVS + 32768;
constexpr int BARS = KVS + 41472;
constexpr int TRC = BARS + 256;
constexpr int SMEM_BYTES = TRC + (TRACE ? 512 : 0);
static_assert(BARS >= PARK + 131072, "barriers overlap park");
static_assert(SMEM_BYTES <= 232448, "smem");

constexpr int SLAB = 36 * 32;
constexpr int SPIN_MAX = 1 << 17;
constexpr int GD = 3;
constexpr int OFF_X = 0;
constexpr int OFF_P = OFF_X + 6 * 128 * SLAB;
constexpr int OFF_S = OFF_P + 8 * 128 * SLAB;
constexpr int OFF_H = OFF_S + 3 * 128 * 96;
constexpr int SCRATCH = OFF_H + 2 * 128 * 384;

}

__device__ uint4 g_scratch[SCRATCH];

namespace {

constexpr uint64_t DESC_HI = 0x4000004000000000ull;
__device__ __forceinline__ void wgmma_rs_n64(float (&d)[32], const uint32_t* a, uint64_t desc, int scale_d) {
  asm volatile("{\n.reg .pred p;\nsetp.ne.b32 p, %37, 0;\n"
    "wgmma.mma_async.sync.aligned.m64n64k16.f32.bf16.bf16 "
    "{%0, %1, %2, %3, %4, %5, %6, %7, %8, %9, %10, %11, %12, %13, %14, %15, %16, %17, %18, %19, %20, %21, %22, %23, %24, %25, %26, %27, %28, %29, %30, %31}, "
    "{%32, %33, %34, %35}, %36, p, 1, 1, 1;\n}\n"
    : "+f"(d[0]), "+f"(d[1]), "+f"(d[2]), "+f"(d[3]), "+f"(d[4]), "+f"(d[5]), "+f"(d[6]), "+f"(d[7]), "+f"(d[8]), "+f"(d[9]), "+f"(d[10]), "+f"(d[11]), "+f"(d[12]), "+f"(d[13]), "+f"(d[14]), "+f"(d[15]), "+f"(d[16]), "+f"(d[17]), "+f"(d[18]), "+f"(d[19]), "+f"(d[20]), "+f"(d[21]), "+f"(d[22]), "+f"(d[23]), "+f"(d[24]), "+f"(d[25]), "+f"(d[26]), "+f"(d[27]), "+f"(d[28]), "+f"(d[29]), "+f"(d[30]), "+f"(d[31])
    : "r"(a[0]), "r"(a[1]), "r"(a[2]), "r"(a[3]), "l"(desc), "r"(scale_d));
}
__device__ __forceinline__ void wgmma_rs_n72(float (&d)[36], const uint32_t* a, uint64_t desc, int scale_d) {
  asm volatile("{\n.reg .pred p;\nsetp.ne.b32 p, %41, 0;\n"
    "wgmma.mma_async.sync.aligned.m64n72k16.f32.bf16.bf16 "
    "{%0, %1, %2, %3, %4, %5, %6, %7, %8, %9, %10, %11, %12, %13, %14, %15, %16, %17, %18, %19, %20, %21, %22, %23, %24, %25, %26, %27, %28, %29, %30, %31, %32, %33, %34, %35}, "
    "{%36, %37, %38, %39}, %40, p, 1, 1, 1;\n}\n"
    : "+f"(d[0]), "+f"(d[1]), "+f"(d[2]), "+f"(d[3]), "+f"(d[4]), "+f"(d[5]), "+f"(d[6]), "+f"(d[7]), "+f"(d[8]), "+f"(d[9]), "+f"(d[10]), "+f"(d[11]), "+f"(d[12]), "+f"(d[13]), "+f"(d[14]), "+f"(d[15]), "+f"(d[16]), "+f"(d[17]), "+f"(d[18]), "+f"(d[19]), "+f"(d[20]), "+f"(d[21]), "+f"(d[22]), "+f"(d[23]), "+f"(d[24]), "+f"(d[25]), "+f"(d[26]), "+f"(d[27]), "+f"(d[28]), "+f"(d[29]), "+f"(d[30]), "+f"(d[31]), "+f"(d[32]), "+f"(d[33]), "+f"(d[34]), "+f"(d[35])
    : "r"(a[0]), "r"(a[1]), "r"(a[2]), "r"(a[3]), "l"(desc), "r"(scale_d));
}

__device__ __forceinline__ void mbar_init(uint32_t a, uint32_t c) { asm volatile("mbarrier.init.shared::cta.b64 [%0], %1;" :: "r"(a), "r"(c)); }
__device__ __forceinline__ void mbar_arrive(uint32_t a) { asm volatile("mbarrier.arrive.shared::cta.b64 _, [%0];" :: "r"(a) : "memory"); }
__device__ __forceinline__ void mbar_wait(uint32_t a, uint32_t ph) {
  asm volatile("{\n.reg .pred p;\n.reg .u32 n;\n"
               "mbarrier.try_wait.parity.shared::cta.b64 p, [%0], %1;\n@p bra D;\n"
               "mov.u32 n, 0;\n"
               "W: mbarrier.try_wait.parity.shared::cta.b64 p, [%0], %1;\n@p bra D;\n"
               "add.u32 n, n, 1;\nsetp.lt.u32 p, n, 4194304;\n@p bra W;\ntrap;\nD:\n}" :: "r"(a), "r"(ph) : "memory");
}
__device__ __forceinline__ void wg_fence() { asm volatile("wgmma.fence.sync.aligned;" ::: "memory"); }
__device__ __forceinline__ void wg_commit() { asm volatile("wgmma.commit_group.sync.aligned;" ::: "memory"); }
template <int N> __device__ __forceinline__ void wg_wait() { asm volatile("wgmma.wait_group.sync.aligned %0;" :: "n"(N) : "memory"); }
__device__ __forceinline__ float tanh_ap(float x) { float y; asm("tanh.approx.f32 %0, %1;" : "=f"(y) : "f"(x)); return y; }
__device__ __forceinline__ float ex2(float x) { float y; asm("ex2.approx.ftz.f32 %0, %1;" : "=f"(y) : "f"(x)); return y; }
__device__ __forceinline__ uint32_t pack_bf16(float lo, float hi) { uint32_t r; asm("cvt.rn.bf16x2.f32 %0, %1, %2;" : "=r"(r) : "f"(hi), "f"(lo)); return r; }
__device__ __forceinline__ float bf_lo(uint32_t v) { return __uint_as_float(v << 16); }
__device__ __forceinline__ float bf_hi(uint32_t v) { return __uint_as_float(v & 0xffff0000u); }
__device__ __forceinline__ uint32_t sub_bf16x2(uint32_t a, uint32_t b) { uint32_t r; asm("sub.rn.bf16x2 %0, %1, %2;" : "=r"(r) : "r"(a), "r"(b)); return r; }
__device__ __forceinline__ uint32_t nz(uint32_t w) { return w == 0u ? 0x8000u : w; }

__device__ __forceinline__ void ldg4(uint32_t* d, const uint4* p) {
  asm volatile("ld.relaxed.gpu.global.v4.b32 {%0,%1,%2,%3}, [%4];" : "=r"(d[0]), "=r"(d[1]), "=r"(d[2]), "=r"(d[3]) : "l"(p) : "memory");
}
__device__ __forceinline__ void ldg2(uint32_t* d, const void* p) {
  asm volatile("ld.relaxed.gpu.global.v2.b32 {%0,%1}, [%2];" : "=r"(d[0]), "=r"(d[1]) : "l"(p) : "memory");
}
__device__ __forceinline__ void stg4(uint4* p, uint32_t a, uint32_t b, uint32_t c, uint32_t d) {
  asm volatile("st.relaxed.gpu.global.v4.b32 [%0], {%1,%2,%3,%4};" :: "l"(p), "r"(a), "r"(b), "r"(c), "r"(d) : "memory");
}
__device__ __forceinline__ void stg2(void* p, uint32_t a, uint32_t b) {
  asm volatile("st.relaxed.gpu.global.v2.b32 [%0], {%1,%2};" :: "l"(p), "r"(a), "r"(b) : "memory");
}
__device__ __forceinline__ void sts4(uint32_t a, const uint32_t* o) { asm volatile("st.shared.v4.b32 [%0], {%1,%2,%3,%4};" :: "r"(a), "r"(o[0]), "r"(o[1]), "r"(o[2]), "r"(o[3]) : "memory"); }
__device__ __forceinline__ void lds4(uint32_t a, uint32_t* o) { asm volatile("ld.shared.v4.b32 {%0,%1,%2,%3}, [%4];" : "=r"(o[0]), "=r"(o[1]), "=r"(o[2]), "=r"(o[3]) : "r"(a) : "memory"); }
__device__ __forceinline__ void cp16(uint32_t dst, const void* src) { asm volatile("cp.async.cg.shared.global [%0], [%1], 16;" :: "r"(dst), "l"(src) : "memory"); }
__device__ __forceinline__ void cp_wait() { asm volatile("cp.async.wait_all;" ::: "memory"); }
__device__ __forceinline__ float rcp(float x) { float y; asm("rcp.approx.ftz.f32 %0, %1;" : "=f"(y) : "f"(x)); return y; }
__device__ __forceinline__ void sts1(uint32_t a, uint32_t v) { asm volatile("st.shared.b32 [%0], %1;" :: "r"(a), "r"(v) : "memory"); }
__device__ __forceinline__ void ldsm4(uint32_t a, uint32_t& r0, uint32_t& r1, uint32_t& r2, uint32_t& r3) {
  asm volatile("ldmatrix.sync.aligned.m8n8.x4.shared.b16 {%0,%1,%2,%3}, [%4];" : "=r"(r0), "=r"(r1), "=r"(r2), "=r"(r3) : "r"(a) : "memory");
}
__device__ __forceinline__ void ldsm4t(uint32_t a, uint32_t& r0, uint32_t& r1, uint32_t& r2, uint32_t& r3) {
  asm volatile("ldmatrix.sync.aligned.m8n8.x4.trans.shared.b16 {%0,%1,%2,%3}, [%4];" : "=r"(r0), "=r"(r1), "=r"(r2), "=r"(r3) : "r"(a) : "memory");
}
__device__ __forceinline__ void mma16(float* c, uint32_t a0, uint32_t a1, uint32_t a2, uint32_t a3, uint32_t b0, uint32_t b1) {
  asm("mma.sync.aligned.m16n8k16.row.col.f32.bf16.bf16.f32 {%0,%1,%2,%3}, {%4,%5,%6,%7}, {%8,%9}, {%0,%1,%2,%3};"
    : "+f"(c[0]), "+f"(c[1]), "+f"(c[2]), "+f"(c[3]) : "r"(a0), "r"(a1), "r"(a2), "r"(a3), "r"(b0), "r"(b1));
}
__device__ __forceinline__ void mma8(float* c, uint32_t a0, uint32_t a1, uint32_t b0) {
  asm("mma.sync.aligned.m16n8k8.row.col.f32.bf16.bf16.f32 {%0,%1,%2,%3}, {%4,%5}, {%6}, {%0,%1,%2,%3};"
    : "+f"(c[0]), "+f"(c[1]), "+f"(c[2]), "+f"(c[3]) : "r"(a0), "r"(a1), "r"(b0));
}
__device__ __forceinline__ float quad_sum(float v) { v += __shfl_xor_sync(~0u, v, 1); v += __shfl_xor_sync(~0u, v, 2); return v; }
__device__ __forceinline__ float quad_max(float v) { v = fmaxf(v, __shfl_xor_sync(~0u, v, 1)); v = fmaxf(v, __shfl_xor_sync(~0u, v, 2)); return v; }
template <int N> __device__ __forceinline__ void pin(float (&d)[N]) {
#pragma unroll
  for (int i = 0; i < N; i++) asm volatile("" : "+f"(d[i]) :: "memory");
}
#define SPIN_GUARD(n) if (++(n) > SPIN_MAX) break

template <int NG> __device__ __forceinline__ void publish_stats(uint4* dst, const float* y, uint32_t tag, int lane) {
  float s0 = 0.f, s1 = 0.f;
#pragma unroll
  for (int g = 0; g < NG; g++) { s0 += y[4 * g] + y[4 * g + 1]; s1 += y[4 * g + 2] + y[4 * g + 3]; }
  s0 = quad_sum(s0); s1 = quad_sum(s1);
  const float m0 = s0 * (1.f / (8 * NG)), m1 = s1 * (1.f / (8 * NG));
  float q0 = 0.f, q1 = 0.f, q2 = 0.f, q3 = 0.f;
#pragma unroll
  for (int g = 0; g < NG; g++) {
    const float a = y[4 * g] - m0, b = y[4 * g + 1] - m0, c = y[4 * g + 2] - m1, d = y[4 * g + 3] - m1;
    q0 = fmaf(a, a, q0); q1 = fmaf(b, b, q1); q2 = fmaf(c, c, q2); q3 = fmaf(d, d, q3);
  }
  q0 = quad_sum(q0 + q1); q2 = quad_sum(q2 + q3);
  if ((lane & 3) == 0)
    stg4(dst + (lane >> 2), (__float_as_uint(s0) & ~1u) | tag, __float_as_uint(q0), __float_as_uint(s1), __float_as_uint(q2));
}

__device__ __forceinline__ void put72(uint4* slab, int j, int lane, const uint32_t* v) {
  uint4* p = slab + ((9 * j + 1) >> 1) * 32;
  if (j & 1) {
    stg2((char*)(p - 16) + lane * 8, nz(v[0]), v[1]);
#pragma unroll
    for (int i = 0; i < 4; i++) stg4(p + lane + i * 32, nz(v[4 * i + 2]), v[4 * i + 3], v[4 * i + 4], v[4 * i + 5]);
  } else {
#pragma unroll
    for (int i = 0; i < 4; i++) stg4(p + lane + i * 32, nz(v[4 * i]), v[4 * i + 1], v[4 * i + 2], v[4 * i + 3]);
    stg2((char*)(p + 4 * 32) + lane * 8, nz(v[16]), v[17]);
  }
}
__device__ __forceinline__ void zero_share(uint4* slab, int j, int lane) {
  uint4* p = slab + j * 144 + lane;
#pragma unroll
  for (int i = 0; i < 4; i++) stg4(p + i * 32, 0u, 0u, 0u, 0u);
  if (lane < 16) stg4(p + 128, 0u, 0u, 0u, 0u);
}

struct Maps { CUtensorMap m[5]; };

struct Ring {
  uint32_t st, ph;
  __device__ __forceinline__ void next() { if (++st == NST) { st = 0; ph ^= 1; } }
};

#define STAMP(i) do {} while (0)

__device__ __forceinline__ void tma_box(uint32_t dst, const CUtensorMap* m, int col, int row, uint32_t bar, uint32_t expect) {
  asm volatile("{\n.reg .pred e, h;\nelect.sync _|e, 0xffffffff;\nsetp.ne.and.u32 h, %5, 0, e;\n"
               "@h mbarrier.arrive.expect_tx.shared::cta.b64 _, [%2], %5;\n"
               "@e cp.async.bulk.tensor.2d.shared::cluster.global.mbarrier::complete_tx::bytes [%0], [%1, {%3, %4}], [%2];\n}"
               :: "r"(dst), "l"(m), "r"(bar), "r"(col), "r"(row), "r"(expect) : "memory");
}

__global__ void __launch_bounds__(384, 1) mega_kernel(
    const __grid_constant__ Maps maps, uint4* __restrict__ scr,
    const __nv_bfloat16* __restrict__ x_in, const __nv_bfloat16* __restrict__ wqkv, const __nv_bfloat16* __restrict__ wo,
    __nv_bfloat16* __restrict__ out) {
  extern __shared__ __align__(1024) uint8_t smem[];
  const uint32_t sb = (uint32_t)__cvta_generic_to_shared(smem);
  const uint32_t full0 = sb + BARS, empty0 = full0 + 8 * NST, rem_full = empty0 + 8 * NST, park_free = rem_full + 8, kv_free = park_free + 8;
  const int w = __shfl_sync(~0u, threadIdx.x >> 5, 0), lane = threadIdx.x & 31;
  const int t = blockIdx.x >> 3, j = blockIdx.x & 7;
  const int r = lane >> 2, q = lane & 3;
  auto load_rem = [&] {
    const int tid = threadIdx.x - 320;
#pragma unroll 1
    for (int p = 0; p < 4; p++) {
      const __nv_bfloat16* src = (p == 3 ? wo : wqkv + (p == 2 ? 0 : 576 * (p + 1))) + 72 * j + 64;
      const int pitch = p == 3 ? 576 : 1728;
#pragma unroll 1
      for (int k = tid; k < 576; k += 64) {
        const int s = k >> 4, rr = k & 7;
        cp16(sb + REM + p * 10240 + (s >> 3) * 2048 + ((k >> 3) & 1) * 1024 + rr * 128 + (((s & 7) ^ rr) << 4), src + k * pitch);
      }
    }
  };
  if (w == 8) {
    if (lane == 0) {
      for (int i = 0; i < NST; i++) { mbar_init(full0 + 8 * i, 1); mbar_init(empty0 + 8 * i, 8); }
      mbar_init(rem_full, 64); mbar_init(park_free, 8); mbar_init(kv_free, 8);
      asm volatile("fence.mbarrier_init.release.cluster;" ::: "memory");
    }
    __syncwarp();
#pragma unroll 1
    for (int b = 0; b < 2 * NST; b++)
      tma_box(sb + b * 8192, &maps.m[0], 72 * j + 576 + 576 * (b & 1), 64 * (b >> 1), full0 + (b >> 1) * 8, (b & 1) ? 0 : STAGE);
  } else if (w >= 10) {
    load_rem();
  } else {
    const int sl = w < 8 ? w : j, ch = w < 8 ? j : 8;
    const uint32_t* xr = (const uint32_t*)(x_in + (128 * t + 32 * (sl >> 1) + 2 * r + (sl & 1)) * 576 + 64 * ch + 2 * q);
    uint32_t v[16];
#pragma unroll
    for (int g = 0; g < 8; g++) { v[2 * g] = __ldg(xr + 4 * g); v[2 * g + 1] = __ldg(xr + 8 * 576 + 4 * g); }
    uint4* p = scr + OFF_X + (t * 8 + sl) * SLAB + 4 * ch * 32 + lane;
#pragma unroll
    for (int i = 0; i < 4; i++) stg4(p + i * 32, nz(v[4 * i]), v[4 * i + 1], nz(v[4 * i + 2]), v[4 * i + 3]);
    float y[32];
#pragma unroll
    for (int i = 0; i < 16; i++) { y[2 * i] = bf_lo(v[i]); y[2 * i + 1] = bf_hi(v[i]); }
    publish_stats<8>(scr + OFF_S + (t * 8 + sl) * 96 + ch * 8, y, 1u, lane);
  }
  __syncthreads();

  if (w >= 8) {
    asm volatile("setmaxnreg.dec.sync.aligned.u32 24;");
    if (w == 8) {
      Ring rg{0, 0};
      int b = 2 * NST;
#pragma unroll 1
      for (int seg = 0; seg < 34; seg++) {
        const int n = seg >= 17 ? seg - 17 : seg;
        int ma, mb, ca, cb, row = 0;
        if (n < 3) { ma = mb = n == 2; ca = 72 * j + (n == 0 ? 576 : 0); cb = ca + 576; }
        else if (n < 12) { ma = 3; mb = 2; ca = cb = 576 * j + 64 * (n - 3); }
        else { ma = mb = 4; ca = n == 12 ? 512 : ((j + 2 * n) & 7) * 64; cb = ((j + 2 * n + 1) & 7) * 64; row = 576 * j; }
        const bool zip = n == 0 || n == 3;
        const int nb = (n == 1 || n == 2 || n == 16) ? 9 : 18;
#pragma unroll 1
        for (; b < nb; b++) {
          const bool second = zip ? (b & 1) : b >= 9, last = b == nb - 1;
          const int kb = zip ? b >> 1 : second ? b - 9 : b;
          if (!(b & 1)) mbar_wait(empty0 + rg.st * 8, rg.ph);
          tma_box(sb + rg.st * STAGE + (b & 1) * 8192, &maps.m[second ? mb : ma], second ? cb : ca, row + 64 * kb, full0 + rg.st * 8,
                  (b & 1) ? 0 : last ? STAGE / 2 : STAGE);
          if ((b & 1) || last) rg.next();
        }
        b = 0;
      }
    } else if (w == 9) {
      const uint32_t stg = sb + HSTG + lane * 16;
#pragma unroll 1
      for (int layer = 0; layer < 2; layer++) {
        const uint32_t tag = 1 - layer;
        mbar_wait(park_free, layer);
        float s0 = 0.f, s1 = 0.f;
#pragma unroll 1
        for (int i = 0; i < 4; i++) {
          uint4* xb = scr + OFF_X + ((4 + layer) * 128 + t * 8 + j) * SLAB + (32 + i) * 32 + lane;
          float a[8];
          int n = 0;
          while (true) {
            const uint4* p = scr + OFF_P + (t * 64 + j) * SLAB + (32 + i) * 32 + lane;
#pragma unroll 1
            for (int s = 0; s < 8; s++) cp16(stg + s * 512, p + s * 8 * SLAB);
            cp16(stg + 4096, xb);
            cp_wait();
            uint32_t bad = 0;
#pragma unroll
            for (int e = 0; e < 8; e++) a[e] = 0.f;
#pragma unroll 1
            for (int s = 0; s < 9; s++) {
              uint32_t v[4];
              lds4(stg + s * 512, v);
              if (s < 8) bad |= v[0] ^ tag;
#pragma unroll
              for (int e = 0; e < 4; e++) { a[2 * e] += bf_lo(v[e]); a[2 * e + 1] += bf_hi(v[e]); }
            }
            if (__all_sync(~0u, (bad & 1u) == 0u)) break;
            __nanosleep(200);
            SPIN_GUARD(n);
          }
          uint32_t x[4];
#pragma unroll
          for (int e = 0; e < 4; e++) x[e] = pack_bf16(a[2 * e], a[2 * e + 1]);
          stg4(xb, 0u, 0u, 0u, 0u);
          if (layer == 0) {
            stg4(xb - 3 * 128 * SLAB, nz(x[0]), x[1], nz(x[2]), x[3]);
            sts4(stg + 4608 + i * 512, x);
            s0 += a[0] + a[1] + a[4] + a[5]; s1 += a[2] + a[3] + a[6] + a[7];
          } else {
            uint32_t* o = (uint32_t*)(out + (128 * t + 32 * (j >> 1) + 2 * r + (j & 1)) * 576 + 512 + 16 * i + 2 * q);
            o[0] = x[0]; o[8 * 576] = x[1]; o[4] = x[2]; o[8 * 576 + 4] = x[3];
          }
        }
        if (layer == 0) {
          s0 = quad_sum(s0); s1 = quad_sum(s1);
          const float m0 = s0 * (1.f / 64), m1 = s1 * (1.f / 64);
          float q0 = 0.f, q1 = 0.f;
#pragma unroll 1
          for (int i = 0; i < 4; i++) {
            uint32_t x[4];
            lds4(stg + 4608 + i * 512, x);
#pragma unroll
            for (int e = 0; e < 4; e++) {
              const float c = bf_lo(x[e]) - ((e & 1) ? m1 : m0), d = bf_hi(x[e]) - ((e & 1) ? m1 : m0);
              if (e & 1) q1 = fmaf(c, c, fmaf(d, d, q1)); else q0 = fmaf(c, c, fmaf(d, d, q0));
            }
          }
          q0 = quad_sum(q0); q1 = quad_sum(q1);
          if (q == 0) stg4(scr + OFF_S + (t * 8 + j) * 96 + 64 + r, __float_as_uint(s0) & ~1u, __float_as_uint(q0), __float_as_uint(s1), __float_as_uint(q1));
        }
      }
    } else {
#pragma unroll 1
      for (int layer = 0; layer < 2; layer++) {
        if (layer) { mbar_wait(park_free, 0); load_rem(); }
        asm volatile("cp.async.wait_all;\nfence.proxy.async.shared::cta;" ::: "memory");
        mbar_arrive(rem_full);
        if (layer) mbar_wait(kv_free, 0);
        if (t > 0) {
#pragma unroll 1
          for (int kv = 0; kv < 2; kv++) {
            uint4* hp = scr + OFF_H + ((layer * 128 + t * 8 + j) * 4 + (w - 10) * 2 + kv) * 96 + lane;
            uint32_t hl[12];
            int n = 0;
            while (true) {
              ldg4(hl, hp); ldg4(hl + 4, hp + 32); ldg4(hl + 8, hp + 64);
              if (__all_sync(~0u, hl[0] != 0u && hl[4] != 0u && hl[8] != 0u)) break;
              __nanosleep(100);
              SPIN_GUARD(n);
            }
#pragma unroll
            for (int g = 0; g < 9; g++) sts1(sb + KVS + kv * 20736 + (w - 10) * 10368 + r * 144 + g * 16 + q * 4, hl[g]);
#pragma unroll
            for (int i = 0; i < 3; i++) stg4(hp + i * 32, 0u, 0u, 0u, 0u);
          }
        }
        asm volatile("bar.arrive 1, 192;" ::: "memory");
      }
    }
  } else {
    asm volatile("setmaxnreg.inc.sync.aligned.u32 240;");
    Ring rg{0, 0};
    uint32_t prev = 0;
    uint32_t X[144];
    float rs0, rs1;
    uint32_t mean0, mean1;
    auto release = [&](uint32_t st) { if (lane == 0) mbar_arrive(empty0 + st * 8); };
    auto load_kb = [&](bool split, int kb, const uint4* src) {
#pragma unroll
      for (int k = 4 * kb; k < 4 * kb + 4; k++) {
        if (split && k % 9 == 4) { const char* lo = (const char*)(src + k * 32) - lane * 8; ldg2(X + 4 * k, lo); ldg2(X + 4 * k + 2, lo + 256); }
        else ldg4(X + 4 * k, src + k * 32);
      }
    };
    auto next_kb = [&](bool split, bool center, int kb, const uint4* src) {
      int n = 0;
      while (true) {
        bool ok = true;
#pragma unroll
        for (int k = 4 * kb; k < 4 * kb + 4; k++) { ok = ok && X[4 * k] != 0u; if (split && k % 9 == 4) ok = ok && X[4 * k + 2] != 0u; }
        if (__all_sync(~0u, ok)) break;
        SPIN_GUARD(n);
        load_kb(split, kb, src);
      }
      if (kb + GD < 9) load_kb(split, kb + GD, src);
      if (center) {
#pragma unroll
        for (int i = 16 * kb; i < 16 * kb + 16; i++) X[i] = sub_bf16x2(X[i], (i & 1) ? mean1 : mean0);
      }
    };
#pragma unroll 1
    for (int layer = 0; layer < 2; layer++) {
      const uint32_t tag = 1 - layer;
      uint4* const xbase = scr + OFF_X + (layer * 128 + t * 8 + w) * SLAB;
      auto begin_gather = [&](int kind) {
        uint32_t s[3][4];
        const uint4* p = scr + OFF_S + (kind * 128 + t * 8 + w) * 96 + q * 8 + r;
        int n = 0;
        s[2][0] = tag; s[2][1] = s[2][2] = s[2][3] = 0u;
        STAMP(kind * 8 + 0);
        while (true) {
          ldg4(s[0], p); ldg4(s[1], p + 32);
          if (kind == 0 && q == 0) ldg4(s[2], p + 64);
          if (__all_sync(~0u, ((s[0][0] ^ tag) | (s[1][0] ^ tag) | (s[2][0] ^ tag)) % 2u == 0u)) break;
          SPIN_GUARD(n);
        }
        STAMP(kind * 8 + 1);
#pragma unroll
        for (int kb = 0; kb < GD; kb++) load_kb(kind != 0, kb, xbase + kind * 256 * SLAB + lane);
        if (kind != 1) {
          const int ns = kind == 0 ? 3 : 2;
          float t0 = 0.f, t1 = 0.f;
#pragma unroll
          for (int i = 0; i < ns; i++) { t0 += __uint_as_float(s[i][0]); t1 += __uint_as_float(s[i][2]); }
          const float m0 = quad_sum(t0) * (1.f / 576), m1 = quad_sum(t1) * (1.f / 576);
          const float cnt = kind == 0 ? 64.f : 72.f;
          float v0 = 0.f, v1 = 0.f;
#pragma unroll
          for (int i = 0; i < ns; i++) {
            const float c = (i < 2 || q == 0) ? cnt : 0.f;
            const float d0 = fmaf(__uint_as_float(s[i][0]), 1.f / cnt, -m0), d1 = fmaf(__uint_as_float(s[i][2]), 1.f / cnt, -m1);
            v0 += fmaf(d0 * d0, c, __uint_as_float(s[i][1])); v1 += fmaf(d1 * d1, c, __uint_as_float(s[i][3]));
          }
          rs0 = rsqrtf(fmaf(quad_sum(v0), 1.f / 576, 1e-5f)); rs1 = rsqrtf(fmaf(quad_sum(v1), 1.f / 576, 1e-5f));
          mean0 = pack_bf16(m0, m0); mean1 = pack_bf16(m1, m1);
        }
      };
      auto box72 = [&](float (&a)[36], int part, int kb, int half) {
        const uint32_t base = sb + rg.st * STAGE + half * 8192;
        const uint64_t d0 = DESC_HI | ((base >> 4) + (((sb + REM + part * 10240 + (kb >> 1) * 2048 + (kb & 1) * 64 - base) >> 4) << 16));
#pragma unroll
        for (int i = 0; i < 4; i++) wgmma_rs_n72(a, X + 4 * (4 * kb + i), d0 - (uint64_t)(i * ((127u << 16) - 128u)), kb + i != 0);
      };
      auto solo72 = [&](float (&a)[36], int part, auto&& pre) {
#pragma unroll
        for (int kb = 0; kb < 9; kb++) {
          pre(kb);
          if (!(kb & 1)) mbar_wait(full0 + rg.st * 8, rg.ph);
          wg_fence();
          box72(a, part, kb, kb & 1);
          wg_commit();
          wg_wait<1>();
          if (kb > 0 && !(kb & 1)) release(prev);
          if ((kb & 1) || kb == 8) { prev = rg.st; rg.next(); }
        }
      };
      const uint32_t kvrow = sb + KVS + (w & 1) * 10368 + (16 * (w >> 1)) * 144;
      uint32_t Q[18];
      begin_gather(0);
      mbar_wait(rem_full, layer);
      {
        float acc[36], acc2[36];
#pragma unroll
        for (int kb = 0; kb < 9; kb++) {
          next_kb(false, true, kb, xbase + lane);
          mbar_wait(full0 + rg.st * 8, rg.ph);
          wg_fence();
          box72(acc, 0, kb, 0); box72(acc2, 1, kb, 1);
          wg_commit();
          wg_wait<1>();
          if (kb > 0) release(prev);
          if (kb == 1) sts4(sb + PARK + w * 512 + lane * 16, X);
          prev = rg.st; rg.next();
        }
        wg_wait<0>();
        release(prev);
        STAMP(2);
        auto put_kv = [&](float (&a)[36], int part) {
          pin(a);
          uint32_t hl[9];
          const uint32_t dst = kvrow + part * 20736 + (8 + r) * 144 + q * 4;
#pragma unroll
          for (int g = 0; g < 9; g++) {
            hl[g] = pack_bf16(a[4 * g + 2] * rs1, a[4 * g + 3] * rs1);
            sts1(dst + g * 16, pack_bf16(a[4 * g] * rs0, a[4 * g + 1] * rs0)); sts1(dst + 8 * 144 + g * 16, hl[g]);
          }
          if (w >= 6 && t < 15) {
            uint4* hp = scr + OFF_H + ((layer * 128 + (t + 1) * 8 + j) * 4 + (w & 1) * 2 + part) * 96 + lane;
            stg4(hp, nz(hl[0]), hl[1], hl[2], hl[3]); stg4(hp + 32, nz(hl[4]), hl[5], hl[6], hl[7]); stg4(hp + 64, nz(hl[8]), 0u, 0u, 0u);
          }
        };
        put_kv(acc2, 1);
        lds4(sb + PARK + w * 512 + lane * 16, X);
        put_kv(acc, 0);
        if (w < 4) asm volatile("bar.arrive 2, 256;" ::: "memory");
        solo72(acc, 2, [](int) {});
        wg_wait<0>();
        release(prev);
        pin(acc);
        STAMP(3);
#pragma unroll
        for (int g = 0; g < 9; g++) {
          Q[2 * g] = pack_bf16(acc[4 * g] * rs0, acc[4 * g + 1] * rs0); Q[2 * g + 1] = pack_bf16(acc[4 * g + 2] * rs1, acc[4 * g + 3] * rs1);
        }
      }
      if (w < 4) asm volatile("bar.sync 1, 192;" ::: "memory");
      else asm volatile("bar.sync 2, 256;" ::: "memory");
      STAMP(4);
      uint32_t O[18];
      {
        const bool edge = (t == 0 && w < 2);
        uint32_t row[3];
#pragma unroll
        for (int nt = 0; nt < 3; nt++) row[nt] = kvrow + (8 * nt + (lane & 7)) * 144;
        if (edge) row[0] = sb + KVS + 8 * 144;
        const uint32_t rlast = ((lane >> 3) == 0 ? row[0] : (lane >> 3) == 1 ? row[1] : row[2]) + 128;
        uint32_t K[3][9], V[3][9], dummy;
#pragma unroll
        for (int nt = 0; nt < 3; nt++) {
          ldsm4(row[nt] + (lane >> 3) * 16, K[nt][0], K[nt][1], K[nt][2], K[nt][3]);
          ldsm4(row[nt] + 64 + (lane >> 3) * 16, K[nt][4], K[nt][5], K[nt][6], K[nt][7]);
        }
        ldsm4(rlast, K[0][8], K[1][8], K[2][8], dummy);
#pragma unroll
        for (int nt = 0; nt < 3; nt++) {
          ldsm4t(row[nt] + 20736 + (lane >> 3) * 16, V[nt][0], V[nt][1], V[nt][2], V[nt][3]);
          ldsm4t(row[nt] + 20736 + 64 + (lane >> 3) * 16, V[nt][4], V[nt][5], V[nt][6], V[nt][7]);
        }
        ldsm4t(rlast + 20736, V[0][8], V[1][8], V[2][8], dummy);
        const bool up0 = 2 * q > r, up1 = 2 * q + 1 > r;
        const float sc = 0.23570226039551584f * 1.4426950408889634f;
        const float neg = -1e9f * 1.4426950408889634f;
        float Of[9][4];
#pragma unroll
        for (int h = 0; h < 4; h++) {
          const uint32_t a0 = q >= h ? Q[4 * h] : 0u, a1 = q >= h ? Q[4 * h + 1] : 0u;
          const uint32_t a4 = q <= h ? Q[4 * h + 4] : 0u, a5 = q <= h ? Q[4 * h + 5] : 0u;
          float S[3][4];
#pragma unroll
          for (int nt = 0; nt < 3; nt++) {
            S[nt][0] = S[nt][1] = S[nt][2] = S[nt][3] = 0.f;
            mma16(S[nt], a0, a1, Q[4 * h + 2], Q[4 * h + 3], K[nt][2 * h], K[nt][2 * h + 1]);
            mma8(S[nt], a4, a5, K[nt][2 * h + 2]);
          }
          float s00 = (up0 ? S[0][0] : S[1][0]) * sc, s01 = (up1 ? S[0][1] : S[1][1]) * sc;
          const float s10 = (up0 ? S[1][2] : S[2][2]) * sc, s11 = (up1 ? S[1][3] : S[2][3]) * sc;
          if (edge && up0) s00 = neg;
          if (edge && up1) s01 = neg;
          const float m0 = quad_max(fmaxf(s00, s01)), m1 = quad_max(fmaxf(s10, s11));
          float p00 = ex2(s00 - m0), p01 = ex2(s01 - m0), p10 = ex2(s10 - m1), p11 = ex2(s11 - m1);
          const float i0 = rcp(quad_sum(p00 + p01)), i1 = rcp(quad_sum(p10 + p11));
          p00 *= i0; p01 *= i0; p10 *= i1; p11 *= i1;
          const uint32_t pa = pack_bf16(up0 ? p00 : 0.f, up1 ? p01 : 0.f), pb = pack_bf16(up0 ? 0.f : p00, up1 ? 0.f : p01);
          const uint32_t pc = pack_bf16(up0 ? p10 : 0.f, up1 ? p11 : 0.f), pd = pack_bf16(up0 ? 0.f : p10, up1 ? 0.f : p11);
#pragma unroll
          for (int gi = 0; gi < 3; gi++) {
            const int g = 2 * h + gi;
            float o[4] = {0.f, 0.f, 0.f, 0.f};
            mma16(o, pa, 0u, pb, pc, V[0][g], V[1][g]);
            mma8(o, 0u, pd, V[2][g]);
#pragma unroll
            for (int e = 0; e < 4; e++) Of[g][e] = (gi == 0 && h > 0 && q < h) ? Of[g][e] : o[e];
          }
        }
#pragma unroll
        for (int g = 0; g < 9; g++) { O[2 * g] = pack_bf16(Of[g][0], Of[g][1]); O[2 * g + 1] = pack_bf16(Of[g][2], Of[g][3]); }
      }
      put72(xbase + 256 * SLAB, j, lane, O);
      if (q == 0) stg4(scr + OFF_S + (128 + t * 8 + w) * 96 + j * 8 + r, tag, 0u, 0u, 0u);
      {
        uint32_t res[18];
        const char* p = (const char*)(xbase + lane) + ((9 * j) >> 1) * 512 + (j & 1) * 8;
#pragma unroll
        for (int g = 0; g < 9; g++) ldg2(res + 2 * g, p + (g >> 1) * 512 + ((g & 1) ? ((j & 1) ? 504 : 8) : 0));
        begin_gather(1);
        float acc[36];
        solo72(acc, 3, [&](int kb) { next_kb(true, false, kb, xbase + 256 * SLAB + lane); });
        wg_wait<0>();
        release(prev);
        pin(acc);
        STAMP(10);
#pragma unroll
        for (int i = 0; i < 18; i++) {
          acc[2 * i] += bf_lo(res[i]); acc[2 * i + 1] += bf_hi(res[i]);
          res[i] = pack_bf16(acc[2 * i], acc[2 * i + 1]);
        }
        put72(xbase + 512 * SLAB, j, lane, res);
        publish_stats<9>(scr + OFF_S + (256 + t * 8 + w) * 96 + j * 8, acc, tag, lane);
      }
      float aA[32], aB[32];
      const uint32_t hp = sb + PARK + w * 512 + lane * 16;
      begin_gather(2);
#pragma unroll
      for (int kb = 0; kb < 9; kb++) {
        next_kb(true, true, kb, xbase + 512 * SLAB + lane);
        mbar_wait(full0 + rg.st * 8, rg.ph);
        const uint64_t desc = DESC_HI | ((sb + rg.st * STAGE) >> 4);
        wg_fence();
#pragma unroll
        for (int i = 0; i < 4; i++) wgmma_rs_n64(aA, X + 4 * (4 * kb + i), desc + i * 128, kb + i != 0);
#pragma unroll
        for (int i = 0; i < 4; i++) wgmma_rs_n64(aB, X + 4 * (4 * kb + i), desc + 512 + i * 128, kb + i != 0);
        wg_commit();
        wg_wait<1>();
        if (kb > 0) release(prev);
        prev = rg.st; rg.next();
      }
      zero_share(xbase, j, lane);
      zero_share(xbase + 256 * SLAB, j, lane);
      wg_wait<0>();
      STAMP(20);
      auto pack8 = [&](float (&a)[32], int p, uint32_t* o) {
#pragma unroll
        for (int e = 0; e < 8; e++) asm volatile("" : "+f"(a[8 * p + e]) :: "memory");
#pragma unroll
        for (int e = 0; e < 4; e++) o[e] = pack_bf16(a[8 * p + 2 * e], a[8 * p + 2 * e + 1]);
      };
      auto geglu8 = [&](int p, uint32_t* u) {
#pragma unroll
        for (int e = 0; e < 8; e++) asm volatile("" : "+f"(aB[8 * p + e]) :: "memory");
        float h[8];
#pragma unroll
        for (int e = 0; e < 8; e++) {
          const float rs = (e & 2) ? rs1 : rs0;
          const float g = aB[8 * p + e] * rs;
          const float th = tanh_ap(g * fmaf(g * g, 0.7978845608028654f * 0.044715f, 0.7978845608028654f));
          const float gu = g * (0.5f * rs) * ((e & 1) ? bf_hi(u[e >> 1]) : bf_lo(u[e >> 1]));
          h[e] = fmaf(gu, th, gu);
        }
#pragma unroll
        for (int e = 0; e < 4; e++) u[e] = pack_bf16(h[2 * e], h[2 * e + 1]);
      };
      auto box = [&](int b) {
        const int kb = b < 9 ? b : b - 9;
        if (!(b & 1)) mbar_wait(full0 + rg.st * 8, rg.ph);
        const uint64_t desc = DESC_HI | ((sb + rg.st * STAGE + (b & 1) * 8192) >> 4);
        wg_fence();
#pragma unroll
        for (int i = 0; i < 4; i++) {
          if (b < 9) wgmma_rs_n64(aA, X + 4 * (4 * kb + i), desc + i * 128, kb + i != 0);
          else wgmma_rs_n64(aB, X + 4 * (4 * kb + i), desc + i * 128, kb + i != 0);
        }
        wg_commit();
        wg_wait<1>();
        if (b & 1) { prev = rg.st; rg.next(); } else release(prev);
      };
      auto step = [&](int st, auto&& filler) { box(2 * st); filler(); box(2 * st + 1); };
#pragma unroll
      for (int p = 0; p < 4; p++) { uint32_t o[4]; pack8(aA, p, o); sts4(hp + p * 4096, o); }
      box(0);
#pragma unroll 1
      for (int c = 1;; c++) {
        const uint32_t hc = hp + c * 4 * 4096;
#pragma unroll
        for (int b = 1; b < 18; b++) {
          if ((b & 1) && b < 8) { uint32_t o[4]; const uint32_t a = hc - (4 - (b >> 1)) * 4096; lds4(a, o); geglu8(b >> 1, o); sts4(a, o); }
          if ((b & 1) && b > 10 && c < 8) { uint32_t o[4]; pack8(aA, (b - 11) >> 1, o); sts4(hc + ((b - 11) >> 1) * 4096, o); }
          box(b);
        }
        if (c == 8) break;
        box(0);
      }
      wg_wait<0>();
      STAMP(21);
#pragma unroll
      for (int s = 0; s < 32; s++) lds4(hp + s * 4096, X + 4 * s);
#pragma unroll
      for (int p = 0; p < 4; p++) pack8(aA, p, X + 128 + 4 * p);
#pragma unroll
      for (int st = 0; st < 4; st++) step(st, [&] { geglu8(st, X + 128 + 4 * st); });
      if (lane == 0) mbar_arrive(park_free);
      uint4* const pw = scr + OFF_P + ((t * 8 + j) * 8 + w) * SLAB + lane;
      const uint4* const pr = scr + OFF_P + (t * 64 + w) * SLAB + 4 * j * 32 + lane;
      auto put_part = [&](float (&a)[32], int p, int chunk) {
        uint32_t o[4];
        pack8(a, p, o);
        stg4(pw + (chunk * 4 + p) * 32, (o[0] & ~1u) | tag, o[1], o[2], o[3]);
      };
      auto slot = [&](int p) { return hp + (p < 4 ? (p - 1) * 16384 : KVS - PARK + (p - 4) * 16384); };
      auto fetch = [&](int p) {
        if (p > 0) {
#pragma unroll
          for (int i = 0; i < 4; i++) cp16(slot(p) + i * 4096, pr + ((j - p) & 7) * 8 * SLAB + i * 32);
        }
      };
#pragma unroll 1
      for (int sp = 0;; sp++) {
        const int ca = sp == 0 ? 8 : ((j + 2 * sp) & 7), cb = (j + 2 * sp + 1) & 7;
#pragma unroll
        for (int st = 4; st < 9; st++) step(st, [&] {
          if (st == 5 || st == 6) { put_part(aA, 2 * (st - 5), ca); put_part(aA, 2 * (st - 5) + 1, ca); }
          if (st == 8) fetch(2 * sp - 1); });
        if (sp == 3) break;
#pragma unroll
        for (int st = 0; st < 4; st++) step(st, [&] {
          if (st < 2) { put_part(aB, 2 * st, cb); put_part(aB, 2 * st + 1, cb); }
          if (st == 3) fetch(2 * sp); });
      }
      uint4* const xb = xbase + 512 * SLAB + 4 * j * 32;
      auto load_p = [&](int p, uint32_t* d) {
#pragma unroll
        for (int i = 0; i < 4; i++) ldg4(d + 4 * i, pr + ((j - p) & 7) * 8 * SLAB + i * 32);
      };
#pragma unroll
      for (int st = 0; st < 4; st++) step(st, [&] {
        if (st == 0) {
#pragma unroll
          for (int p = 0; p < 4; p++) put_part(aB, p, (j + 7) & 7);
        }
        if (st == 1) {
#pragma unroll
          for (int i = 0; i < 4; i++) {
            const bool split = j == 2 * i + 1;
            const char* l = (const char*)(xb + i * 32) + (split ? lane * 8 : lane * 16);
            ldg2(X + 4 * i, l); ldg2(X + 4 * i + 2, l + (split ? 256 : 8));
          }
          load_p(6, X + 16);
        }
        if (st == 3) load_p(7, X + 32); });
      {
        mbar_wait(full0 + rg.st * 8, rg.ph);
        const uint64_t desc = DESC_HI | ((sb + rg.st * STAGE) >> 4);
        wg_fence();
#pragma unroll
        for (int i = 0; i < 4; i++) wgmma_rs_n64(aA, X + 4 * (32 + i), desc + i * 128, 1);
        wg_commit();
        wg_wait<1>(); release(prev);
        prev = rg.st; rg.next();
        cp_wait();
        wg_wait<0>(); release(prev);
        pin(aA);
      }
      STAMP(22);
      {
        const uint32_t eye = r == 2 * q ? 0x3f80u : r == 2 * q + 1 ? 0x3f800000u : 0u;
        auto add_p = [&](int p, uint32_t* d) {
          int n = 0;
          while (!__all_sync(~0u, (((d[0] ^ tag) | (d[4] ^ tag) | (d[8] ^ tag) | (d[12] ^ tag)) & 1u) == 0u)) { SPIN_GUARD(n); load_p(p, d); }
#pragma unroll
          for (int g = 0; g < 8; g++) mma8(aA + 4 * g, d[2 * g], d[2 * g + 1], eye);
        };
#pragma unroll
        for (int p = 1; p < 6; p++)
#pragma unroll
          for (int i = 0; i < 4; i++) lds4(slot(p) + i * 4096, X + 32 + 16 * p + 4 * i);
#pragma unroll
        for (int g = 0; g < 8; g++) mma8(aA + 4 * g, X[2 * g], X[2 * g + 1], eye);
#pragma unroll
        for (int p = 1; p < 6; p++) add_p(p, X + 32 + 16 * p);
        add_p(6, X + 16); add_p(7, X + 32);
        uint32_t res[16];
#pragma unroll
        for (int i = 0; i < 16; i++) res[i] = pack_bf16(aA[2 * i], aA[2 * i + 1]);
        if (layer == 0) {
          uint4* p = xbase + 128 * SLAB + 4 * j * 32 + lane;
#pragma unroll
          for (int i = 0; i < 4; i++) stg4(p + i * 32, nz(res[4 * i]), res[4 * i + 1], nz(res[4 * i + 2]), res[4 * i + 3]);
          publish_stats<8>(scr + OFF_S + (t * 8 + w) * 96 + j * 8, aA, 0u, lane);
          if (lane == 0) mbar_arrive(kv_free);
        } else {
          uint32_t* o = (uint32_t*)(out + (128 * t + 32 * (w >> 1) + 2 * r + (w & 1)) * 576 + 64 * j + 2 * q);
#pragma unroll
          for (int g = 0; g < 8; g++) { o[4 * g] = res[2 * g]; o[8 * 576 + 4 * g] = res[2 * g + 1]; }
        }
#pragma unroll
        for (int i = 0; i < 4; i++) stg4(xb + lane + i * 32, 0u, 0u, 0u, 0u);
      }
      STAMP(23);
    }
  }
}

typedef CUresult (*EncodeFn)(CUtensorMap*, CUtensorMapDataType, cuuint32_t, void*, const cuuint64_t*, const cuuint64_t*,
                             const cuuint32_t*, const cuuint32_t*, CUtensorMapInterleave, CUtensorMapSwizzle,
                             CUtensorMapL2promotion, CUtensorMapFloatOOBfill);

CUtensorMap make_map(EncodeFn f, const void* p, uint64_t cols, uint64_t rows) {
  CUtensorMap m;
  cuuint64_t dims[2] = {cols, rows};
  cuuint64_t str[1] = {cols * 2};
  cuuint32_t box[2] = {64, 64};
  cuuint32_t es[2] = {1, 1};
  f(&m, CU_TENSOR_MAP_DATA_TYPE_BFLOAT16, 2, const_cast<void*>(p), dims, str, box, es, CU_TENSOR_MAP_INTERLEAVE_NONE,
    CU_TENSOR_MAP_SWIZZLE_128B, CU_TENSOR_MAP_L2_PROMOTION_NONE, CU_TENSOR_MAP_FLOAT_OOB_FILL_NONE);
  return m;
}

}

extern "C" void kernel_launch(void* const* d_in, const int* in_sizes, int n_in, void* d_out, int out_size) {
  void* fn = nullptr;
  cudaDriverEntryPointQueryResult qr;
  cudaGetDriverEntryPoint("cuTensorMapEncodeTiled", &fn, cudaEnableDefault, &qr);
  EncodeFn enc = (EncodeFn)fn;
  Maps maps;
  maps.m[0] = make_map(enc, d_in[1], 1728, 576); maps.m[1] = make_map(enc, d_in[2], 576, 576);
  maps.m[2] = make_map(enc, d_in[4], 4608, 576); maps.m[3] = make_map(enc, d_in[5], 4608, 576); maps.m[4] = make_map(enc, d_in[6], 576, 4608);
  void* scr = nullptr;
  cudaGetSymbolAddress(&scr, g_scratch);
  cudaFuncSetAttribute(mega_kernel, cudaFuncAttributeMaxDynamicSharedMemorySize, SMEM_BYTES);
  mega_kernel<<<128, 384, SMEM_BYTES>>>(maps, (uint4*)scr, (const __nv_bfloat16*)d_in[0], (const __nv_bfloat16*)d_in[1],
                                        (const __nv_bfloat16*)d_in[2], (__nv_bfloat16*)d_out);
}
```

```cpp
#include <cuda_runtime.h>
#include <cuda.h>
#include <cuda_bf16.h>
#include <stdint.h>

#define TRACE 0
#define FPOS 2
#define W2 0

namespace {

constexpr int NST = 6;
constexpr int STAGE = 16384;
constexpr int PARK = NST * STAGE;
constexpr int REM = PARK + 49152;
constexpr int KVS = REM + 40960;
constexpr int HSTG = KVS + 32768;
constexpr int BARS = KVS + 41472;
constexpr int TRC = BARS + 256;
constexpr int SMEM_BYTES = TRC + (TRACE ? 512 : 0);
static_assert(BARS >= PARK + 131072, "barriers overlap park");
static_assert(SMEM_BYTES <= 232448, "smem");

constexpr int SLAB = 36 * 32;
constexpr int SPIN_MAX = 1 << 17;
constexpr int GD = 3;
constexpr int OFF_X = 0;
constexpr int OFF_P = OFF_X + 6 * 128 * SLAB;
constexpr int OFF_S = OFF_P + 8 * 128 * SLAB;
constexpr int OFF_H = OFF_S + 3 * 128 * 96;
constexpr int SCRATCH = OFF_H + 2 * 128 * 384;

}

__device__ uint4 g_scratch[SCRATCH];

namespace {

constexpr uint64_t DESC_HI = 0x4000004000000000ull;
__device__ __forceinline__ void wgmma_rs_n64(float (&d)[32], const uint32_t* a, uint64_t desc, int scale_d) {
  asm volatile("{\n.reg .pred p;\nsetp.ne.b32 p, %37, 0;\n"
    "wgmma.mma_async.sync.aligned.m64n64k16.f32.bf16.bf16 "
    "{%0, %1, %2, %3, %4, %5, %6, %7, %8, %9, %10, %11, %12, %13, %14, %15, %16, %17, %18, %19, %20, %21, %22, %23, %24, %25, %26, %27, %28, %29, %30, %31}, "
    "{%32, %33, %34, %35}, %36, p, 1, 1, 1;\n}\n"
    : "+f"(d[0]), "+f"(d[1]), "+f"(d[2]), "+f"(d[3]), "+f"(d[4]), "+f"(d[5]), "+f"(d[6]), "+f"(d[7]), "+f"(d[8]), "+f"(d[9]), "+f"(d[10]), "+f"(d[11]), "+f"(d[12]), "+f"(d[13]), "+f"(d[14]), "+f"(d[15]), "+f"(d[16]), "+f"(d[17]), "+f"(d[18]), "+f"(d[19]), "+f"(d[20]), "+f"(d[21]), "+f"(d[22]), "+f"(d[23]), "+f"(d[24]), "+f"(d[25]), "+f"(d[26]), "+f"(d[27]), "+f"(d[28]), "+f"(d[29]), "+f"(d[30]), "+f"(d[31])
    : "r"(a[0]), "r"(a[1]), "r"(a[2]), "r"(a[3]), "l"(desc), "r"(scale_d));
}
__device__ __forceinline__ void wgmma_rs_n72(float (&d)[36], const uint32_t* a, uint64_t desc, int scale_d) {
  asm volatile("{\n.reg .pred p;\nsetp.ne.b32 p, %41, 0;\n"
    "wgmma.mma_async.sync.aligned.m64n72k16.f32.bf16.bf16 "
    "{%0, %1, %2, %3, %4, %5, %6, %7, %8, %9, %10, %11, %12, %13, %14, %15, %16, %17, %18, %19, %20, %21, %22, %23, %24, %25, %26, %27, %28, %29, %30, %31, %32, %33, %34, %35}, "
    "{%36, %37, %38, %39}, %40, p, 1, 1, 1;\n}\n"
    : "+f"(d[0]), "+f"(d[1]), "+f"(d[2]), "+f"(d[3]), "+f"(d[4]), "+f"(d[5]), "+f"(d[6]), "+f"(d[7]), "+f"(d[8]), "+f"(d[9]), "+f"(d[10]), "+f"(d[11]), "+f"(d[12]), "+f"(d[13]), "+f"(d[14]), "+f"(d[15]), "+f"(d[16]), "+f"(d[17]), "+f"(d[18]), "+f"(d[19]), "+f"(d[20]), "+f"(d[21]), "+f"(d[22]), "+f"(d[23]), "+f"(d[24]), "+f"(d[25]), "+f"(d[26]), "+f"(d[27]), "+f"(d[28]), "+f"(d[29]), "+f"(d[30]), "+f"(d[31]), "+f"(d[32]), "+f"(d[33]), "+f"(d[34]), "+f"(d[35])
    : "r"(a[0]), "r"(a[1]), "r"(a[2]), "r"(a[3]), "l"(desc), "r"(scale_d));
}

__device__ __forceinline__ void mbar_init(uint32_t a, uint32_t c) { asm volatile("mbarrier.init.shared::cta.b64 [%0], %1;" :: "r"(a), "r"(c)); }
__device__ __forceinline__ void mbar_arrive(uint32_t a) { asm volatile("mbarrier.arrive.shared::cta.b64 _, [%0];" :: "r"(a) : "memory"); }
__device__ __forceinline__ void mbar_wait(uint32_t a, uint32_t ph) {
  asm volatile("{\n.reg .pred p;\n.reg .u32 n;\n"
               "mbarrier.try_wait.parity.shared::cta.b64 p, [%0], %1;\n@p bra D;\n"
               "mov.u32 n, 0;\n"
               "W: mbarrier.try_wait.parity.shared::cta.b64 p, [%0], %1;\n@p bra D;\n"
               "add.u32 n, n, 1;\nsetp.lt.u32 p, n, 4194304;\n@p bra W;\ntrap;\nD:\n}" :: "r"(a), "r"(ph) : "memory");
}
__device__ __forceinline__ void wg_fence() { asm volatile("wgmma.fence.sync.aligned;" ::: "memory"); }
__device__ __forceinline__ void wg_commit() { asm volatile("wgmma.commit_group.sync.aligned;" ::: "memory"); }
template <int N> __device__ __forceinline__ void wg_wait() { asm volatile("wgmma.wait_group.sync.aligned %0;" :: "n"(N) : "memory"); }
__device__ __forceinline__ float tanh_ap(float x) { float y; asm("tanh.approx.f32 %0, %1;" : "=f"(y) : "f"(x)); return y; }
__device__ __forceinline__ float ex2(float x) { float y; asm("ex2.approx.ftz.f32 %0, %1;" : "=f"(y) : "f"(x)); return y; }
__device__ __forceinline__ uint32_t pack_bf16(float lo, float hi) { uint32_t r; asm("cvt.rn.bf16x2.f32 %0, %1, %2;" : "=r"(r) : "f"(hi), "f"(lo)); return r; }
__device__ __forceinline__ float bf_lo(uint32_t v) { return __uint_as_float(v << 16); }
__device__ __forceinline__ float bf_hi(uint32_t v) { return __uint_as_float(v & 0xffff0000u); }
__device__ __forceinline__ uint32_t sub_bf16x2(uint32_t a, uint32_t b) { uint32_t r; asm("sub.rn.bf16x2 %0, %1, %2;" : "=r"(r) : "r"(a), "r"(b)); return r; }
__device__ __forceinline__ uint32_t mul_bf16x2(uint32_t a, uint32_t b) { uint32_t r; asm("mul.rn.bf16x2 %0, %1, %2;" : "=r"(r) : "r"(a), "r"(b)); return r; }
__device__ __forceinline__ uint32_t nz(uint32_t w) { return w == 0u ? 0x8000u : w; }

__device__ __forceinline__ void ldg4(uint32_t* d, const uint4* p) {
  asm volatile("ld.relaxed.gpu.global.v4.b32 {%0,%1,%2,%3}, [%4];" : "=r"(d[0]), "=r"(d[1]), "=r"(d[2]), "=r"(d[3]) : "l"(p) : "memory");
}
__device__ __forceinline__ void ldg2(uint32_t* d, const void* p) {
  asm volatile("ld.relaxed.gpu.global.v2.b32 {%0,%1}, [%2];" : "=r"(d[0]), "=r"(d[1]) : "l"(p) : "memory");
}
__device__ __forceinline__ void stg4(uint4* p, uint32_t a, uint32_t b, uint32_t c, uint32_t d) {
  asm volatile("st.relaxed.gpu.global.v4.b32 [%0], {%1,%2,%3,%4};" :: "l"(p), "r"(a), "r"(b), "r"(c), "r"(d) : "memory");
}
__device__ __forceinline__ void stg2(void* p, uint32_t a, uint32_t b) {
  asm volatile("st.relaxed.gpu.global.v2.b32 [%0], {%1,%2};" :: "l"(p), "r"(a), "r"(b) : "memory");
}
__device__ __forceinline__ void sts4(uint32_t a, const uint32_t* o) { asm volatile("st.shared.v4.b32 [%0], {%1,%2,%3,%4};" :: "r"(a), "r"(o[0]), "r"(o[1]), "r"(o[2]), "r"(o[3]) : "memory"); }
__device__ __forceinline__ void lds4(uint32_t a, uint32_t* o) { asm volatile("ld.shared.v4.b32 {%0,%1,%2,%3}, [%4];" : "=r"(o[0]), "=r"(o[1]), "=r"(o[2]), "=r"(o[3]) : "r"(a) : "memory"); }
__device__ __forceinline__ void cp16(uint32_t dst, const void* src) { asm volatile("cp.async.cg.shared.global [%0], [%1], 16;" :: "r"(dst), "l"(src) : "memory"); }
__device__ __forceinline__ void cp_wait() { asm volatile("cp.async.wait_all;" ::: "memory"); }
__device__ __forceinline__ float rcp(float x) { float y; asm("rcp.approx.ftz.f32 %0, %1;" : "=f"(y) : "f"(x)); return y; }
__device__ __forceinline__ void sts1(uint32_t a, uint32_t v) { asm volatile("st.shared.b32 [%0], %1;" :: "r"(a), "r"(v) : "memory"); }
__device__ __forceinline__ void ldsm4(uint32_t a, uint32_t& r0, uint32_t& r1, uint32_t& r2, uint32_t& r3) {
  asm volatile("ldmatrix.sync.aligned.m8n8.x4.shared.b16 {%0,%1,%2,%3}, [%4];" : "=r"(r0), "=r"(r1), "=r"(r2), "=r"(r3) : "r"(a) : "memory");
}
__device__ __forceinline__ void ldsm4t(uint32_t a, uint32_t& r0, uint32_t& r1, uint32_t& r2, uint32_t& r3) {
  asm volatile("ldmatrix.sync.aligned.m8n8.x4.trans.shared.b16 {%0,%1,%2,%3}, [%4];" : "=r"(r0), "=r"(r1), "=r"(r2), "=r"(r3) : "r"(a) : "memory");
}
__device__ __forceinline__ void mma16(float* c, uint32_t a0, uint32_t a1, uint32_t a2, uint32_t a3, uint32_t b0, uint32_t b1) {
  asm("mma.sync.aligned.m16n8k16.row.col.f32.bf16.bf16.f32 {%0,%1,%2,%3}, {%4,%5,%6,%7}, {%8,%9}, {%0,%1,%2,%3};"
    : "+f"(c[0]), "+f"(c[1]), "+f"(c[2]), "+f"(c[3]) : "r"(a0), "r"(a1), "r"(a2), "r"(a3), "r"(b0), "r"(b1));
}
__device__ __forceinline__ void mma8(float* c, uint32_t a0, uint32_t a1, uint32_t b0) {
  asm("mma.sync.aligned.m16n8k8.row.col.f32.bf16.bf16.f32 {%0,%1,%2,%3}, {%4,%5}, {%6}, {%0,%1,%2,%3};"
    : "+f"(c[0]), "+f"(c[1]), "+f"(c[2]), "+f"(c[3]) : "r"(a0), "r"(a1), "r"(b0));
}
__device__ __forceinline__ float quad_sum(float v) { v += __shfl_xor_sync(~0u, v, 1); v += __shfl_xor_sync(~0u, v, 2); return v; }
__device__ __forceinline__ float quad_max(float v) { v = fmaxf(v, __shfl_xor_sync(~0u, v, 1)); v = fmaxf(v, __shfl_xor_sync(~0u, v, 2)); return v; }
template <int N> __device__ __forceinline__ void pin(float (&d)[N]) {
#pragma unroll
  for (int i = 0; i < N; i++) asm volatile("" : "+f"(d[i]) :: "memory");
}
#define SPIN_GUARD(n) if (++(n) > SPIN_MAX) break

template <int NG> __device__ __forceinline__ void publish_stats(uint4* dst, const float* y, uint32_t tag, int lane) {
  float s0 = 0.f, s1 = 0.f;
#pragma unroll
  for (int g = 0; g < NG; g++) { s0 += y[4 * g] + y[4 * g + 1]; s1 += y[4 * g + 2] + y[4 * g + 3]; }
  s0 = quad_sum(s0); s1 = quad_sum(s1);
  const float m0 = s0 * (1.f / (8 * NG)), m1 = s1 * (1.f / (8 * NG));
  float q0 = 0.f, q1 = 0.f, q2 = 0.f, q3 = 0.f;
#pragma unroll
  for (int g = 0; g < NG; g++) {
    const float a = y[4 * g] - m0, b = y[4 * g + 1] - m0, c = y[4 * g + 2] - m1, d = y[4 * g + 3] - m1;
    q0 = fmaf(a, a, q0); q1 = fmaf(b, b, q1); q2 = fmaf(c, c, q2); q3 = fmaf(d, d, q3);
  }
  q0 = quad_sum(q0 + q1); q2 = quad_sum(q2 + q3);
  if ((lane & 3) == 0)
    stg4(dst + (lane >> 2), (__float_as_uint(s0) & ~1u) | tag, __float_as_uint(q0), __float_as_uint(s1), __float_as_uint(q2));
}

__device__ __forceinline__ void put72(uint4* slab, int j, int lane, const uint32_t* v) {
  uint4* p = slab + ((9 * j + 1) >> 1) * 32;
  if (j & 1) {
    stg2((char*)(p - 16) + lane * 8, nz(v[0]), v[1]);
#pragma unroll
    for (int i = 0; i < 4; i++) stg4(p + lane + i * 32, nz(v[4 * i + 2]), v[4 * i + 3], v[4 * i + 4], v[4 * i + 5]);
  } else {
#pragma unroll
    for (int i = 0; i < 4; i++) stg4(p + lane + i * 32, nz(v[4 * i]), v[4 * i + 1], v[4 * i + 2], v[4 * i + 3]);
    stg2((char*)(p + 4 * 32) + lane * 8, nz(v[16]), v[17]);
  }
}
__device__ __forceinline__ void zero_share(uint4* slab, int j, int lane) {
  uint4* p = slab + j * 144 + lane;
#pragma unroll
  for (int i = 0; i < 4; i++) stg4(p + i * 32, 0u, 0u, 0u, 0u);
  if (lane < 16) stg4(p + 128, 0u, 0u, 0u, 0u);
}

struct Maps { CUtensorMap m[5]; };

struct Ring {
  uint32_t st, ph;
  __device__ __forceinline__ void next() { if (++st == NST) { st = 0; ph ^= 1; } }
};

#define STAMP(i) do {} while (0)

__device__ __forceinline__ void tma_box(uint32_t dst, const CUtensorMap* m, int col, int row, uint32_t bar, uint32_t expect) {
  asm volatile("{\n.reg .pred e, h;\nelect.sync _|e, 0xffffffff;\nsetp.ne.and.u32 h, %5, 0, e;\n"
               "@h mbarrier.arrive.expect_tx.shared::cta.b64 _, [%2], %5;\n"
               "@e cp.async.bulk.tensor.2d.shared::cluster.global.mbarrier::complete_tx::bytes [%0], [%1, {%3, %4}], [%2];\n}"
               :: "r"(dst), "l"(m), "r"(bar), "r"(col), "r"(row), "r"(expect) : "memory");
}

__global__ void __launch_bounds__(384, 1) mega_kernel(
    const __grid_constant__ Maps maps, uint4* __restrict__ scr,
    const __nv_bfloat16* __restrict__ x_in, const __nv_bfloat16* __restrict__ wqkv, const __nv_bfloat16* __restrict__ wo,
    __nv_bfloat16* __restrict__ out) {
  extern __shared__ __align__(1024) uint8_t smem[];
  const uint32_t sb = (uint32_t)__cvta_generic_to_shared(smem);
  const uint32_t full0 = sb + BARS, empty0 = full0 + 8 * NST, rem_full = empty0 + 8 * NST, park_free = rem_full + 8, kv_free = park_free + 8;
  const int w = __shfl_sync(~0u, threadIdx.x >> 5, 0), lane = threadIdx.x & 31;
  const int t = blockIdx.x >> 3, j = blockIdx.x & 7;
  const int r = lane >> 2, q = lane & 3;
  auto load_rem = [&] {
    const int tid = threadIdx.x - 320;
#pragma unroll 1
    for (int p = 0; p < 4; p++) {
      const __nv_bfloat16* src = (p == 3 ? wo : wqkv + (p == 2 ? 0 : 576 * (p + 1))) + 72 * j + 64;
      const int pitch = p == 3 ? 576 : 1728;
#pragma unroll 1
      for (int k = tid; k < 576; k += 64) {
        const int s = k >> 4, rr = k & 7;
        cp16(sb + REM + p * 10240 + (s >> 3) * 2048 + ((k >> 3) & 1) * 1024 + rr * 128 + (((s & 7) ^ rr) << 4), src + k * pitch);
      }
    }
  };
  if (w == 8) {
    if (lane == 0) {
      for (int i = 0; i < NST; i++) { mbar_init(full0 + 8 * i, 1); mbar_init(empty0 + 8 * i, 8); }
      mbar_init(rem_full, 64); mbar_init(park_free, 8); mbar_init(kv_free, 8);
      asm volatile("fence.mbarrier_init.release.cluster;" ::: "memory");
    }
    __syncwarp();
#pragma unroll 1
    for (int b = 0; b < 2 * NST; b++)
      tma_box(sb + b * 8192, &maps.m[0], 72 * j + 576 + 576 * (b & 1), 64 * (b >> 1), full0 + (b >> 1) * 8, (b & 1) ? 0 : STAGE);
  } else if (w >= 10) {
    load_rem();
  } else {
    const int sl = w < 8 ? w : j, ch = w < 8 ? j : 8;
    const uint32_t* xr = (const uint32_t*)(x_in + (128 * t + 32 * (sl >> 1) + 2 * r + (sl & 1)) * 576 + 64 * ch + 2 * q);
    uint32_t v[16];
#pragma unroll
    for (int g = 0; g < 8; g++) { v[2 * g] = __ldg(xr + 4 * g); v[2 * g + 1] = __ldg(xr + 8 * 576 + 4 * g); }
    uint4* p = scr + OFF_X + (t * 8 + sl) * SLAB + 4 * ch * 32 + lane;
#pragma unroll
    for (int i = 0; i < 4; i++) stg4(p + i * 32, nz(v[4 * i]), v[4 * i + 1], nz(v[4 * i + 2]), v[4 * i + 3]);
    float y[32];
#pragma unroll
    for (int i = 0; i < 16; i++) { y[2 * i] = bf_lo(v[i]); y[2 * i + 1] = bf_hi(v[i]); }
    publish_stats<8>(scr + OFF_S + (t * 8 + sl) * 96 + ch * 8, y, 1u, lane);
  }
  __syncthreads();

  if (w >= 8) {
    asm volatile("setmaxnreg.dec.sync.aligned.u32 24;");
    if (w == 8) {
      Ring rg{0, 0};
      int b = 2 * NST;
#pragma unroll 1
      for (int seg = 0; seg < 34; seg++) {
        const int n = seg >= 17 ? seg - 17 : seg;
        int ma, mb, ca, cb, row = 0;
        if (n < 3) { ma = mb = n == 2; ca = 72 * j + (n == 0 ? 576 : 0); cb = ca + 576; }
        else if (n < 12) { ma = 3; mb = 2; ca = cb = 576 * j + 64 * (n - 3); }
        else { ma = mb = 4; ca = n == 12 ? 512 : ((j + 2 * n) & 7) * 64; cb = ((j + 2 * n + 1) & 7) * 64; row = 576 * j; }
        const bool zip = n == 0 || n == 3;
        const int nb = (n == 1 || n == 2 || n == 16) ? 9 : 18;
#pragma unroll 1
        for (; b < nb; b++) {
          const bool second = zip ? (b & 1) : b >= 9, last = b == nb - 1;
          const int kb = zip ? b >> 1 : second ? b - 9 : b;
          if (!(b & 1)) mbar_wait(empty0 + rg.st * 8, rg.ph);
          tma_box(sb + rg.st * STAGE + (b & 1) * 8192, &maps.m[second ? mb : ma], second ? cb : ca, row + 64 * kb, full0 + rg.st * 8,
                  (b & 1) ? 0 : last ? STAGE / 2 : STAGE);
          if ((b & 1) || last) rg.next();
        }
        b = 0;
      }
    } else if (w == 9) {
      const uint32_t stg = sb + HSTG + lane * 16;
#pragma unroll 1
      for (int layer = 0; layer < 2; layer++) {
        const uint32_t tag = 1 - layer;
        mbar_wait(park_free, layer);
        float s0 = 0.f, s1 = 0.f;
#pragma unroll 1
        for (int i = 0; i < 4; i++) {
          uint4* xb = scr + OFF_X + ((4 + layer) * 128 + t * 8 + j) * SLAB + (32 + i) * 32 + lane;
          float a[8];
          int n = 0;
          while (true) {
            const uint4* p = scr + OFF_P + (t * 64 + j) * SLAB + (32 + i) * 32 + lane;
#pragma unroll 1
            for (int s = 0; s < 8; s++) cp16(stg + s * 512, p + s * 8 * SLAB);
            cp16(stg + 4096, xb);
            cp_wait();
            uint32_t bad = 0;
#pragma unroll
            for (int e = 0; e < 8; e++) a[e] = 0.f;
#pragma unroll 1
            for (int s = 0; s < 9; s++) {
              uint32_t v[4];
              lds4(stg + s * 512, v);
              if (s < 8) bad |= v[0] ^ tag;
#pragma unroll
              for (int e = 0; e < 4; e++) { a[2 * e] += bf_lo(v[e]); a[2 * e + 1] += bf_hi(v[e]); }
            }
            if (__all_sync(~0u, (bad & 1u) == 0u)) break;
            __nanosleep(200);
            SPIN_GUARD(n);
          }
          uint32_t x[4];
#pragma unroll
          for (int e = 0; e < 4; e++) x[e] = pack_bf16(a[2 * e], a[2 * e + 1]);
          stg4(xb, 0u, 0u, 0u, 0u);
          if (layer == 0) {
            stg4(xb - 3 * 128 * SLAB, nz(x[0]), x[1], nz(x[2]), x[3]);
            sts4(stg + 4608 + i * 512, x);
            s0 += a[0] + a[1] + a[4] + a[5]; s1 += a[2] + a[3] + a[6] + a[7];
          } else {
            uint32_t* o = (uint32_t*)(out + (128 * t + 32 * (j >> 1) + 2 * r + (j & 1)) * 576 + 512 + 16 * i + 2 * q);
            o[0] = x[0]; o[8 * 576] = x[1]; o[4] = x[2]; o[8 * 576 + 4] = x[3];
          }
        }
        if (layer == 0) {
          s0 = quad_sum(s0); s1 = quad_sum(s1);
          const float m0 = s0 * (1.f / 64), m1 = s1 * (1.f / 64);
          float q0 = 0.f, q1 = 0.f;
#pragma unroll 1
          for (int i = 0; i < 4; i++) {
            uint32_t x[4];
            lds4(stg + 4608 + i * 512, x);
#pragma unroll
            for (int e = 0; e < 4; e++) {
              const float c = bf_lo(x[e]) - ((e & 1) ? m1 : m0), d = bf_hi(x[e]) - ((e & 1) ? m1 : m0);
              if (e & 1) q1 = fmaf(c, c, fmaf(d, d, q1)); else q0 = fmaf(c, c, fmaf(d, d, q0));
            }
          }
          q0 = quad_sum(q0); q1 = quad_sum(q1);
          if (q == 0) stg4(scr + OFF_S + (t * 8 + j) * 96 + 64 + r, __float_as_uint(s0) & ~1u, __float_as_uint(q0), __float_as_uint(s1), __float_as_uint(q1));
        }
      }
    } else {
#pragma unroll 1
      for (int layer = 0; layer < 2; layer++) {
        if (layer) { mbar_wait(park_free, 0); load_rem(); }
        asm volatile("cp.async.wait_all;\nfence.proxy.async.shared::cta;" ::: "memory");
        mbar_arrive(rem_full);
        if (layer) mbar_wait(kv_free, 0);
        if (t > 0) {
#pragma unroll 1
          for (int kv = 0; kv < 2; kv++) {
            uint4* hp = scr + OFF_H + ((layer * 128 + t * 8 + j) * 4 + (w - 10) * 2 + kv) * 96 + lane;
            uint32_t hl[12];
            int n = 0;
            while (true) {
              ldg4(hl, hp); ldg4(hl + 4, hp + 32); ldg4(hl + 8, hp + 64);
              if (__all_sync(~0u, hl[0] != 0u && hl[4] != 0u && hl[8] != 0u)) break;
              __nanosleep(100);
              SPIN_GUARD(n);
            }
#pragma unroll
            for (int g = 0; g < 9; g++) sts1(sb + KVS + kv * 20736 + (w - 10) * 10368 + r * 144 + g * 16 + q * 4, hl[g]);
#pragma unroll
            for (int i = 0; i < 3; i++) stg4(hp + i * 32, 0u, 0u, 0u, 0u);
          }
        }
        asm volatile("bar.arrive 1, 192;" ::: "memory");
      }
    }
  } else {
    asm volatile("setmaxnreg.inc.sync.aligned.u32 240;");
    Ring rg{0, 0};
    uint32_t prev = 0;
    uint32_t X[144];
    float rs0, rs1;
    uint32_t mean0, mean1;
    auto release = [&](uint32_t st) { if (lane == 0) mbar_arrive(empty0 + st * 8); };
    auto load_kb = [&](bool split, int kb, const uint4* src) {
#pragma unroll
      for (int k = 4 * kb; k < 4 * kb + 4; k++) {
        if (split && k % 9 == 4) { const char* lo = (const char*)(src + k * 32) - lane * 8; ldg2(X + 4 * k, lo); ldg2(X + 4 * k + 2, lo + 256); }
        else ldg4(X + 4 * k, src + k * 32);
      }
    };
    auto next_kb = [&](bool split, bool center, int kb, const uint4* src) {
      int n = 0;
      while (true) {
        bool ok = true;
#pragma unroll
        for (int k = 4 * kb; k < 4 * kb + 4; k++) { ok = ok && X[4 * k] != 0u; if (split && k % 9 == 4) ok = ok && X[4 * k + 2] != 0u; }
        if (__all_sync(~0u, ok)) break;
        SPIN_GUARD(n);
        load_kb(split, kb, src);
      }
      if (kb + GD < 9) load_kb(split, kb + GD, src);
      if (center) {
#pragma unroll
        for (int i = 16 * kb; i < 16 * kb + 16; i++) X[i] = sub_bf16x2(X[i], (i & 1) ? mean1 : mean0);
      }
    };
#pragma unroll 1
    for (int layer = 0; layer < 2; layer++) {
      const uint32_t tag = 1 - layer;
      uint4* const xbase = scr + OFF_X + (layer * 128 + t * 8 + w) * SLAB;
      auto begin_gather = [&](int kind) {
        uint32_t s[3][4];
        const uint4* p = scr + OFF_S + (kind * 128 + t * 8 + w) * 96 + q * 8 + r;
        int n = 0;
        s[2][0] = tag; s[2][1] = s[2][2] = s[2][3] = 0u;
        STAMP(kind * 8 + 0);
        while (true) {
          ldg4(s[0], p); ldg4(s[1], p + 32);
          if (kind == 0 && q == 0) ldg4(s[2], p + 64);
          if (__all_sync(~0u, ((s[0][0] ^ tag) | (s[1][0] ^ tag) | (s[2][0] ^ tag)) % 2u == 0u)) break;
          SPIN_GUARD(n);
        }
        STAMP(kind * 8 + 1);
#pragma unroll
        for (int kb = 0; kb < GD; kb++) load_kb(kind != 0, kb, xbase + kind * 256 * SLAB + lane);
        if (kind != 1) {
          const int ns = kind == 0 ? 3 : 2;
          float t0 = 0.f, t1 = 0.f;
#pragma unroll
          for (int i = 0; i < ns; i++) { t0 += __uint_as_float(s[i][0]); t1 += __uint_as_float(s[i][2]); }
          const float m0 = quad_sum(t0) * (1.f / 576), m1 = quad_sum(t1) * (1.f / 576);
          const float cnt = kind == 0 ? 64.f : 72.f;
          float v0 = 0.f, v1 = 0.f;
#pragma unroll
          for (int i = 0; i < ns; i++) {
            const float c = (i < 2 || q == 0) ? cnt : 0.f;
            const float d0 = fmaf(__uint_as_float(s[i][0]), 1.f / cnt, -m0), d1 = fmaf(__uint_as_float(s[i][2]), 1.f / cnt, -m1);
            v0 += fmaf(d0 * d0, c, __uint_as_float(s[i][1])); v1 += fmaf(d1 * d1, c, __uint_as_float(s[i][3]));
          }
          rs0 = rsqrtf(fmaf(quad_sum(v0), 1.f / 576, 1e-5f)); rs1 = rsqrtf(fmaf(quad_sum(v1), 1.f / 576, 1e-5f));
          mean0 = pack_bf16(m0, m0); mean1 = pack_bf16(m1, m1);
        }
      };
      auto box72 = [&](float (&a)[36], int part, int kb, int half) {
        const uint32_t base = sb + rg.st * STAGE + half * 8192;
        const uint64_t d0 = DESC_HI | ((base >> 4) + (((sb + REM + part * 10240 + (kb >> 1) * 2048 + (kb & 1) * 64 - base) >> 4) << 16));
#pragma unroll
        for (int i = 0; i < 4; i++) wgmma_rs_n72(a, X + 4 * (4 * kb + i), d0 - (uint64_t)(i * ((127u << 16) - 128u)), kb + i != 0);
      };
      auto solo72 = [&](float (&a)[36], int part, auto&& pre) {
#pragma unroll
        for (int kb = 0; kb < 9; kb++) {
          pre(kb);
          if (!(kb & 1)) mbar_wait(full0 + rg.st * 8, rg.ph);
          wg_fence();
          box72(a, part, kb, kb & 1);
          wg_commit();
          wg_wait<1>();
          if (kb > 0 && !(kb & 1)) release(prev);
          if ((kb & 1) || kb == 8) { prev = rg.st; rg.next(); }
        }
      };
      const uint32_t kvrow = sb + KVS + (w & 1) * 10368 + (16 * (w >> 1)) * 144;
      uint32_t Q[18];
      begin_gather(0);
      mbar_wait(rem_full, layer);
      {
        float acc[36], acc2[36];
#pragma unroll
        for (int kb = 0; kb < 9; kb++) {
          next_kb(false, true, kb, xbase + lane);
          mbar_wait(full0 + rg.st * 8, rg.ph);
          wg_fence();
          box72(acc, 0, kb, 0); box72(acc2, 1, kb, 1);
          wg_commit();
          wg_wait<1>();
          if (kb > 0) release(prev);
          if (kb == 1) sts4(sb + PARK + w * 512 + lane * 16, X);
          prev = rg.st; rg.next();
        }
        wg_wait<0>();
        release(prev);
        STAMP(2);
        auto put_kv = [&](float (&a)[36], int part) {
          pin(a);
          uint32_t hl[9];
          const uint32_t dst = kvrow + part * 20736 + (8 + r) * 144 + q * 4;
#pragma unroll
          for (int g = 0; g < 9; g++) {
            hl[g] = pack_bf16(a[4 * g + 2] * rs1, a[4 * g + 3] * rs1);
            sts1(dst + g * 16, pack_bf16(a[4 * g] * rs0, a[4 * g + 1] * rs0)); sts1(dst + 8 * 144 + g * 16, hl[g]);
          }
          if (w >= 6 && t < 15) {
            uint4* hp = scr + OFF_H + ((layer * 128 + (t + 1) * 8 + j) * 4 + (w & 1) * 2 + part) * 96 + lane;
            stg4(hp, nz(hl[0]), hl[1], hl[2], hl[3]); stg4(hp + 32, nz(hl[4]), hl[5], hl[6], hl[7]); stg4(hp + 64, nz(hl[8]), 0u, 0u, 0u);
          }
        };
        put_kv(acc2, 1);
        lds4(sb + PARK + w * 512 + lane * 16, X);
        put_kv(acc, 0);
        if (w < 4) asm volatile("bar.arrive 2, 256;" ::: "memory");
        solo72(acc, 2, [](int) {});
        wg_wait<0>();
        release(prev);
        pin(acc);
        STAMP(3);
#pragma unroll
        for (int g = 0; g < 9; g++) {
          Q[2 * g] = pack_bf16(acc[4 * g] * rs0, acc[4 * g + 1] * rs0); Q[2 * g + 1] = pack_bf16(acc[4 * g + 2] * rs1, acc[4 * g + 3] * rs1);
        }
      }
      if (w < 4) asm volatile("bar.sync 1, 192;" ::: "memory");
      else asm volatile("bar.sync 2, 256;" ::: "memory");
      STAMP(4);
      uint32_t O[18];
      {
        const bool edge = (t == 0 && w < 2);
        uint32_t row[3];
#pragma unroll
        for (int nt = 0; nt < 3; nt++) row[nt] = kvrow + (8 * nt + (lane & 7)) * 144;
        if (edge) row[0] = sb + KVS + 8 * 144;
        const uint32_t rlast = ((lane >> 3) == 0 ? row[0] : (lane >> 3) == 1 ? row[1] : row[2]) + 128;
        uint32_t K[3][9], V[3][9], dummy;
#pragma unroll
        for (int nt = 0; nt < 3; nt++) {
          ldsm4(row[nt] + (lane >> 3) * 16, K[nt][0], K[nt][1], K[nt][2], K[nt][3]);
          ldsm4(row[nt] + 64 + (lane >> 3) * 16, K[nt][4], K[nt][5], K[nt][6], K[nt][7]);
        }
        ldsm4(rlast, K[0][8], K[1][8], K[2][8], dummy);
#pragma unroll
        for (int nt = 0; nt < 3; nt++) {
          ldsm4t(row[nt] + 20736 + (lane >> 3) * 16, V[nt][0], V[nt][1], V[nt][2], V[nt][3]);
          ldsm4t(row[nt] + 20736 + 64 + (lane >> 3) * 16, V[nt][4], V[nt][5], V[nt][6], V[nt][7]);
        }
        ldsm4t(rlast + 20736, V[0][8], V[1][8], V[2][8], dummy);
        const bool up0 = 2 * q > r, up1 = 2 * q + 1 > r;
        const float sc = 0.23570226039551584f * 1.4426950408889634f;
        const float neg = -1e9f * 1.4426950408889634f;
        float Of[9][4];
#pragma unroll
        for (int h = 0; h < 4; h++) {
          const uint32_t a0 = q >= h ? Q[4 * h] : 0u, a1 = q >= h ? Q[4 * h + 1] : 0u;
          const uint32_t a4 = q <= h ? Q[4 * h + 4] : 0u, a5 = q <= h ? Q[4 * h + 5] : 0u;
          float S[3][4];
#pragma unroll
          for (int nt = 0; nt < 3; nt++) {
            S[nt][0] = S[nt][1] = S[nt][2] = S[nt][3] = 0.f;
            mma16(S[nt], a0, a1, Q[4 * h + 2], Q[4 * h + 3], K[nt][2 * h], K[nt][2 * h + 1]);
            mma8(S[nt], a4, a5, K[nt][2 * h + 2]);
          }
          float s00 = (up0 ? S[0][0] : S[1][0]) * sc, s01 = (up1 ? S[0][1] : S[1][1]) * sc;
          const float s10 = (up0 ? S[1][2] : S[2][2]) * sc, s11 = (up1 ? S[1][3] : S[2][3]) * sc;
          if (edge && up0) s00 = neg;
          if (edge && up1) s01 = neg;
          const float m0 = quad_max(fmaxf(s00, s01)), m1 = quad_max(fmaxf(s10, s11));
          float p00 = ex2(s00 - m0), p01 = ex2(s01 - m0), p10 = ex2(s10 - m1), p11 = ex2(s11 - m1);
          const float i0 = rcp(quad_sum(p00 + p01)), i1 = rcp(quad_sum(p10 + p11));
          p00 *= i0; p01 *= i0; p10 *= i1; p11 *= i1;
          const uint32_t pa = pack_bf16(up0 ? p00 : 0.f, up1 ? p01 : 0.f), pb = pack_bf16(up0 ? 0.f : p00, up1 ? 0.f : p01);
          const uint32_t pc = pack_bf16(up0 ? p10 : 0.f, up1 ? p11 : 0.f), pd = pack_bf16(up0 ? 0.f : p10, up1 ? 0.f : p11);
#pragma unroll
          for (int gi = 0; gi < 3; gi++) {
            const int g = 2 * h + gi;
            float o[4] = {0.f, 0.f, 0.f, 0.f};
            mma16(o, pa, 0u, pb, pc, V[0][g], V[1][g]);
            mma8(o, 0u, pd, V[2][g]);
#pragma unroll
            for (int e = 0; e < 4; e++) Of[g][e] = (gi == 0 && h > 0 && q < h) ? Of[g][e] : o[e];
          }
        }
#pragma unroll
        for (int g = 0; g < 9; g++) { O[2 * g] = pack_bf16(Of[g][0], Of[g][1]); O[2 * g + 1] = pack_bf16(Of[g][2], Of[g][3]); }
      }
      put72(xbase + 256 * SLAB, j, lane, O);
      if (q == 0) stg4(scr + OFF_S + (128 + t * 8 + w) * 96 + j * 8 + r, tag, 0u, 0u, 0u);
      {
        uint32_t res[18];
        const char* p = (const char*)(xbase + lane) + ((9 * j) >> 1) * 512 + (j & 1) * 8;
#pragma unroll
        for (int g = 0; g < 9; g++) ldg2(res + 2 * g, p + (g >> 1) * 512 + ((g & 1) ? ((j & 1) ? 504 : 8) : 0));
        begin_gather(1);
        float acc[36];
        solo72(acc, 3, [&](int kb) { next_kb(true, false, kb, xbase + 256 * SLAB + lane); });
        wg_wait<0>();
        release(prev);
        pin(acc);
        STAMP(10);
#pragma unroll
        for (int i = 0; i < 18; i++) {
          acc[2 * i] += bf_lo(res[i]); acc[2 * i + 1] += bf_hi(res[i]);
          res[i] = pack_bf16(acc[2 * i], acc[2 * i + 1]);
        }
        put72(xbase + 512 * SLAB, j, lane, res);
        publish_stats<9>(scr + OFF_S + (256 + t * 8 + w) * 96 + j * 8, acc, tag, lane);
      }
      float aA[32], aB[32];
      const uint32_t hp = sb + PARK + w * 512 + lane * 16;
      begin_gather(2);
#pragma unroll
      for (int kb = 0; kb < 9; kb++) {
        next_kb(true, true, kb, xbase + 512 * SLAB + lane);
        mbar_wait(full0 + rg.st * 8, rg.ph);
        const uint64_t desc = DESC_HI | ((sb + rg.st * STAGE) >> 4);
        wg_fence();
#pragma unroll
        for (int i = 0; i < 4; i++) wgmma_rs_n64(aA, X + 4 * (4 * kb + i), desc + i * 128, kb + i != 0);
#pragma unroll
        for (int i = 0; i < 4; i++) wgmma_rs_n64(aB, X + 4 * (4 * kb + i), desc + 512 + i * 128, kb + i != 0);
        wg_commit();
        wg_wait<1>();
        if (kb > 0) release(prev);
        prev = rg.st; rg.next();
      }
      zero_share(xbase, j, lane);
      zero_share(xbase + 256 * SLAB, j, lane);
      wg_wait<0>();
      STAMP(20);
      auto pack8 = [&](float (&a)[32], int p, uint32_t* o) {
#pragma unroll
        for (int e = 0; e < 8; e++) asm volatile("" : "+f"(a[8 * p + e]) :: "memory");
#pragma unroll
        for (int e = 0; e < 4; e++) o[e] = pack_bf16(a[8 * p + 2 * e], a[8 * p + 2 * e + 1]);
      };
      const float ka0 = 0.7978845608028654f * rs0, kb0 = 0.044715f * ka0 * rs0 * rs0, ku0 = 0.5f * rs0 * rs0;
      const float ka1 = 0.7978845608028654f * rs1, kb1 = 0.044715f * ka1 * rs1 * rs1, ku1 = 0.5f * rs1 * rs1;
      auto packu8 = [&](int p, uint32_t* o) {
#pragma unroll
        for (int e = 0; e < 8; e++) asm volatile("" : "+f"(aA[8 * p + e]) :: "memory");
#pragma unroll
        for (int e = 0; e < 4; e++) o[e] = pack_bf16(aA[8 * p + 2 * e] * ((e & 1) ? ku1 : ku0), aA[8 * p + 2 * e + 1] * ((e & 1) ? ku1 : ku0));
      };
      auto geglu8 = [&](int p, uint32_t* u) {
#pragma unroll
        for (int e = 0; e < 8; e++) asm volatile("" : "+f"(aB[8 * p + e]) :: "memory");
        float h[8];
#pragma unroll
        for (int e = 0; e < 8; e++) {
          const float g = aB[8 * p + e];
          h[e] = fmaf(g, tanh_ap(g * fmaf(g * g, (e & 2) ? kb1 : kb0, (e & 2) ? ka1 : ka0)), g);
        }
#pragma unroll
        for (int e = 0; e < 4; e++) u[e] = mul_bf16x2(pack_bf16(h[2 * e], h[2 * e + 1]), u[e]);
      };
      auto box = [&](int b, auto&& filler) {
        const int kb = b < 9 ? b : b - 9;
        if (!(b & 1)) mbar_wait(full0 + rg.st * 8, rg.ph);
        const uint64_t desc = DESC_HI | ((sb + rg.st * STAGE + (b & 1) * 8192) >> 4);
        wg_fence();
#pragma unroll
        for (int i = 0; i < 4; i++) {
          if (b < 9) wgmma_rs_n64(aA, X + 4 * (4 * kb + i), desc + i * 128, kb + i != 0);
          else wgmma_rs_n64(aB, X + 4 * (4 * kb + i), desc + i * 128, kb + i != 0);
          if (i == FPOS) filler();
        }
        wg_commit();
        if (b & 1) { if (W2) wg_wait<1>(); prev = rg.st; rg.next(); } else { wg_wait<1>(); release(prev); }
      };
      auto nop = [] {};
      auto step = [&](int st, auto&& filler) { box(2 * st, nop); box(2 * st + 1, filler); };
#pragma unroll
      for (int p = 0; p < 4; p++) { uint32_t o[4]; packu8(p, o); sts4(hp + p * 4096, o); }
      box(0, nop);
#pragma unroll 1
      for (int c = 1;; c++) {
        const uint32_t hc = hp + c * 4 * 4096;
#pragma unroll
        for (int b = 1; b < 18; b++) box(b, [&] {
          if ((b & 1) && b < 8) { uint32_t o[4]; const uint32_t a = hc - (4 - (b >> 1)) * 4096; lds4(a, o); geglu8(b >> 1, o); sts4(a, o); }
          if ((b & 1) && b > 10) { uint32_t o[4]; packu8((b - 11) >> 1, o); if (c < 8) sts4(hc + ((b - 11) >> 1) * 4096, o); } });
        if (c == 8) break;
        box(0, nop);
      }
      wg_wait<0>();
      STAMP(21);
#pragma unroll
      for (int s = 0; s < 32; s++) lds4(hp + s * 4096, X + 4 * s);
#pragma unroll
      for (int p = 0; p < 4; p++) packu8(p, X + 128 + 4 * p);
#pragma unroll
      for (int st = 0; st < 4; st++) step(st, [&] { geglu8(st, X + 128 + 4 * st); });
      if (lane == 0) mbar_arrive(park_free);
      int lane2 = lane;
      asm volatile("" : "+r"(lane2));
      uint4* const pw = scr + OFF_P + ((t * 8 + j) * 8 + w) * SLAB + lane2;
      const uint4* const pr = scr + OFF_P + (t * 64 + w) * SLAB + 4 * j * 32 + lane2;
      auto put_part = [&](float (&a)[32], int p, int chunk) {
        uint32_t o[4];
        pack8(a, p, o);
        stg4(pw + (chunk * 4 + p) * 32, (o[0] & ~1u) | tag, o[1], o[2], o[3]);
      };
      auto slot = [&](int p) { return hp + (p < 4 ? (p - 1) * 16384 : KVS - PARK + (p - 4) * 16384); };
      auto fetch = [&](int p) {
        if (p > 0) {
#pragma unroll
          for (int i = 0; i < 4; i++) cp16(slot(p) + i * 4096, pr + ((j - p) & 7) * 8 * SLAB + i * 32);
        }
      };
#pragma unroll 1
      for (int sp = 0;; sp++) {
        const int ca = sp == 0 ? 8 : ((j + 2 * sp) & 7), cb = (j + 2 * sp + 1) & 7;
#pragma unroll
        for (int st = 4; st < 9; st++) step(st, [&] {
          if (st == 5 || st == 6) { put_part(aA, 2 * (st - 5), ca); put_part(aA, 2 * (st - 5) + 1, ca); }
          if (st == 8) fetch(2 * sp - 1); });
        if (sp == 3) break;
#pragma unroll
        for (int st = 0; st < 4; st++) step(st, [&] {
          if (st < 2) { put_part(aB, 2 * st, cb); put_part(aB, 2 * st + 1, cb); }
          if (st == 3) fetch(2 * sp); });
      }
      uint4* const xb = xbase + 512 * SLAB + 4 * j * 32;
      auto load_p = [&](int p, uint32_t* d) {
#pragma unroll
        for (int i = 0; i < 4; i++) ldg4(d + 4 * i, pr + ((j - p) & 7) * 8 * SLAB + i * 32);
      };
#pragma unroll
      for (int st = 0; st < 4; st++) step(st, [&] {
        if (st == 0) {
#pragma unroll
          for (int p = 0; p < 4; p++) put_part(aB, p, (j + 7) & 7);
        }
        if (st == 1) {
#pragma unroll
          for (int i = 0; i < 4; i++) {
            const bool split = j == 2 * i + 1;
            const char* l = (const char*)(xb + i * 32) + (split ? lane2 * 8 : lane2 * 16);
            ldg2(X + 4 * i, l); ldg2(X + 4 * i + 2, l + (split ? 256 : 8));
          }
          load_p(6, X + 16);
        }
        if (st == 3) load_p(7, X + 32); });
      {
        mbar_wait(full0 + rg.st * 8, rg.ph);
        const uint64_t desc = DESC_HI | ((sb + rg.st * STAGE) >> 4);
        wg_fence();
#pragma unroll
        for (int i = 0; i < 4; i++) wgmma_rs_n64(aA, X + 4 * (32 + i), desc + i * 128, 1);
        wg_commit();
        wg_wait<1>(); release(prev);
        prev = rg.st; rg.next();
        cp_wait();
        wg_wait<0>(); release(prev);
        pin(aA);
      }
      STAMP(22);
      {
        const uint32_t eye = r == 2 * q ? 0x3f80u : r == 2 * q + 1 ? 0x3f800000u : 0u;
        auto add_p = [&](int p, uint32_t* d) {
          int n = 0;
          while (!__all_sync(~0u, (((d[0] ^ tag) | (d[4] ^ tag) | (d[8] ^ tag) | (d[12] ^ tag)) & 1u) == 0u)) { SPIN_GUARD(n); load_p(p, d); }
#pragma unroll
          for (int g = 0; g < 8; g++) mma8(aA + 4 * g, d[2 * g], d[2 * g + 1], eye);
        };
#pragma unroll
        for (int p = 1; p < 6; p++)
#pragma unroll
          for (int i = 0; i < 4; i++) lds4(slot(p) + i * 4096, X + 32 + 16 * p + 4 * i);
#pragma unroll
        for (int g = 0; g < 8; g++) mma8(aA + 4 * g, X[2 * g], X[2 * g + 1], eye);
#pragma unroll
        for (int p = 1; p < 6; p++) add_p(p, X + 32 + 16 * p);
        add_p(6, X + 16); add_p(7, X + 32);
        uint32_t res[16];
#pragma unroll
        for (int i = 0; i < 16; i++) res[i] = pack_bf16(aA[2 * i], aA[2 * i + 1]);
        if (layer == 0) {
          uint4* p = xbase + 128 * SLAB + 4 * j * 32 + lane;
#pragma unroll
          for (int i = 0; i < 4; i++) stg4(p + i * 32, nz(res[4 * i]), res[4 * i + 1], nz(res[4 * i + 2]), res[4 * i + 3]);
          publish_stats<8>(scr + OFF_S + (t * 8 + w) * 96 + j * 8, aA, 0u, lane);
          if (lane == 0) mbar_arrive(kv_free);
        } else {
          uint32_t* o = (uint32_t*)(out + (128 * t + 32 * (w >> 1) + 2 * r + (w & 1)) * 576 + 64 * j + 2 * q);
#pragma unroll
          for (int g = 0; g < 8; g++) { o[4 * g] = res[2 * g]; o[8 * 576 + 4 * g] = res[2 * g + 1]; }
        }
#pragma unroll
        for (int i = 0; i < 4; i++) stg4(xb + lane + i * 32, 0u, 0u, 0u, 0u);
      }
      STAMP(23);
    }
  }
}

typedef CUresult (*EncodeFn)(CUtensorMap*, CUtensorMapDataType, cuuint32_t, void*, const cuuint64_t*, const cuuint64_t*,
                             const cuuint32_t*, const cuuint32_t*, CUtensorMapInterleave, CUtensorMapSwizzle,
                             CUtensorMapL2promotion, CUtensorMapFloatOOBfill);

CUtensorMap make_map(EncodeFn f, const void* p, uint64_t cols, uint64_t rows) {
  CUtensorMap m;
  cuuint64_t dims[2] = {cols, rows};
  cuuint64_t str[1] = {cols * 2};
  cuuint32_t box[2] = {64, 64};
  cuuint32_t es[2] = {1, 1};
  f(&m, CU_TENSOR_MAP_DATA_TYPE_BFLOAT16, 2, const_cast<void*>(p), dims, str, box, es, CU_TENSOR_MAP_INTERLEAVE_NONE,
    CU_TENSOR_MAP_SWIZZLE_128B, CU_TENSOR_MAP_L2_PROMOTION_NONE, CU_TENSOR_MAP_FLOAT_OOB_FILL_NONE);
  return m;
}

}

extern "C" void kernel_launch(void* const* d_in, const int* in_sizes, int n_in, void* d_out, int out_size) {
  void* fn = nullptr;
  cudaDriverEntryPointQueryResult qr;
  cudaGetDriverEntryPoint("cuTensorMapEncodeTiled", &fn, cudaEnableDefault, &qr);
  EncodeFn enc = (EncodeFn)fn;
  Maps maps;
  maps.m[0] = make_map(enc, d_in[1], 1728, 576); maps.m[1] = make_map(enc, d_in[2], 576, 576);
  maps.m[2] = make_map(enc, d_in[4], 4608, 576); maps.m[3] = make_map(enc, d_in[5], 4608, 576); maps.m[4] = make_map(enc, d_in[6], 576, 4608);
  void* scr = nullptr;
  cudaGetSymbolAddress(&scr, g_scratch);
  cudaFuncSetAttribute(mega_kernel, cudaFuncAttributeMaxDynamicSharedMemorySize, SMEM_BYTES);
  mega_kernel<<<128, 384, SMEM_BYTES>>>(maps, (uint4*)scr, (const __nv_bfloat16*)d_in[0], (const __nv_bfloat16*)d_in[1],
                                        (const __nv_bfloat16*)d_in[2], (__nv_bfloat16*)d_out);
}
```

```cpp
#include <cuda_runtime.h>
#include <cuda.h>
#include <cuda_bf16.h>
#include <stdint.h>

#define TRACE 0
#define FPOS 2
#define W2 0

namespace {

constexpr int NST = 6;
constexpr int STAGE = 16384;
constexpr int PARK = NST * STAGE;
constexpr int REM = PARK + 49152;
constexpr int KVS = REM + 40960;
constexpr int RSTG = PARK + 4096;
constexpr int HSTG = KVS + 32768;
constexpr int BARS = KVS + 41472;
constexpr int TRC = BARS + 256;
constexpr int SMEM_BYTES = TRC + (TRACE ? 512 : 0);
static_assert(BARS >= PARK + 131072, "barriers overlap park");
static_assert(SMEM_BYTES <= 232448, "smem");

constexpr int SLAB = 36 * 32;
constexpr int SPIN_MAX = 1 << 17;
constexpr int GD = 3;
constexpr int OFF_X = 0;
constexpr int OFF_P = OFF_X + 6 * 128 * SLAB;
constexpr int OFF_S = OFF_P + 8 * 128 * SLAB;
constexpr int OFF_H = OFF_S + 3 * 128 * 96;
constexpr int SCRATCH = OFF_H + 2 * 128 * 384;

}

__device__ uint4 g_scratch[SCRATCH];

namespace {

constexpr uint64_t DESC_HI = 0x4000004000000000ull;
__device__ __forceinline__ void wgmma_rs_n64(float (&d)[32], const uint32_t* a, uint64_t desc, int scale_d) {
  asm volatile("{\n.reg .pred p;\nsetp.ne.b32 p, %37, 0;\n"
    "wgmma.mma_async.sync.aligned.m64n64k16.f32.bf16.bf16 "
    "{%0, %1, %2, %3, %4, %5, %6, %7, %8, %9, %10, %11, %12, %13, %14, %15, %16, %17, %18, %19, %20, %21, %22, %23, %24, %25, %26, %27, %28, %29, %30, %31}, "
    "{%32, %33, %34, %35}, %36, p, 1, 1, 1;\n}\n"
    : "+f"(d[0]), "+f"(d[1]), "+f"(d[2]), "+f"(d[3]), "+f"(d[4]), "+f"(d[5]), "+f"(d[6]), "+f"(d[7]), "+f"(d[8]), "+f"(d[9]), "+f"(d[10]), "+f"(d[11]), "+f"(d[12]), "+f"(d[13]), "+f"(d[14]), "+f"(d[15]), "+f"(d[16]), "+f"(d[17]), "+f"(d[18]), "+f"(d[19]), "+f"(d[20]), "+f"(d[21]), "+f"(d[22]), "+f"(d[23]), "+f"(d[24]), "+f"(d[25]), "+f"(d[26]), "+f"(d[27]), "+f"(d[28]), "+f"(d[29]), "+f"(d[30]), "+f"(d[31])
    : "r"(a[0]), "r"(a[1]), "r"(a[2]), "r"(a[3]), "l"(desc), "r"(scale_d));
}
__device__ __forceinline__ void wgmma_rs_n72(float (&d)[36], const uint32_t* a, uint64_t desc, int scale_d) {
  asm volatile("{\n.reg .pred p;\nsetp.ne.b32 p, %41, 0;\n"
    "wgmma.mma_async.sync.aligned.m64n72k16.f32.bf16.bf16 "
    "{%0, %1, %2, %3, %4, %5, %6, %7, %8, %9, %10, %11, %12, %13, %14, %15, %16, %17, %18, %19, %20, %21, %22, %23, %24, %25, %26, %27, %28, %29, %30, %31, %32, %33, %34, %35}, "
    "{%36, %37, %38, %39}, %40, p, 1, 1, 1;\n}\n"
    : "+f"(d[0]), "+f"(d[1]), "+f"(d[2]), "+f"(d[3]), "+f"(d[4]), "+f"(d[5]), "+f"(d[6]), "+f"(d[7]), "+f"(d[8]), "+f"(d[9]), "+f"(d[10]), "+f"(d[11]), "+f"(d[12]), "+f"(d[13]), "+f"(d[14]), "+f"(d[15]), "+f"(d[16]), "+f"(d[17]), "+f"(d[18]), "+f"(d[19]), "+f"(d[20]), "+f"(d[21]), "+f"(d[22]), "+f"(d[23]), "+f"(d[24]), "+f"(d[25]), "+f"(d[26]), "+f"(d[27]), "+f"(d[28]), "+f"(d[29]), "+f"(d[30]), "+f"(d[31]), "+f"(d[32]), "+f"(d[33]), "+f"(d[34]), "+f"(d[35])
    : "r"(a[0]), "r"(a[1]), "r"(a[2]), "r"(a[3]), "l"(desc), "r"(scale_d));
}

__device__ __forceinline__ void mbar_init(uint32_t a, uint32_t c) { asm volatile("mbarrier.init.shared::cta.b64 [%0], %1;" :: "r"(a), "r"(c)); }
__device__ __forceinline__ void mbar_arrive(uint32_t a) { asm volatile("mbarrier.arrive.shared::cta.b64 _, [%0];" :: "r"(a) : "memory"); }
__device__ __forceinline__ void mbar_wait(uint32_t a, uint32_t ph) {
  asm volatile("{\n.reg .pred p;\n.reg .u32 n;\n"
               "mbarrier.try_wait.parity.shared::cta.b64 p, [%0], %1;\n@p bra D;\n"
               "mov.u32 n, 0;\n"
               "W: mbarrier.try_wait.parity.shared::cta.b64 p, [%0], %1;\n@p bra D;\n"
               "add.u32 n, n, 1;\nsetp.lt.u32 p, n, 4194304;\n@p bra W;\ntrap;\nD:\n}" :: "r"(a), "r"(ph) : "memory");
}
__device__ __forceinline__ void wg_fence() { asm volatile("wgmma.fence.sync.aligned;" ::: "memory"); }
__device__ __forceinline__ void wg_commit() { asm volatile("wgmma.commit_group.sync.aligned;" ::: "memory"); }
template <int N> __device__ __forceinline__ void wg_wait() { asm volatile("wgmma.wait_group.sync.aligned %0;" :: "n"(N) : "memory"); }
__device__ __forceinline__ float tanh_ap(float x) { float y; asm("tanh.approx.f32 %0, %1;" : "=f"(y) : "f"(x)); return y; }
__device__ __forceinline__ float ex2(float x) { float y; asm("ex2.approx.ftz.f32 %0, %1;" : "=f"(y) : "f"(x)); return y; }
__device__ __forceinline__ uint32_t pack_bf16(float lo, float hi) { uint32_t r; asm("cvt.rn.bf16x2.f32 %0, %1, %2;" : "=r"(r) : "f"(hi), "f"(lo)); return r; }
__device__ __forceinline__ float bf_lo(uint32_t v) { return __uint_as_float(v << 16); }
__device__ __forceinline__ float bf_hi(uint32_t v) { return __uint_as_float(v & 0xffff0000u); }
__device__ __forceinline__ uint32_t sub_bf16x2(uint32_t a, uint32_t b) { uint32_t r; asm("sub.rn.bf16x2 %0, %1, %2;" : "=r"(r) : "r"(a), "r"(b)); return r; }
__device__ __forceinline__ uint32_t mul_bf16x2(uint32_t a, uint32_t b) { uint32_t r; asm("mul.rn.bf16x2 %0, %1, %2;" : "=r"(r) : "r"(a), "r"(b)); return r; }
__device__ __forceinline__ uint32_t nz(uint32_t w) { return w == 0u ? 0x8000u : w; }

__device__ __forceinline__ void ldg4(uint32_t* d, const uint4* p) {
  asm volatile("ld.relaxed.gpu.global.v4.b32 {%0,%1,%2,%3}, [%4];" : "=r"(d[0]), "=r"(d[1]), "=r"(d[2]), "=r"(d[3]) : "l"(p) : "memory");
}
__device__ __forceinline__ void ldg2(uint32_t* d, const void* p) {
  asm volatile("ld.relaxed.gpu.global.v2.b32 {%0,%1}, [%2];" : "=r"(d[0]), "=r"(d[1]) : "l"(p) : "memory");
}
__device__ __forceinline__ void stg4(uint4* p, uint32_t a, uint32_t b, uint32_t c, uint32_t d) {
  asm volatile("st.relaxed.gpu.global.v4.b32 [%0], {%1,%2,%3,%4};" :: "l"(p), "r"(a), "r"(b), "r"(c), "r"(d) : "memory");
}
__device__ __forceinline__ void stg2(void* p, uint32_t a, uint32_t b) {
  asm volatile("st.relaxed.gpu.global.v2.b32 [%0], {%1,%2};" :: "l"(p), "r"(a), "r"(b) : "memory");
}
__device__ __forceinline__ void sts4(uint32_t a, const uint32_t* o) { asm volatile("st.shared.v4.b32 [%0], {%1,%2,%3,%4};" :: "r"(a), "r"(o[0]), "r"(o[1]), "r"(o[2]), "r"(o[3]) : "memory"); }
__device__ __forceinline__ void lds4(uint32_t a, uint32_t* o) { asm volatile("ld.shared.v4.b32 {%0,%1,%2,%3}, [%4];" : "=r"(o[0]), "=r"(o[1]), "=r"(o[2]), "=r"(o[3]) : "r"(a) : "memory"); }
__device__ __forceinline__ void lds2(uint32_t a, uint32_t* o) { asm volatile("ld.shared.v2.b32 {%0,%1}, [%2];" : "=r"(o[0]), "=r"(o[1]) : "r"(a) : "memory"); }
__device__ __forceinline__ void cp16(uint32_t dst, const void* src) { asm volatile("cp.async.cg.shared.global [%0], [%1], 16;" :: "r"(dst), "l"(src) : "memory"); }
__device__ __forceinline__ void cp_wait() { asm volatile("cp.async.wait_all;" ::: "memory"); }
__device__ __forceinline__ float rcp(float x) { float y; asm("rcp.approx.ftz.f32 %0, %1;" : "=f"(y) : "f"(x)); return y; }
__device__ __forceinline__ void sts1(uint32_t a, uint32_t v) { asm volatile("st.shared.b32 [%0], %1;" :: "r"(a), "r"(v) : "memory"); }
__device__ __forceinline__ void ldsm4(uint32_t a, uint32_t& r0, uint32_t& r1, uint32_t& r2, uint32_t& r3) {
  asm volatile("ldmatrix.sync.aligned.m8n8.x4.shared.b16 {%0,%1,%2,%3}, [%4];" : "=r"(r0), "=r"(r1), "=r"(r2), "=r"(r3) : "r"(a) : "memory");
}
__device__ __forceinline__ void ldsm4t(uint32_t a, uint32_t& r0, uint32_t& r1, uint32_t& r2, uint32_t& r3) {
  asm volatile("ldmatrix.sync.aligned.m8n8.x4.trans.shared.b16 {%0,%1,%2,%3}, [%4];" : "=r"(r0), "=r"(r1), "=r"(r2), "=r"(r3) : "r"(a) : "memory");
}
__device__ __forceinline__ void mma16(float* c, uint32_t a0, uint32_t a1, uint32_t a2, uint32_t a3, uint32_t b0, uint32_t b1) {
  asm("mma.sync.aligned.m16n8k16.row.col.f32.bf16.bf16.f32 {%0,%1,%2,%3}, {%4,%5,%6,%7}, {%8,%9}, {%0,%1,%2,%3};"
    : "+f"(c[0]), "+f"(c[1]), "+f"(c[2]), "+f"(c[3]) : "r"(a0), "r"(a1), "r"(a2), "r"(a3), "r"(b0), "r"(b1));
}
__device__ __forceinline__ void mma8(float* c, uint32_t a0, uint32_t a1, uint32_t b0) {
  asm("mma.sync.aligned.m16n8k8.row.col.f32.bf16.bf16.f32 {%0,%1,%2,%3}, {%4,%5}, {%6}, {%0,%1,%2,%3};"
    : "+f"(c[0]), "+f"(c[1]), "+f"(c[2]), "+f"(c[3]) : "r"(a0), "r"(a1), "r"(b0));
}
__device__ __forceinline__ float quad_sum(float v) { v += __shfl_xor_sync(~0u, v, 1); v += __shfl_xor_sync(~0u, v, 2); return v; }
__device__ __forceinline__ float quad_max(float v) { v = fmaxf(v, __shfl_xor_sync(~0u, v, 1)); v = fmaxf(v, __shfl_xor_sync(~0u, v, 2)); return v; }
template <int N> __device__ __forceinline__ void pin(float (&d)[N]) {
#pragma unroll
  for (int i = 0; i < N; i++) asm volatile("" : "+f"(d[i]) :: "memory");
}
#define SPIN_GUARD(n) if (++(n) > SPIN_MAX) break

template <int NG> __device__ __forceinline__ void publish_stats(uint4* dst, const float* y, uint32_t tag, int lane) {
  float s0 = 0.f, s1 = 0.f;
#pragma unroll
  for (int g = 0; g < NG; g++) { s0 += y[4 * g] + y[4 * g + 1]; s1 += y[4 * g + 2] + y[4 * g + 3]; }
  s0 = quad_sum(s0); s1 = quad_sum(s1);
  const float m0 = s0 * (1.f / (8 * NG)), m1 = s1 * (1.f / (8 * NG));
  float q0 = 0.f, q1 = 0.f, q2 = 0.f, q3 = 0.f;
#pragma unroll
  for (int g = 0; g < NG; g++) {
    const float a = y[4 * g] - m0, b = y[4 * g + 1] - m0, c = y[4 * g + 2] - m1, d = y[4 * g + 3] - m1;
    q0 = fmaf(a, a, q0); q1 = fmaf(b, b, q1); q2 = fmaf(c, c, q2); q3 = fmaf(d, d, q3);
  }
  q0 = quad_sum(q0 + q1); q2 = quad_sum(q2 + q3);
  if ((lane & 3) == 0)
    stg4(dst + (lane >> 2), (__float_as_uint(s0) & ~1u) | tag, __float_as_uint(q0), __float_as_uint(s1), __float_as_uint(q2));
}

__device__ __forceinline__ void put72(uint4* slab, int j, int lane, const uint32_t* v) {
  uint4* p = slab + ((9 * j + 1) >> 1) * 32;
  if (j & 1) {
    stg2((char*)(p - 16) + lane * 8, nz(v[0]), v[1]);
#pragma unroll
    for (int i = 0; i < 4; i++) stg4(p + lane + i * 32, nz(v[4 * i + 2]), v[4 * i + 3], v[4 * i + 4], v[4 * i + 5]);
  } else {
#pragma unroll
    for (int i = 0; i < 4; i++) stg4(p + lane + i * 32, nz(v[4 * i]), v[4 * i + 1], v[4 * i + 2], v[4 * i + 3]);
    stg2((char*)(p + 4 * 32) + lane * 8, nz(v[16]), v[17]);
  }
}
__device__ __forceinline__ void zero_share(uint4* slab, int j, int lane) {
  uint4* p = slab + j * 144 + lane;
#pragma unroll
  for (int i = 0; i < 4; i++) stg4(p + i * 32, 0u, 0u, 0u, 0u);
  if (lane < 16) stg4(p + 128, 0u, 0u, 0u, 0u);
}

struct Maps { CUtensorMap m[7]; };

struct Ring {
  uint32_t st, ph;
  __device__ __forceinline__ void next() { if (++st == NST) { st = 0; ph ^= 1; } }
};

#define STAMP(i) do {} while (0)

__device__ __forceinline__ void tma_box(uint32_t dst, const CUtensorMap* m, int col, int row, uint32_t bar, uint32_t expect) {
  asm volatile("{\n.reg .pred e, h;\nelect.sync _|e, 0xffffffff;\nsetp.ne.and.u32 h, %5, 0, e;\n"
               "@h mbarrier.arrive.expect_tx.shared::cta.b64 _, [%2], %5;\n"
               "@e cp.async.bulk.tensor.2d.shared::cluster.global.mbarrier::complete_tx::bytes [%0], [%1, {%3, %4}], [%2];\n}"
               :: "r"(dst), "l"(m), "r"(bar), "r"(col), "r"(row), "r"(expect) : "memory");
}

__global__ void __launch_bounds__(384, 1) mega_kernel(
    const __grid_constant__ Maps maps, uint4* __restrict__ scr,
    const __nv_bfloat16* __restrict__ x_in, __nv_bfloat16* __restrict__ out) {
  extern __shared__ __align__(1024) uint8_t smem[];
  const uint32_t sb = (uint32_t)__cvta_generic_to_shared(smem);
  const uint32_t full0 = sb + BARS, empty0 = full0 + 8 * NST, rem_full = empty0 + 8 * NST, park_free = rem_full + 8, kv_free = park_free + 8;
  const uint32_t c8_go = kv_free + 8, rstg_full = c8_go + 8, pbar0 = rstg_full + 8;
  const int w = __shfl_sync(~0u, threadIdx.x >> 5, 0), lane = threadIdx.x & 31;
  const int t = blockIdx.x >> 3, j = blockIdx.x & 7;
  const int r = lane >> 2, q = lane & 3;
  auto fetch_rem = [&] {
#pragma unroll 1
    for (int b = 0; b < 12; b++) {
      const int p = b / 3;
      tma_box(sb + RSTG + b * 3072, &maps.m[p == 3 ? 6 : 5], 72 * j + 64 + (p < 2 ? 576 * (p + 1) : 0), 192 * (b - 3 * p), rstg_full, b ? 0 : 36864);
    }
  };
  {
    const int sl = w < 8 ? w : j, ch = w < 8 ? j : 8;
    uint32_t v[16];
    if (w < 8 || w == 9) {
      const uint32_t* xr = (const uint32_t*)(x_in + (128 * t + 32 * (sl >> 1) + 2 * r + (sl & 1)) * 576 + 64 * ch + 2 * q);
#pragma unroll
      for (int g = 0; g < 8; g++) { v[2 * g] = __ldg(xr + 4 * g); v[2 * g + 1] = __ldg(xr + 8 * 576 + 4 * g); }
    }
    if (threadIdx.x == 256) {
      for (int i = 0; i < NST; i++) { mbar_init(full0 + 8 * i, 1); mbar_init(empty0 + 8 * i, 8); }
      mbar_init(rem_full, 64); mbar_init(park_free, 8); mbar_init(kv_free, 8); mbar_init(c8_go, 8); mbar_init(rstg_full, 1);
      for (int i = 0; i < 8; i++) mbar_init(pbar0 + 8 * i, 5);
      asm volatile("fence.mbarrier_init.release.cluster;" ::: "memory");
    }
    __syncthreads();
    if (w == 8) {
#pragma unroll 1
      for (int b = 0; b < 2 * NST; b++)
        tma_box(sb + b * 8192, &maps.m[0], 72 * j + 576 + 576 * (b & 1), 64 * (b >> 1), full0 + (b >> 1) * 8, (b & 1) ? 0 : STAGE);
    } else if (w == 10) {
      fetch_rem();
    } else if (w != 11) {
      uint4* p = scr + OFF_X + (t * 8 + sl) * SLAB + 4 * ch * 32 + lane;
#pragma unroll
      for (int i = 0; i < 4; i++) stg4(p + i * 32, nz(v[4 * i]), v[4 * i + 1], v[4 * i + 2], v[4 * i + 3]);
      float y[32];
#pragma unroll
      for (int i = 0; i < 16; i++) { y[2 * i] = bf_lo(v[i]); y[2 * i + 1] = bf_hi(v[i]); }
      publish_stats<8>(scr + OFF_S + (t * 8 + sl) * 96 + ch * 8, y, 1u, lane);
    }
  }

  if (w >= 8) {
    asm volatile("setmaxnreg.dec.sync.aligned.u32 24;");
    if (w == 8) {
      Ring rg{0, 0};
      int b = 2 * NST;
#pragma unroll 1
      for (int seg = 0; seg < 34; seg++) {
        const int n = seg >= 17 ? seg - 17 : seg;
        int ma, mb, ca, cb, row = 0;
        if (n < 3) { ma = mb = n == 2; ca = 72 * j + (n == 0 ? 576 : 0); cb = ca + 576; }
        else if (n < 12) { ma = 3; mb = 2; ca = cb = 576 * j + 64 * (n - 3); }
        else { ma = mb = 4; ca = n == 12 ? 512 : ((j + 2 * n) & 7) * 64; cb = ((j + 2 * n + 1) & 7) * 64; row = 576 * j; }
        const bool zip = n == 0 || n == 3;
        const int nb = (n == 1 || n == 2 || n == 16) ? 9 : 18;
#pragma unroll 1
        for (; b < nb; b++) {
          const bool second = zip ? (b & 1) : b >= 9, last = b == nb - 1;
          const int kb = zip ? b >> 1 : second ? b - 9 : b;
          if (!(b & 1)) mbar_wait(empty0 + rg.st * 8, rg.ph);
          tma_box(sb + rg.st * STAGE + (b & 1) * 8192, &maps.m[second ? mb : ma], second ? cb : ca, row + 64 * kb, full0 + rg.st * 8,
                  (b & 1) ? 0 : last ? STAGE / 2 : STAGE);
          if ((b & 1) || last) rg.next();
        }
        b = 0;
      }
    } else if (w == 9) {
      const uint32_t stg = sb + HSTG + lane * 16;
#pragma unroll 1
      for (int it = 0; it < 8; it++) {
        const int layer = it >> 2, i = it & 3;
        if (i == 0) mbar_wait(c8_go, layer);
        uint4* xb = scr + OFF_X + ((4 + layer) * 128 + t * 8 + j) * SLAB + (32 + i) * 32 + lane;
        cp16(stg + 4096, xb);
        int n = 0;
        while (true) {
#pragma unroll 1
          for (int s = 0; s < 8; s++) cp16(stg + s * 512, scr + OFF_P + (t * 64 + j + s * 8) * SLAB + (32 + i) * 32 + lane);
          cp_wait();
          uint32_t bad = 0;
#pragma unroll 1
          for (int s = 0; s < 8; s++) { uint32_t v[2]; lds2(stg + s * 512, v); bad |= v[0] ^ (1 - layer); }
          if (__all_sync(~0u, (bad & 1u) == 0u)) break;
          __nanosleep(200);
          SPIN_GUARD(n);
        }
        stg4(xb, 0u, 0u, 0u, 0u);
        uint32_t x[4];
#pragma unroll
        for (int h = 0; h < 2; h++) {
          float a0 = 0.f, a1 = 0.f, a2 = 0.f, a3 = 0.f;
#pragma unroll 1
          for (int s = 0; s < 9; s++) { uint32_t v[2]; lds2(stg + s * 512 + h * 8, v); a0 += bf_lo(v[0]); a1 += bf_hi(v[0]); a2 += bf_lo(v[1]); a3 += bf_hi(v[1]); }
          x[2 * h] = pack_bf16(a0, a1); x[2 * h + 1] = pack_bf16(a2, a3);
        }
        if (layer == 0) {
          stg4(xb - 3 * 128 * SLAB, nz(x[0]), x[1], x[2], x[3]);
          sts4(stg + 4608 + i * 512, x);
        } else {
          uint32_t* o = (uint32_t*)(out + (128 * t + 32 * (j >> 1) + 2 * r + (j & 1)) * 576 + 512 + 16 * i + 2 * q);
          o[0] = x[0]; o[8 * 576] = x[1]; o[4] = x[2]; o[8 * 576 + 4] = x[3];
        }
        if (it == 3) {
          float s0 = 0.f, s1 = 0.f, q0 = 0.f, q1 = 0.f;
#pragma unroll 1
          for (int g = 0; g < 8; g++) { uint32_t v[2]; lds2(stg + 4608 + (g >> 1) * 512 + (g & 1) * 8, v); s0 += bf_lo(v[0]) + bf_hi(v[0]); s1 += bf_lo(v[1]) + bf_hi(v[1]); }
          s0 = quad_sum(s0); s1 = quad_sum(s1);
#pragma unroll 1
          for (int g = 0; g < 8; g++) {
            uint32_t v[2]; lds2(stg + 4608 + (g >> 1) * 512 + (g & 1) * 8, v);
            const float a = fmaf(s0, -1.f / 64, bf_lo(v[0])), b = fmaf(s0, -1.f / 64, bf_hi(v[0])), c = fmaf(s1, -1.f / 64, bf_lo(v[1])), d = fmaf(s1, -1.f / 64, bf_hi(v[1]));
            q0 = fmaf(a, a, fmaf(b, b, q0)); q1 = fmaf(c, c, fmaf(d, d, q1));
          }
          q0 = quad_sum(q0); q1 = quad_sum(q1);
          if (q == 0) stg4(scr + OFF_S + (t * 8 + j) * 96 + 64 + r, __float_as_uint(s0) & ~1u, __float_as_uint(q0), __float_as_uint(s1), __float_as_uint(q1));
        }
      }
    } else {
#pragma unroll 1
      for (int layer = 0; layer < 2; layer++) {
        if (layer && w == 10) { mbar_wait(park_free, 0); fetch_rem(); }
        mbar_wait(rstg_full, layer);
#pragma unroll 1
        for (int i = threadIdx.x - 320; i < 2304; i += 64) {
          const int p = i / 576, k = i - 576 * p, s = k >> 4, rr = k & 7;
          uint32_t v[4];
          lds4(sb + RSTG + i * 16, v);
          sts4(sb + REM + p * 10240 + (s >> 3) * 2048 + ((k >> 3) & 1) * 1024 + rr * 128 + (((s & 7) ^ rr) << 4), v);
        }
        asm volatile("fence.proxy.async.shared::cta;" ::: "memory");
        mbar_arrive(rem_full);
        if (layer) mbar_wait(kv_free, 0);
        if (t > 0) {
#pragma unroll 1
          for (int kv = 0; kv < 2; kv++) {
            uint4* hp = scr + OFF_H + ((layer * 128 + t * 8 + j) * 4 + (w - 10) * 2 + kv) * 96 + lane;
            uint32_t hl[12];
            int n = 0;
            while (true) {
              ldg4(hl, hp); ldg4(hl + 4, hp + 32); ldg4(hl + 8, hp + 64);
              if (__all_sync(~0u, hl[0] != 0u && hl[4] != 0u && hl[8] != 0u)) break;
              __nanosleep(100);
              SPIN_GUARD(n);
            }
#pragma unroll
            for (int g = 0; g < 9; g++) sts1(sb + KVS + kv * 20736 + (w - 10) * 10368 + r * 144 + g * 16 + q * 4, hl[g]);
#pragma unroll
            for (int i = 0; i < 3; i++) stg4(hp + i * 32, 0u, 0u, 0u, 0u);
          }
        }
        asm volatile("bar.arrive 1, 192;" ::: "memory");
      }
    }
  } else {
    asm volatile("setmaxnreg.inc.sync.aligned.u32 240;");
    Ring rg{0, 0};
    uint32_t prev = 0;
    uint32_t X[144];
    float rs0, rs1;
    uint32_t mean0, mean1;
    auto release = [&](uint32_t st) { if (lane == 0) mbar_arrive(empty0 + st * 8); };
    auto load_kb = [&](bool split, int kb, const uint4* src) {
#pragma unroll
      for (int k = 4 * kb; k < 4 * kb + 4; k++) {
        if (split && k % 9 == 4) { const char* lo = (const char*)(src + k * 32) - lane * 8; ldg2(X + 4 * k, lo); ldg2(X + 4 * k + 2, lo + 256); }
        else ldg4(X + 4 * k, src + k * 32);
      }
    };
    auto next_kb = [&](bool split, bool center, int kb, const uint4* src) {
      int n = 0;
      while (true) {
        bool ok = true;
#pragma unroll
        for (int k = 4 * kb; k < 4 * kb + 4; k++) { ok = ok && X[4 * k] != 0u; if (split && k % 9 == 4) ok = ok && X[4 * k + 2] != 0u; }
        if (__all_sync(~0u, ok)) break;
        SPIN_GUARD(n);
        load_kb(split, kb, src);
      }
      if (kb + GD < 9) load_kb(split, kb + GD, src);
      if (center) {
#pragma unroll
        for (int i = 16 * kb; i < 16 * kb + 16; i++) X[i] = sub_bf16x2(X[i], (i & 1) ? mean1 : mean0);
      }
    };
#pragma unroll 1
    for (int layer = 0; layer < 2; layer++) {
      const uint32_t tag = 1 - layer;
      uint4* const xbase = scr + OFF_X + (layer * 128 + t * 8 + w) * SLAB;
      auto begin_gather = [&](int kind) {
        uint32_t s[3][4];
        const uint4* p = scr + OFF_S + (kind * 128 + t * 8 + w) * 96 + q * 8 + r;
        int n = 0;
        s[2][0] = tag; s[2][1] = s[2][2] = s[2][3] = 0u;
        STAMP(kind * 8 + 0);
        while (true) {
          ldg4(s[0], p); ldg4(s[1], p + 32);
          if (kind == 0 && q == 0) ldg4(s[2], p + 64);
          if (__all_sync(~0u, ((s[0][0] ^ tag) | (s[1][0] ^ tag) | (s[2][0] ^ tag)) % 2u == 0u)) break;
          SPIN_GUARD(n);
        }
        STAMP(kind * 8 + 1);
#pragma unroll
        for (int kb = 0; kb < GD; kb++) load_kb(kind != 0, kb, xbase + kind * 256 * SLAB + lane);
        if (kind != 1) {
          const int ns = kind == 0 ? 3 : 2;
          float t0 = 0.f, t1 = 0.f;
#pragma unroll
          for (int i = 0; i < ns; i++) { t0 += __uint_as_float(s[i][0]); t1 += __uint_as_float(s[i][2]); }
          const float m0 = quad_sum(t0) * (1.f / 576), m1 = quad_sum(t1) * (1.f / 576);
          const float cnt = kind == 0 ? 64.f : 72.f;
          float v0 = 0.f, v1 = 0.f;
#pragma unroll
          for (int i = 0; i < ns; i++) {
            const float c = (i < 2 || q == 0) ? cnt : 0.f;
            const float d0 = fmaf(__uint_as_float(s[i][0]), 1.f / cnt, -m0), d1 = fmaf(__uint_as_float(s[i][2]), 1.f / cnt, -m1);
            v0 += fmaf(d0 * d0, c, __uint_as_float(s[i][1])); v1 += fmaf(d1 * d1, c, __uint_as_float(s[i][3]));
          }
          rs0 = rsqrtf(fmaf(quad_sum(v0), 1.f / 576, 1e-5f)); rs1 = rsqrtf(fmaf(quad_sum(v1), 1.f / 576, 1e-5f));
          mean0 = pack_bf16(m0, m0); mean1 = pack_bf16(m1, m1);
        }
      };
      auto box72 = [&](float (&a)[36], int part, int kb, int half) {
        const uint32_t base = sb + rg.st * STAGE + half * 8192;
        const uint64_t d0 = DESC_HI | ((base >> 4) + (((sb + REM + part * 10240 + (kb >> 1) * 2048 + (kb & 1) * 64 - base) >> 4) << 16));
#pragma unroll
        for (int i = 0; i < 4; i++) wgmma_rs_n72(a, X + 4 * (4 * kb + i), d0 - (uint64_t)(i * ((127u << 16) - 128u)), kb + i != 0);
      };
      auto solo72 = [&](float (&a)[36], int part, auto&& pre) {
#pragma unroll
        for (int kb = 0; kb < 9; kb++) {
          pre(kb);
          if (!(kb & 1)) mbar_wait(full0 + rg.st * 8, rg.ph);
          wg_fence();
          box72(a, part, kb, kb & 1);
          wg_commit();
          wg_wait<1>();
          if (kb > 0 && !(kb & 1)) release(prev);
          if ((kb & 1) || kb == 8) { prev = rg.st; rg.next(); }
        }
      };
      const uint32_t kvrow = sb + KVS + (w & 1) * 10368 + (16 * (w >> 1)) * 144;
      uint32_t Q[18];
      begin_gather(0);
      mbar_wait(rem_full, layer);
      {
        float acc[36], acc2[36];
#pragma unroll
        for (int kb = 0; kb < 9; kb++) {
          next_kb(false, true, kb, xbase + lane);
          mbar_wait(full0 + rg.st * 8, rg.ph);
          wg_fence();
          box72(acc, 0, kb, 0); box72(acc2, 1, kb, 1);
          wg_commit();
          wg_wait<1>();
          if (kb > 0) release(prev);
          if (kb == 1) sts4(sb + PARK + w * 512 + lane * 16, X);
          prev = rg.st; rg.next();
        }
        wg_wait<0>();
        release(prev);
        STAMP(2);
        auto put_kv = [&](float (&a)[36], int part) {
          pin(a);
          uint32_t hl[9];
          const uint32_t dst = kvrow + part * 20736 + (8 + r) * 144 + q * 4;
#pragma unroll
          for (int g = 0; g < 9; g++) {
            hl[g] = pack_bf16(a[4 * g + 2] * rs1, a[4 * g + 3] * rs1);
            sts1(dst + g * 16, pack_bf16(a[4 * g] * rs0, a[4 * g + 1] * rs0)); sts1(dst + 8 * 144 + g * 16, hl[g]);
          }
          if (w >= 6 && t < 15) {
            uint4* hp = scr + OFF_H + ((layer * 128 + (t + 1) * 8 + j) * 4 + (w & 1) * 2 + part) * 96 + lane;
            stg4(hp, nz(hl[0]), hl[1], hl[2], hl[3]); stg4(hp + 32, nz(hl[4]), hl[5], hl[6], hl[7]); stg4(hp + 64, nz(hl[8]), 0u, 0u, 0u);
          }
        };
        put_kv(acc2, 1);
        lds4(sb + PARK + w * 512 + lane * 16, X);
        put_kv(acc, 0);
        if (w < 4) asm volatile("bar.arrive 2, 256;" ::: "memory");
        solo72(acc, 2, [](int) {});
        wg_wait<0>();
        release(prev);
        pin(acc);
        STAMP(3);
#pragma unroll
        for (int g = 0; g < 9; g++) {
          Q[2 * g] = pack_bf16(acc[4 * g] * rs0, acc[4 * g + 1] * rs0); Q[2 * g + 1] = pack_bf16(acc[4 * g + 2] * rs1, acc[4 * g + 3] * rs1);
        }
      }
      if (w < 4) asm volatile("bar.sync 1, 192;" ::: "memory");
      else asm volatile("bar.sync 2, 256;" ::: "memory");
      STAMP(4);
      uint32_t O[18];
      {
        const bool edge = (t == 0 && w < 2);
        uint32_t row[3];
#pragma unroll
        for (int nt = 0; nt < 3; nt++) row[nt] = kvrow + (8 * nt + (lane & 7)) * 144;
        if (edge) row[0] = sb + KVS + 8 * 144;
        const uint32_t rlast = ((lane >> 3) == 0 ? row[0] : (lane >> 3) == 1 ? row[1] : row[2]) + 128;
        uint32_t K[3][9], V[3][9], dummy;
#pragma unroll
        for (int nt = 0; nt < 3; nt++) {
          ldsm4(row[nt] + (lane >> 3) * 16, K[nt][0], K[nt][1], K[nt][2], K[nt][3]);
          ldsm4(row[nt] + 64 + (lane >> 3) * 16, K[nt][4], K[nt][5], K[nt][6], K[nt][7]);
        }
        ldsm4(rlast, K[0][8], K[1][8], K[2][8], dummy);
#pragma unroll
        for (int nt = 0; nt < 3; nt++) {
          ldsm4t(row[nt] + 20736 + (lane >> 3) * 16, V[nt][0], V[nt][1], V[nt][2], V[nt][3]);
          ldsm4t(row[nt] + 20736 + 64 + (lane >> 3) * 16, V[nt][4], V[nt][5], V[nt][6], V[nt][7]);
        }
        ldsm4t(rlast + 20736, V[0][8], V[1][8], V[2][8], dummy);
        const bool up0 = 2 * q > r, up1 = 2 * q + 1 > r;
        const float sc = 0.23570226039551584f * 1.4426950408889634f;
        const float neg = -1e9f * 1.4426950408889634f;
        float Of[9][4];
#pragma unroll
        for (int h = 0; h < 4; h++) {
          const uint32_t a0 = q >= h ? Q[4 * h] : 0u, a1 = q >= h ? Q[4 * h + 1] : 0u;
          const uint32_t a4 = q <= h ? Q[4 * h + 4] : 0u, a5 = q <= h ? Q[4 * h + 5] : 0u;
          float S[3][4];
#pragma unroll
          for (int nt = 0; nt < 3; nt++) {
            S[nt][0] = S[nt][1] = S[nt][2] = S[nt][3] = 0.f;
            mma16(S[nt], a0, a1, Q[4 * h + 2], Q[4 * h + 3], K[nt][2 * h], K[nt][2 * h + 1]);
            mma8(S[nt], a4, a5, K[nt][2 * h + 2]);
          }
          float s00 = (up0 ? S[0][0] : S[1][0]) * sc, s01 = (up1 ? S[0][1] : S[1][1]) * sc;
          const float s10 = (up0 ? S[1][2] : S[2][2]) * sc, s11 = (up1 ? S[1][3] : S[2][3]) * sc;
          if (edge && up0) s00 = neg;
          if (edge && up1) s01 = neg;
          const float m0 = quad_max(fmaxf(s00, s01)), m1 = quad_max(fmaxf(s10, s11));
          float p00 = ex2(s00 - m0), p01 = ex2(s01 - m0), p10 = ex2(s10 - m1), p11 = ex2(s11 - m1);
          const float i0 = rcp(quad_sum(p00 + p01)), i1 = rcp(quad_sum(p10 + p11));
          p00 *= i0; p01 *= i0; p10 *= i1; p11 *= i1;
          const uint32_t pa = pack_bf16(up0 ? p00 : 0.f, up1 ? p01 : 0.f), pb = pack_bf16(up0 ? 0.f : p00, up1 ? 0.f : p01);
          const uint32_t pc = pack_bf16(up0 ? p10 : 0.f, up1 ? p11 : 0.f), pd = pack_bf16(up0 ? 0.f : p10, up1 ? 0.f : p11);
#pragma unroll
          for (int gi = 0; gi < 3; gi++) {
            const int g = 2 * h + gi;
            float o[4] = {0.f, 0.f, 0.f, 0.f};
            mma16(o, pa, 0u, pb, pc, V[0][g], V[1][g]);
            mma8(o, 0u, pd, V[2][g]);
#pragma unroll
            for (int e = 0; e < 4; e++) Of[g][e] = (gi == 0 && h > 0 && q < h) ? Of[g][e] : o[e];
          }
        }
#pragma unroll
        for (int g = 0; g < 9; g++) { O[2 * g] = pack_bf16(Of[g][0], Of[g][1]); O[2 * g + 1] = pack_bf16(Of[g][2], Of[g][3]); }
      }
      put72(xbase + 256 * SLAB, j, lane, O);
      if (q == 0) stg4(scr + OFF_S + (128 + t * 8 + w) * 96 + j * 8 + r, tag, 0u, 0u, 0u);
      {
        uint32_t res[18];
        const char* p = (const char*)(xbase + lane) + ((9 * j) >> 1) * 512 + (j & 1) * 8;
#pragma unroll
        for (int g = 0; g < 9; g++) ldg2(res + 2 * g, p + (g >> 1) * 512 + ((g & 1) ? ((j & 1) ? 504 : 8) : 0));
        begin_gather(1);
        float acc[36];
        solo72(acc, 3, [&](int kb) { next_kb(true, false, kb, xbase + 256 * SLAB + lane); });
        wg_wait<0>();
        release(prev);
        pin(acc);
        STAMP(10);
#pragma unroll
        for (int i = 0; i < 18; i++) {
          acc[2 * i] += bf_lo(res[i]); acc[2 * i + 1] += bf_hi(res[i]);
          res[i] = pack_bf16(acc[2 * i], acc[2 * i + 1]);
        }
        put72(xbase + 512 * SLAB, j, lane, res);
        publish_stats<9>(scr + OFF_S + (256 + t * 8 + w) * 96 + j * 8, acc, tag, lane);
      }
      float aA[32], aB[32];
      const uint32_t hp = sb + PARK + w * 512 + lane * 16;
      begin_gather(2);
#pragma unroll
      for (int kb = 0; kb < 9; kb++) {
        next_kb(true, true, kb, xbase + 512 * SLAB + lane);
        mbar_wait(full0 + rg.st * 8, rg.ph);
        const uint64_t desc = DESC_HI | ((sb + rg.st * STAGE) >> 4);
        wg_fence();
#pragma unroll
        for (int i = 0; i < 4; i++) wgmma_rs_n64(aA, X + 4 * (4 * kb + i), desc + i * 128, kb + i != 0);
#pragma unroll
        for (int i = 0; i < 4; i++) wgmma_rs_n64(aB, X + 4 * (4 * kb + i), desc + 512 + i * 128, kb + i != 0);
        wg_commit();
        wg_wait<1>();
        if (kb > 0) release(prev);
        prev = rg.st; rg.next();
      }
      zero_share(xbase, j, lane);
      zero_share(xbase + 256 * SLAB, j, lane);
      wg_wait<0>();
      STAMP(20);
      auto pack8 = [&](float (&a)[32], int p, uint32_t* o) {
#pragma unroll
        for (int e = 0; e < 8; e++) asm volatile("" : "+f"(a[8 * p + e]) :: "memory");
#pragma unroll
        for (int e = 0; e < 4; e++) o[e] = pack_bf16(a[8 * p + 2 * e], a[8 * p + 2 * e + 1]);
      };
      const float ka0 = 0.7978845608028654f * rs0, kb0 = 0.044715f * ka0 * rs0 * rs0, ku0 = 0.5f * rs0 * rs0;
      const float ka1 = 0.7978845608028654f * rs1, kb1 = 0.044715f * ka1 * rs1 * rs1, ku1 = 0.5f * rs1 * rs1;
      auto packu8 = [&](int p, uint32_t* o) {
#pragma unroll
        for (int e = 0; e < 8; e++) asm volatile("" : "+f"(aA[8 * p + e]) :: "memory");
#pragma unroll
        for (int e = 0; e < 4; e++) o[e] = pack_bf16(aA[8 * p + 2 * e] * ((e & 1) ? ku1 : ku0), aA[8 * p + 2 * e + 1] * ((e & 1) ? ku1 : ku0));
      };
      auto geglu8 = [&](int p, uint32_t* u) {
#pragma unroll
        for (int e = 0; e < 8; e++) asm volatile("" : "+f"(aB[8 * p + e]) :: "memory");
        float h[8];
#pragma unroll
        for (int e = 0; e < 8; e++) {
          const float g = aB[8 * p + e];
          h[e] = fmaf(g, tanh_ap(g * fmaf(g * g, (e & 2) ? kb1 : kb0, (e & 2) ? ka1 : ka0)), g);
        }
#pragma unroll
        for (int e = 0; e < 4; e++) u[e] = mul_bf16x2(pack_bf16(h[2 * e], h[2 * e + 1]), u[e]);
      };
      auto box = [&](int b, auto&& filler) {
        const int kb = b < 9 ? b : b - 9;
        if (!(b & 1)) mbar_wait(full0 + rg.st * 8, rg.ph);
        const uint64_t desc = DESC_HI | ((sb + rg.st * STAGE + (b & 1) * 8192) >> 4);
        wg_fence();
#pragma unroll
        for (int i = 0; i < 4; i++) {
          if (b < 9) wgmma_rs_n64(aA, X + 4 * (4 * kb + i), desc + i * 128, kb + i != 0);
          else wgmma_rs_n64(aB, X + 4 * (4 * kb + i), desc + i * 128, kb + i != 0);
          if (i == FPOS) filler();
        }
        wg_commit();
        if (b & 1) { if (W2) wg_wait<1>(); prev = rg.st; rg.next(); } else { wg_wait<1>(); release(prev); }
      };
      auto nop = [] {};
      auto step = [&](int st, auto&& filler) { box(2 * st, nop); box(2 * st + 1, filler); };
#pragma unroll
      for (int p = 0; p < 4; p++) { uint32_t o[4]; packu8(p, o); sts4(hp + p * 4096, o); }
      box(0, nop);
#pragma unroll 1
      for (int c = 1;; c++) {
        const uint32_t hc = hp + c * 4 * 4096;
#pragma unroll
        for (int b = 1; b < 18; b++) box(b, [&] {
          if ((b & 1) && b < 8) { uint32_t o[4]; const uint32_t a = hc - (4 - (b >> 1)) * 4096; lds4(a, o); geglu8(b >> 1, o); sts4(a, o); }
          if ((b & 1) && b > 10) { uint32_t o[4]; packu8((b - 11) >> 1, o); if (c < 8) sts4(hc + ((b - 11) >> 1) * 4096, o); } });
        if (c == 8) break;
        box(0, nop);
      }
      wg_wait<0>();
      STAMP(21);
#pragma unroll
      for (int s = 0; s < 32; s++) lds4(hp + s * 4096, X + 4 * s);
#pragma unroll
      for (int p = 0; p < 4; p++) packu8(p, X + 128 + 4 * p);
#pragma unroll
      for (int st = 0; st < 4; st++) step(st, [&] { geglu8(st, X + 128 + 4 * st); });
      STAMP(24);
      if (layer == 0 && lane == 0) mbar_arrive(park_free);
      int lane2 = lane;
      asm volatile("" : "+r"(lane2));
      uint4* const pw = scr + OFF_P + ((t * 8 + j) * 8 + w) * SLAB + lane2;
      const uint4* const pr = scr + OFF_P + (t * 64 + w) * SLAB + 4 * j * 32 + lane2;
      auto put_part = [&](float (&a)[32], int p, int chunk) {
        uint32_t o[4];
        pack8(a, p, o);
        stg4(pw + (chunk * 4 + p) * 32, (o[0] & ~1u) | tag, o[1], o[2], o[3]);
      };
      auto slot = [&](int p) { return sb + w * 2048 + (p < 4 ? PARK + (p - 1) * 16384 : KVS + (p - 4) * 16384); };
      auto fetch = [&](int p) {
        if (p > 0)
          asm volatile("{\n.reg .pred e;\nelect.sync _|e, 0xffffffff;\n"
                       "@e mbarrier.arrive.expect_tx.shared::cta.b64 _, [%2], 2048;\n"
                       "@e cp.async.bulk.shared::cluster.global.mbarrier::complete_tx::bytes [%0], [%1], 2048, [%2];\n}"
                       :: "r"(slot(p)), "l"(scr + OFF_P + (t * 64 + ((j - p) & 7) * 8 + w) * SLAB + 4 * j * 32), "r"(pbar0 + w * 8) : "memory");
      };
      uint4* const xb = xbase + 512 * SLAB + 4 * j * 32;
#pragma unroll 1
      for (int sp = 0;; sp++) {
        const int ca = sp == 0 ? 8 : ((j + 2 * sp) & 7), cb = (j + 2 * sp + 1) & 7;
        if (sp == 1 && layer == 0) mbar_wait(rem_full, 1);
#pragma unroll
        for (int st = 4; st < 9; st++) step(st, [&] {
          if (st == 5 || st == 6) { put_part(aA, 2 * (st - 5), ca); put_part(aA, 2 * (st - 5) + 1, ca); }
          if (st == 8) fetch(2 * sp - 1); });
        STAMP(25 + sp);
        if (sp == 3) break;
        if (sp == 2) asm volatile("{\n.reg .pred e;\nelect.sync _|e, 0xffffffff;\n@e cp.async.bulk.prefetch.L2.global [%0], 2048;\n}" :: "l"(xb) : "memory");
        if (sp == 1 && lane == 0) mbar_arrive(c8_go);
#pragma unroll
        for (int st = 0; st < 4; st++) step(st, [&] {
          if (st < 2) { put_part(aB, 2 * st, cb); put_part(aB, 2 * st + 1, cb); }
          if (st == 3) fetch(2 * sp); });
      }
      auto load_p = [&](int p, uint32_t* d) {
#pragma unroll
        for (int i = 0; i < 4; i++) ldg4(d + 4 * i, pr + ((j - p) & 7) * 8 * SLAB + i * 32);
      };
#pragma unroll
      for (int st = 0; st < 4; st++) step(st, [&] {
        if (st == 0) {
#pragma unroll
          for (int p = 0; p < 4; p++) put_part(aB, p, (j + 7) & 7);
        }
        if (st == 1) {
#pragma unroll
          for (int i = 0; i < 4; i++) {
            const bool split = j == 2 * i + 1;
            const char* l = (const char*)(xb + i * 32) + (split ? lane2 * 8 : lane2 * 16);
            ldg2(X + 4 * i, l); ldg2(X + 4 * i + 2, l + (split ? 256 : 8));
          }
          load_p(6, X + 16);
        }
        if (st == 3) load_p(7, X + 32); });
      {
        mbar_wait(full0 + rg.st * 8, rg.ph);
        const uint64_t desc = DESC_HI | ((sb + rg.st * STAGE) >> 4);
        wg_fence();
#pragma unroll
        for (int i = 0; i < 4; i++) wgmma_rs_n64(aA, X + 4 * (32 + i), desc + i * 128, 1);
        wg_commit();
        wg_wait<1>(); release(prev);
        prev = rg.st; rg.next();
        mbar_wait(pbar0 + w * 8, layer);
        wg_wait<0>(); release(prev);
        pin(aA);
      }
      STAMP(22);
      {
        const uint32_t eye = r == 2 * q ? 0x3f80u : r == 2 * q + 1 ? 0x3f800000u : 0u;
        auto add_p = [&](int p, uint32_t* d) {
          int n = 0;
          while (!__all_sync(~0u, (((d[0] ^ tag) | (d[4] ^ tag) | (d[8] ^ tag) | (d[12] ^ tag)) & 1u) == 0u)) { SPIN_GUARD(n); load_p(p, d); }
#pragma unroll
          for (int g = 0; g < 8; g++) mma8(aA + 4 * g, d[2 * g], d[2 * g + 1], eye);
        };
#pragma unroll
        for (int p = 1; p < 6; p++)
#pragma unroll
          for (int i = 0; i < 4; i++) lds4(slot(p) + lane2 * 16 + i * 512, X + 32 + 16 * p + 4 * i);
#pragma unroll
        for (int g = 0; g < 8; g++) mma8(aA + 4 * g, X[2 * g], X[2 * g + 1], eye);
#pragma unroll
        for (int p = 1; p < 6; p++) add_p(p, X + 32 + 16 * p);
        add_p(6, X + 16); add_p(7, X + 32);
        uint32_t res[16];
#pragma unroll
        for (int i = 0; i < 16; i++) res[i] = pack_bf16(aA[2 * i], aA[2 * i + 1]);
        if (layer == 0) {
          uint4* p = xbase + 128 * SLAB + 4 * j * 32 + lane;
#pragma unroll
          for (int i = 0; i < 4; i++) stg4(p + i * 32, nz(res[4 * i]), res[4 * i + 1], res[4 * i + 2], res[4 * i + 3]);
          publish_stats<8>(scr + OFF_S + (t * 8 + w) * 96 + j * 8, aA, 0u, lane);
          if (lane == 0) mbar_arrive(kv_free);
        } else {
          uint32_t* o = (uint32_t*)(out + (128 * t + 32 * (w >> 1) + 2 * r + (w & 1)) * 576 + 64 * j + 2 * q);
#pragma unroll
          for (int g = 0; g < 8; g++) { o[4 * g] = res[2 * g]; o[8 * 576 + 4 * g] = res[2 * g + 1]; }
        }
#pragma unroll
        for (int i = 0; i < 4; i++) stg4(xb + lane + i * 32, 0u, 0u, 0u, 0u);
      }
      STAMP(23);
    }
  }
}

typedef CUresult (*EncodeFn)(CUtensorMap*, CUtensorMapDataType, cuuint32_t, void*, const cuuint64_t*, const cuuint64_t*,
                             const cuuint32_t*, const cuuint32_t*, CUtensorMapInterleave, CUtensorMapSwizzle,
                             CUtensorMapL2promotion, CUtensorMapFloatOOBfill);

CUtensorMap make_map(EncodeFn f, const void* p, uint64_t cols, uint64_t rows, bool rem = false) {
  CUtensorMap m;
  cuuint64_t dims[2] = {cols, rows};
  cuuint64_t str[1] = {cols * 2};
  cuuint32_t box[2] = {rem ? 8u : 64u, rem ? 192u : 64u};
  cuuint32_t es[2] = {1, 1};
  f(&m, CU_TENSOR_MAP_DATA_TYPE_BFLOAT16, 2, const_cast<void*>(p), dims, str, box, es, CU_TENSOR_MAP_INTERLEAVE_NONE,
    rem ? CU_TENSOR_MAP_SWIZZLE_NONE : CU_TENSOR_MAP_SWIZZLE_128B, CU_TENSOR_MAP_L2_PROMOTION_NONE, CU_TENSOR_MAP_FLOAT_OOB_FILL_NONE);
  return m;
}

}

extern "C" void kernel_launch(void* const* d_in, const int* in_sizes, int n_in, void* d_out, int out_size) {
  void* fn = nullptr;
  cudaDriverEntryPointQueryResult qr;
  cudaGetDriverEntryPoint("cuTensorMapEncodeTiled", &fn, cudaEnableDefault, &qr);
  EncodeFn enc = (EncodeFn)fn;
  Maps maps;
  maps.m[0] = make_map(enc, d_in[1], 1728, 576); maps.m[1] = make_map(enc, d_in[2], 576, 576);
  maps.m[2] = make_map(enc, d_in[4], 4608, 576); maps.m[3] = make_map(enc, d_in[5], 4608, 576); maps.m[4] = make_map(enc, d_in[6], 576, 4608);
  maps.m[5] = make_map(enc, d_in[1], 1728, 576, true); maps.m[6] = make_map(enc, d_in[2], 576, 576, true);
  void* scr = nullptr;
  cudaGetSymbolAddress(&scr, g_scratch);
  cudaFuncSetAttribute(mega_kernel, cudaFuncAttributeMaxDynamicSharedMemorySize, SMEM_BYTES);
  mega_kernel<<<128, 384, SMEM_BYTES>>>(maps, (uint4*)scr, (const __nv_bfloat16*)d_in[0], (__nv_bfloat16*)d_out);
}
```

```cpp
#include <cuda_runtime.h>
#include <cuda.h>
#include <cuda_bf16.h>
#include <stdint.h>

#define TRACE 0
#define FPOS 2
#define W2 0

namespace {

constexpr int NST = 6;
constexpr int STAGE = 16384;
constexpr int PARK = NST * STAGE;
constexpr int REM = PARK + 49152;
constexpr int KVS = REM + 40960;
constexpr int HSTG = KVS + 16384;
constexpr int BARS = KVS + 41472;
constexpr int TRC = BARS + 256;
constexpr int SMEM_BYTES = TRC + (TRACE ? 512 : 0);
static_assert(BARS >= PARK + 131072, "barriers overlap park");
static_assert(SMEM_BYTES <= 232448, "smem");

constexpr int SLAB = 36 * 32;
constexpr int SPIN_MAX = 1 << 17;
constexpr int GD = 3;
constexpr int OFF_X = 0;
constexpr int OFF_P = OFF_X + 6 * 128 * SLAB;
constexpr int OFF_S = OFF_P + 8 * 128 * SLAB;
constexpr int OFF_H = OFF_S + 3 * 128 * 96;
constexpr int OFF_R = OFF_H + 2 * 128 * 384;
constexpr int OFF_F = OFF_R + 8 * 2560;
constexpr int SCRATCH = OFF_F + 128 * 8;

}

__device__ uint4 g_scratch[SCRATCH];

namespace {

constexpr uint64_t DESC_HI = 0x4000004000000000ull;
__device__ __forceinline__ void wgmma_rs_n64(float (&d)[32], const uint32_t* a, uint64_t desc, int scale_d) {
  asm volatile("{\n.reg .pred p;\nsetp.ne.b32 p, %37, 0;\n"
    "wgmma.mma_async.sync.aligned.m64n64k16.f32.bf16.bf16 "
    "{%0, %1, %2, %3, %4, %5, %6, %7, %8, %9, %10, %11, %12, %13, %14, %15, %16, %17, %18, %19, %20, %21, %22, %23, %24, %25, %26, %27, %28, %29, %30, %31}, "
    "{%32, %33, %34, %35}, %36, p, 1, 1, 1;\n}\n"
    : "+f"(d[0]), "+f"(d[1]), "+f"(d[2]), "+f"(d[3]), "+f"(d[4]), "+f"(d[5]), "+f"(d[6]), "+f"(d[7]), "+f"(d[8]), "+f"(d[9]), "+f"(d[10]), "+f"(d[11]), "+f"(d[12]), "+f"(d[13]), "+f"(d[14]), "+f"(d[15]), "+f"(d[16]), "+f"(d[17]), "+f"(d[18]), "+f"(d[19]), "+f"(d[20]), "+f"(d[21]), "+f"(d[22]), "+f"(d[23]), "+f"(d[24]), "+f"(d[25]), "+f"(d[26]), "+f"(d[27]), "+f"(d[28]), "+f"(d[29]), "+f"(d[30]), "+f"(d[31])
    : "r"(a[0]), "r"(a[1]), "r"(a[2]), "r"(a[3]), "l"(desc), "r"(scale_d));
}
__device__ __forceinline__ void wgmma_rs_n72(float (&d)[36], const uint32_t* a, uint64_t desc, int scale_d) {
  asm volatile("{\n.reg .pred p;\nsetp.ne.b32 p, %41, 0;\n"
    "wgmma.mma_async.sync.aligned.m64n72k16.f32.bf16.bf16 "
    "{%0, %1, %2, %3, %4, %5, %6, %7, %8, %9, %10, %11, %12, %13, %14, %15, %16, %17, %18, %19, %20, %21, %22, %23, %24, %25, %26, %27, %28, %29, %30, %31, %32, %33, %34, %35}, "
    "{%36, %37, %38, %39}, %40, p, 1, 1, 1;\n}\n"
    : "+f"(d[0]), "+f"(d[1]), "+f"(d[2]), "+f"(d[3]), "+f"(d[4]), "+f"(d[5]), "+f"(d[6]), "+f"(d[7]), "+f"(d[8]), "+f"(d[9]), "+f"(d[10]), "+f"(d[11]), "+f"(d[12]), "+f"(d[13]), "+f"(d[14]), "+f"(d[15]), "+f"(d[16]), "+f"(d[17]), "+f"(d[18]), "+f"(d[19]), "+f"(d[20]), "+f"(d[21]), "+f"(d[22]), "+f"(d[23]), "+f"(d[24]), "+f"(d[25]), "+f"(d[26]), "+f"(d[27]), "+f"(d[28]), "+f"(d[29]), "+f"(d[30]), "+f"(d[31]), "+f"(d[32]), "+f"(d[33]), "+f"(d[34]), "+f"(d[35])
    : "r"(a[0]), "r"(a[1]), "r"(a[2]), "r"(a[3]), "l"(desc), "r"(scale_d));
}

__device__ __forceinline__ void mbar_init(uint32_t a, uint32_t c) { asm volatile("mbarrier.init.shared::cta.b64 [%0], %1;" :: "r"(a), "r"(c)); }
__device__ __forceinline__ void mbar_arrive(uint32_t a) { asm volatile("mbarrier.arrive.shared::cta.b64 _, [%0];" :: "r"(a) : "memory"); }
__device__ __forceinline__ void mbar_wait(uint32_t a, uint32_t ph) {
  asm volatile("{\n.reg .pred p;\n.reg .u32 n;\n"
               "mbarrier.try_wait.parity.shared::cta.b64 p, [%0], %1;\n@p bra D;\n"
               "mov.u32 n, 0;\n"
               "W: mbarrier.try_wait.parity.shared::cta.b64 p, [%0], %1;\n@p bra D;\n"
               "add.u32 n, n, 1;\nsetp.lt.u32 p, n, 4194304;\n@p bra W;\ntrap;\nD:\n}" :: "r"(a), "r"(ph) : "memory");
}
__device__ __forceinline__ void wg_fence() { asm volatile("wgmma.fence.sync.aligned;" ::: "memory"); }
__device__ __forceinline__ void wg_commit() { asm volatile("wgmma.commit_group.sync.aligned;" ::: "memory"); }
template <int N> __device__ __forceinline__ void wg_wait() { asm volatile("wgmma.wait_group.sync.aligned %0;" :: "n"(N) : "memory"); }
__device__ __forceinline__ float tanh_ap(float x) { float y; asm("tanh.approx.f32 %0, %1;" : "=f"(y) : "f"(x)); return y; }
__device__ __forceinline__ float ex2(float x) { float y; asm("ex2.approx.ftz.f32 %0, %1;" : "=f"(y) : "f"(x)); return y; }
__device__ __forceinline__ uint32_t pack_bf16(float lo, float hi) { uint32_t r; asm("cvt.rn.bf16x2.f32 %0, %1, %2;" : "=r"(r) : "f"(hi), "f"(lo)); return r; }
__device__ __forceinline__ float bf_lo(uint32_t v) { return __uint_as_float(v << 16); }
__device__ __forceinline__ float bf_hi(uint32_t v) { return __uint_as_float(v & 0xffff0000u); }
__device__ __forceinline__ uint32_t sub_bf16x2(uint32_t a, uint32_t b) { uint32_t r; asm("sub.rn.bf16x2 %0, %1, %2;" : "=r"(r) : "r"(a), "r"(b)); return r; }
__device__ __forceinline__ uint32_t mul_bf16x2(uint32_t a, uint32_t b) { uint32_t r; asm("mul.rn.bf16x2 %0, %1, %2;" : "=r"(r) : "r"(a), "r"(b)); return r; }
__device__ __forceinline__ uint32_t nz(uint32_t w) { return w == 0u ? 0x8000u : w; }

__device__ __forceinline__ void ldg4(uint32_t* d, const uint4* p) {
  asm volatile("ld.relaxed.gpu.global.v4.b32 {%0,%1,%2,%3}, [%4];" : "=r"(d[0]), "=r"(d[1]), "=r"(d[2]), "=r"(d[3]) : "l"(p) : "memory");
}
__device__ __forceinline__ void ldg2(uint32_t* d, const void* p) {
  asm volatile("ld.relaxed.gpu.global.v2.b32 {%0,%1}, [%2];" : "=r"(d[0]), "=r"(d[1]) : "l"(p) : "memory");
}
__device__ __forceinline__ void stg4(uint4* p, uint32_t a, uint32_t b, uint32_t c, uint32_t d) {
  asm volatile("st.relaxed.gpu.global.v4.b32 [%0], {%1,%2,%3,%4};" :: "l"(p), "r"(a), "r"(b), "r"(c), "r"(d) : "memory");
}
__device__ __forceinline__ void stg2(void* p, uint32_t a, uint32_t b) {
  asm volatile("st.relaxed.gpu.global.v2.b32 [%0], {%1,%2};" :: "l"(p), "r"(a), "r"(b) : "memory");
}
__device__ __forceinline__ void sts4(uint32_t a, const uint32_t* o) { asm volatile("st.shared.v4.b32 [%0], {%1,%2,%3,%4};" :: "r"(a), "r"(o[0]), "r"(o[1]), "r"(o[2]), "r"(o[3]) : "memory"); }
__device__ __forceinline__ void lds4(uint32_t a, uint32_t* o) { asm volatile("ld.shared.v4.b32 {%0,%1,%2,%3}, [%4];" : "=r"(o[0]), "=r"(o[1]), "=r"(o[2]), "=r"(o[3]) : "r"(a) : "memory"); }
__device__ __forceinline__ void lds2(uint32_t a, uint32_t* o) { asm volatile("ld.shared.v2.b32 {%0,%1}, [%2];" : "=r"(o[0]), "=r"(o[1]) : "r"(a) : "memory"); }
__device__ __forceinline__ float rcp(float x) { float y; asm("rcp.approx.ftz.f32 %0, %1;" : "=f"(y) : "f"(x)); return y; }
__device__ __forceinline__ void sts1(uint32_t a, uint32_t v) { asm volatile("st.shared.b32 [%0], %1;" :: "r"(a), "r"(v) : "memory"); }
__device__ __forceinline__ void ldsm4(uint32_t a, uint32_t& r0, uint32_t& r1, uint32_t& r2, uint32_t& r3) {
  asm volatile("ldmatrix.sync.aligned.m8n8.x4.shared.b16 {%0,%1,%2,%3}, [%4];" : "=r"(r0), "=r"(r1), "=r"(r2), "=r"(r3) : "r"(a) : "memory");
}
__device__ __forceinline__ void ldsm4t(uint32_t a, uint32_t& r0, uint32_t& r1, uint32_t& r2, uint32_t& r3) {
  asm volatile("ldmatrix.sync.aligned.m8n8.x4.trans.shared.b16 {%0,%1,%2,%3}, [%4];" : "=r"(r0), "=r"(r1), "=r"(r2), "=r"(r3) : "r"(a) : "memory");
}
__device__ __forceinline__ void mma16(float* c, uint32_t a0, uint32_t a1, uint32_t a2, uint32_t a3, uint32_t b0, uint32_t b1) {
  asm("mma.sync.aligned.m16n8k16.row.col.f32.bf16.bf16.f32 {%0,%1,%2,%3}, {%4,%5,%6,%7}, {%8,%9}, {%0,%1,%2,%3};"
    : "+f"(c[0]), "+f"(c[1]), "+f"(c[2]), "+f"(c[3]) : "r"(a0), "r"(a1), "r"(a2), "r"(a3), "r"(b0), "r"(b1));
}
__device__ __forceinline__ void mma8(float* c, uint32_t a0, uint32_t a1, uint32_t b0) {
  asm("mma.sync.aligned.m16n8k8.row.col.f32.bf16.bf16.f32 {%0,%1,%2,%3}, {%4,%5}, {%6}, {%0,%1,%2,%3};"
    : "+f"(c[0]), "+f"(c[1]), "+f"(c[2]), "+f"(c[3]) : "r"(a0), "r"(a1), "r"(b0));
}
__device__ __forceinline__ float quad_sum(float v) { v += __shfl_xor_sync(~0u, v, 1); v += __shfl_xor_sync(~0u, v, 2); return v; }
__device__ __forceinline__ float quad_max(float v) { v = fmaxf(v, __shfl_xor_sync(~0u, v, 1)); v = fmaxf(v, __shfl_xor_sync(~0u, v, 2)); return v; }
template <int N> __device__ __forceinline__ void pin(float (&d)[N]) {
#pragma unroll
  for (int i = 0; i < N; i++) asm volatile("" : "+f"(d[i]) :: "memory");
}
#define SPIN_GUARD(n) if (++(n) > SPIN_MAX) break

template <int NG> __device__ __forceinline__ void publish_stats(uint4* dst, const float* y, uint32_t tag, int lane) {
  float s0 = 0.f, s1 = 0.f;
#pragma unroll
  for (int g = 0; g < NG; g++) { s0 += y[4 * g] + y[4 * g + 1]; s1 += y[4 * g + 2] + y[4 * g + 3]; }
  s0 = quad_sum(s0); s1 = quad_sum(s1);
  const float m0 = s0 * (1.f / (8 * NG)), m1 = s1 * (1.f / (8 * NG));
  float q0 = 0.f, q1 = 0.f, q2 = 0.f, q3 = 0.f;
#pragma unroll
  for (int g = 0; g < NG; g++) {
    const float a = y[4 * g] - m0, b = y[4 * g + 1] - m0, c = y[4 * g + 2] - m1, d = y[4 * g + 3] - m1;
    q0 = fmaf(a, a, q0); q1 = fmaf(b, b, q1); q2 = fmaf(c, c, q2); q3 = fmaf(d, d, q3);
  }
  q0 = quad_sum(q0 + q1); q2 = quad_sum(q2 + q3);
  if ((lane & 3) == 0)
    stg4(dst + (lane >> 2), (__float_as_uint(s0) & ~1u) | tag, __float_as_uint(q0), __float_as_uint(s1), __float_as_uint(q2));
}

__device__ __forceinline__ void put72(uint4* slab, int j, int lane, const uint32_t* v) {
  uint4* p = slab + ((9 * j + 1) >> 1) * 32;
  if (j & 1) {
    stg2((char*)(p - 16) + lane * 8, nz(v[0]), v[1]);
#pragma unroll
    for (int i = 0; i < 4; i++) stg4(p + lane + i * 32, nz(v[4 * i + 2]), v[4 * i + 3], v[4 * i + 4], v[4 * i + 5]);
  } else {
#pragma unroll
    for (int i = 0; i < 4; i++) stg4(p + lane + i * 32, nz(v[4 * i]), v[4 * i + 1], v[4 * i + 2], v[4 * i + 3]);
    stg2((char*)(p + 4 * 32) + lane * 8, nz(v[16]), v[17]);
  }
}
__device__ __forceinline__ void zero_share(uint4* slab, int j, int lane) {
  uint4* p = slab + j * 144 + lane;
#pragma unroll
  for (int i = 0; i < 4; i++) stg4(p + i * 32, 0u, 0u, 0u, 0u);
  if (lane < 16) stg4(p + 128, 0u, 0u, 0u, 0u);
}

struct Maps { CUtensorMap m[5]; };

struct Ring {
  uint32_t st, ph;
  __device__ __forceinline__ void next() { if (++st == NST) { st = 0; ph ^= 1; } }
};

#define STAMP(i) do {} while (0)

__device__ __forceinline__ void tma_box(uint32_t dst, const CUtensorMap* m, int col, int row, uint32_t bar, uint32_t expect) {
  asm volatile("{\n.reg .pred e, h;\nelect.sync _|e, 0xffffffff;\nsetp.ne.and.u32 h, %5, 0, e;\n"
               "@h mbarrier.arrive.expect_tx.shared::cta.b64 _, [%2], %5;\n"
               "@e cp.async.bulk.tensor.2d.shared::cluster.global.mbarrier::complete_tx::bytes [%0], [%1, {%3, %4}], [%2];\n}"
               :: "r"(dst), "l"(m), "r"(bar), "r"(col), "r"(row), "r"(expect) : "memory");
}

__device__ __forceinline__ void bulk_load(uint32_t dst, const void* src, uint32_t bytes, uint32_t bar, bool arm) {
  asm volatile("{\n.reg .pred e, h;\nelect.sync _|e, 0xffffffff;\nsetp.ne.and.u32 h, %4, 0, e;\n"
               "@h mbarrier.arrive.expect_tx.shared::cta.b64 _, [%3], %2;\n"
               "@e cp.async.bulk.shared::cluster.global.mbarrier::complete_tx::bytes [%0], [%1], %2, [%3];\n}"
               :: "r"(dst), "l"(src), "r"(bytes), "r"(bar), "r"((uint32_t)arm) : "memory");
}

__global__ void __launch_bounds__(384, 1) mega_kernel(
    const __grid_constant__ Maps maps, uint4* __restrict__ scr,
    const __nv_bfloat16* __restrict__ x_in, const __nv_bfloat16* __restrict__ wqkv, const __nv_bfloat16* __restrict__ wo,
    __nv_bfloat16* __restrict__ out) {
  extern __shared__ __align__(1024) uint8_t smem[];
  const uint32_t sb = (uint32_t)__cvta_generic_to_shared(smem);
  const uint32_t full0 = sb + BARS, empty0 = full0 + 8 * NST, rem_full = empty0 + 8 * NST, park_free = rem_full + 8, kv_free = park_free + 8;
  const uint32_t c8_go = kv_free + 8, c8_done = c8_go + 8, c8_full = c8_done + 8, pbar0 = c8_full + 8;
  const int w = __shfl_sync(~0u, threadIdx.x >> 5, 0), lane = threadIdx.x & 31;
  const int t = blockIdx.x >> 3, j = blockIdx.x & 7;
  const int r = lane >> 2, q = lane & 3;
  {
    const int sl = w < 8 ? w : j, ch = w < 8 ? j : 8;
    __align__(16) uint32_t v[16];
    if (w < 8 || w == 9) {
      const uint32_t* xr = (const uint32_t*)(x_in + (128 * t + 32 * (sl >> 1) + 2 * r + (sl & 1)) * 576 + 64 * ch + 2 * q);
#pragma unroll
      for (int g = 0; g < 8; g++) { v[2 * g] = __ldg(xr + 4 * g); v[2 * g + 1] = __ldg(xr + 8 * 576 + 4 * g); }
    }
    if (w >= 10) {
#pragma unroll
      for (int i = 0; i < 3; i++) {
        const int n = threadIdx.x - 320 + 64 * i, p = t >> 2, k = (t & 3) * 144 + n;
        if (n < 144) *(uint4*)(v + 4 * i) = __ldg((const uint4*)(p == 3 ? wo + k * 576 : wqkv + k * 1728 + (p < 2 ? 576 * (p + 1) : 0)) + 9 * j + 8);
      }
    }
    if (threadIdx.x == 256) {
      for (int i = 0; i < NST; i++) { mbar_init(full0 + 8 * i, 1); mbar_init(empty0 + 8 * i, 8); }
      mbar_init(rem_full, 1); mbar_init(park_free, 8); mbar_init(kv_free, 8); mbar_init(c8_go, 8); mbar_init(c8_done, 1); mbar_init(c8_full, 1);
      for (int i = 0; i < 8; i++) mbar_init(pbar0 + 8 * i, 5);
      asm volatile("fence.mbarrier_init.release.cluster;" ::: "memory");
    }
    __syncthreads();
    if (w == 8) {
#pragma unroll 1
      for (int b = 0; b < 2 * NST; b++)
        tma_box(sb + b * 8192, &maps.m[0], 72 * j + 576 + 576 * (b & 1), 64 * (b >> 1), full0 + (b >> 1) * 8, (b & 1) ? 0 : STAGE);
    } else if (w >= 10) {
#pragma unroll
      for (int i = 0; i < 3; i++) {
        const int n = threadIdx.x - 320 + 64 * i, k = (t & 3) * 144 + n, s = k >> 4, rr = k & 7;
        if (n < 144) stg4(scr + OFF_R + j * 2560 + (t >> 2) * 640 + (s >> 3) * 128 + ((k >> 3) & 1) * 64 + rr * 8 + ((s & 7) ^ rr),
                          v[4 * i], v[4 * i + 1], v[4 * i + 2], v[4 * i + 3]);
      }
      __threadfence();
      __syncwarp();
      if (lane < 16) asm volatile("st.relaxed.gpu.global.b32 [%0], 1;" :: "l"((uint32_t*)(scr + OFF_F + (lane * 8 + j) * 8) + 2 * t + w - 10) : "memory");
    } else {
      uint4* p = scr + OFF_X + (t * 8 + sl) * SLAB + 4 * ch * 32 + lane;
#pragma unroll
      for (int i = 0; i < 4; i++) stg4(p + i * 32, nz(v[4 * i]), v[4 * i + 1], v[4 * i + 2], v[4 * i + 3]);
      float y[32];
#pragma unroll
      for (int i = 0; i < 16; i++) { y[2 * i] = bf_lo(v[i]); y[2 * i + 1] = bf_hi(v[i]); }
      publish_stats<8>(scr + OFF_S + (t * 8 + sl) * 96 + ch * 8, y, 1u, lane);
    }
  }

  if (w >= 8) {
    asm volatile("setmaxnreg.dec.sync.aligned.u32 24;");
    if (w == 8) {
      Ring rg{0, 0};
      int b = 2 * NST;
#pragma unroll 1
      for (int seg = 0; seg < 34; seg++) {
        const int n = seg >= 17 ? seg - 17 : seg;
        int ma, mb, ca, cb, row = 0;
        if (n < 3) { ma = mb = n == 2; ca = 72 * j + (n == 0 ? 576 : 0); cb = ca + 576; }
        else if (n < 12) { ma = 3; mb = 2; ca = cb = 576 * j + 64 * (n - 3); }
        else { ma = mb = 4; ca = n == 12 ? 512 : ((j + 2 * n) & 7) * 64; cb = ((j + 2 * n + 1) & 7) * 64; row = 576 * j; }
        const bool zip = n == 0 || n == 3;
        const int nb = (n == 1 || n == 2 || n == 16) ? 9 : 18;
#pragma unroll 1
        for (; b < nb; b++) {
          const bool second = zip ? (b & 1) : b >= 9, last = b == nb - 1;
          const int kb = zip ? b >> 1 : second ? b - 9 : b;
          if (!(b & 1)) mbar_wait(empty0 + rg.st * 8, rg.ph);
          tma_box(sb + rg.st * STAGE + (b & 1) * 8192, &maps.m[second ? mb : ma], second ? cb : ca, row + 64 * kb, full0 + rg.st * 8,
                  (b & 1) ? 0 : last ? STAGE / 2 : STAGE);
          if ((b & 1) || last) rg.next();
        }
        b = 0;
      }
    } else if (w == 9) {
      const uint32_t stg = sb + HSTG + lane * 16;
      uint32_t fph = 0;
#pragma unroll 1
      for (int it = 0; it < 8; it++) {
        const int layer = it >> 2, i = it & 3;
        uint4* xb = scr + OFF_X + ((4 + layer) * 128 + t * 8 + j) * SLAB + 32 * 32;
        if (i == 0) {
          mbar_wait(c8_go, layer);
          int n = 0;
          while (true) {
            if (lane == 0) asm volatile("mbarrier.arrive.expect_tx.shared::cta.b64 _, [%0], 18432;" :: "r"(c8_full) : "memory");
            __syncwarp();
#pragma unroll 1
            for (int s = 0; s < 9; s++)
              bulk_load(sb + HSTG + s * 2048, s < 8 ? scr + OFF_P + (t * 64 + j + s * 8) * SLAB + 32 * 32 : xb, 2048, c8_full, false);
            mbar_wait(c8_full, fph); fph ^= 1;
            uint32_t bad = 0;
#pragma unroll 4
            for (int s = 0; s < 32; s++) { uint32_t v[2]; lds2(stg + s * 512, v); bad |= v[0] ^ (1 - layer); }
            if (__all_sync(~0u, (bad & 1u) == 0u)) break;
            __nanosleep(300);
            SPIN_GUARD(n);
          }
        }
        xb += i * 32 + lane;
        stg4(xb, 0u, 0u, 0u, 0u);
        uint32_t x[4];
#pragma unroll
        for (int h = 0; h < 2; h++) {
          float a0 = 0.f, a1 = 0.f, a2 = 0.f, a3 = 0.f;
#pragma unroll 3
          for (int s = 0; s < 9; s++) { uint32_t v[2]; lds2(stg + s * 2048 + i * 512 + h * 8, v); a0 += bf_lo(v[0]); a1 += bf_hi(v[0]); a2 += bf_lo(v[1]); a3 += bf_hi(v[1]); }
          x[2 * h] = pack_bf16(a0, a1); x[2 * h + 1] = pack_bf16(a2, a3);
        }
        if (layer == 0) {
          stg4(xb - 3 * 128 * SLAB, nz(x[0]), x[1], x[2], x[3]);
          sts4(stg + 18432 + i * 512, x);
        } else {
          uint32_t* o = (uint32_t*)(out + (128 * t + 32 * (j >> 1) + 2 * r + (j & 1)) * 576 + 512 + 16 * i + 2 * q);
          o[0] = x[0]; o[8 * 576] = x[1]; o[4] = x[2]; o[8 * 576 + 4] = x[3];
        }
        if (i == 3) { __syncwarp(); if (lane == 0) mbar_arrive(c8_done); }
        if (it == 3) {
          float s0 = 0.f, s1 = 0.f, q0 = 0.f, q1 = 0.f;
#pragma unroll 1
          for (int g = 0; g < 8; g++) { uint32_t v[2]; lds2(stg + 18432 + (g >> 1) * 512 + (g & 1) * 8, v); s0 += bf_lo(v[0]) + bf_hi(v[0]); s1 += bf_lo(v[1]) + bf_hi(v[1]); }
          s0 = quad_sum(s0); s1 = quad_sum(s1);
#pragma unroll 1
          for (int g = 0; g < 8; g++) {
            uint32_t v[2]; lds2(stg + 18432 + (g >> 1) * 512 + (g & 1) * 8, v);
            const float a = fmaf(s0, -1.f / 64, bf_lo(v[0])), b = fmaf(s0, -1.f / 64, bf_hi(v[0])), c = fmaf(s1, -1.f / 64, bf_lo(v[1])), d = fmaf(s1, -1.f / 64, bf_hi(v[1]));
            q0 = fmaf(a, a, fmaf(b, b, q0)); q1 = fmaf(c, c, fmaf(d, d, q1));
          }
          q0 = quad_sum(q0); q1 = quad_sum(q1);
          if (q == 0) stg4(scr + OFF_S + (t * 8 + j) * 96 + 64 + r, __float_as_uint(s0) & ~1u, __float_as_uint(q0), __float_as_uint(s1), __float_as_uint(q1));
        }
      }
    } else {
#pragma unroll 1
      for (int layer = 0; layer < 2; layer++) {
        if (w == 10) {
          if (layer) {
            mbar_wait(park_free, 0);
          } else {
            uint32_t* fl = (uint32_t*)(scr + OFF_F + (t * 8 + j) * 8) + lane;
            uint32_t v;
            int n = 0;
            while (true) {
              asm volatile("ld.relaxed.gpu.global.b32 %0, [%1];" : "=r"(v) : "l"(fl) : "memory");
              if (__all_sync(~0u, v != 0u)) break;
              SPIN_GUARD(n);
            }
            __threadfence();
            asm volatile("fence.proxy.async;\nst.relaxed.gpu.global.b32 [%0], 0;" :: "l"(fl) : "memory");
          }
          bulk_load(sb + REM, scr + OFF_R + j * 2560, 40960, rem_full, true);
        }
        if (layer) mbar_wait(kv_free, 0);
        if (t > 0) {
#pragma unroll 1
          for (int kv = 0; kv < 2; kv++) {
            uint4* hp = scr + OFF_H + ((layer * 128 + t * 8 + j) * 4 + (w - 10) * 2 + kv) * 96 + lane;
            uint32_t hl[12];
            int n = 0;
            while (true) {
              ldg4(hl, hp); ldg4(hl + 4, hp + 32); ldg4(hl + 8, hp + 64);
              if (__all_sync(~0u, hl[0] != 0u && hl[4] != 0u && hl[8] != 0u)) break;
              __nanosleep(100);
              SPIN_GUARD(n);
            }
#pragma unroll
            for (int g = 0; g < 9; g++) sts1(sb + KVS + kv * 20736 + (w - 10) * 10368 + r * 144 + g * 16 + q * 4, hl[g]);
#pragma unroll
            for (int i = 0; i < 3; i++) stg4(hp + i * 32, 0u, 0u, 0u, 0u);
          }
        }
        asm volatile("bar.arrive 1, 192;" ::: "memory");
      }
    }
  } else {
    asm volatile("setmaxnreg.inc.sync.aligned.u32 240;");
    Ring rg{0, 0};
    uint32_t prev = 0;
    uint32_t X[144];
    float rs0, rs1;
    uint32_t mean0, mean1;
    auto release = [&](uint32_t st) { if (lane == 0) mbar_arrive(empty0 + st * 8); };
    auto load_kb = [&](bool split, int kb, const uint4* src) {
#pragma unroll
      for (int k = 4 * kb; k < 4 * kb + 4; k++) {
        if (split && k % 9 == 4) { const char* lo = (const char*)(src + k * 32) - lane * 8; ldg2(X + 4 * k, lo); ldg2(X + 4 * k + 2, lo + 256); }
        else ldg4(X + 4 * k, src + k * 32);
      }
    };
    auto next_kb = [&](bool split, bool center, int kb, const uint4* src) {
      int n = 0;
      while (true) {
        bool ok = true;
#pragma unroll
        for (int k = 4 * kb; k < 4 * kb + 4; k++) { ok = ok && X[4 * k] != 0u; if (split && k % 9 == 4) ok = ok && X[4 * k + 2] != 0u; }
        if (__all_sync(~0u, ok)) break;
        SPIN_GUARD(n);
        load_kb(split, kb, src);
      }
      if (kb + GD < 9) load_kb(split, kb + GD, src);
      if (center) {
#pragma unroll
        for (int i = 16 * kb; i < 16 * kb + 16; i++) X[i] = sub_bf16x2(X[i], (i & 1) ? mean1 : mean0);
      }
    };
#pragma unroll 1
    for (int layer = 0; layer < 2; layer++) {
      const uint32_t tag = 1 - layer;
      uint4* const xbase = scr + OFF_X + (layer * 128 + t * 8 + w) * SLAB;
      auto begin_gather = [&](int kind) {
        uint32_t s[3][4];
        const uint4* p = scr + OFF_S + (kind * 128 + t * 8 + w) * 96 + q * 8 + r;
        int n = 0;
        s[2][0] = tag; s[2][1] = s[2][2] = s[2][3] = 0u;
        STAMP(kind * 8 + 0);
        while (true) {
          ldg4(s[0], p); ldg4(s[1], p + 32);
          if (kind == 0 && q == 0) ldg4(s[2], p + 64);
          if (__all_sync(~0u, ((s[0][0] ^ tag) | (s[1][0] ^ tag) | (s[2][0] ^ tag)) % 2u == 0u)) break;
          SPIN_GUARD(n);
        }
        STAMP(kind * 8 + 1);
#pragma unroll
        for (int kb = 0; kb < GD; kb++) load_kb(kind != 0, kb, xbase + kind * 256 * SLAB + lane);
        if (kind != 1) {
          const int ns = kind == 0 ? 3 : 2;
          float t0 = 0.f, t1 = 0.f;
#pragma unroll
          for (int i = 0; i < ns; i++) { t0 += __uint_as_float(s[i][0]); t1 += __uint_as_float(s[i][2]); }
          const float m0 = quad_sum(t0) * (1.f / 576), m1 = quad_sum(t1) * (1.f / 576);
          const float cnt = kind == 0 ? 64.f : 72.f;
          float v0 = 0.f, v1 = 0.f;
#pragma unroll
          for (int i = 0; i < ns; i++) {
            const float c = (i < 2 || q == 0) ? cnt : 0.f;
            const float d0 = fmaf(__uint_as_float(s[i][0]), 1.f / cnt, -m0), d1 = fmaf(__uint_as_float(s[i][2]), 1.f / cnt, -m1);
            v0 += fmaf(d0 * d0, c, __uint_as_float(s[i][1])); v1 += fmaf(d1 * d1, c, __uint_as_float(s[i][3]));
          }
          rs0 = rsqrtf(fmaf(quad_sum(v0), 1.f / 576, 1e-5f)); rs1 = rsqrtf(fmaf(quad_sum(v1), 1.f / 576, 1e-5f));
          mean0 = pack_bf16(m0, m0); mean1 = pack_bf16(m1, m1);
        }
      };
      auto box72 = [&](float (&a)[36], int part, int kb, int half) {
        const uint32_t base = sb + rg.st * STAGE + half * 8192;
        const uint64_t d0 = DESC_HI | ((base >> 4) + (((sb + REM + part * 10240 + (kb >> 1) * 2048 + (kb & 1) * 64 - base) >> 4) << 16));
#pragma unroll
        for (int i = 0; i < 4; i++) wgmma_rs_n72(a, X + 4 * (4 * kb + i), d0 - (uint64_t)(i * ((127u << 16) - 128u)), kb + i != 0);
      };
      auto solo72 = [&](float (&a)[36], int part, auto&& pre) {
#pragma unroll
        for (int kb = 0; kb < 9; kb++) {
          pre(kb);
          if (!(kb & 1)) mbar_wait(full0 + rg.st * 8, rg.ph);
          wg_fence();
          box72(a, part, kb, kb & 1);
          wg_commit();
          wg_wait<1>();
          if (kb > 0 && !(kb & 1)) release(prev);
          if ((kb & 1) || kb == 8) { prev = rg.st; rg.next(); }
        }
      };
      const uint32_t kvrow = sb + KVS + (w & 1) * 10368 + (16 * (w >> 1)) * 144;
      uint32_t Q[18];
      begin_gather(0);
      mbar_wait(rem_full, layer);
      {
        float acc[36], acc2[36];
#pragma unroll
        for (int kb = 0; kb < 9; kb++) {
          next_kb(false, true, kb, xbase + lane);
          mbar_wait(full0 + rg.st * 8, rg.ph);
          wg_fence();
          box72(acc, 0, kb, 0); box72(acc2, 1, kb, 1);
          wg_commit();
          wg_wait<1>();
          if (kb > 0) release(prev);
          if (kb == 1) sts4(sb + PARK + w * 512 + lane * 16, X);
          prev = rg.st; rg.next();
        }
        wg_wait<0>();
        release(prev);
        STAMP(2);
        auto put_kv = [&](float (&a)[36], int part) {
          pin(a);
          uint32_t hl[9];
          const uint32_t dst = kvrow + part * 20736 + (8 + r) * 144 + q * 4;
#pragma unroll
          for (int g = 0; g < 9; g++) {
            hl[g] = pack_bf16(a[4 * g + 2] * rs1, a[4 * g + 3] * rs1);
            sts1(dst + g * 16, pack_bf16(a[4 * g] * rs0, a[4 * g + 1] * rs0)); sts1(dst + 8 * 144 + g * 16, hl[g]);
          }
          if (w >= 6 && t < 15) {
            uint4* hp = scr + OFF_H + ((layer * 128 + (t + 1) * 8 + j) * 4 + (w & 1) * 2 + part) * 96 + lane;
            stg4(hp, nz(hl[0]), hl[1], hl[2], hl[3]); stg4(hp + 32, nz(hl[4]), hl[5], hl[6], hl[7]); stg4(hp + 64, nz(hl[8]), 0u, 0u, 0u);
          }
        };
        put_kv(acc2, 1);
        lds4(sb + PARK + w * 512 + lane * 16, X);
        put_kv(acc, 0);
        if (w < 4) asm volatile("bar.arrive 2, 256;" ::: "memory");
        solo72(acc, 2, [](int) {});
        wg_wait<0>();
        release(prev);
        pin(acc);
        STAMP(3);
#pragma unroll
        for (int g = 0; g < 9; g++) {
          Q[2 * g] = pack_bf16(acc[4 * g] * rs0, acc[4 * g + 1] * rs0); Q[2 * g + 1] = pack_bf16(acc[4 * g + 2] * rs1, acc[4 * g + 3] * rs1);
        }
      }
      if (w < 4) asm volatile("bar.sync 1, 192;" ::: "memory");
      else asm volatile("bar.sync 2, 256;" ::: "memory");
      STAMP(4);
      uint32_t O[18];
      {
        const bool edge = (t == 0 && w < 2);
        uint32_t row[3];
#pragma unroll
        for (int nt = 0; nt < 3; nt++) row[nt] = kvrow + (8 * nt + (lane & 7)) * 144;
        if (edge) row[0] = sb + KVS + 8 * 144;
        const uint32_t rlast = ((lane >> 3) == 0 ? row[0] : (lane >> 3) == 1 ? row[1] : row[2]) + 128;
        uint32_t K[3][9], V[3][9], dummy;
#pragma unroll
        for (int nt = 0; nt < 3; nt++) {
          ldsm4(row[nt] + (lane >> 3) * 16, K[nt][0], K[nt][1], K[nt][2], K[nt][3]);
          ldsm4(row[nt] + 64 + (lane >> 3) * 16, K[nt][4], K[nt][5], K[nt][6], K[nt][7]);
        }
        ldsm4(rlast, K[0][8], K[1][8], K[2][8], dummy);
#pragma unroll
        for (int nt = 0; nt < 3; nt++) {
          ldsm4t(row[nt] + 20736 + (lane >> 3) * 16, V[nt][0], V[nt][1], V[nt][2], V[nt][3]);
          ldsm4t(row[nt] + 20736 + 64 + (lane >> 3) * 16, V[nt][4], V[nt][5], V[nt][6], V[nt][7]);
        }
        ldsm4t(rlast + 20736, V[0][8], V[1][8], V[2][8], dummy);
        const bool up0 = 2 * q > r, up1 = 2 * q + 1 > r;
        const float sc = 0.23570226039551584f * 1.4426950408889634f;
        const float neg = -1e9f * 1.4426950408889634f;
        float Of[9][4];
#pragma unroll
        for (int h = 0; h < 4; h++) {
          const uint32_t a0 = q >= h ? Q[4 * h] : 0u, a1 = q >= h ? Q[4 * h + 1] : 0u;
          const uint32_t a4 = q <= h ? Q[4 * h + 4] : 0u, a5 = q <= h ? Q[4 * h + 5] : 0u;
          float S[3][4];
#pragma unroll
          for (int nt = 0; nt < 3; nt++) {
            S[nt][0] = S[nt][1] = S[nt][2] = S[nt][3] = 0.f;
            mma16(S[nt], a0, a1, Q[4 * h + 2], Q[4 * h + 3], K[nt][2 * h], K[nt][2 * h + 1]);
            mma8(S[nt], a4, a5, K[nt][2 * h + 2]);
          }
          float s00 = (up0 ? S[0][0] : S[1][0]) * sc, s01 = (up1 ? S[0][1] : S[1][1]) * sc;
          const float s10 = (up0 ? S[1][2] : S[2][2]) * sc, s11 = (up1 ? S[1][3] : S[2][3]) * sc;
          if (edge && up0) s00 = neg;
          if (edge && up1) s01 = neg;
          const float m0 = quad_max(fmaxf(s00, s01)), m1 = quad_max(fmaxf(s10, s11));
          float p00 = ex2(s00 - m0), p01 = ex2(s01 - m0), p10 = ex2(s10 - m1), p11 = ex2(s11 - m1);
          const float i0 = rcp(quad_sum(p00 + p01)), i1 = rcp(quad_sum(p10 + p11));
          p00 *= i0; p01 *= i0; p10 *= i1; p11 *= i1;
          const uint32_t pa = pack_bf16(up0 ? p00 : 0.f, up1 ? p01 : 0.f), pb = pack_bf16(up0 ? 0.f : p00, up1 ? 0.f : p01);
          const uint32_t pc = pack_bf16(up0 ? p10 : 0.f, up1 ? p11 : 0.f), pd = pack_bf16(up0 ? 0.f : p10, up1 ? 0.f : p11);
#pragma unroll
          for (int gi = 0; gi < 3; gi++) {
            const int g = 2 * h + gi;
            float o[4] = {0.f, 0.f, 0.f, 0.f};
            mma16(o, pa, 0u, pb, pc, V[0][g], V[1][g]);
            mma8(o, 0u, pd, V[2][g]);
#pragma unroll
            for (int e = 0; e < 4; e++) Of[g][e] = (gi == 0 && h > 0 && q < h) ? Of[g][e] : o[e];
          }
        }
#pragma unroll
        for (int g = 0; g < 9; g++) { O[2 * g] = pack_bf16(Of[g][0], Of[g][1]); O[2 * g + 1] = pack_bf16(Of[g][2], Of[g][3]); }
      }
      put72(xbase + 256 * SLAB, j, lane, O);
      if (q == 0) stg4(scr + OFF_S + (128 + t * 8 + w) * 96 + j * 8 + r, tag, 0u, 0u, 0u);
      {
        uint32_t res[18];
        const char* p = (const char*)(xbase + lane) + ((9 * j) >> 1) * 512 + (j & 1) * 8;
#pragma unroll
        for (int g = 0; g < 9; g++) ldg2(res + 2 * g, p + (g >> 1) * 512 + ((g & 1) ? ((j & 1) ? 504 : 8) : 0));
        begin_gather(1);
        float acc[36];
        solo72(acc, 3, [&](int kb) { next_kb(true, false, kb, xbase + 256 * SLAB + lane); });
        wg_wait<0>();
        release(prev);
        pin(acc);
        STAMP(10);
#pragma unroll
        for (int i = 0; i < 18; i++) {
          acc[2 * i] += bf_lo(res[i]); acc[2 * i + 1] += bf_hi(res[i]);
          res[i] = pack_bf16(acc[2 * i], acc[2 * i + 1]);
        }
        put72(xbase + 512 * SLAB, j, lane, res);
        publish_stats<9>(scr + OFF_S + (256 + t * 8 + w) * 96 + j * 8, acc, tag, lane);
      }
      float aA[32], aB[32];
      const uint32_t hp = sb + PARK + w * 512 + lane * 16;
      begin_gather(2);
#pragma unroll
      for (int kb = 0; kb < 9; kb++) {
        next_kb(true, true, kb, xbase + 512 * SLAB + lane);
        mbar_wait(full0 + rg.st * 8, rg.ph);
        const uint64_t desc = DESC_HI | ((sb + rg.st * STAGE) >> 4);
        wg_fence();
#pragma unroll
        for (int i = 0; i < 4; i++) wgmma_rs_n64(aA, X + 4 * (4 * kb + i), desc + i * 128, kb + i != 0);
#pragma unroll
        for (int i = 0; i < 4; i++) wgmma_rs_n64(aB, X + 4 * (4 * kb + i), desc + 512 + i * 128, kb + i != 0);
        wg_commit();
        wg_wait<1>();
        if (kb > 0) release(prev);
        prev = rg.st; rg.next();
      }
      zero_share(xbase, j, lane);
      zero_share(xbase + 256 * SLAB, j, lane);
      wg_wait<0>();
      STAMP(20);
      auto pack8 = [&](float (&a)[32], int p, uint32_t* o) {
#pragma unroll
        for (int e = 0; e < 8; e++) asm volatile("" : "+f"(a[8 * p + e]) :: "memory");
#pragma unroll
        for (int e = 0; e < 4; e++) o[e] = pack_bf16(a[8 * p + 2 * e], a[8 * p + 2 * e + 1]);
      };
      const float ka0 = 0.7978845608028654f * rs0, kb0 = 0.044715f * ka0 * rs0 * rs0, ku0 = 0.5f * rs0 * rs0;
      const float ka1 = 0.7978845608028654f * rs1, kb1 = 0.044715f * ka1 * rs1 * rs1, ku1 = 0.5f * rs1 * rs1;
      auto packu8 = [&](int p, uint32_t* o) {
#pragma unroll
        for (int e = 0; e < 8; e++) asm volatile("" : "+f"(aA[8 * p + e]) :: "memory");
#pragma unroll
        for (int e = 0; e < 4; e++) o[e] = pack_bf16(aA[8 * p + 2 * e] * ((e & 1) ? ku1 : ku0), aA[8 * p + 2 * e + 1] * ((e & 1) ? ku1 : ku0));
      };
      auto geglu8 = [&](int p, uint32_t* u) {
#pragma unroll
        for (int e = 0; e < 8; e++) asm volatile("" : "+f"(aB[8 * p + e]) :: "memory");
        float h[8];
#pragma unroll
        for (int e = 0; e < 8; e++) {
          const float g = aB[8 * p + e];
          h[e] = fmaf(g, tanh_ap(g * fmaf(g * g, (e & 2) ? kb1 : kb0, (e & 2) ? ka1 : ka0)), g);
        }
#pragma unroll
        for (int e = 0; e < 4; e++) u[e] = mul_bf16x2(pack_bf16(h[2 * e], h[2 * e + 1]), u[e]);
      };
      auto box = [&](int b, auto&& filler) {
        const int kb = b < 9 ? b : b - 9;
        if (!(b & 1)) mbar_wait(full0 + rg.st * 8, rg.ph);
        const uint64_t desc = DESC_HI | ((sb + rg.st * STAGE + (b & 1) * 8192) >> 4);
        wg_fence();
#pragma unroll
        for (int i = 0; i < 4; i++) {
          if (b < 9) wgmma_rs_n64(aA, X + 4 * (4 * kb + i), desc + i * 128, kb + i != 0);
          else wgmma_rs_n64(aB, X + 4 * (4 * kb + i), desc + i * 128, kb + i != 0);
          if (i == FPOS) filler();
        }
        wg_commit();
        if (b & 1) { if (W2) wg_wait<1>(); prev = rg.st; rg.next(); } else { wg_wait<1>(); release(prev); }
      };
      auto nop = [] {};
      auto step = [&](int st, auto&& filler) { box(2 * st, nop); box(2 * st + 1, filler); };
#pragma unroll
      for (int p = 0; p < 4; p++) { uint32_t o[4]; packu8(p, o); sts4(hp + p * 4096, o); }
      box(0, nop);
#pragma unroll 1
      for (int c = 1;; c++) {
        const uint32_t hc = hp + c * 4 * 4096;
#pragma unroll
        for (int b = 1; b < 18; b++) box(b, [&] {
          if ((b & 1) && b < 8) { uint32_t o[4]; const uint32_t a = hc - (4 - (b >> 1)) * 4096; lds4(a, o); geglu8(b >> 1, o); sts4(a, o); }
          if ((b & 1) && b > 10) { uint32_t o[4]; packu8((b - 11) >> 1, o); if (c < 8) sts4(hc + ((b - 11) >> 1) * 4096, o); } });
        if (c == 8) break;
        box(0, nop);
      }
      wg_wait<0>();
      STAMP(21);
#pragma unroll
      for (int s = 0; s < 32; s++) lds4(hp + s * 4096, X + 4 * s);
#pragma unroll
      for (int p = 0; p < 4; p++) packu8(p, X + 128 + 4 * p);
#pragma unroll
      for (int st = 0; st < 4; st++) step(st, [&] { geglu8(st, X + 128 + 4 * st); });
      STAMP(24);
      if (layer == 0 && lane == 0) mbar_arrive(park_free);
      int lane2 = lane;
      asm volatile("" : "+r"(lane2));
      uint4* const pw = scr + OFF_P + ((t * 8 + j) * 8 + w) * SLAB + lane2;
      const uint4* const pr = scr + OFF_P + (t * 64 + w) * SLAB + 4 * j * 32 + lane2;
      auto put_part = [&](float (&a)[32], int p, int chunk) {
        uint32_t o[4];
        pack8(a, p, o);
        stg4(pw + (chunk * 4 + p) * 32, (o[0] & ~1u) | tag, o[1], o[2], o[3]);
      };
      auto slot = [&](int p) { return sb + w * 2048 + (p < 4 ? PARK + (p - 1) * 16384 : KVS + (p - 4) * 16384); };
      auto fetch = [&](int p) {
        if (p > 0) bulk_load(slot(p), scr + OFF_P + (t * 64 + ((j - p) & 7) * 8 + w) * SLAB + 4 * j * 32, 2048, pbar0 + w * 8, true);
      };
      uint4* const xb = xbase + 512 * SLAB + 4 * j * 32;
#pragma unroll 1
      for (int sp = 0;; sp++) {
        const int ca = sp == 0 ? 8 : ((j + 2 * sp) & 7), cb = (j + 2 * sp + 1) & 7;
        if (sp == 1 && lane == 0) mbar_arrive(c8_go);
        if (sp == 3) mbar_wait(c8_done, layer);
#pragma unroll
        for (int st = 4; st < 9; st++) step(st, [&] {
          if (st == 5 || st == 6) { put_part(aA, 2 * (st - 5), ca); put_part(aA, 2 * (st - 5) + 1, ca); }
          if (st == 8) fetch(2 * sp - 1); });
        STAMP(25 + sp);
        if (sp == 3) break;
        if (sp == 2) asm volatile("{\n.reg .pred e;\nelect.sync _|e, 0xffffffff;\n@e cp.async.bulk.prefetch.L2.global [%0], 2048;\n}" :: "l"(xb) : "memory");
#pragma unroll
        for (int st = 0; st < 4; st++) step(st, [&] {
          if (st < 2) { put_part(aB, 2 * st, cb); put_part(aB, 2 * st + 1, cb); }
          if (st == 3) fetch(2 * sp); });
      }
      auto load_p = [&](int p, uint32_t* d) {
#pragma unroll
        for (int i = 0; i < 4; i++) ldg4(d + 4 * i, pr + ((j - p) & 7) * 8 * SLAB + i * 32);
      };
#pragma unroll
      for (int st = 0; st < 4; st++) step(st, [&] {
        if (st == 0) {
#pragma unroll
          for (int p = 0; p < 4; p++) put_part(aB, p, (j + 7) & 7);
        }
        if (st == 1) {
#pragma unroll
          for (int i = 0; i < 4; i++) {
            const bool split = j == 2 * i + 1;
            const char* l = (const char*)(xb + i * 32) + (split ? lane2 * 8 : lane2 * 16);
            ldg2(X + 4 * i, l); ldg2(X + 4 * i + 2, l + (split ? 256 : 8));
          }
          load_p(6, X + 16);
        }
        if (st == 3) load_p(7, X + 32); });
      {
        mbar_wait(full0 + rg.st * 8, rg.ph);
        const uint64_t desc = DESC_HI | ((sb + rg.st * STAGE) >> 4);
        wg_fence();
#pragma unroll
        for (int i = 0; i < 4; i++) wgmma_rs_n64(aA, X + 4 * (32 + i), desc + i * 128, 1);
        wg_commit();
        wg_wait<1>(); release(prev);
        prev = rg.st; rg.next();
        mbar_wait(pbar0 + w * 8, layer);
        wg_wait<0>(); release(prev);
        pin(aA);
      }
      STAMP(22);
      {
        const uint32_t eye = r == 2 * q ? 0x3f80u : r == 2 * q + 1 ? 0x3f800000u : 0u;
        auto add_p = [&](int p, uint32_t* d) {
          int n = 0;
          while (!__all_sync(~0u, (((d[0] ^ tag) | (d[4] ^ tag) | (d[8] ^ tag) | (d[12] ^ tag)) & 1u) == 0u)) { SPIN_GUARD(n); load_p(p, d); }
#pragma unroll
          for (int g = 0; g < 8; g++) mma8(aA + 4 * g, d[2 * g], d[2 * g + 1], eye);
        };
#pragma unroll
        for (int p = 1; p < 6; p++)
#pragma unroll
          for (int i = 0; i < 4; i++) lds4(slot(p) + lane2 * 16 + i * 512, X + 32 + 16 * p + 4 * i);
#pragma unroll
        for (int g = 0; g < 8; g++) mma8(aA + 4 * g, X[2 * g], X[2 * g + 1], eye);
#pragma unroll
        for (int p = 1; p < 6; p++) add_p(p, X + 32 + 16 * p);
        add_p(6, X + 16); add_p(7, X + 32);
        uint32_t res[16];
#pragma unroll
        for (int i = 0; i < 16; i++) res[i] = pack_bf16(aA[2 * i], aA[2 * i + 1]);
        if (layer == 0) {
          uint4* p = xbase + 128 * SLAB + 4 * j * 32 + lane;
#pragma unroll
          for (int i = 0; i < 4; i++) stg4(p + i * 32, nz(res[4 * i]), res[4 * i + 1], res[4 * i + 2], res[4 * i + 3]);
          publish_stats<8>(scr + OFF_S + (t * 8 + w) * 96 + j * 8, aA, 0u, lane);
          if (lane == 0) mbar_arrive(kv_free);
        } else {
          uint32_t* o = (uint32_t*)(out + (128 * t + 32 * (w >> 1) + 2 * r + (w & 1)) * 576 + 64 * j + 2 * q);
#pragma unroll
          for (int g = 0; g < 8; g++) { o[4 * g] = res[2 * g]; o[8 * 576 + 4 * g] = res[2 * g + 1]; }
        }
#pragma unroll
        for (int i = 0; i < 4; i++) stg4(xb + lane + i * 32, 0u, 0u, 0u, 0u);
      }
      STAMP(23);
    }
  }
}

typedef CUresult (*EncodeFn)(CUtensorMap*, CUtensorMapDataType, cuuint32_t, void*, const cuuint64_t*, const cuuint64_t*,
                             const cuuint32_t*, const cuuint32_t*, CUtensorMapInterleave, CUtensorMapSwizzle,
                             CUtensorMapL2promotion, CUtensorMapFloatOOBfill);

CUtensorMap make_map(EncodeFn f, const void* p, uint64_t cols, uint64_t rows) {
  CUtensorMap m;
  cuuint64_t dims[2] = {cols, rows};
  cuuint64_t str[1] = {cols * 2};
  cuuint32_t box[2] = {64, 64};
  cuuint32_t es[2] = {1, 1};
  f(&m, CU_TENSOR_MAP_DATA_TYPE_BFLOAT16, 2, const_cast<void*>(p), dims, str, box, es, CU_TENSOR_MAP_INTERLEAVE_NONE,
    CU_TENSOR_MAP_SWIZZLE_128B, CU_TENSOR_MAP_L2_PROMOTION_NONE, CU_TENSOR_MAP_FLOAT_OOB_FILL_NONE);
  return m;
}

}

extern "C" void kernel_launch(void* const* d_in, const int* in_sizes, int n_in, void* d_out, int out_size) {
  void* fn = nullptr;
  cudaDriverEntryPointQueryResult qr;
  cudaGetDriverEntryPoint("cuTensorMapEncodeTiled", &fn, cudaEnableDefault, &qr);
  EncodeFn enc = (EncodeFn)fn;
  Maps maps;
  maps.m[0] = make_map(enc, d_in[1], 1728, 576); maps.m[1] = make_map(enc, d_in[2], 576, 576);
  maps.m[2] = make_map(enc, d_in[4], 4608, 576); maps.m[3] = make_map(enc, d_in[5], 4608, 576); maps.m[4] = make_map(enc, d_in[6], 576, 4608);
  void* scr = nullptr;
  cudaGetSymbolAddress(&scr, g_scratch);
  cudaFuncSetAttribute(mega_kernel, cudaFuncAttributeMaxDynamicSharedMemorySize, SMEM_BYTES);
  mega_kernel<<<128, 384, SMEM_BYTES>>>(maps, (uint4*)scr, (const __nv_bfloat16*)d_in[0], (const __nv_bfloat16*)d_in[1],
                                        (const __nv_bfloat16*)d_in[2], (__nv_bfloat16*)d_out);
}
```

```cpp
#include <cuda_runtime.h>
#include <cuda.h>
#include <cuda_bf16.h>
#include <stdint.h>

#define TRACE 0
#define FPOS 2
#define W2 0

namespace {

constexpr int NST = 6;
constexpr int STAGE = 16384;
constexpr int PARK = NST * STAGE;
constexpr int REM = PARK + 49152;
constexpr int KVS = REM + 40960;
constexpr int HSTG = KVS + 16384;
constexpr int BARS = KVS + 41472;
constexpr int TRC = BARS + 256;
constexpr int SMEM_BYTES = TRC + (TRACE ? 512 : 0);
static_assert(BARS >= PARK + 131072, "barriers overlap park");
static_assert(SMEM_BYTES <= 232448, "smem");

constexpr int SLAB = 36 * 32;
constexpr int SPIN_MAX = 1 << 17;
constexpr int GD = 3;
constexpr int OFF_X = 0;
constexpr int OFF_P = OFF_X + 6 * 128 * SLAB;
constexpr int OFF_S = OFF_P + 8 * 128 * SLAB;
constexpr int OFF_H = OFF_S + 3 * 128 * 96;
constexpr int OFF_R = OFF_H + 2 * 128 * 384;
constexpr int OFF_F = OFF_R + 8 * 2304;
constexpr int SCRATCH = OFF_F + 128 * 8;

}

__device__ uint4 g_scratch[SCRATCH];

namespace {

constexpr uint64_t DESC_HI = 0x4000004000000000ull;
__device__ __forceinline__ void wgmma_rs_n64(float (&d)[32], const uint32_t* a, uint64_t desc, int scale_d) {
  asm volatile("{\n.reg .pred p;\nsetp.ne.b32 p, %37, 0;\n"
    "wgmma.mma_async.sync.aligned.m64n64k16.f32.bf16.bf16 "
    "{%0, %1, %2, %3, %4, %5, %6, %7, %8, %9, %10, %11, %12, %13, %14, %15, %16, %17, %18, %19, %20, %21, %22, %23, %24, %25, %26, %27, %28, %29, %30, %31}, "
    "{%32, %33, %34, %35}, %36, p, 1, 1, 1;\n}\n"
    : "+f"(d[0]), "+f"(d[1]), "+f"(d[2]), "+f"(d[3]), "+f"(d[4]), "+f"(d[5]), "+f"(d[6]), "+f"(d[7]), "+f"(d[8]), "+f"(d[9]), "+f"(d[10]), "+f"(d[11]), "+f"(d[12]), "+f"(d[13]), "+f"(d[14]), "+f"(d[15]), "+f"(d[16]), "+f"(d[17]), "+f"(d[18]), "+f"(d[19]), "+f"(d[20]), "+f"(d[21]), "+f"(d[22]), "+f"(d[23]), "+f"(d[24]), "+f"(d[25]), "+f"(d[26]), "+f"(d[27]), "+f"(d[28]), "+f"(d[29]), "+f"(d[30]), "+f"(d[31])
    : "r"(a[0]), "r"(a[1]), "r"(a[2]), "r"(a[3]), "l"(desc), "r"(scale_d));
}
__device__ __forceinline__ void wgmma_rs_n72(float (&d)[36], const uint32_t* a, uint64_t desc, int scale_d) {
  asm volatile("{\n.reg .pred p;\nsetp.ne.b32 p, %41, 0;\n"
    "wgmma.mma_async.sync.aligned.m64n72k16.f32.bf16.bf16 "
    "{%0, %1, %2, %3, %4, %5, %6, %7, %8, %9, %10, %11, %12, %13, %14, %15, %16, %17, %18, %19, %20, %21, %22, %23, %24, %25, %26, %27, %28, %29, %30, %31, %32, %33, %34, %35}, "
    "{%36, %37, %38, %39}, %40, p, 1, 1, 1;\n}\n"
    : "+f"(d[0]), "+f"(d[1]), "+f"(d[2]), "+f"(d[3]), "+f"(d[4]), "+f"(d[5]), "+f"(d[6]), "+f"(d[7]), "+f"(d[8]), "+f"(d[9]), "+f"(d[10]), "+f"(d[11]), "+f"(d[12]), "+f"(d[13]), "+f"(d[14]), "+f"(d[15]), "+f"(d[16]), "+f"(d[17]), "+f"(d[18]), "+f"(d[19]), "+f"(d[20]), "+f"(d[21]), "+f"(d[22]), "+f"(d[23]), "+f"(d[24]), "+f"(d[25]), "+f"(d[26]), "+f"(d[27]), "+f"(d[28]), "+f"(d[29]), "+f"(d[30]), "+f"(d[31]), "+f"(d[32]), "+f"(d[33]), "+f"(d[34]), "+f"(d[35])
    : "r"(a[0]), "r"(a[1]), "r"(a[2]), "r"(a[3]), "l"(desc), "r"(scale_d));
}

__device__ __forceinline__ void wgmma_rs_n24(float (&d)[12], const uint32_t* a, uint64_t desc, int scale_d) {
  asm volatile("{\n.reg .pred p;\nsetp.ne.b32 p, %17, 0;\n"
    "wgmma.mma_async.sync.aligned.m64n24k16.f32.bf16.bf16 "
    "{%0, %1, %2, %3, %4, %5, %6, %7, %8, %9, %10, %11}, "
    "{%12, %13, %14, %15}, %16, p, 1, 1, 1;\n}\n"
    : "+f"(d[0]), "+f"(d[1]), "+f"(d[2]), "+f"(d[3]), "+f"(d[4]), "+f"(d[5]), "+f"(d[6]), "+f"(d[7]), "+f"(d[8]), "+f"(d[9]), "+f"(d[10]), "+f"(d[11])
    : "r"(a[0]), "r"(a[1]), "r"(a[2]), "r"(a[3]), "l"(desc), "r"(scale_d));
}

__device__ __forceinline__ void mbar_init(uint32_t a, uint32_t c) { asm volatile("mbarrier.init.shared::cta.b64 [%0], %1;" :: "r"(a), "r"(c)); }
__device__ __forceinline__ void mbar_arrive(uint32_t a) { asm volatile("mbarrier.arrive.shared::cta.b64 _, [%0];" :: "r"(a) : "memory"); }
__device__ __forceinline__ void mbar_wait(uint32_t a, uint32_t ph) {
  asm volatile("{\n.reg .pred p;\n.reg .u32 n;\n"
               "mbarrier.try_wait.parity.shared::cta.b64 p, [%0], %1;\n@p bra D;\n"
               "mov.u32 n, 0;\n"
               "W: mbarrier.try_wait.parity.shared::cta.b64 p, [%0], %1;\n@p bra D;\n"
               "add.u32 n, n, 1;\nsetp.lt.u32 p, n, 4194304;\n@p bra W;\ntrap;\nD:\n}" :: "r"(a), "r"(ph) : "memory");
}
__device__ __forceinline__ void wg_fence() { asm volatile("wgmma.fence.sync.aligned;" ::: "memory"); }
__device__ __forceinline__ void wg_commit() { asm volatile("wgmma.commit_group.sync.aligned;" ::: "memory"); }
template <int N> __device__ __forceinline__ void wg_wait() { asm volatile("wgmma.wait_group.sync.aligned %0;" :: "n"(N) : "memory"); }
__device__ __forceinline__ float tanh_ap(float x) { float y; asm("tanh.approx.f32 %0, %1;" : "=f"(y) : "f"(x)); return y; }
__device__ __forceinline__ float ex2(float x) { float y; asm("ex2.approx.ftz.f32 %0, %1;" : "=f"(y) : "f"(x)); return y; }
__device__ __forceinline__ uint32_t pack_bf16(float lo, float hi) { uint32_t r; asm("cvt.rn.bf16x2.f32 %0, %1, %2;" : "=r"(r) : "f"(hi), "f"(lo)); return r; }
__device__ __forceinline__ float bf_lo(uint32_t v) { return __uint_as_float(v << 16); }
__device__ __forceinline__ float bf_hi(uint32_t v) { return __uint_as_float(v & 0xffff0000u); }
__device__ __forceinline__ uint32_t sub_bf16x2(uint32_t a, uint32_t b) { uint32_t r; asm("sub.rn.bf16x2 %0, %1, %2;" : "=r"(r) : "r"(a), "r"(b)); return r; }
__device__ __forceinline__ uint32_t mul_bf16x2(uint32_t a, uint32_t b) { uint32_t r; asm("mul.rn.bf16x2 %0, %1, %2;" : "=r"(r) : "r"(a), "r"(b)); return r; }
__device__ __forceinline__ uint32_t nz(uint32_t w) { return w == 0u ? 0x8000u : w; }

__device__ __forceinline__ void ldg4(uint32_t* d, const uint4* p) {
  asm volatile("ld.relaxed.gpu.global.v4.b32 {%0,%1,%2,%3}, [%4];" : "=r"(d[0]), "=r"(d[1]), "=r"(d[2]), "=r"(d[3]) : "l"(p) : "memory");
}
__device__ __forceinline__ void ldg2(uint32_t* d, const void* p) {
  asm volatile("ld.relaxed.gpu.global.v2.b32 {%0,%1}, [%2];" : "=r"(d[0]), "=r"(d[1]) : "l"(p) : "memory");
}
__device__ __forceinline__ void stg4(uint4* p, uint32_t a, uint32_t b, uint32_t c, uint32_t d) {
  asm volatile("st.relaxed.gpu.global.v4.b32 [%0], {%1,%2,%3,%4};" :: "l"(p), "r"(a), "r"(b), "r"(c), "r"(d) : "memory");
}
__device__ __forceinline__ void stg2(void* p, uint32_t a, uint32_t b) {
  asm volatile("st.relaxed.gpu.global.v2.b32 [%0], {%1,%2};" :: "l"(p), "r"(a), "r"(b) : "memory");
}
__device__ __forceinline__ void sts4(uint32_t a, const uint32_t* o) { asm volatile("st.shared.v4.b32 [%0], {%1,%2,%3,%4};" :: "r"(a), "r"(o[0]), "r"(o[1]), "r"(o[2]), "r"(o[3]) : "memory"); }
__device__ __forceinline__ void lds4(uint32_t a, uint32_t* o) { asm volatile("ld.shared.v4.b32 {%0,%1,%2,%3}, [%4];" : "=r"(o[0]), "=r"(o[1]), "=r"(o[2]), "=r"(o[3]) : "r"(a) : "memory"); }
__device__ __forceinline__ void lds2(uint32_t a, uint32_t* o) { asm volatile("ld.shared.v2.b32 {%0,%1}, [%2];" : "=r"(o[0]), "=r"(o[1]) : "r"(a) : "memory"); }
__device__ __forceinline__ float rcp(float x) { float y; asm("rcp.approx.ftz.f32 %0, %1;" : "=f"(y) : "f"(x)); return y; }
__device__ __forceinline__ void sts1(uint32_t a, uint32_t v) { asm volatile("st.shared.b32 [%0], %1;" :: "r"(a), "r"(v) : "memory"); }
__device__ __forceinline__ void ldsm4(uint32_t a, uint32_t& r0, uint32_t& r1, uint32_t& r2, uint32_t& r3) {
  asm volatile("ldmatrix.sync.aligned.m8n8.x4.shared.b16 {%0,%1,%2,%3}, [%4];" : "=r"(r0), "=r"(r1), "=r"(r2), "=r"(r3) : "r"(a) : "memory");
}
__device__ __forceinline__ void ldsm4t(uint32_t a, uint32_t& r0, uint32_t& r1, uint32_t& r2, uint32_t& r3) {
  asm volatile("ldmatrix.sync.aligned.m8n8.x4.trans.shared.b16 {%0,%1,%2,%3}, [%4];" : "=r"(r0), "=r"(r1), "=r"(r2), "=r"(r3) : "r"(a) : "memory");
}
__device__ __forceinline__ void mma16(float* c, uint32_t a0, uint32_t a1, uint32_t a2, uint32_t a3, uint32_t b0, uint32_t b1) {
  asm("mma.sync.aligned.m16n8k16.row.col.f32.bf16.bf16.f32 {%0,%1,%2,%3}, {%4,%5,%6,%7}, {%8,%9}, {%0,%1,%2,%3};"
    : "+f"(c[0]), "+f"(c[1]), "+f"(c[2]), "+f"(c[3]) : "r"(a0), "r"(a1), "r"(a2), "r"(a3), "r"(b0), "r"(b1));
}
__device__ __forceinline__ void mma8(float* c, uint32_t a0, uint32_t a1, uint32_t b0) {
  asm("mma.sync.aligned.m16n8k8.row.col.f32.bf16.bf16.f32 {%0,%1,%2,%3}, {%4,%5}, {%6}, {%0,%1,%2,%3};"
    : "+f"(c[0]), "+f"(c[1]), "+f"(c[2]), "+f"(c[3]) : "r"(a0), "r"(a1), "r"(b0));
}
__device__ __forceinline__ float quad_sum(float v) { v += __shfl_xor_sync(~0u, v, 1); v += __shfl_xor_sync(~0u, v, 2); return v; }
__device__ __forceinline__ float quad_max(float v) { v = fmaxf(v, __shfl_xor_sync(~0u, v, 1)); v = fmaxf(v, __shfl_xor_sync(~0u, v, 2)); return v; }
template <int N> __device__ __forceinline__ void pin(float (&d)[N]) {
#pragma unroll
  for (int i = 0; i < N; i++) asm volatile("" : "+f"(d[i]) :: "memory");
}
#define SPIN_GUARD(n) if (++(n) > SPIN_MAX) break

template <int NG> __device__ __forceinline__ void publish_stats(uint4* dst, const float* y, uint32_t tag, int lane) {
  float s0 = 0.f, s1 = 0.f;
#pragma unroll
  for (int g = 0; g < NG; g++) { s0 += y[4 * g] + y[4 * g + 1]; s1 += y[4 * g + 2] + y[4 * g + 3]; }
  s0 = quad_sum(s0); s1 = quad_sum(s1);
  const float m0 = s0 * (1.f / (8 * NG)), m1 = s1 * (1.f / (8 * NG));
  float q0 = 0.f, q1 = 0.f, q2 = 0.f, q3 = 0.f;
#pragma unroll
  for (int g = 0; g < NG; g++) {
    const float a = y[4 * g] - m0, b = y[4 * g + 1] - m0, c = y[4 * g + 2] - m1, d = y[4 * g + 3] - m1;
    q0 = fmaf(a, a, q0); q1 = fmaf(b, b, q1); q2 = fmaf(c, c, q2); q3 = fmaf(d, d, q3);
  }
  q0 = quad_sum(q0 + q1); q2 = quad_sum(q2 + q3);
  if ((lane & 3) == 0)
    stg4(dst + (lane >> 2), (__float_as_uint(s0) & ~1u) | tag, __float_as_uint(q0), __float_as_uint(s1), __float_as_uint(q2));
}

__device__ __forceinline__ void put72(uint4* slab, int j, int lane, const uint32_t* v) {
  uint4* p = slab + ((9 * j + 1) >> 1) * 32;
  if (j & 1) {
    stg2((char*)(p - 16) + lane * 8, nz(v[0]), v[1]);
#pragma unroll
    for (int i = 0; i < 4; i++) stg4(p + lane + i * 32, nz(v[4 * i + 2]), v[4 * i + 3], v[4 * i + 4], v[4 * i + 5]);
  } else {
#pragma unroll
    for (int i = 0; i < 4; i++) stg4(p + lane + i * 32, nz(v[4 * i]), v[4 * i + 1], v[4 * i + 2], v[4 * i + 3]);
    stg2((char*)(p + 4 * 32) + lane * 8, nz(v[16]), v[17]);
  }
}
__device__ __forceinline__ void zero_share(uint4* slab, int j, int lane) {
  uint4* p = slab + j * 144 + lane;
#pragma unroll
  for (int i = 0; i < 4; i++) stg4(p + i * 32, 0u, 0u, 0u, 0u);
  if (lane < 16) stg4(p + 128, 0u, 0u, 0u, 0u);
}

struct Maps { CUtensorMap m[5]; };

struct Ring {
  uint32_t st, ph;
  __device__ __forceinline__ void next() { if (++st == NST) { st = 0; ph ^= 1; } }
};

#define STAMP(i) do {} while (0)

__device__ __forceinline__ void tma_box(uint32_t dst, const CUtensorMap* m, int col, int row, uint32_t bar, uint32_t expect) {
  asm volatile("{\n.reg .pred e, h;\nelect.sync _|e, 0xffffffff;\nsetp.ne.and.u32 h, %5, 0, e;\n"
               "@h mbarrier.arrive.expect_tx.shared::cta.b64 _, [%2], %5;\n"
               "@e cp.async.bulk.tensor.2d.shared::cluster.global.mbarrier::complete_tx::bytes [%0], [%1, {%3, %4}], [%2];\n}"
               :: "r"(dst), "l"(m), "r"(bar), "r"(col), "r"(row), "r"(expect) : "memory");
}

__device__ __forceinline__ void bulk_load(uint32_t dst, const void* src, uint32_t bytes, uint32_t bar, bool arm) {
  asm volatile("{\n.reg .pred e, h;\nelect.sync _|e, 0xffffffff;\nsetp.ne.and.u32 h, %4, 0, e;\n"
               "@h mbarrier.arrive.expect_tx.shared::cta.b64 _, [%3], %2;\n"
               "@e cp.async.bulk.shared::cluster.global.mbarrier::complete_tx::bytes [%0], [%1], %2, [%3];\n}"
               :: "r"(dst), "l"(src), "r"(bytes), "r"(bar), "r"((uint32_t)arm) : "memory");
}

__global__ void __launch_bounds__(384, 1) mega_kernel(
    const __grid_constant__ Maps maps, uint4* __restrict__ scr,
    const __nv_bfloat16* __restrict__ x_in, const __nv_bfloat16* __restrict__ wqkv, const __nv_bfloat16* __restrict__ wo,
    __nv_bfloat16* __restrict__ out) {
  extern __shared__ __align__(1024) uint8_t smem[];
  const uint32_t sb = (uint32_t)__cvta_generic_to_shared(smem);
  const uint32_t full0 = sb + BARS, empty0 = full0 + 8 * NST, rem_full = empty0 + 8 * NST, park_free = rem_full + 8, kv_free = park_free + 8;
  const uint32_t c8_go = kv_free + 8, c8_done = c8_go + 8, c8_full = c8_done + 8, pbar0 = c8_full + 8;
  const int w = __shfl_sync(~0u, threadIdx.x >> 5, 0), lane = threadIdx.x & 31;
  const int t = blockIdx.x >> 3, j = blockIdx.x & 7;
  const int r = lane >> 2, q = lane & 3;
  {
    const int sl = w < 8 ? w : j, ch = w < 8 ? j : 8;
    const uint32_t* xr = (const uint32_t*)(x_in + (128 * t + 32 * (sl >> 1) + 2 * r + (sl & 1)) * 576 + 64 * ch + 2 * q);
    if (w < 8 || w == 9) {
      uint32_t v[16];
#pragma unroll
      for (int g = 0; g < 8; g++) { v[2 * g] = __ldg(xr + 4 * g); v[2 * g + 1] = __ldg(xr + 8 * 576 + 4 * g); }
      uint4* p = scr + OFF_X + (t * 8 + sl) * SLAB + 4 * ch * 32 + lane;
#pragma unroll
      for (int i = 0; i < 4; i++) stg4(p + i * 32, nz(v[4 * i]), v[4 * i + 1], nz(v[4 * i + 2]), v[4 * i + 3]);
      float y[32];
#pragma unroll
      for (int i = 0; i < 16; i++) { y[2 * i] = bf_lo(v[i]); y[2 * i + 1] = bf_hi(v[i]); }
      publish_stats<8>(scr + OFF_S + (t * 8 + sl) * 96 + ch * 8, y, 1u, lane);
    }
    if (w == 8) {
      if (lane == 0) {
        for (int i = 0; i < NST; i++) { mbar_init(full0 + 8 * i, 1); mbar_init(empty0 + 8 * i, 8); }
        mbar_init(rem_full, 1); mbar_init(park_free, 8); mbar_init(kv_free, 8); mbar_init(c8_go, 8); mbar_init(c8_done, 1); mbar_init(c8_full, 1);
        for (int i = 0; i < 8; i++) mbar_init(pbar0 + 8 * i, 5);
        asm volatile("fence.mbarrier_init.release.cluster;" ::: "memory");
      }
      __syncwarp();
      asm volatile("bar.arrive 3, 320;\nbar.arrive 4, 96;" ::: "memory");
    } else if (w < 10) {
      asm volatile("bar.sync 3, 320;" ::: "memory");
    }
  }

  if (w >= 8) {
    asm volatile("setmaxnreg.dec.sync.aligned.u32 24;");
    if (w == 8) {
      Ring rg{0, 1};
#pragma unroll 1
      for (int seg = 0; seg < 34; seg++) {
        const int n = seg >= 17 ? seg - 17 : seg;
        int ma, mb, ca, cb, row = 0;
        if (n < 3) { ma = mb = n == 2; ca = 72 * j + (n == 0 ? 576 : 0); cb = ca + 576; }
        else if (n < 12) { ma = 3; mb = 2; ca = cb = 576 * j + 64 * (n - 3); }
        else { ma = mb = 4; ca = n == 12 ? 512 : ((j + 2 * n) & 7) * 64; cb = ((j + 2 * n + 1) & 7) * 64; row = 576 * j; }
        const bool zip = n == 0 || n == 3;
        const int nb = (n == 1 || n == 2 || n == 16) ? 9 : 18;
#pragma unroll 1
        for (int b = 0; b < nb; b++) {
          const bool second = zip ? (b & 1) : b >= 9, last = b == nb - 1;
          const int kb = zip ? b >> 1 : second ? b - 9 : b;
          if (!(b & 1)) mbar_wait(empty0 + rg.st * 8, rg.ph);
          tma_box(sb + rg.st * STAGE + (b & 1) * 8192, &maps.m[second ? mb : ma], second ? cb : ca, row + 64 * kb, full0 + rg.st * 8,
                  (b & 1) ? 0 : last ? STAGE / 2 : STAGE);
          if ((b & 1) || last) rg.next();
        }
      }
    } else if (w == 9) {
      const uint32_t stg = sb + HSTG + lane * 16;
      uint32_t fph = 0;
#pragma unroll 1
      for (int layer = 0; layer < 2; layer++) {
        uint4* xb = scr + OFF_X + ((4 + layer) * 128 + t * 8 + j) * SLAB + 32 * 32;
        mbar_wait(c8_go, layer);
        int n = 0;
        while (true) {
          if (lane == 0) asm volatile("mbarrier.arrive.expect_tx.shared::cta.b64 _, [%0], 18432;" :: "r"(c8_full) : "memory");
          __syncwarp();
#pragma unroll 1
          for (int s = 0; s < 9; s++)
            bulk_load(sb + HSTG + s * 2048, s < 8 ? scr + OFF_P + (t * 64 + j + s * 8) * SLAB + 32 * 32 : xb, 2048, c8_full, false);
          mbar_wait(c8_full, fph); fph ^= 1;
          uint32_t bad = 0;
#pragma unroll 8
          for (int s = 0; s < 32; s++) { uint32_t v; asm volatile("ld.shared.b32 %0, [%1];" : "=r"(v) : "r"(stg + s * 512) : "memory"); bad |= v ^ (1 - layer); }
          if (__all_sync(~0u, (bad & 1u) == 0u)) break;
          __nanosleep(300);
          SPIN_GUARD(n);
        }
        float s0 = 0.f, s1 = 0.f;
#pragma unroll 1
        for (int g = 0; g < 8; g++) {
          const uint32_t a = stg + (g >> 1) * 512 + (g & 1) * 8;
          float a0 = 0.f, a1 = 0.f, a2 = 0.f, a3 = 0.f;
#pragma unroll
          for (int b = 0; b < 3; b++) {
            uint32_t v[6];
#pragma unroll
            for (int s = 0; s < 3; s++) lds2(a + (3 * b + s) * 2048, v + 2 * s);
#pragma unroll
            for (int s = 0; s < 3; s++) { a0 += bf_lo(v[2 * s]); a1 += bf_hi(v[2 * s]); a2 += bf_lo(v[2 * s + 1]); a3 += bf_hi(v[2 * s + 1]); }
          }
          sts1(a + 18432, pack_bf16(a0, a1)); sts1(a + 18436, pack_bf16(a2, a3));
          s0 += a0 + a1; s1 += a2 + a3;
        }
        __syncwarp();
        if (lane == 0) mbar_arrive(c8_done);
        s0 = quad_sum(s0); s1 = quad_sum(s1);
        float q0 = 0.f, q1 = 0.f;
#pragma unroll 1
        for (int i = 0; i < 4; i++) {
          uint32_t x[4];
          lds4(stg + 18432 + i * 512, x);
          stg4(xb + i * 32 + lane, 0u, 0u, 0u, 0u);
          if (layer == 0) {
            stg4(xb - 3 * 128 * SLAB + i * 32 + lane, nz(x[0]), x[1], x[2], x[3]);
#pragma unroll
            for (int e = 0; e < 4; e++) {
              const float m = (e & 1) ? s1 : s0, c = fmaf(m, -1.f / 64, bf_lo(x[e])), d = fmaf(m, -1.f / 64, bf_hi(x[e]));
              if (e & 1) q1 = fmaf(c, c, fmaf(d, d, q1)); else q0 = fmaf(c, c, fmaf(d, d, q0));
            }
          } else {
            uint32_t* o = (uint32_t*)(out + (128 * t + 32 * (j >> 1) + 2 * r + (j & 1)) * 576 + 512 + 16 * i + 2 * q);
            o[0] = x[0]; o[8 * 576] = x[1]; o[4] = x[2]; o[8 * 576 + 4] = x[3];
          }
        }
        if (layer == 0) {
          q0 = quad_sum(q0); q1 = quad_sum(q1);
          if (q == 0) stg4(scr + OFF_S + (t * 8 + j) * 96 + 64 + r, __float_as_uint(s0) & ~1u, __float_as_uint(q0), __float_as_uint(s1), __float_as_uint(q1));
        }
      }
    } else {
      {
        uint4 v[3];
        const int p = t >> 2, k0 = (t & 3) * 144 + threadIdx.x - 320;
        const uint4* src = (const uint4*)(p == 3 ? wo + k0 * 576 : wqkv + k0 * 1728 + (p < 2 ? 576 * (p + 1) : 0)) + 9 * j + 8;
#pragma unroll
        for (int i = 0; i < 3; i++) if (i < 2 || threadIdx.x < 336) v[i] = __ldg(src + i * (p == 3 ? 8 * 576 : 8 * 1728));
        const int s = k0 >> 4, rr = k0 & 7;
        uint4* dst = scr + OFF_R + j * 2304 + (s >> 1) * 128 + ((k0 >> 3) & 1) * 64 + rr * 8 + (((s & 1) * 4 + p) ^ rr);
#pragma unroll
        for (int i = 0; i < 3; i++) if (i < 2 || threadIdx.x < 336) stg4(dst + i * 256, v[i].x, v[i].y, v[i].z, v[i].w);
        __threadfence();
        __syncwarp();
        if (lane < 16) asm volatile("st.relaxed.gpu.global.b32 [%0], 1;" :: "l"((uint32_t*)(scr + OFF_F + (lane * 8 + j) * 8) + 2 * t + w - 10) : "memory");
        asm volatile("bar.sync 4, 96;" ::: "memory");
      }
#pragma unroll 1
      for (int layer = 0; layer < 2; layer++) {
        if (w == 10) {
          if (layer) {
            mbar_wait(park_free, 0);
          } else {
            uint32_t* fl = (uint32_t*)(scr + OFF_F + (t * 8 + j) * 8) + lane;
            uint32_t v;
            int n = 0;
            while (true) {
              asm volatile("ld.acquire.gpu.global.b32 %0, [%1];" : "=r"(v) : "l"(fl) : "memory");
              if (__all_sync(~0u, v != 0u)) break;
              SPIN_GUARD(n);
            }
            asm volatile("fence.proxy.async;\nst.relaxed.gpu.global.b32 [%0], 0;" :: "l"(fl) : "memory");
          }
          bulk_load(sb + REM, scr + OFF_R + j * 2304, 36864, rem_full, true);
        }
        if (layer) mbar_wait(kv_free, 0);
        if (t > 0) {
#pragma unroll 1
          for (int pc = 0; pc < 3; pc++) {
            uint4* hp = scr + OFF_H + ((layer * 128 + t * 8 + j) * 2 + (w - 10)) * 192 + pc * 64 + lane;
            uint32_t hl[8];
            int n = 0;
            hl[4] = 1u;
            while (true) {
              ldg4(hl, hp);
              if (pc < 2) ldg4(hl + 4, hp + 32);
              if (__all_sync(~0u, hl[0] != 0u && hl[4] != 0u)) break;
              __nanosleep(100);
              SPIN_GUARD(n);
            }
            const uint32_t dst = sb + KVS + (w - 10) * 10368 + r * 144 + q * 4;
            if (pc < 2) {
#pragma unroll
              for (int g = 0; g < 8; g++) sts1(dst + pc * 20736 + g * 16, hl[g]);
              stg4(hp + 32, 0u, 0u, 0u, 0u);
            } else {
              sts1(dst + 128, hl[0]); sts1(dst + 20736 + 128, hl[1]);
            }
            stg4(hp, 0u, 0u, 0u, 0u);
          }
        }
        asm volatile("bar.arrive 1, 192;" ::: "memory");
      }
    }
  } else {
    asm volatile("setmaxnreg.inc.sync.aligned.u32 240;");
    Ring rg{0, 0};
    uint32_t prev = 0;
    uint32_t X[144];
    float rs0, rs1;
    uint32_t mean0, mean1;
    auto release = [&](uint32_t st) { if (lane == 0) mbar_arrive(empty0 + st * 8); };
    auto load_kb = [&](int kb, const uint4* src, const char* lo, uint32_t hoff) {
#pragma unroll
      for (int k = 4 * kb; k < 4 * kb + 4; k++) {
        if (k % 9 == 4) { ldg2(X + 4 * k, lo + k * 512); ldg2(X + 4 * k + 2, lo + hoff + k * 512); }
        else ldg4(X + 4 * k, src + k * 32);
      }
    };
    auto next_kb = [&](bool center, int kb, const uint4* src, const char* lo, uint32_t hoff) {
      int n = 0;
      while (true) {
        bool ok = true;
#pragma unroll
        for (int k = 4 * kb; k < 4 * kb + 4; k++) { ok = ok && X[4 * k] != 0u; if (k % 9 == 4) ok = ok && X[4 * k + 2] != 0u; }
        if (__all_sync(~0u, ok)) break;
        SPIN_GUARD(n);
        load_kb(kb, src, lo, hoff);
      }
      if (kb + GD < 9) load_kb(kb + GD, src, lo, hoff);
      if (center) {
#pragma unroll
        for (int i = 16 * kb; i < 16 * kb + 16; i++) X[i] = sub_bf16x2(X[i], (i & 1) ? mean1 : mean0);
      }
    };
#pragma unroll 1
    for (int hf = 0; hf < 4; hf++) {
      const int layer = hf >> 1;
      const bool ffn = hf & 1;
      const uint32_t tag = 1 - layer;
      uint4* const xbase = scr + OFF_X + (layer * 128 + t * 8 + w) * SLAB;
      float aA[32], aB[32];
      {
        const uint4* src = xbase + (ffn ? 512 * SLAB : 0) + lane;
        const char* lo = (const char*)src - (ffn ? lane * 8 : 0);
        const uint32_t hoff = ffn ? 256 : 8;
        uint32_t s[3][4];
        const uint4* p = scr + OFF_S + ((ffn ? 256 : 0) + t * 8 + w) * 96 + q * 8 + r;
        const bool third = !ffn && q == 0;
        int n = 0;
        s[2][0] = tag; s[2][1] = s[2][2] = s[2][3] = 0u;
        STAMP(ffn * 16 + 0);
        while (true) {
          ldg4(s[0], p); ldg4(s[1], p + 32);
          if (third) ldg4(s[2], p + 64);
          if (__all_sync(~0u, ((s[0][0] ^ tag) | (s[1][0] ^ tag) | (s[2][0] ^ tag)) % 2u == 0u)) break;
          SPIN_GUARD(n);
        }
        STAMP(ffn * 16 + 1);
#pragma unroll
        for (int kb = 0; kb < GD; kb++) load_kb(kb, src, lo, hoff);
        float t0 = 0.f, t1 = 0.f;
#pragma unroll
        for (int i = 0; i < 3; i++) { t0 += __uint_as_float(s[i][0]); t1 += __uint_as_float(s[i][2]); }
        const float m0 = quad_sum(t0) * (1.f / 576), m1 = quad_sum(t1) * (1.f / 576);
        const float cnt = ffn ? 72.f : 64.f, inv = ffn ? 1.f / 72 : 1.f / 64;
        float v0 = 0.f, v1 = 0.f;
#pragma unroll
        for (int i = 0; i < 3; i++) {
          const float c = (i < 2 || third) ? cnt : 0.f;
          const float d0 = fmaf(__uint_as_float(s[i][0]), inv, -m0), d1 = fmaf(__uint_as_float(s[i][2]), inv, -m1);
          v0 += fmaf(d0 * d0, c, __uint_as_float(s[i][1])); v1 += fmaf(d1 * d1, c, __uint_as_float(s[i][3]));
        }
        rs0 = rsqrtf(fmaf(quad_sum(v0), 1.f / 576, 1e-5f)); rs1 = rsqrtf(fmaf(quad_sum(v1), 1.f / 576, 1e-5f));
        mean0 = pack_bf16(m0, m0); mean1 = pack_bf16(m1, m1);
#pragma unroll
        for (int kb = 0; kb < 9; kb++) {
          next_kb(true, kb, src, lo, hoff);
          mbar_wait(full0 + rg.st * 8, rg.ph);
          const uint64_t desc = DESC_HI | ((sb + rg.st * STAGE) >> 4);
          wg_fence();
#pragma unroll
          for (int i = 0; i < 4; i++) wgmma_rs_n64(aA, X + 4 * (4 * kb + i), desc + i * 128, kb + i != 0);
#pragma unroll
          for (int i = 0; i < 4; i++) wgmma_rs_n64(aB, X + 4 * (4 * kb + i), desc + 512 + i * 128, kb + i != 0);
          wg_commit();
          wg_wait<1>();
          if (kb > 0) release(prev);
          prev = rg.st; rg.next();
        }
        wg_wait<0>();
        STAMP(ffn * 16 + 2);
      }
      if (!ffn) {
      release(prev);
      const uint32_t kvrow = sb + KVS + (w & 1) * 10368 + (16 * (w >> 1)) * 144;
      uint32_t Q[18];
      {
        const uint32_t dst = kvrow + (8 + r) * 144 + q * 4;
        const bool edge_out = w >= 6 && t < 15;
        uint4* const hp = scr + OFF_H + ((layer * 128 + (t + 1) * 8 + j) * 2 + (w & 1)) * 192 + lane;
        auto put_kv = [&](float (&a)[32], int part) {
          pin(a);
          uint32_t hl[8];
#pragma unroll
          for (int g = 0; g < 8; g++) {
            hl[g] = pack_bf16(a[4 * g + 2] * rs1, a[4 * g + 3] * rs1);
            sts1(dst + part * 20736 + g * 16, pack_bf16(a[4 * g] * rs0, a[4 * g + 1] * rs0)); sts1(dst + part * 20736 + 8 * 144 + g * 16, hl[g]);
          }
          if (edge_out) { stg4(hp + part * 64, nz(hl[0]), hl[1], hl[2], hl[3]); stg4(hp + part * 64 + 32, nz(hl[4]), hl[5], hl[6], hl[7]); }
        };
        put_kv(aA, 0);
        float aR[12];
        mbar_wait(rem_full, layer);
        const uint64_t dr = DESC_HI | ((sb + REM) >> 4);
        wg_fence();
#pragma unroll
        for (int s = 0; s < 36; s++) {
          wgmma_rs_n24(aR, X + 4 * s, dr + ((s >> 1) * 128 + (s & 1) * 4), s != 0);
          if (s == 4) put_kv(aB, 1);
        }
        wg_commit();
#pragma unroll
        for (int kb = 0; kb < 9; kb++) {
          if (!(kb & 1)) mbar_wait(full0 + rg.st * 8, rg.ph);
          const uint64_t desc = DESC_HI | ((sb + rg.st * STAGE + (kb & 1) * 8192) >> 4);
          wg_fence();
#pragma unroll
          for (int i = 0; i < 4; i++) wgmma_rs_n64(aB, X + 4 * (4 * kb + i), desc + i * 128, kb + i != 0);
          wg_commit();
          wg_wait<1>();
          if (kb > 0 && !(kb & 1)) release(prev);
          if ((kb & 1) || kb == 8) { prev = rg.st; rg.next(); }
          if (kb == 0) {
            pin(aR);
            const uint32_t k1 = pack_bf16(aR[2] * rs1, aR[3] * rs1), v1 = pack_bf16(aR[6] * rs1, aR[7] * rs1);
            if (edge_out) stg4(hp + 128, nz(k1), v1, 0u, 0u);
            sts1(dst + 128, pack_bf16(aR[0] * rs0, aR[1] * rs0)); sts1(dst + 8 * 144 + 128, k1);
            sts1(dst + 20736 + 128, pack_bf16(aR[4] * rs0, aR[5] * rs0)); sts1(dst + 20736 + 8 * 144 + 128, v1);
            Q[16] = pack_bf16(aR[8] * rs0, aR[9] * rs0); Q[17] = pack_bf16(aR[10] * rs1, aR[11] * rs1);
            if (w < 4) asm volatile("bar.arrive 2, 256;" ::: "memory");
          }
        }
        wg_wait<0>();
        release(prev);
        pin(aB);
        STAMP(3);
#pragma unroll
        for (int g = 0; g < 8; g++) {
          Q[2 * g] = pack_bf16(aB[4 * g] * rs0, aB[4 * g + 1] * rs0); Q[2 * g + 1] = pack_bf16(aB[4 * g + 2] * rs1, aB[4 * g + 3] * rs1);
        }
      }
      if (w < 4) asm volatile("bar.sync 1, 192;" ::: "memory");
      else asm volatile("bar.sync 2, 256;" ::: "memory");
      STAMP(4);
      uint32_t O[18];
      {
        const bool edge = (t == 0 && w < 2);
        uint32_t row[3];
#pragma unroll
        for (int nt = 0; nt < 3; nt++) row[nt] = kvrow + (8 * nt + (lane & 7)) * 144;
        if (edge) row[0] = sb + KVS + 8 * 144;
        const uint32_t rlast = ((lane >> 3) == 0 ? row[0] : (lane >> 3) == 1 ? row[1] : row[2]) + 128;
        uint32_t K[3][9], V[3][9], dummy;
#pragma unroll
        for (int nt = 0; nt < 3; nt++) {
          ldsm4(row[nt] + (lane >> 3) * 16, K[nt][0], K[nt][1], K[nt][2], K[nt][3]);
          ldsm4(row[nt] + 64 + (lane >> 3) * 16, K[nt][4], K[nt][5], K[nt][6], K[nt][7]);
        }
        ldsm4(rlast, K[0][8], K[1][8], K[2][8], dummy);
#pragma unroll
        for (int nt = 0; nt < 3; nt++) {
          ldsm4t(row[nt] + 20736 + (lane >> 3) * 16, V[nt][0], V[nt][1], V[nt][2], V[nt][3]);
          ldsm4t(row[nt] + 20736 + 64 + (lane >> 3) * 16, V[nt][4], V[nt][5], V[nt][6], V[nt][7]);
        }
        ldsm4t(rlast + 20736, V[0][8], V[1][8], V[2][8], dummy);
        const bool up0 = 2 * q > r, up1 = 2 * q + 1 > r;
        const float sc = 0.23570226039551584f * 1.4426950408889634f;
        const float neg = -1e9f * 1.4426950408889634f;
        float Of[9][4];
#pragma unroll
        for (int h = 0; h < 4; h++) {
          const uint32_t a0 = q >= h ? Q[4 * h] : 0u, a1 = q >= h ? Q[4 * h + 1] : 0u;
          const uint32_t a4 = q <= h ? Q[4 * h + 4] : 0u, a5 = q <= h ? Q[4 * h + 5] : 0u;
          float S[3][4];
#pragma unroll
          for (int nt = 0; nt < 3; nt++) {
            S[nt][0] = S[nt][1] = S[nt][2] = S[nt][3] = 0.f;
            mma16(S[nt], a0, a1, Q[4 * h + 2], Q[4 * h + 3], K[nt][2 * h], K[nt][2 * h + 1]);
            mma8(S[nt], a4, a5, K[nt][2 * h + 2]);
          }
          float s00 = (up0 ? S[0][0] : S[1][0]) * sc, s01 = (up1 ? S[0][1] : S[1][1]) * sc;
          const float s10 = (up0 ? S[1][2] : S[2][2]) * sc, s11 = (up1 ? S[1][3] : S[2][3]) * sc;
          if (edge && up0) s00 = neg;
          if (edge && up1) s01 = neg;
          const float m0 = quad_max(fmaxf(s00, s01)), m1 = quad_max(fmaxf(s10, s11));
          float p00 = ex2(s00 - m0), p01 = ex2(s01 - m0), p10 = ex2(s10 - m1), p11 = ex2(s11 - m1);
          const float i0 = rcp(quad_sum(p00 + p01)), i1 = rcp(quad_sum(p10 + p11));
          p00 *= i0; p01 *= i0; p10 *= i1; p11 *= i1;
          const uint32_t pa = pack_bf16(up0 ? p00 : 0.f, up1 ? p01 : 0.f), pb = pack_bf16(up0 ? 0.f : p00, up1 ? 0.f : p01);
          const uint32_t pc = pack_bf16(up0 ? p10 : 0.f, up1 ? p11 : 0.f), pd = pack_bf16(up0 ? 0.f : p10, up1 ? 0.f : p11);
#pragma unroll
          for (int gi = 0; gi < 3; gi++) {
            const int g = 2 * h + gi;
            float o[4] = {0.f, 0.f, 0.f, 0.f};
            mma16(o, pa, 0u, pb, pc, V[0][g], V[1][g]);
            mma8(o, 0u, pd, V[2][g]);
#pragma unroll
            for (int e = 0; e < 4; e++) Of[g][e] = (gi == 0 && h > 0 && q < h) ? Of[g][e] : o[e];
          }
        }
#pragma unroll
        for (int g = 0; g < 9; g++) { O[2 * g] = pack_bf16(Of[g][0], Of[g][1]); O[2 * g + 1] = pack_bf16(Of[g][2], Of[g][3]); }
      }
      put72(xbase + 256 * SLAB, j, lane, O);
      if (q == 0) stg4(scr + OFF_S + (128 + t * 8 + w) * 96 + j * 8 + r, tag, 0u, 0u, 0u);
      {
        uint32_t res[18];
        const char* p = (const char*)(xbase + lane) + ((9 * j) >> 1) * 512 + (j & 1) * 8;
#pragma unroll
        for (int g = 0; g < 9; g++) ldg2(res + 2 * g, p + (g >> 1) * 512 + ((g & 1) ? ((j & 1) ? 504 : 8) : 0));
        const uint4* src = xbase + 256 * SLAB + lane;
        {
          const uint4* fp = scr + OFF_S + (128 + t * 8 + w) * 96 + q * 8 + r;
          uint32_t s0[4], s1[4];
          int n = 0;
          STAMP(8);
          while (true) {
            ldg4(s0, fp); ldg4(s1, fp + 32);
            if (__all_sync(~0u, ((s0[0] ^ tag) | (s1[0] ^ tag)) % 2u == 0u)) break;
            SPIN_GUARD(n);
          }
          STAMP(9);
        }
#pragma unroll
        for (int kb = 0; kb < GD; kb++) load_kb(kb, src, (const char*)src - lane * 8, 256);
        float acc[36];
#pragma unroll
        for (int kb = 0; kb < 9; kb++) {
          next_kb(false, kb, src, (const char*)src - lane * 8, 256);
          if (!(kb & 1)) mbar_wait(full0 + rg.st * 8, rg.ph);
          const uint32_t base = sb + rg.st * STAGE + (kb & 1) * 8192;
          const uint64_t d0 = DESC_HI | ((base >> 4) + (((sb + REM + kb * 4096 + 48 - base) >> 4) << 16));
          wg_fence();
#pragma unroll
          for (int i = 0; i < 4; i++)
            wgmma_rs_n72(acc, X + 4 * (4 * kb + i), d0 + (uint64_t)(i * 128) - ((uint64_t)(((i + 1) >> 1) * 128 - (i & 1) * 4) << 16), kb + i != 0);
          wg_commit();
          wg_wait<1>();
          if (kb > 0 && !(kb & 1)) release(prev);
          if ((kb & 1) || kb == 8) { prev = rg.st; rg.next(); }
        }
        wg_wait<0>();
        release(prev);
        pin(acc);
        STAMP(10);
#pragma unroll
        for (int i = 0; i < 18; i++) {
          acc[2 * i] += bf_lo(res[i]); acc[2 * i + 1] += bf_hi(res[i]);
          res[i] = pack_bf16(acc[2 * i], acc[2 * i + 1]);
        }
        put72(xbase + 512 * SLAB, j, lane, res);
        publish_stats<9>(scr + OFF_S + (256 + t * 8 + w) * 96 + j * 8, acc, tag, lane);
      }
      continue;
      }
      const uint32_t hp = sb + PARK + w * 512 + lane * 16;
      auto pack8 = [&](float (&a)[32], int p, uint32_t* o) {
#pragma unroll
        for (int e = 0; e < 8; e++) asm volatile("" : "+f"(a[8 * p + e]) :: "memory");
#pragma unroll
        for (int e = 0; e < 4; e++) o[e] = pack_bf16(a[8 * p + 2 * e], a[8 * p + 2 * e + 1]);
      };
      const float ka0 = 0.7978845608028654f * rs0, kb0 = 0.044715f * ka0 * rs0 * rs0, ku0 = 0.5f * rs0 * rs0;
      const float ka1 = 0.7978845608028654f * rs1, kb1 = 0.044715f * ka1 * rs1 * rs1, ku1 = 0.5f * rs1 * rs1;
      auto packu8 = [&](int p, uint32_t* o) {
#pragma unroll
        for (int e = 0; e < 8; e++) asm volatile("" : "+f"(aA[8 * p + e]) :: "memory");
#pragma unroll
        for (int e = 0; e < 4; e++) o[e] = pack_bf16(aA[8 * p + 2 * e] * ((e & 1) ? ku1 : ku0), aA[8 * p + 2 * e + 1] * ((e & 1) ? ku1 : ku0));
      };
      auto geglu8 = [&](int p, uint32_t* u) {
#pragma unroll
        for (int e = 0; e < 8; e++) asm volatile("" : "+f"(aB[8 * p + e]) :: "memory");
        float h[8];
#pragma unroll
        for (int e = 0; e < 8; e++) {
          const float g = aB[8 * p + e];
          h[e] = fmaf(g, tanh_ap(g * fmaf(g * g, (e & 2) ? kb1 : kb0, (e & 2) ? ka1 : ka0)), g);
        }
#pragma unroll
        for (int e = 0; e < 4; e++) u[e] = mul_bf16x2(pack_bf16(h[2 * e], h[2 * e + 1]), u[e]);
      };
      auto box = [&](int b, auto&& filler) {
        const int kb = b < 9 ? b : b - 9;
        if (!(b & 1)) mbar_wait(full0 + rg.st * 8, rg.ph);
        const uint64_t desc = DESC_HI | ((sb + rg.st * STAGE + (b & 1) * 8192) >> 4);
        wg_fence();
#pragma unroll
        for (int i = 0; i < 4; i++) {
          if (b < 9) wgmma_rs_n64(aA, X + 4 * (4 * kb + i), desc + i * 128, kb + i != 0);
          else wgmma_rs_n64(aB, X + 4 * (4 * kb + i), desc + i * 128, kb + i != 0);
          if (i == FPOS) filler();
        }
        wg_commit();
        if (b & 1) { if (W2) wg_wait<1>(); prev = rg.st; rg.next(); } else { wg_wait<1>(); release(prev); }
      };
      auto nop = [] {};
      auto step = [&](int st, auto&& filler) { box(2 * st, nop); box(2 * st + 1, filler); };
#pragma unroll
      for (int p = 0; p < 4; p++) { uint32_t o[4]; packu8(p, o); sts4(hp + p * 4096, o); }
      box(0, nop);
      zero_share(xbase, j, lane);
      zero_share(xbase + 256 * SLAB, j, lane);
#pragma unroll 1
      for (int c = 1;; c++) {
        const uint32_t hc = hp + c * 4 * 4096;
#pragma unroll
        for (int b = 1; b < 18; b++) box(b, [&] {
          if ((b & 1) && b < 8) { uint32_t o[4]; const uint32_t a = hc - (4 - (b >> 1)) * 4096; lds4(a, o); geglu8(b >> 1, o); sts4(a, o); }
          if ((b & 1) && b > 10) { uint32_t o[4]; packu8((b - 11) >> 1, o); if (c < 8) sts4(hc + ((b - 11) >> 1) * 4096, o); } });
        if (c == 8) break;
        box(0, nop);
      }
      wg_wait<0>();
      STAMP(21);
#pragma unroll
      for (int s = 0; s < 32; s++) lds4(hp + s * 4096, X + 4 * s);
#pragma unroll
      for (int p = 0; p < 4; p++) packu8(p, X + 128 + 4 * p);
#pragma unroll
      for (int st = 0; st < 4; st++) step(st, [&] { geglu8(st, X + 128 + 4 * st); });
      STAMP(24);
      if (layer == 0 && lane == 0) mbar_arrive(park_free);
      int lane2 = lane;
      asm volatile("" : "+r"(lane2));
      uint4* const pw = scr + OFF_P + ((t * 8 + j) * 8 + w) * SLAB + lane2;
      const uint4* const pr = scr + OFF_P + (t * 64 + w) * SLAB + 4 * j * 32 + lane2;
      auto put_part = [&](float (&a)[32], int p, int chunk) {
        uint32_t o[4];
        pack8(a, p, o);
        stg4(pw + (chunk * 4 + p) * 32, (o[0] & ~1u) | tag, o[1], o[2], o[3]);
      };
      auto slot = [&](int p) { return sb + w * 2048 + (p < 4 ? PARK + (p - 1) * 16384 : KVS + (p - 4) * 16384); };
      auto fetch = [&](int p) {
        if (p > 0) bulk_load(slot(p), scr + OFF_P + (t * 64 + ((j - p) & 7) * 8 + w) * SLAB + 4 * j * 32, 2048, pbar0 + w * 8, true);
      };
      uint4* const xb = xbase + 512 * SLAB + 4 * j * 32;
#pragma unroll 1
      for (int sp = 0;; sp++) {
        const int ca = sp == 0 ? 8 : ((j + 2 * sp) & 7), cb = (j + 2 * sp + 1) & 7;
        if (sp == 1 && lane == 0) mbar_arrive(c8_go);
#pragma unroll
        for (int st = 4; st < 9; st++) step(st, [&] {
          if (st == 5 || st == 6) { put_part(aA, 2 * (st - 5), ca); put_part(aA, 2 * (st - 5) + 1, ca); }
          if (st == 8) { if (sp == 3) mbar_wait(c8_done, layer); fetch(2 * sp - 1); } });
        STAMP(25 + sp);
        if (sp == 3) break;
        if (sp == 2) asm volatile("{\n.reg .pred e;\nelect.sync _|e, 0xffffffff;\n@e cp.async.bulk.prefetch.L2.global [%0], 2048;\n}" :: "l"(xb) : "memory");
#pragma unroll
        for (int st = 0; st < 4; st++) step(st, [&] {
          if (st < 2) { put_part(aB, 2 * st, cb); put_part(aB, 2 * st + 1, cb); }
          if (st == 3) fetch(2 * sp); });
      }
      auto load_p = [&](int p, uint32_t* d) {
#pragma unroll
        for (int i = 0; i < 4; i++) ldg4(d + 4 * i, pr + ((j - p) & 7) * 8 * SLAB + i * 32);
      };
#pragma unroll
      for (int st = 0; st < 4; st++) step(st, [&] {
        if (st == 0) {
#pragma unroll
          for (int p = 0; p < 4; p++) put_part(aB, p, (j + 7) & 7);
        }
        if (st == 1) {
#pragma unroll
          for (int i = 0; i < 4; i++) {
            const bool split = j == 2 * i + 1;
            const char* l = (const char*)(xb + i * 32) + (split ? lane2 * 8 : lane2 * 16);
            ldg2(X + 4 * i, l); ldg2(X + 4 * i + 2, l + (split ? 256 : 8));
          }
          load_p(6, X + 16);
        }
        if (st == 3) load_p(7, X + 32); });
      {
        mbar_wait(full0 + rg.st * 8, rg.ph);
        const uint64_t desc = DESC_HI | ((sb + rg.st * STAGE) >> 4);
        wg_fence();
#pragma unroll
        for (int i = 0; i < 4; i++) wgmma_rs_n64(aA, X + 4 * (32 + i), desc + i * 128, 1);
        wg_commit();
        wg_wait<1>(); release(prev);
        prev = rg.st; rg.next();
        mbar_wait(pbar0 + w * 8, layer);
        wg_wait<0>(); release(prev);
        pin(aA);
      }
      STAMP(22);
      {
        const uint32_t eye = r == 2 * q ? 0x3f80u : r == 2 * q + 1 ? 0x3f800000u : 0u;
        auto add_p = [&](int p, uint32_t* d) {
          int n = 0;
          while (!__all_sync(~0u, (((d[0] ^ tag) | (d[4] ^ tag) | (d[8] ^ tag) | (d[12] ^ tag)) & 1u) == 0u)) { SPIN_GUARD(n); load_p(p, d); }
#pragma unroll
          for (int g = 0; g < 8; g++) mma8(aA + 4 * g, d[2 * g], d[2 * g + 1], eye);
        };
#pragma unroll
        for (int p = 1; p < 6; p++)
#pragma unroll
          for (int i = 0; i < 4; i++) lds4(slot(p) + lane2 * 16 + i * 512, X + 32 + 16 * p + 4 * i);
#pragma unroll
        for (int g = 0; g < 8; g++) mma8(aA + 4 * g, X[2 * g], X[2 * g + 1], eye);
#pragma unroll
        for (int p = 1; p < 6; p++) add_p(p, X + 32 + 16 * p);
        add_p(6, X + 16); add_p(7, X + 32);
        uint32_t res[16];
#pragma unroll
        for (int i = 0; i < 16; i++) res[i] = pack_bf16(aA[2 * i], aA[2 * i + 1]);
        if (layer == 0) {
          uint4* p = xbase + 128 * SLAB + 4 * j * 32 + lane;
#pragma unroll
          for (int i = 0; i < 4; i++) stg4(p + i * 32, nz(res[4 * i]), res[4 * i + 1], nz(res[4 * i + 2]), res[4 * i + 3]);
          publish_stats<8>(scr + OFF_S + (t * 8 + w) * 96 + j * 8, aA, 0u, lane);
          if (lane == 0) mbar_arrive(kv_free);
        } else {
          uint32_t* o = (uint32_t*)(out + (128 * t + 32 * (w >> 1) + 2 * r + (w & 1)) * 576 + 64 * j + 2 * q);
#pragma unroll
          for (int g = 0; g < 8; g++) { o[4 * g] = res[2 * g]; o[8 * 576 + 4 * g] = res[2 * g + 1]; }
        }
#pragma unroll
        for (int i = 0; i < 4; i++) stg4(xb + lane + i * 32, 0u, 0u, 0u, 0u);
      }
      STAMP(23);
    }
  }
}

typedef CUresult (*EncodeFn)(CUtensorMap*, CUtensorMapDataType, cuuint32_t, void*, const cuuint64_t*, const cuuint64_t*,
                             const cuuint32_t*, const cuuint32_t*, CUtensorMapInterleave, CUtensorMapSwizzle,
                             CUtensorMapL2promotion, CUtensorMapFloatOOBfill);

CUtensorMap make_map(EncodeFn f, const void* p, uint64_t cols, uint64_t rows) {
  CUtensorMap m;
  cuuint64_t dims[2] = {cols, rows};
  cuuint64_t str[1] = {cols * 2};
  cuuint32_t box[2] = {64, 64};
  cuuint32_t es[2] = {1, 1};
  f(&m, CU_TENSOR_MAP_DATA_TYPE_BFLOAT16, 2, const_cast<void*>(p), dims, str, box, es, CU_TENSOR_MAP_INTERLEAVE_NONE,
    CU_TENSOR_MAP_SWIZZLE_128B, CU_TENSOR_MAP_L2_PROMOTION_NONE, CU_TENSOR_MAP_FLOAT_OOB_FILL_NONE);
  return m;
}

}

extern "C" void kernel_launch(void* const* d_in, const int* in_sizes, int n_in, void* d_out, int out_size) {
  void* fn = nullptr;
  cudaDriverEntryPointQueryResult qr;
  cudaGetDriverEntryPoint("cuTensorMapEncodeTiled", &fn, cudaEnableDefault, &qr);
  EncodeFn enc = (EncodeFn)fn;
  Maps maps;
  maps.m[0] = make_map(enc, d_in[1], 1728, 576); maps.m[1] = make_map(enc, d_in[2], 576, 576);
  maps.m[2] = make_map(enc, d_in[4], 4608, 576); maps.m[3] = make_map(enc, d_in[5], 4608, 576); maps.m[4] = make_map(enc, d_in[6], 576, 4608);
  void* scr = nullptr;
  cudaGetSymbolAddress(&scr, g_scratch);
  cudaFuncSetAttribute(mega_kernel, cudaFuncAttributeMaxDynamicSharedMemorySize, SMEM_BYTES);
  mega_kernel<<<128, 384, SMEM_BYTES>>>(maps, (uint4*)scr, (const __nv_bfloat16*)d_in[0], (const __nv_bfloat16*)d_in[1],
                                        (const __nv_bfloat16*)d_in[2], (__nv_bfloat16*)d_out);
}
```

```cpp
#include <cuda_runtime.h>
#include <cuda.h>
#include <cuda_bf16.h>
#include <stdint.h>

#define TRACE 0
#define FPOS 2
#define W2 0

namespace {

constexpr int NST = 6;
constexpr int STAGE = 16384;
constexpr int PARK = NST * STAGE;
constexpr int REM = PARK + 49152;
constexpr int KVS = REM + 40960;
constexpr int HSTG = KVS + 16384;
constexpr int BARS = KVS + 41472;
constexpr int TRC = BARS + 256;
constexpr int SMEM_BYTES = TRC + (TRACE ? 512 : 0);
static_assert(BARS >= PARK + 131072, "barriers overlap park");
static_assert(SMEM_BYTES <= 232448, "smem");

constexpr int SLAB = 36 * 32;
constexpr int SPIN_MAX = 1 << 17;
constexpr int GD = 3;
constexpr int OFF_S = 0;
constexpr int OFF_H = OFF_S + 3 * 8 * 96;
constexpr int OFF_X = OFF_H + 2 * 8 * 384;
constexpr int OFF_P = OFF_X + 6 * 8 * SLAB;
constexpr int TILE = OFF_P + 8 * 8 * SLAB;
constexpr int OFF_R = 16 * TILE;
constexpr int OFF_F = OFF_R + 8 * 2304;
constexpr int SCRATCH = OFF_F + 128 * 8;

}

__device__ uint4 g_scratch[SCRATCH];

namespace {

constexpr uint64_t DESC_HI = 0x4000004000000000ull;
__device__ __forceinline__ void wgmma_rs_n64(float (&d)[32], const uint32_t* a, uint64_t desc, int scale_d) {
  asm volatile("{\n.reg .pred p;\nsetp.ne.b32 p, %37, 0;\n"
    "wgmma.mma_async.sync.aligned.m64n64k16.f32.bf16.bf16 "
    "{%0, %1, %2, %3, %4, %5, %6, %7, %8, %9, %10, %11, %12, %13, %14, %15, %16, %17, %18, %19, %20, %21, %22, %23, %24, %25, %26, %27, %28, %29, %30, %31}, "
    "{%32, %33, %34, %35}, %36, p, 1, 1, 1;\n}\n"
    : "+f"(d[0]), "+f"(d[1]), "+f"(d[2]), "+f"(d[3]), "+f"(d[4]), "+f"(d[5]), "+f"(d[6]), "+f"(d[7]), "+f"(d[8]), "+f"(d[9]), "+f"(d[10]), "+f"(d[11]), "+f"(d[12]), "+f"(d[13]), "+f"(d[14]), "+f"(d[15]), "+f"(d[16]), "+f"(d[17]), "+f"(d[18]), "+f"(d[19]), "+f"(d[20]), "+f"(d[21]), "+f"(d[22]), "+f"(d[23]), "+f"(d[24]), "+f"(d[25]), "+f"(d[26]), "+f"(d[27]), "+f"(d[28]), "+f"(d[29]), "+f"(d[30]), "+f"(d[31])
    : "r"(a[0]), "r"(a[1]), "r"(a[2]), "r"(a[3]), "l"(desc), "r"(scale_d));
}
__device__ __forceinline__ void wgmma_rs_n72(float (&d)[36], const uint32_t* a, uint64_t desc, int scale_d) {
  asm volatile("{\n.reg .pred p;\nsetp.ne.b32 p, %41, 0;\n"
    "wgmma.mma_async.sync.aligned.m64n72k16.f32.bf16.bf16 "
    "{%0, %1, %2, %3, %4, %5, %6, %7, %8, %9, %10, %11, %12, %13, %14, %15, %16, %17, %18, %19, %20, %21, %22, %23, %24, %25, %26, %27, %28, %29, %30, %31, %32, %33, %34, %35}, "
    "{%36, %37, %38, %39}, %40, p, 1, 1, 1;\n}\n"
    : "+f"(d[0]), "+f"(d[1]), "+f"(d[2]), "+f"(d[3]), "+f"(d[4]), "+f"(d[5]), "+f"(d[6]), "+f"(d[7]), "+f"(d[8]), "+f"(d[9]), "+f"(d[10]), "+f"(d[11]), "+f"(d[12]), "+f"(d[13]), "+f"(d[14]), "+f"(d[15]), "+f"(d[16]), "+f"(d[17]), "+f"(d[18]), "+f"(d[19]), "+f"(d[20]), "+f"(d[21]), "+f"(d[22]), "+f"(d[23]), "+f"(d[24]), "+f"(d[25]), "+f"(d[26]), "+f"(d[27]), "+f"(d[28]), "+f"(d[29]), "+f"(d[30]), "+f"(d[31]), "+f"(d[32]), "+f"(d[33]), "+f"(d[34]), "+f"(d[35])
    : "r"(a[0]), "r"(a[1]), "r"(a[2]), "r"(a[3]), "l"(desc), "r"(scale_d));
}

__device__ __forceinline__ void wgmma_rs_n24(float (&d)[12], const uint32_t* a, uint64_t desc, int scale_d) {
  asm volatile("{\n.reg .pred p;\nsetp.ne.b32 p, %17, 0;\n"
    "wgmma.mma_async.sync.aligned.m64n24k16.f32.bf16.bf16 "
    "{%0, %1, %2, %3, %4, %5, %6, %7, %8, %9, %10, %11}, "
    "{%12, %13, %14, %15}, %16, p, 1, 1, 1;\n}\n"
    : "+f"(d[0]), "+f"(d[1]), "+f"(d[2]), "+f"(d[3]), "+f"(d[4]), "+f"(d[5]), "+f"(d[6]), "+f"(d[7]), "+f"(d[8]), "+f"(d[9]), "+f"(d[10]), "+f"(d[11])
    : "r"(a[0]), "r"(a[1]), "r"(a[2]), "r"(a[3]), "l"(desc), "r"(scale_d));
}

__device__ __forceinline__ void mbar_init(uint32_t a, uint32_t c) { asm volatile("mbarrier.init.shared::cta.b64 [%0], %1;" :: "r"(a), "r"(c)); }
__device__ __forceinline__ void mbar_arrive(uint32_t a) { asm volatile("mbarrier.arrive.shared::cta.b64 _, [%0];" :: "r"(a) : "memory"); }
__device__ __forceinline__ void mbar_wait(uint32_t a, uint32_t ph) {
  asm volatile("{\n.reg .pred p;\n.reg .u32 n;\n"
               "mbarrier.try_wait.parity.shared::cta.b64 p, [%0], %1;\n@p bra D;\n"
               "mov.u32 n, 0;\n"
               "W: mbarrier.try_wait.parity.shared::cta.b64 p, [%0], %1;\n@p bra D;\n"
               "add.u32 n, n, 1;\nsetp.lt.u32 p, n, 4194304;\n@p bra W;\ntrap;\nD:\n}" :: "r"(a), "r"(ph) : "memory");
}
__device__ __forceinline__ void wg_fence() { asm volatile("wgmma.fence.sync.aligned;" ::: "memory"); }
__device__ __forceinline__ void wg_commit() { asm volatile("wgmma.commit_group.sync.aligned;" ::: "memory"); }
template <int N> __device__ __forceinline__ void wg_wait() { asm volatile("wgmma.wait_group.sync.aligned %0;" :: "n"(N) : "memory"); }
__device__ __forceinline__ float tanh_ap(float x) { float y; asm("tanh.approx.f32 %0, %1;" : "=f"(y) : "f"(x)); return y; }
__device__ __forceinline__ float ex2(float x) { float y; asm("ex2.approx.ftz.f32 %0, %1;" : "=f"(y) : "f"(x)); return y; }
__device__ __forceinline__ uint32_t pack_bf16(float lo, float hi) { uint32_t r; asm("cvt.rn.bf16x2.f32 %0, %1, %2;" : "=r"(r) : "f"(hi), "f"(lo)); return r; }
__device__ __forceinline__ float bf_lo(uint32_t v) { return __uint_as_float(v << 16); }
__device__ __forceinline__ float bf_hi(uint32_t v) { return __uint_as_float(v & 0xffff0000u); }
__device__ __forceinline__ uint32_t sub_bf16x2(uint32_t a, uint32_t b) { uint32_t r; asm("sub.rn.bf16x2 %0, %1, %2;" : "=r"(r) : "r"(a), "r"(b)); return r; }
__device__ __forceinline__ uint32_t mul_bf16x2(uint32_t a, uint32_t b) { uint32_t r; asm("mul.rn.bf16x2 %0, %1, %2;" : "=r"(r) : "r"(a), "r"(b)); return r; }
__device__ __forceinline__ uint32_t nz(uint32_t w) { return w == 0u ? 0x8000u : w; }

__device__ __forceinline__ void ldg4(uint32_t* d, const uint4* p) {
  asm volatile("ld.relaxed.gpu.global.v4.b32 {%0,%1,%2,%3}, [%4];" : "=r"(d[0]), "=r"(d[1]), "=r"(d[2]), "=r"(d[3]) : "l"(p) : "memory");
}
__device__ __forceinline__ void ldg2(uint32_t* d, const void* p) {
  asm volatile("ld.relaxed.gpu.global.v2.b32 {%0,%1}, [%2];" : "=r"(d[0]), "=r"(d[1]) : "l"(p) : "memory");
}
__device__ __forceinline__ void stg4(uint4* p, uint32_t a, uint32_t b, uint32_t c, uint32_t d) {
  asm volatile("st.relaxed.gpu.global.v4.b32 [%0], {%1,%2,%3,%4};" :: "l"(p), "r"(a), "r"(b), "r"(c), "r"(d) : "memory");
}
__device__ __forceinline__ void stg2(void* p, uint32_t a, uint32_t b) {
  asm volatile("st.relaxed.gpu.global.v2.b32 [%0], {%1,%2};" :: "l"(p), "r"(a), "r"(b) : "memory");
}
__device__ __forceinline__ void sts4(uint32_t a, const uint32_t* o) { asm volatile("st.shared.v4.b32 [%0], {%1,%2,%3,%4};" :: "r"(a), "r"(o[0]), "r"(o[1]), "r"(o[2]), "r"(o[3]) : "memory"); }
__device__ __forceinline__ void lds4(uint32_t a, uint32_t* o) { asm volatile("ld.shared.v4.b32 {%0,%1,%2,%3}, [%4];" : "=r"(o[0]), "=r"(o[1]), "=r"(o[2]), "=r"(o[3]) : "r"(a) : "memory"); }
__device__ __forceinline__ void lds2(uint32_t a, uint32_t* o) { asm volatile("ld.shared.v2.b32 {%0,%1}, [%2];" : "=r"(o[0]), "=r"(o[1]) : "r"(a) : "memory"); }
__device__ __forceinline__ float rcp(float x) { float y; asm("rcp.approx.ftz.f32 %0, %1;" : "=f"(y) : "f"(x)); return y; }
__device__ __forceinline__ void sts1(uint32_t a, uint32_t v) { asm volatile("st.shared.b32 [%0], %1;" :: "r"(a), "r"(v) : "memory"); }
__device__ __forceinline__ void ldsm4(uint32_t a, uint32_t& r0, uint32_t& r1, uint32_t& r2, uint32_t& r3) {
  asm volatile("ldmatrix.sync.aligned.m8n8.x4.shared.b16 {%0,%1,%2,%3}, [%4];" : "=r"(r0), "=r"(r1), "=r"(r2), "=r"(r3) : "r"(a) : "memory");
}
__device__ __forceinline__ void ldsm4t(uint32_t a, uint32_t& r0, uint32_t& r1, uint32_t& r2, uint32_t& r3) {
  asm volatile("ldmatrix.sync.aligned.m8n8.x4.trans.shared.b16 {%0,%1,%2,%3}, [%4];" : "=r"(r0), "=r"(r1), "=r"(r2), "=r"(r3) : "r"(a) : "memory");
}
__device__ __forceinline__ void mma16(float* c, uint32_t a0, uint32_t a1, uint32_t a2, uint32_t a3, uint32_t b0, uint32_t b1) {
  asm("mma.sync.aligned.m16n8k16.row.col.f32.bf16.bf16.f32 {%0,%1,%2,%3}, {%4,%5,%6,%7}, {%8,%9}, {%0,%1,%2,%3};"
    : "+f"(c[0]), "+f"(c[1]), "+f"(c[2]), "+f"(c[3]) : "r"(a0), "r"(a1), "r"(a2), "r"(a3), "r"(b0), "r"(b1));
}
__device__ __forceinline__ void mma8(float* c, uint32_t a0, uint32_t a1, uint32_t b0) {
  asm("mma.sync.aligned.m16n8k8.row.col.f32.bf16.bf16.f32 {%0,%1,%2,%3}, {%4,%5}, {%6}, {%0,%1,%2,%3};"
    : "+f"(c[0]), "+f"(c[1]), "+f"(c[2]), "+f"(c[3]) : "r"(a0), "r"(a1), "r"(b0));
}
__device__ __forceinline__ float quad_sum(float v) { v += __shfl_xor_sync(~0u, v, 1); v += __shfl_xor_sync(~0u, v, 2); return v; }
__device__ __forceinline__ float quad_max(float v) { v = fmaxf(v, __shfl_xor_sync(~0u, v, 1)); v = fmaxf(v, __shfl_xor_sync(~0u, v, 2)); return v; }
template <int N> __device__ __forceinline__ void pin(float (&d)[N]) {
#pragma unroll
  for (int i = 0; i < N; i++) asm volatile("" : "+f"(d[i]) :: "memory");
}
#define SPIN_GUARD(n) if (++(n) > SPIN_MAX) break

template <int NG> __device__ __forceinline__ void publish_stats(uint4* dst, const float* y, uint32_t tag, int lane) {
  float s0 = 0.f, s1 = 0.f;
#pragma unroll
  for (int g = 0; g < NG; g++) { s0 += y[4 * g] + y[4 * g + 1]; s1 += y[4 * g + 2] + y[4 * g + 3]; }
  s0 = quad_sum(s0); s1 = quad_sum(s1);
  const float m0 = s0 * (1.f / (8 * NG)), m1 = s1 * (1.f / (8 * NG));
  float q0 = 0.f, q1 = 0.f, q2 = 0.f, q3 = 0.f;
#pragma unroll
  for (int g = 0; g < NG; g++) {
    const float a = y[4 * g] - m0, b = y[4 * g + 1] - m0, c = y[4 * g + 2] - m1, d = y[4 * g + 3] - m1;
    q0 = fmaf(a, a, q0); q1 = fmaf(b, b, q1); q2 = fmaf(c, c, q2); q3 = fmaf(d, d, q3);
  }
  q0 = quad_sum(q0 + q1); q2 = quad_sum(q2 + q3);
  if ((lane & 3) == 0)
    stg4(dst + (lane >> 2), (__float_as_uint(s0) & ~1u) | tag, __float_as_uint(q0), __float_as_uint(s1), __float_as_uint(q2));
}

__device__ __forceinline__ void put72(uint4* slab, int j, int lane, const uint32_t* v) {
  uint4* p = slab + ((9 * j + 1) >> 1) * 32;
  if (j & 1) {
    stg2((char*)(p - 16) + lane * 8, nz(v[0]), v[1]);
#pragma unroll
    for (int i = 0; i < 4; i++) stg4(p + lane + i * 32, nz(v[4 * i + 2]), v[4 * i + 3], v[4 * i + 4], v[4 * i + 5]);
  } else {
#pragma unroll
    for (int i = 0; i < 4; i++) stg4(p + lane + i * 32, nz(v[4 * i]), v[4 * i + 1], v[4 * i + 2], v[4 * i + 3]);
    stg2((char*)(p + 4 * 32) + lane * 8, nz(v[16]), v[17]);
  }
}
__device__ __forceinline__ void zero_share(uint4* slab, int j, int lane) {
  uint4* p = slab + j * 144 + lane;
#pragma unroll
  for (int i = 0; i < 4; i++) stg4(p + i * 32, 0u, 0u, 0u, 0u);
  if (lane < 16) stg4(p + 128, 0u, 0u, 0u, 0u);
}

struct Maps { CUtensorMap m[5]; };

struct Ring {
  uint32_t st, ph;
  __device__ __forceinline__ void next() { if (++st == NST) { st = 0; ph ^= 1; } }
};

#define STAMP(i) do {} while (0)

__device__ __forceinline__ void tma_box(uint32_t dst, const CUtensorMap* m, int col, int row, uint32_t bar, uint32_t expect) {
  asm volatile("{\n.reg .pred e, h;\nelect.sync _|e, 0xffffffff;\nsetp.ne.and.u32 h, %5, 0, e;\n"
               "@h mbarrier.arrive.expect_tx.shared::cta.b64 _, [%2], %5;\n"
               "@e cp.async.bulk.tensor.2d.shared::cluster.global.mbarrier::complete_tx::bytes [%0], [%1, {%3, %4}], [%2];\n}"
               :: "r"(dst), "l"(m), "r"(bar), "r"(col), "r"(row), "r"(expect) : "memory");
}

__device__ __forceinline__ void bulk_load(uint32_t dst, const void* src, uint32_t bytes, uint32_t bar, bool arm) {
  asm volatile("{\n.reg .pred e, h;\nelect.sync _|e, 0xffffffff;\nsetp.ne.and.u32 h, %4, 0, e;\n"
               "@h mbarrier.arrive.expect_tx.shared::cta.b64 _, [%3], %2;\n"
               "@e cp.async.bulk.shared::cluster.global.mbarrier::complete_tx::bytes [%0], [%1], %2, [%3];\n}"
               :: "r"(dst), "l"(src), "r"(bytes), "r"(bar), "r"((uint32_t)arm) : "memory");
}

__global__ void __launch_bounds__(384, 1) mega_kernel(
    const __grid_constant__ Maps maps, uint4* __restrict__ scratch,
    const __nv_bfloat16* __restrict__ x_in, const __nv_bfloat16* __restrict__ wqkv, const __nv_bfloat16* __restrict__ wo,
    __nv_bfloat16* __restrict__ out) {
  extern __shared__ __align__(1024) uint8_t smem[];
  const uint32_t sb = (uint32_t)__cvta_generic_to_shared(smem);
  const uint32_t full0 = sb + BARS, empty0 = full0 + 8 * NST, rem_full = empty0 + 8 * NST, park_free = rem_full + 8, kv_free = park_free + 8;
  const uint32_t c8_go = kv_free + 8, c8_done = c8_go + 8, c8_full = c8_done + 8, pbar0 = c8_full + 8;
  const int w = __shfl_sync(~0u, threadIdx.x >> 5, 0), lane = threadIdx.x & 31;
  const int t = blockIdx.x >> 3, j = blockIdx.x & 7;
  const int r = lane >> 2, q = lane & 3;
  uint4* const scr = scratch + t * TILE;
  {
    const int sl = w < 8 ? w : j, ch = w < 8 ? j : 8;
    const uint32_t* xr = (const uint32_t*)(x_in + (128 * t + 32 * (sl >> 1) + 2 * r + (sl & 1)) * 576 + 64 * ch + 2 * q);
    if (w < 8 || w == 9) {
      uint32_t v[16];
#pragma unroll
      for (int g = 0; g < 8; g++) {
        asm volatile("ld.global.nc.b32 %0, [%1];" : "=r"(v[2 * g]) : "l"(xr + 4 * g));
        asm volatile("ld.global.nc.b32 %0, [%1];" : "=r"(v[2 * g + 1]) : "l"(xr + 8 * 576 + 4 * g));
      }
      asm volatile("bar.sync 0;" ::: "memory");
      uint4* p = scr + OFF_X + sl * SLAB + 4 * ch * 32 + lane;
#pragma unroll
      for (int i = 0; i < 4; i++) stg4(p + i * 32, nz(v[4 * i]), v[4 * i + 1], nz(v[4 * i + 2]), v[4 * i + 3]);
      float y[32];
#pragma unroll
      for (int i = 0; i < 16; i++) { y[2 * i] = bf_lo(v[i]); y[2 * i + 1] = bf_hi(v[i]); }
      publish_stats<8>(scr + OFF_S + sl * 96 + ch * 8, y, 1u, lane);
    } else {
      if (threadIdx.x == 256) {
        for (int i = 0; i < NST; i++) { mbar_init(full0 + 8 * i, 1); mbar_init(empty0 + 8 * i, 8); }
        mbar_init(rem_full, 1); mbar_init(park_free, 8); mbar_init(kv_free, 8); mbar_init(c8_go, 8); mbar_init(c8_done, 1); mbar_init(c8_full, 1);
        for (int i = 0; i < 8; i++) mbar_init(pbar0 + 8 * i, 5);
        asm volatile("fence.mbarrier_init.release.cluster;" ::: "memory");
      }
      __syncwarp();
      asm volatile("bar.sync 0;" ::: "memory");
    }
  }

  if (w >= 8) {
    asm volatile("setmaxnreg.dec.sync.aligned.u32 24;");
    if (w == 8) {
      Ring rg{0, 1};
#pragma unroll 1
      for (int seg = 0; seg < 34; seg++) {
        const int n = seg >= 17 ? seg - 17 : seg;
        int ma, mb, ca, cb, row = 0;
        if (n < 3) { ma = mb = n == 2; ca = 72 * j + (n == 0 ? 576 : 0); cb = ca + 576; }
        else if (n < 12) { ma = 3; mb = 2; ca = cb = 576 * j + 64 * (n - 3); }
        else { ma = mb = 4; ca = n == 12 ? 512 : ((j + 2 * n) & 7) * 64; cb = ((j + 2 * n + 1) & 7) * 64; row = 576 * j; }
        const bool zip = n == 0 || n == 3;
        const int nb = (n == 1 || n == 2 || n == 16) ? 9 : 18;
#pragma unroll 1
        for (int b = 0; b < nb; b++) {
          const bool second = zip ? (b & 1) : b >= 9, last = b == nb - 1;
          const int kb = zip ? b >> 1 : second ? b - 9 : b;
          if (!(b & 1)) mbar_wait(empty0 + rg.st * 8, rg.ph);
          tma_box(sb + rg.st * STAGE + (b & 1) * 8192, &maps.m[second ? mb : ma], second ? cb : ca, row + 64 * kb, full0 + rg.st * 8,
                  (b & 1) ? 0 : last ? STAGE / 2 : STAGE);
          if ((b & 1) || last) rg.next();
        }
      }
    } else if (w == 9) {
      const uint32_t stg = sb + HSTG + lane * 16;
      uint32_t fph = 0;
#pragma unroll 1
      for (int layer = 0; layer < 2; layer++) {
        uint4* xb = scr + OFF_X + ((4 + layer) * 8 + j) * SLAB + 32 * 32;
        mbar_wait(c8_go, layer);
        int n = 0;
        while (true) {
          if (lane == 0) asm volatile("mbarrier.arrive.expect_tx.shared::cta.b64 _, [%0], 18432;" :: "r"(c8_full) : "memory");
          __syncwarp();
#pragma unroll 1
          for (int s = 0; s < 9; s++)
            bulk_load(sb + HSTG + s * 2048, s < 8 ? scr + OFF_P + (j + s * 8) * SLAB + 32 * 32 : xb, 2048, c8_full, false);
          mbar_wait(c8_full, fph); fph ^= 1;
          uint32_t bad = 0;
#pragma unroll 8
          for (int s = 0; s < 32; s++) { uint32_t v; asm volatile("ld.shared.b32 %0, [%1];" : "=r"(v) : "r"(stg + s * 512) : "memory"); bad |= v ^ (1 - layer); }
          if (__all_sync(~0u, (bad & 1u) == 0u)) break;
          __nanosleep(300);
          SPIN_GUARD(n);
        }
        float s0 = 0.f, s1 = 0.f;
#pragma unroll 1
        for (int g = 0; g < 8; g++) {
          const uint32_t a = stg + (g >> 1) * 512 + (g & 1) * 8;
          float a0 = 0.f, a1 = 0.f, a2 = 0.f, a3 = 0.f;
#pragma unroll
          for (int b = 0; b < 3; b++) {
            uint32_t v[6];
#pragma unroll
            for (int s = 0; s < 3; s++) lds2(a + (3 * b + s) * 2048, v + 2 * s);
#pragma unroll
            for (int s = 0; s < 3; s++) { a0 += bf_lo(v[2 * s]); a1 += bf_hi(v[2 * s]); a2 += bf_lo(v[2 * s + 1]); a3 += bf_hi(v[2 * s + 1]); }
          }
          sts1(a + 18432, pack_bf16(a0, a1)); sts1(a + 18436, pack_bf16(a2, a3));
          s0 += a0 + a1; s1 += a2 + a3;
        }
        __syncwarp();
        if (lane == 0) mbar_arrive(c8_done);
        s0 = quad_sum(s0); s1 = quad_sum(s1);
        float q0 = 0.f, q1 = 0.f;
#pragma unroll 1
        for (int i = 0; i < 4; i++) {
          uint32_t x[4];
          lds4(stg + 18432 + i * 512, x);
          stg4(xb + i * 32 + lane, 0u, 0u, 0u, 0u);
          if (layer == 0) {
            stg4(xb - 3 * 8 * SLAB + i * 32 + lane, nz(x[0]), x[1], x[2], x[3]);
#pragma unroll
            for (int e = 0; e < 4; e++) {
              const float m = (e & 1) ? s1 : s0, c = fmaf(m, -1.f / 64, bf_lo(x[e])), d = fmaf(m, -1.f / 64, bf_hi(x[e]));
              if (e & 1) q1 = fmaf(c, c, fmaf(d, d, q1)); else q0 = fmaf(c, c, fmaf(d, d, q0));
            }
          } else {
            uint32_t* o = (uint32_t*)(out + (128 * t + 32 * (j >> 1) + 2 * r + (j & 1)) * 576 + 512 + 16 * i + 2 * q);
            o[0] = x[0]; o[8 * 576] = x[1]; o[4] = x[2]; o[8 * 576 + 4] = x[3];
          }
        }
        if (layer == 0) {
          q0 = quad_sum(q0); q1 = quad_sum(q1);
          if (q == 0) stg4(scr + OFF_S + j * 96 + 64 + r, __float_as_uint(s0) & ~1u, __float_as_uint(q0), __float_as_uint(s1), __float_as_uint(q1));
        }
      }
    } else {
      {
        uint4 v[3];
        const int p = t >> 2, k0 = (t & 3) * 144 + threadIdx.x - 320;
        const uint4* src = (const uint4*)(p == 3 ? wo + k0 * 576 : wqkv + k0 * 1728 + (p < 2 ? 576 * (p + 1) : 0)) + 9 * j + 8;
#pragma unroll
        for (int i = 0; i < 3; i++) if (i < 2 || threadIdx.x < 336) v[i] = __ldg(src + i * (p == 3 ? 8 * 576 : 8 * 1728));
        const int s = k0 >> 4, rr = k0 & 7;
        uint4* dst = scratch + OFF_R + j * 2304 + (s >> 1) * 128 + ((k0 >> 3) & 1) * 64 + rr * 8 + (((s & 1) * 4 + p) ^ rr);
#pragma unroll
        for (int i = 0; i < 3; i++) if (i < 2 || threadIdx.x < 336) stg4(dst + i * 256, v[i].x, v[i].y, v[i].z, v[i].w);
        __threadfence();
        __syncwarp();
        if (lane < 16) asm volatile("st.relaxed.gpu.global.b32 [%0], 1;" :: "l"((uint32_t*)(scratch + OFF_F + (lane * 8 + j) * 8) + 2 * t + w - 10) : "memory");
      }
#pragma unroll 1
      for (int layer = 0; layer < 2; layer++) {
        if (w == 10) {
          if (layer) {
            mbar_wait(park_free, 0);
          } else {
            uint32_t* fl = (uint32_t*)(scratch + OFF_F + (t * 8 + j) * 8) + lane;
            uint32_t v;
            int n = 0;
            while (true) {
              asm volatile("ld.acquire.gpu.global.b32 %0, [%1];" : "=r"(v) : "l"(fl) : "memory");
              if (__all_sync(~0u, v != 0u)) break;
              SPIN_GUARD(n);
            }
            asm volatile("fence.proxy.async;\nst.relaxed.gpu.global.b32 [%0], 0;" :: "l"(fl) : "memory");
          }
          bulk_load(sb + REM, scratch + OFF_R + j * 2304, 36864, rem_full, true);
        }
        if (layer) mbar_wait(kv_free, 0);
        if (t > 0) {
#pragma unroll 1
          for (int pc = 0; pc < 3; pc++) {
            uint4* hp = scr + OFF_H + ((layer * 8 + j) * 2 + (w - 10)) * 192 + pc * 64 + lane;
            uint32_t hl[8];
            int n = 0;
            hl[4] = 1u;
            while (true) {
              ldg4(hl, hp);
              if (pc < 2) ldg4(hl + 4, hp + 32);
              if (__all_sync(~0u, hl[0] != 0u && hl[4] != 0u)) break;
              __nanosleep(100);
              SPIN_GUARD(n);
            }
            const uint32_t dst = sb + KVS + (w - 10) * 10368 + r * 144 + q * 4;
            if (pc < 2) {
#pragma unroll
              for (int g = 0; g < 8; g++) sts1(dst + pc * 20736 + g * 16, hl[g]);
              stg4(hp + 32, 0u, 0u, 0u, 0u);
            } else {
              sts1(dst + 128, hl[0]); sts1(dst + 20736 + 128, hl[1]);
            }
            stg4(hp, 0u, 0u, 0u, 0u);
          }
        }
        asm volatile("bar.arrive 1, 192;" ::: "memory");
      }
    }
  } else {
    asm volatile("setmaxnreg.inc.sync.aligned.u32 240;");
    Ring rg{0, 0};
    uint32_t prev = 0;
    uint32_t X[144];
    float rs0, rs1;
    uint32_t mean0, mean1;
    auto release = [&](uint32_t st) { if (lane == 0) mbar_arrive(empty0 + st * 8); };
    auto load_kb = [&](int kb, const uint4* src, const char* lo, uint32_t hoff) {
#pragma unroll
      for (int k = 4 * kb; k < 4 * kb + 4; k++) {
        if (k % 9 == 4) { ldg2(X + 4 * k, lo + k * 512); ldg2(X + 4 * k + 2, lo + hoff + k * 512); }
        else ldg4(X + 4 * k, src + k * 32);
      }
    };
    auto next_kb = [&](bool center, int kb, const uint4* src, const char* lo, uint32_t hoff) {
      int n = 0;
      while (true) {
        bool ok = true;
#pragma unroll
        for (int k = 4 * kb; k < 4 * kb + 4; k++) { ok = ok && X[4 * k] != 0u; if (k % 9 == 4) ok = ok && X[4 * k + 2] != 0u; }
        if (__all_sync(~0u, ok)) break;
        SPIN_GUARD(n);
        load_kb(kb, src, lo, hoff);
      }
      if (kb + GD < 9) load_kb(kb + GD, src, lo, hoff);
      if (center) {
#pragma unroll
        for (int i = 16 * kb; i < 16 * kb + 16; i++) X[i] = sub_bf16x2(X[i], (i & 1) ? mean1 : mean0);
      }
    };
#pragma unroll 1
    for (int hf = 0; hf < 4; hf++) {
      const int layer = hf >> 1;
      const bool ffn = hf & 1;
      const uint32_t tag = 1 - layer;
      uint4* const xbase = scr + OFF_X + (layer * 8 + w) * SLAB;
      float aA[32], aB[32];
      {
        const uint4* src = xbase + (ffn ? 32 * SLAB : 0) + lane;
        const char* lo = (const char*)src - (ffn ? lane * 8 : 0);
        const uint32_t hoff = ffn ? 256 : 8;
        uint32_t s[3][4];
        const uint4* p = scr + OFF_S + ((ffn ? 16 : 0) + w) * 96 + q * 8 + r;
        const bool third = !ffn && q == 0;
        int n = 0;
        s[2][0] = tag; s[2][1] = s[2][2] = s[2][3] = 0u;
        STAMP(ffn * 16 + 0);
        while (true) {
          ldg4(s[0], p); ldg4(s[1], p + 32);
          if (third) ldg4(s[2], p + 64);
          if (__all_sync(~0u, ((s[0][0] ^ tag) | (s[1][0] ^ tag) | (s[2][0] ^ tag)) % 2u == 0u)) break;
          SPIN_GUARD(n);
        }
        STAMP(ffn * 16 + 1);
#pragma unroll
        for (int kb = 0; kb < GD; kb++) load_kb(kb, src, lo, hoff);
        float t0 = 0.f, t1 = 0.f;
#pragma unroll
        for (int i = 0; i < 3; i++) { t0 += __uint_as_float(s[i][0]); t1 += __uint_as_float(s[i][2]); }
        const float m0 = quad_sum(t0) * (1.f / 576), m1 = quad_sum(t1) * (1.f / 576);
        const float cnt = ffn ? 72.f : 64.f, inv = ffn ? 1.f / 72 : 1.f / 64;
        float v0 = 0.f, v1 = 0.f;
#pragma unroll
        for (int i = 0; i < 3; i++) {
          const float c = (i < 2 || third) ? cnt : 0.f;
          const float d0 = fmaf(__uint_as_float(s[i][0]), inv, -m0), d1 = fmaf(__uint_as_float(s[i][2]), inv, -m1);
          v0 += fmaf(d0 * d0, c, __uint_as_float(s[i][1])); v1 += fmaf(d1 * d1, c, __uint_as_float(s[i][3]));
        }
        rs0 = rsqrtf(fmaf(quad_sum(v0), 1.f / 576, 1e-5f)); rs1 = rsqrtf(fmaf(quad_sum(v1), 1.f / 576, 1e-5f));
        mean0 = pack_bf16(m0, m0); mean1 = pack_bf16(m1, m1);
#pragma unroll
        for (int kb = 0; kb < 9; kb++) {
          next_kb(true, kb, src, lo, hoff);
          mbar_wait(full0 + rg.st * 8, rg.ph);
          const uint64_t desc = DESC_HI | ((sb + rg.st * STAGE) >> 4);
          wg_fence();
#pragma unroll
          for (int i = 0; i < 4; i++) wgmma_rs_n64(aA, X + 4 * (4 * kb + i), desc + i * 128, kb + i != 0);
#pragma unroll
          for (int i = 0; i < 4; i++) wgmma_rs_n64(aB, X + 4 * (4 * kb + i), desc + 512 + i * 128, kb + i != 0);
          wg_commit();
          wg_wait<1>();
          if (kb > 0) release(prev);
          prev = rg.st; rg.next();
        }
        wg_wait<0>();
        STAMP(ffn * 16 + 2);
      }
      if (!ffn) {
      release(prev);
      const uint32_t kvrow = sb + KVS + (w & 1) * 10368 + (16 * (w >> 1)) * 144;
      uint32_t Q[18];
      {
        const uint32_t dst = kvrow + (8 + r) * 144 + q * 4;
        const bool edge_out = w >= 6 && t < 15;
        uint4* const hp = scr + TILE + OFF_H + ((layer * 8 + j) * 2 + (w & 1)) * 192 + lane;
        auto put_kv = [&](float (&a)[32], int part) {
          pin(a);
          uint32_t hl[8];
#pragma unroll
          for (int g = 0; g < 8; g++) {
            hl[g] = pack_bf16(a[4 * g + 2] * rs1, a[4 * g + 3] * rs1);
            sts1(dst + part * 20736 + g * 16, pack_bf16(a[4 * g] * rs0, a[4 * g + 1] * rs0)); sts1(dst + part * 20736 + 8 * 144 + g * 16, hl[g]);
          }
          if (edge_out) { stg4(hp + part * 64, nz(hl[0]), hl[1], hl[2], hl[3]); stg4(hp + part * 64 + 32, nz(hl[4]), hl[5], hl[6], hl[7]); }
        };
        put_kv(aA, 0);
        float aR[12];
        mbar_wait(rem_full, layer);
        const uint64_t dr = DESC_HI | ((sb + REM) >> 4);
        wg_fence();
#pragma unroll
        for (int s = 0; s < 36; s++) {
          wgmma_rs_n24(aR, X + 4 * s, dr + ((s >> 1) * 128 + (s & 1) * 4), s != 0);
          if (s == 4) put_kv(aB, 1);
        }
        wg_commit();
#pragma unroll
        for (int kb = 0; kb < 9; kb++) {
          if (!(kb & 1)) mbar_wait(full0 + rg.st * 8, rg.ph);
          const uint64_t desc = DESC_HI | ((sb + rg.st * STAGE + (kb & 1) * 8192) >> 4);
          wg_fence();
#pragma unroll
          for (int i = 0; i < 4; i++) wgmma_rs_n64(aB, X + 4 * (4 * kb + i), desc + i * 128, kb + i != 0);
          wg_commit();
          wg_wait<1>();
          if (kb > 0 && !(kb & 1)) release(prev);
          if ((kb & 1) || kb == 8) { prev = rg.st; rg.next(); }
          if (kb == 0) {
            pin(aR);
            const uint32_t k1 = pack_bf16(aR[2] * rs1, aR[3] * rs1), v1 = pack_bf16(aR[6] * rs1, aR[7] * rs1);
            if (edge_out) stg4(hp + 128, nz(k1), v1, 0u, 0u);
            sts1(dst + 128, pack_bf16(aR[0] * rs0, aR[1] * rs0)); sts1(dst + 8 * 144 + 128, k1);
            sts1(dst + 20736 + 128, pack_bf16(aR[4] * rs0, aR[5] * rs0)); sts1(dst + 20736 + 8 * 144 + 128, v1);
            Q[16] = pack_bf16(aR[8] * rs0, aR[9] * rs0); Q[17] = pack_bf16(aR[10] * rs1, aR[11] * rs1);
            if (w < 4) asm volatile("bar.arrive 2, 256;" ::: "memory");
          }
        }
        wg_wait<0>();
        release(prev);
        pin(aB);
        STAMP(3);
#pragma unroll
        for (int g = 0; g < 8; g++) {
          Q[2 * g] = pack_bf16(aB[4 * g] * rs0, aB[4 * g + 1] * rs0); Q[2 * g + 1] = pack_bf16(aB[4 * g + 2] * rs1, aB[4 * g + 3] * rs1);
        }
      }
      if (w < 4) asm volatile("bar.sync 1, 192;" ::: "memory");
      else asm volatile("bar.sync 2, 256;" ::: "memory");
      STAMP(4);
      uint32_t O[18];
      {
        const bool edge = (t == 0 && w < 2);
        uint32_t row[3];
#pragma unroll
        for (int nt = 0; nt < 3; nt++) row[nt] = kvrow + (8 * nt + (lane & 7)) * 144;
        if (edge) row[0] = sb + KVS + 8 * 144;
        const uint32_t rlast = ((lane >> 3) == 0 ? row[0] : (lane >> 3) == 1 ? row[1] : row[2]) + 128;
        uint32_t K[3][9], V[3][9], dummy;
#pragma unroll
        for (int nt = 0; nt < 3; nt++) {
          ldsm4(row[nt] + (lane >> 3) * 16, K[nt][0], K[nt][1], K[nt][2], K[nt][3]);
          ldsm4(row[nt] + 64 + (lane >> 3) * 16, K[nt][4], K[nt][5], K[nt][6], K[nt][7]);
        }
        ldsm4(rlast, K[0][8], K[1][8], K[2][8], dummy);
#pragma unroll
        for (int nt = 0; nt < 3; nt++) {
          ldsm4t(row[nt] + 20736 + (lane >> 3) * 16, V[nt][0], V[nt][1], V[nt][2], V[nt][3]);
          ldsm4t(row[nt] + 20736 + 64 + (lane >> 3) * 16, V[nt][4], V[nt][5], V[nt][6], V[nt][7]);
        }
        ldsm4t(rlast + 20736, V[0][8], V[1][8], V[2][8], dummy);
        const bool up0 = 2 * q > r, up1 = 2 * q + 1 > r;
        const float sc = 0.23570226039551584f * 1.4426950408889634f;
        const float neg = -1e9f * 1.4426950408889634f;
        float Of[9][4];
#pragma unroll
        for (int h = 0; h < 4; h++) {
          const uint32_t a0 = q >= h ? Q[4 * h] : 0u, a1 = q >= h ? Q[4 * h + 1] : 0u;
          const uint32_t a4 = q <= h ? Q[4 * h + 4] : 0u, a5 = q <= h ? Q[4 * h + 5] : 0u;
          float S[3][4];
#pragma unroll
          for (int nt = 0; nt < 3; nt++) {
            S[nt][0] = S[nt][1] = S[nt][2] = S[nt][3] = 0.f;
            mma16(S[nt], a0, a1, Q[4 * h + 2], Q[4 * h + 3], K[nt][2 * h], K[nt][2 * h + 1]);
            mma8(S[nt], a4, a5, K[nt][2 * h + 2]);
          }
          float s00 = (up0 ? S[0][0] : S[1][0]) * sc, s01 = (up1 ? S[0][1] : S[1][1]) * sc;
          const float s10 = (up0 ? S[1][2] : S[2][2]) * sc, s11 = (up1 ? S[1][3] : S[2][3]) * sc;
          if (edge && up0) s00 = neg;
          if (edge && up1) s01 = neg;
          const float m0 = quad_max(fmaxf(s00, s01)), m1 = quad_max(fmaxf(s10, s11));
          float p00 = ex2(s00 - m0), p01 = ex2(s01 - m0), p10 = ex2(s10 - m1), p11 = ex2(s11 - m1);
          const float i0 = rcp(quad_sum(p00 + p01)), i1 = rcp(quad_sum(p10 + p11));
          p00 *= i0; p01 *= i0; p10 *= i1; p11 *= i1;
          const uint32_t pa = pack_bf16(up0 ? p00 : 0.f, up1 ? p01 : 0.f), pb = pack_bf16(up0 ? 0.f : p00, up1 ? 0.f : p01);
          const uint32_t pc = pack_bf16(up0 ? p10 : 0.f, up1 ? p11 : 0.f), pd = pack_bf16(up0 ? 0.f : p10, up1 ? 0.f : p11);
#pragma unroll
          for (int gi = 0; gi < 3; gi++) {
            const int g = 2 * h + gi;
            float o[4] = {0.f, 0.f, 0.f, 0.f};
            mma16(o, pa, 0u, pb, pc, V[0][g], V[1][g]);
            mma8(o, 0u, pd, V[2][g]);
#pragma unroll
            for (int e = 0; e < 4; e++) Of[g][e] = (gi == 0 && h > 0 && q < h) ? Of[g][e] : o[e];
          }
        }
#pragma unroll
        for (int g = 0; g < 9; g++) { O[2 * g] = pack_bf16(Of[g][0], Of[g][1]); O[2 * g + 1] = pack_bf16(Of[g][2], Of[g][3]); }
      }
      put72(xbase + 16 * SLAB, j, lane, O);
      if (q == 0) stg4(scr + OFF_S + (8 + w) * 96 + j * 8 + r, tag, 0u, 0u, 0u);
      {
        uint32_t res[18];
        const char* p = (const char*)(xbase + lane) + ((9 * j) >> 1) * 512 + (j & 1) * 8;
#pragma unroll
        for (int g = 0; g < 9; g++) ldg2(res + 2 * g, p + (g >> 1) * 512 + ((g & 1) ? ((j & 1) ? 504 : 8) : 0));
        const uint4* src = xbase + 16 * SLAB + lane;
        {
          const uint4* fp = scr + OFF_S + (8 + w) * 96 + q * 8 + r;
          uint32_t s0[4], s1[4];
          int n = 0;
          STAMP(8);
          while (true) {
            ldg4(s0, fp); ldg4(s1, fp + 32);
            if (__all_sync(~0u, ((s0[0] ^ tag) | (s1[0] ^ tag)) % 2u == 0u)) break;
            SPIN_GUARD(n);
          }
          STAMP(9);
        }
#pragma unroll
        for (int kb = 0; kb < GD; kb++) load_kb(kb, src, (const char*)src - lane * 8, 256);
        float acc[36];
#pragma unroll
        for (int kb = 0; kb < 9; kb++) {
          next_kb(false, kb, src, (const char*)src - lane * 8, 256);
          if (!(kb & 1)) mbar_wait(full0 + rg.st * 8, rg.ph);
          const uint32_t base = sb + rg.st * STAGE + (kb & 1) * 8192;
          const uint64_t d0 = DESC_HI | ((base >> 4) + (((sb + REM + kb * 4096 + 48 - base) >> 4) << 16));
          wg_fence();
#pragma unroll
          for (int i = 0; i < 4; i++)
            wgmma_rs_n72(acc, X + 4 * (4 * kb + i), d0 + (uint64_t)(i * 128) - ((uint64_t)(((i + 1) >> 1) * 128 - (i & 1) * 4) << 16), kb + i != 0);
          wg_commit();
          wg_wait<1>();
          if (kb > 0 && !(kb & 1)) release(prev);
          if ((kb & 1) || kb == 8) { prev = rg.st; rg.next(); }
        }
        wg_wait<0>();
        release(prev);
        pin(acc);
        STAMP(10);
#pragma unroll
        for (int i = 0; i < 18; i++) {
          acc[2 * i] += bf_lo(res[i]); acc[2 * i + 1] += bf_hi(res[i]);
          res[i] = pack_bf16(acc[2 * i], acc[2 * i + 1]);
        }
        put72(xbase + 32 * SLAB, j, lane, res);
        publish_stats<9>(scr + OFF_S + (16 + w) * 96 + j * 8, acc, tag, lane);
      }
      continue;
      }
      const uint32_t hp = sb + PARK + w * 512 + lane * 16;
      auto pack8 = [&](float (&a)[32], int p, uint32_t* o) {
#pragma unroll
        for (int e = 0; e < 8; e++) asm volatile("" : "+f"(a[8 * p + e]) :: "memory");
#pragma unroll
        for (int e = 0; e < 4; e++) o[e] = pack_bf16(a[8 * p + 2 * e], a[8 * p + 2 * e + 1]);
      };
      const float ka0 = 0.7978845608028654f * rs0, kb0 = 0.044715f * ka0 * rs0 * rs0, ku0 = 0.5f * rs0 * rs0;
      const float ka1 = 0.7978845608028654f * rs1, kb1 = 0.044715f * ka1 * rs1 * rs1, ku1 = 0.5f * rs1 * rs1;
      auto packu8 = [&](int p, uint32_t* o) {
#pragma unroll
        for (int e = 0; e < 8; e++) asm volatile("" : "+f"(aA[8 * p + e]) :: "memory");
#pragma unroll
        for (int e = 0; e < 4; e++) o[e] = pack_bf16(aA[8 * p + 2 * e] * ((e & 1) ? ku1 : ku0), aA[8 * p + 2 * e + 1] * ((e & 1) ? ku1 : ku0));
      };
      auto geglu8 = [&](int p, uint32_t* u) {
#pragma unroll
        for (int e = 0; e < 8; e++) asm volatile("" : "+f"(aB[8 * p + e]) :: "memory");
        float h[8];
#pragma unroll
        for (int e = 0; e < 8; e++) {
          const float g = aB[8 * p + e];
          h[e] = fmaf(g, tanh_ap(g * fmaf(g * g, (e & 2) ? kb1 : kb0, (e & 2) ? ka1 : ka0)), g);
        }
#pragma unroll
        for (int e = 0; e < 4; e++) u[e] = mul_bf16x2(pack_bf16(h[2 * e], h[2 * e + 1]), u[e]);
      };
      auto box = [&](int b, auto&& filler) {
        const int kb = b < 9 ? b : b - 9;
        if (!(b & 1)) mbar_wait(full0 + rg.st * 8, rg.ph);
        const uint64_t desc = DESC_HI | ((sb + rg.st * STAGE + (b & 1) * 8192) >> 4);
        wg_fence();
#pragma unroll
        for (int i = 0; i < 4; i++) {
          if (b < 9) wgmma_rs_n64(aA, X + 4 * (4 * kb + i), desc + i * 128, kb + i != 0);
          else wgmma_rs_n64(aB, X + 4 * (4 * kb + i), desc + i * 128, kb + i != 0);
          if (i == FPOS) filler();
        }
        wg_commit();
        if (b & 1) { if (W2) wg_wait<1>(); prev = rg.st; rg.next(); } else { wg_wait<1>(); release(prev); }
      };
      auto nop = [] {};
      auto step = [&](int st, auto&& filler) { box(2 * st, nop); box(2 * st + 1, filler); };
#pragma unroll
      for (int p = 0; p < 4; p++) { uint32_t o[4]; packu8(p, o); sts4(hp + p * 4096, o); }
      box(0, nop);
      zero_share(xbase, j, lane);
      zero_share(xbase + 16 * SLAB, j, lane);
#pragma unroll 1
      for (int c = 1;; c++) {
        const uint32_t hc = hp + c * 4 * 4096;
#pragma unroll
        for (int b = 1; b < 18; b++) box(b, [&] {
          if ((b & 1) && b < 8) { uint32_t o[4]; const uint32_t a = hc - (4 - (b >> 1)) * 4096; lds4(a, o); geglu8(b >> 1, o); sts4(a, o); }
          if ((b & 1) && b > 10) { uint32_t o[4]; packu8((b - 11) >> 1, o); if (c < 8) sts4(hc + ((b - 11) >> 1) * 4096, o); } });
        if (c == 8) break;
        box(0, nop);
      }
      wg_wait<0>();
      STAMP(21);
#pragma unroll
      for (int s = 0; s < 32; s++) lds4(hp + s * 4096, X + 4 * s);
#pragma unroll
      for (int p = 0; p < 4; p++) packu8(p, X + 128 + 4 * p);
#pragma unroll
      for (int st = 0; st < 4; st++) step(st, [&] { geglu8(st, X + 128 + 4 * st); });
      STAMP(24);
      if (layer == 0 && lane == 0) mbar_arrive(park_free);
      int lane2 = lane;
      asm volatile("" : "+r"(lane2));
      uint4* const pw = scr + OFF_P + (j * 8 + w) * SLAB + lane2;
      const uint4* const pr = scr + OFF_P + w * SLAB + 4 * j * 32 + lane2;
      auto put_part = [&](float (&a)[32], int p, int chunk) {
        uint32_t o[4];
        pack8(a, p, o);
        stg4(pw + (chunk * 4 + p) * 32, (o[0] & ~1u) | tag, o[1], o[2], o[3]);
      };
      auto slot = [&](int p) { return sb + w * 2048 + (p < 4 ? PARK + (p - 1) * 16384 : KVS + (p - 4) * 16384); };
      auto fetch = [&](int p) {
        if (p > 0) bulk_load(slot(p), scr + OFF_P + (((j - p) & 7) * 8 + w) * SLAB + 4 * j * 32, 2048, pbar0 + w * 8, true);
      };
      uint4* const xb = xbase + 32 * SLAB + 4 * j * 32;
#pragma unroll 1
      for (int sp = 0;; sp++) {
        const int ca = sp == 0 ? 8 : ((j + 2 * sp) & 7), cb = (j + 2 * sp + 1) & 7;
        if (sp == 1 && lane == 0) mbar_arrive(c8_go);
#pragma unroll
        for (int st = 4; st < 9; st++) step(st, [&] {
          if (st == 5 || st == 6) { put_part(aA, 2 * (st - 5), ca); put_part(aA, 2 * (st - 5) + 1, ca); }
          if (st == 8) { if (sp == 3) mbar_wait(c8_done, layer); fetch(2 * sp - 1); } });
        STAMP(25 + sp);
        if (sp == 3) break;
        if (sp == 2) asm volatile("{\n.reg .pred e;\nelect.sync _|e, 0xffffffff;\n@e cp.async.bulk.prefetch.L2.global [%0], 2048;\n}" :: "l"(xb) : "memory");
#pragma unroll
        for (int st = 0; st < 4; st++) step(st, [&] {
          if (st < 2) { put_part(aB, 2 * st, cb); put_part(aB, 2 * st + 1, cb); }
          if (st == 3) fetch(2 * sp); });
      }
      auto load_p = [&](int p, uint32_t* d) {
#pragma unroll
        for (int i = 0; i < 4; i++) ldg4(d + 4 * i, pr + ((j - p) & 7) * 8 * SLAB + i * 32);
      };
#pragma unroll
      for (int st = 0; st < 4; st++) step(st, [&] {
        if (st == 0) {
#pragma unroll
          for (int p = 0; p < 4; p++) put_part(aB, p, (j + 7) & 7);
        }
        if (st == 1) {
#pragma unroll
          for (int i = 0; i < 4; i++) {
            const bool split = j == 2 * i + 1;
            const char* l = (const char*)(xb + i * 32) + (split ? lane2 * 8 : lane2 * 16);
            ldg2(X + 4 * i, l); ldg2(X + 4 * i + 2, l + (split ? 256 : 8));
          }
          load_p(6, X + 16);
        }
        if (st == 3) load_p(7, X + 32); });
      {
        mbar_wait(full0 + rg.st * 8, rg.ph);
        const uint64_t desc = DESC_HI | ((sb + rg.st * STAGE) >> 4);
        wg_fence();
#pragma unroll
        for (int i = 0; i < 4; i++) wgmma_rs_n64(aA, X + 4 * (32 + i), desc + i * 128, 1);
        wg_commit();
        wg_wait<1>(); release(prev);
        prev = rg.st; rg.next();
        mbar_wait(pbar0 + w * 8, layer);
        wg_wait<0>(); release(prev);
        pin(aA);
      }
      STAMP(22);
      {
        const uint32_t eye = r == 2 * q ? 0x3f80u : r == 2 * q + 1 ? 0x3f800000u : 0u;
        auto add_p = [&](int p, uint32_t* d) {
          int n = 0;
          while (!__all_sync(~0u, (((d[0] ^ tag) | (d[4] ^ tag) | (d[8] ^ tag) | (d[12] ^ tag)) & 1u) == 0u)) { SPIN_GUARD(n); load_p(p, d); }
#pragma unroll
          for (int g = 0; g < 8; g++) mma8(aA + 4 * g, d[2 * g], d[2 * g + 1], eye);
        };
#pragma unroll
        for (int p = 1; p < 6; p++)
#pragma unroll
          for (int i = 0; i < 4; i++) lds4(slot(p) + lane2 * 16 + i * 512, X + 32 + 16 * p + 4 * i);
#pragma unroll
        for (int g = 0; g < 8; g++) mma8(aA + 4 * g, X[2 * g], X[2 * g + 1], eye);
#pragma unroll
        for (int p = 1; p < 6; p++) add_p(p, X + 32 + 16 * p);
        add_p(6, X + 16); add_p(7, X + 32);
        uint32_t res[16];
#pragma unroll
        for (int i = 0; i < 16; i++) res[i] = pack_bf16(aA[2 * i], aA[2 * i + 1]);
        if (layer == 0) {
          uint4* p = xbase + 8 * SLAB + 4 * j * 32 + lane;
#pragma unroll
          for (int i = 0; i < 4; i++) stg4(p + i * 32, nz(res[4 * i]), res[4 * i + 1], nz(res[4 * i + 2]), res[4 * i + 3]);
          publish_stats<8>(scr + OFF_S + w * 96 + j * 8, aA, 0u, lane);
          if (lane == 0) mbar_arrive(kv_free);
        } else {
          uint32_t* o = (uint32_t*)(out + (128 * t + 32 * (w >> 1) + 2 * r + (w & 1)) * 576 + 64 * j + 2 * q);
#pragma unroll
          for (int g = 0; g < 8; g++) { o[4 * g] = res[2 * g]; o[8 * 576 + 4 * g] = res[2 * g + 1]; }
        }
#pragma unroll
        for (int i = 0; i < 4; i++) stg4(xb + lane + i * 32, 0u, 0u, 0u, 0u);
      }
      STAMP(23);
    }
  }
}

typedef CUresult (*EncodeFn)(CUtensorMap*, CUtensorMapDataType, cuuint32_t, void*, const cuuint64_t*, const cuuint64_t*,
                             const cuuint32_t*, const cuuint32_t*, CUtensorMapInterleave, CUtensorMapSwizzle,
                             CUtensorMapL2promotion, CUtensorMapFloatOOBfill);

CUtensorMap make_map(EncodeFn f, const void* p, uint64_t cols, uint64_t rows) {
  CUtensorMap m;
  cuuint64_t dims[2] = {cols, rows};
  cuuint64_t str[1] = {cols * 2};
  cuuint32_t box[2] = {64, 64};
  cuuint32_t es[2] = {1, 1};
  f(&m, CU_TENSOR_MAP_DATA_TYPE_BFLOAT16, 2, const_cast<void*>(p), dims, str, box, es, CU_TENSOR_MAP_INTERLEAVE_NONE,
    CU_TENSOR_MAP_SWIZZLE_128B, CU_TENSOR_MAP_L2_PROMOTION_NONE, CU_TENSOR_MAP_FLOAT_OOB_FILL_NONE);
  return m;
}

}

extern "C" void kernel_launch(void* const* d_in, const int* in_sizes, int n_in, void* d_out, int out_size) {
  void* fn = nullptr;
  cudaDriverEntryPointQueryResult qr;
  cudaGetDriverEntryPoint("cuTensorMapEncodeTiled", &fn, cudaEnableDefault, &qr);
  EncodeFn enc = (EncodeFn)fn;
  Maps maps;
  maps.m[0] = make_map(enc, d_in[1], 1728, 576); maps.m[1] = make_map(enc, d_in[2], 576, 576);
  maps.m[2] = make_map(enc, d_in[4], 4608, 576); maps.m[3] = make_map(enc, d_in[5], 4608, 576); maps.m[4] = make_map(enc, d_in[6], 576, 4608);
  void* scr = nullptr;
  cudaGetSymbolAddress(&scr, g_scratch);
  cudaFuncSetAttribute(mega_kernel, cudaFuncAttributeMaxDynamicSharedMemorySize, SMEM_BYTES);
  mega_kernel<<<128, 384, SMEM_BYTES>>>(maps, (uint4*)scr, (const __nv_bfloat16*)d_in[0], (const __nv_bfloat16*)d_in[1],
                                        (const __nv_bfloat16*)d_in[2], (__nv_bfloat16*)d_out);
}
```

```cpp
#include <cuda_runtime.h>
#include <cuda.h>
#include <cuda_bf16.h>
#include <stdint.h>

#define TRACE 0
#define FPOS 2
#define W2 0

namespace {

constexpr int NST = 6;
constexpr int STAGE = 16384;
constexpr int PARK = NST * STAGE;
constexpr int REM = PARK + 49152;
constexpr int KVS = REM + 40960;
constexpr int HSTG = KVS + 16384;
constexpr int BARS = KVS + 41472;
constexpr int TRC = BARS + 256;
constexpr int SMEM_BYTES = TRC + (TRACE ? 512 : 0);
static_assert(BARS >= PARK + 131072, "barriers overlap park");
static_assert(SMEM_BYTES <= 232448, "smem");

constexpr int SLAB = 36 * 32;
constexpr int SPIN_MAX = 1 << 17;
constexpr int GD = 3;
constexpr int OFF_S = 0;
constexpr int OFF_H = OFF_S + 3 * 8 * 96;
constexpr int OFF_X = OFF_H + 2 * 8 * 384;
constexpr int OFF_P = OFF_X + 6 * 8 * SLAB;
constexpr int TILE = OFF_P + 8 * 8 * SLAB;
constexpr int OFF_R = 16 * TILE;
constexpr int OFF_F = OFF_R + 8 * 2304;
constexpr int SCRATCH = OFF_F + 128 * 8;

}

__device__ uint4 g_scratch[SCRATCH];

namespace {

constexpr uint64_t DESC_HI = 0x4000004000000000ull;
__device__ __forceinline__ void wgmma_rs_n64(float (&d)[32], const uint32_t* a, uint64_t desc, int scale_d) {
  asm volatile("{\n.reg .pred p;\nsetp.ne.b32 p, %37, 0;\n"
    "wgmma.mma_async.sync.aligned.m64n64k16.f32.bf16.bf16 "
    "{%0, %1, %2, %3, %4, %5, %6, %7, %8, %9, %10, %11, %12, %13, %14, %15, %16, %17, %18, %19, %20, %21, %22, %23, %24, %25, %26, %27, %28, %29, %30, %31}, "
    "{%32, %33, %34, %35}, %36, p, 1, 1, 1;\n}\n"
    : "+f"(d[0]), "+f"(d[1]), "+f"(d[2]), "+f"(d[3]), "+f"(d[4]), "+f"(d[5]), "+f"(d[6]), "+f"(d[7]), "+f"(d[8]), "+f"(d[9]), "+f"(d[10]), "+f"(d[11]), "+f"(d[12]), "+f"(d[13]), "+f"(d[14]), "+f"(d[15]), "+f"(d[16]), "+f"(d[17]), "+f"(d[18]), "+f"(d[19]), "+f"(d[20]), "+f"(d[21]), "+f"(d[22]), "+f"(d[23]), "+f"(d[24]), "+f"(d[25]), "+f"(d[26]), "+f"(d[27]), "+f"(d[28]), "+f"(d[29]), "+f"(d[30]), "+f"(d[31])
    : "r"(a[0]), "r"(a[1]), "r"(a[2]), "r"(a[3]), "l"(desc), "r"(scale_d));
}
__device__ __forceinline__ void wgmma_rs_n72(float (&d)[36], const uint32_t* a, uint64_t desc, int scale_d) {
  asm volatile("{\n.reg .pred p;\nsetp.ne.b32 p, %41, 0;\n"
    "wgmma.mma_async.sync.aligned.m64n72k16.f32.bf16.bf16 "
    "{%0, %1, %2, %3, %4, %5, %6, %7, %8, %9, %10, %11, %12, %13, %14, %15, %16, %17, %18, %19, %20, %21, %22, %23, %24, %25, %26, %27, %28, %29, %30, %31, %32, %33, %34, %35}, "
    "{%36, %37, %38, %39}, %40, p, 1, 1, 1;\n}\n"
    : "+f"(d[0]), "+f"(d[1]), "+f"(d[2]), "+f"(d[3]), "+f"(d[4]), "+f"(d[5]), "+f"(d[6]), "+f"(d[7]), "+f"(d[8]), "+f"(d[9]), "+f"(d[10]), "+f"(d[11]), "+f"(d[12]), "+f"(d[13]), "+f"(d[14]), "+f"(d[15]), "+f"(d[16]), "+f"(d[17]), "+f"(d[18]), "+f"(d[19]), "+f"(d[20]), "+f"(d[21]), "+f"(d[22]), "+f"(d[23]), "+f"(d[24]), "+f"(d[25]), "+f"(d[26]), "+f"(d[27]), "+f"(d[28]), "+f"(d[29]), "+f"(d[30]), "+f"(d[31]), "+f"(d[32]), "+f"(d[33]), "+f"(d[34]), "+f"(d[35])
    : "r"(a[0]), "r"(a[1]), "r"(a[2]), "r"(a[3]), "l"(desc), "r"(scale_d));
}

__device__ __forceinline__ void wgmma_rs_n24(float (&d)[12], const uint32_t* a, uint64_t desc, int scale_d) {
  asm volatile("{\n.reg .pred p;\nsetp.ne.b32 p, %17, 0;\n"
    "wgmma.mma_async.sync.aligned.m64n24k16.f32.bf16.bf16 "
    "{%0, %1, %2, %3, %4, %5, %6, %7, %8, %9, %10, %11}, "
    "{%12, %13, %14, %15}, %16, p, 1, 1, 1;\n}\n"
    : "+f"(d[0]), "+f"(d[1]), "+f"(d[2]), "+f"(d[3]), "+f"(d[4]), "+f"(d[5]), "+f"(d[6]), "+f"(d[7]), "+f"(d[8]), "+f"(d[9]), "+f"(d[10]), "+f"(d[11])
    : "r"(a[0]), "r"(a[1]), "r"(a[2]), "r"(a[3]), "l"(desc), "r"(scale_d));
}

__device__ __forceinline__ void mbar_init(uint32_t a, uint32_t c) { asm volatile("mbarrier.init.shared::cta.b64 [%0], %1;" :: "r"(a), "r"(c)); }
__device__ __forceinline__ void mbar_arrive(uint32_t a) { asm volatile("mbarrier.arrive.shared::cta.b64 _, [%0];" :: "r"(a) : "memory"); }
__device__ __forceinline__ void mbar_wait(uint32_t a, uint32_t ph) {
  asm volatile("{\n.reg .pred p;\n.reg .u32 n;\n"
               "mbarrier.try_wait.parity.shared::cta.b64 p, [%0], %1;\n@p bra D;\n"
               "mov.u32 n, 0;\n"
               "W: mbarrier.try_wait.parity.shared::cta.b64 p, [%0], %1;\n@p bra D;\n"
               "add.u32 n, n, 1;\nsetp.lt.u32 p, n, 4194304;\n@p bra W;\ntrap;\nD:\n}" :: "r"(a), "r"(ph) : "memory");
}
__device__ __forceinline__ void wg_fence() { asm volatile("wgmma.fence.sync.aligned;" ::: "memory"); }
__device__ __forceinline__ void wg_commit() { asm volatile("wgmma.commit_group.sync.aligned;" ::: "memory"); }
template <int N> __device__ __forceinline__ void wg_wait() { asm volatile("wgmma.wait_group.sync.aligned %0;" :: "n"(N) : "memory"); }
__device__ __forceinline__ float tanh_ap(float x) { float y; asm("tanh.approx.f32 %0, %1;" : "=f"(y) : "f"(x)); return y; }
__device__ __forceinline__ float ex2(float x) { float y; asm("ex2.approx.ftz.f32 %0, %1;" : "=f"(y) : "f"(x)); return y; }
__device__ __forceinline__ uint32_t pack_bf16(float lo, float hi) { uint32_t r; asm("cvt.rn.bf16x2.f32 %0, %1, %2;" : "=r"(r) : "f"(hi), "f"(lo)); return r; }
__device__ __forceinline__ float bf_lo(uint32_t v) { return __uint_as_float(v << 16); }
__device__ __forceinline__ float bf_hi(uint32_t v) { return __uint_as_float(v & 0xffff0000u); }
__device__ __forceinline__ uint32_t sub_bf16x2(uint32_t a, uint32_t b) { uint32_t r; asm("sub.rn.bf16x2 %0, %1, %2;" : "=r"(r) : "r"(a), "r"(b)); return r; }
__device__ __forceinline__ uint32_t mul_bf16x2(uint32_t a, uint32_t b) { uint32_t r; asm("mul.rn.bf16x2 %0, %1, %2;" : "=r"(r) : "r"(a), "r"(b)); return r; }
__device__ __forceinline__ uint32_t nz(uint32_t w) { return w == 0u ? 0x8000u : w; }

__device__ __forceinline__ void ldg4(uint32_t* d, const uint4* p) {
  asm volatile("ld.relaxed.gpu.global.v4.b32 {%0,%1,%2,%3}, [%4];" : "=r"(d[0]), "=r"(d[1]), "=r"(d[2]), "=r"(d[3]) : "l"(p) : "memory");
}
__device__ __forceinline__ void ldg2(uint32_t* d, const void* p) {
  asm volatile("ld.relaxed.gpu.global.v2.b32 {%0,%1}, [%2];" : "=r"(d[0]), "=r"(d[1]) : "l"(p) : "memory");
}
__device__ __forceinline__ void stg4(uint4* p, uint32_t a, uint32_t b, uint32_t c, uint32_t d) {
  asm volatile("st.relaxed.gpu.global.v4.b32 [%0], {%1,%2,%3,%4};" :: "l"(p), "r"(a), "r"(b), "r"(c), "r"(d) : "memory");
}
__device__ __forceinline__ void stg2(void* p, uint32_t a, uint32_t b) {
  asm volatile("st.relaxed.gpu.global.v2.b32 [%0], {%1,%2};" :: "l"(p), "r"(a), "r"(b) : "memory");
}
__device__ __forceinline__ void sts4(uint32_t a, const uint32_t* o) { asm volatile("st.shared.v4.b32 [%0], {%1,%2,%3,%4};" :: "r"(a), "r"(o[0]), "r"(o[1]), "r"(o[2]), "r"(o[3]) : "memory"); }
__device__ __forceinline__ void lds4(uint32_t a, uint32_t* o) { asm volatile("ld.shared.v4.b32 {%0,%1,%2,%3}, [%4];" : "=r"(o[0]), "=r"(o[1]), "=r"(o[2]), "=r"(o[3]) : "r"(a) : "memory"); }
__device__ __forceinline__ void lds2(uint32_t a, uint32_t* o) { asm volatile("ld.shared.v2.b32 {%0,%1}, [%2];" : "=r"(o[0]), "=r"(o[1]) : "r"(a) : "memory"); }
__device__ __forceinline__ float rcp(float x) { float y; asm("rcp.approx.ftz.f32 %0, %1;" : "=f"(y) : "f"(x)); return y; }
__device__ __forceinline__ void sts1(uint32_t a, uint32_t v) { asm volatile("st.shared.b32 [%0], %1;" :: "r"(a), "r"(v) : "memory"); }
__device__ __forceinline__ void ldsm4(uint32_t a, uint32_t& r0, uint32_t& r1, uint32_t& r2, uint32_t& r3) {
  asm volatile("ldmatrix.sync.aligned.m8n8.x4.shared.b16 {%0,%1,%2,%3}, [%4];" : "=r"(r0), "=r"(r1), "=r"(r2), "=r"(r3) : "r"(a) : "memory");
}
__device__ __forceinline__ void ldsm4t(uint32_t a, uint32_t& r0, uint32_t& r1, uint32_t& r2, uint32_t& r3) {
  asm volatile("ldmatrix.sync.aligned.m8n8.x4.trans.shared.b16 {%0,%1,%2,%3}, [%4];" : "=r"(r0), "=r"(r1), "=r"(r2), "=r"(r3) : "r"(a) : "memory");
}
__device__ __forceinline__ void mma16(float* c, uint32_t a0, uint32_t a1, uint32_t a2, uint32_t a3, uint32_t b0, uint32_t b1) {
  asm("mma.sync.aligned.m16n8k16.row.col.f32.bf16.bf16.f32 {%0,%1,%2,%3}, {%4,%5,%6,%7}, {%8,%9}, {%0,%1,%2,%3};"
    : "+f"(c[0]), "+f"(c[1]), "+f"(c[2]), "+f"(c[3]) : "r"(a0), "r"(a1), "r"(a2), "r"(a3), "r"(b0), "r"(b1));
}
__device__ __forceinline__ void mma8(float* c, uint32_t a0, uint32_t a1, uint32_t b0) {
  asm("mma.sync.aligned.m16n8k8.row.col.f32.bf16.bf16.f32 {%0,%1,%2,%3}, {%4,%5}, {%6}, {%0,%1,%2,%3};"
    : "+f"(c[0]), "+f"(c[1]), "+f"(c[2]), "+f"(c[3]) : "r"(a0), "r"(a1), "r"(b0));
}
__device__ __forceinline__ uint32_t lane_id() { uint32_t l; asm volatile("mov.u32 %0, %%laneid;" : "=r"(l)); return l; }
__device__ __forceinline__ float quad_sum(float v) { v += __shfl_xor_sync(~0u, v, 1); v += __shfl_xor_sync(~0u, v, 2); return v; }
__device__ __forceinline__ float quad_max(float v) { v = fmaxf(v, __shfl_xor_sync(~0u, v, 1)); v = fmaxf(v, __shfl_xor_sync(~0u, v, 2)); return v; }
template <int N> __device__ __forceinline__ void pin(float (&d)[N]) {
#pragma unroll
  for (int i = 0; i < N; i++) asm volatile("" : "+f"(d[i]) :: "memory");
}
#define SPIN_GUARD(n) if (++(n) > SPIN_MAX) break

template <int NG> __device__ __forceinline__ void publish_stats(uint4* dst, const float* y, uint32_t tag, uint32_t lane) {
  float s0 = 0.f, s1 = 0.f;
#pragma unroll
  for (int g = 0; g < NG; g++) { s0 += y[4 * g] + y[4 * g + 1]; s1 += y[4 * g + 2] + y[4 * g + 3]; }
  s0 = quad_sum(s0); s1 = quad_sum(s1);
  const float m0 = s0 * (1.f / (8 * NG)), m1 = s1 * (1.f / (8 * NG));
  float q0 = 0.f, q1 = 0.f, q2 = 0.f, q3 = 0.f;
#pragma unroll
  for (int g = 0; g < NG; g++) {
    const float a = y[4 * g] - m0, b = y[4 * g + 1] - m0, c = y[4 * g + 2] - m1, d = y[4 * g + 3] - m1;
    q0 = fmaf(a, a, q0); q1 = fmaf(b, b, q1); q2 = fmaf(c, c, q2); q3 = fmaf(d, d, q3);
  }
  q0 = quad_sum(q0 + q1); q2 = quad_sum(q2 + q3);
  if ((lane & 3) == 0)
    stg4(dst + (lane >> 2), (__float_as_uint(s0) & ~1u) | tag, __float_as_uint(q0), __float_as_uint(s1), __float_as_uint(q2));
}

__device__ __forceinline__ void put72(uint4* slab, uint32_t j, uint32_t lane, const uint32_t* v) {
  uint4* p = slab + ((9 * j + 1) >> 1) * 32;
  if (j & 1) {
    stg2((char*)(p - 16) + lane * 8, nz(v[0]), v[1]);
#pragma unroll
    for (int i = 0; i < 4; i++) stg4(p + lane + i * 32, nz(v[4 * i + 2]), v[4 * i + 3], v[4 * i + 4], v[4 * i + 5]);
  } else {
#pragma unroll
    for (int i = 0; i < 4; i++) stg4(p + lane + i * 32, nz(v[4 * i]), v[4 * i + 1], v[4 * i + 2], v[4 * i + 3]);
    stg2((char*)(p + 4 * 32) + lane * 8, nz(v[16]), v[17]);
  }
}
__device__ __forceinline__ void zero_share(uint4* slab, uint32_t j, uint32_t lane) {
  uint4* p = slab + j * 144 + lane;
#pragma unroll
  for (int i = 0; i < 4; i++) stg4(p + i * 32, 0u, 0u, 0u, 0u);
  if (lane < 16) stg4(p + 128, 0u, 0u, 0u, 0u);
}

struct Maps { CUtensorMap m[5]; };

struct Ring {
  uint32_t st, ph;
  __device__ __forceinline__ void next() { if (++st == NST) { st = 0; ph ^= 1; } }
};

#define STAMP(i) do {} while (0)

__device__ __forceinline__ void tma_box(uint32_t dst, const CUtensorMap* m, int col, int row, uint32_t bar, uint32_t expect) {
  asm volatile("{\n.reg .pred e, h;\nelect.sync _|e, 0xffffffff;\nsetp.ne.and.u32 h, %5, 0, e;\n"
               "@h mbarrier.arrive.expect_tx.shared::cta.b64 _, [%2], %5;\n"
               "@e cp.async.bulk.tensor.2d.shared::cluster.global.mbarrier::complete_tx::bytes [%0], [%1, {%3, %4}], [%2];\n}"
               :: "r"(dst), "l"(m), "r"(bar), "r"(col), "r"(row), "r"(expect) : "memory");
}

__device__ __forceinline__ void bulk_load(uint32_t dst, const void* src, uint32_t bytes, uint32_t bar, bool arm) {
  asm volatile("{\n.reg .pred e, h;\nelect.sync _|e, 0xffffffff;\nsetp.ne.and.u32 h, %4, 0, e;\n"
               "@h mbarrier.arrive.expect_tx.shared::cta.b64 _, [%3], %2;\n"
               "@e cp.async.bulk.shared::cluster.global.mbarrier::complete_tx::bytes [%0], [%1], %2, [%3];\n}"
               :: "r"(dst), "l"(src), "r"(bytes), "r"(bar), "r"((uint32_t)arm) : "memory");
}

__global__ void __launch_bounds__(384, 1) mega_kernel(
    const __grid_constant__ Maps maps, uint4* __restrict__ scratch,
    const __nv_bfloat16* __restrict__ x_in, const __nv_bfloat16* __restrict__ wqkv, const __nv_bfloat16* __restrict__ wo,
    __nv_bfloat16* __restrict__ out) {
  extern __shared__ __align__(1024) uint8_t smem[];
  const uint32_t sb = (uint32_t)__cvta_generic_to_shared(smem);
  const uint32_t full0 = sb + BARS, empty0 = full0 + 8 * NST, rem_full = empty0 + 8 * NST, park_free = rem_full + 8, kv_free = park_free + 8;
  const uint32_t c8_go = kv_free + 8, c8_done = c8_go + 8, c8_full = c8_done + 8, pbar0 = c8_full + 8;
  const uint32_t w = __shfl_sync(~0u, threadIdx.x >> 5, 0);
  const uint32_t t = blockIdx.x >> 3, j = blockIdx.x & 7;
  uint4* const scr = scratch + t * TILE;
  {
    const uint32_t lane = lane_id(), r = lane >> 2, q = lane & 3;
    const uint32_t sl = w < 8 ? w : j, ch = w < 8 ? j : 8;
    const uint32_t* xr = (const uint32_t*)(x_in + (128 * t + 32 * (sl >> 1) + 2 * r + (sl & 1)) * 576 + 64 * ch + 2 * q);
    if (w < 8 || w == 9) {
      uint32_t v[16];
#pragma unroll
      for (int g = 0; g < 8; g++) {
        asm volatile("ld.global.nc.b32 %0, [%1];" : "=r"(v[2 * g]) : "l"(xr + 4 * g));
        asm volatile("ld.global.nc.b32 %0, [%1];" : "=r"(v[2 * g + 1]) : "l"(xr + 8 * 576 + 4 * g));
      }
      asm volatile("bar.sync 0;" ::: "memory");
      uint4* p = scr + OFF_X + sl * SLAB + 4 * ch * 32 + lane;
#pragma unroll
      for (int i = 0; i < 4; i++) stg4(p + i * 32, nz(v[4 * i]), v[4 * i + 1], nz(v[4 * i + 2]), v[4 * i + 3]);
      float y[32];
#pragma unroll
      for (int i = 0; i < 16; i++) { y[2 * i] = bf_lo(v[i]); y[2 * i + 1] = bf_hi(v[i]); }
      publish_stats<8>(scr + OFF_S + sl * 96 + ch * 8, y, 1u, lane);
    } else {
      if (threadIdx.x == 256) {
        for (int i = 0; i < NST; i++) { mbar_init(full0 + 8 * i, 1); mbar_init(empty0 + 8 * i, 8); }
        mbar_init(rem_full, 1); mbar_init(park_free, 8); mbar_init(kv_free, 8); mbar_init(c8_go, 8); mbar_init(c8_done, 1); mbar_init(c8_full, 1);
        for (int i = 0; i < 8; i++) mbar_init(pbar0 + 8 * i, 5);
        asm volatile("fence.mbarrier_init.release.cluster;" ::: "memory");
      }
      __syncwarp();
      asm volatile("bar.sync 0;" ::: "memory");
    }
  }

  if (w >= 8) {
    asm volatile("setmaxnreg.dec.sync.aligned.u32 24;");
    if (w == 8) {
      Ring rg{0, 1};
#pragma unroll 1
      for (int seg = 0; seg < 34; seg++) {
        const int n = seg >= 17 ? seg - 17 : seg;
        int ma, mb, ca, cb, row = 0;
        if (n < 3) { ma = mb = n == 2; ca = 72 * j + (n == 0 ? 576 : 0); cb = ca + 576; }
        else if (n < 12) { ma = 3; mb = 2; ca = cb = 576 * j + 64 * (n - 3); }
        else { ma = mb = 4; ca = n == 12 ? 512 : ((j + 2 * n) & 7) * 64; cb = ((j + 2 * n + 1) & 7) * 64; row = 576 * j; }
        const bool zip = n == 0 || n == 3;
        const int nb = (n == 1 || n == 2 || n == 16) ? 9 : 18;
#pragma unroll 1
        for (int b = 0; b < nb; b++) {
          const bool second = zip ? (b & 1) : b >= 9, last = b == nb - 1;
          const int kb = zip ? b >> 1 : second ? b - 9 : b;
          if (!(b & 1)) mbar_wait(empty0 + rg.st * 8, rg.ph);
          tma_box(sb + rg.st * STAGE + (b & 1) * 8192, &maps.m[second ? mb : ma], second ? cb : ca, row + 64 * kb, full0 + rg.st * 8,
                  (b & 1) ? 0 : last ? STAGE / 2 : STAGE);
          if ((b & 1) || last) rg.next();
        }
      }
    } else if (w == 9) {
      const uint32_t lane = lane_id();
      const uint32_t stg = sb + HSTG + lane * 16;
      uint32_t fph = 0;
#pragma unroll 1
      for (uint32_t layer = 0; layer < 2; layer++) {
        uint4* xb = scr + OFF_X + ((4 + layer) * 8 + j) * SLAB + 32 * 32;
        mbar_wait(c8_go, layer);
        int n = 0;
        while (true) {
          if (lane == 0) asm volatile("mbarrier.arrive.expect_tx.shared::cta.b64 _, [%0], 18432;" :: "r"(c8_full) : "memory");
          __syncwarp();
#pragma unroll 1
          for (uint32_t s = 0; s < 9; s++)
            bulk_load(sb + HSTG + s * 2048, s < 8 ? scr + OFF_P + (j + s * 8) * SLAB + 32 * 32 : xb, 2048, c8_full, false);
          mbar_wait(c8_full, fph); fph ^= 1;
          uint32_t bad = 0;
#pragma unroll 8
          for (int s = 0; s < 32; s++) { uint32_t v; asm volatile("ld.shared.b32 %0, [%1];" : "=r"(v) : "r"(stg + s * 512) : "memory"); bad |= v ^ (1 - layer); }
          if (__all_sync(~0u, (bad & 1u) == 0u)) break;
          __nanosleep(300);
          SPIN_GUARD(n);
        }
        float s0 = 0.f, s1 = 0.f;
#pragma unroll 1
        for (int g = 0; g < 8; g++) {
          const uint32_t a = stg + (g >> 1) * 512 + (g & 1) * 8;
          float a0 = 0.f, a1 = 0.f, a2 = 0.f, a3 = 0.f;
#pragma unroll 1
          for (int b = 0; b < 3; b++) {
            uint32_t v[6];
#pragma unroll
            for (int s = 0; s < 3; s++) lds2(a + (3 * b + s) * 2048, v + 2 * s);
#pragma unroll
            for (int s = 0; s < 3; s++) { a0 += bf_lo(v[2 * s]); a1 += bf_hi(v[2 * s]); a2 += bf_lo(v[2 * s + 1]); a3 += bf_hi(v[2 * s + 1]); }
          }
          sts1(a + 18432, pack_bf16(a0, a1)); sts1(a + 18436, pack_bf16(a2, a3));
          s0 += a0 + a1; s1 += a2 + a3;
        }
        __syncwarp();
        if (lane == 0) mbar_arrive(c8_done);
        s0 = quad_sum(s0); s1 = quad_sum(s1);
        float q0 = 0.f, q1 = 0.f;
        const uint32_t ln = lane_id();
#pragma unroll 1
        for (uint32_t i = 0; i < 4; i++) {
          uint32_t x[4];
          lds4(stg + 18432 + i * 512, x);
          stg4(xb + i * 32 + ln, 0u, 0u, 0u, 0u);
          if (layer == 0) {
            stg4(xb - 3 * 8 * SLAB + i * 32 + ln, nz(x[0]), x[1], x[2], x[3]);
#pragma unroll
            for (int e = 0; e < 4; e++) {
              const float m = (e & 1) ? s1 : s0, c = fmaf(m, -1.f / 64, bf_lo(x[e])), d = fmaf(m, -1.f / 64, bf_hi(x[e]));
              if (e & 1) q1 = fmaf(c, c, fmaf(d, d, q1)); else q0 = fmaf(c, c, fmaf(d, d, q0));
            }
          } else {
            uint32_t* o = (uint32_t*)(out + (128 * t + 32 * (j >> 1) + 2 * (ln >> 2) + (j & 1)) * 576 + 512 + 16 * i + 2 * (ln & 3));
            o[0] = x[0]; o[8 * 576] = x[1]; o[4] = x[2]; o[8 * 576 + 4] = x[3];
          }
        }
        if (layer == 0) {
          q0 = quad_sum(q0); q1 = quad_sum(q1);
          if ((ln & 3) == 0) stg4(scr + OFF_S + j * 96 + 64 + (ln >> 2), __float_as_uint(s0) & ~1u, __float_as_uint(q0), __float_as_uint(s1), __float_as_uint(q1));
        }
      }
    } else {
      const uint32_t lane = lane_id(), r = lane >> 2, q = lane & 3;
      {
        uint4 v[3];
        const uint32_t p = t >> 2, k0 = (t & 3) * 144 + threadIdx.x - 320;
        const uint4* src = (const uint4*)(p == 3 ? wo + k0 * 576 : wqkv + k0 * 1728 + (p < 2 ? 576 * (p + 1) : 0)) + 9 * j + 8;
#pragma unroll
        for (int i = 0; i < 3; i++) if (i < 2 || threadIdx.x < 336) v[i] = __ldg(src + i * (p == 3 ? 8 * 576 : 8 * 1728));
        const uint32_t s = k0 >> 4, rr = k0 & 7;
        uint4* dst = scratch + OFF_R + j * 2304 + (s >> 1) * 128 + ((k0 >> 3) & 1) * 64 + rr * 8 + (((s & 1) * 4 + p) ^ rr);
#pragma unroll
        for (int i = 0; i < 3; i++) if (i < 2 || threadIdx.x < 336) stg4(dst + i * 256, v[i].x, v[i].y, v[i].z, v[i].w);
        __threadfence();
        __syncwarp();
        if (lane < 16) asm volatile("st.relaxed.gpu.global.b32 [%0], 1;" :: "l"((uint32_t*)(scratch + OFF_F + (lane * 8 + j) * 8) + 2 * t + w - 10) : "memory");
      }
#pragma unroll 1
      for (uint32_t layer = 0; layer < 2; layer++) {
        if (w == 10) {
          if (layer) {
            mbar_wait(park_free, 0);
          } else {
            uint32_t* fl = (uint32_t*)(scratch + OFF_F + (t * 8 + j) * 8) + lane;
            uint32_t v;
            int n = 0;
            while (true) {
              asm volatile("ld.acquire.gpu.global.b32 %0, [%1];" : "=r"(v) : "l"(fl) : "memory");
              if (__all_sync(~0u, v != 0u)) break;
              SPIN_GUARD(n);
            }
            asm volatile("fence.proxy.async;\nst.relaxed.gpu.global.b32 [%0], 0;" :: "l"(fl) : "memory");
          }
          bulk_load(sb + REM, scratch + OFF_R + j * 2304, 36864, rem_full, true);
        }
        if (layer) mbar_wait(kv_free, 0);
        if (t > 0) {
#pragma unroll 1
          for (uint32_t pc = 0; pc < 3; pc++) {
            uint4* hp = scr + OFF_H + ((layer * 8 + j) * 2 + (w - 10)) * 192 + pc * 64 + lane;
            uint32_t hl[8];
            int n = 0;
            hl[4] = 1u;
            while (true) {
              ldg4(hl, hp);
              if (pc < 2) ldg4(hl + 4, hp + 32);
              if (__all_sync(~0u, hl[0] != 0u && hl[4] != 0u)) break;
              __nanosleep(100);
              SPIN_GUARD(n);
            }
            const uint32_t dst = sb + KVS + (w - 10) * 10368 + r * 144 + q * 4;
            if (pc < 2) {
#pragma unroll
              for (int g = 0; g < 8; g++) sts1(dst + pc * 20736 + g * 16, hl[g]);
              stg4(hp + 32, 0u, 0u, 0u, 0u);
            } else {
              sts1(dst + 128, hl[0]); sts1(dst + 20736 + 128, hl[1]);
            }
            stg4(hp, 0u, 0u, 0u, 0u);
          }
        }
        asm volatile("bar.arrive 1, 192;" ::: "memory");
      }
    }
  } else {
    asm volatile("setmaxnreg.inc.sync.aligned.u32 240;");
    const uint32_t lane = lane_id(), r = lane >> 2, q = lane & 3;
    Ring rg{0, 0};
    uint32_t prev = 0;
    uint32_t X[144];
    float rs0, rs1;
    uint32_t mean0, mean1;
    auto release = [&](uint32_t st) { if (lane == 0) mbar_arrive(empty0 + st * 8); };
    auto load_kb = [&](int kb, const uint4* src, const char* lo, uint32_t hoff) {
#pragma unroll
      for (int k = 4 * kb; k < 4 * kb + 4; k++) {
        if (k % 9 == 4) { ldg2(X + 4 * k, lo + k * 512); ldg2(X + 4 * k + 2, lo + hoff + k * 512); }
        else ldg4(X + 4 * k, src + k * 32);
      }
    };
    auto next_kb = [&](bool center, int kb, const uint4* src, const char* lo, uint32_t hoff) {
      int n = 0;
      while (true) {
        bool ok = true;
#pragma unroll
        for (int k = 4 * kb; k < 4 * kb + 4; k++) { ok = ok && X[4 * k] != 0u; if (k % 9 == 4) ok = ok && X[4 * k + 2] != 0u; }
        if (__all_sync(~0u, ok)) break;
        SPIN_GUARD(n);
        load_kb(kb, src, lo, hoff);
      }
      if (kb + GD < 9) load_kb(kb + GD, src, lo, hoff);
      if (center) {
#pragma unroll
        for (int i = 16 * kb; i < 16 * kb + 16; i++) X[i] = sub_bf16x2(X[i], (i & 1) ? mean1 : mean0);
      }
    };
#pragma unroll 1
    for (uint32_t hf = 0; hf < 4; hf++) {
      const uint32_t layer = hf >> 1;
      const bool ffn = hf & 1;
      const uint32_t tag = 1 - layer;
      uint4* const xbase = scr + OFF_X + (layer * 8 + w) * SLAB;
      float aA[32], aB[32];
      {
        const uint4* src = xbase + (ffn ? 32 * SLAB : 0) + lane;
        const char* lo = (const char*)src - (ffn ? lane * 8 : 0);
        const uint32_t hoff = ffn ? 256 : 8;
        uint32_t s[3][4];
        const uint4* p = scr + OFF_S + ((ffn ? 16 : 0) + w) * 96 + q * 8 + r;
        const bool third = !ffn && q == 0;
        int n = 0;
        s[2][0] = tag; s[2][1] = s[2][2] = s[2][3] = 0u;
        STAMP(ffn * 16 + 0);
        while (true) {
          ldg4(s[0], p); ldg4(s[1], p + 32);
          if (third) ldg4(s[2], p + 64);
          if (__all_sync(~0u, ((s[0][0] ^ tag) | (s[1][0] ^ tag) | (s[2][0] ^ tag)) % 2u == 0u)) break;
          SPIN_GUARD(n);
        }
        STAMP(ffn * 16 + 1);
#pragma unroll
        for (int kb = 0; kb < GD; kb++) load_kb(kb, src, lo, hoff);
        float t0 = 0.f, t1 = 0.f;
#pragma unroll
        for (int i = 0; i < 3; i++) { t0 += __uint_as_float(s[i][0]); t1 += __uint_as_float(s[i][2]); }
        const float m0 = quad_sum(t0) * (1.f / 576), m1 = quad_sum(t1) * (1.f / 576);
        const float cnt = ffn ? 72.f : 64.f, inv = ffn ? 1.f / 72 : 1.f / 64;
        float v0 = 0.f, v1 = 0.f;
#pragma unroll
        for (int i = 0; i < 3; i++) {
          const float c = (i < 2 || third) ? cnt : 0.f;
          const float d0 = fmaf(__uint_as_float(s[i][0]), inv, -m0), d1 = fmaf(__uint_as_float(s[i][2]), inv, -m1);
          v0 += fmaf(d0 * d0, c, __uint_as_float(s[i][1])); v1 += fmaf(d1 * d1, c, __uint_as_float(s[i][3]));
        }
        rs0 = rsqrtf(fmaf(quad_sum(v0), 1.f / 576, 1e-5f)); rs1 = rsqrtf(fmaf(quad_sum(v1), 1.f / 576, 1e-5f));
        mean0 = pack_bf16(m0, m0); mean1 = pack_bf16(m1, m1);
#pragma unroll
        for (int kb = 0; kb < 9; kb++) {
          next_kb(true, kb, src, lo, hoff);
          mbar_wait(full0 + rg.st * 8, rg.ph);
          const uint64_t desc = DESC_HI | ((sb + rg.st * STAGE) >> 4);
          wg_fence();
#pragma unroll
          for (int i = 0; i < 4; i++) wgmma_rs_n64(aA, X + 4 * (4 * kb + i), desc + i * 128, kb + i != 0);
#pragma unroll
          for (int i = 0; i < 4; i++) wgmma_rs_n64(aB, X + 4 * (4 * kb + i), desc + 512 + i * 128, kb + i != 0);
          wg_commit();
          wg_wait<1>();
          if (kb > 0) release(prev);
          prev = rg.st; rg.next();
        }
        wg_wait<0>();
        STAMP(ffn * 16 + 2);
      }
      if (!ffn) {
      release(prev);
      const uint32_t kvrow = sb + KVS + (w & 1) * 10368 + (16 * (w >> 1)) * 144;
      uint32_t Q[18];
      {
        const uint32_t dst = kvrow + (8 + r) * 144 + q * 4;
        const bool edge_out = w >= 6 && t < 15;
        uint4* const hp = scr + TILE + OFF_H + ((layer * 8 + j) * 2 + (w & 1)) * 192 + lane;
        auto put_kv = [&](float (&a)[32], int part) {
          pin(a);
          uint32_t hl[8];
#pragma unroll
          for (int g = 0; g < 8; g++) {
            hl[g] = pack_bf16(a[4 * g + 2] * rs1, a[4 * g + 3] * rs1);
            sts1(dst + part * 20736 + g * 16, pack_bf16(a[4 * g] * rs0, a[4 * g + 1] * rs0)); sts1(dst + part * 20736 + 8 * 144 + g * 16, hl[g]);
          }
          if (edge_out) { stg4(hp + part * 64, nz(hl[0]), hl[1], hl[2], hl[3]); stg4(hp + part * 64 + 32, nz(hl[4]), hl[5], hl[6], hl[7]); }
        };
        put_kv(aA, 0);
        float aR[12];
        mbar_wait(rem_full, layer);
        const uint64_t dr = DESC_HI | ((sb + REM) >> 4);
        wg_fence();
#pragma unroll
        for (int s = 0; s < 36; s++) {
          wgmma_rs_n24(aR, X + 4 * s, dr + ((s >> 1) * 128 + (s & 1) * 4), s != 0);
          if (s == 4) put_kv(aB, 1);
        }
        wg_commit();
#pragma unroll
        for (int kb = 0; kb < 9; kb++) {
          if (!(kb & 1)) mbar_wait(full0 + rg.st * 8, rg.ph);
          const uint64_t desc = DESC_HI | ((sb + rg.st * STAGE + (kb & 1) * 8192) >> 4);
          wg_fence();
#pragma unroll
          for (int i = 0; i < 4; i++) wgmma_rs_n64(aB, X + 4 * (4 * kb + i), desc + i * 128, kb + i != 0);
          wg_commit();
          wg_wait<1>();
          if (kb > 0 && !(kb & 1)) release(prev);
          if ((kb & 1) || kb == 8) { prev = rg.st; rg.next(); }
          if (kb == 0) {
            pin(aR);
            const uint32_t k1 = pack_bf16(aR[2] * rs1, aR[3] * rs1), v1 = pack_bf16(aR[6] * rs1, aR[7] * rs1);
            if (edge_out) stg4(hp + 128, nz(k1), v1, 0u, 0u);
            sts1(dst + 128, pack_bf16(aR[0] * rs0, aR[1] * rs0)); sts1(dst + 8 * 144 + 128, k1);
            sts1(dst + 20736 + 128, pack_bf16(aR[4] * rs0, aR[5] * rs0)); sts1(dst + 20736 + 8 * 144 + 128, v1);
            Q[16] = pack_bf16(aR[8] * rs0, aR[9] * rs0); Q[17] = pack_bf16(aR[10] * rs1, aR[11] * rs1);
            if (w < 4) asm volatile("bar.arrive 2, 256;" ::: "memory");
          }
        }
        wg_wait<0>();
        release(prev);
        pin(aB);
        STAMP(3);
#pragma unroll
        for (int g = 0; g < 8; g++) {
          Q[2 * g] = pack_bf16(aB[4 * g] * rs0, aB[4 * g + 1] * rs0); Q[2 * g + 1] = pack_bf16(aB[4 * g + 2] * rs1, aB[4 * g + 3] * rs1);
        }
      }
      if (w < 4) asm volatile("bar.sync 1, 192;" ::: "memory");
      else asm volatile("bar.sync 2, 256;" ::: "memory");
      STAMP(4);
      uint32_t O[18];
      {
        const bool edge = (t == 0 && w < 2);
        uint32_t row[3];
#pragma unroll
        for (int nt = 0; nt < 3; nt++) row[nt] = kvrow + (8 * nt + (lane & 7)) * 144;
        if (edge) row[0] = sb + KVS + 8 * 144;
        const uint32_t rlast = ((lane >> 3) == 0 ? row[0] : (lane >> 3) == 1 ? row[1] : row[2]) + 128;
        uint32_t K[3][9], V[3][9], dummy;
#pragma unroll
        for (int nt = 0; nt < 3; nt++) {
          ldsm4(row[nt] + (lane >> 3) * 16, K[nt][0], K[nt][1], K[nt][2], K[nt][3]);
          ldsm4(row[nt] + 64 + (lane >> 3) * 16, K[nt][4], K[nt][5], K[nt][6], K[nt][7]);
        }
        ldsm4(rlast, K[0][8], K[1][8], K[2][8], dummy);
#pragma unroll
        for (int nt = 0; nt < 3; nt++) {
          ldsm4t(row[nt] + 20736 + (lane >> 3) * 16, V[nt][0], V[nt][1], V[nt][2], V[nt][3]);
          ldsm4t(row[nt] + 20736 + 64 + (lane >> 3) * 16, V[nt][4], V[nt][5], V[nt][6], V[nt][7]);
        }
        ldsm4t(rlast + 20736, V[0][8], V[1][8], V[2][8], dummy);
        const bool up0 = 2 * q > r, up1 = 2 * q + 1 > r;
        const float sc = 0.23570226039551584f * 1.4426950408889634f;
        const float neg = -1e9f * 1.4426950408889634f;
        float Of[9][4];
#pragma unroll
        for (int h = 0; h < 4; h++) {
          const uint32_t a0 = q >= h ? Q[4 * h] : 0u, a1 = q >= h ? Q[4 * h + 1] : 0u;
          const uint32_t a4 = q <= h ? Q[4 * h + 4] : 0u, a5 = q <= h ? Q[4 * h + 5] : 0u;
          float S[3][4];
#pragma unroll
          for (int nt = 0; nt < 3; nt++) {
            S[nt][0] = S[nt][1] = S[nt][2] = S[nt][3] = 0.f;
            mma16(S[nt], a0, a1, Q[4 * h + 2], Q[4 * h + 3], K[nt][2 * h], K[nt][2 * h + 1]);
            mma8(S[nt], a4, a5, K[nt][2 * h + 2]);
          }
          float s00 = (up0 ? S[0][0] : S[1][0]) * sc, s01 = (up1 ? S[0][1] : S[1][1]) * sc;
          const float s10 = (up0 ? S[1][2] : S[2][2]) * sc, s11 = (up1 ? S[1][3] : S[2][3]) * sc;
          if (edge && up0) s00 = neg;
          if (edge && up1) s01 = neg;
          const float m0 = quad_max(fmaxf(s00, s01)), m1 = quad_max(fmaxf(s10, s11));
          float p00 = ex2(s00 - m0), p01 = ex2(s01 - m0), p10 = ex2(s10 - m1), p11 = ex2(s11 - m1);
          const float i0 = rcp(quad_sum(p00 + p01)), i1 = rcp(quad_sum(p10 + p11));
          p00 *= i0; p01 *= i0; p10 *= i1; p11 *= i1;
          const uint32_t pa = pack_bf16(up0 ? p00 : 0.f, up1 ? p01 : 0.f), pb = pack_bf16(up0 ? 0.f : p00, up1 ? 0.f : p01);
          const uint32_t pc = pack_bf16(up0 ? p10 : 0.f, up1 ? p11 : 0.f), pd = pack_bf16(up0 ? 0.f : p10, up1 ? 0.f : p11);
#pragma unroll
          for (int gi = 0; gi < 3; gi++) {
            const int g = 2 * h + gi;
            float o[4] = {0.f, 0.f, 0.f, 0.f};
            mma16(o, pa, 0u, pb, pc, V[0][g], V[1][g]);
            mma8(o, 0u, pd, V[2][g]);
#pragma unroll
            for (int e = 0; e < 4; e++) Of[g][e] = (gi == 0 && h > 0 && q < h) ? Of[g][e] : o[e];
          }
        }
#pragma unroll
        for (int g = 0; g < 9; g++) { O[2 * g] = pack_bf16(Of[g][0], Of[g][1]); O[2 * g + 1] = pack_bf16(Of[g][2], Of[g][3]); }
      }
      put72(xbase + 16 * SLAB, j, lane, O);
      if (q == 0) stg4(scr + OFF_S + (8 + w) * 96 + j * 8 + r, tag, 0u, 0u, 0u);
      {
        uint32_t res[18];
        const char* p = (const char*)(xbase + lane) + ((9 * j) >> 1) * 512 + (j & 1) * 8;
#pragma unroll
        for (int g = 0; g < 9; g++) ldg2(res + 2 * g, p + (g >> 1) * 512 + ((g & 1) ? ((j & 1) ? 504 : 8) : 0));
        const uint4* src = xbase + 16 * SLAB + lane;
        {
          const uint4* fp = scr + OFF_S + (8 + w) * 96 + q * 8 + r;
          uint32_t s0[4], s1[4];
          int n = 0;
          STAMP(8);
          while (true) {
            ldg4(s0, fp); ldg4(s1, fp + 32);
            if (__all_sync(~0u, ((s0[0] ^ tag) | (s1[0] ^ tag)) % 2u == 0u)) break;
            SPIN_GUARD(n);
          }
          STAMP(9);
        }
#pragma unroll
        for (int kb = 0; kb < GD; kb++) load_kb(kb, src, (const char*)src - lane * 8, 256);
        float acc[36];
#pragma unroll
        for (int kb = 0; kb < 9; kb++) {
          next_kb(false, kb, src, (const char*)src - lane * 8, 256);
          if (!(kb & 1)) mbar_wait(full0 + rg.st * 8, rg.ph);
          const uint32_t base = sb + rg.st * STAGE + (kb & 1) * 8192;
          const uint64_t d0 = DESC_HI | ((base >> 4) + (((sb + REM + kb * 4096 + 48 - base) >> 4) << 16));
          wg_fence();
#pragma unroll
          for (int i = 0; i < 4; i++)
            wgmma_rs_n72(acc, X + 4 * (4 * kb + i), d0 + (uint64_t)(i * 128) - ((uint64_t)(((i + 1) >> 1) * 128 - (i & 1) * 4) << 16), kb + i != 0);
          wg_commit();
          wg_wait<1>();
          if (kb > 0 && !(kb & 1)) release(prev);
          if ((kb & 1) || kb == 8) { prev = rg.st; rg.next(); }
        }
        wg_wait<0>();
        release(prev);
        pin(acc);
        STAMP(10);
#pragma unroll
        for (int i = 0; i < 18; i++) {
          acc[2 * i] += bf_lo(res[i]); acc[2 * i + 1] += bf_hi(res[i]);
          res[i] = pack_bf16(acc[2 * i], acc[2 * i + 1]);
        }
        put72(xbase + 32 * SLAB, j, lane, res);
        publish_stats<9>(scr + OFF_S + (16 + w) * 96 + j * 8, acc, tag, lane);
      }
      continue;
      }
      const uint32_t hp = sb + PARK + w * 512 + lane * 16;
      auto pack8 = [&](float (&a)[32], int p, uint32_t* o) {
#pragma unroll
        for (int e = 0; e < 8; e++) asm volatile("" : "+f"(a[8 * p + e]) :: "memory");
#pragma unroll
        for (int e = 0; e < 4; e++) o[e] = pack_bf16(a[8 * p + 2 * e], a[8 * p + 2 * e + 1]);
      };
      const float ka0 = 0.7978845608028654f * rs0, kb0 = 0.044715f * ka0 * rs0 * rs0, ku0 = 0.5f * rs0 * rs0;
      const float ka1 = 0.7978845608028654f * rs1, kb1 = 0.044715f * ka1 * rs1 * rs1, ku1 = 0.5f * rs1 * rs1;
      auto packu8 = [&](int p, uint32_t* o) {
#pragma unroll
        for (int e = 0; e < 8; e++) asm volatile("" : "+f"(aA[8 * p + e]) :: "memory");
#pragma unroll
        for (int e = 0; e < 4; e++) o[e] = pack_bf16(aA[8 * p + 2 * e] * ((e & 1) ? ku1 : ku0), aA[8 * p + 2 * e + 1] * ((e & 1) ? ku1 : ku0));
      };
      auto geglu8 = [&](int p, uint32_t* u) {
#pragma unroll
        for (int e = 0; e < 8; e++) asm volatile("" : "+f"(aB[8 * p + e]) :: "memory");
        float h[8];
#pragma unroll
        for (int e = 0; e < 8; e++) {
          const float g = aB[8 * p + e];
          h[e] = fmaf(g, tanh_ap(g * fmaf(g * g, (e & 2) ? kb1 : kb0, (e & 2) ? ka1 : ka0)), g);
        }
#pragma unroll
        for (int e = 0; e < 4; e++) u[e] = mul_bf16x2(pack_bf16(h[2 * e], h[2 * e + 1]), u[e]);
      };
      auto box = [&](int b, auto&& filler) {
        const int kb = b < 9 ? b : b - 9;
        if (!(b & 1)) mbar_wait(full0 + rg.st * 8, rg.ph);
        const uint64_t desc = DESC_HI | ((sb + rg.st * STAGE + (b & 1) * 8192) >> 4);
        wg_fence();
#pragma unroll
        for (int i = 0; i < 4; i++) {
          if (b < 9) wgmma_rs_n64(aA, X + 4 * (4 * kb + i), desc + i * 128, kb + i != 0);
          else wgmma_rs_n64(aB, X + 4 * (4 * kb + i), desc + i * 128, kb + i != 0);
          if (i == FPOS) filler();
        }
        wg_commit();
        if (b & 1) { if (W2) wg_wait<1>(); prev = rg.st; rg.next(); } else { wg_wait<1>(); release(prev); }
      };
      auto nop = [] {};
      auto step = [&](int st, auto&& filler) { box(2 * st, nop); box(2 * st + 1, filler); };
#pragma unroll
      for (int p = 0; p < 4; p++) { uint32_t o[4]; packu8(p, o); sts4(hp + p * 4096, o); }
      box(0, nop);
      zero_share(xbase, j, lane);
      zero_share(xbase + 16 * SLAB, j, lane);
#pragma unroll 1
      for (int c = 1;; c++) {
        const uint32_t hc = hp + c * 4 * 4096;
#pragma unroll
        for (int b = 1; b < 18; b++) box(b, [&] {
          if ((b & 1) && b < 8) { uint32_t o[4]; const uint32_t a = hc - (4 - (b >> 1)) * 4096; lds4(a, o); geglu8(b >> 1, o); sts4(a, o); }
          if ((b & 1) && b > 10) { uint32_t o[4]; packu8((b - 11) >> 1, o); if (c < 8) sts4(hc + ((b - 11) >> 1) * 4096, o); } });
        if (c == 8) break;
        box(0, nop);
      }
      wg_wait<0>();
      STAMP(21);
#pragma unroll
      for (int s = 0; s < 32; s++) lds4(hp + s * 4096, X + 4 * s);
#pragma unroll
      for (int p = 0; p < 4; p++) packu8(p, X + 128 + 4 * p);
#pragma unroll
      for (int st = 0; st < 4; st++) step(st, [&] { geglu8(st, X + 128 + 4 * st); });
      STAMP(24);
      if (layer == 0 && lane == 0) mbar_arrive(park_free);
      const uint32_t lane2 = lane_id();
      uint4* const pw = scr + OFF_P + (j * 8 + w) * SLAB + lane2;
      const uint4* const pr = scr + OFF_P + w * SLAB + 4 * j * 32 + lane2;
      auto put_part = [&](float (&a)[32], int p, uint32_t chunk) {
        uint32_t o[4];
        pack8(a, p, o);
        stg4(pw + (chunk * 4 + p) * 32, (o[0] & ~1u) | tag, o[1], o[2], o[3]);
      };
      auto slot = [&](int p) { return sb + w * 2048 + (p < 4 ? PARK + (p - 1) * 16384 : KVS + (p - 4) * 16384); };
      auto fetch = [&](int p) {
        if (p > 0) bulk_load(slot(p), scr + OFF_P + (((j - p) & 7) * 8 + w) * SLAB + 4 * j * 32, 2048, pbar0 + w * 8, true);
      };
      uint4* const xb = xbase + 32 * SLAB + 4 * j * 32;
#pragma unroll 1
      for (int sp = 0;; sp++) {
        const uint32_t ca = sp == 0 ? 8 : ((j + 2 * sp) & 7), cb = (j + 2 * sp + 1) & 7;
        if (sp == 1 && lane == 0) mbar_arrive(c8_go);
#pragma unroll
        for (int st = 4; st < 9; st++) step(st, [&] {
          if (st == 5 || st == 6) { put_part(aA, 2 * (st - 5), ca); put_part(aA, 2 * (st - 5) + 1, ca); }
          if (st == 8) { if (sp == 3) mbar_wait(c8_done, layer); fetch(2 * sp - 1); } });
        STAMP(25 + sp);
        if (sp == 3) break;
        if (sp == 2) asm volatile("{\n.reg .pred e;\nelect.sync _|e, 0xffffffff;\n@e cp.async.bulk.prefetch.L2.global [%0], 2048;\n}" :: "l"(xb) : "memory");
#pragma unroll
        for (int st = 0; st < 4; st++) step(st, [&] {
          if (st < 2) { put_part(aB, 2 * st, cb); put_part(aB, 2 * st + 1, cb); }
          if (st == 3) fetch(2 * sp); });
      }
      auto load_p = [&](int p, uint32_t* d) {
#pragma unroll
        for (int i = 0; i < 4; i++) ldg4(d + 4 * i, pr + ((j - p) & 7) * 8 * SLAB + i * 32);
      };
#pragma unroll
      for (int st = 0; st < 4; st++) step(st, [&] {
        if (st == 0) {
#pragma unroll
          for (int p = 0; p < 4; p++) put_part(aB, p, (j + 7) & 7);
        }
        if (st == 1) {
#pragma unroll
          for (int i = 0; i < 4; i++) {
            const bool split = j == 2 * i + 1;
            const char* l = (const char*)(xb + i * 32) + (split ? lane2 * 8 : lane2 * 16);
            ldg2(X + 4 * i, l); ldg2(X + 4 * i + 2, l + (split ? 256 : 8));
          }
          load_p(6, X + 16);
        }
        if (st == 3) load_p(7, X + 32); });
      {
        mbar_wait(full0 + rg.st * 8, rg.ph);
        const uint64_t desc = DESC_HI | ((sb + rg.st * STAGE) >> 4);
        wg_fence();
#pragma unroll
        for (int i = 0; i < 4; i++) wgmma_rs_n64(aA, X + 4 * (32 + i), desc + i * 128, 1);
        wg_commit();
        wg_wait<1>(); release(prev);
        prev = rg.st; rg.next();
        mbar_wait(pbar0 + w * 8, layer);
        wg_wait<0>(); release(prev);
        pin(aA);
      }
      STAMP(22);
      {
        const uint32_t eye = r == 2 * q ? 0x3f80u : r == 2 * q + 1 ? 0x3f800000u : 0u;
        auto add_p = [&](int p, uint32_t* d) {
          int n = 0;
          while (!__all_sync(~0u, (((d[0] ^ tag) | (d[4] ^ tag) | (d[8] ^ tag) | (d[12] ^ tag)) & 1u) == 0u)) { SPIN_GUARD(n); load_p(p, d); }
#pragma unroll
          for (int g = 0; g < 8; g++) mma8(aA + 4 * g, d[2 * g], d[2 * g + 1], eye);
        };
#pragma unroll
        for (int p = 1; p < 6; p++)
#pragma unroll
          for (int i = 0; i < 4; i++) lds4(slot(p) + lane2 * 16 + i * 512, X + 32 + 16 * p + 4 * i);
#pragma unroll
        for (int g = 0; g < 8; g++) mma8(aA + 4 * g, X[2 * g], X[2 * g + 1], eye);
#pragma unroll
        for (int p = 1; p < 6; p++) add_p(p, X + 32 + 16 * p);
        add_p(6, X + 16); add_p(7, X + 32);
        uint32_t res[16];
#pragma unroll
        for (int i = 0; i < 16; i++) res[i] = pack_bf16(aA[2 * i], aA[2 * i + 1]);
        if (layer == 0) {
          uint4* p = xbase + 8 * SLAB + 4 * j * 32 + lane;
#pragma unroll
          for (int i = 0; i < 4; i++) stg4(p + i * 32, nz(res[4 * i]), res[4 * i + 1], nz(res[4 * i + 2]), res[4 * i + 3]);
          publish_stats<8>(scr + OFF_S + w * 96 + j * 8, aA, 0u, lane);
          if (lane == 0) mbar_arrive(kv_free);
        } else {
          uint32_t* o = (uint32_t*)(out + (128 * t + 32 * (w >> 1) + 2 * r + (w & 1)) * 576 + 64 * j + 2 * q);
#pragma unroll
          for (int g = 0; g < 8; g++) { o[4 * g] = res[2 * g]; o[8 * 576 + 4 * g] = res[2 * g + 1]; }
        }
#pragma unroll
        for (int i = 0; i < 4; i++) stg4(xb + lane + i * 32, 0u, 0u, 0u, 0u);
      }
      STAMP(23);
    }
  }
}

typedef CUresult (*EncodeFn)(CUtensorMap*, CUtensorMapDataType, cuuint32_t, void*, const cuuint64_t*, const cuuint64_t*,
                             const cuuint32_t*, const cuuint32_t*, CUtensorMapInterleave, CUtensorMapSwizzle,
                             CUtensorMapL2promotion, CUtensorMapFloatOOBfill);

CUtensorMap make_map(EncodeFn f, const void* p, uint64_t cols, uint64_t rows) {
  CUtensorMap m;
  cuuint64_t dims[2] = {cols, rows};
  cuuint64_t str[1] = {cols * 2};
  cuuint32_t box[2] = {64, 64};
  cuuint32_t es[2] = {1, 1};
  f(&m, CU_TENSOR_MAP_DATA_TYPE_BFLOAT16, 2, const_cast<void*>(p), dims, str, box, es, CU_TENSOR_MAP_INTERLEAVE_NONE,
    CU_TENSOR_MAP_SWIZZLE_128B, CU_TENSOR_MAP_L2_PROMOTION_NONE, CU_TENSOR_MAP_FLOAT_OOB_FILL_NONE);
  return m;
}

}

extern "C" void kernel_launch(void* const* d_in, const int* in_sizes, int n_in, void* d_out, int out_size) {
  void* fn = nullptr;
  cudaDriverEntryPointQueryResult qr;
  cudaGetDriverEntryPoint("cuTensorMapEncodeTiled", &fn, cudaEnableDefault, &qr);
  EncodeFn enc = (EncodeFn)fn;
  Maps maps;
  maps.m[0] = make_map(enc, d_in[1], 1728, 576); maps.m[1] = make_map(enc, d_in[2], 576, 576);
  maps.m[2] = make_map(enc, d_in[4], 4608, 576); maps.m[3] = make_map(enc, d_in[5], 4608, 576); maps.m[4] = make_map(enc, d_in[6], 576, 4608);
  void* scr = nullptr;
  cudaGetSymbolAddress(&scr, g_scratch);
  cudaFuncSetAttribute(mega_kernel, cudaFuncAttributeMaxDynamicSharedMemorySize, SMEM_BYTES);
  mega_kernel<<<128, 384, SMEM_BYTES>>>(maps, (uint4*)scr, (const __nv_bfloat16*)d_in[0], (const __nv_bfloat16*)d_in[1],
                                        (const __nv_bfloat16*)d_in[2], (__nv_bfloat16*)d_out);
}
```

```cpp
#include <cuda_runtime.h>
#include <cuda.h>
#include <cuda_bf16.h>
#include <stdint.h>

#define TRACE 0
#define FPOS 2
#define W2 0

namespace {

constexpr int NST = 6;
constexpr int STAGE = 16384;
constexpr int PARK = NST * STAGE;
constexpr int REM = PARK + 49152;
constexpr int KVS = REM + 40960;
constexpr int HSTG = KVS + 16384;
constexpr int BARS = KVS + 41472;
constexpr int TRC = BARS + 256;
constexpr int SMEM_BYTES = TRC + (TRACE ? 512 : 0);
static_assert(BARS >= PARK + 131072, "barriers overlap park");
static_assert(SMEM_BYTES <= 232448, "smem");

constexpr int SLAB = 36 * 32;
constexpr int SPIN_MAX = 1 << 17;
constexpr int GD = 3;
constexpr int OFF_S = 0;
constexpr int OFF_H = OFF_S + 3 * 8 * 96;
constexpr int OFF_X = OFF_H + 2 * 8 * 384;
constexpr int OFF_P = OFF_X + 6 * 8 * SLAB;
constexpr int TILE = OFF_P + 8 * 8 * SLAB;
constexpr int OFF_R = 16 * TILE;
constexpr int SCRATCH = OFF_R + 8 * 2304;

}

__device__ uint4 g_scratch[SCRATCH];

namespace {

constexpr uint64_t DESC_HI = 0x4000004000000000ull;
constexpr uint64_t DESC_REM = (576ull << 32) | (8u << 16);
__device__ __forceinline__ void wgmma_rs_n64(float (&d)[32], const uint32_t* a, uint64_t desc, int scale_d) {
  asm volatile("{\n.reg .pred p;\nsetp.ne.b32 p, %37, 0;\n"
    "wgmma.mma_async.sync.aligned.m64n64k16.f32.bf16.bf16 "
    "{%0, %1, %2, %3, %4, %5, %6, %7, %8, %9, %10, %11, %12, %13, %14, %15, %16, %17, %18, %19, %20, %21, %22, %23, %24, %25, %26, %27, %28, %29, %30, %31}, "
    "{%32, %33, %34, %35}, %36, p, 1, 1, 1;\n}\n"
    : "+f"(d[0]), "+f"(d[1]), "+f"(d[2]), "+f"(d[3]), "+f"(d[4]), "+f"(d[5]), "+f"(d[6]), "+f"(d[7]), "+f"(d[8]), "+f"(d[9]), "+f"(d[10]), "+f"(d[11]), "+f"(d[12]), "+f"(d[13]), "+f"(d[14]), "+f"(d[15]), "+f"(d[16]), "+f"(d[17]), "+f"(d[18]), "+f"(d[19]), "+f"(d[20]), "+f"(d[21]), "+f"(d[22]), "+f"(d[23]), "+f"(d[24]), "+f"(d[25]), "+f"(d[26]), "+f"(d[27]), "+f"(d[28]), "+f"(d[29]), "+f"(d[30]), "+f"(d[31])
    : "r"(a[0]), "r"(a[1]), "r"(a[2]), "r"(a[3]), "l"(desc), "r"(scale_d));
}
__device__ __forceinline__ void wgmma_rs_n8(float (&d)[4], const uint32_t* a, uint64_t desc, int scale_d) {
  asm volatile("{\n.reg .pred p;\nsetp.ne.b32 p, %9, 0;\n"
    "wgmma.mma_async.sync.aligned.m64n8k16.f32.bf16.bf16 "
    "{%0, %1, %2, %3}, "
    "{%4, %5, %6, %7}, %8, p, 1, 1, 1;\n}\n"
    : "+f"(d[0]), "+f"(d[1]), "+f"(d[2]), "+f"(d[3])
    : "r"(a[0]), "r"(a[1]), "r"(a[2]), "r"(a[3]), "l"(desc), "r"(scale_d));
}
__device__ __forceinline__ void wgmma_rs_n24(float (&d)[12], const uint32_t* a, uint64_t desc, int scale_d) {
  asm volatile("{\n.reg .pred p;\nsetp.ne.b32 p, %17, 0;\n"
    "wgmma.mma_async.sync.aligned.m64n24k16.f32.bf16.bf16 "
    "{%0, %1, %2, %3, %4, %5, %6, %7, %8, %9, %10, %11}, "
    "{%12, %13, %14, %15}, %16, p, 1, 1, 1;\n}\n"
    : "+f"(d[0]), "+f"(d[1]), "+f"(d[2]), "+f"(d[3]), "+f"(d[4]), "+f"(d[5]), "+f"(d[6]), "+f"(d[7]), "+f"(d[8]), "+f"(d[9]), "+f"(d[10]), "+f"(d[11])
    : "r"(a[0]), "r"(a[1]), "r"(a[2]), "r"(a[3]), "l"(desc), "r"(scale_d));
}

__device__ __forceinline__ void mbar_init(uint32_t a, uint32_t c) { asm volatile("mbarrier.init.shared::cta.b64 [%0], %1;" :: "r"(a), "r"(c)); }
__device__ __forceinline__ void mbar_arrive(uint32_t a) { asm volatile("mbarrier.arrive.shared::cta.b64 _, [%0];" :: "r"(a) : "memory"); }
__device__ __forceinline__ void mbar_wait(uint32_t a, uint32_t ph) {
  asm volatile("{\n.reg .pred p;\n.reg .u32 n;\n"
               "mbarrier.try_wait.parity.shared::cta.b64 p, [%0], %1;\n@p bra D;\n"
               "mov.u32 n, 0;\n"
               "W: mbarrier.try_wait.parity.shared::cta.b64 p, [%0], %1;\n@p bra D;\n"
               "add.u32 n, n, 1;\nsetp.lt.u32 p, n, 4194304;\n@p bra W;\ntrap;\nD:\n}" :: "r"(a), "r"(ph) : "memory");
}
__device__ __forceinline__ void wg_fence() { asm volatile("wgmma.fence.sync.aligned;" ::: "memory"); }
__device__ __forceinline__ void wg_commit() { asm volatile("wgmma.commit_group.sync.aligned;" ::: "memory"); }
template <int N> __device__ __forceinline__ void wg_wait() { asm volatile("wgmma.wait_group.sync.aligned %0;" :: "n"(N) : "memory"); }
__device__ __forceinline__ float tanh_ap(float x) { float y; asm("tanh.approx.f32 %0, %1;" : "=f"(y) : "f"(x)); return y; }
__device__ __forceinline__ float ex2(float x) { float y; asm("ex2.approx.ftz.f32 %0, %1;" : "=f"(y) : "f"(x)); return y; }
__device__ __forceinline__ uint32_t pack_bf16(float lo, float hi) { uint32_t r; asm("cvt.rn.bf16x2.f32 %0, %1, %2;" : "=r"(r) : "f"(hi), "f"(lo)); return r; }
__device__ __forceinline__ float bf_lo(uint32_t v) { return __uint_as_float(v << 16); }
__device__ __forceinline__ float bf_hi(uint32_t v) { return __uint_as_float(v & 0xffff0000u); }
__device__ __forceinline__ uint32_t sub_bf16x2(uint32_t a, uint32_t b) { uint32_t r; asm("sub.rn.bf16x2 %0, %1, %2;" : "=r"(r) : "r"(a), "r"(b)); return r; }
__device__ __forceinline__ uint32_t mul_bf16x2(uint32_t a, uint32_t b) { uint32_t r; asm("mul.rn.bf16x2 %0, %1, %2;" : "=r"(r) : "r"(a), "r"(b)); return r; }
__device__ __forceinline__ uint32_t nz(uint32_t w) { return w == 0u ? 0x8000u : w; }

__device__ __forceinline__ void ldg4(uint32_t* d, const uint4* p) {
  asm volatile("ld.relaxed.gpu.global.v4.b32 {%0,%1,%2,%3}, [%4];" : "=r"(d[0]), "=r"(d[1]), "=r"(d[2]), "=r"(d[3]) : "l"(p) : "memory");
}
__device__ __forceinline__ void ldg2(uint32_t* d, const void* p) {
  asm volatile("ld.relaxed.gpu.global.v2.b32 {%0,%1}, [%2];" : "=r"(d[0]), "=r"(d[1]) : "l"(p) : "memory");
}
__device__ __forceinline__ void stg4(uint4* p, uint32_t a, uint32_t b, uint32_t c, uint32_t d) {
  asm volatile("st.relaxed.gpu.global.v4.b32 [%0], {%1,%2,%3,%4};" :: "l"(p), "r"(a), "r"(b), "r"(c), "r"(d) : "memory");
}
__device__ __forceinline__ void stg2(void* p, uint32_t a, uint32_t b) {
  asm volatile("st.relaxed.gpu.global.v2.b32 [%0], {%1,%2};" :: "l"(p), "r"(a), "r"(b) : "memory");
}
__device__ __forceinline__ void sts4(uint32_t a, const uint32_t* o) { asm volatile("st.shared.v4.b32 [%0], {%1,%2,%3,%4};" :: "r"(a), "r"(o[0]), "r"(o[1]), "r"(o[2]), "r"(o[3]) : "memory"); }
__device__ __forceinline__ void lds4(uint32_t a, uint32_t* o) { asm volatile("ld.shared.v4.b32 {%0,%1,%2,%3}, [%4];" : "=r"(o[0]), "=r"(o[1]), "=r"(o[2]), "=r"(o[3]) : "r"(a) : "memory"); }
__device__ __forceinline__ void lds2(uint32_t a, uint32_t* o) { asm volatile("ld.shared.v2.b32 {%0,%1}, [%2];" : "=r"(o[0]), "=r"(o[1]) : "r"(a) : "memory"); }
__device__ __forceinline__ float rcp(float x) { float y; asm("rcp.approx.ftz.f32 %0, %1;" : "=f"(y) : "f"(x)); return y; }
__device__ __forceinline__ void sts1(uint32_t a, uint32_t v) { asm volatile("st.shared.b32 [%0], %1;" :: "r"(a), "r"(v) : "memory"); }
__device__ __forceinline__ void ldsm4(uint32_t a, uint32_t& r0, uint32_t& r1, uint32_t& r2, uint32_t& r3) {
  asm volatile("ldmatrix.sync.aligned.m8n8.x4.shared.b16 {%0,%1,%2,%3}, [%4];" : "=r"(r0), "=r"(r1), "=r"(r2), "=r"(r3) : "r"(a) : "memory");
}
__device__ __forceinline__ void ldsm4t(uint32_t a, uint32_t& r0, uint32_t& r1, uint32_t& r2, uint32_t& r3) {
  asm volatile("ldmatrix.sync.aligned.m8n8.x4.trans.shared.b16 {%0,%1,%2,%3}, [%4];" : "=r"(r0), "=r"(r1), "=r"(r2), "=r"(r3) : "r"(a) : "memory");
}
__device__ __forceinline__ void mma16(float* c, uint32_t a0, uint32_t a1, uint32_t a2, uint32_t a3, uint32_t b0, uint32_t b1) {
  asm("mma.sync.aligned.m16n8k16.row.col.f32.bf16.bf16.f32 {%0,%1,%2,%3}, {%4,%5,%6,%7}, {%8,%9}, {%0,%1,%2,%3};"
    : "+f"(c[0]), "+f"(c[1]), "+f"(c[2]), "+f"(c[3]) : "r"(a0), "r"(a1), "r"(a2), "r"(a3), "r"(b0), "r"(b1));
}
__device__ __forceinline__ void mma8(float* c, uint32_t a0, uint32_t a1, uint32_t b0) {
  asm("mma.sync.aligned.m16n8k8.row.col.f32.bf16.bf16.f32 {%0,%1,%2,%3}, {%4,%5}, {%6}, {%0,%1,%2,%3};"
    : "+f"(c[0]), "+f"(c[1]), "+f"(c[2]), "+f"(c[3]) : "r"(a0), "r"(a1), "r"(b0));
}
__device__ __forceinline__ uint32_t lane_id() { uint32_t l; asm volatile("mov.u32 %0, %%laneid;" : "=r"(l)); return l; }
__device__ __forceinline__ float quad_sum(float v) { v += __shfl_xor_sync(~0u, v, 1); v += __shfl_xor_sync(~0u, v, 2); return v; }
__device__ __forceinline__ float quad_max(float v) { v = fmaxf(v, __shfl_xor_sync(~0u, v, 1)); v = fmaxf(v, __shfl_xor_sync(~0u, v, 2)); return v; }
template <int N> __device__ __forceinline__ void pin(float (&d)[N]) {
#pragma unroll
  for (int i = 0; i < N; i++) asm volatile("" : "+f"(d[i]) :: "memory");
}
#define SPIN_GUARD(n) if (++(n) > SPIN_MAX) break

template <int NG> __device__ __forceinline__ void publish_stats(uint4* dst, const float* y, uint32_t tag, uint32_t lane) {
  float s0 = 0.f, s1 = 0.f;
#pragma unroll
  for (int g = 0; g < NG; g++) { s0 += y[4 * g] + y[4 * g + 1]; s1 += y[4 * g + 2] + y[4 * g + 3]; }
  s0 = quad_sum(s0); s1 = quad_sum(s1);
  const float m0 = s0 * (1.f / (8 * NG)), m1 = s1 * (1.f / (8 * NG));
  float q0 = 0.f, q1 = 0.f, q2 = 0.f, q3 = 0.f;
#pragma unroll
  for (int g = 0; g < NG; g++) {
    const float a = y[4 * g] - m0, b = y[4 * g + 1] - m0, c = y[4 * g + 2] - m1, d = y[4 * g + 3] - m1;
    q0 = fmaf(a, a, q0); q1 = fmaf(b, b, q1); q2 = fmaf(c, c, q2); q3 = fmaf(d, d, q3);
  }
  q0 = quad_sum(q0 + q1); q2 = quad_sum(q2 + q3);
  if ((lane & 3) == 0)
    stg4(dst + (lane >> 2), (__float_as_uint(s0) & ~1u) | tag, __float_as_uint(q0), __float_as_uint(s1), __float_as_uint(q2));
}

__device__ __forceinline__ void put72(uint4* slab, uint32_t j, uint32_t lane, const uint32_t* v) {
  uint4* p = slab + ((9 * j + 1) >> 1) * 32;
  if (j & 1) {
    stg2((char*)(p - 16) + lane * 8, nz(v[0]), v[1]);
#pragma unroll
    for (int i = 0; i < 4; i++) stg4(p + lane + i * 32, nz(v[4 * i + 2]), v[4 * i + 3], v[4 * i + 4], v[4 * i + 5]);
  } else {
#pragma unroll
    for (int i = 0; i < 4; i++) stg4(p + lane + i * 32, nz(v[4 * i]), v[4 * i + 1], v[4 * i + 2], v[4 * i + 3]);
    stg2((char*)(p + 4 * 32) + lane * 8, nz(v[16]), v[17]);
  }
}
__device__ __forceinline__ void zero_share(uint4* slab, uint32_t j, uint32_t lane) {
  uint4* p = slab + j * 144 + lane;
#pragma unroll
  for (int i = 0; i < 4; i++) stg4(p + i * 32, 0u, 0u, 0u, 0u);
  if (lane < 16) stg4(p + 128, 0u, 0u, 0u, 0u);
}

struct Maps { CUtensorMap m[7]; };

struct Ring {
  uint32_t st, ph;
  __device__ __forceinline__ void next() { if (++st == NST) { st = 0; ph ^= 1; } }
};

#define GSTAMP(i) do {} while (0)
#define STAMP(i) do {} while (0)

__device__ __forceinline__ void tma_box(uint32_t dst, const CUtensorMap* m, int col, int row, uint32_t bar, uint32_t expect) {
  asm volatile("{\n.reg .pred e, h;\nelect.sync _|e, 0xffffffff;\nsetp.ne.and.u32 h, %5, 0, e;\n"
               "@h mbarrier.arrive.expect_tx.shared::cta.b64 _, [%2], %5;\n"
               "@e cp.async.bulk.tensor.2d.shared::cluster.global.mbarrier::complete_tx::bytes [%0], [%1, {%3, %4}], [%2];\n}"
               :: "r"(dst), "l"(m), "r"(bar), "r"(col), "r"(row), "r"(expect) : "memory");
}

__device__ __forceinline__ void bulk_load(uint32_t dst, const void* src, uint32_t bytes, uint32_t bar, bool arm) {
  asm volatile("{\n.reg .pred e, h;\nelect.sync _|e, 0xffffffff;\nsetp.ne.and.u32 h, %4, 0, e;\n"
               "@h mbarrier.arrive.expect_tx.shared::cta.b64 _, [%3], %2;\n"
               "@e cp.async.bulk.shared::cluster.global.mbarrier::complete_tx::bytes [%0], [%1], %2, [%3];\n}"
               :: "r"(dst), "l"(src), "r"(bytes), "r"(bar), "r"((uint32_t)arm) : "memory");
}

__global__ void __launch_bounds__(384, 1) mega_kernel(
    const __grid_constant__ Maps maps, uint4* __restrict__ scratch,
    const __nv_bfloat16* __restrict__ x_in, __nv_bfloat16* __restrict__ out) {
  extern __shared__ __align__(1024) uint8_t smem[];
  const uint32_t sb = (uint32_t)__cvta_generic_to_shared(smem);
  const uint32_t full0 = sb + BARS, empty0 = full0 + 8 * NST, rem_full = empty0 + 8 * NST, park_free = rem_full + 8, kv_free = park_free + 8;
  const uint32_t c8_go = kv_free + 8, c8_done = c8_go + 8, c8_full = c8_done + 8, remo_full = c8_full + 8, pbar0 = remo_full + 8;
  const uint32_t w = __shfl_sync(~0u, threadIdx.x >> 5, 0);
  const uint32_t t = blockIdx.x >> 3, j = blockIdx.x & 7;
  uint4* const scr = scratch + t * TILE;
  {
    const uint32_t lane = lane_id(), r = lane >> 2, q = lane & 3;
    const uint32_t sl = w < 8 ? w : j, ch = w < 8 ? j : 8;
    const uint32_t* xr = (const uint32_t*)(x_in + (128 * t + 32 * (sl >> 1) + 2 * r + (sl & 1)) * 576 + 64 * ch + 2 * q);
    if (w < 8 || w == 9) {
      uint32_t v[16];
#pragma unroll
      for (int g = 0; g < 8; g++) {
        asm volatile("ld.global.nc.b32 %0, [%1];" : "=r"(v[2 * g]) : "l"(xr + 4 * g));
        asm volatile("ld.global.nc.b32 %0, [%1];" : "=r"(v[2 * g + 1]) : "l"(xr + 8 * 576 + 4 * g));
      }
      if (q == 0) {
#pragma unroll
        for (int k = 0; k < 3; k++) stg4(scr + OFF_S + (k * 8 + sl) * 96 + ch * 8 + r, 0u, 0u, 0u, 0u);
      }
      asm volatile("bar.sync 0;" ::: "memory");
      uint4* p = scr + OFF_X + sl * SLAB + 4 * ch * 32 + lane;
#pragma unroll
      for (int i = 0; i < 4; i++) stg4(p + i * 32, nz(v[4 * i]), v[4 * i + 1], nz(v[4 * i + 2]), v[4 * i + 3]);
      float y[32];
#pragma unroll
      for (int i = 0; i < 16; i++) { y[2 * i] = bf_lo(v[i]); y[2 * i + 1] = bf_hi(v[i]); }
      publish_stats<8>(scr + OFF_S + sl * 96 + ch * 8, y, 1u, lane);
    } else {
      if (threadIdx.x == 256) {
        for (int i = 0; i < NST; i++) { mbar_init(full0 + 8 * i, 1); mbar_init(empty0 + 8 * i, 8); }
        mbar_init(rem_full, 1); mbar_init(park_free, 8); mbar_init(kv_free, 8); mbar_init(c8_go, 8); mbar_init(c8_done, 1); mbar_init(c8_full, 1); mbar_init(remo_full, 1);
        for (int i = 0; i < 8; i++) mbar_init(pbar0 + 8 * i, 5);
        asm volatile("fence.mbarrier_init.release.cluster;" ::: "memory");
      }
      __syncwarp();
      asm volatile("bar.sync 0;" ::: "memory");
    }
  }

  if (w >= 8) {
    asm volatile("setmaxnreg.dec.sync.aligned.u32 24;");
    if (w == 8) {
      Ring rg{0, 1};
#pragma unroll 1
      for (int seg = 0; seg < 34; seg++) {
        const int n = seg >= 17 ? seg - 17 : seg;
        int ma, mb, ca, cb, row = 0;
        if (n < 3) { ma = mb = n == 2; ca = 72 * j + (n == 0 ? 576 : 0); cb = ca + 576; }
        else if (n < 12) { ma = 3; mb = 2; ca = cb = 576 * j + 64 * (n - 3); }
        else { ma = mb = 4; ca = n == 12 ? 512 : ((j + 2 * n) & 7) * 64; cb = ((j + 2 * n + 1) & 7) * 64; row = 576 * j; }
        const bool zip = n == 0 || n == 3;
        const int nb = (n == 1 || n == 2 || n == 16) ? 9 : 18;
#pragma unroll 1
        for (int b = 0; b < nb; b++) {
          const bool second = zip ? (b & 1) : b >= 9, last = b == nb - 1;
          const int kb = zip ? b >> 1 : second ? b - 9 : b;
          if (!(b & 1)) mbar_wait(empty0 + rg.st * 8, rg.ph);
          tma_box(sb + rg.st * STAGE + (b & 1) * 8192, &maps.m[second ? mb : ma], second ? cb : ca, row + 64 * kb, full0 + rg.st * 8,
                  (b & 1) ? 0 : last ? STAGE / 2 : STAGE);
          if ((b & 1) || last) rg.next();
          if (seg == 0 && b == 2 * NST - 1) asm volatile("bar.arrive 3, 64;" ::: "memory");
        }
      }
    } else if (w == 9) {
      const uint32_t lane = lane_id();
      const uint32_t stg = sb + HSTG + lane * 16;
      uint32_t fph = 0;
#pragma unroll 1
      for (uint32_t layer = 0; layer < 2; layer++) {
        uint4* xb = scr + OFF_X + ((4 + layer) * 8 + j) * SLAB + 32 * 32;
        mbar_wait(c8_go, layer);
        int n = 0;
        while (true) {
          if (lane == 0) asm volatile("mbarrier.arrive.expect_tx.shared::cta.b64 _, [%0], 18432;" :: "r"(c8_full) : "memory");
          __syncwarp();
#pragma unroll 1
          for (uint32_t s = 0; s < 9; s++)
            bulk_load(sb + HSTG + s * 2048, s < 8 ? scr + OFF_P + (j + s * 8) * SLAB + 32 * 32 : xb, 2048, c8_full, false);
          mbar_wait(c8_full, fph); fph ^= 1;
          uint32_t bad = 0;
#pragma unroll 8
          for (int s = 0; s < 32; s++) { uint32_t v; asm volatile("ld.shared.b32 %0, [%1];" : "=r"(v) : "r"(stg + s * 512) : "memory"); bad |= v ^ (1 - layer); }
          if (__all_sync(~0u, (bad & 1u) == 0u)) break;
          __nanosleep(300);
          SPIN_GUARD(n);
        }
        float s0 = 0.f, s1 = 0.f;
#pragma unroll 1
        for (int g = 0; g < 8; g++) {
          const uint32_t a = stg + (g >> 1) * 512 + (g & 1) * 8;
          float a0 = 0.f, a1 = 0.f, a2 = 0.f, a3 = 0.f;
#pragma unroll 1
          for (int b = 0; b < 3; b++) {
            uint32_t v[6];
#pragma unroll
            for (int s = 0; s < 3; s++) lds2(a + (3 * b + s) * 2048, v + 2 * s);
#pragma unroll
            for (int s = 0; s < 3; s++) { a0 += bf_lo(v[2 * s]); a1 += bf_hi(v[2 * s]); a2 += bf_lo(v[2 * s + 1]); a3 += bf_hi(v[2 * s + 1]); }
          }
          sts1(a + 18432, pack_bf16(a0, a1)); sts1(a + 18436, pack_bf16(a2, a3));
          s0 += a0 + a1; s1 += a2 + a3;
        }
        __syncwarp();
        if (lane == 0) mbar_arrive(c8_done);
        s0 = quad_sum(s0); s1 = quad_sum(s1);
        float q0 = 0.f, q1 = 0.f;
        const uint32_t ln = lane_id();
#pragma unroll 1
        for (uint32_t i = 0; i < 4; i++) {
          uint32_t x[4];
          lds4(stg + 18432 + i * 512, x);
          stg4(xb + i * 32 + ln, 0u, 0u, 0u, 0u);
          if (layer == 0) {
            stg4(xb - 3 * 8 * SLAB + i * 32 + ln, nz(x[0]), x[1], x[2], x[3]);
#pragma unroll
            for (int e = 0; e < 4; e++) {
              const float m = (e & 1) ? s1 : s0, c = fmaf(m, -1.f / 64, bf_lo(x[e])), d = fmaf(m, -1.f / 64, bf_hi(x[e]));
              if (e & 1) q1 = fmaf(c, c, fmaf(d, d, q1)); else q0 = fmaf(c, c, fmaf(d, d, q0));
            }
          } else {
            uint32_t* o = (uint32_t*)(out + (128 * t + 32 * (j >> 1) + 2 * (ln >> 2) + (j & 1)) * 576 + 512 + 16 * i + 2 * (ln & 3));
            o[0] = x[0]; o[8 * 576] = x[1]; o[4] = x[2]; o[8 * 576 + 4] = x[3];
          }
        }
        if (layer == 0) {
          q0 = quad_sum(q0); q1 = quad_sum(q1);
          if ((ln & 3) == 0) stg4(scr + OFF_S + j * 96 + 64 + (ln >> 2), __float_as_uint(s0) & ~1u, __float_as_uint(q0), __float_as_uint(s1), __float_as_uint(q1));
        }
      }
    } else {
      const uint32_t lane = lane_id(), r = lane >> 2, q = lane & 3;
#pragma unroll 1
      for (uint32_t layer = 0; layer < 2; layer++) {
        if (w == 10) {
          if (layer == 0) {
            asm volatile("bar.sync 3, 64;" ::: "memory");
#pragma unroll 1
            for (uint32_t b = 0; b < 9; b++)
              tma_box(sb + REM + b * 3072, &maps.m[5], 72 * j + 64 + (b < 6 ? 576 * (b / 3 + 1) : 0), 192 * (b % 3), rem_full, b ? 0 : 27648);
          } else {
            mbar_wait(park_free, 0);
            asm volatile("cp.async.bulk.wait_group 0;" ::: "memory");
            bulk_load(sb + REM, scratch + OFF_R + j * 2304, 27648, rem_full, true);
            bulk_load(sb + REM + 27648, scratch + OFF_R + j * 2304 + 1728, 9216, remo_full, true);
          }
        }
        if (layer) mbar_wait(kv_free, 0);
        if (t > 0) {
#pragma unroll 1
          for (uint32_t pc = 0; pc < 3; pc++) {
            uint4* hp = scr + OFF_H + ((layer * 8 + j) * 2 + (w - 10)) * 192 + pc * 64 + lane;
            uint32_t hl[8];
            int n = 0;
            hl[4] = 1u;
            while (true) {
              ldg4(hl, hp);
              if (pc < 2) ldg4(hl + 4, hp + 32);
              if (__all_sync(~0u, hl[0] != 0u && hl[4] != 0u)) break;
              __nanosleep(100);
              SPIN_GUARD(n);
            }
            const uint32_t dst = sb + KVS + (w - 10) * 10368 + r * 144 + q * 4;
            if (pc < 2) {
#pragma unroll
              for (int g = 0; g < 8; g++) sts1(dst + pc * 20736 + g * 16, hl[g]);
              stg4(hp + 32, 0u, 0u, 0u, 0u);
            } else {
              sts1(dst + 128, hl[0]); sts1(dst + 20736 + 128, hl[1]);
            }
            stg4(hp, 0u, 0u, 0u, 0u);
          }
        }
        asm volatile("bar.arrive 1, 192;" ::: "memory");
        if (w == 10 && layer == 0) {
          mbar_wait(rem_full, 0);
#pragma unroll 1
          for (uint32_t b = 0; b < 3; b++) tma_box(sb + REM + 27648 + b * 3072, &maps.m[6], 72 * j + 64, 192 * b, remo_full, b ? 0 : 9216);
          mbar_wait(remo_full, 0);
          asm volatile("{\n.reg .pred e;\nelect.sync _|e, 0xffffffff;\n@e cp.async.bulk.global.shared::cta.bulk_group [%0], [%1], 36864;\n}\n"
                       "cp.async.bulk.commit_group;" :: "l"(scratch + OFF_R + j * 2304), "r"(sb + REM) : "memory");
        }
      }
    }
  } else {
    asm volatile("setmaxnreg.inc.sync.aligned.u32 240;");
    const uint32_t lane = lane_id(), r = lane >> 2, q = lane & 3;
    Ring rg{0, 0};
    uint32_t prev = 0;
    uint32_t X[144];
    float rs0, rs1;
    uint32_t mean0, mean1;
    auto release = [&](uint32_t st) { if (lane == 0) mbar_arrive(empty0 + st * 8); };
    auto load_kb = [&](int kb, const uint4* src, const char* lo, uint32_t hoff) {
#pragma unroll
      for (int k = 4 * kb; k < 4 * kb + 4; k++) {
        if (k % 9 == 4) { ldg2(X + 4 * k, lo + k * 512); ldg2(X + 4 * k + 2, lo + hoff + k * 512); }
        else ldg4(X + 4 * k, src + k * 32);
      }
    };
    auto next_kb = [&](bool center, int kb, const uint4* src, const char* lo, uint32_t hoff) {
      int n = 0;
      while (true) {
        bool ok = true;
#pragma unroll
        for (int k = 4 * kb; k < 4 * kb + 4; k++) { ok = ok && X[4 * k] != 0u; if (k % 9 == 4) ok = ok && X[4 * k + 2] != 0u; }
        if (__all_sync(~0u, ok)) break;
        SPIN_GUARD(n);
        load_kb(kb, src, lo, hoff);
      }
      if (kb + GD < 9) load_kb(kb + GD, src, lo, hoff);
      if (center) {
#pragma unroll
        for (int i = 16 * kb; i < 16 * kb + 16; i++) X[i] = sub_bf16x2(X[i], (i & 1) ? mean1 : mean0);
      }
    };
#pragma unroll 1
    for (uint32_t hf = 0; hf < 4; hf++) {
      const uint32_t layer = hf >> 1;
      const bool ffn = hf & 1;
      const uint32_t tag = 1 - layer;
      uint4* const xbase = scr + OFF_X + (layer * 8 + w) * SLAB;
      float aA[32], aB[32];
      {
        const uint4* src = xbase + (ffn ? 32 * SLAB : 0) + lane;
        const char* lo = (const char*)src - (ffn ? lane * 8 : 0);
        const uint32_t hoff = ffn ? 256 : 8;
        uint32_t s[3][4];
        const uint4* p = scr + OFF_S + ((ffn ? 16 : 0) + w) * 96 + q * 8 + r;
        const bool third = !ffn && q == 0;
        int n = 0;
        s[2][0] = tag; s[2][1] = s[2][2] = s[2][3] = 0u;
        STAMP(ffn * 16 + 0);
        while (true) {
          ldg4(s[0], p); ldg4(s[1], p + 32);
          if (third) ldg4(s[2], p + 64);
          if (__all_sync(~0u, ((s[0][0] ^ tag) | (s[1][0] ^ tag) | (s[2][0] ^ tag)) % 2u == 0u)) break;
          SPIN_GUARD(n);
        }
        STAMP(ffn * 16 + 1);
        GSTAMP(14 + ffn);
#pragma unroll
        for (int kb = 0; kb < GD; kb++) load_kb(kb, src, lo, hoff);
        float t0 = 0.f, t1 = 0.f;
#pragma unroll
        for (int i = 0; i < 3; i++) { t0 += __uint_as_float(s[i][0]); t1 += __uint_as_float(s[i][2]); }
        const float m0 = quad_sum(t0) * (1.f / 576), m1 = quad_sum(t1) * (1.f / 576);
        const float cnt = ffn ? 72.f : 64.f, inv = ffn ? 1.f / 72 : 1.f / 64;
        float v0 = 0.f, v1 = 0.f;
#pragma unroll
        for (int i = 0; i < 3; i++) {
          const float c = (i < 2 || third) ? cnt : 0.f;
          const float d0 = fmaf(__uint_as_float(s[i][0]), inv, -m0), d1 = fmaf(__uint_as_float(s[i][2]), inv, -m1);
          v0 += fmaf(d0 * d0, c, __uint_as_float(s[i][1])); v1 += fmaf(d1 * d1, c, __uint_as_float(s[i][3]));
        }
        rs0 = rsqrtf(fmaf(quad_sum(v0), 1.f / 576, 1e-5f)); rs1 = rsqrtf(fmaf(quad_sum(v1), 1.f / 576, 1e-5f));
        mean0 = pack_bf16(m0, m0); mean1 = pack_bf16(m1, m1);
#pragma unroll
        for (int kb = 0; kb < 9; kb++) {
          next_kb(true, kb, src, lo, hoff);
          mbar_wait(full0 + rg.st * 8, rg.ph);
          const uint64_t desc = DESC_HI | ((sb + rg.st * STAGE) >> 4);
          wg_fence();
#pragma unroll
          for (int i = 0; i < 4; i++) wgmma_rs_n64(aA, X + 4 * (4 * kb + i), desc + i * 128, kb + i != 0);
#pragma unroll
          for (int i = 0; i < 4; i++) wgmma_rs_n64(aB, X + 4 * (4 * kb + i), desc + 512 + i * 128, kb + i != 0);
          wg_commit();
          wg_wait<1>();
          if (kb > 0) release(prev);
          prev = rg.st; rg.next();
        }
        wg_wait<0>();
        STAMP(ffn * 16 + 2);
      }
      if (!ffn) {
      release(prev);
      const uint32_t kvrow = sb + KVS + (w & 1) * 10368 + (16 * (w >> 1)) * 144;
      uint32_t Q[18];
      {
        const uint32_t dst = kvrow + (8 + r) * 144 + q * 4;
        const bool edge_out = w >= 6 && t < 15;
        uint4* const hp = scr + TILE + OFF_H + ((layer * 8 + j) * 2 + (w & 1)) * 192 + lane;
        auto put_kv = [&](float (&a)[32], int part) {
          pin(a);
          uint32_t hl[8];
#pragma unroll
          for (int g = 0; g < 8; g++) {
            hl[g] = pack_bf16(a[4 * g + 2] * rs1, a[4 * g + 3] * rs1);
            sts1(dst + part * 20736 + g * 16, pack_bf16(a[4 * g] * rs0, a[4 * g + 1] * rs0)); sts1(dst + part * 20736 + 8 * 144 + g * 16, hl[g]);
          }
          if (edge_out) { stg4(hp + part * 64, nz(hl[0]), hl[1], hl[2], hl[3]); stg4(hp + part * 64 + 32, nz(hl[4]), hl[5], hl[6], hl[7]); }
        };
        put_kv(aA, 0);
        float aR[12];
        mbar_wait(rem_full, layer);
        const uint64_t dr = DESC_REM | ((sb + REM) >> 4);
        wg_fence();
#pragma unroll
        for (int s = 0; s < 36; s++) {
          wgmma_rs_n24(aR, X + 4 * s, dr + s * 16, s != 0);
          if (s == 4) put_kv(aB, 1);
        }
        wg_commit();
#pragma unroll
        for (int kb = 0; kb < 9; kb++) {
          if (!(kb & 1)) mbar_wait(full0 + rg.st * 8, rg.ph);
          const uint64_t desc = DESC_HI | ((sb + rg.st * STAGE + (kb & 1) * 8192) >> 4);
          wg_fence();
#pragma unroll
          for (int i = 0; i < 4; i++) wgmma_rs_n64(aB, X + 4 * (4 * kb + i), desc + i * 128, kb + i != 0);
          wg_commit();
          wg_wait<1>();
          if (kb > 0 && !(kb & 1)) release(prev);
          if ((kb & 1) || kb == 8) { prev = rg.st; rg.next(); }
          if (kb == 0) {
            pin(aR);
            const uint32_t k1 = pack_bf16(aR[2] * rs1, aR[3] * rs1), v1 = pack_bf16(aR[6] * rs1, aR[7] * rs1);
            if (edge_out) stg4(hp + 128, nz(k1), v1, 0u, 0u);
            sts1(dst + 128, pack_bf16(aR[0] * rs0, aR[1] * rs0)); sts1(dst + 8 * 144 + 128, k1);
            sts1(dst + 20736 + 128, pack_bf16(aR[4] * rs0, aR[5] * rs0)); sts1(dst + 20736 + 8 * 144 + 128, v1);
            Q[16] = pack_bf16(aR[8] * rs0, aR[9] * rs0); Q[17] = pack_bf16(aR[10] * rs1, aR[11] * rs1);
            if (w < 4) asm volatile("bar.arrive 2, 256;" ::: "memory");
          }
        }
        wg_wait<0>();
        release(prev);
        pin(aB);
        STAMP(3);
#pragma unroll
        for (int g = 0; g < 8; g++) {
          Q[2 * g] = pack_bf16(aB[4 * g] * rs0, aB[4 * g + 1] * rs0); Q[2 * g + 1] = pack_bf16(aB[4 * g + 2] * rs1, aB[4 * g + 3] * rs1);
        }
      }
      if (w < 4) asm volatile("bar.sync 1, 192;" ::: "memory");
      else asm volatile("bar.sync 2, 256;" ::: "memory");
      STAMP(4);
      uint32_t O[18];
      {
        const bool edge = (t == 0 && w < 2);
        uint32_t row[3];
#pragma unroll
        for (int nt = 0; nt < 3; nt++) row[nt] = kvrow + (8 * nt + (lane & 7)) * 144;
        if (edge) row[0] = sb + KVS + 8 * 144;
        const uint32_t rlast = ((lane >> 3) == 0 ? row[0] : (lane >> 3) == 1 ? row[1] : row[2]) + 128;
        uint32_t K[3][9], V[3][9], dummy;
#pragma unroll
        for (int nt = 0; nt < 3; nt++) {
          ldsm4(row[nt] + (lane >> 3) * 16, K[nt][0], K[nt][1], K[nt][2], K[nt][3]);
          ldsm4(row[nt] + 64 + (lane >> 3) * 16, K[nt][4], K[nt][5], K[nt][6], K[nt][7]);
        }
        ldsm4(rlast, K[0][8], K[1][8], K[2][8], dummy);
#pragma unroll
        for (int nt = 0; nt < 3; nt++) {
          ldsm4t(row[nt] + 20736 + (lane >> 3) * 16, V[nt][0], V[nt][1], V[nt][2], V[nt][3]);
          ldsm4t(row[nt] + 20736 + 64 + (lane >> 3) * 16, V[nt][4], V[nt][5], V[nt][6], V[nt][7]);
        }
        ldsm4t(rlast + 20736, V[0][8], V[1][8], V[2][8], dummy);
        const bool up0 = 2 * q > r, up1 = 2 * q + 1 > r;
        const float sc = 0.23570226039551584f * 1.4426950408889634f;
        const float neg = -1e9f * 1.4426950408889634f;
        float Of[9][4];
#pragma unroll
        for (int h = 0; h < 4; h++) {
          const uint32_t a0 = q >= h ? Q[4 * h] : 0u, a1 = q >= h ? Q[4 * h + 1] : 0u;
          const uint32_t a4 = q <= h ? Q[4 * h + 4] : 0u, a5 = q <= h ? Q[4 * h + 5] : 0u;
          float S[3][4];
#pragma unroll
          for (int nt = 0; nt < 3; nt++) {
            S[nt][0] = S[nt][1] = S[nt][2] = S[nt][3] = 0.f;
            mma16(S[nt], a0, a1, Q[4 * h + 2], Q[4 * h + 3], K[nt][2 * h], K[nt][2 * h + 1]);
            mma8(S[nt], a4, a5, K[nt][2 * h + 2]);
          }
          float s00 = (up0 ? S[0][0] : S[1][0]) * sc, s01 = (up1 ? S[0][1] : S[1][1]) * sc;
          const float s10 = (up0 ? S[1][2] : S[2][2]) * sc, s11 = (up1 ? S[1][3] : S[2][3]) * sc;
          if (edge && up0) s00 = neg;
          if (edge && up1) s01 = neg;
          const float m0 = quad_max(fmaxf(s00, s01)), m1 = quad_max(fmaxf(s10, s11));
          float p00 = ex2(s00 - m0), p01 = ex2(s01 - m0), p10 = ex2(s10 - m1), p11 = ex2(s11 - m1);
          const float i0 = rcp(quad_sum(p00 + p01)), i1 = rcp(quad_sum(p10 + p11));
          p00 *= i0; p01 *= i0; p10 *= i1; p11 *= i1;
          const uint32_t pa = pack_bf16(up0 ? p00 : 0.f, up1 ? p01 : 0.f), pb = pack_bf16(up0 ? 0.f : p00, up1 ? 0.f : p01);
          const uint32_t pc = pack_bf16(up0 ? p10 : 0.f, up1 ? p11 : 0.f), pd = pack_bf16(up0 ? 0.f : p10, up1 ? 0.f : p11);
#pragma unroll
          for (int gi = 0; gi < 3; gi++) {
            const int g = 2 * h + gi;
            float o[4] = {0.f, 0.f, 0.f, 0.f};
            mma16(o, pa, 0u, pb, pc, V[0][g], V[1][g]);
            mma8(o, 0u, pd, V[2][g]);
#pragma unroll
            for (int e = 0; e < 4; e++) Of[g][e] = (gi == 0 && h > 0 && q < h) ? Of[g][e] : o[e];
          }
        }
#pragma unroll
        for (int g = 0; g < 9; g++) { O[2 * g] = pack_bf16(Of[g][0], Of[g][1]); O[2 * g + 1] = pack_bf16(Of[g][2], Of[g][3]); }
      }
      put72(xbase + 16 * SLAB, j, lane, O);
      if (q == 0) stg4(scr + OFF_S + (8 + w) * 96 + j * 8 + r, tag, 0u, 0u, 0u);
      {
        uint32_t res[18];
        const char* p = (const char*)(xbase + lane) + ((9 * j) >> 1) * 512 + (j & 1) * 8;
#pragma unroll
        for (int g = 0; g < 9; g++) ldg2(res + 2 * g, p + (g >> 1) * 512 + ((g & 1) ? ((j & 1) ? 504 : 8) : 0));
        const uint4* src = xbase + 16 * SLAB + lane;
        {
          const uint4* fp = scr + OFF_S + (8 + w) * 96 + q * 8 + r;
          uint32_t s0[4], s1[4];
          int n = 0;
          STAMP(8);
          while (true) {
            ldg4(s0, fp); ldg4(s1, fp + 32);
            if (__all_sync(~0u, ((s0[0] ^ tag) | (s1[0] ^ tag)) % 2u == 0u)) break;
            SPIN_GUARD(n);
          }
          STAMP(9);
        }
#pragma unroll
        for (int kb = 0; kb < GD; kb++) load_kb(kb, src, (const char*)src - lane * 8, 256);
        float aR[4];
        const uint64_t dr = DESC_REM | ((sb + REM + 27648) >> 4);
        mbar_wait(remo_full, layer);
#pragma unroll
        for (int kb = 0; kb < 9; kb++) {
          next_kb(false, kb, src, (const char*)src - lane * 8, 256);
          if (!(kb & 1)) mbar_wait(full0 + rg.st * 8, rg.ph);
          const uint64_t desc = DESC_HI | ((sb + rg.st * STAGE + (kb & 1) * 8192) >> 4);
          wg_fence();
#pragma unroll
          for (int i = 0; i < 4; i++) wgmma_rs_n8(aR, X + 4 * (4 * kb + i), dr + (4 * kb + i) * 16, kb + i != 0);
#pragma unroll
          for (int i = 0; i < 4; i++) wgmma_rs_n64(aA, X + 4 * (4 * kb + i), desc + i * 128, kb + i != 0);
          wg_commit();
          wg_wait<1>();
          if (kb > 0 && !(kb & 1)) release(prev);
          if ((kb & 1) || kb == 8) { prev = rg.st; rg.next(); }
        }
        wg_wait<0>();
        release(prev);
        pin(aA); pin(aR);
        STAMP(10);
        float acc[36];
#pragma unroll
        for (int i = 0; i < 36; i++) acc[i] = i < 32 ? aA[i] : aR[i - 32];
#pragma unroll
        for (int i = 0; i < 18; i++) {
          acc[2 * i] += bf_lo(res[i]); acc[2 * i + 1] += bf_hi(res[i]);
          res[i] = pack_bf16(acc[2 * i], acc[2 * i + 1]);
        }
        put72(xbase + 32 * SLAB, j, lane, res);
        publish_stats<9>(scr + OFF_S + (16 + w) * 96 + j * 8, acc, tag, lane);
      }
      continue;
      }
      const uint32_t hp = sb + PARK + w * 512 + lane * 16;
      auto pack8 = [&](float (&a)[32], int p, uint32_t* o) {
#pragma unroll
        for (int e = 0; e < 8; e++) asm volatile("" : "+f"(a[8 * p + e]) :: "memory");
#pragma unroll
        for (int e = 0; e < 4; e++) o[e] = pack_bf16(a[8 * p + 2 * e], a[8 * p + 2 * e + 1]);
      };
      const float ka0 = 0.7978845608028654f * rs0, kb0 = 0.044715f * ka0 * rs0 * rs0, ku0 = 0.5f * rs0 * rs0;
      const float ka1 = 0.7978845608028654f * rs1, kb1 = 0.044715f * ka1 * rs1 * rs1, ku1 = 0.5f * rs1 * rs1;
      auto packu8 = [&](int p, uint32_t* o) {
#pragma unroll
        for (int e = 0; e < 8; e++) asm volatile("" : "+f"(aA[8 * p + e]) :: "memory");
#pragma unroll
        for (int e = 0; e < 4; e++) o[e] = pack_bf16(aA[8 * p + 2 * e] * ((e & 1) ? ku1 : ku0), aA[8 * p + 2 * e + 1] * ((e & 1) ? ku1 : ku0));
      };
      auto geglu8 = [&](int p, uint32_t* u) {
#pragma unroll
        for (int e = 0; e < 8; e++) asm volatile("" : "+f"(aB[8 * p + e]) :: "memory");
        float h[8];
#pragma unroll
        for (int e = 0; e < 8; e++) {
          const float g = aB[8 * p + e];
          h[e] = fmaf(g, tanh_ap(g * fmaf(g * g, (e & 2) ? kb1 : kb0, (e & 2) ? ka1 : ka0)), g);
        }
#pragma unroll
        for (int e = 0; e < 4; e++) u[e] = mul_bf16x2(pack_bf16(h[2 * e], h[2 * e + 1]), u[e]);
      };
      auto box = [&](int b, auto&& filler) {
        const int kb = b < 9 ? b : b - 9;
        if (!(b & 1)) mbar_wait(full0 + rg.st * 8, rg.ph);
        const uint64_t desc = DESC_HI | ((sb + rg.st * STAGE + (b & 1) * 8192) >> 4);
        wg_fence();
#pragma unroll
        for (int i = 0; i < 4; i++) {
          if (b < 9) wgmma_rs_n64(aA, X + 4 * (4 * kb + i), desc + i * 128, kb + i != 0);
          else wgmma_rs_n64(aB, X + 4 * (4 * kb + i), desc + i * 128, kb + i != 0);
          if (i == FPOS) filler();
        }
        wg_commit();
        if (b & 1) { if (W2) wg_wait<1>(); prev = rg.st; rg.next(); } else { wg_wait<1>(); release(prev); }
      };
      auto nop = [] {};
      auto step = [&](int st, auto&& filler) { box(2 * st, nop); box(2 * st + 1, filler); };
#pragma unroll
      for (int p = 0; p < 4; p++) { uint32_t o[4]; packu8(p, o); sts4(hp + p * 4096, o); }
      box(0, nop);
      zero_share(xbase, j, lane);
      zero_share(xbase + 16 * SLAB, j, lane);
#pragma unroll 1
      for (int c = 1;; c++) {
        const uint32_t hc = hp + c * 4 * 4096;
#pragma unroll
        for (int b = 1; b < 18; b++) box(b, [&] {
          if ((b & 1) && b < 8) { uint32_t o[4]; const uint32_t a = hc - (4 - (b >> 1)) * 4096; lds4(a, o); geglu8(b >> 1, o); sts4(a, o); }
          if ((b & 1) && b > 10) { uint32_t o[4]; packu8((b - 11) >> 1, o); if (c < 8) sts4(hc + ((b - 11) >> 1) * 4096, o); } });
        if (c == 8) break;
        box(0, nop);
      }
      wg_wait<0>();
      STAMP(21);
      GSTAMP(19);
#pragma unroll
      for (int s = 0; s < 32; s++) lds4(hp + s * 4096, X + 4 * s);
#pragma unroll
      for (int p = 0; p < 4; p++) packu8(p, X + 128 + 4 * p);
#pragma unroll
      for (int st = 0; st < 4; st++) step(st, [&] { geglu8(st, X + 128 + 4 * st); });
      STAMP(24);
      if (layer == 0 && lane == 0) mbar_arrive(park_free);
      const uint32_t lane2 = lane_id();
      uint4* const pw = scr + OFF_P + (j * 8 + w) * SLAB + lane2;
      const uint4* const pr = scr + OFF_P + w * SLAB + 4 * j * 32 + lane2;
      auto put_part = [&](float (&a)[32], int p, uint32_t chunk) {
        uint32_t o[4];
        pack8(a, p, o);
        stg4(pw + (chunk * 4 + p) * 32, (o[0] & ~1u) | tag, o[1], o[2], o[3]);
      };
      auto slot = [&](int p) { return sb + w * 2048 + (p < 4 ? PARK + (p - 1) * 16384 : KVS + (p - 4) * 16384); };
      auto fetch = [&](int p) {
        if (p > 0) bulk_load(slot(p), scr + OFF_P + (((j - p) & 7) * 8 + w) * SLAB + 4 * j * 32, 2048, pbar0 + w * 8, true);
      };
      uint4* const xb = xbase + 32 * SLAB + 4 * j * 32;
#pragma unroll 1
      for (int sp = 0;; sp++) {
        const uint32_t ca = sp == 0 ? 8 : ((j + 2 * sp) & 7), cb = (j + 2 * sp + 1) & 7;
        if (sp == 1 && lane == 0) mbar_arrive(c8_go);
#pragma unroll
        for (int st = 4; st < 9; st++) step(st, [&] {
          if (st == 5 || st == 6) { put_part(aA, 2 * (st - 5), ca); put_part(aA, 2 * (st - 5) + 1, ca); }
          if (st == 8) { if (sp == 3) mbar_wait(c8_done, layer); fetch(2 * sp - 1); } });
        STAMP(25 + sp);
        if (sp == 3) break;
        if (sp == 2 && layer == 0 && (lane2 & 3) == 0) {
#pragma unroll
          for (int k = 0; k < 3; k++) stg4(scr + OFF_S + (k * 8 + w) * 96 + j * 8 + (lane2 >> 2), 1u, 0u, 0u, 0u);
        }
        if (sp == 2) asm volatile("{\n.reg .pred e;\nelect.sync _|e, 0xffffffff;\n@e cp.async.bulk.prefetch.L2.global [%0], 2048;\n}" :: "l"(xb) : "memory");
#pragma unroll
        for (int st = 0; st < 4; st++) step(st, [&] {
          if (st < 2) { put_part(aB, 2 * st, cb); put_part(aB, 2 * st + 1, cb); }
          if (st == 3) fetch(2 * sp); });
      }
      auto load_p = [&](int p, uint32_t* d) {
#pragma unroll
        for (int i = 0; i < 4; i++) ldg4(d + 4 * i, pr + ((j - p) & 7) * 8 * SLAB + i * 32);
      };
#pragma unroll
      for (int st = 0; st < 4; st++) step(st, [&] {
        if (st == 0) {
#pragma unroll
          for (int p = 0; p < 4; p++) put_part(aB, p, (j + 7) & 7);
        }
        if (st == 1) {
#pragma unroll
          for (int i = 0; i < 4; i++) {
            const bool split = j == 2 * i + 1;
            const char* l = (const char*)(xb + i * 32) + (split ? lane2 * 8 : lane2 * 16);
            ldg2(X + 4 * i, l); ldg2(X + 4 * i + 2, l + (split ? 256 : 8));
          }
          load_p(6, X + 16);
        }
        if (st == 3) load_p(7, X + 32); });
      STAMP(13);
      {
        mbar_wait(full0 + rg.st * 8, rg.ph);
        const uint64_t desc = DESC_HI | ((sb + rg.st * STAGE) >> 4);
        wg_fence();
#pragma unroll
        for (int i = 0; i < 4; i++) wgmma_rs_n64(aA, X + 4 * (32 + i), desc + i * 128, 1);
        wg_commit();
        wg_wait<1>(); release(prev);
        prev = rg.st; rg.next();
        mbar_wait(pbar0 + w * 8, layer);
        wg_wait<0>(); release(prev);
        pin(aA);
      }
      STAMP(22);
      GSTAMP(20);
      {
        const uint32_t eye = r == 2 * q ? 0x3f80u : r == 2 * q + 1 ? 0x3f800000u : 0u;
        auto add_p = [&](int p, uint32_t* d) {
          int n = 0;
          while (!__all_sync(~0u, (((d[0] ^ tag) | (d[4] ^ tag) | (d[8] ^ tag) | (d[12] ^ tag)) & 1u) == 0u)) { SPIN_GUARD(n); load_p(p, d); }
#pragma unroll
          for (int g = 0; g < 8; g++) mma8(aA + 4 * g, d[2 * g], d[2 * g + 1], eye);
        };
#pragma unroll
        for (int p = 1; p < 6; p++)
#pragma unroll
          for (int i = 0; i < 4; i++) lds4(slot(p) + lane2 * 16 + i * 512, X + 32 + 16 * p + 4 * i);
#pragma unroll
        for (int g = 0; g < 8; g++) mma8(aA + 4 * g, X[2 * g], X[2 * g + 1], eye);
#pragma unroll
        for (int p = 1; p < 6; p++) add_p(p, X + 32 + 16 * p);
        add_p(6, X + 16);
        STAMP(11);
        add_p(7, X + 32);
        STAMP(12);
        uint32_t res[16];
#pragma unroll
        for (int i = 0; i < 16; i++) res[i] = pack_bf16(aA[2 * i], aA[2 * i + 1]);
        if (layer == 0) {
          uint4* p = xbase + 8 * SLAB + 4 * j * 32 + lane;
#pragma unroll
          for (int i = 0; i < 4; i++) stg4(p + i * 32, nz(res[4 * i]), res[4 * i + 1], nz(res[4 * i + 2]), res[4 * i + 3]);
          publish_stats<8>(scr + OFF_S + w * 96 + j * 8, aA, 0u, lane);
          if (lane == 0) mbar_arrive(kv_free);
        } else {
          uint32_t* o = (uint32_t*)(out + (128 * t + 32 * (w >> 1) + 2 * r + (w & 1)) * 576 + 64 * j + 2 * q);
#pragma unroll
          for (int g = 0; g < 8; g++) { o[4 * g] = res[2 * g]; o[8 * 576 + 4 * g] = res[2 * g + 1]; }
        }
#pragma unroll
        for (int i = 0; i < 4; i++) stg4(xb + lane + i * 32, 0u, 0u, 0u, 0u);
      }
      STAMP(23);
    }
  }
}

typedef CUresult (*EncodeFn)(CUtensorMap*, CUtensorMapDataType, cuuint32_t, void*, const cuuint64_t*, const cuuint64_t*,
                             const cuuint32_t*, const cuuint32_t*, CUtensorMapInterleave, CUtensorMapSwizzle,
                             CUtensorMapL2promotion, CUtensorMapFloatOOBfill);

CUtensorMap make_map(EncodeFn f, const void* p, uint64_t cols, uint64_t rows, bool rem = false) {
  CUtensorMap m;
  cuuint64_t dims[2] = {cols, rows};
  cuuint64_t str[1] = {cols * 2};
  cuuint32_t box[2] = {rem ? 8u : 64u, rem ? 192u : 64u};
  cuuint32_t es[2] = {1, 1};
  f(&m, CU_TENSOR_MAP_DATA_TYPE_BFLOAT16, 2, const_cast<void*>(p), dims, str, box, es, CU_TENSOR_MAP_INTERLEAVE_NONE,
    rem ? CU_TENSOR_MAP_SWIZZLE_NONE : CU_TENSOR_MAP_SWIZZLE_128B, CU_TENSOR_MAP_L2_PROMOTION_NONE, CU_TENSOR_MAP_FLOAT_OOB_FILL_NONE);
  return m;
}

}

extern "C" void kernel_launch(void* const* d_in, const int* in_sizes, int n_in, void* d_out, int out_size) {
  void* fn = nullptr;
  cudaDriverEntryPointQueryResult qr;
  cudaGetDriverEntryPoint("cuTensorMapEncodeTiled", &fn, cudaEnableDefault, &qr);
  EncodeFn enc = (EncodeFn)fn;
  Maps maps;
  maps.m[0] = make_map(enc, d_in[1], 1728, 576); maps.m[1] = make_map(enc, d_in[2], 576, 576);
  maps.m[2] = make_map(enc, d_in[4], 4608, 576); maps.m[3] = make_map(enc, d_in[5], 4608, 576); maps.m[4] = make_map(enc, d_in[6], 576, 4608);
  maps.m[5] = make_map(enc, d_in[1], 1728, 576, true); maps.m[6] = make_map(enc, d_in[2], 576, 576, true);
  void* scr = nullptr;
  cudaGetSymbolAddress(&scr, g_scratch);
  cudaFuncSetAttribute(mega_kernel, cudaFuncAttributeMaxDynamicSharedMemorySize, SMEM_BYTES);
  mega_kernel<<<128, 384, SMEM_BYTES>>>(maps, (uint4*)scr, (const __nv_bfloat16*)d_in[0], (__nv_bfloat16*)d_out);
}
```

```cpp
#include <cuda_runtime.h>
#include <cuda.h>
#include <cuda_bf16.h>
#include <stdint.h>

#define TRACE 0
#define FPOS 2
#define W2 0

namespace {

constexpr int NST = 6;
constexpr int STAGE = 16384;
constexpr int PARK = NST * STAGE;
constexpr int REM = PARK + 49152;
constexpr int KVS = REM + 40960;
constexpr int HSTG = KVS + 16384;
constexpr int BARS = KVS + 41472;
constexpr int TRC = BARS + 256;
constexpr int SMEM_BYTES = TRC + (TRACE ? 512 : 0);
static_assert(BARS >= PARK + 131072, "barriers overlap park");
static_assert(SMEM_BYTES <= 232448, "smem");

constexpr int SLAB = 36 * 32;
constexpr int SPIN_MAX = 1 << 17;
constexpr int GD = 3;
constexpr int OFF_S = 0;
constexpr int OFF_H = OFF_S + 3 * 8 * 96;
constexpr int OFF_X = OFF_H + 2 * 8 * 384;
constexpr int OFF_P = OFF_X + 6 * 8 * SLAB;
constexpr int TILE = OFF_P + 8 * 8 * SLAB;
constexpr int OFF_R = 16 * TILE;
constexpr int OFF_F = OFF_R + 8 * 2304;
constexpr int SCRATCH = OFF_F + 128 * 8;

}

__device__ uint4 g_scratch[SCRATCH];

namespace {

constexpr uint64_t DESC_HI = 0x4000004000000000ull;
constexpr uint64_t DESC_REM = (576ull << 32) | (8u << 16);
__device__ __forceinline__ void wgmma_rs_n64(float (&d)[32], const uint32_t* a, uint64_t desc, int scale_d) {
  asm volatile("{\n.reg .pred p;\nsetp.ne.b32 p, %37, 0;\n"
    "wgmma.mma_async.sync.aligned.m64n64k16.f32.bf16.bf16 "
    "{%0, %1, %2, %3, %4, %5, %6, %7, %8, %9, %10, %11, %12, %13, %14, %15, %16, %17, %18, %19, %20, %21, %22, %23, %24, %25, %26, %27, %28, %29, %30, %31}, "
    "{%32, %33, %34, %35}, %36, p, 1, 1, 1;\n}\n"
    : "+f"(d[0]), "+f"(d[1]), "+f"(d[2]), "+f"(d[3]), "+f"(d[4]), "+f"(d[5]), "+f"(d[6]), "+f"(d[7]), "+f"(d[8]), "+f"(d[9]), "+f"(d[10]), "+f"(d[11]), "+f"(d[12]), "+f"(d[13]), "+f"(d[14]), "+f"(d[15]), "+f"(d[16]), "+f"(d[17]), "+f"(d[18]), "+f"(d[19]), "+f"(d[20]), "+f"(d[21]), "+f"(d[22]), "+f"(d[23]), "+f"(d[24]), "+f"(d[25]), "+f"(d[26]), "+f"(d[27]), "+f"(d[28]), "+f"(d[29]), "+f"(d[30]), "+f"(d[31])
    : "r"(a[0]), "r"(a[1]), "r"(a[2]), "r"(a[3]), "l"(desc), "r"(scale_d));
}
__device__ __forceinline__ void wgmma_rs_n72(float (&d)[36], const uint32_t* a, uint64_t desc, int scale_d) {
  asm volatile("{\n.reg .pred p;\nsetp.ne.b32 p, %41, 0;\n"
    "wgmma.mma_async.sync.aligned.m64n72k16.f32.bf16.bf16 "
    "{%0, %1, %2, %3, %4, %5, %6, %7, %8, %9, %10, %11, %12, %13, %14, %15, %16, %17, %18, %19, %20, %21, %22, %23, %24, %25, %26, %27, %28, %29, %30, %31, %32, %33, %34, %35}, "
    "{%36, %37, %38, %39}, %40, p, 1, 1, 1;\n}\n"
    : "+f"(d[0]), "+f"(d[1]), "+f"(d[2]), "+f"(d[3]), "+f"(d[4]), "+f"(d[5]), "+f"(d[6]), "+f"(d[7]), "+f"(d[8]), "+f"(d[9]), "+f"(d[10]), "+f"(d[11]), "+f"(d[12]), "+f"(d[13]), "+f"(d[14]), "+f"(d[15]), "+f"(d[16]), "+f"(d[17]), "+f"(d[18]), "+f"(d[19]), "+f"(d[20]), "+f"(d[21]), "+f"(d[22]), "+f"(d[23]), "+f"(d[24]), "+f"(d[25]), "+f"(d[26]), "+f"(d[27]), "+f"(d[28]), "+f"(d[29]), "+f"(d[30]), "+f"(d[31]), "+f"(d[32]), "+f"(d[33]), "+f"(d[34]), "+f"(d[35])
    : "r"(a[0]), "r"(a[1]), "r"(a[2]), "r"(a[3]), "l"(desc), "r"(scale_d));
}
__device__ __forceinline__ void wgmma_rs_n24(float (&d)[12], const uint32_t* a, uint64_t desc, int scale_d) {
  asm volatile("{\n.reg .pred p;\nsetp.ne.b32 p, %17, 0;\n"
    "wgmma.mma_async.sync.aligned.m64n24k16.f32.bf16.bf16 "
    "{%0, %1, %2, %3, %4, %5, %6, %7, %8, %9, %10, %11}, "
    "{%12, %13, %14, %15}, %16, p, 1, 1, 1;\n}\n"
    : "+f"(d[0]), "+f"(d[1]), "+f"(d[2]), "+f"(d[3]), "+f"(d[4]), "+f"(d[5]), "+f"(d[6]), "+f"(d[7]), "+f"(d[8]), "+f"(d[9]), "+f"(d[10]), "+f"(d[11])
    : "r"(a[0]), "r"(a[1]), "r"(a[2]), "r"(a[3]), "l"(desc), "r"(scale_d));
}

__device__ __forceinline__ void mbar_init(uint32_t a, uint32_t c) { asm volatile("mbarrier.init.shared::cta.b64 [%0], %1;" :: "r"(a), "r"(c)); }
__device__ __forceinline__ void mbar_arrive(uint32_t a) { asm volatile("mbarrier.arrive.shared::cta.b64 _, [%0];" :: "r"(a) : "memory"); }
__device__ __forceinline__ void mbar_wait(uint32_t a, uint32_t ph) {
  asm volatile("{\n.reg .pred p;\n.reg .u32 n;\n"
               "mbarrier.try_wait.parity.shared::cta.b64 p, [%0], %1;\n@p bra D;\n"
               "mov.u32 n, 0;\n"
               "W: mbarrier.try_wait.parity.shared::cta.b64 p, [%0], %1;\n@p bra D;\n"
               "add.u32 n, n, 1;\nsetp.lt.u32 p, n, 4194304;\n@p bra W;\ntrap;\nD:\n}" :: "r"(a), "r"(ph) : "memory");
}
__device__ __forceinline__ void wg_fence() { asm volatile("wgmma.fence.sync.aligned;" ::: "memory"); }
__device__ __forceinline__ void wg_commit() { asm volatile("wgmma.commit_group.sync.aligned;" ::: "memory"); }
template <int N> __device__ __forceinline__ void wg_wait() { asm volatile("wgmma.wait_group.sync.aligned %0;" :: "n"(N) : "memory"); }
__device__ __forceinline__ float tanh_ap(float x) { float y; asm("tanh.approx.f32 %0, %1;" : "=f"(y) : "f"(x)); return y; }
__device__ __forceinline__ float ex2(float x) { float y; asm("ex2.approx.ftz.f32 %0, %1;" : "=f"(y) : "f"(x)); return y; }
__device__ __forceinline__ uint32_t pack_bf16(float lo, float hi) { uint32_t r; asm("cvt.rn.bf16x2.f32 %0, %1, %2;" : "=r"(r) : "f"(hi), "f"(lo)); return r; }
__device__ __forceinline__ float bf_lo(uint32_t v) { return __uint_as_float(v << 16); }
__device__ __forceinline__ float bf_hi(uint32_t v) { return __uint_as_float(v & 0xffff0000u); }
__device__ __forceinline__ uint32_t sub_bf16x2(uint32_t a, uint32_t b) { uint32_t r; asm("sub.rn.bf16x2 %0, %1, %2;" : "=r"(r) : "r"(a), "r"(b)); return r; }
__device__ __forceinline__ uint32_t mul_bf16x2(uint32_t a, uint32_t b) { uint32_t r; asm("mul.rn.bf16x2 %0, %1, %2;" : "=r"(r) : "r"(a), "r"(b)); return r; }
__device__ __forceinline__ uint32_t nz(uint32_t w) { return w == 0u ? 0x8000u : w; }

__device__ __forceinline__ void ldg4(uint32_t* d, const uint4* p) {
  asm volatile("ld.relaxed.gpu.global.v4.b32 {%0,%1,%2,%3}, [%4];" : "=r"(d[0]), "=r"(d[1]), "=r"(d[2]), "=r"(d[3]) : "l"(p) : "memory");
}
__device__ __forceinline__ void ldg2(uint32_t* d, const void* p) {
  asm volatile("ld.relaxed.gpu.global.v2.b32 {%0,%1}, [%2];" : "=r"(d[0]), "=r"(d[1]) : "l"(p) : "memory");
}
__device__ __forceinline__ void stg4(uint4* p, uint32_t a, uint32_t b, uint32_t c, uint32_t d) {
  asm volatile("st.relaxed.gpu.global.v4.b32 [%0], {%1,%2,%3,%4};" :: "l"(p), "r"(a), "r"(b), "r"(c), "r"(d) : "memory");
}
__device__ __forceinline__ void stg2(void* p, uint32_t a, uint32_t b) {
  asm volatile("st.relaxed.gpu.global.v2.b32 [%0], {%1,%2};" :: "l"(p), "r"(a), "r"(b) : "memory");
}
__device__ __forceinline__ void sts4(uint32_t a, const uint32_t* o) { asm volatile("st.shared.v4.b32 [%0], {%1,%2,%3,%4};" :: "r"(a), "r"(o[0]), "r"(o[1]), "r"(o[2]), "r"(o[3]) : "memory"); }
__device__ __forceinline__ void lds4(uint32_t a, uint32_t* o) { asm volatile("ld.shared.v4.b32 {%0,%1,%2,%3}, [%4];" : "=r"(o[0]), "=r"(o[1]), "=r"(o[2]), "=r"(o[3]) : "r"(a) : "memory"); }
__device__ __forceinline__ void lds2(uint32_t a, uint32_t* o) { asm volatile("ld.shared.v2.b32 {%0,%1}, [%2];" : "=r"(o[0]), "=r"(o[1]) : "r"(a) : "memory"); }
__device__ __forceinline__ float rcp(float x) { float y; asm("rcp.approx.ftz.f32 %0, %1;" : "=f"(y) : "f"(x)); return y; }
__device__ __forceinline__ void sts1(uint32_t a, uint32_t v) { asm volatile("st.shared.b32 [%0], %1;" :: "r"(a), "r"(v) : "memory"); }
__device__ __forceinline__ void ldsm4(uint32_t a, uint32_t& r0, uint32_t& r1, uint32_t& r2, uint32_t& r3) {
  asm volatile("ldmatrix.sync.aligned.m8n8.x4.shared.b16 {%0,%1,%2,%3}, [%4];" : "=r"(r0), "=r"(r1), "=r"(r2), "=r"(r3) : "r"(a) : "memory");
}
__device__ __forceinline__ void ldsm4t(uint32_t a, uint32_t& r0, uint32_t& r1, uint32_t& r2, uint32_t& r3) {
  asm volatile("ldmatrix.sync.aligned.m8n8.x4.trans.shared.b16 {%0,%1,%2,%3}, [%4];" : "=r"(r0), "=r"(r1), "=r"(r2), "=r"(r3) : "r"(a) : "memory");
}
__device__ __forceinline__ void mma16(float* c, uint32_t a0, uint32_t a1, uint32_t a2, uint32_t a3, uint32_t b0, uint32_t b1) {
  asm("mma.sync.aligned.m16n8k16.row.col.f32.bf16.bf16.f32 {%0,%1,%2,%3}, {%4,%5,%6,%7}, {%8,%9}, {%0,%1,%2,%3};"
    : "+f"(c[0]), "+f"(c[1]), "+f"(c[2]), "+f"(c[3]) : "r"(a0), "r"(a1), "r"(a2), "r"(a3), "r"(b0), "r"(b1));
}
__device__ __forceinline__ void mma8(float* c, uint32_t a0, uint32_t a1, uint32_t b0) {
  asm("mma.sync.aligned.m16n8k8.row.col.f32.bf16.bf16.f32 {%0,%1,%2,%3}, {%4,%5}, {%6}, {%0,%1,%2,%3};"
    : "+f"(c[0]), "+f"(c[1]), "+f"(c[2]), "+f"(c[3]) : "r"(a0), "r"(a1), "r"(b0));
}
__device__ __forceinline__ uint32_t lane_id() { uint32_t l; asm volatile("mov.u32 %0, %%laneid;" : "=r"(l)); return l; }
__device__ __forceinline__ float quad_sum(float v) { v += __shfl_xor_sync(~0u, v, 1); v += __shfl_xor_sync(~0u, v, 2); return v; }
__device__ __forceinline__ float quad_max(float v) { v = fmaxf(v, __shfl_xor_sync(~0u, v, 1)); v = fmaxf(v, __shfl_xor_sync(~0u, v, 2)); return v; }
template <int N> __device__ __forceinline__ void pin(float (&d)[N]) {
#pragma unroll
  for (int i = 0; i < N; i++) asm volatile("" : "+f"(d[i]) :: "memory");
}
#define SPIN_GUARD(n) if (++(n) > SPIN_MAX) break

template <int NG> __device__ __forceinline__ void publish_stats(uint4* dst, const float* y, uint32_t tag, uint32_t lane) {
  float s0 = 0.f, s1 = 0.f;
#pragma unroll
  for (int g = 0; g < NG; g++) { s0 += y[4 * g] + y[4 * g + 1]; s1 += y[4 * g + 2] + y[4 * g + 3]; }
  s0 = quad_sum(s0); s1 = quad_sum(s1);
  const float m0 = s0 * (1.f / (8 * NG)), m1 = s1 * (1.f / (8 * NG));
  float q0 = 0.f, q1 = 0.f, q2 = 0.f, q3 = 0.f;
#pragma unroll
  for (int g = 0; g < NG; g++) {
    const float a = y[4 * g] - m0, b = y[4 * g + 1] - m0, c = y[4 * g + 2] - m1, d = y[4 * g + 3] - m1;
    q0 = fmaf(a, a, q0); q1 = fmaf(b, b, q1); q2 = fmaf(c, c, q2); q3 = fmaf(d, d, q3);
  }
  q0 = quad_sum(q0 + q1); q2 = quad_sum(q2 + q3);
  if ((lane & 3) == 0)
    stg4(dst + (lane >> 2), (__float_as_uint(s0) & ~1u) | tag, __float_as_uint(q0), __float_as_uint(s1), __float_as_uint(q2));
}

__device__ __forceinline__ void put72(uint4* slab, uint32_t j, uint32_t lane, const uint32_t* v) {
  uint4* p = slab + ((9 * j + 1) >> 1) * 32;
  if (j & 1) {
    stg2((char*)(p - 16) + lane * 8, nz(v[0]), v[1]);
#pragma unroll
    for (int i = 0; i < 4; i++) stg4(p + lane + i * 32, nz(v[4 * i + 2]), v[4 * i + 3], v[4 * i + 4], v[4 * i + 5]);
  } else {
#pragma unroll
    for (int i = 0; i < 4; i++) stg4(p + lane + i * 32, nz(v[4 * i]), v[4 * i + 1], v[4 * i + 2], v[4 * i + 3]);
    stg2((char*)(p + 4 * 32) + lane * 8, nz(v[16]), v[17]);
  }
}
__device__ __forceinline__ void zero_share(uint4* slab, uint32_t j, uint32_t lane) {
  uint4* p = slab + j * 144 + lane;
#pragma unroll
  for (int i = 0; i < 4; i++) stg4(p + i * 32, 0u, 0u, 0u, 0u);
  if (lane < 16) stg4(p + 128, 0u, 0u, 0u, 0u);
}

struct Maps { CUtensorMap m[7]; };

struct Ring {
  uint32_t st, ph;
  __device__ __forceinline__ void next() { if (++st == NST) { st = 0; ph ^= 1; } }
};

#define GSTAMP(i) do {} while (0)
#define STAMP(i) do {} while (0)

__device__ __forceinline__ void tma_box(uint32_t dst, const CUtensorMap* m, int col, int row, uint32_t bar, uint32_t expect) {
  asm volatile("{\n.reg .pred e, h;\nelect.sync _|e, 0xffffffff;\nsetp.ne.and.u32 h, %5, 0, e;\n"
               "@h mbarrier.arrive.expect_tx.shared::cta.b64 _, [%2], %5;\n"
               "@e cp.async.bulk.tensor.2d.shared::cluster.global.mbarrier::complete_tx::bytes [%0], [%1, {%3, %4}], [%2];\n}"
               :: "r"(dst), "l"(m), "r"(bar), "r"(col), "r"(row), "r"(expect) : "memory");
}

__device__ __forceinline__ void bulk_load(uint32_t dst, const void* src, uint32_t bytes, uint32_t bar, bool arm) {
  asm volatile("{\n.reg .pred e, h;\nelect.sync _|e, 0xffffffff;\nsetp.ne.and.u32 h, %4, 0, e;\n"
               "@h mbarrier.arrive.expect_tx.shared::cta.b64 _, [%3], %2;\n"
               "@e cp.async.bulk.shared::cluster.global.mbarrier::complete_tx::bytes [%0], [%1], %2, [%3];\n}"
               :: "r"(dst), "l"(src), "r"(bytes), "r"(bar), "r"((uint32_t)arm) : "memory");
}

__global__ void __launch_bounds__(384, 1) mega_kernel(
    const __grid_constant__ Maps maps, uint4* __restrict__ scratch,
    const __nv_bfloat16* __restrict__ x_in, __nv_bfloat16* __restrict__ out) {
  extern __shared__ __align__(1024) uint8_t smem[];
  const uint32_t sb = (uint32_t)__cvta_generic_to_shared(smem);
  const uint32_t full0 = sb + BARS, empty0 = full0 + 8 * NST, rem_full = empty0 + 8 * NST, park_free = rem_full + 8, kv_free = park_free + 8;
  const uint32_t c8_go = kv_free + 8, c8_done = c8_go + 8, c8_full = c8_done + 8, remo_full = c8_full + 8, piece_full = remo_full + 8, pbar0 = piece_full + 8;
  const uint32_t w = __shfl_sync(~0u, threadIdx.x >> 5, 0);
  const uint32_t t = blockIdx.x >> 3, j = blockIdx.x & 7;
  uint4* const scr = scratch + t * TILE;
  {
    const uint32_t lane = lane_id(), r = lane >> 2, q = lane & 3;
    const uint32_t sl = w < 8 ? w : j, ch = w < 8 ? j : 8;
    const uint32_t* xr = (const uint32_t*)(x_in + (128 * t + 32 * (sl >> 1) + 2 * r + (sl & 1)) * 576 + 64 * ch + 2 * q);
    if (w < 8 || w == 9) {
      uint32_t v[16];
#pragma unroll
      for (int g = 0; g < 8; g++) {
        asm volatile("ld.global.nc.b32 %0, [%1];" : "=r"(v[2 * g]) : "l"(xr + 4 * g));
        asm volatile("ld.global.nc.b32 %0, [%1];" : "=r"(v[2 * g + 1]) : "l"(xr + 8 * 576 + 4 * g));
      }
      if (q == 0) {
#pragma unroll
        for (int k = 0; k < 3; k++) stg4(scr + OFF_S + (k * 8 + sl) * 96 + ch * 8 + r, 0u, 0u, 0u, 0u);
      }
      asm volatile("bar.sync 0;" ::: "memory");
      uint4* p = scr + OFF_X + sl * SLAB + 4 * ch * 32 + lane;
#pragma unroll
      for (int i = 0; i < 4; i++) stg4(p + i * 32, nz(v[4 * i]), v[4 * i + 1], nz(v[4 * i + 2]), v[4 * i + 3]);
      float y[32];
#pragma unroll
      for (int i = 0; i < 16; i++) { y[2 * i] = bf_lo(v[i]); y[2 * i + 1] = bf_hi(v[i]); }
      publish_stats<8>(scr + OFF_S + sl * 96 + ch * 8, y, 1u, lane);
    } else {
      if (threadIdx.x == 256) {
        for (int i = 0; i < NST; i++) { mbar_init(full0 + 8 * i, 1); mbar_init(empty0 + 8 * i, 8); }
        mbar_init(rem_full, 1); mbar_init(park_free, 8); mbar_init(kv_free, 8); mbar_init(c8_go, 8); mbar_init(c8_done, 1); mbar_init(c8_full, 1); mbar_init(remo_full, 64); mbar_init(piece_full, 1);
        for (int i = 0; i < 8; i++) mbar_init(pbar0 + 8 * i, 5);
        asm volatile("fence.mbarrier_init.release.cluster;" ::: "memory");
      }
      __syncwarp();
      asm volatile("bar.sync 0;" ::: "memory");
    }
  }

  if (w >= 8) {
    asm volatile("setmaxnreg.dec.sync.aligned.u32 24;");
    if (w == 8) {
      Ring rg{0, 1};
#pragma unroll 1
      for (int seg = 0; seg < 34; seg++) {
        const int n = seg >= 17 ? seg - 17 : seg;
        int ma, mb, ca, cb, row = 0;
        if (n < 3) { ma = mb = n == 2; ca = 72 * j + (n == 0 ? 576 : 0); cb = ca + 576; }
        else if (n < 12) { ma = 3; mb = 2; ca = cb = 576 * j + 64 * (n - 3); }
        else { ma = mb = 4; ca = n == 12 ? 512 : ((j + 2 * n) & 7) * 64; cb = ((j + 2 * n + 1) & 7) * 64; row = 576 * j; }
        const bool zip = n == 0 || n == 3;
        const int nb = (n == 1 || n == 2 || n == 16) ? 9 : 18;
#pragma unroll 1
        for (int b = 0; b < nb; b++) {
          const bool second = zip ? (b & 1) : b >= 9, last = b == nb - 1;
          const int kb = zip ? b >> 1 : second ? b - 9 : b;
          if (!(b & 1)) mbar_wait(empty0 + rg.st * 8, rg.ph);
          tma_box(sb + rg.st * STAGE + (b & 1) * 8192, &maps.m[second ? mb : ma], second ? cb : ca, row + 64 * kb, full0 + rg.st * 8,
                  (b & 1) ? 0 : last ? STAGE / 2 : STAGE);
          if ((b & 1) || last) rg.next();
        }
      }
    } else if (w == 9) {
      const uint32_t lane = lane_id();
      const uint32_t stg = sb + HSTG + lane * 16;
      uint32_t fph = 0;
#pragma unroll 1
      for (uint32_t layer = 0; layer < 2; layer++) {
        uint4* xb = scr + OFF_X + ((4 + layer) * 8 + j) * SLAB + 32 * 32;
        mbar_wait(c8_go, layer);
        int n = 0;
        while (true) {
          if (lane == 0) asm volatile("mbarrier.arrive.expect_tx.shared::cta.b64 _, [%0], 18432;" :: "r"(c8_full) : "memory");
          __syncwarp();
#pragma unroll 1
          for (uint32_t s = 0; s < 9; s++)
            bulk_load(sb + HSTG + s * 2048, s < 8 ? scr + OFF_P + (j + s * 8) * SLAB + 32 * 32 : xb, 2048, c8_full, false);
          mbar_wait(c8_full, fph); fph ^= 1;
          uint32_t bad = 0;
#pragma unroll 8
          for (int s = 0; s < 32; s++) { uint32_t v; asm volatile("ld.shared.b32 %0, [%1];" : "=r"(v) : "r"(stg + s * 512) : "memory"); bad |= v ^ (1 - layer); }
          if (__all_sync(~0u, (bad & 1u) == 0u)) break;
          __nanosleep(300);
          SPIN_GUARD(n);
        }
        float s0 = 0.f, s1 = 0.f;
#pragma unroll 1
        for (int g = 0; g < 8; g++) {
          const uint32_t a = stg + (g >> 1) * 512 + (g & 1) * 8;
          float a0 = 0.f, a1 = 0.f, a2 = 0.f, a3 = 0.f;
#pragma unroll 1
          for (int b = 0; b < 3; b++) {
            uint32_t v[6];
#pragma unroll
            for (int s = 0; s < 3; s++) lds2(a + (3 * b + s) * 2048, v + 2 * s);
#pragma unroll
            for (int s = 0; s < 3; s++) { a0 += bf_lo(v[2 * s]); a1 += bf_hi(v[2 * s]); a2 += bf_lo(v[2 * s + 1]); a3 += bf_hi(v[2 * s + 1]); }
          }
          sts1(a + 18432, pack_bf16(a0, a1)); sts1(a + 18436, pack_bf16(a2, a3));
          s0 += a0 + a1; s1 += a2 + a3;
        }
        __syncwarp();
        if (lane == 0) mbar_arrive(c8_done);
        s0 = quad_sum(s0); s1 = quad_sum(s1);
        float q0 = 0.f, q1 = 0.f;
        const uint32_t ln = lane_id();
#pragma unroll 1
        for (uint32_t i = 0; i < 4; i++) {
          uint32_t x[4];
          lds4(stg + 18432 + i * 512, x);
          stg4(xb + i * 32 + ln, 0u, 0u, 0u, 0u);
          if (layer == 0) {
            stg4(xb - 3 * 8 * SLAB + i * 32 + ln, nz(x[0]), x[1], x[2], x[3]);
#pragma unroll
            for (int e = 0; e < 4; e++) {
              const float m = (e & 1) ? s1 : s0, c = fmaf(m, -1.f / 64, bf_lo(x[e])), d = fmaf(m, -1.f / 64, bf_hi(x[e]));
              if (e & 1) q1 = fmaf(c, c, fmaf(d, d, q1)); else q0 = fmaf(c, c, fmaf(d, d, q0));
            }
          } else {
            uint32_t* o = (uint32_t*)(out + (128 * t + 32 * (j >> 1) + 2 * (ln >> 2) + (j & 1)) * 576 + 512 + 16 * i + 2 * (ln & 3));
            o[0] = x[0]; o[8 * 576] = x[1]; o[4] = x[2]; o[8 * 576 + 4] = x[3];
          }
        }
        if (layer == 0) {
          q0 = quad_sum(q0); q1 = quad_sum(q1);
          if ((ln & 3) == 0) stg4(scr + OFF_S + j * 96 + 64 + (ln >> 2), __float_as_uint(s0) & ~1u, __float_as_uint(q0), __float_as_uint(s1), __float_as_uint(q1));
        }
      }
    } else {
      const uint32_t lane = lane_id(), r = lane >> 2, q = lane & 3;
#pragma unroll 1
      for (uint32_t layer = 0; layer < 2; layer++) {
        if (w == 10) {
          if (layer == 0) {
            const uint32_t p = t >> 2;
            tma_box(sb + PARK, &maps.m[p == 3 ? 6 : 5], 72 * j + 64 + (p < 2 ? 576 * (p + 1) : 0), 144 * (t & 3), piece_full, 2304);
            mbar_wait(piece_full, 0);
            asm volatile("{\n.reg .pred e;\nelect.sync _|e, 0xffffffff;\n@e cp.async.bulk.global.shared::cta.bulk_group [%0], [%1], 2304;\n}\n"
                         "cp.async.bulk.commit_group;\ncp.async.bulk.wait_group 0;\nfence.proxy.async;"
                         :: "l"(scratch + OFF_R + j * 2304 + t * 144), "r"(sb + PARK) : "memory");
            __syncwarp();
            if (lane < 16) asm volatile("st.release.gpu.global.b32 [%0], 1;" :: "l"((uint32_t*)(scratch + OFF_F + (lane * 8 + j) * 8) + t) : "memory");
            uint32_t* fl = (uint32_t*)(scratch + OFF_F + (t * 8 + j) * 8) + (lane & 15);
            uint32_t v;
            int n = 0;
            while (true) {
              asm volatile("ld.acquire.gpu.global.b32 %0, [%1];" : "=r"(v) : "l"(fl) : "memory");
              if (__all_sync(~0u, v != 0u)) break;
              __nanosleep(100);
              SPIN_GUARD(n);
            }
            asm volatile("fence.proxy.async;\nst.relaxed.gpu.global.b32 [%0], 0;" :: "l"(fl) : "memory");
          } else {
            mbar_wait(park_free, 0);
          }
          bulk_load(sb + REM, scratch + OFF_R + j * 2304, 36864, rem_full, true);
        }
        mbar_wait(rem_full, layer);
#pragma unroll 1
        for (uint32_t b = 0; b < 5; b++) {
          const uint32_t blk = sb + REM + 27648 + b * 2048, k = threadIdx.x - 320, rr = k & 7;
          const uint32_t dst = blk + ((k >> 3) & 1) * 1024 + rr * 128 + (((k >> 4) ^ rr) << 4);
          uint32_t v[8];
          lds4(blk + k * 16, v); lds4(blk + 1024 + k * 16, v + 4);
          asm volatile("bar.sync 3, 64;" ::: "memory");
          sts4(dst, v); sts4(dst ^ 64, v + 4);
        }
        asm volatile("fence.proxy.async.shared::cta;" ::: "memory");
        mbar_arrive(remo_full);
        if (layer) mbar_wait(kv_free, 0);
        if (t > 0) {
#pragma unroll 1
          for (uint32_t pc = 0; pc < 3; pc++) {
            uint4* hp = scr + OFF_H + ((layer * 8 + j) * 2 + (w - 10)) * 192 + pc * 64 + lane;
            uint32_t hl[8];
            int n = 0;
            hl[4] = 1u;
            while (true) {
              ldg4(hl, hp);
              if (pc < 2) ldg4(hl + 4, hp + 32);
              if (__all_sync(~0u, hl[0] != 0u && hl[4] != 0u)) break;
              __nanosleep(100);
              SPIN_GUARD(n);
            }
            const uint32_t dst = sb + KVS + (w - 10) * 10368 + r * 144 + q * 4;
            if (pc < 2) {
#pragma unroll
              for (int g = 0; g < 8; g++) sts1(dst + pc * 20736 + g * 16, hl[g]);
              stg4(hp + 32, 0u, 0u, 0u, 0u);
            } else {
              sts1(dst + 128, hl[0]); sts1(dst + 20736 + 128, hl[1]);
            }
            stg4(hp, 0u, 0u, 0u, 0u);
          }
        }
        asm volatile("bar.arrive 1, 192;" ::: "memory");
      }
    }
  } else {
    asm volatile("setmaxnreg.inc.sync.aligned.u32 240;");
    const uint32_t lane = lane_id(), r = lane >> 2, q = lane & 3;
    Ring rg{0, 0};
    uint32_t prev = 0;
    uint32_t X[144];
    float rs0, rs1;
    uint32_t mean0, mean1;
    auto release = [&](uint32_t st) { if (lane == 0) mbar_arrive(empty0 + st * 8); };
    auto load_kb = [&](int kb, const uint4* src, const char* lo, uint32_t hoff) {
#pragma unroll
      for (int k = 4 * kb; k < 4 * kb + 4; k++) {
        if (k % 9 == 4) { ldg2(X + 4 * k, lo + k * 512); ldg2(X + 4 * k + 2, lo + hoff + k * 512); }
        else ldg4(X + 4 * k, src + k * 32);
      }
    };
    auto next_kb = [&](bool center, int kb, const uint4* src, const char* lo, uint32_t hoff) {
      int n = 0;
      while (true) {
        bool ok = true;
#pragma unroll
        for (int k = 4 * kb; k < 4 * kb + 4; k++) { ok = ok && X[4 * k] != 0u; if (k % 9 == 4) ok = ok && X[4 * k + 2] != 0u; }
        if (__all_sync(~0u, ok)) break;
        SPIN_GUARD(n);
        load_kb(kb, src, lo, hoff);
      }
      if (kb + GD < 9) load_kb(kb + GD, src, lo, hoff);
      if (center) {
#pragma unroll
        for (int i = 16 * kb; i < 16 * kb + 16; i++) X[i] = sub_bf16x2(X[i], (i & 1) ? mean1 : mean0);
      }
    };
#pragma unroll 1
    for (uint32_t hf = 0; hf < 4; hf++) {
      const uint32_t layer = hf >> 1;
      const bool ffn = hf & 1;
      const uint32_t tag = 1 - layer;
      uint4* const xbase = scr + OFF_X + (layer * 8 + w) * SLAB;
      float aA[32], aB[32];
      {
        const uint4* src = xbase + (ffn ? 32 * SLAB : 0) + lane;
        const char* lo = (const char*)src - (ffn ? lane * 8 : 0);
        const uint32_t hoff = ffn ? 256 : 8;
        uint32_t s[3][4];
        const uint4* p = scr + OFF_S + ((ffn ? 16 : 0) + w) * 96 + q * 8 + r;
        const bool third = !ffn && q == 0;
        int n = 0;
        s[2][0] = tag; s[2][1] = s[2][2] = s[2][3] = 0u;
        STAMP(ffn * 16 + 0);
        while (true) {
          ldg4(s[0], p); ldg4(s[1], p + 32);
          if (third) ldg4(s[2], p + 64);
          if (__all_sync(~0u, ((s[0][0] ^ tag) | (s[1][0] ^ tag) | (s[2][0] ^ tag)) % 2u == 0u)) break;
          SPIN_GUARD(n);
        }
        STAMP(ffn * 16 + 1);
        GSTAMP(14 + ffn);
#pragma unroll
        for (int kb = 0; kb < GD; kb++) load_kb(kb, src, lo, hoff);
        float t0 = 0.f, t1 = 0.f;
#pragma unroll
        for (int i = 0; i < 3; i++) { t0 += __uint_as_float(s[i][0]); t1 += __uint_as_float(s[i][2]); }
        const float m0 = quad_sum(t0) * (1.f / 576), m1 = quad_sum(t1) * (1.f / 576);
        const float cnt = ffn ? 72.f : 64.f, inv = ffn ? 1.f / 72 : 1.f / 64;
        float v0 = 0.f, v1 = 0.f;
#pragma unroll
        for (int i = 0; i < 3; i++) {
          const float c = (i < 2 || third) ? cnt : 0.f;
          const float d0 = fmaf(__uint_as_float(s[i][0]), inv, -m0), d1 = fmaf(__uint_as_float(s[i][2]), inv, -m1);
          v0 += fmaf(d0 * d0, c, __uint_as_float(s[i][1])); v1 += fmaf(d1 * d1, c, __uint_as_float(s[i][3]));
        }
        rs0 = rsqrtf(fmaf(quad_sum(v0), 1.f / 576, 1e-5f)); rs1 = rsqrtf(fmaf(quad_sum(v1), 1.f / 576, 1e-5f));
        mean0 = pack_bf16(m0, m0); mean1 = pack_bf16(m1, m1);
#pragma unroll
        for (int kb = 0; kb < 9; kb++) {
          next_kb(true, kb, src, lo, hoff);
          mbar_wait(full0 + rg.st * 8, rg.ph);
          const uint64_t desc = DESC_HI | ((sb + rg.st * STAGE) >> 4);
          wg_fence();
#pragma unroll
          for (int i = 0; i < 4; i++) wgmma_rs_n64(aA, X + 4 * (4 * kb + i), desc + i * 128, kb + i != 0);
#pragma unroll
          for (int i = 0; i < 4; i++) wgmma_rs_n64(aB, X + 4 * (4 * kb + i), desc + 512 + i * 128, kb + i != 0);
          wg_commit();
          wg_wait<1>();
          if (kb > 0) release(prev);
          prev = rg.st; rg.next();
        }
        wg_wait<0>();
        STAMP(ffn * 16 + 2);
      }
      if (!ffn) {
      release(prev);
      const uint32_t kvrow = sb + KVS + (w & 1) * 10368 + (16 * (w >> 1)) * 144;
      uint32_t Q[18];
      {
        const uint32_t dst = kvrow + (8 + r) * 144 + q * 4;
        const bool edge_out = w >= 6 && t < 15;
        uint4* const hp = scr + TILE + OFF_H + ((layer * 8 + j) * 2 + (w & 1)) * 192 + lane;
        auto put_kv = [&](float (&a)[32], int part) {
          pin(a);
          uint32_t hl[8];
#pragma unroll
          for (int g = 0; g < 8; g++) {
            hl[g] = pack_bf16(a[4 * g + 2] * rs1, a[4 * g + 3] * rs1);
            sts1(dst + part * 20736 + g * 16, pack_bf16(a[4 * g] * rs0, a[4 * g + 1] * rs0)); sts1(dst + part * 20736 + 8 * 144 + g * 16, hl[g]);
          }
          if (edge_out) { stg4(hp + part * 64, nz(hl[0]), hl[1], hl[2], hl[3]); stg4(hp + part * 64 + 32, nz(hl[4]), hl[5], hl[6], hl[7]); }
        };
        put_kv(aA, 0);
        float aR[12];
        mbar_wait(rem_full, layer);
        const uint64_t dr = DESC_REM | ((sb + REM) >> 4);
        wg_fence();
#pragma unroll
        for (int s = 0; s < 36; s++) {
          wgmma_rs_n24(aR, X + 4 * s, dr + s * 16, s != 0);
          if (s == 4) put_kv(aB, 1);
        }
        wg_commit();
#pragma unroll
        for (int kb = 0; kb < 9; kb++) {
          if (!(kb & 1)) mbar_wait(full0 + rg.st * 8, rg.ph);
          const uint64_t desc = DESC_HI | ((sb + rg.st * STAGE + (kb & 1) * 8192) >> 4);
          wg_fence();
#pragma unroll
          for (int i = 0; i < 4; i++) wgmma_rs_n64(aB, X + 4 * (4 * kb + i), desc + i * 128, kb + i != 0);
          wg_commit();
          wg_wait<1>();
          if (kb > 0 && !(kb & 1)) release(prev);
          if ((kb & 1) || kb == 8) { prev = rg.st; rg.next(); }
          if (kb == 0) {
            pin(aR);
            const uint32_t k1 = pack_bf16(aR[2] * rs1, aR[3] * rs1), v1 = pack_bf16(aR[6] * rs1, aR[7] * rs1);
            if (edge_out) stg4(hp + 128, nz(k1), v1, 0u, 0u);
            sts1(dst + 128, pack_bf16(aR[0] * rs0, aR[1] * rs0)); sts1(dst + 8 * 144 + 128, k1);
            sts1(dst + 20736 + 128, pack_bf16(aR[4] * rs0, aR[5] * rs0)); sts1(dst + 20736 + 8 * 144 + 128, v1);
            Q[16] = pack_bf16(aR[8] * rs0, aR[9] * rs0); Q[17] = pack_bf16(aR[10] * rs1, aR[11] * rs1);
            if (w < 4) asm volatile("bar.arrive 2, 256;" ::: "memory");
          }
        }
        wg_wait<0>();
        release(prev);
        pin(aB);
        STAMP(3);
#pragma unroll
        for (int g = 0; g < 8; g++) {
          Q[2 * g] = pack_bf16(aB[4 * g] * rs0, aB[4 * g + 1] * rs0); Q[2 * g + 1] = pack_bf16(aB[4 * g + 2] * rs1, aB[4 * g + 3] * rs1);
        }
      }
      if (w < 4) asm volatile("bar.sync 1, 192;" ::: "memory");
      else asm volatile("bar.sync 2, 256;" ::: "memory");
      STAMP(4);
      uint32_t O[18];
      {
        const bool edge = (t == 0 && w < 2);
        uint32_t row[3];
#pragma unroll
        for (int nt = 0; nt < 3; nt++) row[nt] = kvrow + (8 * nt + (lane & 7)) * 144;
        if (edge) row[0] = sb + KVS + 8 * 144;
        const uint32_t rlast = ((lane >> 3) == 0 ? row[0] : (lane >> 3) == 1 ? row[1] : row[2]) + 128;
        uint32_t K[3][9], V[3][9], dummy;
#pragma unroll
        for (int nt = 0; nt < 3; nt++) {
          ldsm4(row[nt] + (lane >> 3) * 16, K[nt][0], K[nt][1], K[nt][2], K[nt][3]);
          ldsm4(row[nt] + 64 + (lane >> 3) * 16, K[nt][4], K[nt][5], K[nt][6], K[nt][7]);
        }
        ldsm4(rlast, K[0][8], K[1][8], K[2][8], dummy);
#pragma unroll
        for (int nt = 0; nt < 3; nt++) {
          ldsm4t(row[nt] + 20736 + (lane >> 3) * 16, V[nt][0], V[nt][1], V[nt][2], V[nt][3]);
          ldsm4t(row[nt] + 20736 + 64 + (lane >> 3) * 16, V[nt][4], V[nt][5], V[nt][6], V[nt][7]);
        }
        ldsm4t(rlast + 20736, V[0][8], V[1][8], V[2][8], dummy);
        const bool up0 = 2 * q > r, up1 = 2 * q + 1 > r;
        const float sc = 0.23570226039551584f * 1.4426950408889634f;
        const float neg = -1e9f * 1.4426950408889634f;
        float Of[9][4];
#pragma unroll
        for (int h = 0; h < 4; h++) {
          const uint32_t a0 = q >= h ? Q[4 * h] : 0u, a1 = q >= h ? Q[4 * h + 1] : 0u;
          const uint32_t a4 = q <= h ? Q[4 * h + 4] : 0u, a5 = q <= h ? Q[4 * h + 5] : 0u;
          float S[3][4];
#pragma unroll
          for (int nt = 0; nt < 3; nt++) {
            S[nt][0] = S[nt][1] = S[nt][2] = S[nt][3] = 0.f;
            mma16(S[nt], a0, a1, Q[4 * h + 2], Q[4 * h + 3], K[nt][2 * h], K[nt][2 * h + 1]);
            mma8(S[nt], a4, a5, K[nt][2 * h + 2]);
          }
          float s00 = (up0 ? S[0][0] : S[1][0]) * sc, s01 = (up1 ? S[0][1] : S[1][1]) * sc;
          const float s10 = (up0 ? S[1][2] : S[2][2]) * sc, s11 = (up1 ? S[1][3] : S[2][3]) * sc;
          if (edge && up0) s00 = neg;
          if (edge && up1) s01 = neg;
          const float m0 = quad_max(fmaxf(s00, s01)), m1 = quad_max(fmaxf(s10, s11));
          float p00 = ex2(s00 - m0), p01 = ex2(s01 - m0), p10 = ex2(s10 - m1), p11 = ex2(s11 - m1);
          const float i0 = rcp(quad_sum(p00 + p01)), i1 = rcp(quad_sum(p10 + p11));
          p00 *= i0; p01 *= i0; p10 *= i1; p11 *= i1;
          const uint32_t pa = pack_bf16(up0 ? p00 : 0.f, up1 ? p01 : 0.f), pb = pack_bf16(up0 ? 0.f : p00, up1 ? 0.f : p01);
          const uint32_t pc = pack_bf16(up0 ? p10 : 0.f, up1 ? p11 : 0.f), pd = pack_bf16(up0 ? 0.f : p10, up1 ? 0.f : p11);
#pragma unroll
          for (int gi = 0; gi < 3; gi++) {
            const int g = 2 * h + gi;
            float o[4] = {0.f, 0.f, 0.f, 0.f};
            mma16(o, pa, 0u, pb, pc, V[0][g], V[1][g]);
            mma8(o, 0u, pd, V[2][g]);
#pragma unroll
            for (int e = 0; e < 4; e++) Of[g][e] = (gi == 0 && h > 0 && q < h) ? Of[g][e] : o[e];
          }
        }
#pragma unroll
        for (int g = 0; g < 9; g++) { O[2 * g] = pack_bf16(Of[g][0], Of[g][1]); O[2 * g + 1] = pack_bf16(Of[g][2], Of[g][3]); }
      }
      put72(xbase + 16 * SLAB, j, lane, O);
      if (q == 0) stg4(scr + OFF_S + (8 + w) * 96 + j * 8 + r, tag, 0u, 0u, 0u);
      {
        uint32_t res[18];
        const char* p = (const char*)(xbase + lane) + ((9 * j) >> 1) * 512 + (j & 1) * 8;
#pragma unroll
        for (int g = 0; g < 9; g++) ldg2(res + 2 * g, p + (g >> 1) * 512 + ((g & 1) ? ((j & 1) ? 504 : 8) : 0));
        const uint4* src = xbase + 16 * SLAB + lane;
        {
          const uint4* fp = scr + OFF_S + (8 + w) * 96 + q * 8 + r;
          uint32_t s0[4], s1[4];
          int n = 0;
          STAMP(8);
          while (true) {
            ldg4(s0, fp); ldg4(s1, fp + 32);
            if (__all_sync(~0u, ((s0[0] ^ tag) | (s1[0] ^ tag)) % 2u == 0u)) break;
            SPIN_GUARD(n);
          }
          STAMP(9);
        }
#pragma unroll
        for (int kb = 0; kb < GD; kb++) load_kb(kb, src, (const char*)src - lane * 8, 256);
        float acc[36];
        mbar_wait(remo_full, layer);
#pragma unroll
        for (int kb = 0; kb < 9; kb++) {
          next_kb(false, kb, src, (const char*)src - lane * 8, 256);
          if (!(kb & 1)) mbar_wait(full0 + rg.st * 8, rg.ph);
          const uint32_t base = sb + rg.st * STAGE + (kb & 1) * 8192;
          const uint64_t d0 = DESC_HI | ((base >> 4) + (((sb + REM + 27648 + (kb >> 1) * 2048 + (kb & 1) * 64 - base) >> 4) << 16));
          wg_fence();
#pragma unroll
          for (int i = 0; i < 4; i++) wgmma_rs_n72(acc, X + 4 * (4 * kb + i), d0 - (uint64_t)(i * ((127u << 16) - 128u)), kb + i != 0);
          wg_commit();
          wg_wait<1>();
          if (kb > 0 && !(kb & 1)) release(prev);
          if ((kb & 1) || kb == 8) { prev = rg.st; rg.next(); }
        }
        wg_wait<0>();
        release(prev);
        pin(acc);
        STAMP(10);
#pragma unroll
        for (int i = 0; i < 18; i++) {
          acc[2 * i] += bf_lo(res[i]); acc[2 * i + 1] += bf_hi(res[i]);
          res[i] = pack_bf16(acc[2 * i], acc[2 * i + 1]);
        }
        put72(xbase + 32 * SLAB, j, lane, res);
        publish_stats<9>(scr + OFF_S + (16 + w) * 96 + j * 8, acc, tag, lane);
      }
      continue;
      }
      const uint32_t hp = sb + PARK + w * 512 + lane * 16;
      auto pack8 = [&](float (&a)[32], int p, uint32_t* o) {
#pragma unroll
        for (int e = 0; e < 8; e++) asm volatile("" : "+f"(a[8 * p + e]) :: "memory");
#pragma unroll
        for (int e = 0; e < 4; e++) o[e] = pack_bf16(a[8 * p + 2 * e], a[8 * p + 2 * e + 1]);
      };
      const float ka0 = 0.7978845608028654f * rs0, kb0 = 0.044715f * ka0 * rs0 * rs0, ku0 = 0.5f * rs0 * rs0;
      const float ka1 = 0.7978845608028654f * rs1, kb1 = 0.044715f * ka1 * rs1 * rs1, ku1 = 0.5f * rs1 * rs1;
      auto packu8 = [&](int p, uint32_t* o) {
#pragma unroll
        for (int e = 0; e < 8; e++) asm volatile("" : "+f"(aA[8 * p + e]) :: "memory");
#pragma unroll
        for (int e = 0; e < 4; e++) o[e] = pack_bf16(aA[8 * p + 2 * e] * ((e & 1) ? ku1 : ku0), aA[8 * p + 2 * e + 1] * ((e & 1) ? ku1 : ku0));
      };
      auto geglu8 = [&](int p, uint32_t* u) {
#pragma unroll
        for (int e = 0; e < 8; e++) asm volatile("" : "+f"(aB[8 * p + e]) :: "memory");
        float h[8];
#pragma unroll
        for (int e = 0; e < 8; e++) {
          const float g = aB[8 * p + e];
          h[e] = fmaf(g, tanh_ap(g * fmaf(g * g, (e & 2) ? kb1 : kb0, (e & 2) ? ka1 : ka0)), g);
        }
#pragma unroll
        for (int e = 0; e < 4; e++) u[e] = mul_bf16x2(pack_bf16(h[2 * e], h[2 * e + 1]), u[e]);
      };
      auto box = [&](int b, auto&& filler) {
        const int kb = b < 9 ? b : b - 9;
        if (!(b & 1)) mbar_wait(full0 + rg.st * 8, rg.ph);
        const uint64_t desc = DESC_HI | ((sb + rg.st * STAGE + (b & 1) * 8192) >> 4);
        wg_fence();
#pragma unroll
        for (int i = 0; i < 4; i++) {
          if (b < 9) wgmma_rs_n64(aA, X + 4 * (4 * kb + i), desc + i * 128, kb + i != 0);
          else wgmma_rs_n64(aB, X + 4 * (4 * kb + i), desc + i * 128, kb + i != 0);
          if (i == FPOS) filler();
        }
        wg_commit();
        if (b & 1) { if (W2) wg_wait<1>(); prev = rg.st; rg.next(); } else { wg_wait<1>(); release(prev); }
      };
      auto nop = [] {};
      auto step = [&](int st, auto&& filler) { box(2 * st, nop); box(2 * st + 1, filler); };
#pragma unroll
      for (int p = 0; p < 4; p++) { uint32_t o[4]; packu8(p, o); sts4(hp + p * 4096, o); }
      box(0, nop);
      zero_share(xbase, j, lane);
      zero_share(xbase + 16 * SLAB, j, lane);
#pragma unroll 1
      for (int c = 1;; c++) {
        const uint32_t hc = hp + c * 4 * 4096;
#pragma unroll
        for (int b = 1; b < 18; b++) box(b, [&] {
          if ((b & 1) && b < 8) { uint32_t o[4]; const uint32_t a = hc - (4 - (b >> 1)) * 4096; lds4(a, o); geglu8(b >> 1, o); sts4(a, o); }
          if ((b & 1) && b > 10) { uint32_t o[4]; packu8((b - 11) >> 1, o); if (c < 8) sts4(hc + ((b - 11) >> 1) * 4096, o); } });
        if (c == 8) break;
        box(0, nop);
      }
      wg_wait<0>();
      STAMP(21);
      GSTAMP(19);
#pragma unroll
      for (int s = 0; s < 32; s++) lds4(hp + s * 4096, X + 4 * s);
#pragma unroll
      for (int p = 0; p < 4; p++) packu8(p, X + 128 + 4 * p);
#pragma unroll
      for (int st = 0; st < 4; st++) step(st, [&] { geglu8(st, X + 128 + 4 * st); });
      STAMP(24);
      if (layer == 0 && lane == 0) mbar_arrive(park_free);
      const uint32_t lane2 = lane_id();
      uint4* const pw = scr + OFF_P + (j * 8 + w) * SLAB + lane2;
      const uint4* const pr = scr + OFF_P + w * SLAB + 4 * j * 32 + lane2;
      auto put_part = [&](float (&a)[32], int p, uint32_t chunk) {
        uint32_t o[4];
        pack8(a, p, o);
        stg4(pw + (chunk * 4 + p) * 32, (o[0] & ~1u) | tag, o[1], o[2], o[3]);
      };
      auto slot = [&](int p) { return sb + w * 2048 + (p < 4 ? PARK + (p - 1) * 16384 : KVS + (p - 4) * 16384); };
      auto fetch = [&](int p) {
        if (p > 0) bulk_load(slot(p), scr + OFF_P + (((j - p) & 7) * 8 + w) * SLAB + 4 * j * 32, 2048, pbar0 + w * 8, true);
      };
      uint4* const xb = xbase + 32 * SLAB + 4 * j * 32;
#pragma unroll 1
      for (int sp = 0;; sp++) {
        const uint32_t ca = sp == 0 ? 8 : ((j + 2 * sp) & 7), cb = (j + 2 * sp + 1) & 7;
        if (sp == 1 && lane == 0) mbar_arrive(c8_go);
#pragma unroll
        for (int st = 4; st < 9; st++) step(st, [&] {
          if (st == 5 || st == 6) { put_part(aA, 2 * (st - 5), ca); put_part(aA, 2 * (st - 5) + 1, ca); }
          if (st == 8) { if (sp == 3) mbar_wait(c8_done, layer); fetch(2 * sp - 1); } });
        STAMP(25 + sp);
        if (sp == 3) break;
        if (sp == 2 && layer == 0 && (lane2 & 3) == 0) {
#pragma unroll
          for (int k = 0; k < 3; k++) stg4(scr + OFF_S + (k * 8 + w) * 96 + j * 8 + (lane2 >> 2), 1u, 0u, 0u, 0u);
        }
        if (sp == 2) asm volatile("{\n.reg .pred e;\nelect.sync _|e, 0xffffffff;\n@e cp.async.bulk.prefetch.L2.global [%0], 2048;\n}" :: "l"(xb) : "memory");
#pragma unroll
        for (int st = 0; st < 4; st++) step(st, [&] {
          if (st < 2) { put_part(aB, 2 * st, cb); put_part(aB, 2 * st + 1, cb); }
          if (st == 3) fetch(2 * sp); });
      }
      auto load_p = [&](int p, uint32_t* d) {
#pragma unroll
        for (int i = 0; i < 4; i++) ldg4(d + 4 * i, pr + ((j - p) & 7) * 8 * SLAB + i * 32);
      };
#pragma unroll
      for (int st = 0; st < 4; st++) step(st, [&] {
        if (st == 0) {
#pragma unroll
          for (int p = 0; p < 4; p++) put_part(aB, p, (j + 7) & 7);
        }
        if (st == 1) {
#pragma unroll
          for (int i = 0; i < 4; i++) {
            const bool split = j == 2 * i + 1;
            const char* l = (const char*)(xb + i * 32) + (split ? lane2 * 8 : lane2 * 16);
            ldg2(X + 4 * i, l); ldg2(X + 4 * i + 2, l + (split ? 256 : 8));
          }
          load_p(6, X + 16);
        }
        if (st == 3) load_p(7, X + 32); });
      STAMP(13);
      {
        mbar_wait(full0 + rg.st * 8, rg.ph);
        const uint64_t desc = DESC_HI | ((sb + rg.st * STAGE) >> 4);
        wg_fence();
#pragma unroll
        for (int i = 0; i < 4; i++) wgmma_rs_n64(aA, X + 4 * (32 + i), desc + i * 128, 1);
        wg_commit();
        wg_wait<1>(); release(prev);
        prev = rg.st; rg.next();
        mbar_wait(pbar0 + w * 8, layer);
        wg_wait<0>(); release(prev);
        pin(aA);
      }
      STAMP(22);
      GSTAMP(20);
      {
        const uint32_t eye = r == 2 * q ? 0x3f80u : r == 2 * q + 1 ? 0x3f800000u : 0u;
        auto add_p = [&](int p, uint32_t* d) {
          int n = 0;
          while (!__all_sync(~0u, (((d[0] ^ tag) | (d[4] ^ tag) | (d[8] ^ tag) | (d[12] ^ tag)) & 1u) == 0u)) { SPIN_GUARD(n); load_p(p, d); }
#pragma unroll
          for (int g = 0; g < 8; g++) mma8(aA + 4 * g, d[2 * g], d[2 * g + 1], eye);
        };
#pragma unroll
        for (int p = 1; p < 6; p++)
#pragma unroll
          for (int i = 0; i < 4; i++) lds4(slot(p) + lane2 * 16 + i * 512, X + 32 + 16 * p + 4 * i);
#pragma unroll
        for (int g = 0; g < 8; g++) mma8(aA + 4 * g, X[2 * g], X[2 * g + 1], eye);
#pragma unroll
        for (int p = 1; p < 6; p++) add_p(p, X + 32 + 16 * p);
        add_p(6, X + 16);
        STAMP(11);
        add_p(7, X + 32);
        STAMP(12);
        uint32_t res[16];
#pragma unroll
        for (int i = 0; i < 16; i++) res[i] = pack_bf16(aA[2 * i], aA[2 * i + 1]);
        if (layer == 0) {
          uint4* p = xbase + 8 * SLAB + 4 * j * 32 + lane;
#pragma unroll
          for (int i = 0; i < 4; i++) stg4(p + i * 32, nz(res[4 * i]), res[4 * i + 1], nz(res[4 * i + 2]), res[4 * i + 3]);
          publish_stats<8>(scr + OFF_S + w * 96 + j * 8, aA, 0u, lane);
          if (lane == 0) mbar_arrive(kv_free);
        } else {
          uint32_t* o = (uint32_t*)(out + (128 * t + 32 * (w >> 1) + 2 * r + (w & 1)) * 576 + 64 * j + 2 * q);
#pragma unroll
          for (int g = 0; g < 8; g++) { o[4 * g] = res[2 * g]; o[8 * 576 + 4 * g] = res[2 * g + 1]; }
        }
#pragma unroll
        for (int i = 0; i < 4; i++) stg4(xb + lane + i * 32, 0u, 0u, 0u, 0u);
      }
      STAMP(23);
    }
  }
}

typedef CUresult (*EncodeFn)(CUtensorMap*, CUtensorMapDataType, cuuint32_t, void*, const cuuint64_t*, const cuuint64_t*,
                             const cuuint32_t*, const cuuint32_t*, CUtensorMapInterleave, CUtensorMapSwizzle,
                             CUtensorMapL2promotion, CUtensorMapFloatOOBfill);

CUtensorMap make_map(EncodeFn f, const void* p, uint64_t cols, uint64_t rows, bool rem = false) {
  CUtensorMap m;
  cuuint64_t dims[2] = {cols, rows};
  cuuint64_t str[1] = {cols * 2};
  cuuint32_t box[2] = {rem ? 8u : 64u, rem ? 144u : 64u};
  cuuint32_t es[2] = {1, 1};
  f(&m, CU_TENSOR_MAP_DATA_TYPE_BFLOAT16, 2, const_cast<void*>(p), dims, str, box, es, CU_TENSOR_MAP_INTERLEAVE_NONE,
    rem ? CU_TENSOR_MAP_SWIZZLE_NONE : CU_TENSOR_MAP_SWIZZLE_128B, CU_TENSOR_MAP_L2_PROMOTION_NONE, CU_TENSOR_MAP_FLOAT_OOB_FILL_NONE);
  return m;
}

}

extern "C" void kernel_launch(void* const* d_in, const int* in_sizes, int n_in, void* d_out, int out_size) {
  void* fn = nullptr;
  cudaDriverEntryPointQueryResult qr;
  cudaGetDriverEntryPoint("cuTensorMapEncodeTiled", &fn, cudaEnableDefault, &qr);
  EncodeFn enc = (EncodeFn)fn;
  Maps maps;
  maps.m[0] = make_map(enc, d_in[1], 1728, 576); maps.m[1] = make_map(enc, d_in[2], 576, 576);
  maps.m[2] = make_map(enc, d_in[4], 4608, 576); maps.m[3] = make_map(enc, d_in[5], 4608, 576); maps.m[4] = make_map(enc, d_in[6], 576, 4608);
  maps.m[5] = make_map(enc, d_in[1], 1728, 576, true); maps.m[6] = make_map(enc, d_in[2], 576, 576, true);
  void* scr = nullptr;
  cudaGetSymbolAddress(&scr, g_scratch);
  cudaFuncSetAttribute(mega_kernel, cudaFuncAttributeMaxDynamicSharedMemorySize, SMEM_BYTES);
  mega_kernel<<<128, 384, SMEM_BYTES>>>(maps, (uint4*)scr, (const __nv_bfloat16*)d_in[0], (__nv_bfloat16*)d_out);
}
```

```cpp
#include <cuda_runtime.h>
#include <cuda.h>
#include <cuda_bf16.h>
#include <stdint.h>

#define TRACE 0
#define EXP 0
#define FPOS 2
#define W2 0

namespace {

constexpr int NST = 6;
constexpr int STAGE = 16384;
constexpr int PARK = NST * STAGE;
constexpr int REM = PARK + 49152;
constexpr int KVS = REM + 40960;
constexpr int HSTG = KVS + 16384;
constexpr int BARS = KVS + 41472;
constexpr int TRC = BARS + 256;
constexpr int SMEM_BYTES = TRC + (TRACE ? 512 : 0);
static_assert(NST == 6, "the producer addresses empty barriers as full + 48");
static_assert(BARS >= PARK + 131072, "barriers overlap park");
static_assert(SMEM_BYTES <= 232448, "smem");

constexpr int SLAB = 36 * 32;
constexpr int SPIN_MAX = 1 << 17;
constexpr int GD = 3;
constexpr int OFF_S = 0;
constexpr int OFF_H = OFF_S + 3 * 8 * 96;
constexpr int OFF_X = OFF_H + 2 * 8 * 384;
constexpr int OFF_P = OFF_X + 6 * 8 * SLAB;
constexpr int TILE = OFF_P + 8 * 8 * SLAB;
constexpr int OFF_R = 16 * TILE;
constexpr int OFF_F = OFF_R + 8 * 2304;
constexpr int SCRATCH = OFF_F + 128 * 8;

}

__device__ uint4 g_scratch[SCRATCH];

namespace {

constexpr uint64_t DESC_HI = 0x4000004000000000ull;
constexpr uint64_t DESC_REM = (576ull << 32) | (8u << 16);
__device__ __forceinline__ void wgmma_rs_n64(float (&d)[32], const uint32_t* a, uint64_t desc, int scale_d) {
  asm volatile("{\n.reg .pred p;\nsetp.ne.b32 p, %37, 0;\n"
    "wgmma.mma_async.sync.aligned.m64n64k16.f32.bf16.bf16 "
    "{%0, %1, %2, %3, %4, %5, %6, %7, %8, %9, %10, %11, %12, %13, %14, %15, %16, %17, %18, %19, %20, %21, %22, %23, %24, %25, %26, %27, %28, %29, %30, %31}, "
    "{%32, %33, %34, %35}, %36, p, 1, 1, 1;\n}\n"
    : "+f"(d[0]), "+f"(d[1]), "+f"(d[2]), "+f"(d[3]), "+f"(d[4]), "+f"(d[5]), "+f"(d[6]), "+f"(d[7]), "+f"(d[8]), "+f"(d[9]), "+f"(d[10]), "+f"(d[11]), "+f"(d[12]), "+f"(d[13]), "+f"(d[14]), "+f"(d[15]), "+f"(d[16]), "+f"(d[17]), "+f"(d[18]), "+f"(d[19]), "+f"(d[20]), "+f"(d[21]), "+f"(d[22]), "+f"(d[23]), "+f"(d[24]), "+f"(d[25]), "+f"(d[26]), "+f"(d[27]), "+f"(d[28]), "+f"(d[29]), "+f"(d[30]), "+f"(d[31])
    : "r"(a[0]), "r"(a[1]), "r"(a[2]), "r"(a[3]), "l"(desc), "r"(scale_d));
}
__device__ __forceinline__ void wgmma_rs_n72(float (&d)[36], const uint32_t* a, uint64_t desc, int scale_d) {
  asm volatile("{\n.reg .pred p;\nsetp.ne.b32 p, %41, 0;\n"
    "wgmma.mma_async.sync.aligned.m64n72k16.f32.bf16.bf16 "
    "{%0, %1, %2, %3, %4, %5, %6, %7, %8, %9, %10, %11, %12, %13, %14, %15, %16, %17, %18, %19, %20, %21, %22, %23, %24, %25, %26, %27, %28, %29, %30, %31, %32, %33, %34, %35}, "
    "{%36, %37, %38, %39}, %40, p, 1, 1, 1;\n}\n"
    : "+f"(d[0]), "+f"(d[1]), "+f"(d[2]), "+f"(d[3]), "+f"(d[4]), "+f"(d[5]), "+f"(d[6]), "+f"(d[7]), "+f"(d[8]), "+f"(d[9]), "+f"(d[10]), "+f"(d[11]), "+f"(d[12]), "+f"(d[13]), "+f"(d[14]), "+f"(d[15]), "+f"(d[16]), "+f"(d[17]), "+f"(d[18]), "+f"(d[19]), "+f"(d[20]), "+f"(d[21]), "+f"(d[22]), "+f"(d[23]), "+f"(d[24]), "+f"(d[25]), "+f"(d[26]), "+f"(d[27]), "+f"(d[28]), "+f"(d[29]), "+f"(d[30]), "+f"(d[31]), "+f"(d[32]), "+f"(d[33]), "+f"(d[34]), "+f"(d[35])
    : "r"(a[0]), "r"(a[1]), "r"(a[2]), "r"(a[3]), "l"(desc), "r"(scale_d));
}
__device__ __forceinline__ void wgmma_rs_n24(float (&d)[12], const uint32_t* a, uint64_t desc, int scale_d) {
  asm volatile("{\n.reg .pred p;\nsetp.ne.b32 p, %17, 0;\n"
    "wgmma.mma_async.sync.aligned.m64n24k16.f32.bf16.bf16 "
    "{%0, %1, %2, %3, %4, %5, %6, %7, %8, %9, %10, %11}, "
    "{%12, %13, %14, %15}, %16, p, 1, 1, 1;\n}\n"
    : "+f"(d[0]), "+f"(d[1]), "+f"(d[2]), "+f"(d[3]), "+f"(d[4]), "+f"(d[5]), "+f"(d[6]), "+f"(d[7]), "+f"(d[8]), "+f"(d[9]), "+f"(d[10]), "+f"(d[11])
    : "r"(a[0]), "r"(a[1]), "r"(a[2]), "r"(a[3]), "l"(desc), "r"(scale_d));
}

__device__ __forceinline__ void mbar_init(uint32_t a, uint32_t c) { asm volatile("mbarrier.init.shared::cta.b64 [%0], %1;" :: "r"(a), "r"(c)); }
__device__ __forceinline__ void mbar_arrive(uint32_t a) { asm volatile("mbarrier.arrive.shared::cta.b64 _, [%0];" :: "r"(a) : "memory"); }
__device__ __forceinline__ void mbar_wait(uint32_t a, uint32_t ph) {
  asm volatile("{\n.reg .pred p;\n.reg .u32 n;\n"
               "mbarrier.try_wait.parity.shared::cta.b64 p, [%0], %1;\n@p bra D;\n"
               "mov.u32 n, 0;\n"
               "W: mbarrier.try_wait.parity.shared::cta.b64 p, [%0], %1;\n@p bra D;\n"
               "add.u32 n, n, 1;\nsetp.lt.u32 p, n, 4194304;\n@p bra W;\ntrap;\nD:\n}" :: "r"(a), "r"(ph) : "memory");
}
__device__ __forceinline__ void wg_fence() { asm volatile("wgmma.fence.sync.aligned;" ::: "memory"); }
__device__ __forceinline__ void wg_commit() { asm volatile("wgmma.commit_group.sync.aligned;" ::: "memory"); }
template <int N> __device__ __forceinline__ void wg_wait() { asm volatile("wgmma.wait_group.sync.aligned %0;" :: "n"(N) : "memory"); }
__device__ __forceinline__ float tanh_ap(float x) { float y; asm("tanh.approx.f32 %0, %1;" : "=f"(y) : "f"(x)); return y; }
__device__ __forceinline__ float ex2(float x) { float y; asm("ex2.approx.ftz.f32 %0, %1;" : "=f"(y) : "f"(x)); return y; }
__device__ __forceinline__ uint32_t pack_bf16(float lo, float hi) { uint32_t r; asm("cvt.rn.bf16x2.f32 %0, %1, %2;" : "=r"(r) : "f"(hi), "f"(lo)); return r; }
__device__ __forceinline__ float bf_lo(uint32_t v) { return __uint_as_float(v << 16); }
__device__ __forceinline__ float bf_hi(uint32_t v) { return __uint_as_float(v & 0xffff0000u); }
__device__ __forceinline__ uint32_t sub_bf16x2(uint32_t a, uint32_t b) { uint32_t r; asm("sub.rn.bf16x2 %0, %1, %2;" : "=r"(r) : "r"(a), "r"(b)); return r; }
__device__ __forceinline__ uint32_t mul_bf16x2(uint32_t a, uint32_t b) { uint32_t r; asm("mul.rn.bf16x2 %0, %1, %2;" : "=r"(r) : "r"(a), "r"(b)); return r; }
__device__ __forceinline__ uint32_t nz(uint32_t w) { return w == 0u ? 0x8000u : w; }

__device__ __forceinline__ void ldg4(uint32_t* d, const uint4* p) {
  asm volatile("ld.relaxed.gpu.global.v4.b32 {%0,%1,%2,%3}, [%4];" : "=r"(d[0]), "=r"(d[1]), "=r"(d[2]), "=r"(d[3]) : "l"(p) : "memory");
}
__device__ __forceinline__ void ldg2(uint32_t* d, const void* p) {
  asm volatile("ld.relaxed.gpu.global.v2.b32 {%0,%1}, [%2];" : "=r"(d[0]), "=r"(d[1]) : "l"(p) : "memory");
}
__device__ __forceinline__ void stg4(uint4* p, uint32_t a, uint32_t b, uint32_t c, uint32_t d) {
  asm volatile("st.relaxed.gpu.global.v4.b32 [%0], {%1,%2,%3,%4};" :: "l"(p), "r"(a), "r"(b), "r"(c), "r"(d) : "memory");
}
__device__ __forceinline__ void stg2(void* p, uint32_t a, uint32_t b) {
  asm volatile("st.relaxed.gpu.global.v2.b32 [%0], {%1,%2};" :: "l"(p), "r"(a), "r"(b) : "memory");
}
__device__ __forceinline__ void sts4(uint32_t a, const uint32_t* o) { asm volatile("st.shared.v4.b32 [%0], {%1,%2,%3,%4};" :: "r"(a), "r"(o[0]), "r"(o[1]), "r"(o[2]), "r"(o[3]) : "memory"); }
__device__ __forceinline__ void lds4(uint32_t a, uint32_t* o) { asm volatile("ld.shared.v4.b32 {%0,%1,%2,%3}, [%4];" : "=r"(o[0]), "=r"(o[1]), "=r"(o[2]), "=r"(o[3]) : "r"(a) : "memory"); }
__device__ __forceinline__ void lds2(uint32_t a, uint32_t* o) { asm volatile("ld.shared.v2.b32 {%0,%1}, [%2];" : "=r"(o[0]), "=r"(o[1]) : "r"(a) : "memory"); }
__device__ __forceinline__ float rcp(float x) { float y; asm("rcp.approx.ftz.f32 %0, %1;" : "=f"(y) : "f"(x)); return y; }
__device__ __forceinline__ void sts1(uint32_t a, uint32_t v) { asm volatile("st.shared.b32 [%0], %1;" :: "r"(a), "r"(v) : "memory"); }
__device__ __forceinline__ void ldsm4(uint32_t a, uint32_t& r0, uint32_t& r1, uint32_t& r2, uint32_t& r3) {
  asm volatile("ldmatrix.sync.aligned.m8n8.x4.shared.b16 {%0,%1,%2,%3}, [%4];" : "=r"(r0), "=r"(r1), "=r"(r2), "=r"(r3) : "r"(a) : "memory");
}
__device__ __forceinline__ void ldsm4t(uint32_t a, uint32_t& r0, uint32_t& r1, uint32_t& r2, uint32_t& r3) {
  asm volatile("ldmatrix.sync.aligned.m8n8.x4.trans.shared.b16 {%0,%1,%2,%3}, [%4];" : "=r"(r0), "=r"(r1), "=r"(r2), "=r"(r3) : "r"(a) : "memory");
}
__device__ __forceinline__ void mma16(float* c, uint32_t a0, uint32_t a1, uint32_t a2, uint32_t a3, uint32_t b0, uint32_t b1) {
  asm("mma.sync.aligned.m16n8k16.row.col.f32.bf16.bf16.f32 {%0,%1,%2,%3}, {%4,%5,%6,%7}, {%8,%9}, {%0,%1,%2,%3};"
    : "+f"(c[0]), "+f"(c[1]), "+f"(c[2]), "+f"(c[3]) : "r"(a0), "r"(a1), "r"(a2), "r"(a3), "r"(b0), "r"(b1));
}
__device__ __forceinline__ void mma8(float* c, uint32_t a0, uint32_t a1, uint32_t b0) {
  asm("mma.sync.aligned.m16n8k8.row.col.f32.bf16.bf16.f32 {%0,%1,%2,%3}, {%4,%5}, {%6}, {%0,%1,%2,%3};"
    : "+f"(c[0]), "+f"(c[1]), "+f"(c[2]), "+f"(c[3]) : "r"(a0), "r"(a1), "r"(b0));
}
__device__ __forceinline__ uint32_t lane_id() { uint32_t l; asm volatile("mov.u32 %0, %%laneid;" : "=r"(l)); return l; }
__device__ __forceinline__ float quad_sum(float v) { v += __shfl_xor_sync(~0u, v, 1); v += __shfl_xor_sync(~0u, v, 2); return v; }
__device__ __forceinline__ float quad_max(float v) { v = fmaxf(v, __shfl_xor_sync(~0u, v, 1)); v = fmaxf(v, __shfl_xor_sync(~0u, v, 2)); return v; }
template <int N> __device__ __forceinline__ void pin(float (&d)[N]) {
#pragma unroll
  for (int i = 0; i < N; i++) asm volatile("" : "+f"(d[i]) :: "memory");
}
#define SPIN_GUARD(n) if (++(n) > SPIN_MAX) break

template <int NG> __device__ __forceinline__ void publish_stats(uint4* dst, const float* y, uint32_t tag, uint32_t lane) {
  float s0 = 0.f, s1 = 0.f;
#pragma unroll
  for (int g = 0; g < NG; g++) { s0 += y[4 * g] + y[4 * g + 1]; s1 += y[4 * g + 2] + y[4 * g + 3]; }
  s0 = quad_sum(s0); s1 = quad_sum(s1);
  const float m0 = s0 * (1.f / (8 * NG)), m1 = s1 * (1.f / (8 * NG));
  float q0 = 0.f, q1 = 0.f, q2 = 0.f, q3 = 0.f;
#pragma unroll
  for (int g = 0; g < NG; g++) {
    const float a = y[4 * g] - m0, b = y[4 * g + 1] - m0, c = y[4 * g + 2] - m1, d = y[4 * g + 3] - m1;
    q0 = fmaf(a, a, q0); q1 = fmaf(b, b, q1); q2 = fmaf(c, c, q2); q3 = fmaf(d, d, q3);
  }
  q0 = quad_sum(q0 + q1); q2 = quad_sum(q2 + q3);
  if ((lane & 3) == 0)
    stg4(dst + (lane >> 2), (__float_as_uint(s0) & ~1u) | tag, __float_as_uint(q0), __float_as_uint(s1), __float_as_uint(q2));
}

__device__ __forceinline__ void put72(uint4* slab, uint32_t j, uint32_t lane, const uint32_t* v, uint32_t r0, uint32_t r1) {
  uint4* p = slab + ((9 * j + 1) >> 1) * 32;
#pragma unroll
  for (int i = 0; i < 4; i++) stg4(p + lane + i * 32, nz(v[4 * i]), v[4 * i + 1], v[4 * i + 2], v[4 * i + 3]);
  stg2((char*)((j & 1) ? p - 16 : p + 4 * 32) + lane * 8, nz(r0), r1);
}
__device__ __forceinline__ void zero_share(uint4* slab, uint32_t j, uint32_t lane) {
  uint4* p = slab + j * 144 + lane;
#pragma unroll
  for (int i = 0; i < 4; i++) stg4(p + i * 32, 0u, 0u, 0u, 0u);
  if (lane < 16) stg4(p + 128, 0u, 0u, 0u, 0u);
}

struct Maps { CUtensorMap m[7]; };

struct Ring {
  uint32_t st, ph;
  __device__ __forceinline__ void next() { if (++st == NST) { st = 0; ph ^= 1; } }
};

#define GSTAMP(i) do {} while (0)
#define STAMP(i) do {} while (0)

__device__ __forceinline__ void tma_box(uint32_t dst, const CUtensorMap* m, int col, int row, uint32_t bar, uint32_t expect) {
  asm volatile("{\n.reg .pred e, h;\nelect.sync _|e, 0xffffffff;\nsetp.ne.and.u32 h, %5, 0, e;\n"
               "@h mbarrier.arrive.expect_tx.shared::cta.b64 _, [%2], %5;\n"
               "@e cp.async.bulk.tensor.2d.shared::cluster.global.mbarrier::complete_tx::bytes [%0], [%1, {%3, %4}], [%2];\n}"
               :: "r"(dst), "l"(m), "r"(bar), "r"(col), "r"(row), "r"(expect) : "memory");
}

__device__ __forceinline__ void bulk_load(uint32_t dst, const void* src, uint32_t bytes, uint32_t bar, bool arm) {
  asm volatile("{\n.reg .pred e, h;\nelect.sync _|e, 0xffffffff;\nsetp.ne.and.u32 h, %4, 0, e;\n"
               "@h mbarrier.arrive.expect_tx.shared::cta.b64 _, [%3], %2;\n"
               "@e cp.async.bulk.shared::cluster.global.mbarrier::complete_tx::bytes [%0], [%1], %2, [%3];\n}"
               :: "r"(dst), "l"(src), "r"(bytes), "r"(bar), "r"((uint32_t)arm) : "memory");
}

__global__ void __launch_bounds__(384, 1) mega_kernel(
    const __grid_constant__ Maps maps, uint4* __restrict__ scratch,
    const __nv_bfloat16* __restrict__ x_in, __nv_bfloat16* __restrict__ out) {
  extern __shared__ __align__(1024) uint8_t smem[];
  const uint32_t sb = (uint32_t)__cvta_generic_to_shared(smem);
  const uint32_t full0 = sb + BARS, empty0 = full0 + 8 * NST, rem_full = empty0 + 8 * NST, park_free = rem_full + 8, kv_free = park_free + 8;
  const uint32_t c8_go = kv_free + 8, c8_done = c8_go + 8, c8_full = c8_done + 8, remo_full = c8_full + 8, piece_full = remo_full + 8, pbar0 = piece_full + 8;
  const uint32_t w = __shfl_sync(~0u, threadIdx.x >> 5, 0);
  const uint32_t t = blockIdx.x >> 3, j = blockIdx.x & 7;
  const uint32_t odd = j & 1;
  uint4* const scr = scratch + t * TILE;
  {
    const uint32_t lane = lane_id(), r = lane >> 2, q = lane & 3;
    const uint32_t sl = w < 8 ? w : j, ch = w < 8 ? j : 8;
    const uint32_t* xr = (const uint32_t*)(x_in + (128 * t + 32 * (sl >> 1) + 2 * r + (sl & 1)) * 576 + 64 * ch + 2 * q);
    if (w < 8 || w == 9) {
      uint32_t v[16];
#pragma unroll
      for (int g = 0; g < 8; g++) {
        asm volatile("ld.global.nc.b32 %0, [%1];" : "=r"(v[2 * g]) : "l"(xr + 4 * g));
        asm volatile("ld.global.nc.b32 %0, [%1];" : "=r"(v[2 * g + 1]) : "l"(xr + 8 * 576 + 4 * g));
      }
      if (q == 0) {
#pragma unroll
        for (int k = 0; k < 3; k++) stg4(scr + OFF_S + (k * 8 + sl) * 96 + ch * 8 + r, 0u, 0u, 0u, 0u);
      }
      asm volatile("bar.sync 0, 384;" ::: "memory");
      uint4* p = scr + OFF_X + sl * SLAB + 4 * ch * 32 + lane;
#pragma unroll
      for (int i = 0; i < 4; i++) stg4(p + i * 32, nz(v[4 * i]), v[4 * i + 1], nz(v[4 * i + 2]), v[4 * i + 3]);
      float y[32];
#pragma unroll
      for (int i = 0; i < 16; i++) { y[2 * i] = bf_lo(v[i]); y[2 * i + 1] = bf_hi(v[i]); }
      publish_stats<8>(scr + OFF_S + sl * 96 + ch * 8, y, 1u, lane);
    } else {
      if (threadIdx.x == 256) {
        for (int i = 0; i < NST; i++) { mbar_init(full0 + 8 * i, 1); mbar_init(empty0 + 8 * i, 8); }
        mbar_init(rem_full, 1); mbar_init(park_free, 8); mbar_init(kv_free, 8); mbar_init(c8_go, 8); mbar_init(c8_done, 1); mbar_init(c8_full, 1); mbar_init(remo_full, 64); mbar_init(piece_full, 1);
        for (int i = 0; i < 8; i++) mbar_init(pbar0 + 8 * i, 5);
        asm volatile("fence.mbarrier_init.release.cluster;" ::: "memory");
      }
      __syncwarp();
      asm volatile("bar.sync 0, 384;" ::: "memory");
    }
  }

  if (w >= 8) {
    asm volatile("setmaxnreg.dec.sync.aligned.u32 24;");
    if (w == 8) {
      uint32_t dst = sb, bar = full0, ph = 1;
#pragma unroll 1
      for (int seg = 0; seg < 34; seg++) {
        const int n = seg >= 17 ? seg - 17 : seg;
        int ma, mb, ca, cb, row = 0;
        if (n < 3) { ma = mb = n == 2; ca = 72 * j + 8 * odd + (n == 0 ? 576 : 0); cb = ca + 576; }
        else if (n < 12) { ma = 3; mb = 2; ca = cb = 576 * j + 64 * (n - 3); }
        else { ma = mb = 4; ca = n == 12 ? 512 : ((j + 2 * n) & 7) * 64; cb = ((j + 2 * n + 1) & 7) * 64; row = 576 * j; }
        const bool zip = n == 0 || n == 3, solo = n == 1 || n == 2 || n == 16;
        const CUtensorMap *pa = &maps.m[ma], *pb = &maps.m[mb];
#pragma unroll 1
        for (int st = 0; st < (solo ? 5 : 9); st++) {
          const bool s0 = !zip && st > 4, s1 = zip || st >= 4;
          const int r0 = row + (zip ? 64 * st : s0 ? 128 * st - 576 : 128 * st), r1 = zip ? r0 : st == 4 ? row : r0 + 64;
          asm volatile("{\n.reg .pred p, e, f;\n.reg .u32 n;\nelect.sync _|e, 0xffffffff;\nsetp.eq.and.u32 f, %9, 16384, e;\nmov.u32 n, 0;\n"
                       "W: mbarrier.try_wait.parity.shared::cta.b64 p, [%1+48], %2;\n@p bra D;\n"
                       "add.u32 n, n, 1;\nsetp.lt.u32 p, n, 4194304;\n@p bra W;\ntrap;\n"
                       "D: @e mbarrier.arrive.expect_tx.shared::cta.b64 _, [%1], %9;\n"
                       "@e cp.async.bulk.tensor.2d.shared::cluster.global.mbarrier::complete_tx::bytes [%0], [%3, {%4, %5}], [%1];\n"
                       "@f cp.async.bulk.tensor.2d.shared::cluster.global.mbarrier::complete_tx::bytes [%0+8192], [%6, {%7, %8}], [%1];\n}"
                       :: "r"(dst), "r"(bar), "r"(ph), "l"(s0 ? pb : pa), "r"(s0 ? cb : ca), "r"(r0), "l"(s1 ? pb : pa), "r"(s1 ? cb : ca), "r"(r1),
                          "r"(solo && st == 4 ? STAGE / 2 : STAGE) : "memory");
          dst += STAGE; bar += 8;
          if (bar == full0 + 8 * NST) { dst = sb; bar = full0; ph ^= 1; }
        }
      }
    } else if (w == 9) {
      const uint32_t lane = lane_id();
      const uint32_t stg = sb + HSTG + lane * 16;
      uint32_t fph = 0;
#pragma unroll 1
      for (uint32_t layer = 0; layer < 2; layer++) {
        uint4* xb = scr + OFF_X + ((4 + layer) * 8 + j) * SLAB + 32 * 32;
        mbar_wait(c8_go, layer);
        int n = 0;
        while (true) {
          if (lane == 0) asm volatile("mbarrier.arrive.expect_tx.shared::cta.b64 _, [%0], 18432;" :: "r"(c8_full) : "memory");
          __syncwarp();
#pragma unroll 1
          for (uint32_t s = 0; s < 9; s++)
            bulk_load(sb + HSTG + s * 2048, s < 8 ? scr + OFF_P + (j + s * 8) * SLAB + 32 * 32 : xb, 2048, c8_full, false);
          mbar_wait(c8_full, fph); fph ^= 1;
          uint32_t bad = 0;
#pragma unroll 8
          for (int s = 0; s < 32; s++) { uint32_t v; asm volatile("ld.shared.b32 %0, [%1];" : "=r"(v) : "r"(stg + s * 512) : "memory"); bad |= v ^ (1 - layer); }
          if (__all_sync(~0u, (bad & 1u) == 0u)) break;
          __nanosleep(300);
          SPIN_GUARD(n);
        }
        float s0 = 0.f, s1 = 0.f;
#pragma unroll 1
        for (int g = 0; g < 8; g++) {
          const uint32_t a = stg + (g >> 1) * 512 + (g & 1) * 8;
          float a0 = 0.f, a1 = 0.f, a2 = 0.f, a3 = 0.f;
#pragma unroll 1
          for (int b = 0; b < 3; b++) {
            uint32_t v[6];
#pragma unroll
            for (int s = 0; s < 3; s++) lds2(a + (3 * b + s) * 2048, v + 2 * s);
#pragma unroll
            for (int s = 0; s < 3; s++) { a0 += bf_lo(v[2 * s]); a1 += bf_hi(v[2 * s]); a2 += bf_lo(v[2 * s + 1]); a3 += bf_hi(v[2 * s + 1]); }
          }
          sts1(a + 18432, pack_bf16(a0, a1)); sts1(a + 18436, pack_bf16(a2, a3));
          s0 += a0 + a1; s1 += a2 + a3;
        }
        __syncwarp();
        if (lane == 0) mbar_arrive(c8_done);
        s0 = quad_sum(s0); s1 = quad_sum(s1);
        float q0 = 0.f, q1 = 0.f;
        const uint32_t ln = lane_id();
#pragma unroll 1
        for (uint32_t i = 0; i < 4; i++) {
          uint32_t x[4];
          lds4(stg + 18432 + i * 512, x);
          stg4(xb + i * 32 + ln, 0u, 0u, 0u, 0u);
          if (layer == 0) {
            stg4(xb - 3 * 8 * SLAB + i * 32 + ln, nz(x[0]), x[1], x[2], x[3]);
#pragma unroll
            for (int e = 0; e < 4; e++) {
              const float m = (e & 1) ? s1 : s0, c = fmaf(m, -1.f / 64, bf_lo(x[e])), d = fmaf(m, -1.f / 64, bf_hi(x[e]));
              if (e & 1) q1 = fmaf(c, c, fmaf(d, d, q1)); else q0 = fmaf(c, c, fmaf(d, d, q0));
            }
          } else {
            uint32_t* o = (uint32_t*)(out + (128 * t + 32 * (j >> 1) + 2 * (ln >> 2) + (j & 1)) * 576 + 512 + 16 * i + 2 * (ln & 3));
            o[0] = x[0]; o[8 * 576] = x[1]; o[4] = x[2]; o[8 * 576 + 4] = x[3];
          }
        }
        if (layer == 0) {
          q0 = quad_sum(q0); q1 = quad_sum(q1);
          if ((ln & 3) == 0) stg4(scr + OFF_S + j * 96 + 64 + (ln >> 2), __float_as_uint(s0) & ~1u, __float_as_uint(q0), __float_as_uint(s1), __float_as_uint(q1));
        }
      }
    } else {
      const uint32_t lane = lane_id(), r = lane >> 2, q = lane & 3;
#pragma unroll 1
      for (uint32_t layer = 0; layer < 2; layer++) {
        if (w == 10) {
          if (layer == 0) {
            const uint32_t p = t >> 2;
            tma_box(sb + PARK, &maps.m[p == 3 ? 6 : 5], 72 * j + (odd ? 0 : 64) + (p < 2 ? 576 * (p + 1) : 0), 144 * (t & 3), piece_full, 2304);
            mbar_wait(piece_full, 0);
            asm volatile("{\n.reg .pred e;\nelect.sync _|e, 0xffffffff;\n@e cp.async.bulk.global.shared::cta.bulk_group [%0], [%1], 2304;\n}\n"
                         "cp.async.bulk.commit_group;\ncp.async.bulk.wait_group 0;\nfence.proxy.async;"
                         :: "l"(scratch + OFF_R + j * 2304 + t * 144), "r"(sb + PARK) : "memory");
            __syncwarp();
            if (lane < 16) asm volatile("st.release.gpu.global.b32 [%0], 1;" :: "l"((uint32_t*)(scratch + OFF_F + (lane * 8 + j) * 8) + t) : "memory");
            uint32_t* fl = (uint32_t*)(scratch + OFF_F + (t * 8 + j) * 8) + (lane & 15);
            uint32_t v;
            int n = 0;
            while (true) {
              asm volatile("ld.acquire.gpu.global.b32 %0, [%1];" : "=r"(v) : "l"(fl) : "memory");
              if (__all_sync(~0u, v != 0u)) break;
              __nanosleep(100);
              SPIN_GUARD(n);
            }
            asm volatile("fence.proxy.async;\nst.relaxed.gpu.global.b32 [%0], 0;" :: "l"(fl) : "memory");
          } else {
            mbar_wait(park_free, 0);
          }
          bulk_load(sb + REM, scratch + OFF_R + j * 2304, 36864, rem_full, true);
        }
        mbar_wait(rem_full, layer);
#pragma unroll 1
        for (uint32_t b = 0; b < 5; b++) {
          const uint32_t blk = sb + REM + 27648 + b * 2048, k = threadIdx.x - 320, rr = k & 7;
          const uint32_t dst = blk + ((k >> 3) & 1) * 1024 + rr * 128 + (((k >> 4) ^ rr) << 4);
          uint32_t v[8];
          lds4(blk + k * 16, v); lds4(blk + 1024 + k * 16, v + 4);
          asm volatile("bar.sync 3, 64;" ::: "memory");
          sts4(dst, v); sts4(dst ^ 64, v + 4);
        }
        asm volatile("fence.proxy.async.shared::cta;" ::: "memory");
        mbar_arrive(remo_full);
        if (layer) mbar_wait(kv_free, 0);
        if (t > 0) {
#pragma unroll 1
          for (uint32_t pc = 0; pc < 3; pc++) {
            uint4* hp = scr + OFF_H + ((layer * 8 + j) * 2 + (w - 10)) * 192 + pc * 64 + lane;
            uint32_t hl[8];
            int n = 0;
            hl[4] = 1u;
            while (true) {
              ldg4(hl, hp);
              if (pc < 2) ldg4(hl + 4, hp + 32);
              if (__all_sync(~0u, hl[0] != 0u && hl[4] != 0u)) break;
              __nanosleep(100);
              SPIN_GUARD(n);
            }
            const uint32_t dst = sb + KVS + (w - 10) * 10368 + r * 144 + q * 4;
            if (pc < 2) {
#pragma unroll
              for (int g = 0; g < 8; g++) sts1(dst + pc * 20736 + odd * 16 + g * 16, hl[g]);
              stg4(hp + 32, 0u, 0u, 0u, 0u);
            } else {
              sts1(dst + (odd ? 0 : 128), hl[0]); sts1(dst + 20736 + (odd ? 0 : 128), hl[1]);
            }
            stg4(hp, 0u, 0u, 0u, 0u);
          }
        }
        asm volatile("bar.arrive 1, 192;" ::: "memory");
      }
    }
  } else {
    asm volatile("setmaxnreg.inc.sync.aligned.u32 240;");
    const uint32_t lane = lane_id(), r = lane >> 2, q = lane & 3;
    Ring rg{0, 0};
    uint32_t prev = 0;
    uint32_t X[144];
    float rs0, rs1;
    uint32_t mean0, mean1;
    auto release = [&](uint32_t st) { if (lane == 0) mbar_arrive(empty0 + st * 8); };
    auto load_kb = [&](int kb, const uint4* src, const char* lo, uint32_t hoff) {
#pragma unroll
      for (int k = 4 * kb; k < 4 * kb + 4; k++) {
        if (k % 9 == 4) { ldg2(X + 4 * k, lo + k * 512); ldg2(X + 4 * k + 2, lo + hoff + k * 512); }
        else ldg4(X + 4 * k, src + k * 32);
      }
    };
    auto next_kb = [&](bool center, int kb, const uint4* src, const char* lo, uint32_t hoff) {
      int n = 0;
      while (true) {
        bool ok = true;
#pragma unroll
        for (int k = 4 * kb; k < 4 * kb + 4; k++) { ok = ok && X[4 * k] != 0u; if (k % 9 == 4) ok = ok && X[4 * k + 2] != 0u; }
        if (__all_sync(~0u, ok)) break;
        SPIN_GUARD(n);
        load_kb(kb, src, lo, hoff);
      }
      if (kb + GD < 9) load_kb(kb + GD, src, lo, hoff);
      if (center) {
#pragma unroll
        for (int i = 16 * kb; i < 16 * kb + 16; i++) X[i] = sub_bf16x2(X[i], (i & 1) ? mean1 : mean0);
      }
    };
#pragma unroll 1
    for (uint32_t hf = 0; hf < 4; hf++) {
      const uint32_t layer = hf >> 1;
      const bool ffn = hf & 1;
      const uint32_t tag = 1 - layer;
      uint4* const xbase = scr + OFF_X + (layer * 8 + w) * SLAB;
      float aA[32], aB[32];
      {
        const uint4* src = xbase + (ffn ? 32 * SLAB : 0) + lane;
        const char* lo = (const char*)src - (ffn ? lane * 8 : 0);
        const uint32_t hoff = ffn ? 256 : 8;
        uint32_t s[3][4];
        const uint4* p = scr + OFF_S + ((ffn ? 16 : 0) + w) * 96 + q * 8 + r;
        const bool third = !ffn && q == 0;
        int n = 0;
        s[2][0] = tag; s[2][1] = s[2][2] = s[2][3] = 0u;
        STAMP(ffn * 16 + 0);
        while (true) {
          ldg4(s[0], p); ldg4(s[1], p + 32);
          if (third) ldg4(s[2], p + 64);
          if (__all_sync(~0u, ((s[0][0] ^ tag) | (s[1][0] ^ tag) | (s[2][0] ^ tag)) % 2u == 0u)) break;
          SPIN_GUARD(n);
        }
        STAMP(ffn * 16 + 1);
        GSTAMP(14 + ffn);
#pragma unroll
        for (int kb = 0; kb < GD; kb++) load_kb(kb, src, lo, hoff);
        float t0 = 0.f, t1 = 0.f;
#pragma unroll
        for (int i = 0; i < 3; i++) { t0 += __uint_as_float(s[i][0]); t1 += __uint_as_float(s[i][2]); }
        const float m0 = quad_sum(t0) * (1.f / 576), m1 = quad_sum(t1) * (1.f / 576);
        const float cnt = ffn ? 72.f : 64.f, inv = ffn ? 1.f / 72 : 1.f / 64;
        float v0 = 0.f, v1 = 0.f;
#pragma unroll
        for (int i = 0; i < 3; i++) {
          const float c = (i < 2 || third) ? cnt : 0.f;
          const float d0 = fmaf(__uint_as_float(s[i][0]), inv, -m0), d1 = fmaf(__uint_as_float(s[i][2]), inv, -m1);
          v0 += fmaf(d0 * d0, c, __uint_as_float(s[i][1])); v1 += fmaf(d1 * d1, c, __uint_as_float(s[i][3]));
        }
        rs0 = rsqrtf(fmaf(quad_sum(v0), 1.f / 576, 1e-5f)); rs1 = rsqrtf(fmaf(quad_sum(v1), 1.f / 576, 1e-5f));
        mean0 = pack_bf16(m0, m0); mean1 = pack_bf16(m1, m1);
#pragma unroll
        for (int kb = 0; kb < 9; kb++) {
          next_kb(true, kb, src, lo, hoff);
          mbar_wait(full0 + rg.st * 8, rg.ph);
          const uint64_t desc = DESC_HI | ((sb + rg.st * STAGE) >> 4);
          wg_fence();
#pragma unroll
          for (int i = 0; i < 4; i++) wgmma_rs_n64(aA, X + 4 * (4 * kb + i), desc + i * 128, kb + i != 0);
#pragma unroll
          for (int i = 0; i < 4; i++) wgmma_rs_n64(aB, X + 4 * (4 * kb + i), desc + 512 + i * 128, kb + i != 0);
          wg_commit();
          wg_wait<1>();
          if (kb > 0) release(prev);
          prev = rg.st; rg.next();
        }
        wg_wait<0>();
        STAMP(ffn * 16 + 2);
      }
      if (!ffn) {
      release(prev);
      const uint32_t kvrow = sb + KVS + (w & 1) * 10368 + (16 * (w >> 1)) * 144;
      uint32_t Q[18];
      {
        const uint32_t dst = kvrow + (8 + r) * 144 + q * 4 + odd * 16, dstr = dst + (odd ? -16 : 128);
        const bool edge_out = w >= 6 && t < 15;
        uint4* const hp = scr + TILE + OFF_H + ((layer * 8 + j) * 2 + (w & 1)) * 192 + lane;
        auto put_kv = [&](float (&a)[32], int part) {
          pin(a);
          uint32_t hl[8];
#pragma unroll
          for (int g = 0; g < 8; g++) {
            hl[g] = pack_bf16(a[4 * g + 2] * rs1, a[4 * g + 3] * rs1);
            sts1(dst + part * 20736 + g * 16, pack_bf16(a[4 * g] * rs0, a[4 * g + 1] * rs0)); sts1(dst + part * 20736 + 8 * 144 + g * 16, hl[g]);
          }
          if (edge_out) { stg4(hp + part * 64, nz(hl[0]), hl[1], hl[2], hl[3]); stg4(hp + part * 64 + 32, nz(hl[4]), hl[5], hl[6], hl[7]); }
        };
        put_kv(aA, 0);
        float aR[12];
        mbar_wait(rem_full, layer);
        const uint64_t dr = DESC_REM | ((sb + REM) >> 4);
        wg_fence();
#pragma unroll
        for (int s = 0; s < 36; s++) {
          wgmma_rs_n24(aR, X + 4 * s, dr + s * 16, s != 0);
          if (s == 4) put_kv(aB, 1);
        }
        wg_commit();
#pragma unroll
        for (int kb = 0; kb < 9; kb++) {
          if (!(kb & 1)) mbar_wait(full0 + rg.st * 8, rg.ph);
          const uint64_t desc = DESC_HI | ((sb + rg.st * STAGE + (kb & 1) * 8192) >> 4);
          wg_fence();
#pragma unroll
          for (int i = 0; i < 4; i++) wgmma_rs_n64(aB, X + 4 * (4 * kb + i), desc + i * 128, kb + i != 0);
          wg_commit();
          wg_wait<1>();
          if (kb > 0 && !(kb & 1)) release(prev);
          if ((kb & 1) || kb == 8) { prev = rg.st; rg.next(); }
          if (kb == 0) {
            pin(aR);
            const uint32_t k1 = pack_bf16(aR[2] * rs1, aR[3] * rs1), v1 = pack_bf16(aR[6] * rs1, aR[7] * rs1);
            if (edge_out) stg4(hp + 128, nz(k1), v1, 0u, 0u);
            sts1(dstr, pack_bf16(aR[0] * rs0, aR[1] * rs0)); sts1(dstr + 8 * 144, k1);
            sts1(dstr + 20736, pack_bf16(aR[4] * rs0, aR[5] * rs0)); sts1(dstr + 20736 + 8 * 144, v1);
            Q[16] = pack_bf16(aR[8] * rs0, aR[9] * rs0); Q[17] = pack_bf16(aR[10] * rs1, aR[11] * rs1);
            if (w < 4) asm volatile("bar.arrive 2, 256;" ::: "memory");
          }
        }
        wg_wait<0>();
        release(prev);
        pin(aB);
        STAMP(3);
#pragma unroll
        for (int g = 0; g < 8; g++) {
          Q[2 * g] = pack_bf16(aB[4 * g] * rs0, aB[4 * g + 1] * rs0); Q[2 * g + 1] = pack_bf16(aB[4 * g + 2] * rs1, aB[4 * g + 3] * rs1);
        }
        if (odd) {
          const uint32_t r0 = Q[16], r1 = Q[17];
#pragma unroll
          for (int i = 17; i >= 2; i--) Q[i] = Q[i - 2];
          Q[0] = r0; Q[1] = r1;
        }
      }
      if (w < 4) asm volatile("bar.sync 1, 192;" ::: "memory");
      else asm volatile("bar.sync 2, 256;" ::: "memory");
      STAMP(4);
      uint32_t O[18];
      {
        const bool edge = (t == 0 && w < 2);
        uint32_t row[3];
#pragma unroll
        for (int nt = 0; nt < 3; nt++) row[nt] = kvrow + (8 * nt + (lane & 7)) * 144;
        if (edge) row[0] = sb + KVS + 8 * 144;
        const uint32_t rlast = ((lane >> 3) == 0 ? row[0] : (lane >> 3) == 1 ? row[1] : row[2]) + 128;
        uint32_t K[3][9], V[3][9], dummy;
#pragma unroll
        for (int nt = 0; nt < 3; nt++) {
          ldsm4(row[nt] + (lane >> 3) * 16, K[nt][0], K[nt][1], K[nt][2], K[nt][3]);
          ldsm4(row[nt] + 64 + (lane >> 3) * 16, K[nt][4], K[nt][5], K[nt][6], K[nt][7]);
        }
        ldsm4(rlast, K[0][8], K[1][8], K[2][8], dummy);
#pragma unroll
        for (int nt = 0; nt < 3; nt++) {
          ldsm4t(row[nt] + 20736 + (lane >> 3) * 16, V[nt][0], V[nt][1], V[nt][2], V[nt][3]);
          ldsm4t(row[nt] + 20736 + 64 + (lane >> 3) * 16, V[nt][4], V[nt][5], V[nt][6], V[nt][7]);
        }
        ldsm4t(rlast + 20736, V[0][8], V[1][8], V[2][8], dummy);
        const bool up0 = 2 * q > r, up1 = 2 * q + 1 > r;
        const float sc = 0.23570226039551584f * 1.4426950408889634f;
        const float neg = -1e9f * 1.4426950408889634f;
        float Of[9][4];
#pragma unroll
        for (int h = 0; h < 4; h++) {
          const uint32_t a0 = q >= h ? Q[4 * h] : 0u, a1 = q >= h ? Q[4 * h + 1] : 0u;
          const uint32_t a4 = q <= h ? Q[4 * h + 4] : 0u, a5 = q <= h ? Q[4 * h + 5] : 0u;
          float S[3][4];
#pragma unroll
          for (int nt = 0; nt < 3; nt++) {
            S[nt][0] = S[nt][1] = S[nt][2] = S[nt][3] = 0.f;
            mma16(S[nt], a0, a1, Q[4 * h + 2], Q[4 * h + 3], K[nt][2 * h], K[nt][2 * h + 1]);
            mma8(S[nt], a4, a5, K[nt][2 * h + 2]);
          }
          float s00 = (up0 ? S[0][0] : S[1][0]) * sc, s01 = (up1 ? S[0][1] : S[1][1]) * sc;
          const float s10 = (up0 ? S[1][2] : S[2][2]) * sc, s11 = (up1 ? S[1][3] : S[2][3]) * sc;
          if (edge && up0) s00 = neg;
          if (edge && up1) s01 = neg;
          const float m0 = quad_max(fmaxf(s00, s01)), m1 = quad_max(fmaxf(s10, s11));
          float p00 = ex2(s00 - m0), p01 = ex2(s01 - m0), p10 = ex2(s10 - m1), p11 = ex2(s11 - m1);
          const float i0 = rcp(quad_sum(p00 + p01)), i1 = rcp(quad_sum(p10 + p11));
          p00 *= i0; p01 *= i0; p10 *= i1; p11 *= i1;
          const uint32_t pa = pack_bf16(up0 ? p00 : 0.f, up1 ? p01 : 0.f), pb = pack_bf16(up0 ? 0.f : p00, up1 ? 0.f : p01);
          const uint32_t pc = pack_bf16(up0 ? p10 : 0.f, up1 ? p11 : 0.f), pd = pack_bf16(up0 ? 0.f : p10, up1 ? 0.f : p11);
#pragma unroll
          for (int gi = 0; gi < 3; gi++) {
            const int g = 2 * h + gi;
            float o[4] = {0.f, 0.f, 0.f, 0.f};
            mma16(o, pa, 0u, pb, pc, V[0][g], V[1][g]);
            mma8(o, 0u, pd, V[2][g]);
#pragma unroll
            for (int e = 0; e < 4; e++) Of[g][e] = (gi == 0 && h > 0 && q < h) ? Of[g][e] : o[e];
          }
        }
#pragma unroll
        for (int g = 0; g < 9; g++) { O[2 * g] = pack_bf16(Of[g][0], Of[g][1]); O[2 * g + 1] = pack_bf16(Of[g][2], Of[g][3]); }
      }
      if (odd) put72(xbase + 16 * SLAB, j, lane, O + 2, O[0], O[1]);
      else put72(xbase + 16 * SLAB, j, lane, O, O[16], O[17]);
      if (q == 0) stg4(scr + OFF_S + (8 + w) * 96 + j * 8 + r, tag, 0u, 0u, 0u);
      {
        uint32_t res[18];
        const uint4* p = xbase + ((9 * j + 1) >> 1) * 32 + lane;
#pragma unroll
        for (int i = 0; i < 4; i++) ldg4(res + 4 * i, p + i * 32);
        ldg2(res + 16, odd ? (const char*)(p - 32) + 8 : (const char*)(p + 4 * 32));
        const uint4* src = xbase + 16 * SLAB + lane;
        {
          const uint4* fp = scr + OFF_S + (8 + w) * 96 + q * 8 + r;
          uint32_t s0[4], s1[4];
          int n = 0;
          STAMP(8);
          while (true) {
            ldg4(s0, fp); ldg4(s1, fp + 32);
            if (__all_sync(~0u, ((s0[0] ^ tag) | (s1[0] ^ tag)) % 2u == 0u)) break;
            SPIN_GUARD(n);
          }
          STAMP(9);
        }
#pragma unroll
        for (int kb = 0; kb < GD; kb++) load_kb(kb, src, (const char*)src - lane * 8, 256);
        float acc[36];
        mbar_wait(remo_full, layer);
#pragma unroll
        for (int kb = 0; kb < 9; kb++) {
          next_kb(false, kb, src, (const char*)src - lane * 8, 256);
          if (!(kb & 1)) mbar_wait(full0 + rg.st * 8, rg.ph);
          const uint32_t base = sb + rg.st * STAGE + (kb & 1) * 8192;
          const uint64_t d0 = DESC_HI | ((base >> 4) + (((sb + REM + 27648 + (kb >> 1) * 2048 + (kb & 1) * 64 - base) >> 4) << 16));
          wg_fence();
#pragma unroll
          for (int i = 0; i < 4; i++) wgmma_rs_n72(acc, X + 4 * (4 * kb + i), d0 - (uint64_t)(i * ((127u << 16) - 128u)), kb + i != 0);
          wg_commit();
          wg_wait<1>();
          if (kb > 0 && !(kb & 1)) release(prev);
          if ((kb & 1) || kb == 8) { prev = rg.st; rg.next(); }
        }
        wg_wait<0>();
        release(prev);
        pin(acc);
        STAMP(10);
#pragma unroll
        for (int i = 0; i < 18; i++) {
          acc[2 * i] += bf_lo(res[i]); acc[2 * i + 1] += bf_hi(res[i]);
          res[i] = pack_bf16(acc[2 * i], acc[2 * i + 1]);
        }
        put72(xbase + 32 * SLAB, j, lane, res, res[16], res[17]);
        publish_stats<9>(scr + OFF_S + (16 + w) * 96 + j * 8, acc, tag, lane);
      }
      continue;
      }
      const uint32_t hp = sb + PARK + w * 512 + lane * 16;
      auto pack8 = [&](float (&a)[32], int p, uint32_t* o) {
#pragma unroll
        for (int e = 0; e < 8; e++) asm volatile("" : "+f"(a[8 * p + e]) :: "memory");
#pragma unroll
        for (int e = 0; e < 4; e++) o[e] = pack_bf16(a[8 * p + 2 * e], a[8 * p + 2 * e + 1]);
      };
      const float ka0 = 0.7978845608028654f * rs0, kb0 = 0.044715f * ka0 * rs0 * rs0, ku0 = 0.5f * rs0 * rs0;
      const float ka1 = 0.7978845608028654f * rs1, kb1 = 0.044715f * ka1 * rs1 * rs1, ku1 = 0.5f * rs1 * rs1;
      auto packu8 = [&](int p, uint32_t* o) {
#pragma unroll
        for (int e = 0; e < 8; e++) asm volatile("" : "+f"(aA[8 * p + e]) :: "memory");
#pragma unroll
        for (int e = 0; e < 4; e++) o[e] = pack_bf16(aA[8 * p + 2 * e] * ((e & 1) ? ku1 : ku0), aA[8 * p + 2 * e + 1] * ((e & 1) ? ku1 : ku0));
      };
      auto geglu8 = [&](int p, uint32_t* u) {
#pragma unroll
        for (int e = 0; e < 8; e++) asm volatile("" : "+f"(aB[8 * p + e]) :: "memory");
        float h[8];
#pragma unroll
        for (int e = 0; e < 8; e++) {
          const float g = aB[8 * p + e];
          h[e] = fmaf(g, tanh_ap(g * fmaf(g * g, (e & 2) ? kb1 : kb0, (e & 2) ? ka1 : ka0)), g);
        }
#pragma unroll
        for (int e = 0; e < 4; e++) u[e] = mul_bf16x2(pack_bf16(h[2 * e], h[2 * e + 1]), u[e]);
      };
      auto box = [&](int b, auto&& filler) {
        const int kb = b < 9 ? b : b - 9;
        if (!(b & 1)) mbar_wait(full0 + rg.st * 8, rg.ph);
        const uint64_t desc = DESC_HI | ((sb + rg.st * STAGE + (b & 1) * 8192) >> 4);
        wg_fence();
#pragma unroll
        for (int i = 0; i < 4; i++) {
          if (b < 9) wgmma_rs_n64(aA, X + 4 * (4 * kb + i), desc + i * 128, kb + i != 0);
          else wgmma_rs_n64(aB, X + 4 * (4 * kb + i), desc + i * 128, kb + i != 0);
          if (i == FPOS) filler();
        }
        wg_commit();
        if (b & 1) { if (W2) wg_wait<1>(); prev = rg.st; rg.next(); } else { wg_wait<1>(); release(prev); }
      };
      auto nop = [] {};
      auto step = [&](int st, auto&& filler) { box(2 * st, nop); box(2 * st + 1, filler); };
#pragma unroll
      for (int p = 0; p < 4; p++) { uint32_t o[4]; packu8(p, o); sts4(hp + p * 4096, o); }
      box(0, nop);
      zero_share(xbase, j, lane);
      zero_share(xbase + 16 * SLAB, j, lane);
#pragma unroll 1
      for (int c = 1;; c++) {
        const uint32_t hc = hp + c * 4 * 4096;
#pragma unroll
        for (int b = 1; b < 18; b++) box(b, [&] {
          if ((b & 1) && b < 8) { uint32_t o[4]; const uint32_t a = hc - (4 - (b >> 1)) * 4096; lds4(a, o); geglu8(b >> 1, o); sts4(a, o); }
          if ((b & 1) && b > 10) { uint32_t o[4]; packu8((b - 11) >> 1, o); if (c < 8) sts4(hc + ((b - 11) >> 1) * 4096, o); } });
        if (c == 8) break;
        box(0, nop);
      }
      wg_wait<0>();
      STAMP(21);
      GSTAMP(19);
#pragma unroll
      for (int s = 0; s < 32; s++) lds4(hp + s * 4096, X + 4 * s);
#pragma unroll
      for (int p = 0; p < 4; p++) packu8(p, X + 128 + 4 * p);
#pragma unroll
      for (int st = 0; st < 4; st++) step(st, [&] { geglu8(st, X + 128 + 4 * st); });
      STAMP(24);
      if (layer == 0 && lane == 0) mbar_arrive(park_free);
      const uint32_t lane2 = lane_id();
      uint4* const pw = scr + OFF_P + (j * 8 + w) * SLAB + lane2;
      const uint4* const pr = scr + OFF_P + w * SLAB + 4 * j * 32 + lane2;
      auto put_part = [&](float (&a)[32], int p, uint32_t chunk) {
        uint32_t o[4];
        pack8(a, p, o);
        stg4(pw + (chunk * 4 + p) * 32, (o[0] & ~1u) | tag, o[1], o[2], o[3]);
      };
      auto slot = [&](int p) { return sb + w * 2048 + (p < 4 ? PARK + (p - 1) * 16384 : KVS + (p - 4) * 16384); };
      auto fetch = [&](int p) {
        if (p > 0) bulk_load(slot(p), scr + OFF_P + (((j - p) & 7) * 8 + w) * SLAB + 4 * j * 32, 2048, pbar0 + w * 8, true);
      };
      uint4* const xb = xbase + 32 * SLAB + 4 * j * 32;
#pragma unroll 1
      for (int sp = 0;; sp++) {
        const uint32_t ca = sp == 0 ? 8 : ((j + 2 * sp) & 7), cb = (j + 2 * sp + 1) & 7;
        if (sp == 1 && lane == 0) mbar_arrive(c8_go);
#pragma unroll
        for (int st = 4; st < 9; st++) step(st, [&] {
          if (st == 5 || st == 6) { put_part(aA, 2 * (st - 5), ca); put_part(aA, 2 * (st - 5) + 1, ca); }
          if (st == 8) { if (sp == 3) mbar_wait(c8_done, layer); fetch(2 * sp - 1); } });
        STAMP(25 + sp);
        if (sp == 3) break;
        if (sp == 2 && layer == 0 && (lane2 & 3) == 0) {
#pragma unroll
          for (int k = 0; k < 3; k++) stg4(scr + OFF_S + (k * 8 + w) * 96 + j * 8 + (lane2 >> 2), 1u, 0u, 0u, 0u);
        }
        if (sp == 2) asm volatile("{\n.reg .pred e;\nelect.sync _|e, 0xffffffff;\n@e cp.async.bulk.prefetch.L2.global [%0], 2048;\n}" :: "l"(xb) : "memory");
#pragma unroll
        for (int st = 0; st < 4; st++) step(st, [&] {
          if (st < 2) { put_part(aB, 2 * st, cb); put_part(aB, 2 * st + 1, cb); }
          if (st == 3) fetch(2 * sp); });
      }
      auto load_p = [&](int p, uint32_t* d) {
#pragma unroll
        for (int i = 0; i < 4; i++) ldg4(d + 4 * i, pr + ((j - p) & 7) * 8 * SLAB + i * 32);
      };
#pragma unroll
      for (int st = 0; st < 4; st++) step(st, [&] {
        if (st == 0) {
#pragma unroll
          for (int p = 0; p < 4; p++) put_part(aB, p, (j + 7) & 7);
        }
        if (st == 1) {
#pragma unroll
          for (int i = 0; i < 4; i++) {
            const bool split = j == 2 * i + 1;
            const char* l = (const char*)(xb + i * 32) + (split ? lane2 * 8 : lane2 * 16);
            ldg2(X + 4 * i, l); ldg2(X + 4 * i + 2, l + (split ? 256 : 8));
          }
          load_p(6, X + 16);
        }
        if (st == 3) load_p(7, X + 32); });
      STAMP(13);
      {
        mbar_wait(full0 + rg.st * 8, rg.ph);
        const uint64_t desc = DESC_HI | ((sb + rg.st * STAGE) >> 4);
        wg_fence();
#pragma unroll
        for (int i = 0; i < 4; i++) wgmma_rs_n64(aA, X + 4 * (32 + i), desc + i * 128, 1);
        wg_commit();
        wg_wait<1>(); release(prev);
        prev = rg.st; rg.next();
        mbar_wait(pbar0 + w * 8, layer);
        wg_wait<0>(); release(prev);
        pin(aA);
      }
      STAMP(22);
      GSTAMP(20);
      {
        const uint32_t eye = r == 2 * q ? 0x3f80u : r == 2 * q + 1 ? 0x3f800000u : 0u;
        auto add_p = [&](int p, uint32_t* d) {
          int n = 0;
          while (!__all_sync(~0u, (((d[0] ^ tag) | (d[4] ^ tag) | (d[8] ^ tag) | (d[12] ^ tag)) & 1u) == 0u)) { SPIN_GUARD(n); load_p(p, d); }
#pragma unroll
          for (int g = 0; g < 8; g++) mma8(aA + 4 * g, d[2 * g], d[2 * g + 1], eye);
        };
#pragma unroll
        for (int p = 1; p < 6; p++)
#pragma unroll
          for (int i = 0; i < 4; i++) lds4(slot(p) + lane2 * 16 + i * 512, X + 32 + 16 * p + 4 * i);
#pragma unroll
        for (int g = 0; g < 8; g++) mma8(aA + 4 * g, X[2 * g], X[2 * g + 1], eye);
#pragma unroll
        for (int p = 1; p < 6; p++) add_p(p, X + 32 + 16 * p);
        add_p(6, X + 16);
        STAMP(11);
        add_p(7, X + 32);
        STAMP(12);
        uint32_t res[16];
#pragma unroll
        for (int i = 0; i < 16; i++) res[i] = pack_bf16(aA[2 * i], aA[2 * i + 1]);
        if (layer == 0) {
          uint4* p = xbase + 8 * SLAB + 4 * j * 32 + lane;
#pragma unroll
          for (int i = 0; i < 4; i++) stg4(p + i * 32, nz(res[4 * i]), res[4 * i + 1], nz(res[4 * i + 2]), res[4 * i + 3]);
          publish_stats<8>(scr + OFF_S + w * 96 + j * 8, aA, 0u, lane);
          if (lane == 0) mbar_arrive(kv_free);
        } else {
          uint32_t* o = (uint32_t*)(out + (128 * t + 32 * (w >> 1) + 2 * r + (w & 1)) * 576 + 64 * j + 2 * q);
#pragma unroll
          for (int g = 0; g < 8; g++) { o[4 * g] = res[2 * g]; o[8 * 576 + 4 * g] = res[2 * g + 1]; }
        }
#pragma unroll
        for (int i = 0; i < 4; i++) stg4(xb + lane + i * 32, 0u, 0u, 0u, 0u);
      }
      STAMP(23);
    }
  }
}

typedef CUresult (*EncodeFn)(CUtensorMap*, CUtensorMapDataType, cuuint32_t, void*, const cuuint64_t*, const cuuint64_t*,
                             const cuuint32_t*, const cuuint32_t*, CUtensorMapInterleave, CUtensorMapSwizzle,
                             CUtensorMapL2promotion, CUtensorMapFloatOOBfill);

CUtensorMap make_map(EncodeFn f, const void* p, uint64_t cols, uint64_t rows, bool rem = false) {
  CUtensorMap m;
  cuuint64_t dims[2] = {cols, rows};
  cuuint64_t str[1] = {cols * 2};
  cuuint32_t box[2] = {rem ? 8u : 64u, rem ? 144u : 64u};
  cuuint32_t es[2] = {1, 1};
  f(&m, CU_TENSOR_MAP_DATA_TYPE_BFLOAT16, 2, const_cast<void*>(p), dims, str, box, es, CU_TENSOR_MAP_INTERLEAVE_NONE,
    rem ? CU_TENSOR_MAP_SWIZZLE_NONE : CU_TENSOR_MAP_SWIZZLE_128B, CU_TENSOR_MAP_L2_PROMOTION_NONE, CU_TENSOR_MAP_FLOAT_OOB_FILL_NONE);
  return m;
}

}

extern "C" void kernel_launch(void* const* d_in, const int* in_sizes, int n_in, void* d_out, int out_size) {
  void* fn = nullptr;
  cudaDriverEntryPointQueryResult qr;
  cudaGetDriverEntryPoint("cuTensorMapEncodeTiled", &fn, cudaEnableDefault, &qr);
  EncodeFn enc = (EncodeFn)fn;
  Maps maps;
  maps.m[0] = make_map(enc, d_in[1], 1728, 576); maps.m[1] = make_map(enc, d_in[2], 576, 576);
  maps.m[2] = make_map(enc, d_in[4], 4608, 576); maps.m[3] = make_map(enc, d_in[5], 4608, 576); maps.m[4] = make_map(enc, d_in[6], 576, 4608);
  maps.m[5] = make_map(enc, d_in[1], 1728, 576, true); maps.m[6] = make_map(enc, d_in[2], 576, 576, true);
  void* scr = nullptr;
  cudaGetSymbolAddress(&scr, g_scratch);
  cudaFuncSetAttribute(mega_kernel, cudaFuncAttributeMaxDynamicSharedMemorySize, SMEM_BYTES);
  mega_kernel<<<128, 384, SMEM_BYTES>>>(maps, (uint4*)scr, (const __nv_bfloat16*)d_in[0], (__nv_bfloat16*)d_out);
}
```

```cpp
#include <cuda_runtime.h>
#include <cuda.h>
#include <cuda_bf16.h>
#include <stdint.h>

#define TRACE 0
#define GUARD 1
#define TRAPB 1
#define HOFF1 99
#define HOFF2 99
#define GDZ 3
#define GDO 3
#define EXP 0
#define FPOS 2

namespace {

constexpr int NST = 6;
constexpr int STAGE = 16384;
constexpr int PARK = NST * STAGE;
constexpr int REM = PARK + 49152;
constexpr int KVS = REM + 40960;
constexpr int HSTG = KVS + 16384;
constexpr int BARS = KVS + 41472;
constexpr int TRC = BARS + 256;
constexpr int SMEM_BYTES = TRC + (TRACE ? 512 : 0);
static_assert(NST == 6, "the producer addresses empty barriers as full + 48");
static_assert(BARS >= PARK + 131072, "barriers overlap park");
static_assert(SMEM_BYTES <= 232448, "smem");

constexpr int SLAB = 36 * 32;
constexpr int SPIN_MAX = 1 << 17;
constexpr int GD = GDZ, GO = GDO;
constexpr int OFF_S = 0;
constexpr int OFF_H = OFF_S + 3 * 8 * 96;
constexpr int OFF_X = OFF_H + 2 * 8 * 384;
constexpr int OFF_P = OFF_X + 6 * 8 * SLAB;
constexpr int TILE = OFF_P + 8 * 8 * SLAB;
constexpr int OFF_R = 16 * TILE;
constexpr int OFF_F = OFF_R + 8 * 2304;
constexpr int SCRATCH = OFF_F + 128 * 8;

}

__device__ uint4 g_scratch[SCRATCH];

namespace {

constexpr uint64_t DESC_HI = 0x4000004000000000ull;
constexpr uint64_t DESC_REM = (576ull << 32) | (8u << 16);
__device__ __forceinline__ void wgmma_rs_n64(float (&d)[32], const uint32_t* a, uint64_t desc, int scale_d) {
  asm volatile("{\n.reg .pred p;\nsetp.ne.b32 p, %37, 0;\n"
    "wgmma.mma_async.sync.aligned.m64n64k16.f32.bf16.bf16 "
    "{%0, %1, %2, %3, %4, %5, %6, %7, %8, %9, %10, %11, %12, %13, %14, %15, %16, %17, %18, %19, %20, %21, %22, %23, %24, %25, %26, %27, %28, %29, %30, %31}, "
    "{%32, %33, %34, %35}, %36, p, 1, 1, 1;\n}\n"
    : "+f"(d[0]), "+f"(d[1]), "+f"(d[2]), "+f"(d[3]), "+f"(d[4]), "+f"(d[5]), "+f"(d[6]), "+f"(d[7]), "+f"(d[8]), "+f"(d[9]), "+f"(d[10]), "+f"(d[11]), "+f"(d[12]), "+f"(d[13]), "+f"(d[14]), "+f"(d[15]), "+f"(d[16]), "+f"(d[17]), "+f"(d[18]), "+f"(d[19]), "+f"(d[20]), "+f"(d[21]), "+f"(d[22]), "+f"(d[23]), "+f"(d[24]), "+f"(d[25]), "+f"(d[26]), "+f"(d[27]), "+f"(d[28]), "+f"(d[29]), "+f"(d[30]), "+f"(d[31])
    : "r"(a[0]), "r"(a[1]), "r"(a[2]), "r"(a[3]), "l"(desc), "r"(scale_d));
}
__device__ __forceinline__ void wgmma_rs_n72(float (&d)[36], const uint32_t* a, uint64_t desc, int scale_d) {
  asm volatile("{\n.reg .pred p;\nsetp.ne.b32 p, %41, 0;\n"
    "wgmma.mma_async.sync.aligned.m64n72k16.f32.bf16.bf16 "
    "{%0, %1, %2, %3, %4, %5, %6, %7, %8, %9, %10, %11, %12, %13, %14, %15, %16, %17, %18, %19, %20, %21, %22, %23, %24, %25, %26, %27, %28, %29, %30, %31, %32, %33, %34, %35}, "
    "{%36, %37, %38, %39}, %40, p, 1, 1, 1;\n}\n"
    : "+f"(d[0]), "+f"(d[1]), "+f"(d[2]), "+f"(d[3]), "+f"(d[4]), "+f"(d[5]), "+f"(d[6]), "+f"(d[7]), "+f"(d[8]), "+f"(d[9]), "+f"(d[10]), "+f"(d[11]), "+f"(d[12]), "+f"(d[13]), "+f"(d[14]), "+f"(d[15]), "+f"(d[16]), "+f"(d[17]), "+f"(d[18]), "+f"(d[19]), "+f"(d[20]), "+f"(d[21]), "+f"(d[22]), "+f"(d[23]), "+f"(d[24]), "+f"(d[25]), "+f"(d[26]), "+f"(d[27]), "+f"(d[28]), "+f"(d[29]), "+f"(d[30]), "+f"(d[31]), "+f"(d[32]), "+f"(d[33]), "+f"(d[34]), "+f"(d[35])
    : "r"(a[0]), "r"(a[1]), "r"(a[2]), "r"(a[3]), "l"(desc), "r"(scale_d));
}
__device__ __forceinline__ void wgmma_rs_n24(float (&d)[12], const uint32_t* a, uint64_t desc, int scale_d) {
  asm volatile("{\n.reg .pred p;\nsetp.ne.b32 p, %17, 0;\n"
    "wgmma.mma_async.sync.aligned.m64n24k16.f32.bf16.bf16 "
    "{%0, %1, %2, %3, %4, %5, %6, %7, %8, %9, %10, %11}, "
    "{%12, %13, %14, %15}, %16, p, 1, 1, 1;\n}\n"
    : "+f"(d[0]), "+f"(d[1]), "+f"(d[2]), "+f"(d[3]), "+f"(d[4]), "+f"(d[5]), "+f"(d[6]), "+f"(d[7]), "+f"(d[8]), "+f"(d[9]), "+f"(d[10]), "+f"(d[11])
    : "r"(a[0]), "r"(a[1]), "r"(a[2]), "r"(a[3]), "l"(desc), "r"(scale_d));
}

__device__ __forceinline__ void mbar_init(uint32_t a, uint32_t c) { asm volatile("mbarrier.init.shared::cta.b64 [%0], %1;" :: "r"(a), "r"(c)); }
__device__ __forceinline__ void mbar_arrive(uint32_t a) { asm volatile("mbarrier.arrive.shared::cta.b64 _, [%0];" :: "r"(a) : "memory"); }
__device__ __forceinline__ void mbar_wait_trap(uint32_t a, uint32_t ph) {
  asm volatile("{\n.reg .pred p;\n.reg .u32 n;\nmov.u32 n, 0;\n"
               "W: mbarrier.try_wait.parity.shared::cta.b64 p, [%0], %1;\n@p bra D;\n"
               "add.u32 n, n, 1;\nsetp.lt.u32 p, n, 4194304;\n@p bra W;\ntrap;\nD:\n}" :: "r"(a), "r"(ph) : "memory");
}
__device__ __forceinline__ void mbar_wait(uint32_t a, uint32_t ph) {
  mbar_wait_trap(a, ph);
}
__device__ __forceinline__ void wg_fence() { asm volatile("wgmma.fence.sync.aligned;" ::: "memory"); }
__device__ __forceinline__ void wg_commit() { asm volatile("wgmma.commit_group.sync.aligned;" ::: "memory"); }
template <int N> __device__ __forceinline__ void wg_wait() { asm volatile("wgmma.wait_group.sync.aligned %0;" :: "n"(N) : "memory"); }
__device__ __forceinline__ float tanh_ap(float x) { float y; asm("tanh.approx.f32 %0, %1;" : "=f"(y) : "f"(x)); return y; }
__device__ __forceinline__ float ex2(float x) { float y; asm("ex2.approx.ftz.f32 %0, %1;" : "=f"(y) : "f"(x)); return y; }
__device__ __forceinline__ uint32_t pack_bf16(float lo, float hi) { uint32_t r; asm("cvt.rn.bf16x2.f32 %0, %1, %2;" : "=r"(r) : "f"(hi), "f"(lo)); return r; }
__device__ __forceinline__ float bf_lo(uint32_t v) { return __uint_as_float(v << 16); }
__device__ __forceinline__ float bf_hi(uint32_t v) { return __uint_as_float(v & 0xffff0000u); }
__device__ __forceinline__ uint32_t sub_bf16x2(uint32_t a, uint32_t b) { uint32_t r; asm("sub.rn.bf16x2 %0, %1, %2;" : "=r"(r) : "r"(a), "r"(b)); return r; }
__device__ __forceinline__ uint32_t mul_bf16x2(uint32_t a, uint32_t b) { uint32_t r; asm("mul.rn.bf16x2 %0, %1, %2;" : "=r"(r) : "r"(a), "r"(b)); return r; }
__device__ __forceinline__ uint32_t diff2(uint32_t a, uint32_t b, uint32_t t) { uint32_t r; asm("lop3.b32 %0, %1, %2, %3, 0x7e;" : "=r"(r) : "r"(a), "r"(b), "r"(t)); return r; }
__device__ __forceinline__ uint32_t or3(uint32_t a, uint32_t b, uint32_t c) { uint32_t r; asm("lop3.b32 %0, %1, %2, %3, 0xfe;" : "=r"(r) : "r"(a), "r"(b), "r"(c)); return r; }
__device__ __forceinline__ uint32_t umin2(uint32_t a, uint32_t b) { uint32_t r; asm("min.u32 %0, %1, %2;" : "=r"(r) : "r"(a), "r"(b)); return r; }
__device__ __forceinline__ uint32_t nz(uint32_t w) { return w == 0u ? 0x8000u : w; }

__device__ __forceinline__ void ldg4(uint32_t* d, const uint4* p) {
  asm volatile("ld.relaxed.gpu.global.v4.b32 {%0,%1,%2,%3}, [%4];" : "=r"(d[0]), "=r"(d[1]), "=r"(d[2]), "=r"(d[3]) : "l"(p) : "memory");
}
__device__ __forceinline__ void ldg2(uint32_t* d, const void* p) {
  asm volatile("ld.relaxed.gpu.global.v2.b32 {%0,%1}, [%2];" : "=r"(d[0]), "=r"(d[1]) : "l"(p) : "memory");
}
__device__ __forceinline__ void stg4(uint4* p, uint32_t a, uint32_t b, uint32_t c, uint32_t d) {
  asm volatile("st.relaxed.gpu.global.v4.b32 [%0], {%1,%2,%3,%4};" :: "l"(p), "r"(a), "r"(b), "r"(c), "r"(d) : "memory");
}
__device__ __forceinline__ void stg2(void* p, uint32_t a, uint32_t b) {
  asm volatile("st.relaxed.gpu.global.v2.b32 [%0], {%1,%2};" :: "l"(p), "r"(a), "r"(b) : "memory");
}
__device__ __forceinline__ void sts4(uint32_t a, const uint32_t* o) { asm volatile("st.shared.v4.b32 [%0], {%1,%2,%3,%4};" :: "r"(a), "r"(o[0]), "r"(o[1]), "r"(o[2]), "r"(o[3]) : "memory"); }
__device__ __forceinline__ void lds4(uint32_t a, uint32_t* o) { asm volatile("ld.shared.v4.b32 {%0,%1,%2,%3}, [%4];" : "=r"(o[0]), "=r"(o[1]), "=r"(o[2]), "=r"(o[3]) : "r"(a) : "memory"); }
__device__ __forceinline__ void lds2(uint32_t a, uint32_t* o) { asm volatile("ld.shared.v2.b32 {%0,%1}, [%2];" : "=r"(o[0]), "=r"(o[1]) : "r"(a) : "memory"); }
__device__ __forceinline__ float rcp(float x) { float y; asm("rcp.approx.ftz.f32 %0, %1;" : "=f"(y) : "f"(x)); return y; }
__device__ __forceinline__ void sts1(uint32_t a, uint32_t v) { asm volatile("st.shared.b32 [%0], %1;" :: "r"(a), "r"(v) : "memory"); }
__device__ __forceinline__ void ldsm4(uint32_t a, uint32_t& r0, uint32_t& r1, uint32_t& r2, uint32_t& r3) {
  asm volatile("ldmatrix.sync.aligned.m8n8.x4.shared.b16 {%0,%1,%2,%3}, [%4];" : "=r"(r0), "=r"(r1), "=r"(r2), "=r"(r3) : "r"(a) : "memory");
}
__device__ __forceinline__ void ldsm4t(uint32_t a, uint32_t& r0, uint32_t& r1, uint32_t& r2, uint32_t& r3) {
  asm volatile("ldmatrix.sync.aligned.m8n8.x4.trans.shared.b16 {%0,%1,%2,%3}, [%4];" : "=r"(r0), "=r"(r1), "=r"(r2), "=r"(r3) : "r"(a) : "memory");
}
__device__ __forceinline__ void mma16(float* c, uint32_t a0, uint32_t a1, uint32_t a2, uint32_t a3, uint32_t b0, uint32_t b1) {
  asm("mma.sync.aligned.m16n8k16.row.col.f32.bf16.bf16.f32 {%0,%1,%2,%3}, {%4,%5,%6,%7}, {%8,%9}, {%0,%1,%2,%3};"
    : "+f"(c[0]), "+f"(c[1]), "+f"(c[2]), "+f"(c[3]) : "r"(a0), "r"(a1), "r"(a2), "r"(a3), "r"(b0), "r"(b1));
}
__device__ __forceinline__ void mma8(float* c, uint32_t a0, uint32_t a1, uint32_t b0) {
  asm("mma.sync.aligned.m16n8k8.row.col.f32.bf16.bf16.f32 {%0,%1,%2,%3}, {%4,%5}, {%6}, {%0,%1,%2,%3};"
    : "+f"(c[0]), "+f"(c[1]), "+f"(c[2]), "+f"(c[3]) : "r"(a0), "r"(a1), "r"(b0));
}
__device__ __forceinline__ uint32_t lane_id() { uint32_t l; asm volatile("mov.u32 %0, %%laneid;" : "=r"(l)); return l; }
__device__ __forceinline__ float quad_sum(float v) { v += __shfl_xor_sync(~0u, v, 1); v += __shfl_xor_sync(~0u, v, 2); return v; }
__device__ __forceinline__ float quad_max(float v) { v = fmaxf(v, __shfl_xor_sync(~0u, v, 1)); v = fmaxf(v, __shfl_xor_sync(~0u, v, 2)); return v; }
template <int N> __device__ __forceinline__ void pin(float (&d)[N]) {
#pragma unroll
  for (int i = 0; i < N; i++) asm volatile("" : "+f"(d[i]) :: "memory");
}
#define SPIN_GUARD(n) if (++(n) > SPIN_MAX) break

template <int NG> __device__ __forceinline__ void publish_stats(uint4* dst, const float* y, uint32_t tag, uint32_t lane) {
  float s0 = 0.f, s1 = 0.f;
#pragma unroll
  for (int g = 0; g < NG; g++) { s0 += y[4 * g] + y[4 * g + 1]; s1 += y[4 * g + 2] + y[4 * g + 3]; }
  s0 = quad_sum(s0); s1 = quad_sum(s1);
  const float m0 = s0 * (1.f / (8 * NG)), m1 = s1 * (1.f / (8 * NG));
  float q0 = 0.f, q1 = 0.f, q2 = 0.f, q3 = 0.f;
#pragma unroll
  for (int g = 0; g < NG; g++) {
    const float a = y[4 * g] - m0, b = y[4 * g + 1] - m0, c = y[4 * g + 2] - m1, d = y[4 * g + 3] - m1;
    q0 = fmaf(a, a, q0); q1 = fmaf(b, b, q1); q2 = fmaf(c, c, q2); q3 = fmaf(d, d, q3);
  }
  q0 = quad_sum(q0 + q1); q2 = quad_sum(q2 + q3);
  if ((lane & 3) == 0)
    stg4(dst + (lane >> 2), (__float_as_uint(s0) & ~1u) | tag, __float_as_uint(q0), __float_as_uint(s1), __float_as_uint(q2));
}

__device__ __forceinline__ void put72(uint4* slab, uint32_t j, uint32_t lane, const uint32_t* v, uint32_t r0, uint32_t r1) {
  uint4* p = slab + ((9 * j + 1) >> 1) * 32;
#pragma unroll
  for (int i = 0; i < 4; i++) stg4(p + lane + i * 32, nz(v[4 * i]), v[4 * i + 1], v[4 * i + 2], v[4 * i + 3]);
  stg2((char*)((j & 1) ? p - 16 : p + 4 * 32) + lane * 8, nz(r0), r1);
}
__device__ __forceinline__ void zero_share(uint4* slab, uint32_t j, uint32_t lane) {
  uint4* p = slab + j * 144 + lane;
#pragma unroll
  for (int i = 0; i < 4; i++) stg4(p + i * 32, 0u, 0u, 0u, 0u);
  if (lane < 16) stg4(p + 128, 0u, 0u, 0u, 0u);
}

struct Maps { CUtensorMap m[7]; };

struct Ring {
  uint32_t st, ph;
  __device__ __forceinline__ void next() { if (++st == NST) { st = 0; ph ^= 1; } }
};

#define GSTAMP(i) do {} while (0)
#define STAMP(i) do {} while (0)

__device__ __forceinline__ void tma_box(uint32_t dst, const CUtensorMap* m, int col, int row, uint32_t bar, uint32_t expect) {
  asm volatile("{\n.reg .pred e, h;\nelect.sync _|e, 0xffffffff;\nsetp.ne.and.u32 h, %5, 0, e;\n"
               "@h mbarrier.arrive.expect_tx.shared::cta.b64 _, [%2], %5;\n"
               "@e cp.async.bulk.tensor.2d.shared::cluster.global.mbarrier::complete_tx::bytes [%0], [%1, {%3, %4}], [%2];\n}"
               :: "r"(dst), "l"(m), "r"(bar), "r"(col), "r"(row), "r"(expect) : "memory");
}

__device__ __forceinline__ void bulk_load(uint32_t dst, const void* src, uint32_t bytes, uint32_t bar, bool arm) {
  asm volatile("{\n.reg .pred e, h;\nelect.sync _|e, 0xffffffff;\nsetp.ne.and.u32 h, %4, 0, e;\n"
               "@h mbarrier.arrive.expect_tx.shared::cta.b64 _, [%3], %2;\n"
               "@e cp.async.bulk.shared::cluster.global.mbarrier::complete_tx::bytes [%0], [%1], %2, [%3];\n}"
               :: "r"(dst), "l"(src), "r"(bytes), "r"(bar), "r"((uint32_t)arm) : "memory");
}

__global__ void __launch_bounds__(384, 1) mega_kernel(
    const __grid_constant__ Maps maps, uint4* __restrict__ scratch,
    const __nv_bfloat16* __restrict__ x_in, __nv_bfloat16* __restrict__ out) {
  extern __shared__ __align__(1024) uint8_t smem[];
  const uint32_t sb = (uint32_t)__cvta_generic_to_shared(smem);
  const uint32_t full0 = sb + BARS, empty0 = full0 + 8 * NST, rem_full = empty0 + 8 * NST, park_free = rem_full + 8, kv_free = park_free + 8;
  const uint32_t c8_go = kv_free + 8, c8_done = c8_go + 8, c8_full = c8_done + 8, remo_full = c8_full + 8, piece_full = remo_full + 8, pbar0 = piece_full + 8;
  const uint32_t w = __shfl_sync(~0u, threadIdx.x >> 5, 0);
  const uint32_t t = blockIdx.x >> 3, j = blockIdx.x & 7;
  const uint32_t odd = j & 1;
  uint4* const scr = scratch + t * TILE;
  {
    const uint32_t lane = lane_id(), r = lane >> 2, q = lane & 3;
    const uint32_t sl = w < 8 ? w : j, ch = w < 8 ? j : 8;
    const uint32_t* xr = (const uint32_t*)(x_in + (128 * t + 32 * (sl >> 1) + 2 * r + (sl & 1)) * 576 + 64 * ch + 2 * q);
    if (w < 8 || w == 9) {
      uint32_t v[16];
#pragma unroll
      for (int g = 0; g < 8; g++) {
        asm volatile("ld.global.nc.b32 %0, [%1];" : "=r"(v[2 * g]) : "l"(xr + 4 * g));
        asm volatile("ld.global.nc.b32 %0, [%1];" : "=r"(v[2 * g + 1]) : "l"(xr + 8 * 576 + 4 * g));
      }
      if (q == 0) {
#pragma unroll
        for (int k = 0; k < 3; k++) stg4(scr + OFF_S + (k * 8 + sl) * 96 + ch * 8 + r, 0u, 0u, 0u, 0u);
      }
      asm volatile("bar.sync 0, 384;" ::: "memory");
      uint4* p = scr + OFF_X + sl * SLAB + 4 * ch * 32 + lane;
#pragma unroll
      for (int i = 0; i < 4; i++) stg4(p + i * 32, nz(v[4 * i]), v[4 * i + 1], nz(v[4 * i + 2]), v[4 * i + 3]);
      float y[32];
#pragma unroll
      for (int i = 0; i < 16; i++) { y[2 * i] = bf_lo(v[i]); y[2 * i + 1] = bf_hi(v[i]); }
      publish_stats<8>(scr + OFF_S + sl * 96 + ch * 8, y, 1u, lane);
    } else {
      if (threadIdx.x == 256) {
        for (int i = 0; i < NST; i++) { mbar_init(full0 + 8 * i, 1); mbar_init(empty0 + 8 * i, 8); }
        mbar_init(rem_full, 1); mbar_init(park_free, 8); mbar_init(kv_free, 8); mbar_init(c8_go, 8); mbar_init(c8_done, 1); mbar_init(c8_full, 1); mbar_init(remo_full, 64); mbar_init(piece_full, 1);
        for (int i = 0; i < 8; i++) mbar_init(pbar0 + 8 * i, 5);
        asm volatile("fence.mbarrier_init.release.cluster;" ::: "memory");
      }
      __syncwarp();
      asm volatile("bar.sync 0, 384;" ::: "memory");
    }
  }

  if (w >= 8) {
    asm volatile("setmaxnreg.dec.sync.aligned.u32 24;");
    if (w == 8) {
      uint32_t dst = sb, bar = full0, ph = 1;
#pragma unroll 1
      for (int seg = 0; seg < 34; seg++) {
        const int n = seg >= 17 ? seg - 17 : seg;
        int ma, mb, ca, cb, row = 0;
        if (n < 3) { ma = mb = n == 2; ca = 72 * j + 8 * odd + (n == 0 ? 576 : 0); cb = ca + 576; }
        else if (n < 12) { ma = 3; mb = 2; ca = cb = 576 * j + 64 * (n - 3); }
        else { ma = mb = 4; ca = n == 12 ? 512 : ((j + 2 * n) & 7) * 64; cb = ((j + 2 * n + 1) & 7) * 64; row = 576 * j; }
        const bool zip = n == 0 || n == 3, solo = n == 1 || n == 2 || n == 16;
        const CUtensorMap *pa = &maps.m[ma], *pb = &maps.m[mb];
#pragma unroll 1
        for (int st = 0; st < (solo ? 5 : 9); st++) {
          const bool s0 = !zip && st > 4, s1 = zip || st >= 4;
          const int r0 = row + (zip ? 64 * st : s0 ? 128 * st - 576 : 128 * st), r1 = zip ? r0 : st == 4 ? row : r0 + 64;
          asm volatile("{\n.reg .pred p, e, f;\n.reg .u32 n;\nelect.sync _|e, 0xffffffff;\nsetp.eq.and.u32 f, %9, 16384, e;\nmov.u32 n, 0;\n"
                       "W: mbarrier.try_wait.parity.shared::cta.b64 p, [%1+48], %2;\n@p bra D;\n"
                       "add.u32 n, n, 1;\nsetp.lt.u32 p, n, 4194304;\n@p bra W;\ntrap;\n"
                       "D: @e mbarrier.arrive.expect_tx.shared::cta.b64 _, [%1], %9;\n"
                       "@e cp.async.bulk.tensor.2d.shared::cluster.global.mbarrier::complete_tx::bytes [%0], [%3, {%4, %5}], [%1];\n"
                       "@f cp.async.bulk.tensor.2d.shared::cluster.global.mbarrier::complete_tx::bytes [%0+8192], [%6, {%7, %8}], [%1];\n}"
                       :: "r"(dst), "r"(bar), "r"(ph), "l"(s0 ? pb : pa), "r"(s0 ? cb : ca), "r"(r0), "l"(s1 ? pb : pa), "r"(s1 ? cb : ca), "r"(r1),
                          "r"(solo && st == 4 ? STAGE / 2 : STAGE) : "memory");
          dst += STAGE; bar += 8;
          if (bar == full0 + 8 * NST) { dst = sb; bar = full0; ph ^= 1; }
        }
      }
    } else if (w == 9) {
      const uint32_t lane = lane_id();
      const uint32_t stg = sb + HSTG + lane * 16;
      uint32_t fph = 0;
#pragma unroll 1
      for (uint32_t layer = 0; layer < 2; layer++) {
        uint4* xb = scr + OFF_X + ((4 + layer) * 8 + j) * SLAB + 32 * 32;
        mbar_wait(c8_go, layer);
        int n = 0;
        while (true) {
          if (lane == 0) asm volatile("mbarrier.arrive.expect_tx.shared::cta.b64 _, [%0], 18432;" :: "r"(c8_full) : "memory");
          __syncwarp();
#pragma unroll 1
          for (uint32_t s = 0; s < 9; s++)
            bulk_load(sb + HSTG + s * 2048, s < 8 ? scr + OFF_P + (j + s * 8) * SLAB + 32 * 32 : xb, 2048, c8_full, false);
          mbar_wait(c8_full, fph); fph ^= 1;
          uint32_t bad = 0;
#pragma unroll 8
          for (int s = 0; s < 32; s++) { uint32_t v; asm volatile("ld.shared.b32 %0, [%1];" : "=r"(v) : "r"(stg + s * 512) : "memory"); bad |= v ^ (1 - layer); }
          if (__all_sync(~0u, (bad & 1u) == 0u)) break;
          __nanosleep(300);
          SPIN_GUARD(n);
        }
        float s0 = 0.f, s1 = 0.f;
#pragma unroll 1
        for (int g = 0; g < 8; g++) {
          const uint32_t a = stg + (g >> 1) * 512 + (g & 1) * 8;
          float a0 = 0.f, a1 = 0.f, a2 = 0.f, a3 = 0.f;
#pragma unroll 1
          for (int b = 0; b < 3; b++) {
            uint32_t v[6];
#pragma unroll
            for (int s = 0; s < 3; s++) lds2(a + (3 * b + s) * 2048, v + 2 * s);
#pragma unroll
            for (int s = 0; s < 3; s++) { a0 += bf_lo(v[2 * s]); a1 += bf_hi(v[2 * s]); a2 += bf_lo(v[2 * s + 1]); a3 += bf_hi(v[2 * s + 1]); }
          }
          sts1(a + 18432, pack_bf16(a0, a1)); sts1(a + 18436, pack_bf16(a2, a3));
          s0 += a0 + a1; s1 += a2 + a3;
        }
        __syncwarp();
        if (lane == 0) mbar_arrive(c8_done);
        s0 = quad_sum(s0); s1 = quad_sum(s1);
        float q0 = 0.f, q1 = 0.f;
        const uint32_t ln = lane_id();
#pragma unroll 1
        for (uint32_t i = 0; i < 4; i++) {
          uint32_t x[4];
          lds4(stg + 18432 + i * 512, x);
          stg4(xb + i * 32 + ln, 0u, 0u, 0u, 0u);
          if (layer == 0) {
            stg4(xb - 3 * 8 * SLAB + i * 32 + ln, nz(x[0]), x[1], x[2], x[3]);
#pragma unroll
            for (int e = 0; e < 4; e++) {
              const float m = (e & 1) ? s1 : s0, c = fmaf(m, -1.f / 64, bf_lo(x[e])), d = fmaf(m, -1.f / 64, bf_hi(x[e]));
              if (e & 1) q1 = fmaf(c, c, fmaf(d, d, q1)); else q0 = fmaf(c, c, fmaf(d, d, q0));
            }
          } else {
            uint32_t* o = (uint32_t*)(out + (128 * t + 32 * (j >> 1) + 2 * (ln >> 2) + (j & 1)) * 576 + 512 + 16 * i + 2 * (ln & 3));
            o[0] = x[0]; o[8 * 576] = x[1]; o[4] = x[2]; o[8 * 576 + 4] = x[3];
          }
        }
        if (layer == 0) {
          q0 = quad_sum(q0); q1 = quad_sum(q1);
          if ((ln & 3) == 0) stg4(scr + OFF_S + j * 96 + 64 + (ln >> 2), __float_as_uint(s0) & ~1u, __float_as_uint(q0), __float_as_uint(s1), __float_as_uint(q1));
        }
      }
    } else {
      const uint32_t lane = lane_id(), r = lane >> 2, q = lane & 3;
#pragma unroll 1
      for (uint32_t layer = 0; layer < 2; layer++) {
        if (w == 10) {
          if (layer == 0) {
            const uint32_t p = t >> 2;
            tma_box(sb + PARK, &maps.m[p == 3 ? 6 : 5], 72 * j + (odd ? 0 : 64) + (p < 2 ? 576 * (p + 1) : 0), 144 * (t & 3), piece_full, 2304);
            mbar_wait(piece_full, 0);
            asm volatile("{\n.reg .pred e;\nelect.sync _|e, 0xffffffff;\n@e cp.async.bulk.global.shared::cta.bulk_group [%0], [%1], 2304;\n}\n"
                         "cp.async.bulk.commit_group;\ncp.async.bulk.wait_group 0;\nfence.proxy.async;"
                         :: "l"(scratch + OFF_R + j * 2304 + t * 144), "r"(sb + PARK) : "memory");
            __syncwarp();
            if (lane < 16) asm volatile("st.release.gpu.global.b32 [%0], 1;" :: "l"((uint32_t*)(scratch + OFF_F + (lane * 8 + j) * 8) + t) : "memory");
            uint32_t* fl = (uint32_t*)(scratch + OFF_F + (t * 8 + j) * 8) + (lane & 15);
            uint32_t v;
            int n = 0;
            while (true) {
              asm volatile("ld.acquire.gpu.global.b32 %0, [%1];" : "=r"(v) : "l"(fl) : "memory");
              if (__all_sync(~0u, v != 0u)) break;
              __nanosleep(100);
              SPIN_GUARD(n);
            }
            asm volatile("fence.proxy.async;\nst.relaxed.gpu.global.b32 [%0], 0;" :: "l"(fl) : "memory");
          } else {
            mbar_wait(park_free, 0);
          }
          bulk_load(sb + REM, scratch + OFF_R + j * 2304, 36864, rem_full, true);
        }
        mbar_wait(rem_full, layer);
#pragma unroll 1
        for (uint32_t b = 0; b < 5; b++) {
          const uint32_t blk = sb + REM + 27648 + b * 2048, k = threadIdx.x - 320, rr = k & 7;
          const uint32_t dst = blk + ((k >> 3) & 1) * 1024 + rr * 128 + (((k >> 4) ^ rr) << 4);
          uint32_t v[8];
          lds4(blk + k * 16, v); lds4(blk + 1024 + k * 16, v + 4);
          asm volatile("bar.sync 3, 64;" ::: "memory");
          sts4(dst, v); sts4(dst ^ 64, v + 4);
        }
        asm volatile("fence.proxy.async.shared::cta;" ::: "memory");
        mbar_arrive(remo_full);
        if (layer) mbar_wait(kv_free, 0);
        if (t > 0) {
#pragma unroll 1
          for (uint32_t pc = 0; pc < 3; pc++) {
            uint4* hp = scr + OFF_H + ((layer * 8 + j) * 2 + (w - 10)) * 192 + pc * 64 + lane;
            uint32_t hl[8];
            int n = 0;
            hl[4] = 1u;
            while (true) {
              ldg4(hl, hp);
              if (pc < 2) ldg4(hl + 4, hp + 32);
              if (__all_sync(~0u, hl[0] != 0u && hl[4] != 0u)) break;
              __nanosleep(100);
              SPIN_GUARD(n);
            }
            const uint32_t dst = sb + KVS + (w - 10) * 10368 + r * 144 + q * 4;
            if (pc < 2) {
#pragma unroll
              for (int g = 0; g < 8; g++) sts1(dst + pc * 20736 + odd * 16 + g * 16, hl[g]);
              stg4(hp + 32, 0u, 0u, 0u, 0u);
            } else {
              sts1(dst + (odd ? 0 : 128), hl[0]); sts1(dst + 20736 + (odd ? 0 : 128), hl[1]);
            }
            stg4(hp, 0u, 0u, 0u, 0u);
          }
        }
        asm volatile("bar.arrive 1, 192;" ::: "memory");
      }
    }
  } else {
    asm volatile("setmaxnreg.inc.sync.aligned.u32 240;");
    const uint32_t lane = lane_id(), r = lane >> 2, q = lane & 3;
    Ring rg{0, 0};
    uint32_t prev = 0;
    uint32_t X[144];
    float rs0, rs1;
    uint32_t mean0, mean1;
    auto release = [&](uint32_t st) { if (lane == 0) mbar_arrive(empty0 + st * 8); };
    auto load_kb = [&](int kb, const uint4* src, const char* lo, uint32_t hoff) {
#pragma unroll
      for (int k = 4 * kb; k < 4 * kb + 4; k++) {
        if (k % 9 == 4) { ldg2(X + 4 * k, lo + k * 512); ldg2(X + 4 * k + 2, lo + hoff + k * 512); }
        else ldg4(X + 4 * k, src + k * 32);
      }
    };
    auto next_kb = [&](bool center, int kb, const uint4* src, const char* lo, uint32_t hoff) {
      int n = 0;
      while (true) {
        uint32_t m = umin2(umin2(X[16 * kb], X[16 * kb + 4]), umin2(X[16 * kb + 8], X[16 * kb + 12]));
        if (kb & 1) m = umin2(m, X[16 * kb + 4 * (kb >> 1) + 2]);
        if (__all_sync(~0u, m != 0u)) break;
        SPIN_GUARD(n);
        load_kb(kb, src, lo, hoff);
      }
      if (kb + (center ? GD : GO) < 9) load_kb(kb + (center ? GD : GO), src, lo, hoff);
      if (center) {
#pragma unroll
        for (int i = 16 * kb; i < 16 * kb + 16; i++) X[i] = sub_bf16x2(X[i], (i & 1) ? mean1 : mean0);
      }
    };
#pragma unroll 1
    for (uint32_t hf = 0; hf < 4; hf++) {
      const uint32_t layer = hf >> 1;
      const bool ffn = hf & 1;
      const uint32_t tag = 1 - layer;
      uint4* const xbase = scr + OFF_X + (layer * 8 + w) * SLAB;
      float aA[32], aB[32];
      {
        const uint4* src = xbase + (ffn ? 32 * SLAB : 0) + lane;
        const char* lo = (const char*)src - (ffn ? lane * 8 : 0);
        const uint32_t hoff = ffn ? 256 : 8;
        uint32_t s[3][4];
        const uint4* p = scr + OFF_S + ((ffn ? 16 : 0) + w) * 96 + q * 8 + r;
        const bool third = !ffn && q == 0;
        int n = 0;
        s[2][0] = tag; s[2][1] = s[2][2] = s[2][3] = 0u;
        STAMP(ffn * 16 + 0);
        while (true) {
          ldg4(s[0], p); ldg4(s[1], p + 32);
          if (third) ldg4(s[2], p + 64);
          if (__all_sync(~0u, ((diff2(s[0][0], s[1][0], tag) | diff2(s[2][0], s[2][0], tag)) & 1u) == 0u)) break;
          SPIN_GUARD(n);
        }
        STAMP(ffn * 16 + 1);
        GSTAMP(14 + ffn);
#pragma unroll
        for (int kb = 0; kb < GD; kb++) load_kb(kb, src, lo, hoff);
        float t0 = 0.f, t1 = 0.f;
#pragma unroll
        for (int i = 0; i < 3; i++) { t0 += __uint_as_float(s[i][0]); t1 += __uint_as_float(s[i][2]); }
        const float m0 = quad_sum(t0) * (1.f / 576), m1 = quad_sum(t1) * (1.f / 576);
        const float cnt = ffn ? 72.f : 64.f, inv = ffn ? 1.f / 72 : 1.f / 64;
        float v0 = 0.f, v1 = 0.f;
#pragma unroll
        for (int i = 0; i < 3; i++) {
          const float c = (i < 2 || third) ? cnt : 0.f;
          const float d0 = fmaf(__uint_as_float(s[i][0]), inv, -m0), d1 = fmaf(__uint_as_float(s[i][2]), inv, -m1);
          v0 += fmaf(d0 * d0, c, __uint_as_float(s[i][1])); v1 += fmaf(d1 * d1, c, __uint_as_float(s[i][3]));
        }
        rs0 = rsqrtf(fmaf(quad_sum(v0), 1.f / 576, 1e-5f)); rs1 = rsqrtf(fmaf(quad_sum(v1), 1.f / 576, 1e-5f));
        mean0 = pack_bf16(m0, m0); mean1 = pack_bf16(m1, m1);
#pragma unroll
        for (int kb = 0; kb < 9; kb++) {
          next_kb(true, kb, src, lo, hoff);
          mbar_wait(full0 + rg.st * 8, rg.ph);
          const uint64_t desc = DESC_HI | ((sb + rg.st * STAGE) >> 4);
          wg_fence();
#pragma unroll
          for (int i = 0; i < 4; i++) wgmma_rs_n64(aA, X + 4 * (4 * kb + i), desc + i * 128, kb + i != 0);
#pragma unroll
          for (int i = 0; i < 4; i++) wgmma_rs_n64(aB, X + 4 * (4 * kb + i), desc + 512 + i * 128, kb + i != 0);
          wg_commit();
          wg_wait<1>();
          if (kb > 0) release(prev);
          prev = rg.st; rg.next();
        }
        wg_wait<0>();
        STAMP(ffn * 16 + 2);
      }
      if (!ffn) {
      release(prev);
      const uint32_t kvrow = sb + KVS + (w & 1) * 10368 + (16 * (w >> 1)) * 144;
      uint32_t Q[18];
      {
        const uint32_t dst = kvrow + (8 + r) * 144 + q * 4 + odd * 16, dstr = dst + (odd ? -16 : 128);
        const bool edge_out = w >= 6 && t < 15;
        uint4* const hp = scr + TILE + OFF_H + ((layer * 8 + j) * 2 + (w & 1)) * 192 + lane;
        auto put_kv = [&](float (&a)[32], int part) {
          pin(a);
          uint32_t hl[8];
#pragma unroll
          for (int g = 0; g < 8; g++) {
            hl[g] = pack_bf16(a[4 * g + 2] * rs1, a[4 * g + 3] * rs1);
            sts1(dst + part * 20736 + g * 16, pack_bf16(a[4 * g] * rs0, a[4 * g + 1] * rs0)); sts1(dst + part * 20736 + 8 * 144 + g * 16, hl[g]);
          }
          if (edge_out) { stg4(hp + part * 64, nz(hl[0]), hl[1], hl[2], hl[3]); stg4(hp + part * 64 + 32, nz(hl[4]), hl[5], hl[6], hl[7]); }
        };
        put_kv(aA, 0);
        float aR[12];
        mbar_wait(rem_full, layer);
        const uint64_t dr = DESC_REM | ((sb + REM) >> 4);
        wg_fence();
#pragma unroll
        for (int s = 0; s < 36; s++) {
          wgmma_rs_n24(aR, X + 4 * s, dr + s * 16, s != 0);
          if (s == 4) put_kv(aB, 1);
        }
        wg_commit();
#pragma unroll
        for (int kb = 0; kb < 9; kb++) {
          if (kb == HOFF1 && w < 4) asm volatile("bar.sync 4, 256;" ::: "memory");
          if (kb == 8 && HOFF1 < 9 && w >= 4) asm volatile("bar.arrive 4, 256;" ::: "memory");
          if (!(kb & 1)) mbar_wait(full0 + rg.st * 8, rg.ph);
          const uint64_t desc = DESC_HI | ((sb + rg.st * STAGE + (kb & 1) * 8192) >> 4);
          wg_fence();
#pragma unroll
          for (int i = 0; i < 4; i++) wgmma_rs_n64(aB, X + 4 * (4 * kb + i), desc + i * 128, kb + i != 0);
          wg_commit();
          wg_wait<1>();
          if (kb > 0 && !(kb & 1)) release(prev);
          if ((kb & 1) || kb == 8) { prev = rg.st; rg.next(); }
          if (kb == 0) {
            pin(aR);
            const uint32_t k1 = pack_bf16(aR[2] * rs1, aR[3] * rs1), v1 = pack_bf16(aR[6] * rs1, aR[7] * rs1);
            if (edge_out) stg4(hp + 128, nz(k1), v1, 0u, 0u);
            sts1(dstr, pack_bf16(aR[0] * rs0, aR[1] * rs0)); sts1(dstr + 8 * 144, k1);
            sts1(dstr + 20736, pack_bf16(aR[4] * rs0, aR[5] * rs0)); sts1(dstr + 20736 + 8 * 144, v1);
            Q[16] = pack_bf16(aR[8] * rs0, aR[9] * rs0); Q[17] = pack_bf16(aR[10] * rs1, aR[11] * rs1);
            if (w < 4) asm volatile("bar.arrive 2, 256;" ::: "memory");
          }
        }
        wg_wait<0>();
        release(prev);
        pin(aB);
        STAMP(3);
#pragma unroll
        for (int g = 0; g < 8; g++) {
          Q[2 * g] = pack_bf16(aB[4 * g] * rs0, aB[4 * g + 1] * rs0); Q[2 * g + 1] = pack_bf16(aB[4 * g + 2] * rs1, aB[4 * g + 3] * rs1);
        }
        if (odd) {
          const uint32_t r0 = Q[16], r1 = Q[17];
#pragma unroll
          for (int i = 17; i >= 2; i--) Q[i] = Q[i - 2];
          Q[0] = r0; Q[1] = r1;
        }
      }
      if (w < 4) asm volatile("bar.sync 1, 192;" ::: "memory");
      else asm volatile("bar.sync 2, 256;" ::: "memory");
      STAMP(4);
      uint32_t O[18];
      {
        const bool edge = (t == 0 && w < 2);
        uint32_t row[3];
#pragma unroll
        for (int nt = 0; nt < 3; nt++) row[nt] = kvrow + (8 * nt + (lane & 7)) * 144;
        if (edge) row[0] = sb + KVS + 8 * 144;
        const uint32_t rlast = ((lane >> 3) == 0 ? row[0] : (lane >> 3) == 1 ? row[1] : row[2]) + 128;
        uint32_t K[3][9], V[3][9], dummy;
#pragma unroll
        for (int nt = 0; nt < 3; nt++) {
          ldsm4(row[nt] + (lane >> 3) * 16, K[nt][0], K[nt][1], K[nt][2], K[nt][3]);
          ldsm4(row[nt] + 64 + (lane >> 3) * 16, K[nt][4], K[nt][5], K[nt][6], K[nt][7]);
        }
        ldsm4(rlast, K[0][8], K[1][8], K[2][8], dummy);
#pragma unroll
        for (int nt = 0; nt < 3; nt++) {
          ldsm4t(row[nt] + 20736 + (lane >> 3) * 16, V[nt][0], V[nt][1], V[nt][2], V[nt][3]);
          ldsm4t(row[nt] + 20736 + 64 + (lane >> 3) * 16, V[nt][4], V[nt][5], V[nt][6], V[nt][7]);
        }
        ldsm4t(rlast + 20736, V[0][8], V[1][8], V[2][8], dummy);
        const bool up0 = 2 * q > r, up1 = 2 * q + 1 > r;
        const float sc = 0.23570226039551584f * 1.4426950408889634f;
        const float neg = -1e9f * 1.4426950408889634f;
        float Of[9][4];
#pragma unroll
        for (int h = 0; h < 4; h++) {
          const uint32_t a0 = q >= h ? Q[4 * h] : 0u, a1 = q >= h ? Q[4 * h + 1] : 0u;
          const uint32_t a4 = q <= h ? Q[4 * h + 4] : 0u, a5 = q <= h ? Q[4 * h + 5] : 0u;
          float S[3][4];
#pragma unroll
          for (int nt = 0; nt < 3; nt++) {
            S[nt][0] = S[nt][1] = S[nt][2] = S[nt][3] = 0.f;
            mma16(S[nt], a0, a1, Q[4 * h + 2], Q[4 * h + 3], K[nt][2 * h], K[nt][2 * h + 1]);
            mma8(S[nt], a4, a5, K[nt][2 * h + 2]);
          }
          float s00 = (up0 ? S[0][0] : S[1][0]) * sc, s01 = (up1 ? S[0][1] : S[1][1]) * sc;
          const float s10 = (up0 ? S[1][2] : S[2][2]) * sc, s11 = (up1 ? S[1][3] : S[2][3]) * sc;
          if (edge && up0) s00 = neg;
          if (edge && up1) s01 = neg;
          const float m0 = quad_max(fmaxf(s00, s01)), m1 = quad_max(fmaxf(s10, s11));
          float p00 = ex2(s00 - m0), p01 = ex2(s01 - m0), p10 = ex2(s10 - m1), p11 = ex2(s11 - m1);
          const float i0 = rcp(quad_sum(p00 + p01)), i1 = rcp(quad_sum(p10 + p11));
          p00 *= i0; p01 *= i0; p10 *= i1; p11 *= i1;
          const uint32_t pa = pack_bf16(up0 ? p00 : 0.f, up1 ? p01 : 0.f), pb = pack_bf16(up0 ? 0.f : p00, up1 ? 0.f : p01);
          const uint32_t pc = pack_bf16(up0 ? p10 : 0.f, up1 ? p11 : 0.f), pd = pack_bf16(up0 ? 0.f : p10, up1 ? 0.f : p11);
#pragma unroll
          for (int gi = 0; gi < 3; gi++) {
            const int g = 2 * h + gi;
            float o[4] = {0.f, 0.f, 0.f, 0.f};
            mma16(o, pa, 0u, pb, pc, V[0][g], V[1][g]);
            mma8(o, 0u, pd, V[2][g]);
#pragma unroll
            for (int e = 0; e < 4; e++) Of[g][e] = (gi == 0 && h > 0 && q < h) ? Of[g][e] : o[e];
          }
        }
#pragma unroll
        for (int g = 0; g < 9; g++) { O[2 * g] = pack_bf16(Of[g][0], Of[g][1]); O[2 * g + 1] = pack_bf16(Of[g][2], Of[g][3]); }
      }
      if (odd) put72(xbase + 16 * SLAB, j, lane, O + 2, O[0], O[1]);
      else put72(xbase + 16 * SLAB, j, lane, O, O[16], O[17]);
      if (q == 0) stg4(scr + OFF_S + (8 + w) * 96 + j * 8 + r, tag, 0u, 0u, 0u);
      {
        uint32_t res[18];
        const uint4* p = xbase + ((9 * j + 1) >> 1) * 32 + lane;
#pragma unroll
        for (int i = 0; i < 4; i++) ldg4(res + 4 * i, p + i * 32);
        ldg2(res + 16, odd ? (const char*)(p - 32) + 8 : (const char*)(p + 4 * 32));
        const uint4* src = xbase + 16 * SLAB + lane;
        {
          const uint4* fp = scr + OFF_S + (8 + w) * 96 + q * 8 + r;
          uint32_t s0[4], s1[4];
          int n = 0;
          STAMP(8);
          while (true) {
            ldg4(s0, fp); ldg4(s1, fp + 32);
            if (__all_sync(~0u, (diff2(s0[0], s1[0], tag) & 1u) == 0u)) break;
            SPIN_GUARD(n);
          }
          STAMP(9);
        }
#pragma unroll
        for (int kb = 0; kb < GO; kb++) load_kb(kb, src, (const char*)src - lane * 8, 256);
        float acc[36];
        mbar_wait(remo_full, layer);
#pragma unroll
        for (int kb = 0; kb < 9; kb++) {
          next_kb(false, kb, src, (const char*)src - lane * 8, 256);
          if (!(kb & 1)) mbar_wait(full0 + rg.st * 8, rg.ph);
          const uint32_t base = sb + rg.st * STAGE + (kb & 1) * 8192;
          const uint64_t d0 = DESC_HI | ((base >> 4) + (((sb + REM + 27648 + (kb >> 1) * 2048 + (kb & 1) * 64 - base) >> 4) << 16));
          wg_fence();
#pragma unroll
          for (int i = 0; i < 4; i++) wgmma_rs_n72(acc, X + 4 * (4 * kb + i), d0 - (uint64_t)(i * ((127u << 16) - 128u)), kb + i != 0);
          wg_commit();
          wg_wait<1>();
          if (kb > 0 && !(kb & 1)) release(prev);
          if ((kb & 1) || kb == 8) { prev = rg.st; rg.next(); }
        }
        wg_wait<0>();
        release(prev);
        pin(acc);
        STAMP(10);
#pragma unroll
        for (int i = 0; i < 18; i++) {
          acc[2 * i] += bf_lo(res[i]); acc[2 * i + 1] += bf_hi(res[i]);
          res[i] = pack_bf16(acc[2 * i], acc[2 * i + 1]);
        }
        put72(xbase + 32 * SLAB, j, lane, res, res[16], res[17]);
        publish_stats<9>(scr + OFF_S + (16 + w) * 96 + j * 8, acc, tag, lane);
      }
      continue;
      }
      const uint32_t hp = sb + PARK + w * 512 + lane * 16;
      auto pack8 = [&](float (&a)[32], int p, uint32_t* o) {
#pragma unroll
        for (int e = 0; e < 8; e++) asm volatile("" : "+f"(a[8 * p + e]) :: "memory");
#pragma unroll
        for (int e = 0; e < 4; e++) o[e] = pack_bf16(a[8 * p + 2 * e], a[8 * p + 2 * e + 1]);
      };
      const float ka0 = 0.7978845608028654f * rs0, kb0 = 0.044715f * ka0 * rs0 * rs0, ku0 = 0.5f * rs0 * rs0;
      const float ka1 = 0.7978845608028654f * rs1, kb1 = 0.044715f * ka1 * rs1 * rs1, ku1 = 0.5f * rs1 * rs1;
      auto packu8 = [&](int p, uint32_t* o) {
#pragma unroll
        for (int e = 0; e < 8; e++) asm volatile("" : "+f"(aA[8 * p + e]) :: "memory");
#pragma unroll
        for (int e = 0; e < 4; e++) o[e] = pack_bf16(aA[8 * p + 2 * e] * ((e & 1) ? ku1 : ku0), aA[8 * p + 2 * e + 1] * ((e & 1) ? ku1 : ku0));
      };
      auto geglu8 = [&](int p, uint32_t* u) {
#pragma unroll
        for (int e = 0; e < 8; e++) asm volatile("" : "+f"(aB[8 * p + e]) :: "memory");
        float h[8];
#pragma unroll
        for (int e = 0; e < 8; e++) {
          const float g = aB[8 * p + e];
          h[e] = fmaf(g, tanh_ap(g * fmaf(g * g, (e & 2) ? kb1 : kb0, (e & 2) ? ka1 : ka0)), g);
        }
#pragma unroll
        for (int e = 0; e < 4; e++) u[e] = mul_bf16x2(pack_bf16(h[2 * e], h[2 * e + 1]), u[e]);
      };
      auto box = [&](int b, auto&& filler) {
        const int kb = b < 9 ? b : b - 9;
        if (!(b & 1)) { if ((TRAPB >> (b >> 1)) & 1) mbar_wait_trap(full0 + rg.st * 8, rg.ph); else mbar_wait(full0 + rg.st * 8, rg.ph); }
        const uint64_t desc = DESC_HI | ((sb + rg.st * STAGE + (b & 1) * 8192) >> 4);
        wg_fence();
#pragma unroll
        for (int i = 0; i < 4; i++) {
          if (b < 9) wgmma_rs_n64(aA, X + 4 * (4 * kb + i), desc + i * 128, kb + i != 0);
          else wgmma_rs_n64(aB, X + 4 * (4 * kb + i), desc + i * 128, kb + i != 0);
          if (i == FPOS) filler();
        }
        wg_commit();
        if (b & 1) { prev = rg.st; rg.next(); } else { wg_wait<1>(); release(prev); }
      };
      auto nop = [] {};
      auto step = [&](int st, auto&& filler) { box(2 * st, nop); box(2 * st + 1, filler); };
#pragma unroll
      for (int p = 0; p < 4; p++) { uint32_t o[4]; packu8(p, o); sts4(hp + p * 4096, o); }
      box(0, nop);
      zero_share(xbase, j, lane);
      zero_share(xbase + 16 * SLAB, j, lane);
#pragma unroll 1
      for (int c = 1;; c++) {
        const uint32_t hc = hp + c * 4 * 4096;
#pragma unroll
        for (int b = 1; b < 18; b++) box(b, [&] {
          if ((b & 1) && b < 8) { uint32_t o[4]; const uint32_t a = hc - (4 - (b >> 1)) * 4096; lds4(a, o); geglu8(b >> 1, o); sts4(a, o); }
          if ((b & 1) && b > 10) { uint32_t o[4]; packu8((b - 11) >> 1, o); if (c < 8) sts4(hc + ((b - 11) >> 1) * 4096, o); } });
        if (c == 8) break;
        box(0, nop);
      }
      wg_wait<0>();
      STAMP(21);
      GSTAMP(19);
#pragma unroll
      for (int s = 0; s < 32; s++) lds4(hp + s * 4096, X + 4 * s);
#pragma unroll
      for (int p = 0; p < 4; p++) packu8(p, X + 128 + 4 * p);
#pragma unroll
      for (int st = 0; st < 4; st++) step(st, [&] { geglu8(st, X + 128 + 4 * st); });
      STAMP(24);
      if (layer == 0 && lane == 0) mbar_arrive(park_free);
      const uint32_t lane2 = lane_id();
      uint4* const pw = scr + OFF_P + (j * 8 + w) * SLAB + lane2;
      const uint4* const pr = scr + OFF_P + w * SLAB + 4 * j * 32 + lane2;
      auto put_part = [&](float (&a)[32], int p, uint32_t chunk) {
        uint32_t o[4];
        pack8(a, p, o);
        stg4(pw + (chunk * 4 + p) * 32, (o[0] & ~1u) | tag, o[1], o[2], o[3]);
      };
      uint4* const xb = xbase + 32 * SLAB + 4 * j * 32;
      auto slot = [&](int p) { return sb + w * 2048 + (p < 3 ? PARK + p * 16384 : KVS + (p - 3) * 16384); };
      auto fetch = [&](int p) {
        bulk_load(slot(p), p ? scr + OFF_P + (((j - p) & 7) * 8 + w) * SLAB + 4 * j * 32 : xb, 2048, pbar0 + w * 8, true);
      };
#pragma unroll 1
      for (int sp = 0;; sp++) {
        const uint32_t ca = sp == 0 ? 8 : ((j + 2 * sp) & 7), cb = (j + 2 * sp + 1) & 7;
        if (sp == 1 && lane2 == 0) mbar_arrive(c8_go);
#pragma unroll
        for (int st = 4; st < 9; st++) step(st, [&] {
          if (st == 5 || st == 6) { put_part(aA, 2 * (st - 5), ca); put_part(aA, 2 * (st - 5) + 1, ca); }
          if (st == 8 && sp > 0) { if (sp == 3) mbar_wait(c8_done, layer); fetch(2 * sp - 2); } });
        STAMP(25 + sp);
        if (sp == 3) break;
        if (sp == 2 && layer == 0 && (lane2 & 3) == 0) {
#pragma unroll
          for (int k = 0; k < 3; k++) stg4(scr + OFF_S + (k * 8 + w) * 96 + j * 8 + (lane2 >> 2), 1u, 0u, 0u, 0u);
        }
#pragma unroll
        for (int st = 0; st < 4; st++) step(st, [&] {
          if (st < 2) { put_part(aB, 2 * st, cb); put_part(aB, 2 * st + 1, cb); }
          if (st == 3 && sp > 0) fetch(2 * sp - 1); });
      }
      auto load_p = [&](int p, uint32_t* d) {
#pragma unroll
        for (int i = 0; i < 4; i++) ldg4(d + 4 * i, pr + ((j - p) & 7) * 8 * SLAB + i * 32);
      };
#pragma unroll
      for (int b = 0; b < 9; b++) {
        if (b == HOFF2 && w < 4) asm volatile("bar.sync 5, 256;" ::: "memory");
        box(b, [&] {
          if (b == 1) {
#pragma unroll
            for (int p = 0; p < 4; p++) put_part(aB, p, (j + 7) & 7);
          }
          if (b == 3) { load_p(5, X); load_p(6, X + 16); }
          if (b == 7 && EXP != 1) load_p(7, X + 32); });
        if (b == 7 && HOFF2 < 9 && w >= 4) asm volatile("bar.arrive 5, 256;" ::: "memory");
      }
      mbar_wait(pbar0 + w * 8, layer);
#pragma unroll
      for (int p = 1; p < 5; p++)
#pragma unroll
        for (int i = 0; i < 4; i++) lds4(slot(p) + lane2 * 16 + i * 512, X + 48 + 16 * p + 4 * i);
#pragma unroll
      for (int i = 0; i < 4; i++) {
        const bool split = j == 2 * i + 1;
        const uint32_t a = slot(0) + i * 512 + (split ? lane2 * 8 : lane2 * 16);
        lds2(a, X + 48 + 4 * i); lds2(a + (split ? 256 : 8), X + 50 + 4 * i);
      }
      wg_wait<0>();
      release(rg.st); rg.next();
      pin(aA);
      STAMP(22);
      GSTAMP(20);
      {
        const uint32_t eye = r == 2 * q ? 0x3f80u : r == 2 * q + 1 ? 0x3f800000u : 0u;
        auto bad = [&](const uint32_t* d) { return diff2(d[0], d[4], tag) | diff2(d[8], d[12], tag); };
        auto add = [&](const uint32_t* d) {
#pragma unroll
          for (int g = 0; g < 8; g++) mma8(aA + 4 * g, d[2 * g], d[2 * g + 1], eye);
        };
        int n = 0;
        while (!__all_sync(~0u, ((or3(bad(X), bad(X + 16), bad(X + 64)) | or3(bad(X + 80), bad(X + 96), bad(X + 112))) & 1u) == 0u)) {
          SPIN_GUARD(n);
          load_p(5, X); load_p(6, X + 16);
#pragma unroll
          for (int p = 1; p < 5; p++) load_p(p, X + 48 + 16 * p);
        }
        add(X); add(X + 16);
#pragma unroll
        for (int p = 4; p >= 0; p--) add(X + 48 + 16 * ((p + 1) % 5));
        STAMP(11);
        if (EXP != 1) while (!__all_sync(~0u, (bad(X + 32) & 1u) == 0u)) { SPIN_GUARD(n); load_p(7, X + 32); }
        add(X + 32);
        STAMP(12);
        uint32_t res[16];
#pragma unroll
        for (int i = 0; i < 16; i++) res[i] = pack_bf16(aA[2 * i], aA[2 * i + 1]);
        if (layer == 0) {
          uint4* p = xbase + 8 * SLAB + 4 * j * 32 + lane;
#pragma unroll
          for (int i = 0; i < 4; i++) stg4(p + i * 32, nz(res[4 * i]), res[4 * i + 1], nz(res[4 * i + 2]), res[4 * i + 3]);
          publish_stats<8>(scr + OFF_S + w * 96 + j * 8, aA, 0u, lane);
          if (lane == 0) mbar_arrive(kv_free);
        } else {
          const uint32_t tb = slot(0);
          __syncwarp();
#pragma unroll
          for (int i = 0; i < 4; i++) {
            const uint32_t row = (lane2 & 7) + (lane2 & 8), g = 2 * i + (lane2 >> 4);
            asm volatile("stmatrix.sync.aligned.m8n8.x4.shared.b16 [%0], {%1,%2,%3,%4};"
                         :: "r"(tb + row * 128 + ((g ^ (row & 7)) << 4)), "r"(res[4 * i]), "r"(res[4 * i + 1]), "r"(res[4 * i + 2]), "r"(res[4 * i + 3]) : "memory");
          }
          __syncwarp();
#pragma unroll
          for (int i = 0; i < 4; i++) {
            const uint32_t row = 4 * i + (lane2 >> 3), g = lane2 & 7;
            uint32_t v[4];
            lds4(tb + row * 128 + ((g ^ (row & 7)) << 4), v);
            *(uint4*)(out + (128 * t + 32 * (w >> 1) + 2 * row + (w & 1)) * 576 + 64 * j + 8 * g) = make_uint4(v[0], v[1], v[2], v[3]);
          }
        }
#pragma unroll
        for (int i = 0; i < 4; i++) stg4(xb + lane + i * 32, 0u, 0u, 0u, 0u);
      }
      STAMP(23);
    }
  }
}

typedef CUresult (*EncodeFn)(CUtensorMap*, CUtensorMapDataType, cuuint32_t, void*, const cuuint64_t*, const cuuint64_t*,
                             const cuuint32_t*, const cuuint32_t*, CUtensorMapInterleave, CUtensorMapSwizzle,
                             CUtensorMapL2promotion, CUtensorMapFloatOOBfill);

CUtensorMap make_map(EncodeFn f, const void* p, uint64_t cols, uint64_t rows, bool rem = false) {
  CUtensorMap m;
  cuuint64_t dims[2] = {cols, rows};
  cuuint64_t str[1] = {cols * 2};
  cuuint32_t box[2] = {rem ? 8u : 64u, rem ? 144u : 64u};
  cuuint32_t es[2] = {1, 1};
  f(&m, CU_TENSOR_MAP_DATA_TYPE_BFLOAT16, 2, const_cast<void*>(p), dims, str, box, es, CU_TENSOR_MAP_INTERLEAVE_NONE,
    rem ? CU_TENSOR_MAP_SWIZZLE_NONE : CU_TENSOR_MAP_SWIZZLE_128B, CU_TENSOR_MAP_L2_PROMOTION_NONE, CU_TENSOR_MAP_FLOAT_OOB_FILL_NONE);
  return m;
}

}

extern "C" void kernel_launch(void* const* d_in, const int* in_sizes, int n_in, void* d_out, int out_size) {
  void* fn = nullptr;
  cudaDriverEntryPointQueryResult qr;
  cudaGetDriverEntryPoint("cuTensorMapEncodeTiled", &fn, cudaEnableDefault, &qr);
  EncodeFn enc = (EncodeFn)fn;
  Maps maps;
  maps.m[0] = make_map(enc, d_in[1], 1728, 576); maps.m[1] = make_map(enc, d_in[2], 576, 576);
  maps.m[2] = make_map(enc, d_in[4], 4608, 576); maps.m[3] = make_map(enc, d_in[5], 4608, 576); maps.m[4] = make_map(enc, d_in[6], 576, 4608);
  maps.m[5] = make_map(enc, d_in[1], 1728, 576, true); maps.m[6] = make_map(enc, d_in[2], 576, 576, true);
  void* scr = nullptr;
  cudaGetSymbolAddress(&scr, g_scratch);
  cudaFuncSetAttribute(mega_kernel, cudaFuncAttributeMaxDynamicSharedMemorySize, SMEM_BYTES);
  mega_kernel<<<128, 384, SMEM_BYTES>>>(maps, (uint4*)scr, (const __nv_bfloat16*)d_in[0], (__nv_bfloat16*)d_out);
}
```

```cpp
#include <cuda_runtime.h>
#include <cuda.h>
#include <cuda_bf16.h>
#include <stdint.h>

#define TRACE 0
#define GUARD 0
#define TRAPB 1
#define HOFF1 99
#define HOFF2 99
#define GDZ 3
#define GDO 3
#define KLD 6
#define EXP 0
#define FPOS 2

namespace {

constexpr int NST = 6;
constexpr int STAGE = 16384;
constexpr int PARK = NST * STAGE;
constexpr int REM = PARK + 49152;
constexpr int KVS = REM + 40960;
constexpr int HSTG = KVS + 16384;
constexpr int BARS = KVS + 41472;
constexpr int TRC = BARS + 256;
constexpr int SMEM_BYTES = TRC + (TRACE ? 512 : 0);
static_assert(NST == 6, "the producer addresses empty barriers as full + 48");
static_assert(BARS >= PARK + 131072, "barriers overlap park");
static_assert(SMEM_BYTES <= 232448, "smem");

constexpr int SLAB = 36 * 32;
constexpr int SPIN_MAX = 1 << 17;
constexpr int GD = GDZ, GO = GDO;
constexpr int OFF_S = 0;
constexpr int OFF_H = OFF_S + 3 * 8 * 96;
constexpr int OFF_X = OFF_H + 2 * 8 * 384;
constexpr int OFF_P = OFF_X + 6 * 8 * SLAB;
constexpr int TILE = OFF_P + 8 * 8 * SLAB;
constexpr int OFF_R = 16 * TILE;
constexpr int OFF_F = OFF_R + 8 * 2304;
constexpr int SCRATCH = OFF_F + 128 * 8;

}

__device__ uint4 g_scratch[SCRATCH];

namespace {

constexpr uint64_t DESC_HI = 0x4000004000000000ull;
constexpr uint64_t DESC_REM = (576ull << 32) | (8u << 16);
__device__ __forceinline__ void wgmma_rs_n64(float (&d)[32], const uint32_t* a, uint64_t desc, int scale_d) {
  asm volatile("{\n.reg .pred p;\nsetp.ne.b32 p, %37, 0;\n"
    "wgmma.mma_async.sync.aligned.m64n64k16.f32.bf16.bf16 "
    "{%0, %1, %2, %3, %4, %5, %6, %7, %8, %9, %10, %11, %12, %13, %14, %15, %16, %17, %18, %19, %20, %21, %22, %23, %24, %25, %26, %27, %28, %29, %30, %31}, "
    "{%32, %33, %34, %35}, %36, p, 1, 1, 1;\n}\n"
    : "+f"(d[0]), "+f"(d[1]), "+f"(d[2]), "+f"(d[3]), "+f"(d[4]), "+f"(d[5]), "+f"(d[6]), "+f"(d[7]), "+f"(d[8]), "+f"(d[9]), "+f"(d[10]), "+f"(d[11]), "+f"(d[12]), "+f"(d[13]), "+f"(d[14]), "+f"(d[15]), "+f"(d[16]), "+f"(d[17]), "+f"(d[18]), "+f"(d[19]), "+f"(d[20]), "+f"(d[21]), "+f"(d[22]), "+f"(d[23]), "+f"(d[24]), "+f"(d[25]), "+f"(d[26]), "+f"(d[27]), "+f"(d[28]), "+f"(d[29]), "+f"(d[30]), "+f"(d[31])
    : "r"(a[0]), "r"(a[1]), "r"(a[2]), "r"(a[3]), "l"(desc), "r"(scale_d));
}
__device__ __forceinline__ void wgmma_rs_n72(float (&d)[36], const uint32_t* a, uint64_t desc, int scale_d) {
  asm volatile("{\n.reg .pred p;\nsetp.ne.b32 p, %41, 0;\n"
    "wgmma.mma_async.sync.aligned.m64n72k16.f32.bf16.bf16 "
    "{%0, %1, %2, %3, %4, %5, %6, %7, %8, %9, %10, %11, %12, %13, %14, %15, %16, %17, %18, %19, %20, %21, %22, %23, %24, %25, %26, %27, %28, %29, %30, %31, %32, %33, %34, %35}, "
    "{%36, %37, %38, %39}, %40, p, 1, 1, 1;\n}\n"
    : "+f"(d[0]), "+f"(d[1]), "+f"(d[2]), "+f"(d[3]), "+f"(d[4]), "+f"(d[5]), "+f"(d[6]), "+f"(d[7]), "+f"(d[8]), "+f"(d[9]), "+f"(d[10]), "+f"(d[11]), "+f"(d[12]), "+f"(d[13]), "+f"(d[14]), "+f"(d[15]), "+f"(d[16]), "+f"(d[17]), "+f"(d[18]), "+f"(d[19]), "+f"(d[20]), "+f"(d[21]), "+f"(d[22]), "+f"(d[23]), "+f"(d[24]), "+f"(d[25]), "+f"(d[26]), "+f"(d[27]), "+f"(d[28]), "+f"(d[29]), "+f"(d[30]), "+f"(d[31]), "+f"(d[32]), "+f"(d[33]), "+f"(d[34]), "+f"(d[35])
    : "r"(a[0]), "r"(a[1]), "r"(a[2]), "r"(a[3]), "l"(desc), "r"(scale_d));
}
__device__ __forceinline__ void wgmma_rs_n24(float (&d)[12], const uint32_t* a, uint64_t desc, int scale_d) {
  asm volatile("{\n.reg .pred p;\nsetp.ne.b32 p, %17, 0;\n"
    "wgmma.mma_async.sync.aligned.m64n24k16.f32.bf16.bf16 "
    "{%0, %1, %2, %3, %4, %5, %6, %7, %8, %9, %10, %11}, "
    "{%12, %13, %14, %15}, %16, p, 1, 1, 1;\n}\n"
    : "+f"(d[0]), "+f"(d[1]), "+f"(d[2]), "+f"(d[3]), "+f"(d[4]), "+f"(d[5]), "+f"(d[6]), "+f"(d[7]), "+f"(d[8]), "+f"(d[9]), "+f"(d[10]), "+f"(d[11])
    : "r"(a[0]), "r"(a[1]), "r"(a[2]), "r"(a[3]), "l"(desc), "r"(scale_d));
}

__device__ __forceinline__ void mbar_init(uint32_t a, uint32_t c) { asm volatile("mbarrier.init.shared::cta.b64 [%0], %1;" :: "r"(a), "r"(c)); }
__device__ __forceinline__ void mbar_arrive(uint32_t a) { asm volatile("mbarrier.arrive.shared::cta.b64 _, [%0];" :: "r"(a) : "memory"); }
__device__ __forceinline__ void mbar_wait_trap(uint32_t a, uint32_t ph) {
  asm volatile("{\n.reg .pred p;\n.reg .u32 n;\nmov.u32 n, 0;\n"
               "W: mbarrier.try_wait.parity.shared::cta.b64 p, [%0], %1;\n@p bra D;\n"
               "add.u32 n, n, 1;\nsetp.lt.u32 p, n, 4194304;\n@p bra W;\ntrap;\nD:\n}" :: "r"(a), "r"(ph) : "memory");
}
__device__ __forceinline__ void mbar_wait(uint32_t a, uint32_t ph) {
  asm volatile("{\n.reg .pred p;\nW: mbarrier.try_wait.parity.shared::cta.b64 p, [%0], %1;\n@!p bra W;\n}" :: "r"(a), "r"(ph) : "memory");
}
__device__ __forceinline__ void wg_fence() { asm volatile("wgmma.fence.sync.aligned;" ::: "memory"); }
__device__ __forceinline__ void wg_commit() { asm volatile("wgmma.commit_group.sync.aligned;" ::: "memory"); }
template <int N> __device__ __forceinline__ void wg_wait() { asm volatile("wgmma.wait_group.sync.aligned %0;" :: "n"(N) : "memory"); }
__device__ __forceinline__ float tanh_ap(float x) { float y; asm("tanh.approx.f32 %0, %1;" : "=f"(y) : "f"(x)); return y; }
__device__ __forceinline__ float ex2(float x) { float y; asm("ex2.approx.ftz.f32 %0, %1;" : "=f"(y) : "f"(x)); return y; }
__device__ __forceinline__ uint32_t pack_bf16(float lo, float hi) { uint32_t r; asm("cvt.rn.bf16x2.f32 %0, %1, %2;" : "=r"(r) : "f"(hi), "f"(lo)); return r; }
__device__ __forceinline__ float bf_lo(uint32_t v) { return __uint_as_float(v << 16); }
__device__ __forceinline__ float bf_hi(uint32_t v) { return __uint_as_float(v & 0xffff0000u); }
__device__ __forceinline__ uint32_t sub_bf16x2(uint32_t a, uint32_t b) { uint32_t r; asm("sub.rn.bf16x2 %0, %1, %2;" : "=r"(r) : "r"(a), "r"(b)); return r; }
__device__ __forceinline__ uint32_t mul_bf16x2(uint32_t a, uint32_t b) { uint32_t r; asm("mul.rn.bf16x2 %0, %1, %2;" : "=r"(r) : "r"(a), "r"(b)); return r; }
__device__ __forceinline__ uint32_t diff2(uint32_t a, uint32_t b, uint32_t t) { uint32_t r; asm("lop3.b32 %0, %1, %2, %3, 0x7e;" : "=r"(r) : "r"(a), "r"(b), "r"(t)); return r; }
__device__ __forceinline__ uint32_t or3(uint32_t a, uint32_t b, uint32_t c) { uint32_t r; asm("lop3.b32 %0, %1, %2, %3, 0xfe;" : "=r"(r) : "r"(a), "r"(b), "r"(c)); return r; }
__device__ __forceinline__ uint32_t umin2(uint32_t a, uint32_t b) { uint32_t r; asm("min.u32 %0, %1, %2;" : "=r"(r) : "r"(a), "r"(b)); return r; }
__device__ __forceinline__ uint32_t nz(uint32_t w) { return w == 0u ? 0x8000u : w; }

__device__ __forceinline__ void ldg4(uint32_t* d, const uint4* p) {
  asm volatile("ld.relaxed.gpu.global.v4.b32 {%0,%1,%2,%3}, [%4];" : "=r"(d[0]), "=r"(d[1]), "=r"(d[2]), "=r"(d[3]) : "l"(p) : "memory");
}
__device__ __forceinline__ void ldg2(uint32_t* d, const void* p) {
  asm volatile("ld.relaxed.gpu.global.v2.b32 {%0,%1}, [%2];" : "=r"(d[0]), "=r"(d[1]) : "l"(p) : "memory");
}
__device__ __forceinline__ void stg4(uint4* p, uint32_t a, uint32_t b, uint32_t c, uint32_t d) {
  asm volatile("st.relaxed.gpu.global.v4.b32 [%0], {%1,%2,%3,%4};" :: "l"(p), "r"(a), "r"(b), "r"(c), "r"(d) : "memory");
}
__device__ __forceinline__ void stg2(void* p, uint32_t a, uint32_t b) {
  asm volatile("st.relaxed.gpu.global.v2.b32 [%0], {%1,%2};" :: "l"(p), "r"(a), "r"(b) : "memory");
}
__device__ __forceinline__ void sts4(uint32_t a, const uint32_t* o) { asm volatile("st.shared.v4.b32 [%0], {%1,%2,%3,%4};" :: "r"(a), "r"(o[0]), "r"(o[1]), "r"(o[2]), "r"(o[3]) : "memory"); }
__device__ __forceinline__ void lds4(uint32_t a, uint32_t* o) { asm volatile("ld.shared.v4.b32 {%0,%1,%2,%3}, [%4];" : "=r"(o[0]), "=r"(o[1]), "=r"(o[2]), "=r"(o[3]) : "r"(a) : "memory"); }
__device__ __forceinline__ void lds2(uint32_t a, uint32_t* o) { asm volatile("ld.shared.v2.b32 {%0,%1}, [%2];" : "=r"(o[0]), "=r"(o[1]) : "r"(a) : "memory"); }
__device__ __forceinline__ float rcp(float x) { float y; asm("rcp.approx.ftz.f32 %0, %1;" : "=f"(y) : "f"(x)); return y; }
__device__ __forceinline__ void sts1(uint32_t a, uint32_t v) { asm volatile("st.shared.b32 [%0], %1;" :: "r"(a), "r"(v) : "memory"); }
__device__ __forceinline__ void ldsm4(uint32_t a, uint32_t& r0, uint32_t& r1, uint32_t& r2, uint32_t& r3) {
  asm volatile("ldmatrix.sync.aligned.m8n8.x4.shared.b16 {%0,%1,%2,%3}, [%4];" : "=r"(r0), "=r"(r1), "=r"(r2), "=r"(r3) : "r"(a) : "memory");
}
__device__ __forceinline__ void ldsm4t(uint32_t a, uint32_t& r0, uint32_t& r1, uint32_t& r2, uint32_t& r3) {
  asm volatile("ldmatrix.sync.aligned.m8n8.x4.trans.shared.b16 {%0,%1,%2,%3}, [%4];" : "=r"(r0), "=r"(r1), "=r"(r2), "=r"(r3) : "r"(a) : "memory");
}
__device__ __forceinline__ void mma16c(float* d, const uint32_t* a, uint32_t b0, uint32_t b1, float c01) {
  asm("mma.sync.aligned.m16n8k16.row.col.f32.bf16.bf16.f32 {%0,%1,%2,%3}, {%4,%5,%6,%7}, {%8,%9}, {%10,%10,%10,%10};"
    : "=f"(d[0]), "=f"(d[1]), "=f"(d[2]), "=f"(d[3]) : "r"(a[0]), "r"(a[1]), "r"(a[2]), "r"(a[3]), "r"(b0), "r"(b1), "f"(c01));
}
__device__ __forceinline__ void mma8(float* c, uint32_t a0, uint32_t a1, uint32_t b0) {
  asm("mma.sync.aligned.m16n8k8.row.col.f32.bf16.bf16.f32 {%0,%1,%2,%3}, {%4,%5}, {%6}, {%0,%1,%2,%3};"
    : "+f"(c[0]), "+f"(c[1]), "+f"(c[2]), "+f"(c[3]) : "r"(a0), "r"(a1), "r"(b0));
}
__device__ __forceinline__ uint32_t lane_id() { uint32_t l; asm volatile("mov.u32 %0, %%laneid;" : "=r"(l)); return l; }
__device__ __forceinline__ float quad_sum(float v) { v += __shfl_xor_sync(~0u, v, 1); v += __shfl_xor_sync(~0u, v, 2); return v; }
__device__ __forceinline__ float quad_max(float v) { v = fmaxf(v, __shfl_xor_sync(~0u, v, 1)); v = fmaxf(v, __shfl_xor_sync(~0u, v, 2)); return v; }
template <int N> __device__ __forceinline__ void pin(float (&d)[N]) {
#pragma unroll
  for (int i = 0; i < N; i++) asm volatile("" : "+f"(d[i]) :: "memory");
}
#define SPIN_GUARD(n) if (++(n) > SPIN_MAX) break

template <int NG> __device__ __forceinline__ void publish_stats(uint4* dst, const float* y, uint32_t tag, uint32_t lane) {
  float s0 = 0.f, s1 = 0.f;
#pragma unroll
  for (int g = 0; g < NG; g++) { s0 += y[4 * g] + y[4 * g + 1]; s1 += y[4 * g + 2] + y[4 * g + 3]; }
  s0 = quad_sum(s0); s1 = quad_sum(s1);
  const float m0 = s0 * (1.f / (8 * NG)), m1 = s1 * (1.f / (8 * NG));
  float q0 = 0.f, q1 = 0.f, q2 = 0.f, q3 = 0.f;
#pragma unroll
  for (int g = 0; g < NG; g++) {
    const float a = y[4 * g] - m0, b = y[4 * g + 1] - m0, c = y[4 * g + 2] - m1, d = y[4 * g + 3] - m1;
    q0 = fmaf(a, a, q0); q1 = fmaf(b, b, q1); q2 = fmaf(c, c, q2); q3 = fmaf(d, d, q3);
  }
  q0 = quad_sum(q0 + q1); q2 = quad_sum(q2 + q3);
  if ((lane & 3) == 0)
    stg4(dst + (lane >> 2), (__float_as_uint(s0) & ~1u) | tag, __float_as_uint(q0), __float_as_uint(s1), __float_as_uint(q2));
}

__device__ __forceinline__ void put72(uint4* slab, uint32_t j, uint32_t lane, const uint32_t* v, uint32_t r0, uint32_t r1) {
  uint4* p = slab + ((9 * j + 1) >> 1) * 32;
#pragma unroll
  for (int i = 0; i < 4; i++) stg4(p + lane + i * 32, nz(v[4 * i]), v[4 * i + 1], v[4 * i + 2], v[4 * i + 3]);
  stg2((char*)((j & 1) ? p - 16 : p + 4 * 32) + lane * 8, nz(r0), r1);
}
__device__ __forceinline__ void zero_share(uint4* slab, uint32_t j, uint32_t lane) {
  uint4* p = slab + j * 144 + lane;
#pragma unroll
  for (int i = 0; i < 4; i++) stg4(p + i * 32, 0u, 0u, 0u, 0u);
  if (lane < 16) stg4(p + 128, 0u, 0u, 0u, 0u);
}

struct Maps { CUtensorMap m[7]; };

struct Ring {
  uint32_t st, ph;
  __device__ __forceinline__ void next() { if (++st == NST) { st = 0; ph ^= 1; } }
};

#define GSTAMP(i) do {} while (0)
#define STAMP(i) do {} while (0)

__device__ __forceinline__ void tma_box(uint32_t dst, const CUtensorMap* m, int col, int row, uint32_t bar, uint32_t expect) {
  asm volatile("{\n.reg .pred e, h;\nelect.sync _|e, 0xffffffff;\nsetp.ne.and.u32 h, %5, 0, e;\n"
               "@h mbarrier.arrive.expect_tx.shared::cta.b64 _, [%2], %5;\n"
               "@e cp.async.bulk.tensor.2d.shared::cluster.global.mbarrier::complete_tx::bytes [%0], [%1, {%3, %4}], [%2];\n}"
               :: "r"(dst), "l"(m), "r"(bar), "r"(col), "r"(row), "r"(expect) : "memory");
}

__device__ __forceinline__ void bulk_load(uint32_t dst, const void* src, uint32_t bytes, uint32_t bar, bool arm) {
  asm volatile("{\n.reg .pred e, h;\nelect.sync _|e, 0xffffffff;\nsetp.ne.and.u32 h, %4, 0, e;\n"
               "@h mbarrier.arrive.expect_tx.shared::cta.b64 _, [%3], %2;\n"
               "@e cp.async.bulk.shared::cluster.global.mbarrier::complete_tx::bytes [%0], [%1], %2, [%3];\n}"
               :: "r"(dst), "l"(src), "r"(bytes), "r"(bar), "r"((uint32_t)arm) : "memory");
}

__global__ void __launch_bounds__(384, 1) mega_kernel(
    const __grid_constant__ Maps maps, uint4* __restrict__ scratch,
    const __nv_bfloat16* __restrict__ x_in, __nv_bfloat16* __restrict__ out) {
  extern __shared__ __align__(1024) uint8_t smem[];
  const uint32_t sb = (uint32_t)__cvta_generic_to_shared(smem);
  const uint32_t full0 = sb + BARS, empty0 = full0 + 8 * NST, rem_full = empty0 + 8 * NST, park_free = rem_full + 8, kv_free = park_free + 8;
  const uint32_t c8_go = kv_free + 8, c8_done = c8_go + 8, c8_full = c8_done + 8, remo_full = c8_full + 8, piece_full = remo_full + 8, pbar0 = piece_full + 8;
  const uint32_t w = __shfl_sync(~0u, threadIdx.x >> 5, 0);
  const uint32_t t = blockIdx.x >> 3, j = blockIdx.x & 7;
  const uint32_t odd = j & 1;
  uint4* const scr = scratch + t * TILE;
  {
    const uint32_t lane = lane_id(), r = lane >> 2, q = lane & 3;
    const uint32_t sl = w < 8 ? w : j, ch = w < 8 ? j : 8;
    const uint32_t* xr = (const uint32_t*)(x_in + (128 * t + 32 * (sl >> 1) + 2 * r + (sl & 1)) * 576 + 64 * ch + 2 * q);
    if (w < 8 || w == 9) {
      uint32_t v[16];
#pragma unroll
      for (int g = 0; g < 8; g++) {
        asm volatile("ld.global.nc.b32 %0, [%1];" : "=r"(v[2 * g]) : "l"(xr + 4 * g));
        asm volatile("ld.global.nc.b32 %0, [%1];" : "=r"(v[2 * g + 1]) : "l"(xr + 8 * 576 + 4 * g));
      }
      if (q == 0) {
#pragma unroll
        for (int k = 0; k < 3; k++) stg4(scr + OFF_S + (k * 8 + sl) * 96 + ch * 8 + r, 0u, 0u, 0u, 0u);
      }
      asm volatile("bar.sync 0, 384;" ::: "memory");
      uint4* p = scr + OFF_X + sl * SLAB + 4 * ch * 32 + lane;
#pragma unroll
      for (int i = 0; i < 4; i++) stg4(p + i * 32, nz(v[4 * i]), v[4 * i + 1], nz(v[4 * i + 2]), v[4 * i + 3]);
      float y[32];
#pragma unroll
      for (int i = 0; i < 16; i++) { y[2 * i] = bf_lo(v[i]); y[2 * i + 1] = bf_hi(v[i]); }
      publish_stats<8>(scr + OFF_S + sl * 96 + ch * 8, y, 1u, lane);
    } else {
      if (threadIdx.x == 256) {
        for (int i = 0; i < NST; i++) { mbar_init(full0 + 8 * i, 1); mbar_init(empty0 + 8 * i, 8); }
        mbar_init(rem_full, 1); mbar_init(park_free, 8); mbar_init(kv_free, 8); mbar_init(c8_go, 8); mbar_init(c8_done, 1); mbar_init(c8_full, 1); mbar_init(remo_full, 64); mbar_init(piece_full, 1);
        for (int i = 0; i < 8; i++) mbar_init(pbar0 + 8 * i, 5);
        asm volatile("fence.mbarrier_init.release.cluster;" ::: "memory");
      }
      __syncwarp();
      asm volatile("bar.sync 0, 384;" ::: "memory");
    }
  }

  if (w >= 8) {
    asm volatile("setmaxnreg.dec.sync.aligned.u32 24;");
    if (w == 8) {
      uint32_t dst = sb, bar = full0, ph = 1;
#pragma unroll 1
      for (int seg = 0; seg < 34; seg++) {
        const int n = seg >= 17 ? seg - 17 : seg;
        int ma, mb, ca, cb, row = 0;
        if (n < 3) { ma = mb = n == 2; ca = 72 * j + 8 * odd + (n == 0 ? 576 : 0); cb = ca + 576; }
        else if (n < 12) { ma = 3; mb = 2; ca = cb = 576 * j + 64 * (n - 3); }
        else { ma = mb = 4; ca = n == 12 ? 512 : ((j + 2 * n) & 7) * 64; cb = ((j + 2 * n + 1) & 7) * 64; row = 576 * j; }
        const bool zip = n == 0 || n == 3, solo = n == 1 || n == 2 || n == 16;
        const CUtensorMap *pa = &maps.m[ma], *pb = &maps.m[mb];
#pragma unroll 1
        for (int st = 0; st < (solo ? 5 : 9); st++) {
          const bool s0 = !zip && st > 4, s1 = zip || st >= 4;
          const int r0 = row + (zip ? 64 * st : s0 ? 128 * st - 576 : 128 * st), r1 = zip ? r0 : st == 4 ? row : r0 + 64;
          asm volatile("{\n.reg .pred p, e, f;\n.reg .u32 n;\nelect.sync _|e, 0xffffffff;\nsetp.eq.and.u32 f, %9, 16384, e;\nmov.u32 n, 0;\n"
                       "W: mbarrier.try_wait.parity.shared::cta.b64 p, [%1+48], %2;\n@p bra D;\n"
                       "add.u32 n, n, 1;\nsetp.lt.u32 p, n, 4194304;\n@p bra W;\ntrap;\n"
                       "D: @e mbarrier.arrive.expect_tx.shared::cta.b64 _, [%1], %9;\n"
                       "@e cp.async.bulk.tensor.2d.shared::cluster.global.mbarrier::complete_tx::bytes [%0], [%3, {%4, %5}], [%1];\n"
                       "@f cp.async.bulk.tensor.2d.shared::cluster.global.mbarrier::complete_tx::bytes [%0+8192], [%6, {%7, %8}], [%1];\n}"
                       :: "r"(dst), "r"(bar), "r"(ph), "l"(s0 ? pb : pa), "r"(s0 ? cb : ca), "r"(r0), "l"(s1 ? pb : pa), "r"(s1 ? cb : ca), "r"(r1),
                          "r"(solo && st == 4 ? STAGE / 2 : STAGE) : "memory");
          dst += STAGE; bar += 8;
          if (bar == full0 + 8 * NST) { dst = sb; bar = full0; ph ^= 1; }
        }
      }
    } else if (w == 9) {
      const uint32_t lane = lane_id();
      const uint32_t stg = sb + HSTG + lane * 16;
      uint32_t fph = 0;
#pragma unroll 1
      for (uint32_t layer = 0; layer < 2; layer++) {
        uint4* xb = scr + OFF_X + ((4 + layer) * 8 + j) * SLAB + 32 * 32;
        mbar_wait(c8_go, layer);
        int n = 0;
        while (true) {
          if (lane == 0) asm volatile("mbarrier.arrive.expect_tx.shared::cta.b64 _, [%0], 18432;" :: "r"(c8_full) : "memory");
          __syncwarp();
#pragma unroll 1
          for (uint32_t s = 0; s < 9; s++)
            bulk_load(sb + HSTG + s * 2048, s < 8 ? scr + OFF_P + (j + s * 8) * SLAB + 32 * 32 : xb, 2048, c8_full, false);
          mbar_wait(c8_full, fph); fph ^= 1;
          uint32_t bad = 0;
#pragma unroll 8
          for (int s = 0; s < 32; s++) { uint32_t v; asm volatile("ld.shared.b32 %0, [%1];" : "=r"(v) : "r"(stg + s * 512) : "memory"); bad |= v ^ (1 - layer); }
          if (__all_sync(~0u, (bad & 1u) == 0u)) break;
          __nanosleep(300);
          SPIN_GUARD(n);
        }
        float s0 = 0.f, s1 = 0.f;
#pragma unroll 1
        for (int g = 0; g < 8; g++) {
          const uint32_t a = stg + (g >> 1) * 512 + (g & 1) * 8;
          float a0 = 0.f, a1 = 0.f, a2 = 0.f, a3 = 0.f;
#pragma unroll 1
          for (int b = 0; b < 3; b++) {
            uint32_t v[6];
#pragma unroll
            for (int s = 0; s < 3; s++) lds2(a + (3 * b + s) * 2048, v + 2 * s);
#pragma unroll
            for (int s = 0; s < 3; s++) { a0 += bf_lo(v[2 * s]); a1 += bf_hi(v[2 * s]); a2 += bf_lo(v[2 * s + 1]); a3 += bf_hi(v[2 * s + 1]); }
          }
          sts1(a + 18432, pack_bf16(a0, a1)); sts1(a + 18436, pack_bf16(a2, a3));
          s0 += a0 + a1; s1 += a2 + a3;
        }
        __syncwarp();
        if (lane == 0) mbar_arrive(c8_done);
        s0 = quad_sum(s0); s1 = quad_sum(s1);
        float q0 = 0.f, q1 = 0.f;
        const uint32_t ln = lane_id();
#pragma unroll 1
        for (uint32_t i = 0; i < 4; i++) {
          uint32_t x[4];
          lds4(stg + 18432 + i * 512, x);
          stg4(xb + i * 32 + ln, 0u, 0u, 0u, 0u);
          if (layer == 0) {
            stg4(xb - 3 * 8 * SLAB + i * 32 + ln, nz(x[0]), x[1], x[2], x[3]);
#pragma unroll
            for (int e = 0; e < 4; e++) {
              const float m = (e & 1) ? s1 : s0, c = fmaf(m, -1.f / 64, bf_lo(x[e])), d = fmaf(m, -1.f / 64, bf_hi(x[e]));
              if (e & 1) q1 = fmaf(c, c, fmaf(d, d, q1)); else q0 = fmaf(c, c, fmaf(d, d, q0));
            }
          } else {
            uint32_t* o = (uint32_t*)(out + (128 * t + 32 * (j >> 1) + 2 * (ln >> 2) + (j & 1)) * 576 + 512 + 16 * i + 2 * (ln & 3));
            o[0] = x[0]; o[8 * 576] = x[1]; o[4] = x[2]; o[8 * 576 + 4] = x[3];
          }
        }
        if (layer == 0) {
          q0 = quad_sum(q0); q1 = quad_sum(q1);
          if ((ln & 3) == 0) stg4(scr + OFF_S + j * 96 + 64 + (ln >> 2), __float_as_uint(s0) & ~1u, __float_as_uint(q0), __float_as_uint(s1), __float_as_uint(q1));
        }
      }
    } else {
      const uint32_t lane = lane_id(), r = lane >> 2, q = lane & 3;
#pragma unroll 1
      for (uint32_t layer = 0; layer < 2; layer++) {
        if (w == 10) {
          if (layer == 0) {
            const uint32_t p = t >> 2;
            tma_box(sb + PARK, &maps.m[p == 3 ? 6 : 5], 72 * j + (odd ? 0 : 64) + (p < 2 ? 576 * (p + 1) : 0), 144 * (t & 3), piece_full, 2304);
            mbar_wait(piece_full, 0);
            asm volatile("{\n.reg .pred e;\nelect.sync _|e, 0xffffffff;\n@e cp.async.bulk.global.shared::cta.bulk_group [%0], [%1], 2304;\n}\n"
                         "cp.async.bulk.commit_group;\ncp.async.bulk.wait_group 0;\nfence.proxy.async;"
                         :: "l"(scratch + OFF_R + j * 2304 + t * 144), "r"(sb + PARK) : "memory");
            __syncwarp();
            if (lane < 16) asm volatile("st.release.gpu.global.b32 [%0], 1;" :: "l"((uint32_t*)(scratch + OFF_F + (lane * 8 + j) * 8) + t) : "memory");
            uint32_t* fl = (uint32_t*)(scratch + OFF_F + (t * 8 + j) * 8) + (lane & 15);
            uint32_t v;
            int n = 0;
            while (true) {
              asm volatile("ld.acquire.gpu.global.b32 %0, [%1];" : "=r"(v) : "l"(fl) : "memory");
              if (__all_sync(~0u, v != 0u)) break;
              __nanosleep(100);
              SPIN_GUARD(n);
            }
            asm volatile("fence.proxy.async;\nst.relaxed.gpu.global.b32 [%0], 0;" :: "l"(fl) : "memory");
          } else {
            mbar_wait(park_free, 0);
          }
          bulk_load(sb + REM, scratch + OFF_R + j * 2304, 36864, rem_full, true);
        }
        mbar_wait(rem_full, layer);
#pragma unroll 1
        for (uint32_t b = 0; b < 5; b++) {
          const uint32_t blk = sb + REM + 27648 + b * 2048, k = threadIdx.x - 320, rr = k & 7;
          const uint32_t dst = blk + ((k >> 3) & 1) * 1024 + rr * 128 + (((k >> 4) ^ rr) << 4);
          uint32_t v[8];
          lds4(blk + k * 16, v); lds4(blk + 1024 + k * 16, v + 4);
          asm volatile("bar.sync 3, 64;" ::: "memory");
          sts4(dst, v); sts4(dst ^ 64, v + 4);
        }
        asm volatile("fence.proxy.async.shared::cta;" ::: "memory");
        mbar_arrive(remo_full);
        if (layer) mbar_wait(kv_free, 0);
        if (t > 0) {
#pragma unroll 1
          for (uint32_t pc = 0; pc < 3; pc++) {
            uint4* hp = scr + OFF_H + ((layer * 8 + j) * 2 + (w - 10)) * 192 + pc * 64 + lane;
            uint32_t hl[8];
            int n = 0;
            hl[4] = 1u;
            while (true) {
              ldg4(hl, hp);
              if (pc < 2) ldg4(hl + 4, hp + 32);
              if (__all_sync(~0u, hl[0] != 0u && hl[4] != 0u)) break;
              __nanosleep(100);
              SPIN_GUARD(n);
            }
            const uint32_t dst = sb + KVS + (w - 10) * 10368 + r * 144 + q * 4;
            if (pc < 2) {
#pragma unroll
              for (int g = 0; g < 8; g++) sts1(dst + pc * 20736 + odd * 16 + g * 16, hl[g]);
              stg4(hp + 32, 0u, 0u, 0u, 0u);
            } else {
              sts1(dst + (odd ? 0 : 128), hl[0]); sts1(dst + 20736 + (odd ? 0 : 128), hl[1]);
            }
            stg4(hp, 0u, 0u, 0u, 0u);
          }
        }
        asm volatile("bar.arrive 1, 192;" ::: "memory");
      }
    }
  } else {
    asm volatile("setmaxnreg.inc.sync.aligned.u32 240;");
    const uint32_t lane = lane_id(), r = lane >> 2, q = lane & 3;
    Ring rg{0, 0};
    uint32_t prev = 0;
    uint32_t X[144];
    float rs0, rs1;
    uint32_t mean0, mean1;
    auto release = [&](uint32_t st) { if (lane == 0) mbar_arrive(empty0 + st * 8); };
    auto load_kb = [&](int kb, const uint4* src, const char* lo, uint32_t hoff) {
#pragma unroll
      for (int k = 4 * kb; k < 4 * kb + 4; k++) {
        if (k % 9 == 4) { ldg2(X + 4 * k, lo + k * 512); ldg2(X + 4 * k + 2, lo + hoff + k * 512); }
        else ldg4(X + 4 * k, src + k * 32);
      }
    };
    auto next_kb = [&](bool center, int kb, const uint4* src, const char* lo, uint32_t hoff) {
      int n = 0;
      while (true) {
        uint32_t m = umin2(umin2(X[16 * kb], X[16 * kb + 4]), umin2(X[16 * kb + 8], X[16 * kb + 12]));
        if (kb & 1) m = umin2(m, X[16 * kb + 4 * (kb >> 1) + 2]);
        if (__all_sync(~0u, m != 0u)) break;
        SPIN_GUARD(n);
        load_kb(kb, src, lo, hoff);
      }
      if (kb + (center ? GD : GO) < 9) load_kb(kb + (center ? GD : GO), src, lo, hoff);
      if (center) {
#pragma unroll
        for (int i = 16 * kb; i < 16 * kb + 16; i++) X[i] = sub_bf16x2(X[i], (i & 1) ? mean1 : mean0);
      }
    };
#pragma unroll 1
    for (uint32_t hf = 0; hf < 4; hf++) {
      const uint32_t layer = hf >> 1;
      const bool ffn = hf & 1;
      const uint32_t tag = 1 - layer;
      uint4* const xbase = scr + OFF_X + (layer * 8 + w) * SLAB;
      float aA[32], aB[32];
      {
        const uint4* src = xbase + (ffn ? 32 * SLAB : 0) + lane;
        const char* lo = (const char*)src - (ffn ? lane * 8 : 0);
        const uint32_t hoff = ffn ? 256 : 8;
        uint32_t s[3][4];
        const uint4* p = scr + OFF_S + ((ffn ? 16 : 0) + w) * 96 + q * 8 + r;
        const bool third = !ffn && q == 0;
        int n = 0;
        s[2][0] = tag; s[2][1] = s[2][2] = s[2][3] = 0u;
        STAMP(ffn * 16 + 0);
        while (true) {
          ldg4(s[0], p); ldg4(s[1], p + 32);
          if (third) ldg4(s[2], p + 64);
          if (__all_sync(~0u, ((diff2(s[0][0], s[1][0], tag) | diff2(s[2][0], s[2][0], tag)) & 1u) == 0u)) break;
          SPIN_GUARD(n);
        }
        STAMP(ffn * 16 + 1);
        GSTAMP(14 + ffn);
#pragma unroll
        for (int kb = 0; kb < GD; kb++) load_kb(kb, src, lo, hoff);
        float t0 = 0.f, t1 = 0.f;
#pragma unroll
        for (int i = 0; i < 3; i++) { t0 += __uint_as_float(s[i][0]); t1 += __uint_as_float(s[i][2]); }
        const float m0 = quad_sum(t0) * (1.f / 576), m1 = quad_sum(t1) * (1.f / 576);
        const float cnt = ffn ? 72.f : 64.f, inv = ffn ? 1.f / 72 : 1.f / 64;
        float v0 = 0.f, v1 = 0.f;
#pragma unroll
        for (int i = 0; i < 3; i++) {
          const float c = (i < 2 || third) ? cnt : 0.f;
          const float d0 = fmaf(__uint_as_float(s[i][0]), inv, -m0), d1 = fmaf(__uint_as_float(s[i][2]), inv, -m1);
          v0 += fmaf(d0 * d0, c, __uint_as_float(s[i][1])); v1 += fmaf(d1 * d1, c, __uint_as_float(s[i][3]));
        }
        rs0 = rsqrtf(fmaf(quad_sum(v0), 1.f / 576, 1e-5f)); rs1 = rsqrtf(fmaf(quad_sum(v1), 1.f / 576, 1e-5f));
        mean0 = pack_bf16(m0, m0); mean1 = pack_bf16(m1, m1);
#pragma unroll
        for (int kb = 0; kb < 9; kb++) {
          next_kb(true, kb, src, lo, hoff);
          mbar_wait(full0 + rg.st * 8, rg.ph);
          const uint64_t desc = DESC_HI | ((sb + rg.st * STAGE) >> 4);
          wg_fence();
#pragma unroll
          for (int i = 0; i < 4; i++) wgmma_rs_n64(aA, X + 4 * (4 * kb + i), desc + i * 128, kb + i != 0);
#pragma unroll
          for (int i = 0; i < 4; i++) wgmma_rs_n64(aB, X + 4 * (4 * kb + i), desc + 512 + i * 128, kb + i != 0);
          wg_commit();
          wg_wait<1>();
          if (kb > 0) release(prev);
          prev = rg.st; rg.next();
        }
        wg_wait<0>();
        STAMP(ffn * 16 + 2);
      }
      if (!ffn) {
      release(prev);
      const uint32_t kvrow = sb + KVS + (w & 1) * 10368 + (16 * (w >> 1)) * 144;
      uint32_t Q[18], Km[3][8], Ke[3][4];
      const bool edge = (t == 0 && w < 2);
      const uint32_t row0 = edge ? sb + KVS + 8 * 144 : kvrow + (lane & 7) * 144, row1 = kvrow + (8 + (lane & 7)) * 144;
      {
        const uint32_t dst = kvrow + (8 + r) * 144 + q * 4 + odd * 16, dstr = dst + (odd ? -16 : 128);
        const bool edge_out = w >= 6 && t < 15;
        uint4* const hp = scr + TILE + OFF_H + ((layer * 8 + j) * 2 + (w & 1)) * 192 + lane;
        auto put_kv = [&](float (&a)[32], int part) {
          pin(a);
          uint32_t hl[8];
#pragma unroll
          for (int g = 0; g < 8; g++) {
            hl[g] = pack_bf16(a[4 * g + 2] * rs1, a[4 * g + 3] * rs1);
            sts1(dst + part * 20736 + g * 16, pack_bf16(a[4 * g] * rs0, a[4 * g + 1] * rs0)); sts1(dst + part * 20736 + 8 * 144 + g * 16, hl[g]);
          }
          if (edge_out) { stg4(hp + part * 64, nz(hl[0]), hl[1], hl[2], hl[3]); stg4(hp + part * 64 + 32, nz(hl[4]), hl[5], hl[6], hl[7]); }
        };
        put_kv(aA, 0);
        float aR[12];
        mbar_wait(rem_full, layer);
        const uint64_t dr = DESC_REM | ((sb + REM) >> 4);
        wg_fence();
#pragma unroll
        for (int s = 0; s < 36; s++) {
          wgmma_rs_n24(aR, X + 4 * s, dr + s * 16, s != 0);
          if (s == 4) put_kv(aB, 1);
        }
        wg_commit();
#pragma unroll
        for (int kb = 0; kb < 9; kb++) {
          if (kb == HOFF1 && w < 4) asm volatile("bar.sync 4, 256;" ::: "memory");
          if (kb == 8 && HOFF1 < 9 && w >= 4) asm volatile("bar.arrive 4, 256;" ::: "memory");
          if (!(kb & 1)) mbar_wait(full0 + rg.st * 8, rg.ph);
          const uint64_t desc = DESC_HI | ((sb + rg.st * STAGE + (kb & 1) * 8192) >> 4);
          wg_fence();
#pragma unroll
          for (int i = 0; i < 4; i++) wgmma_rs_n64(aB, X + 4 * (4 * kb + i), desc + i * 128, kb + i != 0);
          wg_commit();
          wg_wait<1>();
          if (kb > 0 && !(kb & 1)) release(prev);
          if ((kb & 1) || kb == 8) { prev = rg.st; rg.next(); }
          if (kb == 0) {
            pin(aR);
            const uint32_t k1 = pack_bf16(aR[2] * rs1, aR[3] * rs1), v1 = pack_bf16(aR[6] * rs1, aR[7] * rs1);
            if (edge_out) stg4(hp + 128, nz(k1), v1, 0u, 0u);
            sts1(dstr, pack_bf16(aR[0] * rs0, aR[1] * rs0)); sts1(dstr + 8 * 144, k1);
            sts1(dstr + 20736, pack_bf16(aR[4] * rs0, aR[5] * rs0)); sts1(dstr + 20736 + 8 * 144, v1);
            Q[16] = pack_bf16(aR[8], aR[9]); Q[17] = pack_bf16(aR[10], aR[11]);
            if (w < 4) asm volatile("bar.arrive 2, 256;" ::: "memory");
          }
          if (kb == KLD) {
            if (w < 4) asm volatile("bar.sync 1, 192;" ::: "memory");
            else asm volatile("bar.sync 2, 256;" ::: "memory");
#pragma unroll
            for (int nt = 0; nt < 3; nt++) {
              const uint32_t ra = (nt == 0 ? row0 : row1 + (nt - 1) * 8 * 144);
              ldsm4(ra + odd * 16 + (lane >> 3) * 16, Km[nt][0], Km[nt][1], Km[nt][2], Km[nt][3]);
              ldsm4(ra + odd * 16 + 64 + (lane >> 3) * 16, Km[nt][4], Km[nt][5], Km[nt][6], Km[nt][7]);
              ldsm4(ra + (odd ? 0 : 32) + (lane >> 3) * 32, Ke[nt][0], Ke[nt][1], Ke[nt][2], Ke[nt][3]);
#pragma unroll
              for (int h = 0; h < 4; h++) {
                const bool off = nt == 0 && edge, ge = q >= h, le = q <= h;
                if (off || (!odd && !ge)) Km[nt][2 * h] = 0u;
                if (off || (odd && !le)) Km[nt][2 * h + 1] = 0u;
                if (off || !(odd ? ge : le)) Ke[nt][h] = 0u;
              }
            }
          }
        }
        wg_wait<0>();
        release(prev);
        pin(aB);
        STAMP(3);
#pragma unroll
        for (int i = 0; i < 16; i++) Q[i] = pack_bf16(aB[2 * i], aB[2 * i + 1]);
      }
      {
        uint32_t V01[12][2], V2[12];
        const uint32_t rv = ((lane & 8) ? row1 : row0) + 20736, rw = row1 + 8 * 144 + 20736;
#pragma unroll
        for (int i = 0; i < 4; i++) ldsm4t(rv + odd * 16 + i * 32 + (lane >> 4) * 16, V01[2 * i][0], V01[2 * i][1], V01[2 * i + 1][0], V01[2 * i + 1][1]);
#pragma unroll
        for (int i = 0; i < 2; i++) ldsm4t(rv + (odd ? 0 : 32) + i * 64 + (lane >> 4) * 32, V01[8 + 2 * i][0], V01[8 + 2 * i][1], V01[9 + 2 * i][0], V01[9 + 2 * i][1]);
        ldsm4t(rw + odd * 16 + (lane >> 3) * 16, V2[0], V2[1], V2[2], V2[3]);
        ldsm4t(rw + odd * 16 + 64 + (lane >> 3) * 16, V2[4], V2[5], V2[6], V2[7]);
        ldsm4t(rw + (odd ? 0 : 32) + (lane >> 3) * 32, V2[8], V2[9], V2[10], V2[11]);
        const bool up0 = 2 * q > r, up1 = 2 * q + 1 > r;
        const uint32_t upm = (up0 ? 0xffffu : 0u) | (up1 ? 0xffff0000u : 0u);
        const float c0 = 0.23570226039551584f * 1.4426950408889634f * rs0, c1 = 0.23570226039551584f * 1.4426950408889634f * rs1;
        const float masked = edge ? -1e9f * 1.4426950408889634f / c0 : 0.f;
        uint32_t Om[16], Oe[8];
#pragma unroll
        for (int h = 0; h < 4; h++) {
          const uint32_t e0 = odd ? Q[(4 * h + 16) % 18] : Q[4 * h + 4], e1 = odd ? Q[(4 * h + 17) % 18] : Q[4 * h + 5];
          float S[3][4];
#pragma unroll
          for (int nt = 0; nt < 3; nt++) {
            mma16c(S[nt], Q + 4 * h, Km[nt][2 * h], Km[nt][2 * h + 1], nt == 0 ? masked : 0.f);
            mma8(S[nt], e0, e1, Ke[nt][h]);
          }
          const float s00 = up0 ? S[0][0] : S[1][0], s01 = up1 ? S[0][1] : S[1][1];
          const float s10 = up0 ? S[1][2] : S[2][2], s11 = up1 ? S[1][3] : S[2][3];
          const float m0 = quad_max(fmaxf(s00, s01)) * c0, m1 = quad_max(fmaxf(s10, s11)) * c1;
          const float p00 = ex2(fmaf(s00, c0, -m0)), p01 = ex2(fmaf(s01, c0, -m0)), p10 = ex2(fmaf(s10, c1, -m1)), p11 = ex2(fmaf(s11, c1, -m1));
          const float i0 = rcp(quad_sum(p00 + p01)), i1 = rcp(quad_sum(p10 + p11));
          const uint32_t p0 = pack_bf16(p00 * i0, p01 * i0), p1 = pack_bf16(p10 * i1, p11 * i1);
          const uint32_t pf[4] = {p0 & upm, 0u, p0 & ~upm, p1 & upm};
#pragma unroll
          for (int gi = 0; gi < 3; gi++) {
            const int g = gi < 2 ? 2 * h + gi : 8 + h;
            float o[4];
            mma16c(o, pf, V01[g][0], V01[g][1], 0.f);
            mma8(o, 0u, p1 & ~upm, V2[g]);
            uint32_t* d = gi < 2 ? Om + 2 * g : Oe + 2 * h;
            d[0] = pack_bf16(o[0], o[1]); d[1] = pack_bf16(o[2], o[3]);
          }
        }
#pragma unroll
        for (int h = 0; h < 4; h++)
#pragma unroll
          for (int e = 0; e < 2; e++) {
            if (h > 0 && !odd && q < h) Om[4 * h + e] = Oe[2 * h - 2 + e];
            if (h < 3 && odd && q > h) Om[4 * h + 2 + e] = Oe[2 * h + 2 + e];
          }
        put72(xbase + 16 * SLAB, j, lane, Om, odd ? Oe[0] : Oe[6], odd ? Oe[1] : Oe[7]);
      }
      if (q == 0) stg4(scr + OFF_S + (8 + w) * 96 + j * 8 + r, tag, 0u, 0u, 0u);
      {
        uint32_t res[18];
        const uint4* p = xbase + ((9 * j + 1) >> 1) * 32 + lane;
#pragma unroll
        for (int i = 0; i < 4; i++) ldg4(res + 4 * i, p + i * 32);
        ldg2(res + 16, odd ? (const char*)(p - 32) + 8 : (const char*)(p + 4 * 32));
        const uint4* src = xbase + 16 * SLAB + lane;
        {
          const uint4* fp = scr + OFF_S + (8 + w) * 96 + q * 8 + r;
          uint32_t s0[4], s1[4];
          int n = 0;
          STAMP(8);
          while (true) {
            ldg4(s0, fp); ldg4(s1, fp + 32);
            if (__all_sync(~0u, (diff2(s0[0], s1[0], tag) & 1u) == 0u)) break;
            SPIN_GUARD(n);
          }
          STAMP(9);
        }
#pragma unroll
        for (int kb = 0; kb < GO; kb++) load_kb(kb, src, (const char*)src - lane * 8, 256);
        float acc[36];
#pragma unroll
        for (int i = 0; i < 18; i++) { acc[2 * i] = bf_lo(res[i]); acc[2 * i + 1] = bf_hi(res[i]); }
        mbar_wait(remo_full, layer);
#pragma unroll
        for (int kb = 0; kb < 9; kb++) {
          next_kb(false, kb, src, (const char*)src - lane * 8, 256);
          if (!(kb & 1)) mbar_wait(full0 + rg.st * 8, rg.ph);
          const uint32_t base = sb + rg.st * STAGE + (kb & 1) * 8192;
          const uint64_t d0 = DESC_HI | ((base >> 4) + (((sb + REM + 27648 + (kb >> 1) * 2048 + (kb & 1) * 64 - base) >> 4) << 16));
          wg_fence();
#pragma unroll
          for (int i = 0; i < 4; i++) wgmma_rs_n72(acc, X + 4 * (4 * kb + i), d0 - (uint64_t)(i * ((127u << 16) - 128u)), 1);
          wg_commit();
          wg_wait<1>();
          if (kb > 0 && !(kb & 1)) release(prev);
          if ((kb & 1) || kb == 8) { prev = rg.st; rg.next(); }
        }
        wg_wait<0>();
        release(prev);
        pin(acc);
        STAMP(10);
#pragma unroll
        for (int i = 0; i < 18; i++) res[i] = pack_bf16(acc[2 * i], acc[2 * i + 1]);
        put72(xbase + 32 * SLAB, j, lane, res, res[16], res[17]);
        publish_stats<9>(scr + OFF_S + (16 + w) * 96 + j * 8, acc, tag, lane);
      }
      continue;
      }
      const uint32_t hp = sb + PARK + w * 512 + lane * 16;
      auto pack8 = [&](float (&a)[32], int p, uint32_t* o) {
#pragma unroll
        for (int e = 0; e < 8; e++) asm volatile("" : "+f"(a[8 * p + e]) :: "memory");
#pragma unroll
        for (int e = 0; e < 4; e++) o[e] = pack_bf16(a[8 * p + 2 * e], a[8 * p + 2 * e + 1]);
      };
      const float ka0 = 0.7978845608028654f * rs0, kb0 = 0.044715f * ka0 * rs0 * rs0, ku0 = 0.5f * rs0 * rs0;
      const float ka1 = 0.7978845608028654f * rs1, kb1 = 0.044715f * ka1 * rs1 * rs1, ku1 = 0.5f * rs1 * rs1;
      auto packu8 = [&](int p, uint32_t* o) {
#pragma unroll
        for (int e = 0; e < 8; e++) asm volatile("" : "+f"(aA[8 * p + e]) :: "memory");
#pragma unroll
        for (int e = 0; e < 4; e++) o[e] = pack_bf16(aA[8 * p + 2 * e] * ((e & 1) ? ku1 : ku0), aA[8 * p + 2 * e + 1] * ((e & 1) ? ku1 : ku0));
      };
      auto geglu8 = [&](int p, uint32_t* u) {
#pragma unroll
        for (int e = 0; e < 8; e++) asm volatile("" : "+f"(aB[8 * p + e]) :: "memory");
        float h[8];
#pragma unroll
        for (int e = 0; e < 8; e++) {
          const float g = aB[8 * p + e];
          h[e] = fmaf(g, tanh_ap(g * fmaf(g * g, (e & 2) ? kb1 : kb0, (e & 2) ? ka1 : ka0)), g);
        }
#pragma unroll
        for (int e = 0; e < 4; e++) u[e] = mul_bf16x2(pack_bf16(h[2 * e], h[2 * e + 1]), u[e]);
      };
      auto box = [&](int b, auto&& filler) {
        const int kb = b < 9 ? b : b - 9;
        if (!(b & 1)) { if ((TRAPB >> (b >> 1)) & 1) mbar_wait_trap(full0 + rg.st * 8, rg.ph); else mbar_wait(full0 + rg.st * 8, rg.ph); }
        const uint64_t desc = DESC_HI | ((sb + rg.st * STAGE + (b & 1) * 8192) >> 4);
        wg_fence();
#pragma unroll
        for (int i = 0; i < 4; i++) {
          if (b < 9) wgmma_rs_n64(aA, X + 4 * (4 * kb + i), desc + i * 128, kb + i != 0);
          else wgmma_rs_n64(aB, X + 4 * (4 * kb + i), desc + i * 128, kb + i != 0);
          if (i == FPOS) filler();
        }
        wg_commit();
        if (b & 1) { prev = rg.st; rg.next(); } else { wg_wait<1>(); release(prev); }
      };
      auto nop = [] {};
      auto step = [&](int st, auto&& filler) { box(2 * st, nop); box(2 * st + 1, filler); };
#pragma unroll
      for (int p = 0; p < 4; p++) { uint32_t o[4]; packu8(p, o); sts4(hp + p * 4096, o); }
      box(0, nop);
      zero_share(xbase, j, lane);
      zero_share(xbase + 16 * SLAB, j, lane);
#pragma unroll 1
      for (int c = 1;; c++) {
        const uint32_t hc = hp + c * 4 * 4096;
#pragma unroll
        for (int b = 1; b < 18; b++) box(b, [&] {
          if ((b & 1) && b < 8) { uint32_t o[4]; const uint32_t a = hc - (4 - (b >> 1)) * 4096; lds4(a, o); geglu8(b >> 1, o); sts4(a, o); }
          if ((b & 1) && b > 10) { uint32_t o[4]; packu8((b - 11) >> 1, o); if (c < 8) sts4(hc + ((b - 11) >> 1) * 4096, o); } });
        if (c == 8) break;
        box(0, nop);
      }
      wg_wait<0>();
      STAMP(21);
      GSTAMP(19);
#pragma unroll
      for (int s = 0; s < 32; s++) lds4(hp + s * 4096, X + 4 * s);
#pragma unroll
      for (int p = 0; p < 4; p++) packu8(p, X + 128 + 4 * p);
#pragma unroll
      for (int st = 0; st < 4; st++) step(st, [&] { geglu8(st, X + 128 + 4 * st); });
      STAMP(24);
      if (layer == 0 && lane == 0) mbar_arrive(park_free);
      const uint32_t lane2 = lane_id();
      uint4* const pw = scr + OFF_P + (j * 8 + w) * SLAB + lane2;
      const uint4* const pr = scr + OFF_P + w * SLAB + 4 * j * 32 + lane2;
      auto put_part = [&](float (&a)[32], int p, uint32_t chunk) {
        uint32_t o[4];
        pack8(a, p, o);
        stg4(pw + (chunk * 4 + p) * 32, (o[0] & ~1u) | tag, o[1], o[2], o[3]);
      };
      uint4* const xb = xbase + 32 * SLAB + 4 * j * 32;
      auto slot = [&](int p) { return sb + w * 2048 + (p < 3 ? PARK + p * 16384 : KVS + (p - 3) * 16384); };
      auto fetch = [&](int p) {
        bulk_load(slot(p), p ? scr + OFF_P + (((j - p) & 7) * 8 + w) * SLAB + 4 * j * 32 : xb, 2048, pbar0 + w * 8, true);
      };
#pragma unroll 1
      for (int sp = 0;; sp++) {
        const uint32_t ca = sp == 0 ? 8 : ((j + 2 * sp) & 7), cb = (j + 2 * sp + 1) & 7;
        if (sp == 1 && lane2 == 0) mbar_arrive(c8_go);
#pragma unroll
        for (int st = 4; st < 9; st++) step(st, [&] {
          if (st == 5 || st == 6) { put_part(aA, 2 * (st - 5), ca); put_part(aA, 2 * (st - 5) + 1, ca); }
          if (st == 8 && sp > 0) { if (sp == 3) mbar_wait(c8_done, layer); fetch(2 * sp - 2); } });
        STAMP(25 + sp);
        if (sp == 3) break;
        if (sp == 2 && layer == 0 && (lane2 & 3) == 0) {
#pragma unroll
          for (int k = 0; k < 3; k++) stg4(scr + OFF_S + (k * 8 + w) * 96 + j * 8 + (lane2 >> 2), 1u, 0u, 0u, 0u);
        }
#pragma unroll
        for (int st = 0; st < 4; st++) step(st, [&] {
          if (st < 2) { put_part(aB, 2 * st, cb); put_part(aB, 2 * st + 1, cb); }
          if (st == 3 && sp > 0) fetch(2 * sp - 1); });
      }
      auto load_p = [&](int p, uint32_t* d) {
#pragma unroll
        for (int i = 0; i < 4; i++) ldg4(d + 4 * i, pr + ((j - p) & 7) * 8 * SLAB + i * 32);
      };
#pragma unroll
      for (int b = 0; b < 9; b++) {
        if (b == HOFF2 && w < 4) asm volatile("bar.sync 5, 256;" ::: "memory");
        box(b, [&] {
          if (b == 1) {
#pragma unroll
            for (int p = 0; p < 4; p++) put_part(aB, p, (j + 7) & 7);
          }
          if (b == 3) { load_p(5, X); load_p(6, X + 16); }
          if (b == 7 && EXP != 1) load_p(7, X + 32); });
        if (b == 7 && HOFF2 < 9 && w >= 4) asm volatile("bar.arrive 5, 256;" ::: "memory");
      }
      mbar_wait(pbar0 + w * 8, layer);
#pragma unroll
      for (int p = 1; p < 5; p++)
#pragma unroll
        for (int i = 0; i < 4; i++) lds4(slot(p) + lane2 * 16 + i * 512, X + 48 + 16 * p + 4 * i);
#pragma unroll
      for (int i = 0; i < 4; i++) {
        const bool split = j == 2 * i + 1;
        const uint32_t a = slot(0) + i * 512 + (split ? lane2 * 8 : lane2 * 16);
        lds2(a, X + 48 + 4 * i); lds2(a + (split ? 256 : 8), X + 50 + 4 * i);
      }
      wg_wait<0>();
      release(rg.st); rg.next();
      pin(aA);
      STAMP(22);
      GSTAMP(20);
      {
        const uint32_t eye = r == 2 * q ? 0x3f80u : r == 2 * q + 1 ? 0x3f800000u : 0u;
        auto bad = [&](const uint32_t* d) { return diff2(d[0], d[4], tag) | diff2(d[8], d[12], tag); };
        auto add = [&](const uint32_t* d) {
#pragma unroll
          for (int g = 0; g < 8; g++) mma8(aA + 4 * g, d[2 * g], d[2 * g + 1], eye);
        };
        int n = 0;
        while (!__all_sync(~0u, ((or3(bad(X), bad(X + 16), bad(X + 64)) | or3(bad(X + 80), bad(X + 96), bad(X + 112))) & 1u) == 0u)) {
          SPIN_GUARD(n);
          load_p(5, X); load_p(6, X + 16);
#pragma unroll
          for (int p = 1; p < 5; p++) load_p(p, X + 48 + 16 * p);
        }
        add(X); add(X + 16);
#pragma unroll
        for (int p = 4; p >= 0; p--) add(X + 48 + 16 * ((p + 1) % 5));
        STAMP(11);
        if (EXP != 1) while (!__all_sync(~0u, (bad(X + 32) & 1u) == 0u)) { SPIN_GUARD(n); load_p(7, X + 32); }
        add(X + 32);
        STAMP(12);
        uint32_t res[16];
#pragma unroll
        for (int i = 0; i < 16; i++) res[i] = pack_bf16(aA[2 * i], aA[2 * i + 1]);
        if (layer == 0) {
          uint4* p = xbase + 8 * SLAB + 4 * j * 32 + lane;
#pragma unroll
          for (int i = 0; i < 4; i++) stg4(p + i * 32, nz(res[4 * i]), res[4 * i + 1], nz(res[4 * i + 2]), res[4 * i + 3]);
          publish_stats<8>(scr + OFF_S + w * 96 + j * 8, aA, 0u, lane);
          if (lane == 0) mbar_arrive(kv_free);
        } else {
          const uint32_t tb = slot(0);
          __syncwarp();
#pragma unroll
          for (int i = 0; i < 4; i++) {
            const uint32_t row = (lane2 & 7) + (lane2 & 8), g = 2 * i + (lane2 >> 4);
            asm volatile("stmatrix.sync.aligned.m8n8.x4.shared.b16 [%0], {%1,%2,%3,%4};"
                         :: "r"(tb + row * 128 + ((g ^ (row & 7)) << 4)), "r"(res[4 * i]), "r"(res[4 * i + 1]), "r"(res[4 * i + 2]), "r"(res[4 * i + 3]) : "memory");
          }
          __syncwarp();
#pragma unroll
          for (int i = 0; i < 4; i++) {
            const uint32_t row = 4 * i + (lane2 >> 3), g = lane2 & 7;
            uint32_t v[4];
            lds4(tb + row * 128 + ((g ^ (row & 7)) << 4), v);
            *(uint4*)(out + (128 * t + 32 * (w >> 1) + 2 * row + (w & 1)) * 576 + 64 * j + 8 * g) = make_uint4(v[0], v[1], v[2], v[3]);
          }
        }
#pragma unroll
        for (int i = 0; i < 4; i++) stg4(xb + lane + i * 32, 0u, 0u, 0u, 0u);
      }
      STAMP(23);
    }
  }
}

typedef CUresult (*EncodeFn)(CUtensorMap*, CUtensorMapDataType, cuuint32_t, void*, const cuuint64_t*, const cuuint64_t*,
                             const cuuint32_t*, const cuuint32_t*, CUtensorMapInterleave, CUtensorMapSwizzle,
                             CUtensorMapL2promotion, CUtensorMapFloatOOBfill);

CUtensorMap make_map(EncodeFn f, const void* p, uint64_t cols, uint64_t rows, bool rem = false) {
  CUtensorMap m;
  cuuint64_t dims[2] = {cols, rows};
  cuuint64_t str[1] = {cols * 2};
  cuuint32_t box[2] = {rem ? 8u : 64u, rem ? 144u : 64u};
  cuuint32_t es[2] = {1, 1};
  f(&m, CU_TENSOR_MAP_DATA_TYPE_BFLOAT16, 2, const_cast<void*>(p), dims, str, box, es, CU_TENSOR_MAP_INTERLEAVE_NONE,
    rem ? CU_TENSOR_MAP_SWIZZLE_NONE : CU_TENSOR_MAP_SWIZZLE_128B, CU_TENSOR_MAP_L2_PROMOTION_NONE, CU_TENSOR_MAP_FLOAT_OOB_FILL_NONE);
  return m;
}

}

extern "C" void kernel_launch(void* const* d_in, const int* in_sizes, int n_in, void* d_out, int out_size) {
  void* fn = nullptr;
  cudaDriverEntryPointQueryResult qr;
  cudaGetDriverEntryPoint("cuTensorMapEncodeTiled", &fn, cudaEnableDefault, &qr);
  EncodeFn enc = (EncodeFn)fn;
  Maps maps;
  maps.m[0] = make_map(enc, d_in[1], 1728, 576); maps.m[1] = make_map(enc, d_in[2], 576, 576);
  maps.m[2] = make_map(enc, d_in[4], 4608, 576); maps.m[3] = make_map(enc, d_in[5], 4608, 576); maps.m[4] = make_map(enc, d_in[6], 576, 4608);
  maps.m[5] = make_map(enc, d_in[1], 1728, 576, true); maps.m[6] = make_map(enc, d_in[2], 576, 576, true);
  void* scr = nullptr;
  cudaGetSymbolAddress(&scr, g_scratch);
  cudaFuncSetAttribute(mega_kernel, cudaFuncAttributeMaxDynamicSharedMemorySize, SMEM_BYTES);
  mega_kernel<<<128, 384, SMEM_BYTES>>>(maps, (uint4*)scr, (const __nv_bfloat16*)d_in[0], (__nv_bfloat16*)d_out);
}
```

```cpp
#include <cuda_runtime.h>
#include <cuda.h>
#include <cuda_bf16.h>
#include <stdint.h>

#define TRACE 0
#define GUARD 0
#define TRAPB 1
#define HOFF1 99
#define HOFF2 99
#define KLD 8
#define ZT 0
#define SLEEP 500
#define SPLITZ 1
#define EXP 0
#define FPOS 2

namespace {

constexpr int NST = 6;
constexpr int STAGE = 16384;
constexpr int PARK = NST * STAGE;
constexpr int REM = PARK + 49152;
constexpr int KVS = REM + 40960;
constexpr int HSTG = KVS + 16384;
constexpr int BARS = KVS + 41472;
constexpr int TRC = BARS + 256;
constexpr int SMEM_BYTES = TRC + (TRACE ? 512 : 0);
static_assert(NST == 6, "the producer addresses empty barriers as full + 48");
static_assert(BARS >= PARK + 131072, "barriers overlap park");
static_assert(SMEM_BYTES <= 232448, "smem");

constexpr int SLAB = 36 * 32;
constexpr int SPIN_MAX = 1 << 17;
constexpr int GD = 3;
constexpr int OFF_S = 0;
constexpr int OFF_H = OFF_S + 3 * 8 * 96;
constexpr int OFF_X = OFF_H + 2 * 8 * 384;
constexpr int OFF_P = OFF_X + 6 * 8 * SLAB;
constexpr int TILE = OFF_P + 8 * 8 * SLAB;
constexpr int OFF_R = 16 * TILE;
constexpr int OFF_F = OFF_R + 8 * 2304;
constexpr int SCRATCH = OFF_F + 128 * 8;

}

__device__ uint4 g_scratch[SCRATCH];

namespace {

constexpr uint64_t DESC_HI = 0x4000004000000000ull;
constexpr uint64_t DESC_REM = (576ull << 32) | (8u << 16);
__device__ __forceinline__ void wgmma_rs_n64(float (&d)[32], const uint32_t* a, uint64_t desc, int scale_d) {
  asm volatile("{\n.reg .pred p;\nsetp.ne.b32 p, %37, 0;\n"
    "wgmma.mma_async.sync.aligned.m64n64k16.f32.bf16.bf16 "
    "{%0, %1, %2, %3, %4, %5, %6, %7, %8, %9, %10, %11, %12, %13, %14, %15, %16, %17, %18, %19, %20, %21, %22, %23, %24, %25, %26, %27, %28, %29, %30, %31}, "
    "{%32, %33, %34, %35}, %36, p, 1, 1, 1;\n}\n"
    : "+f"(d[0]), "+f"(d[1]), "+f"(d[2]), "+f"(d[3]), "+f"(d[4]), "+f"(d[5]), "+f"(d[6]), "+f"(d[7]), "+f"(d[8]), "+f"(d[9]), "+f"(d[10]), "+f"(d[11]), "+f"(d[12]), "+f"(d[13]), "+f"(d[14]), "+f"(d[15]), "+f"(d[16]), "+f"(d[17]), "+f"(d[18]), "+f"(d[19]), "+f"(d[20]), "+f"(d[21]), "+f"(d[22]), "+f"(d[23]), "+f"(d[24]), "+f"(d[25]), "+f"(d[26]), "+f"(d[27]), "+f"(d[28]), "+f"(d[29]), "+f"(d[30]), "+f"(d[31])
    : "r"(a[0]), "r"(a[1]), "r"(a[2]), "r"(a[3]), "l"(desc), "r"(scale_d));
}
__device__ __forceinline__ void wgmma_rs_n72(float (&d)[36], const uint32_t* a, uint64_t desc, int scale_d) {
  asm volatile("{\n.reg .pred p;\nsetp.ne.b32 p, %41, 0;\n"
    "wgmma.mma_async.sync.aligned.m64n72k16.f32.bf16.bf16 "
    "{%0, %1, %2, %3, %4, %5, %6, %7, %8, %9, %10, %11, %12, %13, %14, %15, %16, %17, %18, %19, %20, %21, %22, %23, %24, %25, %26, %27, %28, %29, %30, %31, %32, %33, %34, %35}, "
    "{%36, %37, %38, %39}, %40, p, 1, 1, 1;\n}\n"
    : "+f"(d[0]), "+f"(d[1]), "+f"(d[2]), "+f"(d[3]), "+f"(d[4]), "+f"(d[5]), "+f"(d[6]), "+f"(d[7]), "+f"(d[8]), "+f"(d[9]), "+f"(d[10]), "+f"(d[11]), "+f"(d[12]), "+f"(d[13]), "+f"(d[14]), "+f"(d[15]), "+f"(d[16]), "+f"(d[17]), "+f"(d[18]), "+f"(d[19]), "+f"(d[20]), "+f"(d[21]), "+f"(d[22]), "+f"(d[23]), "+f"(d[24]), "+f"(d[25]), "+f"(d[26]), "+f"(d[27]), "+f"(d[28]), "+f"(d[29]), "+f"(d[30]), "+f"(d[31]), "+f"(d[32]), "+f"(d[33]), "+f"(d[34]), "+f"(d[35])
    : "r"(a[0]), "r"(a[1]), "r"(a[2]), "r"(a[3]), "l"(desc), "r"(scale_d));
}
__device__ __forceinline__ void wgmma_rs_n24(float (&d)[12], const uint32_t* a, uint64_t desc, int scale_d) {
  asm volatile("{\n.reg .pred p;\nsetp.ne.b32 p, %17, 0;\n"
    "wgmma.mma_async.sync.aligned.m64n24k16.f32.bf16.bf16 "
    "{%0, %1, %2, %3, %4, %5, %6, %7, %8, %9, %10, %11}, "
    "{%12, %13, %14, %15}, %16, p, 1, 1, 1;\n}\n"
    : "+f"(d[0]), "+f"(d[1]), "+f"(d[2]), "+f"(d[3]), "+f"(d[4]), "+f"(d[5]), "+f"(d[6]), "+f"(d[7]), "+f"(d[8]), "+f"(d[9]), "+f"(d[10]), "+f"(d[11])
    : "r"(a[0]), "r"(a[1]), "r"(a[2]), "r"(a[3]), "l"(desc), "r"(scale_d));
}

__device__ __forceinline__ void mbar_init(uint32_t a, uint32_t c) { asm volatile("mbarrier.init.shared::cta.b64 [%0], %1;" :: "r"(a), "r"(c)); }
__device__ __forceinline__ void mbar_arrive(uint32_t a) { asm volatile("mbarrier.arrive.shared::cta.b64 _, [%0];" :: "r"(a) : "memory"); }
__device__ __forceinline__ void mbar_wait_trap(uint32_t a, uint32_t ph) {
  asm volatile("{\n.reg .pred p;\n.reg .u32 n;\nmov.u32 n, 0;\n"
               "W: mbarrier.try_wait.parity.shared::cta.b64 p, [%0], %1;\n@p bra D;\n"
               "add.u32 n, n, 1;\nsetp.lt.u32 p, n, 4194304;\n@p bra W;\ntrap;\nD:\n}" :: "r"(a), "r"(ph) : "memory");
}
__device__ __forceinline__ void mbar_wait(uint32_t a, uint32_t ph) {
  asm volatile("{\n.reg .pred p;\nW: mbarrier.try_wait.parity.shared::cta.b64 p, [%0], %1;\n@!p bra W;\n}" :: "r"(a), "r"(ph) : "memory");
}
__device__ __forceinline__ void mbar_wait_sleep(uint32_t a, uint32_t ph) {
  asm volatile("{\n.reg .pred p;\nW: mbarrier.test_wait.parity.shared::cta.b64 p, [%0], %1;\n@p bra D;\nnanosleep.u32 %2;\nbra W;\nD:\n}" :: "r"(a), "r"(ph), "n"(SLEEP) : "memory");
}
__device__ __forceinline__ void wg_fence() { asm volatile("wgmma.fence.sync.aligned;" ::: "memory"); }
__device__ __forceinline__ void wg_commit() { asm volatile("wgmma.commit_group.sync.aligned;" ::: "memory"); }
template <int N> __device__ __forceinline__ void wg_wait() { asm volatile("wgmma.wait_group.sync.aligned %0;" :: "n"(N) : "memory"); }
__device__ __forceinline__ float tanh_ap(float x) { float y; asm("tanh.approx.f32 %0, %1;" : "=f"(y) : "f"(x)); return y; }
__device__ __forceinline__ float ex2(float x) { float y; asm("ex2.approx.ftz.f32 %0, %1;" : "=f"(y) : "f"(x)); return y; }
__device__ __forceinline__ uint32_t pack_bf16(float lo, float hi) { uint32_t r; asm("cvt.rn.bf16x2.f32 %0, %1, %2;" : "=r"(r) : "f"(hi), "f"(lo)); return r; }
__device__ __forceinline__ float bf_lo(uint32_t v) { return __uint_as_float(v << 16); }
__device__ __forceinline__ float bf_hi(uint32_t v) { return __uint_as_float(v & 0xffff0000u); }
__device__ __forceinline__ uint32_t sub_bf16x2(uint32_t a, uint32_t b) { uint32_t r; asm("sub.rn.bf16x2 %0, %1, %2;" : "=r"(r) : "r"(a), "r"(b)); return r; }
__device__ __forceinline__ uint32_t mul_bf16x2(uint32_t a, uint32_t b) { uint32_t r; asm("mul.rn.bf16x2 %0, %1, %2;" : "=r"(r) : "r"(a), "r"(b)); return r; }
__device__ __forceinline__ uint32_t diff2(uint32_t a, uint32_t b, uint32_t t) { uint32_t r; asm("lop3.b32 %0, %1, %2, %3, 0x7e;" : "=r"(r) : "r"(a), "r"(b), "r"(t)); return r; }
__device__ __forceinline__ uint32_t or3(uint32_t a, uint32_t b, uint32_t c) { uint32_t r; asm("lop3.b32 %0, %1, %2, %3, 0xfe;" : "=r"(r) : "r"(a), "r"(b), "r"(c)); return r; }
__device__ __forceinline__ uint32_t umin2(uint32_t a, uint32_t b) { uint32_t r; asm("min.u32 %0, %1, %2;" : "=r"(r) : "r"(a), "r"(b)); return r; }
__device__ __forceinline__ uint32_t bitmask(uint32_t v, int bit) { uint32_t r; asm("bfe.s32 %0, %1, %2, 1;" : "=r"(r) : "r"(v), "r"(bit)); return r; }
__device__ __forceinline__ uint32_t nz(uint32_t w) { return w == 0u ? 0x8000u : w; }

__device__ __forceinline__ void ldg4(uint32_t* d, const uint4* p) {
  asm volatile("ld.relaxed.gpu.global.v4.b32 {%0,%1,%2,%3}, [%4];" : "=r"(d[0]), "=r"(d[1]), "=r"(d[2]), "=r"(d[3]) : "l"(p) : "memory");
}
__device__ __forceinline__ void ldg2(uint32_t* d, const void* p) {
  asm volatile("ld.relaxed.gpu.global.v2.b32 {%0,%1}, [%2];" : "=r"(d[0]), "=r"(d[1]) : "l"(p) : "memory");
}
__device__ __forceinline__ void stg4(uint4* p, uint32_t a, uint32_t b, uint32_t c, uint32_t d) {
  asm volatile("st.relaxed.gpu.global.v4.b32 [%0], {%1,%2,%3,%4};" :: "l"(p), "r"(a), "r"(b), "r"(c), "r"(d) : "memory");
}
__device__ __forceinline__ void stg2(void* p, uint32_t a, uint32_t b) {
  asm volatile("st.relaxed.gpu.global.v2.b32 [%0], {%1,%2};" :: "l"(p), "r"(a), "r"(b) : "memory");
}
__device__ __forceinline__ void sts4(uint32_t a, const uint32_t* o) { asm volatile("st.shared.v4.b32 [%0], {%1,%2,%3,%4};" :: "r"(a), "r"(o[0]), "r"(o[1]), "r"(o[2]), "r"(o[3]) : "memory"); }
__device__ __forceinline__ void lds4(uint32_t a, uint32_t* o) { asm volatile("ld.shared.v4.b32 {%0,%1,%2,%3}, [%4];" : "=r"(o[0]), "=r"(o[1]), "=r"(o[2]), "=r"(o[3]) : "r"(a) : "memory"); }
__device__ __forceinline__ void lds2(uint32_t a, uint32_t* o) { asm volatile("ld.shared.v2.b32 {%0,%1}, [%2];" : "=r"(o[0]), "=r"(o[1]) : "r"(a) : "memory"); }
__device__ __forceinline__ float rcp(float x) { float y; asm("rcp.approx.ftz.f32 %0, %1;" : "=f"(y) : "f"(x)); return y; }
__device__ __forceinline__ void sts1(uint32_t a, uint32_t v) { asm volatile("st.shared.b32 [%0], %1;" :: "r"(a), "r"(v) : "memory"); }
__device__ __forceinline__ void ldsm4(uint32_t a, uint32_t& r0, uint32_t& r1, uint32_t& r2, uint32_t& r3) {
  asm volatile("ldmatrix.sync.aligned.m8n8.x4.shared.b16 {%0,%1,%2,%3}, [%4];" : "=r"(r0), "=r"(r1), "=r"(r2), "=r"(r3) : "r"(a) : "memory");
}
__device__ __forceinline__ void ldsm4t(uint32_t a, uint32_t& r0, uint32_t& r1, uint32_t& r2, uint32_t& r3) {
  asm volatile("ldmatrix.sync.aligned.m8n8.x4.trans.shared.b16 {%0,%1,%2,%3}, [%4];" : "=r"(r0), "=r"(r1), "=r"(r2), "=r"(r3) : "r"(a) : "memory");
}
__device__ __forceinline__ void mma16c(float* d, const uint32_t* a, uint32_t b0, uint32_t b1, float c01) {
  asm("mma.sync.aligned.m16n8k16.row.col.f32.bf16.bf16.f32 {%0,%1,%2,%3}, {%4,%5,%6,%7}, {%8,%9}, {%10,%10,%10,%10};"
    : "=f"(d[0]), "=f"(d[1]), "=f"(d[2]), "=f"(d[3]) : "r"(a[0]), "r"(a[1]), "r"(a[2]), "r"(a[3]), "r"(b0), "r"(b1), "f"(c01));
}
__device__ __forceinline__ void mma8(float* c, uint32_t a0, uint32_t a1, uint32_t b0) {
  asm("mma.sync.aligned.m16n8k8.row.col.f32.bf16.bf16.f32 {%0,%1,%2,%3}, {%4,%5}, {%6}, {%0,%1,%2,%3};"
    : "+f"(c[0]), "+f"(c[1]), "+f"(c[2]), "+f"(c[3]) : "r"(a0), "r"(a1), "r"(b0));
}
__device__ __forceinline__ uint32_t lane_id() { uint32_t l; asm volatile("mov.u32 %0, %%laneid;" : "=r"(l)); return l; }
__device__ __forceinline__ float quad_sum(float v) { v += __shfl_xor_sync(~0u, v, 1); v += __shfl_xor_sync(~0u, v, 2); return v; }
__device__ __forceinline__ float quad_max(float v) { v = fmaxf(v, __shfl_xor_sync(~0u, v, 1)); v = fmaxf(v, __shfl_xor_sync(~0u, v, 2)); return v; }
template <int N> __device__ __forceinline__ void pin(float (&d)[N]) {
#pragma unroll
  for (int i = 0; i < N; i++) asm volatile("" : "+f"(d[i]) :: "memory");
}
#define SPIN_GUARD(n) if (++(n) > SPIN_MAX) break

template <int NG> __device__ __forceinline__ void publish_stats(uint4* dst, const float* y, uint32_t tag, uint32_t lane) {
  float s0 = 0.f, s1 = 0.f;
#pragma unroll
  for (int g = 0; g < NG; g++) { s0 += y[4 * g] + y[4 * g + 1]; s1 += y[4 * g + 2] + y[4 * g + 3]; }
  s0 = quad_sum(s0); s1 = quad_sum(s1);
  const float m0 = s0 * (1.f / (8 * NG)), m1 = s1 * (1.f / (8 * NG));
  float q0 = 0.f, q1 = 0.f, q2 = 0.f, q3 = 0.f;
#pragma unroll
  for (int g = 0; g < NG; g++) {
    const float a = y[4 * g] - m0, b = y[4 * g + 1] - m0, c = y[4 * g + 2] - m1, d = y[4 * g + 3] - m1;
    q0 = fmaf(a, a, q0); q1 = fmaf(b, b, q1); q2 = fmaf(c, c, q2); q3 = fmaf(d, d, q3);
  }
  q0 = quad_sum(q0 + q1); q2 = quad_sum(q2 + q3);
  if ((lane & 3) == 0)
    stg4(dst + (lane >> 2), (__float_as_uint(s0) & ~1u) | tag, __float_as_uint(q0), __float_as_uint(s1), __float_as_uint(q2));
}

__device__ __forceinline__ void put72(uint4* slab, uint32_t j, uint32_t lane, const uint32_t* v, uint32_t r0, uint32_t r1) {
  uint4* p = slab + ((9 * j + 1) >> 1) * 32;
#pragma unroll
  for (int i = 0; i < 4; i++) stg4(p + lane + i * 32, nz(v[4 * i]), v[4 * i + 1], v[4 * i + 2], v[4 * i + 3]);
  stg2((char*)((j & 1) ? p - 16 : p + 4 * 32) + lane * 8, nz(r0), r1);
}
__device__ __forceinline__ void zero_share(uint4* slab, uint32_t j, uint32_t lane) {
  uint4* p = slab + j * 144 + lane;
#pragma unroll
  for (int i = 0; i < 4; i++) stg4(p + i * 32, 0u, 0u, 0u, 0u);
  if (lane < 16) stg4(p + 128, 0u, 0u, 0u, 0u);
}

struct Maps { CUtensorMap m[7]; };

struct Ring {
  uint32_t st, ph;
  __device__ __forceinline__ void next() { if (++st == NST) { st = 0; ph ^= 1; } }
};

#define GSTAMP(i) do {} while (0)
#define STAMP(i) do {} while (0)
#define ZSTAMP(m, i) do {} while (0)

__device__ __forceinline__ void tma_box(uint32_t dst, const CUtensorMap* m, int col, int row, uint32_t bar, uint32_t expect) {
  asm volatile("{\n.reg .pred e, h;\nelect.sync _|e, 0xffffffff;\nsetp.ne.and.u32 h, %5, 0, e;\n"
               "@h mbarrier.arrive.expect_tx.shared::cta.b64 _, [%2], %5;\n"
               "@e cp.async.bulk.tensor.2d.shared::cluster.global.mbarrier::complete_tx::bytes [%0], [%1, {%3, %4}], [%2];\n}"
               :: "r"(dst), "l"(m), "r"(bar), "r"(col), "r"(row), "r"(expect) : "memory");
}

__device__ __forceinline__ void bulk_load(uint32_t dst, const void* src, uint32_t bytes, uint32_t bar, bool arm) {
  asm volatile("{\n.reg .pred e, h;\nelect.sync _|e, 0xffffffff;\nsetp.ne.and.u32 h, %4, 0, e;\n"
               "@h mbarrier.arrive.expect_tx.shared::cta.b64 _, [%3], %2;\n"
               "@e cp.async.bulk.shared::cluster.global.mbarrier::complete_tx::bytes [%0], [%1], %2, [%3];\n}"
               :: "r"(dst), "l"(src), "r"(bytes), "r"(bar), "r"((uint32_t)arm) : "memory");
}

__global__ void __launch_bounds__(384, 1) mega_kernel(
    const __grid_constant__ Maps maps, uint4* __restrict__ scratch,
    const __nv_bfloat16* __restrict__ x_in, __nv_bfloat16* __restrict__ out) {
  extern __shared__ __align__(1024) uint8_t smem[];
  const uint32_t sb = (uint32_t)__cvta_generic_to_shared(smem);
  const uint32_t full0 = sb + BARS, empty0 = full0 + 8 * NST, rem_full = empty0 + 8 * NST, park_free = rem_full + 8, kv_free = park_free + 8;
  const uint32_t c8_go = kv_free + 8, c8_done = c8_go + 8, c8_full = c8_done + 8, remo_full = c8_full + 8, piece_full = remo_full + 8, xb_done = piece_full + 8, pbar0 = xb_done + 8;
  const uint32_t w = __shfl_sync(~0u, threadIdx.x >> 5, 0);
  const uint32_t t = blockIdx.x >> 3, j = blockIdx.x & 7;
  const uint32_t odd = j & 1;
  uint4* const scr = scratch + t * TILE;
  {
    const uint32_t lane = lane_id(), r = lane >> 2, q = lane & 3;
    const uint32_t sl = w < 8 ? w : j, ch = w < 8 ? j : 8;
    const uint32_t* xr = (const uint32_t*)(x_in + (128 * t + 32 * (sl >> 1) + 2 * r + (sl & 1)) * 576 + 64 * ch + 2 * q);
    if (w < 8 || w == 9) {
      uint32_t v[16];
#pragma unroll
      for (int g = 0; g < 8; g++) {
        asm volatile("ld.global.nc.b32 %0, [%1];" : "=r"(v[2 * g]) : "l"(xr + 4 * g));
        asm volatile("ld.global.nc.b32 %0, [%1];" : "=r"(v[2 * g + 1]) : "l"(xr + 8 * 576 + 4 * g));
      }
      if (q == 0) {
#pragma unroll
        for (int k = 0; k < 3; k++) stg4(scr + OFF_S + (k * 8 + sl) * 96 + ch * 8 + r, 0u, 0u, 0u, 0u);
      }
      asm volatile("bar.sync 0, 384;" ::: "memory");
      uint4* p = scr + OFF_X + sl * SLAB + 4 * ch * 32 + lane;
#pragma unroll
      for (int i = 0; i < 4; i++) stg4(p + i * 32, nz(v[4 * i]), v[4 * i + 1], nz(v[4 * i + 2]), v[4 * i + 3]);
      float y[32];
#pragma unroll
      for (int i = 0; i < 16; i++) { y[2 * i] = bf_lo(v[i]); y[2 * i + 1] = bf_hi(v[i]); }
      publish_stats<8>(scr + OFF_S + sl * 96 + ch * 8, y, 1u, lane);
    } else {
      if (threadIdx.x == 256) {
        for (int i = 0; i < NST; i++) { mbar_init(full0 + 8 * i, 1); mbar_init(empty0 + 8 * i, 8); }
        mbar_init(rem_full, 1); mbar_init(park_free, 8); mbar_init(kv_free, 8); mbar_init(c8_go, 8); mbar_init(c8_done, 1); mbar_init(c8_full, 1); mbar_init(remo_full, 64); mbar_init(piece_full, 1); mbar_init(xb_done, 8);
        for (int i = 0; i < 8; i++) mbar_init(pbar0 + 8 * i, 5);
        asm volatile("fence.mbarrier_init.release.cluster;" ::: "memory");
      }
      __syncwarp();
      asm volatile("bar.sync 0, 384;" ::: "memory");
    }
  }

  if (w >= 8) {
    asm volatile("setmaxnreg.dec.sync.aligned.u32 24;");
    if (w == 8) {
      uint32_t dst = sb, bar = full0, ph = 1;
#pragma unroll 1
      for (int seg = 0; seg < 34; seg++) {
        const int n = seg >= 17 ? seg - 17 : seg;
        int ma, mb, ca, cb, row = 0;
        if (n < 3) { ma = mb = n == 2; ca = 72 * j + 8 * odd + (n == 0 ? 576 : 0); cb = ca + 576; }
        else if (n < 12) { ma = 3; mb = 2; ca = cb = 576 * j + 64 * (n - 3); }
        else { ma = mb = 4; ca = n == 12 ? 512 : ((j + 2 * n) & 7) * 64; cb = ((j + 2 * n + 1) & 7) * 64; row = 576 * j; }
        const bool zip = n == 0 || n == 3, solo = n == 1 || n == 2 || n == 16;
        const CUtensorMap *pa = &maps.m[ma], *pb = &maps.m[mb];
#pragma unroll 1
        for (int st = 0; st < (solo ? 5 : 9); st++) {
          const bool s0 = !zip && st > 4, s1 = zip || st >= 4;
          const int r0 = row + (zip ? 64 * st : s0 ? 128 * st - 576 : 128 * st), r1 = zip ? r0 : st == 4 ? row : r0 + 64;
          asm volatile("{\n.reg .pred p, e, f;\n.reg .u32 n;\nelect.sync _|e, 0xffffffff;\nsetp.eq.and.u32 f, %9, 16384, e;\nmov.u32 n, 0;\n"
                       "W: mbarrier.try_wait.parity.shared::cta.b64 p, [%1+48], %2;\n@p bra D;\n"
                       "add.u32 n, n, 1;\nsetp.lt.u32 p, n, 4194304;\n@p bra W;\ntrap;\n"
                       "D: @e mbarrier.arrive.expect_tx.shared::cta.b64 _, [%1], %9;\n"
                       "@e cp.async.bulk.tensor.2d.shared::cluster.global.mbarrier::complete_tx::bytes [%0], [%3, {%4, %5}], [%1];\n"
                       "@f cp.async.bulk.tensor.2d.shared::cluster.global.mbarrier::complete_tx::bytes [%0+8192], [%6, {%7, %8}], [%1];\n}"
                       :: "r"(dst), "r"(bar), "r"(ph), "l"(s0 ? pb : pa), "r"(s0 ? cb : ca), "r"(r0), "l"(s1 ? pb : pa), "r"(s1 ? cb : ca), "r"(r1),
                          "r"(solo && st == 4 ? STAGE / 2 : STAGE) : "memory");
          dst += STAGE; bar += 8;
          if (bar == full0 + 8 * NST) { dst = sb; bar = full0; ph ^= 1; }
        }
      }
    } else if (w == 9) {
      const uint32_t lane = lane_id();
      const uint32_t stg = sb + HSTG + lane * 16;
      uint32_t fph = 0;
#pragma unroll 1
      for (uint32_t layer = 0; layer < 2; layer++) {
        uint4* xb = scr + OFF_X + ((4 + layer) * 8 + j) * SLAB + 32 * 32;
        mbar_wait_sleep(c8_go, layer);
        int n = 0;
        while (true) {
          if (lane == 0) asm volatile("mbarrier.arrive.expect_tx.shared::cta.b64 _, [%0], 18432;" :: "r"(c8_full) : "memory");
          __syncwarp();
#pragma unroll 1
          for (uint32_t s = 0; s < 9; s++)
            bulk_load(sb + HSTG + s * 2048, s < 8 ? scr + OFF_P + (j + s * 8) * SLAB + 32 * 32 : xb, 2048, c8_full, false);
          mbar_wait(c8_full, fph); fph ^= 1;
          uint32_t bad = 0;
#pragma unroll 8
          for (int s = 0; s < 32; s++) { uint32_t v; asm volatile("ld.shared.b32 %0, [%1];" : "=r"(v) : "r"(stg + s * 512) : "memory"); bad |= v ^ (1 - layer); }
          if (__all_sync(~0u, (bad & 1u) == 0u)) break;
          __nanosleep(300);
          SPIN_GUARD(n);
        }
        float s0 = 0.f, s1 = 0.f;
#pragma unroll 1
        for (int g = 0; g < 8; g++) {
          const uint32_t a = stg + (g >> 1) * 512 + (g & 1) * 8;
          float a0 = 0.f, a1 = 0.f, a2 = 0.f, a3 = 0.f;
#pragma unroll 1
          for (int b = 0; b < 3; b++) {
            uint32_t v[6];
#pragma unroll
            for (int s = 0; s < 3; s++) lds2(a + (3 * b + s) * 2048, v + 2 * s);
#pragma unroll
            for (int s = 0; s < 3; s++) { a0 += bf_lo(v[2 * s]); a1 += bf_hi(v[2 * s]); a2 += bf_lo(v[2 * s + 1]); a3 += bf_hi(v[2 * s + 1]); }
          }
          sts1(a + 18432, pack_bf16(a0, a1)); sts1(a + 18436, pack_bf16(a2, a3));
          s0 += a0 + a1; s1 += a2 + a3;
        }
        __syncwarp();
        if (lane == 0) mbar_arrive(c8_done);
        s0 = quad_sum(s0); s1 = quad_sum(s1);
        float q0 = 0.f, q1 = 0.f;
        const uint32_t ln = lane_id();
#pragma unroll 1
        for (uint32_t i = 0; i < 4; i++) {
          uint32_t x[4];
          lds4(stg + 18432 + i * 512, x);
          stg4(xb + i * 32 + ln, 0u, 0u, 0u, 0u);
          if (layer == 0) {
            stg4(xb - 3 * 8 * SLAB + i * 32 + ln, nz(x[0]), x[1], x[2], x[3]);
#pragma unroll
            for (int e = 0; e < 4; e++) {
              const float m = (e & 1) ? s1 : s0, c = fmaf(m, -1.f / 64, bf_lo(x[e])), d = fmaf(m, -1.f / 64, bf_hi(x[e]));
              if (e & 1) q1 = fmaf(c, c, fmaf(d, d, q1)); else q0 = fmaf(c, c, fmaf(d, d, q0));
            }
          } else {
            uint32_t* o = (uint32_t*)(out + (128 * t + 32 * (j >> 1) + 2 * (ln >> 2) + (j & 1)) * 576 + 512 + 16 * i + 2 * (ln & 3));
            o[0] = x[0]; o[8 * 576] = x[1]; o[4] = x[2]; o[8 * 576 + 4] = x[3];
          }
        }
        if (layer == 0) {
          q0 = quad_sum(q0); q1 = quad_sum(q1);
          if ((ln & 3) == 0) stg4(scr + OFF_S + j * 96 + 64 + (ln >> 2), __float_as_uint(s0) & ~1u, __float_as_uint(q0), __float_as_uint(s1), __float_as_uint(q1));
        }
      }
    } else {
#pragma unroll 1
      for (uint32_t layer = 0; layer < 2; layer++) {
        if (w == 10) {
          if (layer == 0) {
            const uint32_t lane = lane_id();
            const uint32_t p = t >> 2;
            tma_box(sb + PARK, &maps.m[p == 3 ? 6 : 5], 72 * j + (odd ? 0 : 64) + (p < 2 ? 576 * (p + 1) : 0), 144 * (t & 3), piece_full, 2304);
            mbar_wait(piece_full, 0);
            asm volatile("{\n.reg .pred e;\nelect.sync _|e, 0xffffffff;\n@e cp.async.bulk.global.shared::cta.bulk_group [%0], [%1], 2304;\n}\n"
                         "cp.async.bulk.commit_group;\ncp.async.bulk.wait_group 0;\nfence.proxy.async;"
                         :: "l"(scratch + OFF_R + j * 2304 + t * 144), "r"(sb + PARK) : "memory");
            __syncwarp();
            if (lane < 16) asm volatile("st.release.gpu.global.b32 [%0], 1;" :: "l"((uint32_t*)(scratch + OFF_F + (lane * 8 + j) * 8) + t) : "memory");
            uint32_t* fl = (uint32_t*)(scratch + OFF_F + (t * 8 + j) * 8) + (lane & 15);
            uint32_t v;
            int n = 0;
            while (true) {
              asm volatile("ld.acquire.gpu.global.b32 %0, [%1];" : "=r"(v) : "l"(fl) : "memory");
              if (__all_sync(~0u, v != 0u)) break;
              __nanosleep(100);
              SPIN_GUARD(n);
            }
            asm volatile("fence.proxy.async;\nst.relaxed.gpu.global.b32 [%0], 0;" :: "l"(fl) : "memory");
          } else {
            mbar_wait_sleep(park_free, 0);
          }
          bulk_load(sb + REM, scratch + OFF_R + j * 2304, 36864, rem_full, true);
        }
        mbar_wait_sleep(rem_full, layer);
#pragma unroll 1
        for (uint32_t b = 0; b < 5; b++) {
          const uint32_t blk = sb + REM + 27648 + b * 2048, k = (w - 10) * 32 + lane_id(), rr = k & 7;
          const uint32_t dst = blk + ((k >> 3) & 1) * 1024 + rr * 128 + (((k >> 4) ^ rr) << 4);
          uint32_t v[8];
          lds4(blk + k * 16, v); lds4(blk + 1024 + k * 16, v + 4);
          asm volatile("bar.sync 3, 64;" ::: "memory");
          sts4(dst, v); sts4(dst ^ 64, v + 4);
        }
        asm volatile("fence.proxy.async.shared::cta;" ::: "memory");
        mbar_arrive(remo_full);
        if (layer) mbar_wait_sleep(kv_free, 0);
        if (t > 0) {
          const uint32_t lane = lane_id(), r = lane >> 2, q = lane & 3;
#pragma unroll 1
          for (uint32_t pc = 0; pc < 3; pc++) {
            uint4* hp = scr + OFF_H + ((layer * 8 + j) * 2 + (w - 10)) * 192 + pc * 64 + lane;
            uint32_t hl[8];
            int n = 0;
            hl[4] = 1u;
            while (true) {
              ldg4(hl, hp);
              if (pc < 2) ldg4(hl + 4, hp + 32);
              if (__all_sync(~0u, hl[0] != 0u && hl[4] != 0u)) break;
              __nanosleep(100);
              SPIN_GUARD(n);
            }
            const uint32_t dst = sb + KVS + (w - 10) * 10368 + r * 144 + q * 4;
            if (pc < 2) {
#pragma unroll
              for (int g = 0; g < 8; g++) sts1(dst + pc * 20736 + odd * 16 + g * 16, hl[g]);
              stg4(hp + 32, 0u, 0u, 0u, 0u);
            } else {
              sts1(dst + (odd ? 0 : 128), hl[0]); sts1(dst + 20736 + (odd ? 0 : 128), hl[1]);
            }
            stg4(hp, 0u, 0u, 0u, 0u);
          }
        }
        asm volatile("bar.arrive 1, 192;" ::: "memory");
        mbar_wait_sleep(xb_done, layer);
#pragma unroll 1
        for (uint32_t i = 0; i < 8; i++) {
          zero_share(scr + OFF_X + ((w - 10) * 16 + layer * 8 + i) * SLAB, j, lane_id());
          __nanosleep(500);
        }
      }
    }
  } else {
    asm volatile("setmaxnreg.inc.sync.aligned.u32 240;");
    const bool lead = lane_id() == 0;
    Ring rg{0, 0};
    uint32_t prev = 0;
    uint32_t X[144];
    float rs0, rs1;
    uint32_t mean0, mean1;
    auto release = [&](uint32_t st) { if (lead) mbar_arrive(empty0 + st * 8); };
    auto load_kb = [&](int kb, const uint4* src, const char* lo, uint32_t hoff) {
#pragma unroll
      for (int k = 4 * kb; k < 4 * kb + 4; k++) {
        if (k % 9 == 4) { ldg2(X + 4 * k, lo + k * 512); ldg2(X + 4 * k + 2, lo + hoff + k * 512); }
        else ldg4(X + 4 * k, src + k * 32);
      }
    };
    auto next_kb = [&](bool center, int kb, const uint4* src, const char* lo, uint32_t hoff) {
      int n = 0;
      while (true) {
        uint32_t m = umin2(umin2(X[16 * kb], X[16 * kb + 4]), umin2(X[16 * kb + 8], X[16 * kb + 12]));
        if (kb & 1) m = umin2(m, X[16 * kb + 4 * (kb >> 1) + 2]);
        if (__all_sync(~0u, m != 0u)) break;
        SPIN_GUARD(n);
        load_kb(kb, src, lo, hoff);
      }
      if (kb + GD < 9) load_kb(kb + GD, src, lo, hoff);
      if (center) {
#pragma unroll
        for (int i = 16 * kb; i < 16 * kb + 16; i++) X[i] = sub_bf16x2(X[i], (i & 1) ? mean1 : mean0);
      }
    };
#pragma unroll 1
    for (uint32_t hf = 0; hf < 4; hf++) {
      const uint32_t layer = hf >> 1;
      const bool ffn = hf & 1;
      const uint32_t tag = 1 - layer;
      uint4* const xbase = scr + OFF_X + (layer * 8 + w) * SLAB;
      float aA[32], aB[32];
      {
        const uint32_t lane = lane_id(), r = lane >> 2, q = lane & 3;
        const uint4* src = xbase + (ffn ? 32 * SLAB : 0) + lane;
        const char* lo = (const char*)src - (ffn ? lane * 8 : 0);
        const uint32_t hoff = ffn ? 256 : 8;
        uint32_t s[3][4];
        const uint4* p = scr + OFF_S + ((ffn ? 16 : 0) + w) * 96 + q * 8 + r;
        const bool third = !ffn && q == 0;
        int n = 0;
        s[2][0] = tag; s[2][1] = s[2][2] = s[2][3] = 0u;
        STAMP(ffn * 16 + 0);
        while (true) {
          ldg4(s[0], p); ldg4(s[1], p + 32);
          if (third) ldg4(s[2], p + 64);
          if (__all_sync(~0u, ((diff2(s[0][0], s[1][0], tag) | diff2(s[2][0], s[2][0], tag)) & 1u) == 0u)) break;
          SPIN_GUARD(n);
        }
        STAMP(ffn * 16 + 1);
        ZSTAMP(1 + ffn, 0);
        GSTAMP(14 + ffn);
#pragma unroll
        for (int kb = 0; kb < GD; kb++) load_kb(kb, src, lo, hoff);
        float t0 = 0.f, t1 = 0.f;
#pragma unroll
        for (int i = 0; i < 3; i++) { t0 += __uint_as_float(s[i][0]); t1 += __uint_as_float(s[i][2]); }
        const float m0 = quad_sum(t0) * (1.f / 576), m1 = quad_sum(t1) * (1.f / 576);
        const float cnt = ffn ? 72.f : 64.f, inv = ffn ? 1.f / 72 : 1.f / 64;
        float v0 = 0.f, v1 = 0.f;
#pragma unroll
        for (int i = 0; i < 3; i++) {
          const float c = (i < 2 || third) ? cnt : 0.f;
          const float d0 = fmaf(__uint_as_float(s[i][0]), inv, -m0), d1 = fmaf(__uint_as_float(s[i][2]), inv, -m1);
          v0 += fmaf(d0 * d0, c, __uint_as_float(s[i][1])); v1 += fmaf(d1 * d1, c, __uint_as_float(s[i][3]));
        }
        rs0 = rsqrtf(fmaf(quad_sum(v0), 1.f / 576, 1e-5f)); rs1 = rsqrtf(fmaf(quad_sum(v1), 1.f / 576, 1e-5f));
        mean0 = pack_bf16(m0, m0); mean1 = pack_bf16(m1, m1);
#pragma unroll
        for (int kb = 0; kb < 9; kb++) {
          next_kb(true, kb, src, lo, hoff);
          ZSTAMP(1 + ffn, 1 + 3 * kb);
          mbar_wait(full0 + rg.st * 8, rg.ph);
          ZSTAMP(1 + ffn, 2 + 3 * kb);
          const uint64_t desc = DESC_HI | ((sb + rg.st * STAGE) >> 4);
          wg_fence();
#pragma unroll
          for (int i = 0; i < 4; i++) wgmma_rs_n64(aA, X + 4 * (4 * kb + i), desc + i * 128, kb + i != 0);
          if (SPLITZ && kb == 8) { wg_commit(); wg_wait<1>(); wg_fence(); }
#pragma unroll
          for (int i = 0; i < 4; i++) wgmma_rs_n64(aB, X + 4 * (4 * kb + i), desc + 512 + i * 128, kb + i != 0);
          wg_commit();
          wg_wait<1>();
          ZSTAMP(1 + ffn, 3 + 3 * kb);
          if (kb > 0) release(prev);
          prev = rg.st; rg.next();
        }
        if (!SPLITZ) wg_wait<0>();
        ZSTAMP(1 + ffn, 28);
        ZSTAMP(4, 0);
        STAMP(ffn * 16 + 2);
      }
      if (!ffn) {
      const uint32_t lane = lane_id(), r = lane >> 2, q = lane & 3;
      const uint32_t kvrow = sb + KVS + (w & 1) * 10368 + (16 * (w >> 1)) * 144;
      uint32_t Q[18], Km[3][8], Ke[3][4];
      const bool edge = (t == 0 && w < 2);
      const uint32_t row0 = edge ? sb + KVS + 8 * 144 : kvrow + (lane & 7) * 144, row1 = kvrow + (8 + (lane & 7)) * 144;
      {
        const uint32_t dst = kvrow + (8 + r) * 144 + q * 4 + odd * 16, dstr = dst + (odd ? -16 : 128);
        const bool edge_out = w >= 6 && t < 15;
        uint4* const hp = scr + TILE + OFF_H + ((layer * 8 + j) * 2 + (w & 1)) * 192 + lane;
        auto put_kv = [&](float (&a)[32], int part) {
          pin(a);
          uint32_t hl[8];
#pragma unroll
          for (int g = 0; g < 8; g++) {
            hl[g] = pack_bf16(a[4 * g + 2] * rs1, a[4 * g + 3] * rs1);
            sts1(dst + part * 20736 + g * 16, pack_bf16(a[4 * g] * rs0, a[4 * g + 1] * rs0)); sts1(dst + part * 20736 + 8 * 144 + g * 16, hl[g]);
          }
          if (edge_out) { stg4(hp + part * 64, nz(hl[0]), hl[1], hl[2], hl[3]); stg4(hp + part * 64 + 32, nz(hl[4]), hl[5], hl[6], hl[7]); }
        };
        put_kv(aA, 0);
        wg_wait<0>();
        release(prev);
        float aR[12];
        mbar_wait(rem_full, layer);
        const uint64_t dr = DESC_REM | ((sb + REM) >> 4);
        wg_fence();
#pragma unroll
        for (int s = 0; s < 36; s++) {
          wgmma_rs_n24(aR, X + 4 * s, dr + s * 16, s != 0);
          if (s == 4) put_kv(aB, 1);
        }
        wg_commit();
#pragma unroll
        for (int kb = 0; kb < 9; kb++) {
          if (kb == HOFF1 && w < 4) asm volatile("bar.sync 4, 256;" ::: "memory");
          if (kb == 8 && HOFF1 < 9 && w >= 4) asm volatile("bar.arrive 4, 256;" ::: "memory");
          if (!(kb & 1)) mbar_wait(full0 + rg.st * 8, rg.ph);
          const uint64_t desc = DESC_HI | ((sb + rg.st * STAGE + (kb & 1) * 8192) >> 4);
          wg_fence();
#pragma unroll
          for (int i = 0; i < 4; i++) wgmma_rs_n64(aB, X + 4 * (4 * kb + i), desc + i * 128, kb + i != 0);
          wg_commit();
          wg_wait<1>();
          if (kb > 0 && !(kb & 1)) release(prev);
          if ((kb & 1) || kb == 8) { prev = rg.st; rg.next(); }
          if (kb == 0) {
            pin(aR);
            const uint32_t k1 = pack_bf16(aR[2] * rs1, aR[3] * rs1), v1 = pack_bf16(aR[6] * rs1, aR[7] * rs1);
            if (edge_out) stg4(hp + 128, nz(k1), v1, 0u, 0u);
            sts1(dstr, pack_bf16(aR[0] * rs0, aR[1] * rs0)); sts1(dstr + 8 * 144, k1);
            sts1(dstr + 20736, pack_bf16(aR[4] * rs0, aR[5] * rs0)); sts1(dstr + 20736 + 8 * 144, v1);
            Q[16] = pack_bf16(aR[8], aR[9]); Q[17] = pack_bf16(aR[10], aR[11]);
            if (w < 4) asm volatile("bar.arrive 2, 256;" ::: "memory");
          }
          if (kb == KLD) {
            if (w < 4) asm volatile("bar.sync 1, 192;" ::: "memory");
            else asm volatile("bar.sync 2, 256;" ::: "memory");
#pragma unroll
            for (int nt = 0; nt < 3; nt++) {
              const uint32_t ra = (nt == 0 ? row0 : row1 + (nt - 1) * 8 * 144);
              ldsm4(ra + odd * 16 + (lane >> 3) * 16, Km[nt][0], Km[nt][1], Km[nt][2], Km[nt][3]);
              ldsm4(ra + odd * 16 + 64 + (lane >> 3) * 16, Km[nt][4], Km[nt][5], Km[nt][6], Km[nt][7]);
              ldsm4(ra + (odd ? 0 : 32) + (lane >> 3) * 32, Ke[nt][0], Ke[nt][1], Ke[nt][2], Ke[nt][3]);
            }
            const uint32_t ge = (2u << q) - 1, le = 0xfu << q, on = edge ? 0u : ~0u;
            const uint32_t bits = odd ? 0xfu | ((le & 0xfu) << 4) | (ge << 8) : ge | 0xf0u | (le << 8);
#pragma unroll
            for (int h = 0; h < 4; h++) {
              const uint32_t ma = bitmask(bits, h), mb = bitmask(bits, 4 + h), mc = bitmask(bits, 8 + h);
              Km[0][2 * h] &= ma & on; Km[0][2 * h + 1] &= mb & on; Ke[0][h] &= mc & on;
#pragma unroll
              for (int nt = 1; nt < 3; nt++) { Km[nt][2 * h] &= ma; Km[nt][2 * h + 1] &= mb; Ke[nt][h] &= mc; }
            }
          }
        }
        wg_wait<0>();
        release(prev);
        pin(aB);
        STAMP(3);
#pragma unroll
        for (int i = 0; i < 16; i++) Q[i] = pack_bf16(aB[2 * i], aB[2 * i + 1]);
      }
      {
        uint32_t V01[12][2], V2[12];
        const uint32_t rv = ((lane & 8) ? row1 : row0) + 20736, rw = row1 + 8 * 144 + 20736;
#pragma unroll
        for (int i = 0; i < 4; i++) ldsm4t(rv + odd * 16 + i * 32 + (lane >> 4) * 16, V01[2 * i][0], V01[2 * i][1], V01[2 * i + 1][0], V01[2 * i + 1][1]);
#pragma unroll
        for (int i = 0; i < 2; i++) ldsm4t(rv + (odd ? 0 : 32) + i * 64 + (lane >> 4) * 32, V01[8 + 2 * i][0], V01[8 + 2 * i][1], V01[9 + 2 * i][0], V01[9 + 2 * i][1]);
        ldsm4t(rw + odd * 16 + (lane >> 3) * 16, V2[0], V2[1], V2[2], V2[3]);
        ldsm4t(rw + odd * 16 + 64 + (lane >> 3) * 16, V2[4], V2[5], V2[6], V2[7]);
        ldsm4t(rw + (odd ? 0 : 32) + (lane >> 3) * 32, V2[8], V2[9], V2[10], V2[11]);
        const bool up0 = 2 * q > r, up1 = 2 * q + 1 > r;
        const uint32_t upm = (up0 ? 0xffffu : 0u) | (up1 ? 0xffff0000u : 0u);
        const float c0 = 0.23570226039551584f * 1.4426950408889634f * rs0, c1 = 0.23570226039551584f * 1.4426950408889634f * rs1;
        const float masked = edge ? -1e9f * 1.4426950408889634f * rcp(c0) : 0.f;
        uint32_t Om[16], Oe[8];
#pragma unroll
        for (int h = 0; h < 4; h++) {
          const uint32_t e0 = odd ? Q[(4 * h + 16) % 18] : Q[4 * h + 4], e1 = odd ? Q[(4 * h + 17) % 18] : Q[4 * h + 5];
          float S[3][4];
#pragma unroll
          for (int nt = 0; nt < 3; nt++) {
            mma16c(S[nt], Q + 4 * h, Km[nt][2 * h], Km[nt][2 * h + 1], nt == 0 ? masked : 0.f);
            mma8(S[nt], e0, e1, Ke[nt][h]);
          }
          const float s00 = up0 ? S[0][0] : S[1][0], s01 = up1 ? S[0][1] : S[1][1];
          const float s10 = up0 ? S[1][2] : S[2][2], s11 = up1 ? S[1][3] : S[2][3];
          const float m0 = quad_max(fmaxf(s00, s01)) * c0, m1 = quad_max(fmaxf(s10, s11)) * c1;
          const float p00 = ex2(fmaf(s00, c0, -m0)), p01 = ex2(fmaf(s01, c0, -m0)), p10 = ex2(fmaf(s10, c1, -m1)), p11 = ex2(fmaf(s11, c1, -m1));
          const float i0 = rcp(quad_sum(p00 + p01)), i1 = rcp(quad_sum(p10 + p11));
          const uint32_t p0 = pack_bf16(p00 * i0, p01 * i0), p1 = pack_bf16(p10 * i1, p11 * i1);
          const uint32_t pf[4] = {p0 & upm, 0u, p0 & ~upm, p1 & upm};
#pragma unroll
          for (int gi = 0; gi < 3; gi++) {
            const int g = gi < 2 ? 2 * h + gi : 8 + h;
            float o[4];
            mma16c(o, pf, V01[g][0], V01[g][1], 0.f);
            mma8(o, 0u, p1 & ~upm, V2[g]);
            uint32_t* d = gi < 2 ? Om + 2 * g : Oe + 2 * h;
            d[0] = pack_bf16(o[0], o[1]); d[1] = pack_bf16(o[2], o[3]);
          }
        }
#pragma unroll
        for (int h = 0; h < 4; h++)
#pragma unroll
          for (int e = 0; e < 2; e++) {
            if (h > 0 && !odd && q < h) Om[4 * h + e] = Oe[2 * h - 2 + e];
            if (h < 3 && odd && q > h) Om[4 * h + 2 + e] = Oe[2 * h + 2 + e];
          }
        STAMP(4);
        put72(xbase + 16 * SLAB, j, lane, Om, odd ? Oe[0] : Oe[6], odd ? Oe[1] : Oe[7]);
      }
      if (q == 0) stg4(scr + OFF_S + (8 + w) * 96 + j * 8 + r, tag, 0u, 0u, 0u);
      {
        uint32_t res[18];
        const uint4* p = xbase + ((9 * j + 1) >> 1) * 32 + lane;
#pragma unroll
        for (int i = 0; i < 4; i++) ldg4(res + 4 * i, p + i * 32);
        ldg2(res + 16, odd ? (const char*)(p - 32) + 8 : (const char*)(p + 4 * 32));
        const uint4* src = xbase + 16 * SLAB + lane;
        {
          const uint4* fp = scr + OFF_S + (8 + w) * 96 + q * 8 + r;
          uint32_t s0[4], s1[4];
          int n = 0;
          STAMP(8);
          while (true) {
            ldg4(s0, fp); ldg4(s1, fp + 32);
            if (__all_sync(~0u, (diff2(s0[0], s1[0], tag) & 1u) == 0u)) break;
            SPIN_GUARD(n);
          }
          STAMP(9);
        }
#pragma unroll
        for (int kb = 0; kb < GD; kb++) load_kb(kb, src, (const char*)src - lane * 8, 256);
        float acc[36];
#pragma unroll
        for (int i = 0; i < 18; i++) { acc[2 * i] = bf_lo(res[i]); acc[2 * i + 1] = bf_hi(res[i]); }
        mbar_wait(remo_full, layer);
#pragma unroll
        for (int kb = 0; kb < 9; kb++) {
          next_kb(false, kb, src, (const char*)src - lane * 8, 256);
          if (!(kb & 1)) mbar_wait(full0 + rg.st * 8, rg.ph);
          const uint32_t base = sb + rg.st * STAGE + (kb & 1) * 8192;
          const uint64_t d0 = DESC_HI | ((base >> 4) + (((sb + REM + 27648 + (kb >> 1) * 2048 + (kb & 1) * 64 - base) >> 4) << 16));
          wg_fence();
#pragma unroll
          for (int i = 0; i < 4; i++) wgmma_rs_n72(acc, X + 4 * (4 * kb + i), d0 - (uint64_t)(i * ((127u << 16) - 128u)), 1);
          wg_commit();
          wg_wait<1>();
          if (kb > 0 && !(kb & 1)) release(prev);
          if ((kb & 1) || kb == 8) { prev = rg.st; rg.next(); }
        }
        wg_wait<0>();
        release(prev);
        pin(acc);
        STAMP(10);
#pragma unroll
        for (int i = 0; i < 18; i++) res[i] = pack_bf16(acc[2 * i], acc[2 * i + 1]);
        put72(xbase + 32 * SLAB, j, lane, res, res[16], res[17]);
        publish_stats<9>(scr + OFF_S + (16 + w) * 96 + j * 8, acc, tag, lane);
      }
      continue;
      }
      const uint32_t hp = sb + PARK + w * 512 + lane_id() * 16;
      auto pack8 = [&](float (&a)[32], int p, uint32_t* o) {
#pragma unroll
        for (int e = 0; e < 8; e++) asm volatile("" : "+f"(a[8 * p + e]) :: "memory");
#pragma unroll
        for (int e = 0; e < 4; e++) o[e] = pack_bf16(a[8 * p + 2 * e], a[8 * p + 2 * e + 1]);
      };
      const float ka0 = 0.7978845608028654f * rs0, kb0 = 0.044715f * ka0 * rs0 * rs0, ku0 = 0.5f * rs0 * rs0;
      const float ka1 = 0.7978845608028654f * rs1, kb1 = 0.044715f * ka1 * rs1 * rs1, ku1 = 0.5f * rs1 * rs1;
      auto packu8 = [&](int p, uint32_t* o) {
#pragma unroll
        for (int e = 0; e < 8; e++) asm volatile("" : "+f"(aA[8 * p + e]) :: "memory");
#pragma unroll
        for (int e = 0; e < 4; e++) o[e] = pack_bf16(aA[8 * p + 2 * e] * ((e & 1) ? ku1 : ku0), aA[8 * p + 2 * e + 1] * ((e & 1) ? ku1 : ku0));
      };
      auto geglu8 = [&](int p, uint32_t* u) {
#pragma unroll
        for (int e = 0; e < 8; e++) asm volatile("" : "+f"(aB[8 * p + e]) :: "memory");
        float h[8];
#pragma unroll
        for (int e = 0; e < 8; e++) {
          const float g = aB[8 * p + e];
          h[e] = fmaf(g, tanh_ap(g * fmaf(g * g, (e & 2) ? kb1 : kb0, (e & 2) ? ka1 : ka0)), g);
        }
#pragma unroll
        for (int e = 0; e < 4; e++) u[e] = mul_bf16x2(pack_bf16(h[2 * e], h[2 * e + 1]), u[e]);
      };
      auto box = [&](int b, auto&& filler) {
        const int kb = b < 9 ? b : b - 9;
        if (!(b & 1)) { if ((TRAPB >> (b >> 1)) & 1) mbar_wait_trap(full0 + rg.st * 8, rg.ph); else mbar_wait(full0 + rg.st * 8, rg.ph); }
        const uint64_t desc = DESC_HI | ((sb + rg.st * STAGE + (b & 1) * 8192) >> 4);
        wg_fence();
#pragma unroll
        for (int i = 0; i < 4; i++) {
          if (b < 9) wgmma_rs_n64(aA, X + 4 * (4 * kb + i), desc + i * 128, kb + i != 0);
          else wgmma_rs_n64(aB, X + 4 * (4 * kb + i), desc + i * 128, kb + i != 0);
          if (i == FPOS) filler();
        }
        wg_commit();
        if (b & 1) { prev = rg.st; rg.next(); } else { wg_wait<1>(); release(prev); }
      };
      auto nop = [] {};
      auto step = [&](int st, auto&& filler) { box(2 * st, nop); box(2 * st + 1, filler); };
#pragma unroll
      for (int p = 0; p < 4; p++) { uint32_t o[4]; packu8(p, o); sts4(hp + p * 4096, o); }
      box(0, nop);
      if (lead) mbar_arrive(xb_done);
#pragma unroll 1
      for (int c = 1;; c++) {
        const uint32_t hc = hp + c * 4 * 4096;
#pragma unroll
        for (int b = 1; b < 18; b++) box(b, [&] {
          if ((b & 1) && b < 8) { uint32_t o[4]; const uint32_t a = hc - (4 - (b >> 1)) * 4096; lds4(a, o); geglu8(b >> 1, o); sts4(a, o); }
          if ((b & 1) && b > 10) { uint32_t o[4]; packu8((b - 11) >> 1, o); if (c < 8) sts4(hc + ((b - 11) >> 1) * 4096, o); } });
        ZSTAMP(4, c);
        if (c == 8) break;
        box(0, nop);
      }
      wg_wait<0>();
      STAMP(21);
      GSTAMP(19);
#pragma unroll
      for (int s = 0; s < 32; s++) lds4(hp + s * 4096, X + 4 * s);
#pragma unroll
      for (int p = 0; p < 4; p++) packu8(p, X + 128 + 4 * p);
#pragma unroll
      for (int st = 0; st < 4; st++) step(st, [&] { geglu8(st, X + 128 + 4 * st); });
      STAMP(24);
      if (layer == 0 && lead) mbar_arrive(park_free);
      const uint32_t lane2 = lane_id();
      uint4* const pw = scr + OFF_P + (j * 8 + w) * SLAB + lane2;
      const uint4* const pr = scr + OFF_P + w * SLAB + 4 * j * 32 + lane2;
      auto put_part = [&](float (&a)[32], int p, uint32_t chunk) {
        uint32_t o[4];
        pack8(a, p, o);
        stg4(pw + (chunk * 4 + p) * 32, (o[0] & ~1u) | tag, o[1], o[2], o[3]);
      };
      uint4* const xb = xbase + 32 * SLAB + 4 * j * 32;
      auto slot = [&](int p) { return sb + w * 2048 + (p < 3 ? PARK + p * 16384 : KVS + (p - 3) * 16384); };
      auto fetch = [&](int p) {
        bulk_load(slot(p), p ? scr + OFF_P + (((j - p) & 7) * 8 + w) * SLAB + 4 * j * 32 : xb, 2048, pbar0 + w * 8, true);
      };
#pragma unroll 1
      for (int sp = 0;; sp++) {
        const uint32_t ca = sp == 0 ? 8 : ((j + 2 * sp) & 7), cb = (j + 2 * sp + 1) & 7;
        if (sp == 1 && lead) mbar_arrive(c8_go);
#pragma unroll
        for (int st = 4; st < 9; st++) step(st, [&] {
          if (st == 5 || st == 6) { put_part(aA, 2 * (st - 5), ca); put_part(aA, 2 * (st - 5) + 1, ca); }
          if (st == 8 && sp > 0) { if (sp == 3) mbar_wait(c8_done, layer); fetch(2 * sp - 2); } });
        STAMP(25 + sp);
        if (sp == 3) break;
        if (sp == 2 && layer == 0 && (lane2 & 3) == 0) {
#pragma unroll
          for (int k = 0; k < 3; k++) stg4(scr + OFF_S + (k * 8 + w) * 96 + j * 8 + (lane2 >> 2), 1u, 0u, 0u, 0u);
        }
#pragma unroll
        for (int st = 0; st < 4; st++) step(st, [&] {
          if (st < 2) { put_part(aB, 2 * st, cb); put_part(aB, 2 * st + 1, cb); }
          if (st == 3 && sp > 0) fetch(2 * sp - 1); });
      }
      auto load_p = [&](int p, uint32_t* d) {
#pragma unroll
        for (int i = 0; i < 4; i++) ldg4(d + 4 * i, pr + ((j - p) & 7) * 8 * SLAB + i * 32);
      };
#pragma unroll
      for (int b = 0; b < 9; b++) {
        if (b == HOFF2 && w < 4) asm volatile("bar.sync 5, 256;" ::: "memory");
        box(b, [&] {
          if (b == 1) {
#pragma unroll
            for (int p = 0; p < 4; p++) put_part(aB, p, (j + 7) & 7);
          }
          if (b == 3) { load_p(5, X); load_p(6, X + 16); }
          if (b == 7 && EXP != 1) load_p(7, X + 32); });
        if (b == 7 && HOFF2 < 9 && w >= 4) asm volatile("bar.arrive 5, 256;" ::: "memory");
      }
      mbar_wait(pbar0 + w * 8, layer);
#pragma unroll
      for (int p = 1; p < 5; p++)
#pragma unroll
        for (int i = 0; i < 4; i++) lds4(slot(p) + lane2 * 16 + i * 512, X + 48 + 16 * p + 4 * i);
#pragma unroll
      for (int i = 0; i < 4; i++) {
        const bool split = j == 2 * i + 1;
        const uint32_t a = slot(0) + i * 512 + (split ? lane2 * 8 : lane2 * 16);
        lds2(a, X + 48 + 4 * i); lds2(a + (split ? 256 : 8), X + 50 + 4 * i);
      }
      wg_wait<0>();
      release(rg.st); rg.next();
      pin(aA);
      STAMP(22);
      GSTAMP(20);
      {
        const uint32_t lane = lane2, r = lane >> 2, q = lane & 3;
        const uint32_t eye = r == 2 * q ? 0x3f80u : r == 2 * q + 1 ? 0x3f800000u : 0u;
        auto bad = [&](const uint32_t* d) { return diff2(d[0], d[4], tag) | diff2(d[8], d[12], tag); };
        auto add = [&](const uint32_t* d) {
#pragma unroll
          for (int g = 0; g < 8; g++) mma8(aA + 4 * g, d[2 * g], d[2 * g + 1], eye);
        };
        int n = 0;
        while (!__all_sync(~0u, ((or3(bad(X), bad(X + 16), bad(X + 64)) | or3(bad(X + 80), bad(X + 96), bad(X + 112))) & 1u) == 0u)) {
          SPIN_GUARD(n);
          load_p(5, X); load_p(6, X + 16);
#pragma unroll
          for (int p = 1; p < 5; p++) load_p(p, X + 48 + 16 * p);
        }
        add(X); add(X + 16);
#pragma unroll
        for (int p = 4; p >= 0; p--) add(X + 48 + 16 * ((p + 1) % 5));
        STAMP(11);
        if (EXP != 1) while (!__all_sync(~0u, (bad(X + 32) & 1u) == 0u)) { SPIN_GUARD(n); load_p(7, X + 32); }
        add(X + 32);
        STAMP(12);
        uint32_t res[16];
#pragma unroll
        for (int i = 0; i < 16; i++) res[i] = pack_bf16(aA[2 * i], aA[2 * i + 1]);
        if (layer == 0) {
          uint4* p = xbase + 8 * SLAB + 4 * j * 32 + lane;
#pragma unroll
          for (int i = 0; i < 4; i++) stg4(p + i * 32, nz(res[4 * i]), res[4 * i + 1], nz(res[4 * i + 2]), res[4 * i + 3]);
          publish_stats<8>(scr + OFF_S + w * 96 + j * 8, aA, 0u, lane);
          if (lane == 0) mbar_arrive(kv_free);
        } else {
          const uint32_t tb = slot(0);
          __syncwarp();
#pragma unroll
          for (int i = 0; i < 4; i++) {
            const uint32_t row = (lane2 & 7) + (lane2 & 8), g = 2 * i + (lane2 >> 4);
            asm volatile("stmatrix.sync.aligned.m8n8.x4.shared.b16 [%0], {%1,%2,%3,%4};"
                         :: "r"(tb + row * 128 + ((g ^ (row & 7)) << 4)), "r"(res[4 * i]), "r"(res[4 * i + 1]), "r"(res[4 * i + 2]), "r"(res[4 * i + 3]) : "memory");
          }
          __syncwarp();
#pragma unroll
          for (int i = 0; i < 4; i++) {
            const uint32_t row = 4 * i + (lane2 >> 3), g = lane2 & 7;
            uint32_t v[4];
            lds4(tb + row * 128 + ((g ^ (row & 7)) << 4), v);
            *(uint4*)(out + (128 * t + 32 * (w >> 1) + 2 * row + (w & 1)) * 576 + 64 * j + 8 * g) = make_uint4(v[0], v[1], v[2], v[3]);
          }
        }
#pragma unroll
        for (int i = 0; i < 4; i++) stg4(xb + lane + i * 32, 0u, 0u, 0u, 0u);
      }
      STAMP(23);
    }
  }
}

typedef CUresult (*EncodeFn)(CUtensorMap*, CUtensorMapDataType, cuuint32_t, void*, const cuuint64_t*, const cuuint64_t*,
                             const cuuint32_t*, const cuuint32_t*, CUtensorMapInterleave, CUtensorMapSwizzle,
                             CUtensorMapL2promotion, CUtensorMapFloatOOBfill);

CUtensorMap make_map(EncodeFn f, const void* p, uint64_t cols, uint64_t rows, bool rem = false) {
  CUtensorMap m;
  cuuint64_t dims[2] = {cols, rows};
  cuuint64_t str[1] = {cols * 2};
  cuuint32_t box[2] = {rem ? 8u : 64u, rem ? 144u : 64u};
  cuuint32_t es[2] = {1, 1};
  f(&m, CU_TENSOR_MAP_DATA_TYPE_BFLOAT16, 2, const_cast<void*>(p), dims, str, box, es, CU_TENSOR_MAP_INTERLEAVE_NONE,
    rem ? CU_TENSOR_MAP_SWIZZLE_NONE : CU_TENSOR_MAP_SWIZZLE_128B, CU_TENSOR_MAP_L2_PROMOTION_NONE, CU_TENSOR_MAP_FLOAT_OOB_FILL_NONE);
  return m;
}

}

extern "C" void kernel_launch(void* const* d_in, const int* in_sizes, int n_in, void* d_out, int out_size) {
  void* fn = nullptr;
  cudaDriverEntryPointQueryResult qr;
  cudaGetDriverEntryPoint("cuTensorMapEncodeTiled", &fn, cudaEnableDefault, &qr);
  EncodeFn enc = (EncodeFn)fn;
  Maps maps;
  maps.m[0] = make_map(enc, d_in[1], 1728, 576); maps.m[1] = make_map(enc, d_in[2], 576, 576);
  maps.m[2] = make_map(enc, d_in[4], 4608, 576); maps.m[3] = make_map(enc, d_in[5], 4608, 576); maps.m[4] = make_map(enc, d_in[6], 576, 4608);
  maps.m[5] = make_map(enc, d_in[1], 1728, 576, true); maps.m[6] = make_map(enc, d_in[2], 576, 576, true);
  void* scr = nullptr;
  cudaGetSymbolAddress(&scr, g_scratch);
  cudaFuncSetAttribute(mega_kernel, cudaFuncAttributeMaxDynamicSharedMemorySize, SMEM_BYTES);
  mega_kernel<<<128, 384, SMEM_BYTES>>>(maps, (uint4*)scr, (const __nv_bfloat16*)d_in[0], (__nv_bfloat16*)d_out);
}
```

```cpp
#include <cuda_runtime.h>
#include <cuda.h>
#include <cuda_bf16.h>
#include <stdint.h>

#define TRACE 0
#define GUARD 0
#define TRAPB 1
#define HOFF1 99
#define HOFF2 99
#define KLD 8
#define ZT 0
#define SLEEP 500
#define SPLITZ 1
#define C8 1
#define HOFF3 99
#define GO 3
#define EXP 0
#define FPOS 2

namespace {

constexpr int NST = 6;
constexpr int STAGE = 16384;
constexpr int PARK = NST * STAGE;
constexpr int REM = PARK + 49152;
constexpr int KVS = REM + 40960;
constexpr int HSTG = KVS + 16384;
constexpr int BARS = KVS + 41472;
constexpr int TRC = BARS + 256;
constexpr int SMEM_BYTES = TRC + (TRACE ? 512 : 0);
static_assert(NST == 6, "the producer addresses empty barriers as full + 48");
static_assert(BARS >= PARK + 131072, "barriers overlap park");
static_assert(SMEM_BYTES <= 232448, "smem");

constexpr int SLAB = 36 * 32;
constexpr int SPIN_MAX = 1 << 17;
constexpr int GD = 3;
constexpr int OFF_S = 0;
constexpr int OFF_H = OFF_S + 3 * 8 * 96;
constexpr int OFF_X = OFF_H + 2 * 8 * 384;
constexpr int OFF_P = OFF_X + 6 * 8 * SLAB;
constexpr int TILE = OFF_P + 8 * 8 * SLAB;
constexpr int OFF_R = 16 * TILE;
constexpr int OFF_F = OFF_R + 8 * 2304;
constexpr int SCRATCH = OFF_F + 128 * 8;

}

__device__ uint4 g_scratch[SCRATCH];

namespace {

constexpr uint64_t DESC_HI = 0x4000004000000000ull;
constexpr uint64_t DESC_REM = (576ull << 32) | (8u << 16);
__device__ __forceinline__ void wgmma_rs_n64(float (&d)[32], const uint32_t* a, uint64_t desc, int scale_d) {
  asm volatile("{\n.reg .pred p;\nsetp.ne.b32 p, %37, 0;\n"
    "wgmma.mma_async.sync.aligned.m64n64k16.f32.bf16.bf16 "
    "{%0, %1, %2, %3, %4, %5, %6, %7, %8, %9, %10, %11, %12, %13, %14, %15, %16, %17, %18, %19, %20, %21, %22, %23, %24, %25, %26, %27, %28, %29, %30, %31}, "
    "{%32, %33, %34, %35}, %36, p, 1, 1, 1;\n}\n"
    : "+f"(d[0]), "+f"(d[1]), "+f"(d[2]), "+f"(d[3]), "+f"(d[4]), "+f"(d[5]), "+f"(d[6]), "+f"(d[7]), "+f"(d[8]), "+f"(d[9]), "+f"(d[10]), "+f"(d[11]), "+f"(d[12]), "+f"(d[13]), "+f"(d[14]), "+f"(d[15]), "+f"(d[16]), "+f"(d[17]), "+f"(d[18]), "+f"(d[19]), "+f"(d[20]), "+f"(d[21]), "+f"(d[22]), "+f"(d[23]), "+f"(d[24]), "+f"(d[25]), "+f"(d[26]), "+f"(d[27]), "+f"(d[28]), "+f"(d[29]), "+f"(d[30]), "+f"(d[31])
    : "r"(a[0]), "r"(a[1]), "r"(a[2]), "r"(a[3]), "l"(desc), "r"(scale_d));
}
__device__ __forceinline__ void wgmma_rs_n72(float (&d)[36], const uint32_t* a, uint64_t desc, int scale_d) {
  asm volatile("{\n.reg .pred p;\nsetp.ne.b32 p, %41, 0;\n"
    "wgmma.mma_async.sync.aligned.m64n72k16.f32.bf16.bf16 "
    "{%0, %1, %2, %3, %4, %5, %6, %7, %8, %9, %10, %11, %12, %13, %14, %15, %16, %17, %18, %19, %20, %21, %22, %23, %24, %25, %26, %27, %28, %29, %30, %31, %32, %33, %34, %35}, "
    "{%36, %37, %38, %39}, %40, p, 1, 1, 1;\n}\n"
    : "+f"(d[0]), "+f"(d[1]), "+f"(d[2]), "+f"(d[3]), "+f"(d[4]), "+f"(d[5]), "+f"(d[6]), "+f"(d[7]), "+f"(d[8]), "+f"(d[9]), "+f"(d[10]), "+f"(d[11]), "+f"(d[12]), "+f"(d[13]), "+f"(d[14]), "+f"(d[15]), "+f"(d[16]), "+f"(d[17]), "+f"(d[18]), "+f"(d[19]), "+f"(d[20]), "+f"(d[21]), "+f"(d[22]), "+f"(d[23]), "+f"(d[24]), "+f"(d[25]), "+f"(d[26]), "+f"(d[27]), "+f"(d[28]), "+f"(d[29]), "+f"(d[30]), "+f"(d[31]), "+f"(d[32]), "+f"(d[33]), "+f"(d[34]), "+f"(d[35])
    : "r"(a[0]), "r"(a[1]), "r"(a[2]), "r"(a[3]), "l"(desc), "r"(scale_d));
}
__device__ __forceinline__ void wgmma_rs_n24(float (&d)[12], const uint32_t* a, uint64_t desc, int scale_d) {
  asm volatile("{\n.reg .pred p;\nsetp.ne.b32 p, %17, 0;\n"
    "wgmma.mma_async.sync.aligned.m64n24k16.f32.bf16.bf16 "
    "{%0, %1, %2, %3, %4, %5, %6, %7, %8, %9, %10, %11}, "
    "{%12, %13, %14, %15}, %16, p, 1, 1, 1;\n}\n"
    : "+f"(d[0]), "+f"(d[1]), "+f"(d[2]), "+f"(d[3]), "+f"(d[4]), "+f"(d[5]), "+f"(d[6]), "+f"(d[7]), "+f"(d[8]), "+f"(d[9]), "+f"(d[10]), "+f"(d[11])
    : "r"(a[0]), "r"(a[1]), "r"(a[2]), "r"(a[3]), "l"(desc), "r"(scale_d));
}

__device__ __forceinline__ void mbar_init(uint32_t a, uint32_t c) { asm volatile("mbarrier.init.shared::cta.b64 [%0], %1;" :: "r"(a), "r"(c)); }
__device__ __forceinline__ void mbar_arrive(uint32_t a) { asm volatile("mbarrier.arrive.shared::cta.b64 _, [%0];" :: "r"(a) : "memory"); }
__device__ __forceinline__ void mbar_wait_trap(uint32_t a, uint32_t ph) {
  asm volatile("{\n.reg .pred p;\n.reg .u32 n;\nmov.u32 n, 0;\n"
               "W: mbarrier.try_wait.parity.shared::cta.b64 p, [%0], %1;\n@p bra D;\n"
               "add.u32 n, n, 1;\nsetp.lt.u32 p, n, 4194304;\n@p bra W;\ntrap;\nD:\n}" :: "r"(a), "r"(ph) : "memory");
}
__device__ __forceinline__ void mbar_wait(uint32_t a, uint32_t ph) {
  asm volatile("{\n.reg .pred p;\nW: mbarrier.try_wait.parity.shared::cta.b64 p, [%0], %1;\n@!p bra W;\n}" :: "r"(a), "r"(ph) : "memory");
}
__device__ __forceinline__ void mbar_wait_sleep(uint32_t a, uint32_t ph) {
  asm volatile("{\n.reg .pred p;\nW: mbarrier.test_wait.parity.shared::cta.b64 p, [%0], %1;\n@p bra D;\nnanosleep.u32 %2;\nbra W;\nD:\n}" :: "r"(a), "r"(ph), "n"(SLEEP) : "memory");
}
__device__ __forceinline__ void wg_fence() { asm volatile("wgmma.fence.sync.aligned;" ::: "memory"); }
__device__ __forceinline__ void wg_commit() { asm volatile("wgmma.commit_group.sync.aligned;" ::: "memory"); }
template <int N> __device__ __forceinline__ void wg_wait() { asm volatile("wgmma.wait_group.sync.aligned %0;" :: "n"(N) : "memory"); }
__device__ __forceinline__ float tanh_ap(float x) { float y; asm("tanh.approx.f32 %0, %1;" : "=f"(y) : "f"(x)); return y; }
__device__ __forceinline__ float ex2(float x) { float y; asm("ex2.approx.ftz.f32 %0, %1;" : "=f"(y) : "f"(x)); return y; }
__device__ __forceinline__ uint32_t pack_bf16(float lo, float hi) { uint32_t r; asm("cvt.rn.bf16x2.f32 %0, %1, %2;" : "=r"(r) : "f"(hi), "f"(lo)); return r; }
__device__ __forceinline__ float bf_lo(uint32_t v) { return __uint_as_float(v << 16); }
__device__ __forceinline__ float bf_hi(uint32_t v) { return __uint_as_float(v & 0xffff0000u); }
__device__ __forceinline__ uint32_t sub_bf16x2(uint32_t a, uint32_t b) { uint32_t r; asm("sub.rn.bf16x2 %0, %1, %2;" : "=r"(r) : "r"(a), "r"(b)); return r; }
__device__ __forceinline__ uint32_t mul_bf16x2(uint32_t a, uint32_t b) { uint32_t r; asm("mul.rn.bf16x2 %0, %1, %2;" : "=r"(r) : "r"(a), "r"(b)); return r; }
__device__ __forceinline__ uint32_t diff2(uint32_t a, uint32_t b, uint32_t t) { uint32_t r; asm("lop3.b32 %0, %1, %2, %3, 0x7e;" : "=r"(r) : "r"(a), "r"(b), "r"(t)); return r; }
__device__ __forceinline__ uint32_t or3(uint32_t a, uint32_t b, uint32_t c) { uint32_t r; asm("lop3.b32 %0, %1, %2, %3, 0xfe;" : "=r"(r) : "r"(a), "r"(b), "r"(c)); return r; }
__device__ __forceinline__ uint32_t umin2(uint32_t a, uint32_t b) { uint32_t r; asm("min.u32 %0, %1, %2;" : "=r"(r) : "r"(a), "r"(b)); return r; }
__device__ __forceinline__ uint32_t bitmask(uint32_t v, int bit) { uint32_t r; asm("bfe.s32 %0, %1, %2, 1;" : "=r"(r) : "r"(v), "r"(bit)); return r; }
__device__ __forceinline__ uint32_t nz(uint32_t w) { return w == 0u ? 0x8000u : w; }

__device__ __forceinline__ void ldg4(uint32_t* d, const uint4* p) {
  asm volatile("ld.relaxed.gpu.global.v4.b32 {%0,%1,%2,%3}, [%4];" : "=r"(d[0]), "=r"(d[1]), "=r"(d[2]), "=r"(d[3]) : "l"(p) : "memory");
}
__device__ __forceinline__ void ldg2(uint32_t* d, const void* p) {
  asm volatile("ld.relaxed.gpu.global.v2.b32 {%0,%1}, [%2];" : "=r"(d[0]), "=r"(d[1]) : "l"(p) : "memory");
}
__device__ __forceinline__ void stg4(uint4* p, uint32_t a, uint32_t b, uint32_t c, uint32_t d) {
  asm volatile("st.relaxed.gpu.global.v4.b32 [%0], {%1,%2,%3,%4};" :: "l"(p), "r"(a), "r"(b), "r"(c), "r"(d) : "memory");
}
__device__ __forceinline__ void stg2(void* p, uint32_t a, uint32_t b) {
  asm volatile("st.relaxed.gpu.global.v2.b32 [%0], {%1,%2};" :: "l"(p), "r"(a), "r"(b) : "memory");
}
__device__ __forceinline__ void sts4(uint32_t a, const uint32_t* o) { asm volatile("st.shared.v4.b32 [%0], {%1,%2,%3,%4};" :: "r"(a), "r"(o[0]), "r"(o[1]), "r"(o[2]), "r"(o[3]) : "memory"); }
__device__ __forceinline__ void lds4(uint32_t a, uint32_t* o) { asm volatile("ld.shared.v4.b32 {%0,%1,%2,%3}, [%4];" : "=r"(o[0]), "=r"(o[1]), "=r"(o[2]), "=r"(o[3]) : "r"(a) : "memory"); }
__device__ __forceinline__ void lds2(uint32_t a, uint32_t* o) { asm volatile("ld.shared.v2.b32 {%0,%1}, [%2];" : "=r"(o[0]), "=r"(o[1]) : "r"(a) : "memory"); }
__device__ __forceinline__ float rcp(float x) { float y; asm("rcp.approx.ftz.f32 %0, %1;" : "=f"(y) : "f"(x)); return y; }
__device__ __forceinline__ void sts1(uint32_t a, uint32_t v) { asm volatile("st.shared.b32 [%0], %1;" :: "r"(a), "r"(v) : "memory"); }
__device__ __forceinline__ void ldsm4(uint32_t a, uint32_t& r0, uint32_t& r1, uint32_t& r2, uint32_t& r3) {
  asm volatile("ldmatrix.sync.aligned.m8n8.x4.shared.b16 {%0,%1,%2,%3}, [%4];" : "=r"(r0), "=r"(r1), "=r"(r2), "=r"(r3) : "r"(a) : "memory");
}
__device__ __forceinline__ void ldsm4t(uint32_t a, uint32_t& r0, uint32_t& r1, uint32_t& r2, uint32_t& r3) {
  asm volatile("ldmatrix.sync.aligned.m8n8.x4.trans.shared.b16 {%0,%1,%2,%3}, [%4];" : "=r"(r0), "=r"(r1), "=r"(r2), "=r"(r3) : "r"(a) : "memory");
}
__device__ __forceinline__ void mma16c(float* d, const uint32_t* a, uint32_t b0, uint32_t b1, float c01) {
  asm("mma.sync.aligned.m16n8k16.row.col.f32.bf16.bf16.f32 {%0,%1,%2,%3}, {%4,%5,%6,%7}, {%8,%9}, {%10,%10,%10,%10};"
    : "=f"(d[0]), "=f"(d[1]), "=f"(d[2]), "=f"(d[3]) : "r"(a[0]), "r"(a[1]), "r"(a[2]), "r"(a[3]), "r"(b0), "r"(b1), "f"(c01));
}
__device__ __forceinline__ void mma8(float* c, uint32_t a0, uint32_t a1, uint32_t b0) {
  asm("mma.sync.aligned.m16n8k8.row.col.f32.bf16.bf16.f32 {%0,%1,%2,%3}, {%4,%5}, {%6}, {%0,%1,%2,%3};"
    : "+f"(c[0]), "+f"(c[1]), "+f"(c[2]), "+f"(c[3]) : "r"(a0), "r"(a1), "r"(b0));
}
__device__ __forceinline__ uint32_t lane_id() { uint32_t l; asm volatile("mov.u32 %0, %%laneid;" : "=r"(l)); return l; }
__device__ __forceinline__ float quad_sum(float v) { v += __shfl_xor_sync(~0u, v, 1); v += __shfl_xor_sync(~0u, v, 2); return v; }
__device__ __forceinline__ float quad_max(float v) { v = fmaxf(v, __shfl_xor_sync(~0u, v, 1)); v = fmaxf(v, __shfl_xor_sync(~0u, v, 2)); return v; }
template <int N> __device__ __forceinline__ void pin(float (&d)[N]) {
#pragma unroll
  for (int i = 0; i < N; i++) asm volatile("" : "+f"(d[i]) :: "memory");
}
#define SPIN_GUARD(n) if (++(n) > SPIN_MAX) break

template <int NG> __device__ __forceinline__ void publish_stats(uint4* dst, const float* y, uint32_t tag, uint32_t lane) {
  float s0 = 0.f, s1 = 0.f;
#pragma unroll
  for (int g = 0; g < NG; g++) { s0 += y[4 * g] + y[4 * g + 1]; s1 += y[4 * g + 2] + y[4 * g + 3]; }
  s0 = quad_sum(s0); s1 = quad_sum(s1);
  const float m0 = s0 * (1.f / (8 * NG)), m1 = s1 * (1.f / (8 * NG));
  float q0 = 0.f, q1 = 0.f, q2 = 0.f, q3 = 0.f;
#pragma unroll
  for (int g = 0; g < NG; g++) {
    const float a = y[4 * g] - m0, b = y[4 * g + 1] - m0, c = y[4 * g + 2] - m1, d = y[4 * g + 3] - m1;
    q0 = fmaf(a, a, q0); q1 = fmaf(b, b, q1); q2 = fmaf(c, c, q2); q3 = fmaf(d, d, q3);
  }
  q0 = quad_sum(q0 + q1); q2 = quad_sum(q2 + q3);
  if ((lane & 3) == 0)
    stg4(dst + (lane >> 2), (__float_as_uint(s0) & ~1u) | tag, __float_as_uint(q0), __float_as_uint(s1), __float_as_uint(q2));
}

__device__ __forceinline__ void put72(uint4* slab, uint32_t j, uint32_t lane, const uint32_t* v, uint32_t r0, uint32_t r1) {
  uint4* p = slab + ((9 * j + 1) >> 1) * 32;
#pragma unroll
  for (int i = 0; i < 4; i++) stg4(p + lane + i * 32, nz(v[4 * i]), v[4 * i + 1], v[4 * i + 2], v[4 * i + 3]);
  stg2((char*)((j & 1) ? p - 16 : p + 4 * 32) + lane * 8, nz(r0), r1);
}
__device__ __forceinline__ void zero_share(uint4* slab, uint32_t j, uint32_t lane) {
  uint4* p = slab + j * 144 + lane;
#pragma unroll
  for (int i = 0; i < 4; i++) stg4(p + i * 32, 0u, 0u, 0u, 0u);
  if (lane < 16) stg4(p + 128, 0u, 0u, 0u, 0u);
}

struct Maps { CUtensorMap m[7]; };

struct Ring {
  uint32_t st, ph;
  __device__ __forceinline__ void next() { if (++st == NST) { st = 0; ph ^= 1; } }
};

#define GSTAMP(i) do {} while (0)
#define STAMP(i) do {} while (0)
#define ZSTAMP(m, i) do {} while (0)

__device__ __forceinline__ void tma_box(uint32_t dst, const CUtensorMap* m, int col, int row, uint32_t bar, uint32_t expect) {
  asm volatile("{\n.reg .pred e, h;\nelect.sync _|e, 0xffffffff;\nsetp.ne.and.u32 h, %5, 0, e;\n"
               "@h mbarrier.arrive.expect_tx.shared::cta.b64 _, [%2], %5;\n"
               "@e cp.async.bulk.tensor.2d.shared::cluster.global.mbarrier::complete_tx::bytes [%0], [%1, {%3, %4}], [%2];\n}"
               :: "r"(dst), "l"(m), "r"(bar), "r"(col), "r"(row), "r"(expect) : "memory");
}

__device__ __forceinline__ void bulk_load(uint32_t dst, const void* src, uint32_t bytes, uint32_t bar, bool arm) {
  asm volatile("{\n.reg .pred e, h;\nelect.sync _|e, 0xffffffff;\nsetp.ne.and.u32 h, %4, 0, e;\n"
               "@h mbarrier.arrive.expect_tx.shared::cta.b64 _, [%3], %2;\n"
               "@e cp.async.bulk.shared::cluster.global.mbarrier::complete_tx::bytes [%0], [%1], %2, [%3];\n}"
               :: "r"(dst), "l"(src), "r"(bytes), "r"(bar), "r"((uint32_t)arm) : "memory");
}

__global__ void __launch_bounds__(384, 1) mega_kernel(
    const __grid_constant__ Maps maps, uint4* __restrict__ scratch,
    const __nv_bfloat16* __restrict__ x_in, __nv_bfloat16* __restrict__ out) {
  extern __shared__ __align__(1024) uint8_t smem[];
  const uint32_t sb = (uint32_t)__cvta_generic_to_shared(smem);
  const uint32_t full0 = sb + BARS, empty0 = full0 + 8 * NST, rem_full = empty0 + 8 * NST, park_free = rem_full + 8, kv_free = park_free + 8;
  const uint32_t c8_go = kv_free + 8, c8_done = c8_go + 8, c8_full = c8_done + 8, remo_full = c8_full + 8, piece_full = remo_full + 8, xb_done = piece_full + 8, res_full = xb_done + 8, pbar0 = res_full + 8;
  const uint32_t w = __shfl_sync(~0u, threadIdx.x >> 5, 0);
  uint32_t pair = blockIdx.x >> 1;
  if (gridDim.x == 132) {
    uint32_t smid;
    asm("mov.u32 %0, %%smid;" : "=r"(smid));
    const uint32_t tpc = smid >> 1;
    if (tpc == 60 || tpc == 61) { if (threadIdx.x == 0) { __nanosleep(20000); } return; }
    pair = tpc < 32 ? tpc : tpc >= 62 ? (tpc - 58) * 8 : 33 + (tpc - 32) / 7 * 8 + (tpc - 32) % 7;
  }
  const uint32_t rank = blockIdx.x & 1, t = (pair & 7) * 2 + rank, j = pair >> 3;
  const uint32_t sd = sb & 0x3ffff;
  const uint32_t odd = j & 1;
  uint4* const scr = scratch + t * TILE;
  {
    const uint32_t lane = lane_id(), r = lane >> 2, q = lane & 3;
    const uint32_t sl = w < 8 ? w : j, ch = w < 8 ? j : 8;
    const uint32_t* xr = (const uint32_t*)(x_in + (128 * t + 32 * (sl >> 1) + 2 * r + (sl & 1)) * 576 + 64 * ch + 2 * q);
    if (w < 8 || w == 9) {
      uint32_t v[16];
#pragma unroll
      for (int g = 0; g < 8; g++) {
        asm volatile("ld.global.nc.b32 %0, [%1];" : "=r"(v[2 * g]) : "l"(xr + 4 * g));
        asm volatile("ld.global.nc.b32 %0, [%1];" : "=r"(v[2 * g + 1]) : "l"(xr + 8 * 576 + 4 * g));
      }
      if (q == 0) {
#pragma unroll
        for (int k = 0; k < 3; k++) stg4(scr + OFF_S + (k * 8 + sl) * 96 + ch * 8 + r, 0u, 0u, 0u, 0u);
      }
      asm volatile("bar.sync 0, 384;" ::: "memory");
      asm volatile("barrier.cluster.arrive.relaxed.aligned;" ::: "memory");
      uint4* p = scr + OFF_X + sl * SLAB + 4 * ch * 32 + lane;
#pragma unroll
      for (int i = 0; i < 4; i++) stg4(p + i * 32, nz(v[4 * i]), v[4 * i + 1], nz(v[4 * i + 2]), v[4 * i + 3]);
      float y[32];
#pragma unroll
      for (int i = 0; i < 16; i++) { y[2 * i] = bf_lo(v[i]); y[2 * i + 1] = bf_hi(v[i]); }
      publish_stats<8>(scr + OFF_S + sl * 96 + ch * 8, y, 1u, lane);
    } else {
      if (threadIdx.x == 256) {
        for (int i = 0; i < NST; i++) { mbar_init(full0 + 8 * i, 1); mbar_init(empty0 + 8 * i, 16); }
        mbar_init(rem_full, 1); mbar_init(park_free, 8); mbar_init(kv_free, 8); mbar_init(c8_go, 8); mbar_init(c8_done, 2); mbar_init(c8_full, 1); mbar_init(remo_full, 64); mbar_init(piece_full, 1); mbar_init(xb_done, 8); mbar_init(res_full, 8);
        for (int i = 0; i < 8; i++) mbar_init(pbar0 + 8 * i, 4);
        asm volatile("fence.mbarrier_init.release.cluster;" ::: "memory");
      }
      __syncwarp();
      asm volatile("bar.sync 0, 384;" ::: "memory");
      asm volatile("barrier.cluster.arrive.relaxed.aligned;" ::: "memory");
    }
    asm volatile("barrier.cluster.wait.aligned;" ::: "memory");
  }

  if (w >= 8) {
    asm volatile("setmaxnreg.dec.sync.aligned.u32 24;");
    if (w == 8) {
      uint32_t dst = sb, bar = full0, ph = 1;
#pragma unroll 1
      for (int seg = 0; seg < 34; seg++) {
        const int n = seg >= 17 ? seg - 17 : seg;
        int ma, mb, ca, cb, row = 0;
        if (n < 3) { ma = mb = n == 2; ca = 72 * j + 8 * odd + (n == 0 ? 576 : 0); cb = ca + 576; }
        else if (n < 12) { ma = 3; mb = 2; ca = cb = 576 * j + 64 * (n - 3); }
        else { ma = mb = 4; ca = n == 12 ? 512 : ((j + 2 * n) & 7) * 64; cb = ((j + 2 * n + 1) & 7) * 64; row = 576 * j; }
        const bool zip = n == 0 || n == 3, solo = n == 1 || n == 2 || n == 16;
        const CUtensorMap *pa = &maps.m[ma], *pb = &maps.m[mb];
#pragma unroll 1
        for (int st = 0; st < (solo ? 5 : 9); st++) {
          const bool s0 = !zip && st > 4, s1 = zip || st >= 4;
          const int r0 = row + (zip ? 64 * st : s0 ? 128 * st - 576 : 128 * st), r1 = zip ? r0 : st == 4 ? row : r0 + 64;
          const bool rk = rank, sm = rk ? s1 : s0;
          asm volatile("{\n.reg .pred p, e, f;\n.reg .u32 n;\nelect.sync _|e, 0xffffffff;\nsetp.ne.and.u32 f, %7, 0, e;\nmov.u32 n, 0;\n"
                       "W: mbarrier.try_wait.parity.shared::cta.b64 p, [%1+48], %2;\n@p bra D;\n"
                       "add.u32 n, n, 1;\nsetp.lt.u32 p, n, 4194304;\n@p bra W;\ntrap;\n"
                       "D: @e mbarrier.arrive.expect_tx.shared::cta.b64 _, [%1], %6;\n"
                       "@f cp.async.bulk.tensor.2d.shared::cluster.global.mbarrier::complete_tx::bytes.multicast::cluster [%0], [%3, {%4, %5}], [%1], 3;\n}"
                       :: "r"(dst + rk * 8192), "r"(bar), "r"(ph), "l"(sm ? pb : pa), "r"(sm ? cb : ca), "r"(rk ? r1 : r0),
                          "r"(solo && st == 4 ? STAGE / 2 : STAGE), "r"((uint32_t)!(rk && solo && st == 4)) : "memory");
          dst += STAGE; bar += 8;
          if (bar == full0 + 8 * NST) { dst = sb; bar = full0; ph ^= 1; }
        }
      }
      {
#pragma unroll 1
        for (int i = 0; i < NST; i++) {
          mbar_wait_trap(bar + 48, ph);
          bar += 8;
          if (bar == full0 + 8 * NST) { bar = full0; ph ^= 1; }
        }
      }
    } else if (w == 9) {
      const uint32_t lane = lane_id();
      const uint32_t stg = sb + HSTG + lane * 16;
      uint32_t fph = 0;
#pragma unroll 1
      for (uint32_t layer = 0; layer < 2; layer++) {
        uint4* xb = scr + OFF_X + ((4 + layer) * 8 + j) * SLAB + 32 * 32;
        mbar_wait_sleep(c8_go, layer);
        int n = 0;
        while (true) {
          if (lane == 0) asm volatile("mbarrier.arrive.expect_tx.shared::cta.b64 _, [%0], 18432;" :: "r"(c8_full) : "memory");
          __syncwarp();
#pragma unroll 1
          for (uint32_t s = 0; s < 9; s++)
            bulk_load(sb + HSTG + s * 2048, s < 8 ? scr + OFF_P + (j + s * 8) * SLAB + 32 * 32 : xb, 2048, c8_full, false);
          mbar_wait(c8_full, fph); fph ^= 1;
          uint32_t bad = 0;
#pragma unroll 8
          for (int s = 0; s < 32; s++) { uint32_t v; asm volatile("ld.shared.b32 %0, [%1];" : "=r"(v) : "r"(stg + s * 512) : "memory"); bad |= v ^ (1 - layer); }
          if (__all_sync(~0u, (bad & 1u) == 0u)) break;
          __nanosleep(300);
          SPIN_GUARD(n);
        }
        asm volatile("bar.arrive 7, 96;" ::: "memory");
        float s0 = 0.f, s1 = 0.f;
#pragma unroll 1
        for (int g = 0; g < 8; g++) {
          const uint32_t a = stg + (g >> 1) * 512 + (g & 1) * 8;
          float a0 = 0.f, a1 = 0.f, a2 = 0.f, a3 = 0.f;
#pragma unroll 1
          for (int b = 0; b < 3; b++) {
            uint32_t v[6];
#pragma unroll
            for (int s = 0; s < 3; s++) lds2(a + (3 * b + s) * 2048, v + 2 * s);
#pragma unroll
            for (int s = 0; s < 3; s++) { a0 += bf_lo(v[2 * s]); a1 += bf_hi(v[2 * s]); a2 += bf_lo(v[2 * s + 1]); a3 += bf_hi(v[2 * s + 1]); }
          }
          sts1(a + 18432, pack_bf16(a0, a1)); sts1(a + 18436, pack_bf16(a2, a3));
          s0 += a0 + a1; s1 += a2 + a3;
        }
        __syncwarp();
        if (lane == 0) mbar_arrive(c8_done);
        s0 = quad_sum(s0); s1 = quad_sum(s1);
        float q0 = 0.f, q1 = 0.f;
        const uint32_t ln = lane_id();
#pragma unroll 1
        for (uint32_t i = 0; i < 4; i++) {
          uint32_t x[4];
          lds4(stg + 18432 + i * 512, x);
          stg4(xb + i * 32 + ln, 0u, 0u, 0u, 0u);
          if (layer == 0) {
            stg4(xb - 3 * 8 * SLAB + i * 32 + ln, nz(x[0]), x[1], x[2], x[3]);
#pragma unroll
            for (int e = 0; e < 4; e++) {
              const float m = (e & 1) ? s1 : s0, c = fmaf(m, -1.f / 64, bf_lo(x[e])), d = fmaf(m, -1.f / 64, bf_hi(x[e]));
              if (e & 1) q1 = fmaf(c, c, fmaf(d, d, q1)); else q0 = fmaf(c, c, fmaf(d, d, q0));
            }
          } else {
            uint32_t* o = (uint32_t*)(out + (128 * t + 32 * (j >> 1) + 2 * (ln >> 2) + (j & 1)) * 576 + 512 + 16 * i + 2 * (ln & 3));
            o[0] = x[0]; o[8 * 576] = x[1]; o[4] = x[2]; o[8 * 576 + 4] = x[3];
          }
        }
        if (layer == 0) {
          q0 = quad_sum(q0); q1 = quad_sum(q1);
          if ((ln & 3) == 0) stg4(scr + OFF_S + j * 96 + 64 + (ln >> 2), __float_as_uint(s0) & ~1u, __float_as_uint(q0), __float_as_uint(s1), __float_as_uint(q1));
        }
      }
    } else {
      auto phase2_duties = [&](uint32_t layer) {
        const uint32_t lane = lane_id();
        asm volatile("bar.sync 7, 96;" ::: "memory");
        if (w == 11) {
          if (layer == 0) {
#pragma unroll 1
            for (uint32_t k = 0; k < 6; k++) stg4(scr + OFF_S + (k * 4 + (lane >> 3)) * 96 + j * 8 + (lane & 7), 1u, 0u, 0u, 0u);
          }
          __syncwarp();
          if (lane == 0) mbar_arrive(c8_done);
        }
        mbar_wait_sleep(res_full, layer);
#pragma unroll 1
        for (uint32_t i = 0; i < 4; i++) {
          uint4* z = scr + OFF_X + ((4 + layer) * 8 + (w - 10) * 4 + i) * SLAB + 4 * j * 32 + lane;
#pragma unroll
          for (int k = 0; k < 4; k++) stg4(z + k * 32, 0u, 0u, 0u, 0u);
          __nanosleep(300);
        }
      };
#pragma unroll 1
      for (uint32_t layer = 0; layer < 2; layer++) {
        if (w == 10) {
          if (layer == 0) {
            const uint32_t lane = lane_id();
            const uint32_t p = t >> 2;
            tma_box(sb + PARK, &maps.m[p == 3 ? 6 : 5], 72 * j + (odd ? 0 : 64) + (p < 2 ? 576 * (p + 1) : 0), 144 * (t & 3), piece_full, 2304);
            mbar_wait(piece_full, 0);
            asm volatile("{\n.reg .pred e;\nelect.sync _|e, 0xffffffff;\n@e cp.async.bulk.global.shared::cta.bulk_group [%0], [%1], 2304;\n}\n"
                         "cp.async.bulk.commit_group;\ncp.async.bulk.wait_group 0;\nfence.proxy.async;"
                         :: "l"(scratch + OFF_R + j * 2304 + t * 144), "r"(sb + PARK) : "memory");
            __syncwarp();
            if (lane < 16) asm volatile("st.release.gpu.global.b32 [%0], 1;" :: "l"((uint32_t*)(scratch + OFF_F + (lane * 8 + j) * 8) + t) : "memory");
            uint32_t* fl = (uint32_t*)(scratch + OFF_F + (t * 8 + j) * 8) + (lane & 15);
            uint32_t v;
            int n = 0;
            while (true) {
              asm volatile("ld.acquire.gpu.global.b32 %0, [%1];" : "=r"(v) : "l"(fl) : "memory");
              if (__all_sync(~0u, v != 0u)) break;
              __nanosleep(100);
              SPIN_GUARD(n);
            }
            asm volatile("fence.proxy.async;\nst.relaxed.gpu.global.b32 [%0], 0;" :: "l"(fl) : "memory");
          } else {
            mbar_wait_sleep(park_free, 0);
          }
          bulk_load(sb + REM, scratch + OFF_R + j * 2304, 36864, rem_full, true);
        }
        mbar_wait_sleep(rem_full, layer);
#pragma unroll 1
        for (uint32_t b = 0; b < 5; b++) {
          const uint32_t blk = sb + REM + 27648 + b * 2048, k = (w - 10) * 32 + lane_id(), rr = k & 7;
          const uint32_t dst = blk + ((k >> 3) & 1) * 1024 + rr * 128 + (((k >> 4) ^ rr) << 4);
          uint32_t v[8];
          lds4(blk + k * 16, v); lds4(blk + 1024 + k * 16, v + 4);
          asm volatile("bar.sync 3, 64;" ::: "memory");
          sts4(dst, v); sts4(dst ^ 64, v + 4);
        }
        asm volatile("fence.proxy.async.shared::cta;" ::: "memory");
        mbar_arrive(remo_full);
        if (layer) { phase2_duties(0); mbar_wait_sleep(kv_free, 0); }
        if (t > 0) {
          const uint32_t lane = lane_id(), r = lane >> 2, q = lane & 3;
#pragma unroll 1
          for (uint32_t pc = 0; pc < 3; pc++) {
            uint4* hp = scr + OFF_H + ((layer * 8 + j) * 2 + (w - 10)) * 192 + pc * 64 + lane;
            uint32_t hl[8];
            int n = 0;
            hl[4] = 1u;
            while (true) {
              ldg4(hl, hp);
              if (pc < 2) ldg4(hl + 4, hp + 32);
              if (__all_sync(~0u, hl[0] != 0u && hl[4] != 0u)) break;
              __nanosleep(100);
              SPIN_GUARD(n);
            }
            const uint32_t dst = sb + KVS + (w - 10) * 10368 + r * 144 + q * 4;
            if (pc < 2) {
#pragma unroll
              for (int g = 0; g < 8; g++) sts1(dst + pc * 20736 + odd * 16 + g * 16, hl[g]);
              stg4(hp + 32, 0u, 0u, 0u, 0u);
            } else {
              sts1(dst + (odd ? 0 : 128), hl[0]); sts1(dst + 20736 + (odd ? 0 : 128), hl[1]);
            }
            stg4(hp, 0u, 0u, 0u, 0u);
          }
        }
        asm volatile("bar.arrive 1, 192;" ::: "memory");
        mbar_wait_sleep(xb_done, layer);
#pragma unroll 1
        for (uint32_t i = 0; i < 8; i++) {
          zero_share(scr + OFF_X + ((w - 10) * 16 + layer * 8 + i) * SLAB, j, lane_id());
          __nanosleep(500);
        }
      }
      phase2_duties(1);
    }
  } else {
    asm volatile("setmaxnreg.inc.sync.aligned.u32 240;");
    const bool lead = lane_id() == 0;
    Ring rg{0, 0};
    uint32_t prev = 0;
    uint32_t X[144];
    float rs0, rs1;
    uint32_t mean0, mean1;
    const bool lead2 = lane_id() < 2;
    uint32_t empty_at;
    asm volatile("mapa.shared::cluster.u32 %0, %1, %2;" : "=r"(empty_at) : "r"(empty0), "r"(lane_id() & 1));
    auto release = [&](uint32_t st) { if (lead2) asm volatile("mbarrier.arrive.shared::cluster.b64 _, [%0];" :: "r"(empty_at + st * 8) : "memory"); };
    auto load_kb = [&](int kb, const uint4* src, const char* lo, uint32_t hoff) {
#pragma unroll
      for (int k = 4 * kb; k < 4 * kb + 4; k++) {
        if (k % 9 == 4) { ldg2(X + 4 * k, lo + k * 512); ldg2(X + 4 * k + 2, lo + hoff + k * 512); }
        else ldg4(X + 4 * k, src + k * 32);
      }
    };
    auto next_kb = [&](bool center, int kb, const uint4* src, const char* lo, uint32_t hoff) {
      int n = 0;
      while (true) {
        uint32_t m = umin2(umin2(X[16 * kb], X[16 * kb + 4]), umin2(X[16 * kb + 8], X[16 * kb + 12]));
        if (kb & 1) m = umin2(m, X[16 * kb + 4 * (kb >> 1) + 2]);
        if (__all_sync(~0u, m != 0u)) break;
        SPIN_GUARD(n);
        load_kb(kb, src, lo, hoff);
      }
      if (kb + (center ? GD : GO) < 9) load_kb(kb + (center ? GD : GO), src, lo, hoff);
      if (center) {
#pragma unroll
        for (int i = 16 * kb; i < 16 * kb + 16; i++) X[i] = sub_bf16x2(X[i], (i & 1) ? mean1 : mean0);
      }
    };
#pragma unroll 1
    for (uint32_t hf = 0; hf < 4; hf++) {
      const uint32_t layer = hf >> 1;
      const bool ffn = hf & 1;
      const uint32_t tag = 1 - layer;
      uint4* const xbase = scr + OFF_X + (layer * 8 + w) * SLAB;
      float aA[32], aB[32];
      {
        const uint32_t lane = lane_id(), r = lane >> 2, q = lane & 3;
        const uint4* src = xbase + (ffn ? 32 * SLAB : 0) + lane;
        const char* lo = (const char*)src - (ffn ? lane * 8 : 0);
        const uint32_t hoff = ffn ? 256 : 8;
        uint32_t s[3][4];
        const uint4* p = scr + OFF_S + ((ffn ? 16 : 0) + w) * 96 + q * 8 + r;
        const bool third = !ffn && q == 0;
        int n = 0;
        s[2][0] = tag; s[2][1] = s[2][2] = s[2][3] = 0u;
        STAMP(ffn * 16 + 0);
        while (true) {
          ldg4(s[0], p); ldg4(s[1], p + 32);
          if (third) ldg4(s[2], p + 64);
          if (__all_sync(~0u, ((diff2(s[0][0], s[1][0], tag) | diff2(s[2][0], s[2][0], tag)) & 1u) == 0u)) break;
          SPIN_GUARD(n);
        }
        STAMP(ffn * 16 + 1);
        ZSTAMP(1 + ffn, 0);
        GSTAMP(14 + ffn);
#pragma unroll
        for (int kb = 0; kb < GD; kb++) load_kb(kb, src, lo, hoff);
        float t0 = 0.f, t1 = 0.f;
#pragma unroll
        for (int i = 0; i < 3; i++) { t0 += __uint_as_float(s[i][0]); t1 += __uint_as_float(s[i][2]); }
        const float m0 = quad_sum(t0) * (1.f / 576), m1 = quad_sum(t1) * (1.f / 576);
        const float cnt = ffn ? 72.f : 64.f, inv = ffn ? 1.f / 72 : 1.f / 64;
        float v0 = 0.f, v1 = 0.f;
#pragma unroll
        for (int i = 0; i < 3; i++) {
          const float c = (i < 2 || third) ? cnt : 0.f;
          const float d0 = fmaf(__uint_as_float(s[i][0]), inv, -m0), d1 = fmaf(__uint_as_float(s[i][2]), inv, -m1);
          v0 += fmaf(d0 * d0, c, __uint_as_float(s[i][1])); v1 += fmaf(d1 * d1, c, __uint_as_float(s[i][3]));
        }
        rs0 = rsqrtf(fmaf(quad_sum(v0), 1.f / 576, 1e-5f)); rs1 = rsqrtf(fmaf(quad_sum(v1), 1.f / 576, 1e-5f));
        mean0 = pack_bf16(m0, m0); mean1 = pack_bf16(m1, m1);
#pragma unroll
        for (int kb = 0; kb < 9; kb++) {
          next_kb(true, kb, src, lo, hoff);
          ZSTAMP(1 + ffn, 1 + 3 * kb);
          mbar_wait(full0 + rg.st * 8, rg.ph);
          ZSTAMP(1 + ffn, 2 + 3 * kb);
          const uint64_t desc = DESC_HI | ((sd + rg.st * STAGE) >> 4);
          wg_fence();
#pragma unroll
          for (int i = 0; i < 4; i++) wgmma_rs_n64(aA, X + 4 * (4 * kb + i), desc + i * 128, kb + i != 0);
          if (SPLITZ && kb == 8) { wg_commit(); wg_wait<1>(); wg_fence(); }
#pragma unroll
          for (int i = 0; i < 4; i++) wgmma_rs_n64(aB, X + 4 * (4 * kb + i), desc + 512 + i * 128, kb + i != 0);
          wg_commit();
          wg_wait<1>();
          ZSTAMP(1 + ffn, 3 + 3 * kb);
          if (kb > 0) release(prev);
          prev = rg.st; rg.next();
        }
        if (!SPLITZ) wg_wait<0>();
        ZSTAMP(1 + ffn, 28);
        ZSTAMP(4, 0);
        STAMP(ffn * 16 + 2);
      }
      if (!ffn) {
      const uint32_t lane = lane_id(), r = lane >> 2, q = lane & 3;
      const uint32_t kvrow = sb + KVS + (w & 1) * 10368 + (16 * (w >> 1)) * 144;
      uint32_t Q[18], Km[3][8], Ke[3][4];
      const bool edge = (t == 0 && w < 2);
      const uint32_t row0 = edge ? sb + KVS + 8 * 144 : kvrow + (lane & 7) * 144, row1 = kvrow + (8 + (lane & 7)) * 144;
      {
        const uint32_t dst = kvrow + (8 + r) * 144 + q * 4 + odd * 16, dstr = dst + (odd ? -16 : 128);
        const bool edge_out = w >= 6 && t < 15;
        uint4* const hp = scr + TILE + OFF_H + ((layer * 8 + j) * 2 + (w & 1)) * 192 + lane;
        auto put_kv = [&](float (&a)[32], int part) {
          pin(a);
          uint32_t hl[8];
#pragma unroll
          for (int g = 0; g < 8; g++) {
            hl[g] = pack_bf16(a[4 * g + 2] * rs1, a[4 * g + 3] * rs1);
            sts1(dst + part * 20736 + g * 16, pack_bf16(a[4 * g] * rs0, a[4 * g + 1] * rs0)); sts1(dst + part * 20736 + 8 * 144 + g * 16, hl[g]);
          }
          if (edge_out) { stg4(hp + part * 64, nz(hl[0]), hl[1], hl[2], hl[3]); stg4(hp + part * 64 + 32, nz(hl[4]), hl[5], hl[6], hl[7]); }
        };
        put_kv(aA, 0);
        wg_wait<0>();
        release(prev);
        float aR[12];
        mbar_wait(rem_full, layer);
        const uint64_t dr = DESC_REM | ((sd + REM) >> 4);
        wg_fence();
#pragma unroll
        for (int s = 0; s < 36; s++) {
          wgmma_rs_n24(aR, X + 4 * s, dr + s * 16, s != 0);
          if (s == 4) put_kv(aB, 1);
        }
        wg_commit();
#pragma unroll
        for (int kb = 0; kb < 9; kb++) {
          if (kb == HOFF1 && w < 4) asm volatile("bar.sync 4, 256;" ::: "memory");
          if (kb == 8 && HOFF1 < 9 && w >= 4) asm volatile("bar.arrive 4, 256;" ::: "memory");
          if (!(kb & 1)) mbar_wait(full0 + rg.st * 8, rg.ph);
          const uint64_t desc = DESC_HI | ((sd + rg.st * STAGE + (kb & 1) * 8192) >> 4);
          wg_fence();
#pragma unroll
          for (int i = 0; i < 4; i++) wgmma_rs_n64(aB, X + 4 * (4 * kb + i), desc + i * 128, kb + i != 0);
          wg_commit();
          wg_wait<1>();
          if (kb > 0 && !(kb & 1)) release(prev);
          if ((kb & 1) || kb == 8) { prev = rg.st; rg.next(); }
          if (kb == 0) {
            pin(aR);
            const uint32_t k1 = pack_bf16(aR[2] * rs1, aR[3] * rs1), v1 = pack_bf16(aR[6] * rs1, aR[7] * rs1);
            if (edge_out) stg4(hp + 128, nz(k1), v1, 0u, 0u);
            sts1(dstr, pack_bf16(aR[0] * rs0, aR[1] * rs0)); sts1(dstr + 8 * 144, k1);
            sts1(dstr + 20736, pack_bf16(aR[4] * rs0, aR[5] * rs0)); sts1(dstr + 20736 + 8 * 144, v1);
            Q[16] = pack_bf16(aR[8], aR[9]); Q[17] = pack_bf16(aR[10], aR[11]);
            if (w < 4) asm volatile("bar.arrive 2, 256;" ::: "memory");
          }
          if (kb == KLD) {
            if (w < 4) asm volatile("bar.sync 1, 192;" ::: "memory");
            else asm volatile("bar.sync 2, 256;" ::: "memory");
#pragma unroll
            for (int nt = 0; nt < 3; nt++) {
              const uint32_t ra = (nt == 0 ? row0 : row1 + (nt - 1) * 8 * 144);
              ldsm4(ra + odd * 16 + (lane >> 3) * 16, Km[nt][0], Km[nt][1], Km[nt][2], Km[nt][3]);
              ldsm4(ra + odd * 16 + 64 + (lane >> 3) * 16, Km[nt][4], Km[nt][5], Km[nt][6], Km[nt][7]);
              ldsm4(ra + (odd ? 0 : 32) + (lane >> 3) * 32, Ke[nt][0], Ke[nt][1], Ke[nt][2], Ke[nt][3]);
            }
            const uint32_t ge = (2u << q) - 1, le = 0xfu << q, on = edge ? 0u : ~0u;
            const uint32_t bits = odd ? 0xfu | ((le & 0xfu) << 4) | (ge << 8) : ge | 0xf0u | (le << 8);
#pragma unroll
            for (int h = 0; h < 4; h++) {
              const uint32_t ma = bitmask(bits, h), mb = bitmask(bits, 4 + h), mc = bitmask(bits, 8 + h);
              Km[0][2 * h] &= ma & on; Km[0][2 * h + 1] &= mb & on; Ke[0][h] &= mc & on;
#pragma unroll
              for (int nt = 1; nt < 3; nt++) { Km[nt][2 * h] &= ma; Km[nt][2 * h + 1] &= mb; Ke[nt][h] &= mc; }
            }
          }
        }
        wg_wait<0>();
        release(prev);
        pin(aB);
        STAMP(3);
#pragma unroll
        for (int i = 0; i < 16; i++) Q[i] = pack_bf16(aB[2 * i], aB[2 * i + 1]);
      }
      {
        uint32_t V01[12][2], V2[12];
        const uint32_t rv = ((lane & 8) ? row1 : row0) + 20736, rw = row1 + 8 * 144 + 20736;
#pragma unroll
        for (int i = 0; i < 4; i++) ldsm4t(rv + odd * 16 + i * 32 + (lane >> 4) * 16, V01[2 * i][0], V01[2 * i][1], V01[2 * i + 1][0], V01[2 * i + 1][1]);
#pragma unroll
        for (int i = 0; i < 2; i++) ldsm4t(rv + (odd ? 0 : 32) + i * 64 + (lane >> 4) * 32, V01[8 + 2 * i][0], V01[8 + 2 * i][1], V01[9 + 2 * i][0], V01[9 + 2 * i][1]);
        ldsm4t(rw + odd * 16 + (lane >> 3) * 16, V2[0], V2[1], V2[2], V2[3]);
        ldsm4t(rw + odd * 16 + 64 + (lane >> 3) * 16, V2[4], V2[5], V2[6], V2[7]);
        ldsm4t(rw + (odd ? 0 : 32) + (lane >> 3) * 32, V2[8], V2[9], V2[10], V2[11]);
        const bool up0 = 2 * q > r, up1 = 2 * q + 1 > r;
        const uint32_t upm = (up0 ? 0xffffu : 0u) | (up1 ? 0xffff0000u : 0u);
        const float c0 = 0.23570226039551584f * 1.4426950408889634f * rs0, c1 = 0.23570226039551584f * 1.4426950408889634f * rs1;
        const float masked = edge ? -1e9f * 1.4426950408889634f * rcp(c0) : 0.f;
        uint32_t Om[16], Oe[8];
#pragma unroll
        for (int h = 0; h < 4; h++) {
          const uint32_t e0 = odd ? Q[(4 * h + 16) % 18] : Q[4 * h + 4], e1 = odd ? Q[(4 * h + 17) % 18] : Q[4 * h + 5];
          float S[3][4];
#pragma unroll
          for (int nt = 0; nt < 3; nt++) {
            mma16c(S[nt], Q + 4 * h, Km[nt][2 * h], Km[nt][2 * h + 1], nt == 0 ? masked : 0.f);
            mma8(S[nt], e0, e1, Ke[nt][h]);
          }
          const float s00 = up0 ? S[0][0] : S[1][0], s01 = up1 ? S[0][1] : S[1][1];
          const float s10 = up0 ? S[1][2] : S[2][2], s11 = up1 ? S[1][3] : S[2][3];
          const float m0 = quad_max(fmaxf(s00, s01)) * c0, m1 = quad_max(fmaxf(s10, s11)) * c1;
          const float p00 = ex2(fmaf(s00, c0, -m0)), p01 = ex2(fmaf(s01, c0, -m0)), p10 = ex2(fmaf(s10, c1, -m1)), p11 = ex2(fmaf(s11, c1, -m1));
          const float i0 = rcp(quad_sum(p00 + p01)), i1 = rcp(quad_sum(p10 + p11));
          const uint32_t p0 = pack_bf16(p00 * i0, p01 * i0), p1 = pack_bf16(p10 * i1, p11 * i1);
          const uint32_t pf[4] = {p0 & upm, 0u, p0 & ~upm, p1 & upm};
#pragma unroll
          for (int gi = 0; gi < 3; gi++) {
            const int g = gi < 2 ? 2 * h + gi : 8 + h;
            float o[4];
            mma16c(o, pf, V01[g][0], V01[g][1], 0.f);
            mma8(o, 0u, p1 & ~upm, V2[g]);
            uint32_t* d = gi < 2 ? Om + 2 * g : Oe + 2 * h;
            d[0] = pack_bf16(o[0], o[1]); d[1] = pack_bf16(o[2], o[3]);
          }
        }
#pragma unroll
        for (int h = 0; h < 4; h++)
#pragma unroll
          for (int e = 0; e < 2; e++) {
            if (h > 0 && !odd && q < h) Om[4 * h + e] = Oe[2 * h - 2 + e];
            if (h < 3 && odd && q > h) Om[4 * h + 2 + e] = Oe[2 * h + 2 + e];
          }
        STAMP(4);
        put72(xbase + 16 * SLAB, j, lane, Om, odd ? Oe[0] : Oe[6], odd ? Oe[1] : Oe[7]);
      }
      if (lane == 0) asm volatile("st.relaxed.gpu.global.b32 [%0], %1;" :: "l"(scr + OFF_S + (8 + w) * 96 + j * 8), "r"(tag) : "memory");
      {
        uint32_t res[18];
        const uint4* p = xbase + ((9 * j + 1) >> 1) * 32 + lane;
#pragma unroll
        for (int i = 0; i < 4; i++) ldg4(res + 4 * i, p + i * 32);
        ldg2(res + 16, odd ? (const char*)(p - 32) + 8 : (const char*)(p + 4 * 32));
        const uint4* src = xbase + 16 * SLAB + lane;
        {
          const uint4* fp = scr + OFF_S + (8 + w) * 96 + (lane & 7) * 8;
          int n = 0;
          mbar_wait(remo_full, layer);
          STAMP(8);
          while (true) {
            uint32_t f;
            asm volatile("ld.relaxed.gpu.global.b32 %0, [%1];" : "=r"(f) : "l"(fp) : "memory");
            if (__all_sync(~0u, f == tag)) break;
            SPIN_GUARD(n);
          }
          STAMP(9);
        }
        if (HOFF3 < 9 && w < 4) asm volatile("bar.sync 6, 256;" ::: "memory");
#pragma unroll
        for (int kb = 0; kb < GO; kb++) load_kb(kb, src, (const char*)src - lane * 8, 256);
        float acc[36];
#pragma unroll
        for (int i = 0; i < 18; i++) { acc[2 * i] = bf_lo(res[i]); acc[2 * i + 1] = bf_hi(res[i]); }
#pragma unroll
        for (int kb = 0; kb < 9; kb++) {
          next_kb(false, kb, src, (const char*)src - lane * 8, 256);
          if (kb == HOFF3 && w >= 4) asm volatile("bar.arrive 6, 256;" ::: "memory");
          if (!(kb & 1)) mbar_wait(full0 + rg.st * 8, rg.ph);
          const uint32_t base = sd + rg.st * STAGE + (kb & 1) * 8192;
          const uint64_t d0 = DESC_HI | ((base >> 4) + (((sd + REM + 27648 + (kb >> 1) * 2048 + (kb & 1) * 64 - base) >> 4) << 16));
          wg_fence();
#pragma unroll
          for (int i = 0; i < 4; i++) wgmma_rs_n72(acc, X + 4 * (4 * kb + i), d0 - (uint64_t)(i * ((127u << 16) - 128u)), 1);
          wg_commit();
          wg_wait<1>();
          if (kb > 0 && !(kb & 1)) release(prev);
          if ((kb & 1) || kb == 8) { prev = rg.st; rg.next(); }
        }
        wg_wait<0>();
        release(prev);
        pin(acc);
        STAMP(10);
#pragma unroll
        for (int i = 0; i < 18; i++) res[i] = pack_bf16(acc[2 * i], acc[2 * i + 1]);
        put72(xbase + 32 * SLAB, j, lane, res, res[16], res[17]);
        publish_stats<9>(scr + OFF_S + (16 + w) * 96 + j * 8, acc, tag, lane);
      }
      continue;
      }
      const uint32_t hp = sb + PARK + w * 512 + lane_id() * 16;
      auto pack8 = [&](float (&a)[32], int p, uint32_t* o) {
#pragma unroll
        for (int e = 0; e < 8; e++) asm volatile("" : "+f"(a[8 * p + e]) :: "memory");
#pragma unroll
        for (int e = 0; e < 4; e++) o[e] = pack_bf16(a[8 * p + 2 * e], a[8 * p + 2 * e + 1]);
      };
      const float ka0 = 0.7978845608028654f * rs0, kb0 = 0.044715f * ka0 * rs0 * rs0, ku0 = 0.5f * rs0 * rs0;
      const float ka1 = 0.7978845608028654f * rs1, kb1 = 0.044715f * ka1 * rs1 * rs1, ku1 = 0.5f * rs1 * rs1;
      auto packu8 = [&](int p, uint32_t* o) {
#pragma unroll
        for (int e = 0; e < 8; e++) asm volatile("" : "+f"(aA[8 * p + e]) :: "memory");
#pragma unroll
        for (int e = 0; e < 4; e++) o[e] = pack_bf16(aA[8 * p + 2 * e] * ((e & 1) ? ku1 : ku0), aA[8 * p + 2 * e + 1] * ((e & 1) ? ku1 : ku0));
      };
      auto geglu8 = [&](int p, uint32_t* u) {
#pragma unroll
        for (int e = 0; e < 8; e++) asm volatile("" : "+f"(aB[8 * p + e]) :: "memory");
        float h[8];
#pragma unroll
        for (int e = 0; e < 8; e++) {
          const float g = aB[8 * p + e];
          h[e] = fmaf(g, tanh_ap(g * fmaf(g * g, (e & 2) ? kb1 : kb0, (e & 2) ? ka1 : ka0)), g);
        }
#pragma unroll
        for (int e = 0; e < 4; e++) u[e] = mul_bf16x2(pack_bf16(h[2 * e], h[2 * e + 1]), u[e]);
      };
      auto box = [&](int b, auto&& filler) {
        const int kb = b < 9 ? b : b - 9;
        if (!(b & 1)) { if ((TRAPB >> (b >> 1)) & 1) mbar_wait_trap(full0 + rg.st * 8, rg.ph); else mbar_wait(full0 + rg.st * 8, rg.ph); }
        const uint64_t desc = DESC_HI | ((sd + rg.st * STAGE + (b & 1) * 8192) >> 4);
        wg_fence();
#pragma unroll
        for (int i = 0; i < 4; i++) {
          if (b < 9) wgmma_rs_n64(aA, X + 4 * (4 * kb + i), desc + i * 128, kb + i != 0);
          else wgmma_rs_n64(aB, X + 4 * (4 * kb + i), desc + i * 128, kb + i != 0);
          if (i == FPOS) filler();
        }
        wg_commit();
        if (b & 1) { prev = rg.st; rg.next(); } else { wg_wait<1>(); release(prev); }
      };
      auto nop = [] {};
      auto step = [&](int st, auto&& filler) { box(2 * st, nop); box(2 * st + 1, filler); };
#pragma unroll
      for (int p = 0; p < 4; p++) { uint32_t o[4]; packu8(p, o); sts4(hp + p * 4096, o); }
      box(0, nop);
      if (lead) mbar_arrive(xb_done);
#pragma unroll 1
      for (int c = 1;; c++) {
        const uint32_t hc = hp + c * 4 * 4096;
#pragma unroll
        for (int b = 1; b < 18; b++) box(b, [&] {
          if ((b & 1) && b < 8) { uint32_t o[4]; const uint32_t a = hc - (4 - (b >> 1)) * 4096; lds4(a, o); geglu8(b >> 1, o); sts4(a, o); }
          if ((b & 1) && b > 10) { uint32_t o[4]; packu8((b - 11) >> 1, o); if (c < 8) sts4(hc + ((b - 11) >> 1) * 4096, o); } });
        ZSTAMP(4, c);
        if (c == 8) break;
        box(0, nop);
      }
      wg_wait<0>();
      STAMP(21);
      GSTAMP(19);
      auto unpark = [&](int kb) {
#pragma unroll
        for (int s = 4 * kb; s < 4 * kb + 4; s++) lds4(hp + s * 4096, X + 4 * s);
      };
      unpark(0);
      uint32_t U[16];
#pragma unroll
      for (int p = 0; p < 4; p++) packu8(p, U + 4 * p);
#pragma unroll
      for (int b = 0; b < 8; b++) box(b, [&] {
        if (b < 7) unpark(b + 1);
        if (b & 1) {
          geglu8(b >> 1, U + 2 * (b - 1));
          if (rg.ph > 1) sts4(hp, U + 2 * (b - 1));
#pragma unroll
          for (int i = 0; i < 4; i++) X[128 + 2 * (b - 1) + i] = U[2 * (b - 1) + i];
        } });
      STAMP(24);
      if (layer == 0 && lead) mbar_arrive(park_free);
      const uint32_t lane2 = lane_id();
      uint4* const pw = scr + OFF_P + (j * 8 + w) * SLAB + lane2;
      const uint4* const pr = scr + OFF_P + w * SLAB + 4 * j * 32 + lane2;
      auto put_part = [&](float (&a)[32], int p, uint32_t chunk) {
        uint32_t o[4];
        pack8(a, p, o);
        stg4(pw + (chunk * 4 + p) * 32, (o[0] & ~1u) | tag, o[1], o[2], o[3]);
      };
      uint4* const xb = xbase + 32 * SLAB + 4 * j * 32;
      auto slot = [&](int p) { return sb + w * 2048 + (p < 3 ? PARK + p * 16384 : KVS + (p - 3) * 16384); };
      auto fetch = [&](int p) {
        bulk_load(slot(p), p ? scr + OFF_P + (((j - p) & 7) * 8 + w) * SLAB + 4 * j * 32 : xb, 2048, p ? pbar0 + w * 8 : res_full, true);
      };
#pragma unroll 1
      for (int sp = 0;; sp++) {
        const uint32_t ca = sp == 0 ? 8 : ((j + 2 * sp) & 7), cb = (j + 2 * sp + 1) & 7;
        if (C8 == 1 && sp == 1 && lead) mbar_arrive(c8_go);
#pragma unroll
        for (int st = 4; st < 9; st++) step(st, [&] {
          if (st == 5 || st == 6) { put_part(aA, 2 * (st - 5), ca); put_part(aA, 2 * (st - 5) + 1, ca); }
          if (st == 8 && sp > 0) { if (sp == 3) mbar_wait(c8_done, layer); fetch(2 * sp - 2); } });
        STAMP(25 + sp);
        if (sp == 3) break;
        if (C8 == 0 && sp == 0 && lead) mbar_arrive(c8_go);
#pragma unroll
        for (int st = 0; st < 4; st++) step(st, [&] {
          if (st < 2) { put_part(aB, 2 * st, cb); put_part(aB, 2 * st + 1, cb); }
          if (st == 3 && sp > 0) fetch(2 * sp - 1); });
      }
      auto load_p = [&](int p, uint32_t* d) {
#pragma unroll
        for (int i = 0; i < 4; i++) ldg4(d + 4 * i, pr + ((j - p) & 7) * 8 * SLAB + i * 32);
      };
#pragma unroll
      for (int b = 0; b < 9; b++) {
        if (b == HOFF2 && w < 4) asm volatile("bar.sync 5, 256;" ::: "memory");
        box(b, [&] {
          if (b == 1) {
#pragma unroll
            for (int p = 0; p < 4; p++) put_part(aB, p, (j + 7) & 7);
          }
          if (b == 3) { load_p(5, X); load_p(6, X + 16); }
          if (b == 7 && EXP != 1) load_p(7, X + 32); });
        if (b == 7 && HOFF2 < 9 && w >= 4) asm volatile("bar.arrive 5, 256;" ::: "memory");
      }
      mbar_wait(res_full, layer);
      mbar_wait(pbar0 + w * 8, layer);
#pragma unroll
      for (int p = 1; p < 5; p++)
#pragma unroll
        for (int i = 0; i < 4; i++) lds4(slot(p) + lane2 * 16 + i * 512, X + 48 + 16 * p + 4 * i);
#pragma unroll
      for (int i = 0; i < 4; i++) {
        const bool split = j == 2 * i + 1;
        const uint32_t a = slot(0) + i * 512 + (split ? lane2 * 8 : lane2 * 16);
        lds2(a, X + 48 + 4 * i); lds2(a + (split ? 256 : 8), X + 50 + 4 * i);
      }
      wg_wait<0>();
      release(rg.st); rg.next();
      pin(aA);
      STAMP(22);
      GSTAMP(20);
      {
        const uint32_t lane = lane2, r = lane >> 2, q = lane & 3;
        const uint32_t eye = r == 2 * q ? 0x3f80u : r == 2 * q + 1 ? 0x3f800000u : 0u;
        auto bad = [&](const uint32_t* d) { return diff2(d[0], d[4], tag) | diff2(d[8], d[12], tag); };
        auto add = [&](const uint32_t* d) {
#pragma unroll
          for (int g = 0; g < 8; g++) mma8(aA + 4 * g, d[2 * g], d[2 * g + 1], eye);
        };
        int n = 0;
        while (!__all_sync(~0u, ((or3(bad(X), bad(X + 16), bad(X + 64)) | or3(bad(X + 80), bad(X + 96), bad(X + 112))) & 1u) == 0u)) {
          SPIN_GUARD(n);
          load_p(5, X); load_p(6, X + 16);
#pragma unroll
          for (int p = 1; p < 5; p++) load_p(p, X + 48 + 16 * p);
        }
        add(X); add(X + 16);
#pragma unroll
        for (int p = 4; p >= 0; p--) add(X + 48 + 16 * ((p + 1) % 5));
        STAMP(11);
        if (EXP != 1) while (!__all_sync(~0u, (bad(X + 32) & 1u) == 0u)) { SPIN_GUARD(n); load_p(7, X + 32); }
        add(X + 32);
        STAMP(12);
        uint32_t res[16];
#pragma unroll
        for (int i = 0; i < 16; i++) res[i] = pack_bf16(aA[2 * i], aA[2 * i + 1]);
        if (layer == 0) {
          uint4* p = xbase + 8 * SLAB + 4 * j * 32 + lane;
#pragma unroll
          for (int i = 0; i < 4; i++) stg4(p + i * 32, nz(res[4 * i]), res[4 * i + 1], nz(res[4 * i + 2]), res[4 * i + 3]);
          publish_stats<8>(scr + OFF_S + w * 96 + j * 8, aA, 0u, lane);
          if (lane == 0) mbar_arrive(kv_free);
        } else {
          const uint32_t tb = slot(0);
          __syncwarp();
#pragma unroll
          for (int i = 0; i < 4; i++) {
            const uint32_t row = (lane2 & 7) + (lane2 & 8), g = 2 * i + (lane2 >> 4);
            asm volatile("stmatrix.sync.aligned.m8n8.x4.shared.b16 [%0], {%1,%2,%3,%4};"
                         :: "r"(tb + row * 128 + ((g ^ (row & 7)) << 4)), "r"(res[4 * i]), "r"(res[4 * i + 1]), "r"(res[4 * i + 2]), "r"(res[4 * i + 3]) : "memory");
          }
          __syncwarp();
#pragma unroll
          for (int i = 0; i < 4; i++) {
            const uint32_t row = 4 * i + (lane2 >> 3), g = lane2 & 7;
            uint32_t v[4];
            lds4(tb + row * 128 + ((g ^ (row & 7)) << 4), v);
            *(uint4*)(out + (128 * t + 32 * (w >> 1) + 2 * row + (w & 1)) * 576 + 64 * j + 8 * g) = make_uint4(v[0], v[1], v[2], v[3]);
          }
        }
      }
      STAMP(23);
    }
  }
}

typedef CUresult (*EncodeFn)(CUtensorMap*, CUtensorMapDataType, cuuint32_t, void*, const cuuint64_t*, const cuuint64_t*,
                             const cuuint32_t*, const cuuint32_t*, CUtensorMapInterleave, CUtensorMapSwizzle,
                             CUtensorMapL2promotion, CUtensorMapFloatOOBfill);

CUtensorMap make_map(EncodeFn f, const void* p, uint64_t cols, uint64_t rows, bool rem = false) {
  CUtensorMap m;
  cuuint64_t dims[2] = {cols, rows};
  cuuint64_t str[1] = {cols * 2};
  cuuint32_t box[2] = {rem ? 8u : 64u, rem ? 144u : 64u};
  cuuint32_t es[2] = {1, 1};
  f(&m, CU_TENSOR_MAP_DATA_TYPE_BFLOAT16, 2, const_cast<void*>(p), dims, str, box, es, CU_TENSOR_MAP_INTERLEAVE_NONE,
    rem ? CU_TENSOR_MAP_SWIZZLE_NONE : CU_TENSOR_MAP_SWIZZLE_128B, CU_TENSOR_MAP_L2_PROMOTION_NONE, CU_TENSOR_MAP_FLOAT_OOB_FILL_NONE);
  return m;
}

}

extern "C" void kernel_launch(void* const* d_in, const int* in_sizes, int n_in, void* d_out, int out_size) {
  void* fn = nullptr;
  cudaDriverEntryPointQueryResult qr;
  cudaGetDriverEntryPoint("cuTensorMapEncodeTiled", &fn, cudaEnableDefault, &qr);
  EncodeFn enc = (EncodeFn)fn;
  Maps maps;
  maps.m[0] = make_map(enc, d_in[1], 1728, 576); maps.m[1] = make_map(enc, d_in[2], 576, 576);
  maps.m[2] = make_map(enc, d_in[4], 4608, 576); maps.m[3] = make_map(enc, d_in[5], 4608, 576); maps.m[4] = make_map(enc, d_in[6], 576, 4608);
  maps.m[5] = make_map(enc, d_in[1], 1728, 576, true); maps.m[6] = make_map(enc, d_in[2], 576, 576, true);
  void* scr = nullptr;
  cudaGetSymbolAddress(&scr, g_scratch);
  cudaFuncSetAttribute(mega_kernel, cudaFuncAttributeMaxDynamicSharedMemorySize, SMEM_BYTES);
  cudaLaunchConfig_t cfg = {};
  cfg.gridDim = dim3(128); cfg.blockDim = dim3(384); cfg.dynamicSmemBytes = SMEM_BYTES; cfg.stream = cudaStreamPerThread;
  cudaLaunchAttribute at[1];
  at[0].id = cudaLaunchAttributeClusterDimension; at[0].val.clusterDim.x = 2; at[0].val.clusterDim.y = 1; at[0].val.clusterDim.z = 1;
  cfg.attrs = at; cfg.numAttrs = 1;
  int dev = 0, sms = 0, clusters = 0;
  cudaGetDevice(&dev);
  cudaDeviceGetAttribute(&sms, cudaDevAttrMultiProcessorCount, dev);
  cudaOccupancyMaxActiveClusters(&clusters, mega_kernel, &cfg);
  if (sms == 132 && clusters == 66) cfg.gridDim = dim3(132);
  cudaLaunchKernelEx(&cfg, mega_kernel, maps, (uint4*)scr, (const __nv_bfloat16*)d_in[0], (__nv_bfloat16*)d_out);
}
```

```cpp
#include <cuda_runtime.h>
#include <cuda.h>
#include <cuda_bf16.h>
#include <stdint.h>

#define TRACE 0
#define GUARD 0
#define TRAPB 1
#define HOFF1 99
#define HOFF2 99
#define KLD 8
#define ZT 0
#define SLEEP 500
#define SPLITZ 1
#define C8 1
#define HOFF3 99
#define GO 3
#define FEN 5
#define EXP 0
#define FPOS 2

namespace {

constexpr int NST = 6;
constexpr int STAGE = 16384;
constexpr int PARK = NST * STAGE;
constexpr int REM = PARK + 49152;
constexpr int KVS = REM + 40960;
constexpr int HSTG = KVS + 16384;
constexpr int BARS = KVS + 41472;
constexpr int TRC = BARS + 256;
constexpr int SMEM_BYTES = TRC + (TRACE ? 512 : 0);
static_assert(NST == 6, "the producer addresses empty barriers as full + 48");
static_assert(BARS >= PARK + 131072, "barriers overlap park");
static_assert(SMEM_BYTES <= 232448, "smem");

constexpr int SLAB = 36 * 32;
constexpr int SPIN_MAX = 1 << 17;
constexpr uint32_t PRI = 3;
constexpr int GD = 3;
constexpr int OFF_S = 0;
constexpr int OFF_H = OFF_S + 3 * 8 * 96;
constexpr int OFF_X = OFF_H + 2 * 8 * 384;
constexpr int OFF_P = OFF_X + 6 * 8 * SLAB;
constexpr int TILE = OFF_P + 8 * 8 * SLAB;
constexpr int OFF_R = 16 * TILE;
constexpr int OFF_F = OFF_R + 8 * 2304;
constexpr int SCRATCH = OFF_F + 128 * 8;

}

__device__ uint4 g_scratch[SCRATCH];

namespace {

constexpr uint64_t DESC_HI = 0x4000004000000000ull;
constexpr uint64_t DESC_REM = (576ull << 32) | (8u << 16);
__device__ __forceinline__ void wgmma_rs_n64(float (&d)[32], const uint32_t* a, uint64_t desc, int scale_d) {
  asm volatile("{\n.reg .pred p;\nsetp.ne.b32 p, %37, 0;\n"
    "wgmma.mma_async.sync.aligned.m64n64k16.f32.bf16.bf16 "
    "{%0, %1, %2, %3, %4, %5, %6, %7, %8, %9, %10, %11, %12, %13, %14, %15, %16, %17, %18, %19, %20, %21, %22, %23, %24, %25, %26, %27, %28, %29, %30, %31}, "
    "{%32, %33, %34, %35}, %36, p, 1, 1, 1;\n}\n"
    : "+f"(d[0]), "+f"(d[1]), "+f"(d[2]), "+f"(d[3]), "+f"(d[4]), "+f"(d[5]), "+f"(d[6]), "+f"(d[7]), "+f"(d[8]), "+f"(d[9]), "+f"(d[10]), "+f"(d[11]), "+f"(d[12]), "+f"(d[13]), "+f"(d[14]), "+f"(d[15]), "+f"(d[16]), "+f"(d[17]), "+f"(d[18]), "+f"(d[19]), "+f"(d[20]), "+f"(d[21]), "+f"(d[22]), "+f"(d[23]), "+f"(d[24]), "+f"(d[25]), "+f"(d[26]), "+f"(d[27]), "+f"(d[28]), "+f"(d[29]), "+f"(d[30]), "+f"(d[31])
    : "r"(a[0]), "r"(a[1]), "r"(a[2]), "r"(a[3]), "l"(desc), "r"(scale_d));
}
__device__ __forceinline__ void wgmma_rs_n72(float (&d)[36], const uint32_t* a, uint64_t desc, int scale_d) {
  asm volatile("{\n.reg .pred p;\nsetp.ne.b32 p, %41, 0;\n"
    "wgmma.mma_async.sync.aligned.m64n72k16.f32.bf16.bf16 "
    "{%0, %1, %2, %3, %4, %5, %6, %7, %8, %9, %10, %11, %12, %13, %14, %15, %16, %17, %18, %19, %20, %21, %22, %23, %24, %25, %26, %27, %28, %29, %30, %31, %32, %33, %34, %35}, "
    "{%36, %37, %38, %39}, %40, p, 1, 1, 1;\n}\n"
    : "+f"(d[0]), "+f"(d[1]), "+f"(d[2]), "+f"(d[3]), "+f"(d[4]), "+f"(d[5]), "+f"(d[6]), "+f"(d[7]), "+f"(d[8]), "+f"(d[9]), "+f"(d[10]), "+f"(d[11]), "+f"(d[12]), "+f"(d[13]), "+f"(d[14]), "+f"(d[15]), "+f"(d[16]), "+f"(d[17]), "+f"(d[18]), "+f"(d[19]), "+f"(d[20]), "+f"(d[21]), "+f"(d[22]), "+f"(d[23]), "+f"(d[24]), "+f"(d[25]), "+f"(d[26]), "+f"(d[27]), "+f"(d[28]), "+f"(d[29]), "+f"(d[30]), "+f"(d[31]), "+f"(d[32]), "+f"(d[33]), "+f"(d[34]), "+f"(d[35])
    : "r"(a[0]), "r"(a[1]), "r"(a[2]), "r"(a[3]), "l"(desc), "r"(scale_d));
}
__device__ __forceinline__ void wgmma_rs_n24(float (&d)[12], const uint32_t* a, uint64_t desc, int scale_d) {
  asm volatile("{\n.reg .pred p;\nsetp.ne.b32 p, %17, 0;\n"
    "wgmma.mma_async.sync.aligned.m64n24k16.f32.bf16.bf16 "
    "{%0, %1, %2, %3, %4, %5, %6, %7, %8, %9, %10, %11}, "
    "{%12, %13, %14, %15}, %16, p, 1, 1, 1;\n}\n"
    : "+f"(d[0]), "+f"(d[1]), "+f"(d[2]), "+f"(d[3]), "+f"(d[4]), "+f"(d[5]), "+f"(d[6]), "+f"(d[7]), "+f"(d[8]), "+f"(d[9]), "+f"(d[10]), "+f"(d[11])
    : "r"(a[0]), "r"(a[1]), "r"(a[2]), "r"(a[3]), "l"(desc), "r"(scale_d));
}

__device__ __forceinline__ void mbar_init(uint32_t a, uint32_t c) { asm volatile("mbarrier.init.shared::cta.b64 [%0], %1;" :: "r"(a), "r"(c)); }
__device__ __forceinline__ void mbar_arrive(uint32_t a) { asm volatile("mbarrier.arrive.shared::cta.b64 _, [%0];" :: "r"(a) : "memory"); }
__device__ __forceinline__ void mbar_wait_trap(uint32_t a, uint32_t ph) {
  asm volatile("{\n.reg .pred p;\n.reg .u32 n;\nmov.u32 n, 0;\n"
               "W: mbarrier.try_wait.parity.shared::cta.b64 p, [%0], %1;\n@p bra D;\n"
               "add.u32 n, n, 1;\nsetp.lt.u32 p, n, 4194304;\n@p bra W;\ntrap;\nD:\n}" :: "r"(a), "r"(ph) : "memory");
}
__device__ __forceinline__ void mbar_wait(uint32_t a, uint32_t ph) {
  asm volatile("{\n.reg .pred p;\nW: mbarrier.try_wait.parity.shared::cta.b64 p, [%0], %1;\n@!p bra W;\n}" :: "r"(a), "r"(ph) : "memory");
}
__device__ __forceinline__ void mbar_wait_sleep(uint32_t a, uint32_t ph) {
  asm volatile("{\n.reg .pred p;\nW: mbarrier.test_wait.parity.shared::cta.b64 p, [%0], %1;\n@p bra D;\nnanosleep.u32 %2;\nbra W;\nD:\n}" :: "r"(a), "r"(ph), "n"(SLEEP) : "memory");
}
__device__ __forceinline__ void wg_fence() { asm volatile("wgmma.fence.sync.aligned;" ::: "memory"); }
__device__ __forceinline__ void wg_commit() { asm volatile("wgmma.commit_group.sync.aligned;" ::: "memory"); }
template <int N> __device__ __forceinline__ void wg_wait() { asm volatile("wgmma.wait_group.sync.aligned %0;" :: "n"(N) : "memory"); }
__device__ __forceinline__ float tanh_ap(float x) { float y; asm("tanh.approx.f32 %0, %1;" : "=f"(y) : "f"(x)); return y; }
__device__ __forceinline__ float ex2(float x) { float y; asm("ex2.approx.ftz.f32 %0, %1;" : "=f"(y) : "f"(x)); return y; }
__device__ __forceinline__ uint32_t pack_bf16(float lo, float hi) { uint32_t r; asm("cvt.rn.bf16x2.f32 %0, %1, %2;" : "=r"(r) : "f"(hi), "f"(lo)); return r; }
__device__ __forceinline__ float bf_lo(uint32_t v) { return __uint_as_float(v << 16); }
__device__ __forceinline__ float bf_hi(uint32_t v) { return __uint_as_float(v & 0xffff0000u); }
__device__ __forceinline__ uint32_t sub_bf16x2(uint32_t a, uint32_t b) { uint32_t r; asm("sub.rn.bf16x2 %0, %1, %2;" : "=r"(r) : "r"(a), "r"(b)); return r; }
__device__ __forceinline__ uint32_t mul_bf16x2(uint32_t a, uint32_t b) { uint32_t r; asm("mul.rn.bf16x2 %0, %1, %2;" : "=r"(r) : "r"(a), "r"(b)); return r; }
__device__ __forceinline__ uint32_t diff2(uint32_t a, uint32_t b, uint32_t t) { uint32_t r; asm("lop3.b32 %0, %1, %2, %3, 0x7e;" : "=r"(r) : "r"(a), "r"(b), "r"(t)); return r; }
__device__ __forceinline__ uint32_t or3(uint32_t a, uint32_t b, uint32_t c) { uint32_t r; asm("lop3.b32 %0, %1, %2, %3, 0xfe;" : "=r"(r) : "r"(a), "r"(b), "r"(c)); return r; }
__device__ __forceinline__ uint32_t umin2(uint32_t a, uint32_t b) { uint32_t r; asm("min.u32 %0, %1, %2;" : "=r"(r) : "r"(a), "r"(b)); return r; }
__device__ __forceinline__ uint32_t bitmask(uint32_t v, int bit) { uint32_t r; asm("bfe.s32 %0, %1, %2, 1;" : "=r"(r) : "r"(v), "r"(bit)); return r; }
__device__ __forceinline__ uint32_t nz(uint32_t w) { return w == 0u ? 0x8000u : w; }

__device__ __forceinline__ void ldg4(uint32_t* d, const uint4* p) {
  asm volatile("ld.relaxed.gpu.global.v4.b32 {%0,%1,%2,%3}, [%4];" : "=r"(d[0]), "=r"(d[1]), "=r"(d[2]), "=r"(d[3]) : "l"(p) : "memory");
}
__device__ __forceinline__ void ldg2(uint32_t* d, const void* p) {
  asm volatile("ld.relaxed.gpu.global.v2.b32 {%0,%1}, [%2];" : "=r"(d[0]), "=r"(d[1]) : "l"(p) : "memory");
}
__device__ __forceinline__ void stg4(uint4* p, uint32_t a, uint32_t b, uint32_t c, uint32_t d) {
  asm volatile("st.relaxed.gpu.global.v4.b32 [%0], {%1,%2,%3,%4};" :: "l"(p), "r"(a), "r"(b), "r"(c), "r"(d) : "memory");
}
__device__ __forceinline__ void stg2(void* p, uint32_t a, uint32_t b) {
  asm volatile("st.relaxed.gpu.global.v2.b32 [%0], {%1,%2};" :: "l"(p), "r"(a), "r"(b) : "memory");
}
__device__ __forceinline__ void sts4(uint32_t a, const uint32_t* o) { asm volatile("st.shared.v4.b32 [%0], {%1,%2,%3,%4};" :: "r"(a), "r"(o[0]), "r"(o[1]), "r"(o[2]), "r"(o[3]) : "memory"); }
__device__ __forceinline__ void lds4(uint32_t a, uint32_t* o) { asm volatile("ld.shared.v4.b32 {%0,%1,%2,%3}, [%4];" : "=r"(o[0]), "=r"(o[1]), "=r"(o[2]), "=r"(o[3]) : "r"(a) : "memory"); }
__device__ __forceinline__ void lds2(uint32_t a, uint32_t* o) { asm volatile("ld.shared.v2.b32 {%0,%1}, [%2];" : "=r"(o[0]), "=r"(o[1]) : "r"(a) : "memory"); }
__device__ __forceinline__ float rcp(float x) { float y; asm("rcp.approx.ftz.f32 %0, %1;" : "=f"(y) : "f"(x)); return y; }
__device__ __forceinline__ void sts1(uint32_t a, uint32_t v) { asm volatile("st.shared.b32 [%0], %1;" :: "r"(a), "r"(v) : "memory"); }
__device__ __forceinline__ void ldsm4(uint32_t a, uint32_t& r0, uint32_t& r1, uint32_t& r2, uint32_t& r3) {
  asm volatile("ldmatrix.sync.aligned.m8n8.x4.shared.b16 {%0,%1,%2,%3}, [%4];" : "=r"(r0), "=r"(r1), "=r"(r2), "=r"(r3) : "r"(a) : "memory");
}
__device__ __forceinline__ void ldsm4t(uint32_t a, uint32_t& r0, uint32_t& r1, uint32_t& r2, uint32_t& r3) {
  asm volatile("ldmatrix.sync.aligned.m8n8.x4.trans.shared.b16 {%0,%1,%2,%3}, [%4];" : "=r"(r0), "=r"(r1), "=r"(r2), "=r"(r3) : "r"(a) : "memory");
}
__device__ __forceinline__ void mma16c(float* d, const uint32_t* a, uint32_t b0, uint32_t b1, float c01) {
  asm("mma.sync.aligned.m16n8k16.row.col.f32.bf16.bf16.f32 {%0,%1,%2,%3}, {%4,%5,%6,%7}, {%8,%9}, {%10,%10,%10,%10};"
    : "=f"(d[0]), "=f"(d[1]), "=f"(d[2]), "=f"(d[3]) : "r"(a[0]), "r"(a[1]), "r"(a[2]), "r"(a[3]), "r"(b0), "r"(b1), "f"(c01));
}
__device__ __forceinline__ void mma8(float* c, uint32_t a0, uint32_t a1, uint32_t b0) {
  asm("mma.sync.aligned.m16n8k8.row.col.f32.bf16.bf16.f32 {%0,%1,%2,%3}, {%4,%5}, {%6}, {%0,%1,%2,%3};"
    : "+f"(c[0]), "+f"(c[1]), "+f"(c[2]), "+f"(c[3]) : "r"(a0), "r"(a1), "r"(b0));
}
__device__ __forceinline__ uint32_t lane_id() { uint32_t l; asm volatile("mov.u32 %0, %%laneid;" : "=r"(l)); return l; }
__device__ __forceinline__ float quad_sum(float v) { v += __shfl_xor_sync(~0u, v, 1); v += __shfl_xor_sync(~0u, v, 2); return v; }
__device__ __forceinline__ float quad_max(float v) { v = fmaxf(v, __shfl_xor_sync(~0u, v, 1)); v = fmaxf(v, __shfl_xor_sync(~0u, v, 2)); return v; }
template <int N> __device__ __forceinline__ void pin(float (&d)[N]) {
#pragma unroll
  for (int i = 0; i < N; i++) asm volatile("" : "+f"(d[i]) :: "memory");
}
#define SPIN_GUARD(n) if (++(n) > SPIN_MAX) break

template <int NG> __device__ __forceinline__ void publish_stats(uint4* dst, const float* y, uint32_t tag, uint32_t lane) {
  float s0 = 0.f, s1 = 0.f;
#pragma unroll
  for (int g = 0; g < NG; g++) { s0 += y[4 * g] + y[4 * g + 1]; s1 += y[4 * g + 2] + y[4 * g + 3]; }
  s0 = quad_sum(s0); s1 = quad_sum(s1);
  const float m0 = s0 * (1.f / (8 * NG)), m1 = s1 * (1.f / (8 * NG));
  float q0 = 0.f, q1 = 0.f, q2 = 0.f, q3 = 0.f;
#pragma unroll
  for (int g = 0; g < NG; g++) {
    const float a = y[4 * g] - m0, b = y[4 * g + 1] - m0, c = y[4 * g + 2] - m1, d = y[4 * g + 3] - m1;
    q0 = fmaf(a, a, q0); q1 = fmaf(b, b, q1); q2 = fmaf(c, c, q2); q3 = fmaf(d, d, q3);
  }
  q0 = quad_sum(q0 + q1); q2 = quad_sum(q2 + q3);
  if ((lane & 3) == 0)
    stg4(dst + (lane >> 2), (__float_as_uint(s0) & ~1u) | tag, __float_as_uint(q0), __float_as_uint(s1), __float_as_uint(q2));
}

__device__ __forceinline__ void put72(uint4* slab, uint32_t j, uint32_t lane, const uint32_t* v, uint32_t r0, uint32_t r1) {
  uint4* p = slab + ((9 * j + 1) >> 1) * 32;
#pragma unroll
  for (int i = 0; i < 4; i++) stg4(p + lane + i * 32, nz(v[4 * i]), v[4 * i + 1], v[4 * i + 2], v[4 * i + 3]);
  stg2((char*)((j & 1) ? p - 16 : p + 4 * 32) + lane * 8, nz(r0), r1);
}
__device__ __forceinline__ void zero_share(uint4* slab, uint32_t j, uint32_t lane) {
  uint4* p = slab + j * 144 + lane;
#pragma unroll
  for (int i = 0; i < 4; i++) stg4(p + i * 32, 0u, 0u, 0u, 0u);
  if (lane < 16) stg4(p + 128, 0u, 0u, 0u, 0u);
}

struct Maps { CUtensorMap m[7]; };

struct Ring {
  uint32_t st, ph;
  __device__ __forceinline__ void next() { if (++st == NST) { st = 0; ph ^= 1; } }
};

#define GSTAMP(i) do {} while (0)
#define STAMP(i) do {} while (0)
#define ZSTAMP(m, i) do {} while (0)

__device__ __forceinline__ void tma_box(uint32_t dst, const CUtensorMap* m, int col, int row, uint32_t bar, uint32_t expect) {
  asm volatile("{\n.reg .pred e, h;\nelect.sync _|e, 0xffffffff;\nsetp.ne.and.u32 h, %5, 0, e;\n"
               "@h mbarrier.arrive.expect_tx.shared::cta.b64 _, [%2], %5;\n"
               "@e cp.async.bulk.tensor.2d.shared::cluster.global.mbarrier::complete_tx::bytes [%0], [%1, {%3, %4}], [%2];\n}"
               :: "r"(dst), "l"(m), "r"(bar), "r"(col), "r"(row), "r"(expect) : "memory");
}

__device__ __forceinline__ void bulk_load(uint32_t dst, const void* src, uint32_t bytes, uint32_t bar, bool arm) {
  asm volatile("{\n.reg .pred e, h;\nelect.sync _|e, 0xffffffff;\nsetp.ne.and.u32 h, %4, 0, e;\n"
               "@h mbarrier.arrive.expect_tx.shared::cta.b64 _, [%3], %2;\n"
               "@e cp.async.bulk.shared::cluster.global.mbarrier::complete_tx::bytes [%0], [%1], %2, [%3];\n}"
               :: "r"(dst), "l"(src), "r"(bytes), "r"(bar), "r"((uint32_t)arm) : "memory");
}

__global__ void __launch_bounds__(384, 1) mega_kernel(
    const __grid_constant__ Maps maps, uint4* __restrict__ scratch,
    const __nv_bfloat16* __restrict__ x_in, __nv_bfloat16* __restrict__ out) {
  extern __shared__ __align__(1024) uint8_t smem[];
  const uint32_t sb = (uint32_t)__cvta_generic_to_shared(smem);
  const uint32_t full0 = sb + BARS, empty0 = full0 + 8 * NST, rem_full = empty0 + 8 * NST, park_free = rem_full + 8, kv_free = park_free + 8;
  const uint32_t c8_go = kv_free + 8, c8_done = c8_go + 8, c8_full = c8_done + 8, remo_full = c8_full + 8, piece_full = remo_full + 8, xb_done = piece_full + 8, res_full = xb_done + 8, pbar0 = res_full + 8;
  const uint32_t w = __shfl_sync(~0u, threadIdx.x >> 5, 0);
  uint32_t pair = blockIdx.x >> 1;
  if (gridDim.x == 132) {
    uint32_t smid;
    asm("mov.u32 %0, %%smid;" : "=r"(smid));
    const uint32_t tpc = smid >> 1;
    if (tpc == 60 || tpc == 61) { if (threadIdx.x == 0) { __nanosleep(20000); } return; }
    pair = tpc < 32 ? tpc : tpc >= 62 ? (tpc - 58) * 8 : 33 + (tpc - 32) / 7 * 8 + (tpc - 32) % 7;
  }
  const uint32_t rank = blockIdx.x & 1, t = (pair & 7) * 2 + rank, j = pair >> 3;
  const uint32_t sd = sb & 0x3ffff;
  const uint32_t odd = j & 1;
  uint4* const scr = scratch + t * TILE;
  {
    const uint32_t lane = lane_id(), r = lane >> 2, q = lane & 3;
    const uint32_t sl = w < 8 ? w : j, ch = w < 8 ? j : 8;
    const uint32_t* xr = (const uint32_t*)(x_in + (128 * t + 32 * (sl >> 1) + 2 * r + (sl & 1)) * 576 + 64 * ch + 2 * q);
    if (w < 8 || w == 9) {
      uint32_t v[16];
#pragma unroll
      for (int g = 0; g < 8; g++) {
        asm volatile("ld.global.nc.b32 %0, [%1];" : "=r"(v[2 * g]) : "l"(xr + 4 * g));
        asm volatile("ld.global.nc.b32 %0, [%1];" : "=r"(v[2 * g + 1]) : "l"(xr + 8 * 576 + 4 * g));
      }
      if (q == 0) {
#pragma unroll
        for (int k = 0; k < 3; k++) stg4(scr + OFF_S + (k * 8 + sl) * 96 + ch * 8 + r, 0u, 0u, 0u, 0u);
      }
      asm volatile("bar.sync 0, 384;" ::: "memory");
      asm volatile("barrier.cluster.arrive.relaxed.aligned;" ::: "memory");
      uint4* p = scr + OFF_X + sl * SLAB + 4 * ch * 32 + lane;
      auto put = [&] {
#pragma unroll
        for (int i = 0; i < 4; i++) stg4(p + i * 32, nz(v[4 * i]), v[4 * i + 1], nz(v[4 * i + 2]), v[4 * i + 3]);
      };
      if (ch < PRI) put();
      float y[32];
#pragma unroll
      for (int i = 0; i < 16; i++) { y[2 * i] = bf_lo(v[i]); y[2 * i + 1] = bf_hi(v[i]); }
      publish_stats<8>(scr + OFF_S + sl * 96 + ch * 8, y, 1u, lane);
      if (ch >= PRI) put();
    } else {
      if (threadIdx.x == 256) {
        for (int i = 0; i < NST; i++) { mbar_init(full0 + 8 * i, 1); mbar_init(empty0 + 8 * i, 16); }
        mbar_init(rem_full, 1); mbar_init(park_free, 8); mbar_init(kv_free, 8); mbar_init(c8_go, 8); mbar_init(c8_done, 2); mbar_init(c8_full, 1); mbar_init(remo_full, 64); mbar_init(piece_full, 1); mbar_init(xb_done, 8); mbar_init(res_full, 8);
        for (int i = 0; i < 8; i++) mbar_init(pbar0 + 8 * i, 4);
        asm volatile("fence.mbarrier_init.release.cluster;" ::: "memory");
      }
      __syncwarp();
      asm volatile("bar.sync 0, 384;" ::: "memory");
      asm volatile("barrier.cluster.arrive.relaxed.aligned;" ::: "memory");
    }
    asm volatile("barrier.cluster.wait.aligned;" ::: "memory");
  }

  if (w >= 8) {
    asm volatile("setmaxnreg.dec.sync.aligned.u32 24;");
    if (w == 8) {
      uint32_t dst = sb, bar = full0, ph = 1;
#pragma unroll 1
      for (int seg = 0; seg < 34; seg++) {
        const int n = seg >= 17 ? seg - 17 : seg;
        int ma, mb, ca, cb, row = 0;
        if (n < 3) { ma = mb = n == 2; ca = 72 * j + 8 * odd + (n == 0 ? 576 : 0); cb = ca + 576; }
        else if (n < 12) { ma = 3; mb = 2; ca = cb = 576 * j + 64 * (n - 3); }
        else { ma = mb = 4; ca = n == 12 ? 512 : ((j + 2 * n) & 7) * 64; cb = ((j + 2 * n + 1) & 7) * 64; row = 576 * j; }
        const bool zip = n == 0 || n == 3, solo = n == 1 || n == 2 || n == 16;
        const CUtensorMap *pa = &maps.m[ma], *pb = &maps.m[mb];
#pragma unroll 1
        for (int st = 0; st < (solo ? 5 : 9); st++) {
          const bool s0 = !zip && st > 4, s1 = zip || st >= 4;
          const int r0 = row + (zip ? 64 * st : s0 ? 128 * st - 576 : 128 * st), r1 = zip ? r0 : st == 4 ? row : r0 + 64;
          const bool rk = rank, sm = rk ? s1 : s0;
          asm volatile("{\n.reg .pred p, e, f;\n.reg .u32 n;\nelect.sync _|e, 0xffffffff;\nsetp.ne.and.u32 f, %7, 0, e;\nmov.u32 n, 0;\n"
                       "W: mbarrier.try_wait.parity.shared::cta.b64 p, [%1+48], %2;\n@p bra D;\n"
                       "add.u32 n, n, 1;\nsetp.lt.u32 p, n, 4194304;\n@p bra W;\ntrap;\n"
                       "D: @e mbarrier.arrive.expect_tx.shared::cta.b64 _, [%1], %6;\n"
                       "@f cp.async.bulk.tensor.2d.shared::cluster.global.mbarrier::complete_tx::bytes.multicast::cluster [%0], [%3, {%4, %5}], [%1], 3;\n}"
                       :: "r"(dst + rk * 8192), "r"(bar), "r"(ph), "l"(sm ? pb : pa), "r"(sm ? cb : ca), "r"(rk ? r1 : r0),
                          "r"(solo && st == 4 ? STAGE / 2 : STAGE), "r"((uint32_t)!(rk && solo && st == 4)) : "memory");
          dst += STAGE; bar += 8;
          if (bar == full0 + 8 * NST) { dst = sb; bar = full0; ph ^= 1; }
        }
      }
      {
#pragma unroll 1
        for (int i = 0; i < NST; i++) {
          mbar_wait_trap(bar + 48, ph);
          bar += 8;
          if (bar == full0 + 8 * NST) { bar = full0; ph ^= 1; }
        }
      }
    } else if (w == 9) {
      const uint32_t lane = lane_id();
      const uint32_t stg = sb + HSTG + lane * 16;
      uint32_t fph = 0;
#pragma unroll 1
      for (uint32_t layer = 0; layer < 2; layer++) {
        uint4* xb = scr + OFF_X + ((4 + layer) * 8 + j) * SLAB + 32 * 32;
        mbar_wait_sleep(c8_go, layer);
        int n = 0;
        while (true) {
          if (lane == 0) asm volatile("mbarrier.arrive.expect_tx.shared::cta.b64 _, [%0], 18432;" :: "r"(c8_full) : "memory");
          __syncwarp();
#pragma unroll 1
          for (uint32_t s = 0; s < 9; s++)
            bulk_load(sb + HSTG + s * 2048, s < 8 ? scr + OFF_P + (j + s * 8) * SLAB + 32 * 32 : xb, 2048, c8_full, false);
          mbar_wait(c8_full, fph); fph ^= 1;
          uint32_t bad = 0;
#pragma unroll 8
          for (int s = 0; s < 32; s++) { uint32_t v; asm volatile("ld.shared.b32 %0, [%1];" : "=r"(v) : "r"(stg + s * 512) : "memory"); bad |= v ^ (1 - layer); }
          if (__all_sync(~0u, (bad & 1u) == 0u)) break;
          __nanosleep(300);
          SPIN_GUARD(n);
        }
        asm volatile("bar.arrive 7, 96;" ::: "memory");
        float s0 = 0.f, s1 = 0.f;
#pragma unroll 1
        for (int g = 0; g < 8; g++) {
          const uint32_t a = stg + (g >> 1) * 512 + (g & 1) * 8;
          float a0 = 0.f, a1 = 0.f, a2 = 0.f, a3 = 0.f;
#pragma unroll 1
          for (int b = 0; b < 3; b++) {
            uint32_t v[6];
#pragma unroll
            for (int s = 0; s < 3; s++) lds2(a + (3 * b + s) * 2048, v + 2 * s);
#pragma unroll
            for (int s = 0; s < 3; s++) { a0 += bf_lo(v[2 * s]); a1 += bf_hi(v[2 * s]); a2 += bf_lo(v[2 * s + 1]); a3 += bf_hi(v[2 * s + 1]); }
          }
          sts1(a + 18432, pack_bf16(a0, a1)); sts1(a + 18436, pack_bf16(a2, a3));
          s0 += a0 + a1; s1 += a2 + a3;
        }
        __syncwarp();
        if (lane == 0) mbar_arrive(c8_done);
        s0 = quad_sum(s0); s1 = quad_sum(s1);
        float q0 = 0.f, q1 = 0.f;
        const uint32_t ln = lane_id();
#pragma unroll 1
        for (uint32_t i = 0; i < 4; i++) {
          uint32_t x[4];
          lds4(stg + 18432 + i * 512, x);
          stg4(xb + i * 32 + ln, 0u, 0u, 0u, 0u);
          if (layer == 0) {
            stg4(xb - 3 * 8 * SLAB + i * 32 + ln, nz(x[0]), x[1], x[2], x[3]);
#pragma unroll
            for (int e = 0; e < 4; e++) {
              const float m = (e & 1) ? s1 : s0, c = fmaf(m, -1.f / 64, bf_lo(x[e])), d = fmaf(m, -1.f / 64, bf_hi(x[e]));
              if (e & 1) q1 = fmaf(c, c, fmaf(d, d, q1)); else q0 = fmaf(c, c, fmaf(d, d, q0));
            }
          } else {
            uint32_t* o = (uint32_t*)(out + (128 * t + 32 * (j >> 1) + 2 * (ln >> 2) + (j & 1)) * 576 + 512 + 16 * i + 2 * (ln & 3));
            o[0] = x[0]; o[8 * 576] = x[1]; o[4] = x[2]; o[8 * 576 + 4] = x[3];
          }
        }
        if (layer == 0) {
          q0 = quad_sum(q0); q1 = quad_sum(q1);
          if ((ln & 3) == 0) stg4(scr + OFF_S + j * 96 + 64 + (ln >> 2), __float_as_uint(s0) & ~1u, __float_as_uint(q0), __float_as_uint(s1), __float_as_uint(q1));
        }
      }
    } else {
      auto phase2_duties = [&](uint32_t layer) {
        const uint32_t lane = lane_id();
        asm volatile("bar.sync 7, 96;" ::: "memory");
        if (w == 11) {
          if (layer == 0) {
#pragma unroll 1
            for (uint32_t k = 0; k < 6; k++) stg4(scr + OFF_S + (k * 4 + (lane >> 3)) * 96 + j * 8 + (lane & 7), 1u, 0u, 0u, 0u);
          }
          __syncwarp();
          if (lane == 0) mbar_arrive(c8_done);
        }
        mbar_wait_sleep(res_full, layer);
#pragma unroll 1
        for (uint32_t i = 0; i < 4; i++) {
          uint4* z = scr + OFF_X + ((4 + layer) * 8 + (w - 10) * 4 + i) * SLAB + 4 * j * 32 + lane;
#pragma unroll
          for (int k = 0; k < 4; k++) stg4(z + k * 32, 0u, 0u, 0u, 0u);
          __nanosleep(300);
        }
      };
#pragma unroll 1
      for (uint32_t layer = 0; layer < 2; layer++) {
        if (w == 10) {
          if (layer == 0) {
            const uint32_t lane = lane_id();
            const uint32_t p = t >> 2;
            tma_box(sb + PARK, &maps.m[p == 3 ? 6 : 5], 72 * j + (odd ? 0 : 64) + (p < 2 ? 576 * (p + 1) : 0), 144 * (t & 3), piece_full, 2304);
            mbar_wait(piece_full, 0);
            asm volatile("{\n.reg .pred e;\nelect.sync _|e, 0xffffffff;\n@e cp.async.bulk.global.shared::cta.bulk_group [%0], [%1], 2304;\n}\n"
                         "cp.async.bulk.commit_group;\ncp.async.bulk.wait_group 0;\nfence.proxy.async;"
                         :: "l"(scratch + OFF_R + j * 2304 + t * 144), "r"(sb + PARK) : "memory");
            __syncwarp();
            if (FEN & 1) { if (lane < 16) asm volatile("st.release.gpu.global.b32 [%0], 1;" :: "l"((uint32_t*)(scratch + OFF_F + (lane * 8 + j) * 8) + t) : "memory"); }
            else if (lane < 16) asm volatile("st.relaxed.gpu.global.b32 [%0], 1;" :: "l"((uint32_t*)(scratch + OFF_F + (lane * 8 + j) * 8) + t) : "memory");
            uint32_t* fl = (uint32_t*)(scratch + OFF_F + (t * 8 + j) * 8) + (lane & 15);
            uint32_t v;
            int n = 0;
            while (true) {
              if (FEN & 2) asm volatile("ld.acquire.gpu.global.b32 %0, [%1];" : "=r"(v) : "l"(fl) : "memory");
              else asm volatile("ld.relaxed.gpu.global.b32 %0, [%1];" : "=r"(v) : "l"(fl) : "memory");
              if (__all_sync(~0u, v != 0u)) break;
              __nanosleep(100);
              SPIN_GUARD(n);
            }
            if (FEN & 4) asm volatile("ld.acquire.gpu.global.b32 %0, [%1];" : "=r"(v) : "l"(fl) : "memory");
            asm volatile("fence.proxy.async;\nst.relaxed.gpu.global.b32 [%0], 0;" :: "l"(fl) : "memory");
          } else {
            mbar_wait_sleep(park_free, 0);
          }
          bulk_load(sb + REM, scratch + OFF_R + j * 2304, 36864, rem_full, true);
        }
        mbar_wait_sleep(rem_full, layer);
#pragma unroll 1
        for (uint32_t b = 0; b < 5; b++) {
          const uint32_t blk = sb + REM + 27648 + b * 2048, k = (w - 10) * 32 + lane_id(), rr = k & 7;
          const uint32_t dst = blk + ((k >> 3) & 1) * 1024 + rr * 128 + (((k >> 4) ^ rr) << 4);
          uint32_t v[8];
          lds4(blk + k * 16, v); lds4(blk + 1024 + k * 16, v + 4);
          asm volatile("bar.sync 3, 64;" ::: "memory");
          sts4(dst, v); sts4(dst ^ 64, v + 4);
        }
        asm volatile("fence.proxy.async.shared::cta;" ::: "memory");
        mbar_arrive(remo_full);
        if (layer) { phase2_duties(0); mbar_wait_sleep(kv_free, 0); }
        if (t > 0) {
          const uint32_t lane = lane_id(), r = lane >> 2, q = lane & 3;
#pragma unroll 1
          for (uint32_t pc = 0; pc < 3; pc++) {
            uint4* hp = scr + OFF_H + ((layer * 8 + j) * 2 + (w - 10)) * 192 + pc * 64 + lane;
            uint32_t hl[8];
            int n = 0;
            hl[4] = 1u;
            while (true) {
              ldg4(hl, hp);
              if (pc < 2) ldg4(hl + 4, hp + 32);
              if (__all_sync(~0u, hl[0] != 0u && hl[4] != 0u)) break;
              __nanosleep(100);
              SPIN_GUARD(n);
            }
            const uint32_t dst = sb + KVS + (w - 10) * 10368 + r * 144 + q * 4;
            if (pc < 2) {
#pragma unroll
              for (int g = 0; g < 8; g++) sts1(dst + pc * 20736 + odd * 16 + g * 16, hl[g]);
              stg4(hp + 32, 0u, 0u, 0u, 0u);
            } else {
              sts1(dst + (odd ? 0 : 128), hl[0]); sts1(dst + 20736 + (odd ? 0 : 128), hl[1]);
            }
            stg4(hp, 0u, 0u, 0u, 0u);
          }
        }
        asm volatile("bar.arrive 1, 192;" ::: "memory");
        mbar_wait_sleep(xb_done, layer);
#pragma unroll 1
        for (uint32_t i = 0; i < 8; i++) {
          zero_share(scr + OFF_X + ((w - 10) * 16 + layer * 8 + i) * SLAB, j, lane_id());
          __nanosleep(500);
        }
      }
      phase2_duties(1);
    }
  } else {
    asm volatile("setmaxnreg.inc.sync.aligned.u32 240;");
    const bool lead = lane_id() == 0;
    Ring rg{0, 0};
    uint32_t prev = 0;
    uint32_t X[144];
    float rs0, rs1;
    uint32_t mean0, mean1;
    const bool lead2 = lane_id() < 2;
    uint32_t empty_at;
    asm volatile("mapa.shared::cluster.u32 %0, %1, %2;" : "=r"(empty_at) : "r"(empty0), "r"(lane_id() & 1));
    auto release = [&](uint32_t st) { if (lead2) asm volatile("mbarrier.arrive.shared::cluster.b64 _, [%0];" :: "r"(empty_at + st * 8) : "memory"); };
    auto load_kb = [&](int kb, const uint4* src, const char* lo, uint32_t hoff) {
#pragma unroll
      for (int k = 4 * kb; k < 4 * kb + 4; k++) {
        if (k % 9 == 4) { ldg2(X + 4 * k, lo + k * 512); ldg2(X + 4 * k + 2, lo + hoff + k * 512); }
        else ldg4(X + 4 * k, src + k * 32);
      }
    };
    auto next_kb = [&](bool center, int kb, const uint4* src, const char* lo, uint32_t hoff) {
      int n = 0;
      while (true) {
        uint32_t m = umin2(umin2(X[16 * kb], X[16 * kb + 4]), umin2(X[16 * kb + 8], X[16 * kb + 12]));
        if (kb & 1) m = umin2(m, X[16 * kb + 4 * (kb >> 1) + 2]);
        if (__all_sync(~0u, m != 0u)) break;
        SPIN_GUARD(n);
        load_kb(kb, src, lo, hoff);
      }
      if (kb + (center ? GD : GO) < 9) load_kb(kb + (center ? GD : GO), src, lo, hoff);
      if (center) {
#pragma unroll
        for (int i = 16 * kb; i < 16 * kb + 16; i++) X[i] = sub_bf16x2(X[i], (i & 1) ? mean1 : mean0);
      }
    };
#pragma unroll 1
    for (uint32_t hf = 0; hf < 4; hf++) {
      const uint32_t layer = hf >> 1;
      const bool ffn = hf & 1;
      const uint32_t tag = 1 - layer;
      uint4* const xbase = scr + OFF_X + (layer * 8 + w) * SLAB;
      float aA[32], aB[32];
      {
        const uint32_t lane = lane_id(), r = lane >> 2, q = lane & 3;
        const uint4* src = xbase + (ffn ? 32 * SLAB : 0) + lane;
        const char* lo = (const char*)src - (ffn ? lane * 8 : 0);
        const uint32_t hoff = ffn ? 256 : 8;
        uint32_t s[3][4];
        const uint4* p = scr + OFF_S + ((ffn ? 16 : 0) + w) * 96 + q * 8 + r;
        const bool third = !ffn && q == 0;
        int n = 0;
        s[2][0] = tag; s[2][1] = s[2][2] = s[2][3] = 0u;
        STAMP(ffn * 16 + 0);
        while (true) {
          ldg4(s[0], p); ldg4(s[1], p + 32);
          if (third) ldg4(s[2], p + 64);
          if (__all_sync(~0u, ((diff2(s[0][0], s[1][0], tag) | diff2(s[1][0], s[2][0], tag)) & 1u) == 0u)) break;
          SPIN_GUARD(n);
        }
        STAMP(ffn * 16 + 1);
        ZSTAMP(1 + ffn, 0);
        GSTAMP(14 + ffn);
#pragma unroll
        for (int kb = 0; kb < GD; kb++) load_kb(kb, src, lo, hoff);
        float t0 = 0.f, t1 = 0.f;
#pragma unroll
        for (int i = 0; i < 3; i++) { t0 += __uint_as_float(s[i][0]); t1 += __uint_as_float(s[i][2]); }
        const float m0 = quad_sum(t0) * (1.f / 576), m1 = quad_sum(t1) * (1.f / 576);
        const float cnt = ffn ? 72.f : 64.f, inv = ffn ? 1.f / 72 : 1.f / 64;
        float v0 = 0.f, v1 = 0.f;
#pragma unroll
        for (int i = 0; i < 3; i++) {
          const float c = (i < 2 || third) ? cnt : 0.f;
          const float d0 = fmaf(__uint_as_float(s[i][0]), inv, -m0), d1 = fmaf(__uint_as_float(s[i][2]), inv, -m1);
          v0 += fmaf(d0 * d0, c, __uint_as_float(s[i][1])); v1 += fmaf(d1 * d1, c, __uint_as_float(s[i][3]));
        }
        rs0 = rsqrtf(fmaf(quad_sum(v0), 1.f / 576, 1e-5f)); rs1 = rsqrtf(fmaf(quad_sum(v1), 1.f / 576, 1e-5f));
        mean0 = pack_bf16(m0, m0); mean1 = pack_bf16(m1, m1);
#pragma unroll
        for (int kb = 0; kb < 9; kb++) {
          next_kb(true, kb, src, lo, hoff);
          ZSTAMP(1 + ffn, 1 + 3 * kb);
          mbar_wait(full0 + rg.st * 8, rg.ph);
          ZSTAMP(1 + ffn, 2 + 3 * kb);
          const uint64_t desc = DESC_HI | ((sd + rg.st * STAGE) >> 4);
          wg_fence();
#pragma unroll
          for (int i = 0; i < 4; i++) wgmma_rs_n64(aA, X + 4 * (4 * kb + i), desc + i * 128, kb + i != 0);
          if (SPLITZ && kb == 8) { wg_commit(); wg_wait<1>(); wg_fence(); }
#pragma unroll
          for (int i = 0; i < 4; i++) wgmma_rs_n64(aB, X + 4 * (4 * kb + i), desc + 512 + i * 128, kb + i != 0);
          wg_commit();
          wg_wait<1>();
          ZSTAMP(1 + ffn, 3 + 3 * kb);
          if (kb > 0) release(prev);
          prev = rg.st; rg.next();
        }
        if (!SPLITZ) wg_wait<0>();
        ZSTAMP(1 + ffn, 28);
        ZSTAMP(4, 0);
        STAMP(ffn * 16 + 2);
      }
      if (!ffn) {
      const uint32_t lane = lane_id(), r = lane >> 2, q = lane & 3;
      const uint32_t kvrow = sb + KVS + (w & 1) * 10368 + (16 * (w >> 1)) * 144;
      uint32_t Q[18], Km[3][8], Ke[3][4];
      const bool edge = (t == 0 && w < 2);
      const uint32_t row0 = edge ? sb + KVS + 8 * 144 : kvrow + (lane & 7) * 144, row1 = kvrow + (8 + (lane & 7)) * 144;
      {
        const uint32_t dst = kvrow + (8 + r) * 144 + q * 4 + odd * 16, dstr = dst + (odd ? -16 : 128);
        const bool edge_out = w >= 6 && t < 15;
        uint4* const hp = scr + TILE + OFF_H + ((layer * 8 + j) * 2 + (w & 1)) * 192 + lane;
        auto put_kv = [&](float (&a)[32], int part) {
          pin(a);
          uint32_t hl[8];
#pragma unroll
          for (int g = 0; g < 8; g++) {
            hl[g] = pack_bf16(a[4 * g + 2] * rs1, a[4 * g + 3] * rs1);
            sts1(dst + part * 20736 + g * 16, pack_bf16(a[4 * g] * rs0, a[4 * g + 1] * rs0)); sts1(dst + part * 20736 + 8 * 144 + g * 16, hl[g]);
          }
          if (edge_out) { stg4(hp + part * 64, nz(hl[0]), hl[1], hl[2], hl[3]); stg4(hp + part * 64 + 32, nz(hl[4]), hl[5], hl[6], hl[7]); }
        };
        put_kv(aA, 0);
        wg_wait<0>();
        release(prev);
        float aR[12];
        mbar_wait(rem_full, layer);
        const uint64_t dr = DESC_REM | ((sd + REM) >> 4);
        wg_fence();
#pragma unroll
        for (int s = 0; s < 36; s++) {
          wgmma_rs_n24(aR, X + 4 * s, dr + s * 16, s != 0);
          if (s == 4) put_kv(aB, 1);
        }
        wg_commit();
#pragma unroll
        for (int kb = 0; kb < 9; kb++) {
          if (kb == HOFF1 && w < 4) asm volatile("bar.sync 4, 256;" ::: "memory");
          if (kb == 8 && HOFF1 < 9 && w >= 4) asm volatile("bar.arrive 4, 256;" ::: "memory");
          if (!(kb & 1)) mbar_wait(full0 + rg.st * 8, rg.ph);
          const uint64_t desc = DESC_HI | ((sd + rg.st * STAGE + (kb & 1) * 8192) >> 4);
          wg_fence();
#pragma unroll
          for (int i = 0; i < 4; i++) wgmma_rs_n64(aB, X + 4 * (4 * kb + i), desc + i * 128, kb + i != 0);
          wg_commit();
          wg_wait<1>();
          if (kb > 0 && !(kb & 1)) release(prev);
          if ((kb & 1) || kb == 8) { prev = rg.st; rg.next(); }
          if (kb == 0) {
            pin(aR);
            const uint32_t k1 = pack_bf16(aR[2] * rs1, aR[3] * rs1), v1 = pack_bf16(aR[6] * rs1, aR[7] * rs1);
            if (edge_out) stg4(hp + 128, nz(k1), v1, 0u, 0u);
            sts1(dstr, pack_bf16(aR[0] * rs0, aR[1] * rs0)); sts1(dstr + 8 * 144, k1);
            sts1(dstr + 20736, pack_bf16(aR[4] * rs0, aR[5] * rs0)); sts1(dstr + 20736 + 8 * 144, v1);
            Q[16] = pack_bf16(aR[8], aR[9]); Q[17] = pack_bf16(aR[10], aR[11]);
            if (w < 4) asm volatile("bar.arrive 2, 256;" ::: "memory");
          }
          if (kb == KLD) {
            if (w < 4) asm volatile("bar.sync 1, 192;" ::: "memory");
            else asm volatile("bar.sync 2, 256;" ::: "memory");
#pragma unroll
            for (int nt = 0; nt < 3; nt++) {
              const uint32_t ra = (nt == 0 ? row0 : row1 + (nt - 1) * 8 * 144);
              ldsm4(ra + odd * 16 + (lane >> 3) * 16, Km[nt][0], Km[nt][1], Km[nt][2], Km[nt][3]);
              ldsm4(ra + odd * 16 + 64 + (lane >> 3) * 16, Km[nt][4], Km[nt][5], Km[nt][6], Km[nt][7]);
              ldsm4(ra + (odd ? 0 : 32) + (lane >> 3) * 32, Ke[nt][0], Ke[nt][1], Ke[nt][2], Ke[nt][3]);
            }
            const uint32_t ge = (2u << q) - 1, le = 0xfu << q, on = edge ? 0u : ~0u;
            const uint32_t bits = odd ? 0xfu | ((le & 0xfu) << 4) | (ge << 8) : ge | 0xf0u | (le << 8);
#pragma unroll
            for (int h = 0; h < 4; h++) {
              const uint32_t ma = bitmask(bits, h), mb = bitmask(bits, 4 + h), mc = bitmask(bits, 8 + h);
              Km[0][2 * h] &= ma & on; Km[0][2 * h + 1] &= mb & on; Ke[0][h] &= mc & on;
#pragma unroll
              for (int nt = 1; nt < 3; nt++) { Km[nt][2 * h] &= ma; Km[nt][2 * h + 1] &= mb; Ke[nt][h] &= mc; }
            }
          }
        }
        wg_wait<0>();
        release(prev);
        pin(aB);
        STAMP(3);
#pragma unroll
        for (int i = 0; i < 16; i++) Q[i] = pack_bf16(aB[2 * i], aB[2 * i + 1]);
      }
      {
        uint32_t V01[12][2], V2[12];
        const uint32_t rv = ((lane & 8) ? row1 : row0) + 20736, rw = row1 + 8 * 144 + 20736;
#pragma unroll
        for (int i = 0; i < 4; i++) ldsm4t(rv + odd * 16 + i * 32 + (lane >> 4) * 16, V01[2 * i][0], V01[2 * i][1], V01[2 * i + 1][0], V01[2 * i + 1][1]);
#pragma unroll
        for (int i = 0; i < 2; i++) ldsm4t(rv + (odd ? 0 : 32) + i * 64 + (lane >> 4) * 32, V01[8 + 2 * i][0], V01[8 + 2 * i][1], V01[9 + 2 * i][0], V01[9 + 2 * i][1]);
        ldsm4t(rw + odd * 16 + (lane >> 3) * 16, V2[0], V2[1], V2[2], V2[3]);
        ldsm4t(rw + odd * 16 + 64 + (lane >> 3) * 16, V2[4], V2[5], V2[6], V2[7]);
        ldsm4t(rw + (odd ? 0 : 32) + (lane >> 3) * 32, V2[8], V2[9], V2[10], V2[11]);
        const bool up0 = 2 * q > r, up1 = 2 * q + 1 > r;
        const uint32_t upm = (up0 ? 0xffffu : 0u) | (up1 ? 0xffff0000u : 0u);
        const float c0 = 0.23570226039551584f * 1.4426950408889634f * rs0, c1 = 0.23570226039551584f * 1.4426950408889634f * rs1;
        const float masked = edge ? -1e9f * 1.4426950408889634f * rcp(c0) : 0.f;
        uint32_t Om[16], Oe[8];
#pragma unroll
        for (int h = 0; h < 4; h++) {
          const uint32_t e0 = odd ? Q[(4 * h + 16) % 18] : Q[4 * h + 4], e1 = odd ? Q[(4 * h + 17) % 18] : Q[4 * h + 5];
          float S[3][4];
#pragma unroll
          for (int nt = 0; nt < 3; nt++) {
            mma16c(S[nt], Q + 4 * h, Km[nt][2 * h], Km[nt][2 * h + 1], nt == 0 ? masked : 0.f);
            mma8(S[nt], e0, e1, Ke[nt][h]);
          }
          const float s00 = up0 ? S[0][0] : S[1][0], s01 = up1 ? S[0][1] : S[1][1];
          const float s10 = up0 ? S[1][2] : S[2][2], s11 = up1 ? S[1][3] : S[2][3];
          const float m0 = quad_max(fmaxf(s00, s01)) * c0, m1 = quad_max(fmaxf(s10, s11)) * c1;
          const float p00 = ex2(fmaf(s00, c0, -m0)), p01 = ex2(fmaf(s01, c0, -m0)), p10 = ex2(fmaf(s10, c1, -m1)), p11 = ex2(fmaf(s11, c1, -m1));
          const float i0 = rcp(quad_sum(p00 + p01)), i1 = rcp(quad_sum(p10 + p11));
          const uint32_t p0 = pack_bf16(p00 * i0, p01 * i0), p1 = pack_bf16(p10 * i1, p11 * i1);
          const uint32_t pf[4] = {p0 & upm, 0u, p0 & ~upm, p1 & upm};
#pragma unroll
          for (int gi = 0; gi < 3; gi++) {
            const int g = gi < 2 ? 2 * h + gi : 8 + h;
            float o[4];
            mma16c(o, pf, V01[g][0], V01[g][1], 0.f);
            mma8(o, 0u, p1 & ~upm, V2[g]);
            uint32_t* d = gi < 2 ? Om + 2 * g : Oe + 2 * h;
            d[0] = pack_bf16(o[0], o[1]); d[1] = pack_bf16(o[2], o[3]);
          }
        }
#pragma unroll
        for (int h = 0; h < 4; h++)
#pragma unroll
          for (int e = 0; e < 2; e++) {
            if (h > 0 && !odd && q < h) Om[4 * h + e] = Oe[2 * h - 2 + e];
            if (h < 3 && odd && q > h) Om[4 * h + 2 + e] = Oe[2 * h + 2 + e];
          }
        STAMP(4);
        if (j >= PRI && lane == 0) asm volatile("st.relaxed.gpu.global.b32 [%0], %1;" :: "l"(scr + OFF_S + (8 + w) * 96 + j * 8), "r"(tag) : "memory");
        put72(xbase + 16 * SLAB, j, lane, Om, odd ? Oe[0] : Oe[6], odd ? Oe[1] : Oe[7]);
      }
      if (j < PRI && lane == 0) asm volatile("st.relaxed.gpu.global.b32 [%0], %1;" :: "l"(scr + OFF_S + (8 + w) * 96 + j * 8), "r"(tag) : "memory");
      {
        uint32_t res[18];
        const uint4* p = xbase + ((9 * j + 1) >> 1) * 32 + lane;
#pragma unroll
        for (int i = 0; i < 4; i++) ldg4(res + 4 * i, p + i * 32);
        ldg2(res + 16, odd ? (const char*)(p - 32) + 8 : (const char*)(p + 4 * 32));
        const uint4* src = xbase + 16 * SLAB + lane;
        {
          const uint4* fp = scr + OFF_S + (8 + w) * 96 + (lane & 7) * 8;
          int n = 0;
          mbar_wait(remo_full, layer);
          STAMP(8);
          while (true) {
            uint32_t f;
            asm volatile("ld.relaxed.gpu.global.b32 %0, [%1];" : "=r"(f) : "l"(fp) : "memory");
            if (__all_sync(~0u, f == tag)) break;
            SPIN_GUARD(n);
          }
          STAMP(9);
        }
        if (HOFF3 < 9 && w < 4) asm volatile("bar.sync 6, 256;" ::: "memory");
#pragma unroll
        for (int kb = 0; kb < GO; kb++) load_kb(kb, src, (const char*)src - lane * 8, 256);
        float acc[36];
#pragma unroll
        for (int i = 0; i < 18; i++) { acc[2 * i] = bf_lo(res[i]); acc[2 * i + 1] = bf_hi(res[i]); }
#pragma unroll
        for (int kb = 0; kb < 9; kb++) {
          next_kb(false, kb, src, (const char*)src - lane * 8, 256);
          if (kb == HOFF3 && w >= 4) asm volatile("bar.arrive 6, 256;" ::: "memory");
          if (!(kb & 1)) mbar_wait(full0 + rg.st * 8, rg.ph);
          const uint32_t base = sd + rg.st * STAGE + (kb & 1) * 8192;
          const uint64_t d0 = DESC_HI | ((base >> 4) + (((sd + REM + 27648 + (kb >> 1) * 2048 + (kb & 1) * 64 - base) >> 4) << 16));
          wg_fence();
#pragma unroll
          for (int i = 0; i < 4; i++) wgmma_rs_n72(acc, X + 4 * (4 * kb + i), d0 - (uint64_t)(i * ((127u << 16) - 128u)), 1);
          wg_commit();
          wg_wait<1>();
          if (kb > 0 && !(kb & 1)) release(prev);
          if ((kb & 1) || kb == 8) { prev = rg.st; rg.next(); }
        }
        wg_wait<0>();
        release(prev);
        pin(acc);
        STAMP(10);
#pragma unroll
        for (int i = 0; i < 18; i++) res[i] = pack_bf16(acc[2 * i], acc[2 * i + 1]);
        if (j < PRI) put72(xbase + 32 * SLAB, j, lane, res, res[16], res[17]);
        publish_stats<9>(scr + OFF_S + (16 + w) * 96 + j * 8, acc, tag, lane);
        if (j >= PRI) put72(xbase + 32 * SLAB, j, lane, res, res[16], res[17]);
      }
      continue;
      }
      const uint32_t hp = sb + PARK + w * 512 + lane_id() * 16;
      auto pack8 = [&](float (&a)[32], int p, uint32_t* o) {
#pragma unroll
        for (int e = 0; e < 8; e++) asm volatile("" : "+f"(a[8 * p + e]) :: "memory");
#pragma unroll
        for (int e = 0; e < 4; e++) o[e] = pack_bf16(a[8 * p + 2 * e], a[8 * p + 2 * e + 1]);
      };
      const float ka0 = 0.7978845608028654f * rs0, kb0 = 0.044715f * ka0 * rs0 * rs0, ku0 = 0.5f * rs0 * rs0;
      const float ka1 = 0.7978845608028654f * rs1, kb1 = 0.044715f * ka1 * rs1 * rs1, ku1 = 0.5f * rs1 * rs1;
      auto packu8 = [&](int p, uint32_t* o) {
#pragma unroll
        for (int e = 0; e < 8; e++) asm volatile("" : "+f"(aA[8 * p + e]) :: "memory");
#pragma unroll
        for (int e = 0; e < 4; e++) o[e] = pack_bf16(aA[8 * p + 2 * e] * ((e & 1) ? ku1 : ku0), aA[8 * p + 2 * e + 1] * ((e & 1) ? ku1 : ku0));
      };
      auto geglu8 = [&](int p, uint32_t* u) {
#pragma unroll
        for (int e = 0; e < 8; e++) asm volatile("" : "+f"(aB[8 * p + e]) :: "memory");
        float h[8];
#pragma unroll
        for (int e = 0; e < 8; e++) {
          const float g = aB[8 * p + e];
          h[e] = fmaf(g, tanh_ap(g * fmaf(g * g, (e & 2) ? kb1 : kb0, (e & 2) ? ka1 : ka0)), g);
        }
#pragma unroll
        for (int e = 0; e < 4; e++) u[e] = mul_bf16x2(pack_bf16(h[2 * e], h[2 * e + 1]), u[e]);
      };
      auto box = [&](int b, auto&& filler) {
        const int kb = b < 9 ? b : b - 9;
        if (!(b & 1)) { if ((TRAPB >> (b >> 1)) & 1) mbar_wait_trap(full0 + rg.st * 8, rg.ph); else mbar_wait(full0 + rg.st * 8, rg.ph); }
        const uint64_t desc = DESC_HI | ((sd + rg.st * STAGE + (b & 1) * 8192) >> 4);
        wg_fence();
#pragma unroll
        for (int i = 0; i < 4; i++) {
          if (b < 9) wgmma_rs_n64(aA, X + 4 * (4 * kb + i), desc + i * 128, kb + i != 0);
          else wgmma_rs_n64(aB, X + 4 * (4 * kb + i), desc + i * 128, kb + i != 0);
          if (i == FPOS) filler();
        }
        wg_commit();
        if (b & 1) { prev = rg.st; rg.next(); } else { wg_wait<1>(); release(prev); }
      };
      auto nop = [] {};
      auto step = [&](int st, auto&& filler) { box(2 * st, nop); box(2 * st + 1, filler); };
#pragma unroll
      for (int p = 0; p < 4; p++) { uint32_t o[4]; packu8(p, o); sts4(hp + p * 4096, o); }
      box(0, nop);
      if (lead) mbar_arrive(xb_done);
#pragma unroll 1
      for (int c = 1;; c++) {
        const uint32_t hc = hp + c * 4 * 4096;
#pragma unroll
        for (int b = 1; b < 18; b++) box(b, [&] {
          if ((b & 1) && b < 8) { uint32_t o[4]; const uint32_t a = hc - (4 - (b >> 1)) * 4096; lds4(a, o); geglu8(b >> 1, o); sts4(a, o); }
          if ((b & 1) && b > 10) { uint32_t o[4]; packu8((b - 11) >> 1, o); if (c < 8) sts4(hc + ((b - 11) >> 1) * 4096, o); } });
        ZSTAMP(4, c);
        if (c == 8) break;
        box(0, nop);
      }
      wg_wait<0>();
      STAMP(21);
      GSTAMP(19);
      auto unpark = [&](int kb) {
#pragma unroll
        for (int s = 4 * kb; s < 4 * kb + 4; s++) lds4(hp + s * 4096, X + 4 * s);
      };
      unpark(0);
      uint32_t U[16];
#pragma unroll
      for (int p = 0; p < 4; p++) packu8(p, U + 4 * p);
#pragma unroll
      for (int b = 0; b < 8; b++) box(b, [&] {
        if (b < 7) unpark(b + 1);
        if (b & 1) {
          geglu8(b >> 1, U + 2 * (b - 1));
          if (rg.ph > 1) sts4(hp, U + 2 * (b - 1));
#pragma unroll
          for (int i = 0; i < 4; i++) X[128 + 2 * (b - 1) + i] = U[2 * (b - 1) + i];
        } });
      STAMP(24);
      if (layer == 0 && lead) mbar_arrive(park_free);
      const uint32_t lane2 = lane_id();
      uint4* const pw = scr + OFF_P + (j * 8 + w) * SLAB + lane2;
      const uint4* const pr = scr + OFF_P + w * SLAB + 4 * j * 32 + lane2;
      auto put_part = [&](float (&a)[32], int p, uint32_t chunk) {
        uint32_t o[4];
        pack8(a, p, o);
        stg4(pw + (chunk * 4 + p) * 32, (o[0] & ~1u) | tag, o[1], o[2], o[3]);
      };
      uint4* const xb = xbase + 32 * SLAB + 4 * j * 32;
      auto slot = [&](int p) { return sb + w * 2048 + (p < 3 ? PARK + p * 16384 : KVS + (p - 3) * 16384); };
      auto fetch = [&](int p) {
        bulk_load(slot(p), p ? scr + OFF_P + (((j - p) & 7) * 8 + w) * SLAB + 4 * j * 32 : xb, 2048, p ? pbar0 + w * 8 : res_full, true);
      };
#pragma unroll 1
      for (int sp = 0;; sp++) {
        const uint32_t ca = sp == 0 ? 8 : ((j + 2 * sp) & 7), cb = (j + 2 * sp + 1) & 7;
        if (C8 == 1 && sp == 1 && lead) mbar_arrive(c8_go);
#pragma unroll
        for (int st = 4; st < 9; st++) step(st, [&] {
          if (st == 5 || st == 6) { put_part(aA, 2 * (st - 5), ca); put_part(aA, 2 * (st - 5) + 1, ca); }
          if (st == 8 && sp > 0) { if (sp == 3) mbar_wait(c8_done, layer); fetch(2 * sp - 2); } });
        STAMP(25 + sp);
        if (sp == 3) break;
        if (C8 == 0 && sp == 0 && lead) mbar_arrive(c8_go);
#pragma unroll
        for (int st = 0; st < 4; st++) step(st, [&] {
          if (st < 2) { put_part(aB, 2 * st, cb); put_part(aB, 2 * st + 1, cb); }
          if (st == 3 && sp > 0) fetch(2 * sp - 1); });
      }
      auto load_p = [&](int p, uint32_t* d) {
#pragma unroll
        for (int i = 0; i < 4; i++) ldg4(d + 4 * i, pr + ((j - p) & 7) * 8 * SLAB + i * 32);
      };
#pragma unroll
      for (int b = 0; b < 9; b++) {
        if (b == HOFF2 && w < 4) asm volatile("bar.sync 5, 256;" ::: "memory");
        box(b, [&] {
          if (b == 1) {
#pragma unroll
            for (int p = 0; p < 4; p++) put_part(aB, p, (j + 7) & 7);
          }
          if (b == 3) { load_p(5, X); load_p(6, X + 16); }
          if (b == 7 && EXP != 1) load_p(7, X + 32); });
        if (b == 7 && HOFF2 < 9 && w >= 4) asm volatile("bar.arrive 5, 256;" ::: "memory");
      }
      mbar_wait(res_full, layer);
      mbar_wait(pbar0 + w * 8, layer);
#pragma unroll
      for (int p = 1; p < 5; p++)
#pragma unroll
        for (int i = 0; i < 4; i++) lds4(slot(p) + lane2 * 16 + i * 512, X + 48 + 16 * p + 4 * i);
#pragma unroll
      for (int i = 0; i < 4; i++) {
        const bool split = j == 2 * i + 1;
        const uint32_t a = slot(0) + i * 512 + (split ? lane2 * 8 : lane2 * 16);
        lds2(a, X + 48 + 4 * i); lds2(a + (split ? 256 : 8), X + 50 + 4 * i);
      }
      wg_wait<0>();
      release(rg.st); rg.next();
      pin(aA);
      STAMP(22);
      GSTAMP(20);
      {
        const uint32_t lane = lane2, r = lane >> 2, q = lane & 3;
        const uint32_t eye = r == 2 * q ? 0x3f80u : r == 2 * q + 1 ? 0x3f800000u : 0u;
        auto bad = [&](const uint32_t* d) { return diff2(d[0], d[4], tag) | diff2(d[8], d[12], tag); };
        auto add = [&](const uint32_t* d) {
#pragma unroll
          for (int g = 0; g < 8; g++) mma8(aA + 4 * g, d[2 * g], d[2 * g + 1], eye);
        };
        int n = 0;
        while (!__all_sync(~0u, ((or3(bad(X), bad(X + 16), bad(X + 64)) | or3(bad(X + 80), bad(X + 96), bad(X + 112))) & 1u) == 0u)) {
          SPIN_GUARD(n);
          load_p(5, X); load_p(6, X + 16);
#pragma unroll
          for (int p = 1; p < 5; p++) load_p(p, X + 48 + 16 * p);
        }
        add(X); add(X + 16);
#pragma unroll
        for (int p = 4; p >= 0; p--) add(X + 48 + 16 * ((p + 1) % 5));
        STAMP(11);
        if (EXP != 1) while (!__all_sync(~0u, (bad(X + 32) & 1u) == 0u)) { SPIN_GUARD(n); load_p(7, X + 32); }
        add(X + 32);
        STAMP(12);
        uint32_t res[16];
#pragma unroll
        for (int i = 0; i < 16; i++) res[i] = pack_bf16(aA[2 * i], aA[2 * i + 1]);
        if (layer == 0) {
          uint4* p = xbase + 8 * SLAB + 4 * j * 32 + lane;
          auto put = [&] {
#pragma unroll
            for (int i = 0; i < 4; i++) stg4(p + i * 32, nz(res[4 * i]), res[4 * i + 1], nz(res[4 * i + 2]), res[4 * i + 3]);
          };
          if (j < PRI) put();
          publish_stats<8>(scr + OFF_S + w * 96 + j * 8, aA, 0u, lane);
          if (j >= PRI) put();
          if (lane == 0) mbar_arrive(kv_free);
        } else {
          const uint32_t tb = slot(0);
          __syncwarp();
#pragma unroll
          for (int i = 0; i < 4; i++) {
            const uint32_t row = (lane2 & 7) + (lane2 & 8), g = 2 * i + (lane2 >> 4);
            asm volatile("stmatrix.sync.aligned.m8n8.x4.shared.b16 [%0], {%1,%2,%3,%4};"
                         :: "r"(tb + row * 128 + ((g ^ (row & 7)) << 4)), "r"(res[4 * i]), "r"(res[4 * i + 1]), "r"(res[4 * i + 2]), "r"(res[4 * i + 3]) : "memory");
          }
          __syncwarp();
#pragma unroll
          for (int i = 0; i < 4; i++) {
            const uint32_t row = 4 * i + (lane2 >> 3), g = lane2 & 7;
            uint32_t v[4];
            lds4(tb + row * 128 + ((g ^ (row & 7)) << 4), v);
            *(uint4*)(out + (128 * t + 32 * (w >> 1) + 2 * row + (w & 1)) * 576 + 64 * j + 8 * g) = make_uint4(v[0], v[1], v[2], v[3]);
          }
        }
      }
      STAMP(23);
    }
  }
}

typedef CUresult (*EncodeFn)(CUtensorMap*, CUtensorMapDataType, cuuint32_t, void*, const cuuint64_t*, const cuuint64_t*,
                             const cuuint32_t*, const cuuint32_t*, CUtensorMapInterleave, CUtensorMapSwizzle,
                             CUtensorMapL2promotion, CUtensorMapFloatOOBfill);

CUtensorMap make_map(EncodeFn f, const void* p, uint64_t cols, uint64_t rows, bool rem = false) {
  CUtensorMap m;
  cuuint64_t dims[2] = {cols, rows};
  cuuint64_t str[1] = {cols * 2};
  cuuint32_t box[2] = {rem ? 8u : 64u, rem ? 144u : 64u};
  cuuint32_t es[2] = {1, 1};
  f(&m, CU_TENSOR_MAP_DATA_TYPE_BFLOAT16, 2, const_cast<void*>(p), dims, str, box, es, CU_TENSOR_MAP_INTERLEAVE_NONE,
    rem ? CU_TENSOR_MAP_SWIZZLE_NONE : CU_TENSOR_MAP_SWIZZLE_128B, CU_TENSOR_MAP_L2_PROMOTION_NONE, CU_TENSOR_MAP_FLOAT_OOB_FILL_NONE);
  return m;
}

}

extern "C" void kernel_launch(void* const* d_in, const int* in_sizes, int n_in, void* d_out, int out_size) {
  void* fn = nullptr;
  cudaDriverEntryPointQueryResult qr;
  cudaGetDriverEntryPoint("cuTensorMapEncodeTiled", &fn, cudaEnableDefault, &qr);
  EncodeFn enc = (EncodeFn)fn;
  Maps maps;
  maps.m[0] = make_map(enc, d_in[1], 1728, 576); maps.m[1] = make_map(enc, d_in[2], 576, 576);
  maps.m[2] = make_map(enc, d_in[4], 4608, 576); maps.m[3] = make_map(enc, d_in[5], 4608, 576); maps.m[4] = make_map(enc, d_in[6], 576, 4608);
  maps.m[5] = make_map(enc, d_in[1], 1728, 576, true); maps.m[6] = make_map(enc, d_in[2], 576, 576, true);
  void* scr = nullptr;
  cudaGetSymbolAddress(&scr, g_scratch);
  cudaFuncSetAttribute(mega_kernel, cudaFuncAttributeMaxDynamicSharedMemorySize, SMEM_BYTES);
  cudaLaunchConfig_t cfg = {};
  cfg.gridDim = dim3(128); cfg.blockDim = dim3(384); cfg.dynamicSmemBytes = SMEM_BYTES; cfg.stream = cudaStreamPerThread;
  cudaLaunchAttribute at[1];
  at[0].id = cudaLaunchAttributeClusterDimension; at[0].val.clusterDim.x = 2; at[0].val.clusterDim.y = 1; at[0].val.clusterDim.z = 1;
  cfg.attrs = at; cfg.numAttrs = 1;
  int dev = 0, sms = 0, clusters = 0;
  cudaGetDevice(&dev);
  cudaDeviceGetAttribute(&sms, cudaDevAttrMultiProcessorCount, dev);
  cudaOccupancyMaxActiveClusters(&clusters, mega_kernel, &cfg);
  if (sms == 132 && clusters == 66) cfg.gridDim = dim3(132);
  cudaLaunchKernelEx(&cfg, mega_kernel, maps, (uint4*)scr, (const __nv_bfloat16*)d_in[0], (__nv_bfloat16*)d_out);
}
```

```cpp
#include <cuda_runtime.h>
#include <cuda.h>
#include <cuda_bf16.h>
#include <stdint.h>

#define TRACE 0
#define GUARD 0
#define TRAPB 1
#define HOFF1 99
#define HOFF2 99
#define KLD 8
#define ZT 0
#define SLEEP 500
#define SPLITZ 1
#define C8 1
#define HOFF3 99
#define GO 3
#define FEN 5
#define EXP 0
#define FPOS 2

namespace {

constexpr int NST = 6;
constexpr int STAGE = 16384;
constexpr int PARK = NST * STAGE;
constexpr int REM = PARK + 49152;
constexpr int KVS = REM + 40960;
constexpr int HSTG = KVS + 16384;
constexpr int BARS = KVS + 41472;
constexpr int TRC = BARS + 256;
constexpr int SMEM_BYTES = TRC + (TRACE ? 512 : 0);
static_assert(NST == 6, "the producer addresses empty barriers as full + 48");
static_assert(BARS >= PARK + 131072, "barriers overlap park");
static_assert(SMEM_BYTES <= 232448, "smem");

constexpr int SLAB = 36 * 32;
constexpr int SPIN_MAX = 1 << 17;
constexpr uint32_t PRI = 3;
constexpr int GD = 3;
constexpr int OFF_S = 0;
constexpr int OFF_H = OFF_S + 3 * 8 * 96;
constexpr int OFF_X = OFF_H + 2 * 8 * 384;
constexpr int OFF_P = OFF_X + 6 * 8 * SLAB;
constexpr int TILE = OFF_P + 8 * 8 * SLAB;
constexpr int OFF_R = 16 * TILE;
constexpr int OFF_F = OFF_R + 8 * 2304;
constexpr int SCRATCH = OFF_F + 128 * 8;

}

__device__ uint4 g_scratch[SCRATCH];

namespace {

constexpr uint64_t DESC_HI = 0x4000004000000000ull;
constexpr uint64_t DESC_REM = (576ull << 32) | (8u << 16);
__device__ __forceinline__ void wgmma_rs_n64(float (&d)[32], const uint32_t* a, uint64_t desc, int scale_d) {
  asm volatile("{\n.reg .pred p;\nsetp.ne.b32 p, %37, 0;\n"
    "wgmma.mma_async.sync.aligned.m64n64k16.f32.bf16.bf16 "
    "{%0, %1, %2, %3, %4, %5, %6, %7, %8, %9, %10, %11, %12, %13, %14, %15, %16, %17, %18, %19, %20, %21, %22, %23, %24, %25, %26, %27, %28, %29, %30, %31}, "
    "{%32, %33, %34, %35}, %36, p, 1, 1, 1;\n}\n"
    : "+f"(d[0]), "+f"(d[1]), "+f"(d[2]), "+f"(d[3]), "+f"(d[4]), "+f"(d[5]), "+f"(d[6]), "+f"(d[7]), "+f"(d[8]), "+f"(d[9]), "+f"(d[10]), "+f"(d[11]), "+f"(d[12]), "+f"(d[13]), "+f"(d[14]), "+f"(d[15]), "+f"(d[16]), "+f"(d[17]), "+f"(d[18]), "+f"(d[19]), "+f"(d[20]), "+f"(d[21]), "+f"(d[22]), "+f"(d[23]), "+f"(d[24]), "+f"(d[25]), "+f"(d[26]), "+f"(d[27]), "+f"(d[28]), "+f"(d[29]), "+f"(d[30]), "+f"(d[31])
    : "r"(a[0]), "r"(a[1]), "r"(a[2]), "r"(a[3]), "l"(desc), "r"(scale_d));
}
__device__ __forceinline__ void wgmma_rs_n72(float (&d)[36], const uint32_t* a, uint64_t desc, int scale_d) {
  asm volatile("{\n.reg .pred p;\nsetp.ne.b32 p, %41, 0;\n"
    "wgmma.mma_async.sync.aligned.m64n72k16.f32.bf16.bf16 "
    "{%0, %1, %2, %3, %4, %5, %6, %7, %8, %9, %10, %11, %12, %13, %14, %15, %16, %17, %18, %19, %20, %21, %22, %23, %24, %25, %26, %27, %28, %29, %30, %31, %32, %33, %34, %35}, "
    "{%36, %37, %38, %39}, %40, p, 1, 1, 1;\n}\n"
    : "+f"(d[0]), "+f"(d[1]), "+f"(d[2]), "+f"(d[3]), "+f"(d[4]), "+f"(d[5]), "+f"(d[6]), "+f"(d[7]), "+f"(d[8]), "+f"(d[9]), "+f"(d[10]), "+f"(d[11]), "+f"(d[12]), "+f"(d[13]), "+f"(d[14]), "+f"(d[15]), "+f"(d[16]), "+f"(d[17]), "+f"(d[18]), "+f"(d[19]), "+f"(d[20]), "+f"(d[21]), "+f"(d[22]), "+f"(d[23]), "+f"(d[24]), "+f"(d[25]), "+f"(d[26]), "+f"(d[27]), "+f"(d[28]), "+f"(d[29]), "+f"(d[30]), "+f"(d[31]), "+f"(d[32]), "+f"(d[33]), "+f"(d[34]), "+f"(d[35])
    : "r"(a[0]), "r"(a[1]), "r"(a[2]), "r"(a[3]), "l"(desc), "r"(scale_d));
}
__device__ __forceinline__ void wgmma_rs_n24(float (&d)[12], const uint32_t* a, uint64_t desc, int scale_d) {
  asm volatile("{\n.reg .pred p;\nsetp.ne.b32 p, %17, 0;\n"
    "wgmma.mma_async.sync.aligned.m64n24k16.f32.bf16.bf16 "
    "{%0, %1, %2, %3, %4, %5, %6, %7, %8, %9, %10, %11}, "
    "{%12, %13, %14, %15}, %16, p, 1, 1, 1;\n}\n"
    : "+f"(d[0]), "+f"(d[1]), "+f"(d[2]), "+f"(d[3]), "+f"(d[4]), "+f"(d[5]), "+f"(d[6]), "+f"(d[7]), "+f"(d[8]), "+f"(d[9]), "+f"(d[10]), "+f"(d[11])
    : "r"(a[0]), "r"(a[1]), "r"(a[2]), "r"(a[3]), "l"(desc), "r"(scale_d));
}

__device__ __forceinline__ void mbar_init(uint32_t a, uint32_t c) { asm volatile("mbarrier.init.shared::cta.b64 [%0], %1;" :: "r"(a), "r"(c)); }
__device__ __forceinline__ void mbar_arrive(uint32_t a) { asm volatile("mbarrier.arrive.shared::cta.b64 _, [%0];" :: "r"(a) : "memory"); }
__device__ __forceinline__ void mbar_wait_trap(uint32_t a, uint32_t ph) {
  asm volatile("{\n.reg .pred p;\n.reg .u32 n;\nmov.u32 n, 0;\n"
               "W: mbarrier.try_wait.parity.shared::cta.b64 p, [%0], %1;\n@p bra D;\n"
               "add.u32 n, n, 1;\nsetp.lt.u32 p, n, 4194304;\n@p bra W;\ntrap;\nD:\n}" :: "r"(a), "r"(ph) : "memory");
}
__device__ __forceinline__ void mbar_wait(uint32_t a, uint32_t ph) {
  asm volatile("{\n.reg .pred p;\nW: mbarrier.try_wait.parity.shared::cta.b64 p, [%0], %1;\n@!p bra W;\n}" :: "r"(a), "r"(ph) : "memory");
}
__device__ __forceinline__ void mbar_wait_sleep(uint32_t a, uint32_t ph) {
  asm volatile("{\n.reg .pred p;\nW: mbarrier.test_wait.parity.shared::cta.b64 p, [%0], %1;\n@p bra D;\nnanosleep.u32 %2;\nbra W;\nD:\n}" :: "r"(a), "r"(ph), "n"(SLEEP) : "memory");
}
__device__ __forceinline__ void wg_fence() { asm volatile("wgmma.fence.sync.aligned;" ::: "memory"); }
__device__ __forceinline__ void wg_commit() { asm volatile("wgmma.commit_group.sync.aligned;" ::: "memory"); }
template <int N> __device__ __forceinline__ void wg_wait() { asm volatile("wgmma.wait_group.sync.aligned %0;" :: "n"(N) : "memory"); }
__device__ __forceinline__ float tanh_ap(float x) { float y; asm("tanh.approx.f32 %0, %1;" : "=f"(y) : "f"(x)); return y; }
__device__ __forceinline__ float ex2(float x) { float y; asm("ex2.approx.ftz.f32 %0, %1;" : "=f"(y) : "f"(x)); return y; }
__device__ __forceinline__ uint32_t pack_bf16(float lo, float hi) { uint32_t r; asm("cvt.rn.bf16x2.f32 %0, %1, %2;" : "=r"(r) : "f"(hi), "f"(lo)); return r; }
__device__ __forceinline__ float bf_lo(uint32_t v) { return __uint_as_float(v << 16); }
__device__ __forceinline__ float bf_hi(uint32_t v) { return __uint_as_float(v & 0xffff0000u); }
__device__ __forceinline__ uint32_t sub_bf16x2(uint32_t a, uint32_t b) { uint32_t r; asm("sub.rn.bf16x2 %0, %1, %2;" : "=r"(r) : "r"(a), "r"(b)); return r; }
__device__ __forceinline__ uint32_t mul_bf16x2(uint32_t a, uint32_t b) { uint32_t r; asm("mul.rn.bf16x2 %0, %1, %2;" : "=r"(r) : "r"(a), "r"(b)); return r; }
__device__ __forceinline__ uint32_t diff2(uint32_t a, uint32_t b, uint32_t t) { uint32_t r; asm("lop3.b32 %0, %1, %2, %3, 0x7e;" : "=r"(r) : "r"(a), "r"(b), "r"(t)); return r; }
__device__ __forceinline__ uint32_t or3(uint32_t a, uint32_t b, uint32_t c) { uint32_t r; asm("lop3.b32 %0, %1, %2, %3, 0xfe;" : "=r"(r) : "r"(a), "r"(b), "r"(c)); return r; }
__device__ __forceinline__ uint32_t umin2(uint32_t a, uint32_t b) { uint32_t r; asm("min.u32 %0, %1, %2;" : "=r"(r) : "r"(a), "r"(b)); return r; }
__device__ __forceinline__ uint32_t bitmask(uint32_t v, int bit) { uint32_t r; asm("bfe.s32 %0, %1, %2, 1;" : "=r"(r) : "r"(v), "r"(bit)); return r; }
__device__ __forceinline__ uint32_t nz(uint32_t w) { return w == 0u ? 0x8000u : w; }

__device__ __forceinline__ void ldg4(uint32_t* d, const uint4* p) {
  asm volatile("ld.relaxed.gpu.global.v4.b32 {%0,%1,%2,%3}, [%4];" : "=r"(d[0]), "=r"(d[1]), "=r"(d[2]), "=r"(d[3]) : "l"(p) : "memory");
}
__device__ __forceinline__ void ldg2(uint32_t* d, const void* p) {
  asm volatile("ld.relaxed.gpu.global.v2.b32 {%0,%1}, [%2];" : "=r"(d[0]), "=r"(d[1]) : "l"(p) : "memory");
}
__device__ __forceinline__ void stg4(uint4* p, uint32_t a, uint32_t b, uint32_t c, uint32_t d) {
  asm volatile("st.relaxed.gpu.global.v4.b32 [%0], {%1,%2,%3,%4};" :: "l"(p), "r"(a), "r"(b), "r"(c), "r"(d) : "memory");
}
__device__ __forceinline__ void stg2(void* p, uint32_t a, uint32_t b) {
  asm volatile("st.relaxed.gpu.global.v2.b32 [%0], {%1,%2};" :: "l"(p), "r"(a), "r"(b) : "memory");
}
__device__ __forceinline__ void sts4(uint32_t a, const uint32_t* o) { asm volatile("st.shared.v4.b32 [%0], {%1,%2,%3,%4};" :: "r"(a), "r"(o[0]), "r"(o[1]), "r"(o[2]), "r"(o[3]) : "memory"); }
__device__ __forceinline__ void lds4(uint32_t a, uint32_t* o) { asm volatile("ld.shared.v4.b32 {%0,%1,%2,%3}, [%4];" : "=r"(o[0]), "=r"(o[1]), "=r"(o[2]), "=r"(o[3]) : "r"(a) : "memory"); }
__device__ __forceinline__ void lds2(uint32_t a, uint32_t* o) { asm volatile("ld.shared.v2.b32 {%0,%1}, [%2];" : "=r"(o[0]), "=r"(o[1]) : "r"(a) : "memory"); }
__device__ __forceinline__ float rcp(float x) { float y; asm("rcp.approx.ftz.f32 %0, %1;" : "=f"(y) : "f"(x)); return y; }
__device__ __forceinline__ void sts1(uint32_t a, uint32_t v) { asm volatile("st.shared.b32 [%0], %1;" :: "r"(a), "r"(v) : "memory"); }
__device__ __forceinline__ void ldsm4(uint32_t a, uint32_t& r0, uint32_t& r1, uint32_t& r2, uint32_t& r3) {
  asm volatile("ldmatrix.sync.aligned.m8n8.x4.shared.b16 {%0,%1,%2,%3}, [%4];" : "=r"(r0), "=r"(r1), "=r"(r2), "=r"(r3) : "r"(a) : "memory");
}
__device__ __forceinline__ void ldsm4t(uint32_t a, uint32_t& r0, uint32_t& r1, uint32_t& r2, uint32_t& r3) {
  asm volatile("ldmatrix.sync.aligned.m8n8.x4.trans.shared.b16 {%0,%1,%2,%3}, [%4];" : "=r"(r0), "=r"(r1), "=r"(r2), "=r"(r3) : "r"(a) : "memory");
}
__device__ __forceinline__ void mma16c(float* d, const uint32_t* a, uint32_t b0, uint32_t b1, float c01) {
  asm("mma.sync.aligned.m16n8k16.row.col.f32.bf16.bf16.f32 {%0,%1,%2,%3}, {%4,%5,%6,%7}, {%8,%9}, {%10,%10,%10,%10};"
    : "=f"(d[0]), "=f"(d[1]), "=f"(d[2]), "=f"(d[3]) : "r"(a[0]), "r"(a[1]), "r"(a[2]), "r"(a[3]), "r"(b0), "r"(b1), "f"(c01));
}
__device__ __forceinline__ void mma8(float* c, uint32_t a0, uint32_t a1, uint32_t b0) {
  asm("mma.sync.aligned.m16n8k8.row.col.f32.bf16.bf16.f32 {%0,%1,%2,%3}, {%4,%5}, {%6}, {%0,%1,%2,%3};"
    : "+f"(c[0]), "+f"(c[1]), "+f"(c[2]), "+f"(c[3]) : "r"(a0), "r"(a1), "r"(b0));
}
__device__ __forceinline__ uint32_t lane_id() { uint32_t l; asm volatile("mov.u32 %0, %%laneid;" : "=r"(l)); return l; }
__device__ __forceinline__ float quad_sum(float v) { v += __shfl_xor_sync(~0u, v, 1); v += __shfl_xor_sync(~0u, v, 2); return v; }
__device__ __forceinline__ float quad_max(float v) { v = fmaxf(v, __shfl_xor_sync(~0u, v, 1)); v = fmaxf(v, __shfl_xor_sync(~0u, v, 2)); return v; }
template <int N> __device__ __forceinline__ void pin(float (&d)[N]) {
#pragma unroll
  for (int i = 0; i < N; i++) asm volatile("" : "+f"(d[i]) :: "memory");
}
#define SPIN_GUARD(n) if (++(n) > SPIN_MAX) break

template <int NG> __device__ __forceinline__ void publish_stats(uint4* dst, const float* y, uint32_t tag, uint32_t lane) {
  float s0 = 0.f, s1 = 0.f;
#pragma unroll
  for (int g = 0; g < NG; g++) { s0 += y[4 * g] + y[4 * g + 1]; s1 += y[4 * g + 2] + y[4 * g + 3]; }
  s0 = quad_sum(s0); s1 = quad_sum(s1);
  const float m0 = s0 * (1.f / (8 * NG)), m1 = s1 * (1.f / (8 * NG));
  float q0 = 0.f, q1 = 0.f, q2 = 0.f, q3 = 0.f;
#pragma unroll
  for (int g = 0; g < NG; g++) {
    const float a = y[4 * g] - m0, b = y[4 * g + 1] - m0, c = y[4 * g + 2] - m1, d = y[4 * g + 3] - m1;
    q0 = fmaf(a, a, q0); q1 = fmaf(b, b, q1); q2 = fmaf(c, c, q2); q3 = fmaf(d, d, q3);
  }
  q0 = quad_sum(q0 + q1); q2 = quad_sum(q2 + q3);
  if ((lane & 3) == 0)
    stg4(dst + (lane >> 2), (__float_as_uint(s0) & ~1u) | tag, __float_as_uint(q0), __float_as_uint(s1), __float_as_uint(q2));
}

__device__ __forceinline__ void put72(uint4* slab, uint32_t j, uint32_t lane, const uint32_t* v, uint32_t r0, uint32_t r1) {
  uint4* p = slab + ((9 * j + 1) >> 1) * 32;
#pragma unroll
  for (int i = 0; i < 4; i++) stg4(p + lane + i * 32, nz(v[4 * i]), v[4 * i + 1], v[4 * i + 2], v[4 * i + 3]);
  stg2((char*)((j & 1) ? p - 16 : p + 4 * 32) + lane * 8, nz(r0), r1);
}
__device__ __forceinline__ void zero_share(uint4* slab, uint32_t j, uint32_t lane) {
  uint4* p = slab + j * 144 + lane;
#pragma unroll
  for (int i = 0; i < 4; i++) stg4(p + i * 32, 0u, 0u, 0u, 0u);
  if (lane < 16) stg4(p + 128, 0u, 0u, 0u, 0u);
}

struct Maps { CUtensorMap m[7]; };

struct Ring {
  uint32_t st, ph;
  __device__ __forceinline__ void next() { if (++st == NST) { st = 0; ph ^= 1; } }
};

#define GSTAMP(i) do {} while (0)
#define STAMP(i) do {} while (0)
#define ZSTAMP(m, i) do {} while (0)

__device__ __forceinline__ void tma_box(uint32_t dst, const CUtensorMap* m, int col, int row, uint32_t bar, uint32_t expect) {
  asm volatile("{\n.reg .pred e, h;\nelect.sync _|e, 0xffffffff;\nsetp.ne.and.u32 h, %5, 0, e;\n"
               "@h mbarrier.arrive.expect_tx.shared::cta.b64 _, [%2], %5;\n"
               "@e cp.async.bulk.tensor.2d.shared::cluster.global.mbarrier::complete_tx::bytes [%0], [%1, {%3, %4}], [%2];\n}"
               :: "r"(dst), "l"(m), "r"(bar), "r"(col), "r"(row), "r"(expect) : "memory");
}

__device__ __forceinline__ void bulk_load(uint32_t dst, const void* src, uint32_t bytes, uint32_t bar, bool arm) {
  asm volatile("{\n.reg .pred e, h;\nelect.sync _|e, 0xffffffff;\nsetp.ne.and.u32 h, %4, 0, e;\n"
               "@h mbarrier.arrive.expect_tx.shared::cta.b64 _, [%3], %2;\n"
               "@e cp.async.bulk.shared::cluster.global.mbarrier::complete_tx::bytes [%0], [%1], %2, [%3];\n}"
               :: "r"(dst), "l"(src), "r"(bytes), "r"(bar), "r"((uint32_t)arm) : "memory");
}

__global__ void __launch_bounds__(384, 1) mega_kernel(
    const __grid_constant__ Maps maps, uint4* __restrict__ scratch,
    const __nv_bfloat16* __restrict__ x_in, __nv_bfloat16* __restrict__ out) {
  extern __shared__ __align__(1024) uint8_t smem[];
  const uint32_t sb = (uint32_t)__cvta_generic_to_shared(smem);
  const uint32_t full0 = sb + BARS, empty0 = full0 + 8 * NST, rem_full = empty0 + 8 * NST, park_free = rem_full + 8, kv_free = park_free + 8;
  const uint32_t c8_go = kv_free + 8, c8_done = c8_go + 8, c8_full = c8_done + 8, remo_full = c8_full + 8, piece_full = remo_full + 8, xb_done = piece_full + 8, res_full = xb_done + 8, pbar0 = res_full + 8;
  const uint32_t w = __shfl_sync(~0u, threadIdx.x >> 5, 0);
  uint32_t pair = blockIdx.x >> 1;
  if (gridDim.x == 132) {
    uint32_t smid;
    asm("mov.u32 %0, %%smid;" : "=r"(smid));
    const uint32_t tpc = smid >> 1;
    if (tpc == 60 || tpc == 61) { if (threadIdx.x == 0) { __nanosleep(20000); } return; }
    pair = tpc < 32 ? tpc : tpc >= 62 ? (tpc - 58) * 8 : 33 + (tpc - 32) / 7 * 8 + (tpc - 32) % 7;
  }
  const uint32_t rank = blockIdx.x & 1, t = (pair & 7) * 2 + rank, j = pair >> 3;
  const uint32_t sd = sb & 0x3ffff;
  const uint32_t odd = j & 1;
  uint4* const scr = scratch + t * TILE;
  {
    const uint32_t lane = lane_id(), r = lane >> 2, q = lane & 3;
    const uint32_t sl = w < 8 ? w : j, ch = w < 8 ? j : 8;
    if (w < 8 || w == 9) {
      uint32_t v[16];
      const uint4* xr = (const uint4*)(x_in + (128 * t + 32 * (sl >> 1) + 2 * (lane >> 3) + (sl & 1)) * 576 + 64 * ch) + (lane & 7);
#pragma unroll
      for (int i = 0; i < 4; i++)
        asm volatile("ld.global.nc.v4.b32 {%0,%1,%2,%3}, [%4];" : "=r"(v[4 * i]), "=r"(v[4 * i + 1]), "=r"(v[4 * i + 2]), "=r"(v[4 * i + 3]) : "l"(xr + i * 576));
      if (q == 0) {
#pragma unroll
        for (int k = 0; k < 3; k++) stg4(scr + OFF_S + (k * 8 + sl) * 96 + ch * 8 + r, 0u, 0u, 0u, 0u);
      }
      asm volatile("bar.sync 0, 384;" ::: "memory");
      asm volatile("barrier.cluster.arrive.relaxed.aligned;" ::: "memory");
      const uint32_t tb = sb + PARK + 4096 + w * 2048;
#pragma unroll
      for (int i = 0; i < 4; i++) { const uint32_t row = 4 * i + (lane >> 3); sts4(tb + row * 128 + (((lane & 7) ^ (row & 7)) << 4), v + 4 * i); }
      __syncwarp();
#pragma unroll
      for (int i = 0; i < 4; i++) {
        const uint32_t row = lane & 15, g = 2 * i + (lane >> 4);
        ldsm4(tb + row * 128 + ((g ^ (row & 7)) << 4), v[4 * i], v[4 * i + 1], v[4 * i + 2], v[4 * i + 3]);
      }
      uint4* p = scr + OFF_X + sl * SLAB + 4 * ch * 32 + lane;
      auto put = [&] {
#pragma unroll
        for (int i = 0; i < 4; i++) stg4(p + i * 32, nz(v[4 * i]), v[4 * i + 1], nz(v[4 * i + 2]), v[4 * i + 3]);
      };
      if (ch < PRI) put();
      float y[32];
#pragma unroll
      for (int i = 0; i < 16; i++) { y[2 * i] = bf_lo(v[i]); y[2 * i + 1] = bf_hi(v[i]); }
      publish_stats<8>(scr + OFF_S + sl * 96 + ch * 8, y, 1u, lane);
      if (ch >= PRI) put();
    } else {
      if (threadIdx.x == 256) {
        for (int i = 0; i < NST; i++) { mbar_init(full0 + 8 * i, 1); mbar_init(empty0 + 8 * i, 16); }
        mbar_init(rem_full, 1); mbar_init(park_free, 8); mbar_init(kv_free, 8); mbar_init(c8_go, 8); mbar_init(c8_done, 2); mbar_init(c8_full, 1); mbar_init(remo_full, 64); mbar_init(piece_full, 1); mbar_init(xb_done, 8); mbar_init(res_full, 8);
        for (int i = 0; i < 8; i++) mbar_init(pbar0 + 8 * i, 4);
        asm volatile("fence.mbarrier_init.release.cluster;" ::: "memory");
      }
      __syncwarp();
      asm volatile("bar.sync 0, 384;" ::: "memory");
      asm volatile("barrier.cluster.arrive.relaxed.aligned;" ::: "memory");
    }
    asm volatile("barrier.cluster.wait.aligned;" ::: "memory");
  }

  if (w >= 8) {
    asm volatile("setmaxnreg.dec.sync.aligned.u32 24;");
    if (w == 8) {
      uint32_t dst = sb, bar = full0, ph = 1;
#pragma unroll 1
      for (int seg = 0; seg < 34; seg++) {
        const int n = seg >= 17 ? seg - 17 : seg;
        int ma, mb, ca, cb, row = 0;
        if (n < 3) { ma = mb = n == 2; ca = 72 * j + 8 * odd + (n == 0 ? 576 : 0); cb = ca + 576; }
        else if (n < 12) { ma = 3; mb = 2; ca = cb = 576 * j + 64 * (n - 3); }
        else { ma = mb = 4; ca = n == 12 ? 512 : ((j + 2 * n) & 7) * 64; cb = ((j + 2 * n + 1) & 7) * 64; row = 576 * j; }
        const bool zip = n == 0 || n == 3, solo = n == 1 || n == 2 || n == 16;
        const CUtensorMap *pa = &maps.m[ma], *pb = &maps.m[mb];
#pragma unroll 1
        for (int st = 0; st < (solo ? 5 : 9); st++) {
          const bool s0 = !zip && st > 4, s1 = zip || st >= 4;
          const int r0 = row + (zip ? 64 * st : s0 ? 128 * st - 576 : 128 * st), r1 = zip ? r0 : st == 4 ? row : r0 + 64;
          const bool rk = rank, sm = rk ? s1 : s0;
          asm volatile("{\n.reg .pred p, e, f;\n.reg .u32 n;\nelect.sync _|e, 0xffffffff;\nsetp.ne.and.u32 f, %7, 0, e;\nmov.u32 n, 0;\n"
                       "W: mbarrier.try_wait.parity.shared::cta.b64 p, [%1+48], %2;\n@p bra D;\n"
                       "add.u32 n, n, 1;\nsetp.lt.u32 p, n, 4194304;\n@p bra W;\ntrap;\n"
                       "D: @e mbarrier.arrive.expect_tx.shared::cta.b64 _, [%1], %6;\n"
                       "@f cp.async.bulk.tensor.2d.shared::cluster.global.mbarrier::complete_tx::bytes.multicast::cluster [%0], [%3, {%4, %5}], [%1], 3;\n}"
                       :: "r"(dst + rk * 8192), "r"(bar), "r"(ph), "l"(sm ? pb : pa), "r"(sm ? cb : ca), "r"(rk ? r1 : r0),
                          "r"(solo && st == 4 ? STAGE / 2 : STAGE), "r"((uint32_t)!(rk && solo && st == 4)) : "memory");
          dst += STAGE; bar += 8;
          if (bar == full0 + 8 * NST) { dst = sb; bar = full0; ph ^= 1; }
        }
      }
      {
#pragma unroll 1
        for (int i = 0; i < NST; i++) {
          mbar_wait_trap(bar + 48, ph);
          bar += 8;
          if (bar == full0 + 8 * NST) { bar = full0; ph ^= 1; }
        }
      }
    } else if (w == 9) {
      const uint32_t lane = lane_id();
      const uint32_t stg = sb + HSTG + lane * 16;
      uint32_t fph = 0;
#pragma unroll 1
      for (uint32_t layer = 0; layer < 2; layer++) {
        uint4* xb = scr + OFF_X + ((4 + layer) * 8 + j) * SLAB + 32 * 32;
        mbar_wait_sleep(c8_go, layer);
        int n = 0;
        while (true) {
          if (lane == 0) asm volatile("mbarrier.arrive.expect_tx.shared::cta.b64 _, [%0], 18432;" :: "r"(c8_full) : "memory");
          __syncwarp();
#pragma unroll 1
          for (uint32_t s = 0; s < 9; s++)
            bulk_load(sb + HSTG + s * 2048, s < 8 ? scr + OFF_P + (j + s * 8) * SLAB + 32 * 32 : xb, 2048, c8_full, false);
          mbar_wait(c8_full, fph); fph ^= 1;
          uint32_t bad = 0;
#pragma unroll 8
          for (int s = 0; s < 32; s++) { uint32_t v; asm volatile("ld.shared.b32 %0, [%1];" : "=r"(v) : "r"(stg + s * 512) : "memory"); bad |= v ^ (1 - layer); }
          if (__all_sync(~0u, (bad & 1u) == 0u)) break;
          __nanosleep(300);
          SPIN_GUARD(n);
        }
        asm volatile("bar.arrive 7, 96;" ::: "memory");
        float s0 = 0.f, s1 = 0.f;
#pragma unroll 1
        for (int g = 0; g < 8; g++) {
          const uint32_t a = stg + (g >> 1) * 512 + (g & 1) * 8;
          float a0 = 0.f, a1 = 0.f, a2 = 0.f, a3 = 0.f;
#pragma unroll 1
          for (int b = 0; b < 3; b++) {
            uint32_t v[6];
#pragma unroll
            for (int s = 0; s < 3; s++) lds2(a + (3 * b + s) * 2048, v + 2 * s);
#pragma unroll
            for (int s = 0; s < 3; s++) { a0 += bf_lo(v[2 * s]); a1 += bf_hi(v[2 * s]); a2 += bf_lo(v[2 * s + 1]); a3 += bf_hi(v[2 * s + 1]); }
          }
          sts1(a + 18432, pack_bf16(a0, a1)); sts1(a + 18436, pack_bf16(a2, a3));
          s0 += a0 + a1; s1 += a2 + a3;
        }
        __syncwarp();
        if (lane == 0) mbar_arrive(c8_done);
        s0 = quad_sum(s0); s1 = quad_sum(s1);
        float q0 = 0.f, q1 = 0.f;
        const uint32_t ln = lane_id();
#pragma unroll 1
        for (uint32_t i = 0; i < 4; i++) {
          uint32_t x[4];
          lds4(stg + 18432 + i * 512, x);
          stg4(xb + i * 32 + ln, 0u, 0u, 0u, 0u);
          if (layer == 0) {
            stg4(xb - 3 * 8 * SLAB + i * 32 + ln, nz(x[0]), x[1], x[2], x[3]);
#pragma unroll
            for (int e = 0; e < 4; e++) {
              const float m = (e & 1) ? s1 : s0, c = fmaf(m, -1.f / 64, bf_lo(x[e])), d = fmaf(m, -1.f / 64, bf_hi(x[e]));
              if (e & 1) q1 = fmaf(c, c, fmaf(d, d, q1)); else q0 = fmaf(c, c, fmaf(d, d, q0));
            }
          } else {
            uint32_t* o = (uint32_t*)(out + (128 * t + 32 * (j >> 1) + 2 * (ln >> 2) + (j & 1)) * 576 + 512 + 16 * i + 2 * (ln & 3));
            o[0] = x[0]; o[8 * 576] = x[1]; o[4] = x[2]; o[8 * 576 + 4] = x[3];
          }
        }
        if (layer == 0) {
          q0 = quad_sum(q0); q1 = quad_sum(q1);
          if ((ln & 3) == 0) stg4(scr + OFF_S + j * 96 + 64 + (ln >> 2), __float_as_uint(s0) & ~1u, __float_as_uint(q0), __float_as_uint(s1), __float_as_uint(q1));
        }
      }
    } else {
      auto phase2_duties = [&](uint32_t layer) {
        const uint32_t lane = lane_id();
        asm volatile("bar.sync 7, 96;" ::: "memory");
        if (w == 11) {
          if (layer == 0) {
#pragma unroll 1
            for (uint32_t k = 0; k < 6; k++) stg4(scr + OFF_S + (k * 4 + (lane >> 3)) * 96 + j * 8 + (lane & 7), 1u, 0u, 0u, 0u);
          }
          __syncwarp();
          if (lane == 0) mbar_arrive(c8_done);
        }
        mbar_wait_sleep(res_full, layer);
#pragma unroll 1
        for (uint32_t i = 0; i < 4; i++) {
          uint4* z = scr + OFF_X + ((4 + layer) * 8 + (w - 10) * 4 + i) * SLAB + 4 * j * 32 + lane;
#pragma unroll
          for (int k = 0; k < 4; k++) stg4(z + k * 32, 0u, 0u, 0u, 0u);
          __nanosleep(300);
        }
      };
#pragma unroll 1
      for (uint32_t layer = 0; layer < 2; layer++) {
        if (w == 10) {
          if (layer == 0) {
            const uint32_t lane = lane_id();
            const uint32_t p = t >> 2;
            tma_box(sb + PARK, &maps.m[p == 3 ? 6 : 5], 72 * j + (odd ? 0 : 64) + (p < 2 ? 576 * (p + 1) : 0), 144 * (t & 3), piece_full, 2304);
            mbar_wait(piece_full, 0);
            asm volatile("{\n.reg .pred e;\nelect.sync _|e, 0xffffffff;\n@e cp.async.bulk.global.shared::cta.bulk_group [%0], [%1], 2304;\n}\n"
                         "cp.async.bulk.commit_group;\ncp.async.bulk.wait_group 0;\nfence.proxy.async;"
                         :: "l"(scratch + OFF_R + j * 2304 + t * 144), "r"(sb + PARK) : "memory");
            __syncwarp();
            if (FEN & 1) { if (lane < 16) asm volatile("st.release.gpu.global.b32 [%0], 1;" :: "l"((uint32_t*)(scratch + OFF_F + (lane * 8 + j) * 8) + t) : "memory"); }
            else if (lane < 16) asm volatile("st.relaxed.gpu.global.b32 [%0], 1;" :: "l"((uint32_t*)(scratch + OFF_F + (lane * 8 + j) * 8) + t) : "memory");
            uint32_t* fl = (uint32_t*)(scratch + OFF_F + (t * 8 + j) * 8) + (lane & 15);
            uint32_t v;
            int n = 0;
            while (true) {
              if (FEN & 2) asm volatile("ld.acquire.gpu.global.b32 %0, [%1];" : "=r"(v) : "l"(fl) : "memory");
              else asm volatile("ld.relaxed.gpu.global.b32 %0, [%1];" : "=r"(v) : "l"(fl) : "memory");
              if (__all_sync(~0u, v != 0u)) break;
              __nanosleep(100);
              SPIN_GUARD(n);
            }
            if (FEN & 4) asm volatile("ld.acquire.gpu.global.b32 %0, [%1];" : "=r"(v) : "l"(fl) : "memory");
            asm volatile("fence.proxy.async;\nst.relaxed.gpu.global.b32 [%0], 0;" :: "l"(fl) : "memory");
          } else {
            mbar_wait_sleep(park_free, 0);
          }
          bulk_load(sb + REM, scratch + OFF_R + j * 2304, 36864, rem_full, true);
        }
        mbar_wait_sleep(rem_full, layer);
#pragma unroll 1
        for (uint32_t b = 0; b < 5; b++) {
          const uint32_t blk = sb + REM + 27648 + b * 2048, k = (w - 10) * 32 + lane_id(), rr = k & 7;
          const uint32_t dst = blk + ((k >> 3) & 1) * 1024 + rr * 128 + (((k >> 4) ^ rr) << 4);
          uint32_t v[8];
          lds4(blk + k * 16, v); lds4(blk + 1024 + k * 16, v + 4);
          asm volatile("bar.sync 3, 64;" ::: "memory");
          sts4(dst, v); sts4(dst ^ 64, v + 4);
        }
        asm volatile("fence.proxy.async.shared::cta;" ::: "memory");
        mbar_arrive(remo_full);
        if (layer) { phase2_duties(0); mbar_wait_sleep(kv_free, 0); }
        if (t > 0) {
          const uint32_t lane = lane_id(), r = lane >> 2, q = lane & 3;
#pragma unroll 1
          for (uint32_t pc = 0; pc < 3; pc++) {
            uint4* hp = scr + OFF_H + ((layer * 8 + j) * 2 + (w - 10)) * 192 + pc * 64 + lane;
            uint32_t hl[8];
            int n = 0;
            hl[4] = 1u;
            while (true) {
              ldg4(hl, hp);
              if (pc < 2) ldg4(hl + 4, hp + 32);
              if (__all_sync(~0u, hl[0] != 0u && hl[4] != 0u)) break;
              __nanosleep(100);
              SPIN_GUARD(n);
            }
            const uint32_t dst = sb + KVS + (w - 10) * 10368 + r * 144 + q * 4;
            if (pc < 2) {
#pragma unroll
              for (int g = 0; g < 8; g++) sts1(dst + pc * 20736 + odd * 16 + g * 16, hl[g]);
              stg4(hp + 32, 0u, 0u, 0u, 0u);
            } else {
              sts1(dst + (odd ? 0 : 128), hl[0]); sts1(dst + 20736 + (odd ? 0 : 128), hl[1]);
            }
            stg4(hp, 0u, 0u, 0u, 0u);
          }
        }
        asm volatile("bar.arrive 1, 192;" ::: "memory");
        mbar_wait_sleep(xb_done, layer);
#pragma unroll 1
        for (uint32_t i = 0; i < 8; i++) {
          zero_share(scr + OFF_X + ((w - 10) * 16 + layer * 8 + i) * SLAB, j, lane_id());
          __nanosleep(500);
        }
      }
      phase2_duties(1);
    }
  } else {
    asm volatile("setmaxnreg.inc.sync.aligned.u32 240;");
    const bool lead = lane_id() == 0;
    Ring rg{0, 0};
    uint32_t prev = 0;
    uint32_t X[144];
    float rs0, rs1;
    uint32_t mean0, mean1;
    const bool lead2 = lane_id() < 2;
    uint32_t empty_at;
    asm volatile("mapa.shared::cluster.u32 %0, %1, %2;" : "=r"(empty_at) : "r"(empty0), "r"(lane_id() & 1));
    auto release = [&](uint32_t st) { if (lead2) asm volatile("mbarrier.arrive.shared::cluster.b64 _, [%0];" :: "r"(empty_at + st * 8) : "memory"); };
    auto load_kb = [&](int kb, const uint4* src, const char* lo, uint32_t hoff) {
#pragma unroll
      for (int k = 4 * kb; k < 4 * kb + 4; k++) {
        if (k % 9 == 4) { ldg2(X + 4 * k, lo + k * 512); ldg2(X + 4 * k + 2, lo + hoff + k * 512); }
        else ldg4(X + 4 * k, src + k * 32);
      }
    };
    auto next_kb = [&](bool center, int kb, const uint4* src, const char* lo, uint32_t hoff) {
      int n = 0;
      while (true) {
        uint32_t m = umin2(umin2(X[16 * kb], X[16 * kb + 4]), umin2(X[16 * kb + 8], X[16 * kb + 12]));
        if (kb & 1) m = umin2(m, X[16 * kb + 4 * (kb >> 1) + 2]);
        if (__all_sync(~0u, m != 0u)) break;
        SPIN_GUARD(n);
        load_kb(kb, src, lo, hoff);
      }
      if (kb + (center ? GD : GO) < 9) load_kb(kb + (center ? GD : GO), src, lo, hoff);
      if (center) {
#pragma unroll
        for (int i = 16 * kb; i < 16 * kb + 16; i++) X[i] = sub_bf16x2(X[i], (i & 1) ? mean1 : mean0);
      }
    };
#pragma unroll 1
    for (uint32_t hf = 0; hf < 4; hf++) {
      const uint32_t layer = hf >> 1;
      const bool ffn = hf & 1;
      const uint32_t tag = 1 - layer;
      uint4* const xbase = scr + OFF_X + (layer * 8 + w) * SLAB;
      float aA[32], aB[32];
      {
        const uint32_t lane = lane_id(), r = lane >> 2, q = lane & 3;
        const uint4* src = xbase + (ffn ? 32 * SLAB : 0) + lane;
        const char* lo = (const char*)src - (ffn ? lane * 8 : 0);
        const uint32_t hoff = ffn ? 256 : 8;
        uint32_t s[3][4];
        const uint4* p = scr + OFF_S + ((ffn ? 16 : 0) + w) * 96 + q * 8 + r;
        const bool third = !ffn && q == 0;
        int n = 0;
        s[2][0] = tag; s[2][1] = s[2][2] = s[2][3] = 0u;
        STAMP(ffn * 16 + 0);
        while (true) {
          ldg4(s[0], p); ldg4(s[1], p + 32);
          if (third) ldg4(s[2], p + 64);
          if (__all_sync(~0u, ((diff2(s[0][0], s[1][0], tag) | diff2(s[1][0], s[2][0], tag)) & 1u) == 0u)) break;
          SPIN_GUARD(n);
        }
        STAMP(ffn * 16 + 1);
        ZSTAMP(1 + ffn, 0);
        GSTAMP(14 + ffn);
#pragma unroll
        for (int kb = 0; kb < GD; kb++) load_kb(kb, src, lo, hoff);
        float t0 = 0.f, t1 = 0.f;
#pragma unroll
        for (int i = 0; i < 3; i++) { t0 += __uint_as_float(s[i][0]); t1 += __uint_as_float(s[i][2]); }
        const float m0 = quad_sum(t0) * (1.f / 576), m1 = quad_sum(t1) * (1.f / 576);
        const float cnt = ffn ? 72.f : 64.f, inv = ffn ? 1.f / 72 : 1.f / 64;
        float v0 = 0.f, v1 = 0.f;
#pragma unroll
        for (int i = 0; i < 3; i++) {
          const float c = (i < 2 || third) ? cnt : 0.f;
          const float d0 = fmaf(__uint_as_float(s[i][0]), inv, -m0), d1 = fmaf(__uint_as_float(s[i][2]), inv, -m1);
          v0 += fmaf(d0 * d0, c, __uint_as_float(s[i][1])); v1 += fmaf(d1 * d1, c, __uint_as_float(s[i][3]));
        }
        rs0 = rsqrtf(fmaf(quad_sum(v0), 1.f / 576, 1e-5f)); rs1 = rsqrtf(fmaf(quad_sum(v1), 1.f / 576, 1e-5f));
        mean0 = pack_bf16(m0, m0); mean1 = pack_bf16(m1, m1);
#pragma unroll
        for (int kb = 0; kb < 9; kb++) {
          next_kb(true, kb, src, lo, hoff);
          ZSTAMP(1 + ffn, 1 + 3 * kb);
          mbar_wait(full0 + rg.st * 8, rg.ph);
          ZSTAMP(1 + ffn, 2 + 3 * kb);
          const uint64_t desc = DESC_HI | ((sd + rg.st * STAGE) >> 4);
          wg_fence();
#pragma unroll
          for (int i = 0; i < 4; i++) wgmma_rs_n64(aA, X + 4 * (4 * kb + i), desc + i * 128, kb + i != 0);
          if (SPLITZ && kb == 8) { wg_commit(); wg_wait<1>(); wg_fence(); }
#pragma unroll
          for (int i = 0; i < 4; i++) wgmma_rs_n64(aB, X + 4 * (4 * kb + i), desc + 512 + i * 128, kb + i != 0);
          wg_commit();
          wg_wait<1>();
          ZSTAMP(1 + ffn, 3 + 3 * kb);
          if (kb > 0) release(prev);
          prev = rg.st; rg.next();
        }
        if (!SPLITZ) wg_wait<0>();
        ZSTAMP(1 + ffn, 28);
        ZSTAMP(4, 0);
        STAMP(ffn * 16 + 2);
      }
      if (!ffn) {
      const uint32_t lane = lane_id(), r = lane >> 2, q = lane & 3;
      const uint32_t kvrow = sb + KVS + (w & 1) * 10368 + (16 * (w >> 1)) * 144;
      uint32_t Q[18], Km[3][8], Ke[3][4];
      const bool edge = (t == 0 && w < 2);
      const uint32_t row0 = edge ? sb + KVS + 8 * 144 : kvrow + (lane & 7) * 144, row1 = kvrow + (8 + (lane & 7)) * 144;
      {
        const uint32_t dst = kvrow + (8 + r) * 144 + q * 4 + odd * 16, dstr = dst + (odd ? -16 : 128);
        const bool edge_out = w >= 6 && t < 15;
        uint4* const hp = scr + TILE + OFF_H + ((layer * 8 + j) * 2 + (w & 1)) * 192 + lane;
        auto put_kv = [&](float (&a)[32], int part) {
          pin(a);
          uint32_t hl[8];
#pragma unroll
          for (int g = 0; g < 8; g++) {
            hl[g] = pack_bf16(a[4 * g + 2] * rs1, a[4 * g + 3] * rs1);
            sts1(dst + part * 20736 + g * 16, pack_bf16(a[4 * g] * rs0, a[4 * g + 1] * rs0)); sts1(dst + part * 20736 + 8 * 144 + g * 16, hl[g]);
          }
          if (edge_out) { stg4(hp + part * 64, nz(hl[0]), hl[1], hl[2], hl[3]); stg4(hp + part * 64 + 32, nz(hl[4]), hl[5], hl[6], hl[7]); }
        };
        put_kv(aA, 0);
        wg_wait<0>();
        release(prev);
        float aR[12];
        mbar_wait(rem_full, layer);
        const uint64_t dr = DESC_REM | ((sd + REM) >> 4);
        wg_fence();
#pragma unroll
        for (int s = 0; s < 36; s++) {
          wgmma_rs_n24(aR, X + 4 * s, dr + s * 16, s != 0);
          if (s == 4) put_kv(aB, 1);
        }
        wg_commit();
#pragma unroll
        for (int kb = 0; kb < 9; kb++) {
          if (kb == HOFF1 && w < 4) asm volatile("bar.sync 4, 256;" ::: "memory");
          if (kb == 8 && HOFF1 < 9 && w >= 4) asm volatile("bar.arrive 4, 256;" ::: "memory");
          if (!(kb & 1)) mbar_wait(full0 + rg.st * 8, rg.ph);
          const uint64_t desc = DESC_HI | ((sd + rg.st * STAGE + (kb & 1) * 8192) >> 4);
          wg_fence();
#pragma unroll
          for (int i = 0; i < 4; i++) wgmma_rs_n64(aB, X + 4 * (4 * kb + i), desc + i * 128, kb + i != 0);
          wg_commit();
          wg_wait<1>();
          if (kb > 0 && !(kb & 1)) release(prev);
          if ((kb & 1) || kb == 8) { prev = rg.st; rg.next(); }
          if (kb == 0) {
            pin(aR);
            const uint32_t k1 = pack_bf16(aR[2] * rs1, aR[3] * rs1), v1 = pack_bf16(aR[6] * rs1, aR[7] * rs1);
            if (edge_out) stg4(hp + 128, nz(k1), v1, 0u, 0u);
            sts1(dstr, pack_bf16(aR[0] * rs0, aR[1] * rs0)); sts1(dstr + 8 * 144, k1);
            sts1(dstr + 20736, pack_bf16(aR[4] * rs0, aR[5] * rs0)); sts1(dstr + 20736 + 8 * 144, v1);
            Q[16] = pack_bf16(aR[8], aR[9]); Q[17] = pack_bf16(aR[10], aR[11]);
            if (w < 4) asm volatile("bar.arrive 2, 256;" ::: "memory");
          }
          if (kb == KLD) {
            if (w < 4) asm volatile("bar.sync 1, 192;" ::: "memory");
            else asm volatile("bar.sync 2, 256;" ::: "memory");
#pragma unroll
            for (int nt = 0; nt < 3; nt++) {
              const uint32_t ra = (nt == 0 ? row0 : row1 + (nt - 1) * 8 * 144);
              ldsm4(ra + odd * 16 + (lane >> 3) * 16, Km[nt][0], Km[nt][1], Km[nt][2], Km[nt][3]);
              ldsm4(ra + odd * 16 + 64 + (lane >> 3) * 16, Km[nt][4], Km[nt][5], Km[nt][6], Km[nt][7]);
              ldsm4(ra + (odd ? 0 : 32) + (lane >> 3) * 32, Ke[nt][0], Ke[nt][1], Ke[nt][2], Ke[nt][3]);
            }
            const uint32_t ge = (2u << q) - 1, le = 0xfu << q, on = edge ? 0u : ~0u;
            const uint32_t bits = odd ? 0xfu | ((le & 0xfu) << 4) | (ge << 8) : ge | 0xf0u | (le << 8);
#pragma unroll
            for (int h = 0; h < 4; h++) {
              const uint32_t ma = bitmask(bits, h), mb = bitmask(bits, 4 + h), mc = bitmask(bits, 8 + h);
              Km[0][2 * h] &= ma & on; Km[0][2 * h + 1] &= mb & on; Ke[0][h] &= mc & on;
#pragma unroll
              for (int nt = 1; nt < 3; nt++) { Km[nt][2 * h] &= ma; Km[nt][2 * h + 1] &= mb; Ke[nt][h] &= mc; }
            }
          }
        }
        wg_wait<0>();
        release(prev);
        pin(aB);
        STAMP(3);
#pragma unroll
        for (int i = 0; i < 16; i++) Q[i] = pack_bf16(aB[2 * i], aB[2 * i + 1]);
      }
      {
        uint32_t V01[12][2], V2[12];
        const uint32_t rv = ((lane & 8) ? row1 : row0) + 20736, rw = row1 + 8 * 144 + 20736;
#pragma unroll
        for (int i = 0; i < 4; i++) ldsm4t(rv + odd * 16 + i * 32 + (lane >> 4) * 16, V01[2 * i][0], V01[2 * i][1], V01[2 * i + 1][0], V01[2 * i + 1][1]);
#pragma unroll
        for (int i = 0; i < 2; i++) ldsm4t(rv + (odd ? 0 : 32) + i * 64 + (lane >> 4) * 32, V01[8 + 2 * i][0], V01[8 + 2 * i][1], V01[9 + 2 * i][0], V01[9 + 2 * i][1]);
        ldsm4t(rw + odd * 16 + (lane >> 3) * 16, V2[0], V2[1], V2[2], V2[3]);
        ldsm4t(rw + odd * 16 + 64 + (lane >> 3) * 16, V2[4], V2[5], V2[6], V2[7]);
        ldsm4t(rw + (odd ? 0 : 32) + (lane >> 3) * 32, V2[8], V2[9], V2[10], V2[11]);
        const bool up0 = 2 * q > r, up1 = 2 * q + 1 > r;
        const uint32_t upm = (up0 ? 0xffffu : 0u) | (up1 ? 0xffff0000u : 0u);
        const float c0 = 0.23570226039551584f * 1.4426950408889634f * rs0, c1 = 0.23570226039551584f * 1.4426950408889634f * rs1;
        const float masked = edge ? -1e9f * 1.4426950408889634f * rcp(c0) : 0.f;
        uint32_t Om[16], Oe[8];
#pragma unroll
        for (int h = 0; h < 4; h++) {
          const uint32_t e0 = odd ? Q[(4 * h + 16) % 18] : Q[4 * h + 4], e1 = odd ? Q[(4 * h + 17) % 18] : Q[4 * h + 5];
          float S[3][4];
#pragma unroll
          for (int nt = 0; nt < 3; nt++) {
            mma16c(S[nt], Q + 4 * h, Km[nt][2 * h], Km[nt][2 * h + 1], nt == 0 ? masked : 0.f);
            mma8(S[nt], e0, e1, Ke[nt][h]);
          }
          const float s00 = up0 ? S[0][0] : S[1][0], s01 = up1 ? S[0][1] : S[1][1];
          const float s10 = up0 ? S[1][2] : S[2][2], s11 = up1 ? S[1][3] : S[2][3];
          const float m0 = quad_max(fmaxf(s00, s01)) * c0, m1 = quad_max(fmaxf(s10, s11)) * c1;
          const float p00 = ex2(fmaf(s00, c0, -m0)), p01 = ex2(fmaf(s01, c0, -m0)), p10 = ex2(fmaf(s10, c1, -m1)), p11 = ex2(fmaf(s11, c1, -m1));
          const float i0 = rcp(quad_sum(p00 + p01)), i1 = rcp(quad_sum(p10 + p11));
          const uint32_t p0 = pack_bf16(p00 * i0, p01 * i0), p1 = pack_bf16(p10 * i1, p11 * i1);
          const uint32_t pf[4] = {p0 & upm, 0u, p0 & ~upm, p1 & upm};
#pragma unroll
          for (int gi = 0; gi < 3; gi++) {
            const int g = gi < 2 ? 2 * h + gi : 8 + h;
            float o[4];
            mma16c(o, pf, V01[g][0], V01[g][1], 0.f);
            mma8(o, 0u, p1 & ~upm, V2[g]);
            uint32_t* d = gi < 2 ? Om + 2 * g : Oe + 2 * h;
            d[0] = pack_bf16(o[0], o[1]); d[1] = pack_bf16(o[2], o[3]);
          }
        }
#pragma unroll
        for (int h = 0; h < 4; h++)
#pragma unroll
          for (int e = 0; e < 2; e++) {
            if (h > 0 && !odd && q < h) Om[4 * h + e] = Oe[2 * h - 2 + e];
            if (h < 3 && odd && q > h) Om[4 * h + 2 + e] = Oe[2 * h + 2 + e];
          }
        STAMP(4);
        if (j >= PRI && lane == 0) asm volatile("st.relaxed.gpu.global.b32 [%0], %1;" :: "l"(scr + OFF_S + (8 + w) * 96 + j * 8), "r"(tag) : "memory");
        put72(xbase + 16 * SLAB, j, lane, Om, odd ? Oe[0] : Oe[6], odd ? Oe[1] : Oe[7]);
      }
      if (j < PRI && lane == 0) asm volatile("st.relaxed.gpu.global.b32 [%0], %1;" :: "l"(scr + OFF_S + (8 + w) * 96 + j * 8), "r"(tag) : "memory");
      {
        uint32_t res[18];
        const uint4* p = xbase + ((9 * j + 1) >> 1) * 32 + lane;
#pragma unroll
        for (int i = 0; i < 4; i++) ldg4(res + 4 * i, p + i * 32);
        ldg2(res + 16, odd ? (const char*)(p - 32) + 8 : (const char*)(p + 4 * 32));
        const uint4* src = xbase + 16 * SLAB + lane;
        {
          const uint4* fp = scr + OFF_S + (8 + w) * 96 + (lane & 7) * 8;
          int n = 0;
          mbar_wait(remo_full, layer);
          STAMP(8);
          while (true) {
            uint32_t f;
            asm volatile("ld.relaxed.gpu.global.b32 %0, [%1];" : "=r"(f) : "l"(fp) : "memory");
            if (__all_sync(~0u, f == tag)) break;
            SPIN_GUARD(n);
          }
          STAMP(9);
        }
        if (HOFF3 < 9 && w < 4) asm volatile("bar.sync 6, 256;" ::: "memory");
#pragma unroll
        for (int kb = 0; kb < GO; kb++) load_kb(kb, src, (const char*)src - lane * 8, 256);
        float acc[36];
#pragma unroll
        for (int i = 0; i < 18; i++) { acc[2 * i] = bf_lo(res[i]); acc[2 * i + 1] = bf_hi(res[i]); }
#pragma unroll
        for (int kb = 0; kb < 9; kb++) {
          next_kb(false, kb, src, (const char*)src - lane * 8, 256);
          if (kb == HOFF3 && w >= 4) asm volatile("bar.arrive 6, 256;" ::: "memory");
          if (!(kb & 1)) mbar_wait(full0 + rg.st * 8, rg.ph);
          const uint32_t base = sd + rg.st * STAGE + (kb & 1) * 8192;
          const uint64_t d0 = DESC_HI | ((base >> 4) + (((sd + REM + 27648 + (kb >> 1) * 2048 + (kb & 1) * 64 - base) >> 4) << 16));
          wg_fence();
#pragma unroll
          for (int i = 0; i < 4; i++) wgmma_rs_n72(acc, X + 4 * (4 * kb + i), d0 - (uint64_t)(i * ((127u << 16) - 128u)), 1);
          wg_commit();
          wg_wait<1>();
          if (kb > 0 && !(kb & 1)) release(prev);
          if ((kb & 1) || kb == 8) { prev = rg.st; rg.next(); }
        }
        wg_wait<0>();
        release(prev);
        pin(acc);
        STAMP(10);
#pragma unroll
        for (int i = 0; i < 18; i++) res[i] = pack_bf16(acc[2 * i], acc[2 * i + 1]);
        if (j < PRI) put72(xbase + 32 * SLAB, j, lane, res, res[16], res[17]);
        publish_stats<9>(scr + OFF_S + (16 + w) * 96 + j * 8, acc, tag, lane);
        if (j >= PRI) put72(xbase + 32 * SLAB, j, lane, res, res[16], res[17]);
      }
      continue;
      }
      const uint32_t hp = sb + PARK + w * 512 + lane_id() * 16;
      auto pack8 = [&](float (&a)[32], int p, uint32_t* o) {
#pragma unroll
        for (int e = 0; e < 8; e++) asm volatile("" : "+f"(a[8 * p + e]) :: "memory");
#pragma unroll
        for (int e = 0; e < 4; e++) o[e] = pack_bf16(a[8 * p + 2 * e], a[8 * p + 2 * e + 1]);
      };
      const float ka0 = 0.7978845608028654f * rs0, kb0 = 0.044715f * ka0 * rs0 * rs0, ku0 = 0.5f * rs0 * rs0;
      const float ka1 = 0.7978845608028654f * rs1, kb1 = 0.044715f * ka1 * rs1 * rs1, ku1 = 0.5f * rs1 * rs1;
      auto packu8 = [&](int p, uint32_t* o) {
#pragma unroll
        for (int e = 0; e < 8; e++) asm volatile("" : "+f"(aA[8 * p + e]) :: "memory");
#pragma unroll
        for (int e = 0; e < 4; e++) o[e] = pack_bf16(aA[8 * p + 2 * e] * ((e & 1) ? ku1 : ku0), aA[8 * p + 2 * e + 1] * ((e & 1) ? ku1 : ku0));
      };
      auto geglu8 = [&](int p, uint32_t* u) {
#pragma unroll
        for (int e = 0; e < 8; e++) asm volatile("" : "+f"(aB[8 * p + e]) :: "memory");
        float h[8];
#pragma unroll
        for (int e = 0; e < 8; e++) {
          const float g = aB[8 * p + e];
          h[e] = fmaf(g, tanh_ap(g * fmaf(g * g, (e & 2) ? kb1 : kb0, (e & 2) ? ka1 : ka0)), g);
        }
#pragma unroll
        for (int e = 0; e < 4; e++) u[e] = mul_bf16x2(pack_bf16(h[2 * e], h[2 * e + 1]), u[e]);
      };
      auto box = [&](int b, auto&& filler) {
        const int kb = b < 9 ? b : b - 9;
        if (!(b & 1)) { if ((TRAPB >> (b >> 1)) & 1) mbar_wait_trap(full0 + rg.st * 8, rg.ph); else mbar_wait(full0 + rg.st * 8, rg.ph); }
        const uint64_t desc = DESC_HI | ((sd + rg.st * STAGE + (b & 1) * 8192) >> 4);
        wg_fence();
#pragma unroll
        for (int i = 0; i < 4; i++) {
          if (b < 9) wgmma_rs_n64(aA, X + 4 * (4 * kb + i), desc + i * 128, kb + i != 0);
          else wgmma_rs_n64(aB, X + 4 * (4 * kb + i), desc + i * 128, kb + i != 0);
          if (i == FPOS) filler();
        }
        wg_commit();
        if (b & 1) { prev = rg.st; rg.next(); } else { wg_wait<1>(); release(prev); }
      };
      auto nop = [] {};
      auto step = [&](int st, auto&& filler) { box(2 * st, nop); box(2 * st + 1, filler); };
#pragma unroll
      for (int p = 0; p < 4; p++) { uint32_t o[4]; packu8(p, o); sts4(hp + p * 4096, o); }
      box(0, nop);
      if (lead) mbar_arrive(xb_done);
#pragma unroll 1
      for (int c = 1;; c++) {
        const uint32_t hc = hp + c * 4 * 4096;
#pragma unroll
        for (int b = 1; b < 18; b++) box(b, [&] {
          if ((b & 1) && b < 8) { uint32_t o[4]; const uint32_t a = hc - (4 - (b >> 1)) * 4096; lds4(a, o); geglu8(b >> 1, o); sts4(a, o); }
          if ((b & 1) && b > 10) { uint32_t o[4]; packu8((b - 11) >> 1, o); if (c < 8) sts4(hc + ((b - 11) >> 1) * 4096, o); } });
        ZSTAMP(4, c);
        if (c == 8) break;
        box(0, nop);
      }
      wg_wait<0>();
      STAMP(21);
      GSTAMP(19);
      auto unpark = [&](int kb) {
#pragma unroll
        for (int s = 4 * kb; s < 4 * kb + 4; s++) lds4(hp + s * 4096, X + 4 * s);
      };
      unpark(0);
      uint32_t U[16];
#pragma unroll
      for (int p = 0; p < 4; p++) packu8(p, U + 4 * p);
#pragma unroll
      for (int b = 0; b < 8; b++) box(b, [&] {
        if (b < 7) unpark(b + 1);
        if (b & 1) {
          geglu8(b >> 1, U + 2 * (b - 1));
          if (rg.ph > 1) sts4(hp, U + 2 * (b - 1));
#pragma unroll
          for (int i = 0; i < 4; i++) X[128 + 2 * (b - 1) + i] = U[2 * (b - 1) + i];
        } });
      STAMP(24);
      if (layer == 0 && lead) mbar_arrive(park_free);
      const uint32_t lane2 = lane_id();
      uint4* const pw = scr + OFF_P + (j * 8 + w) * SLAB + lane2;
      const uint4* const pr = scr + OFF_P + w * SLAB + 4 * j * 32 + lane2;
      auto put_part = [&](float (&a)[32], int p, uint32_t chunk) {
        uint32_t o[4];
        pack8(a, p, o);
        stg4(pw + (chunk * 4 + p) * 32, (o[0] & ~1u) | tag, o[1], o[2], o[3]);
      };
      uint4* const xb = xbase + 32 * SLAB + 4 * j * 32;
      auto slot = [&](int p) { return sb + w * 2048 + (p < 3 ? PARK + p * 16384 : KVS + (p - 3) * 16384); };
      auto fetch = [&](int p) {
        bulk_load(slot(p), p ? scr + OFF_P + (((j - p) & 7) * 8 + w) * SLAB + 4 * j * 32 : xb, 2048, p ? pbar0 + w * 8 : res_full, true);
      };
#pragma unroll 1
      for (int sp = 0;; sp++) {
        const uint32_t ca = sp == 0 ? 8 : ((j + 2 * sp) & 7), cb = (j + 2 * sp + 1) & 7;
        if (C8 == 1 && sp == 1 && lead) mbar_arrive(c8_go);
#pragma unroll
        for (int st = 4; st < 9; st++) step(st, [&] {
          if (st == 5 || st == 6) { put_part(aA, 2 * (st - 5), ca); put_part(aA, 2 * (st - 5) + 1, ca); }
          if (st == 8 && sp > 0) { if (sp == 3) mbar_wait(c8_done, layer); fetch(2 * sp - 2); } });
        STAMP(25 + sp);
        if (sp == 3) break;
        if (C8 == 0 && sp == 0 && lead) mbar_arrive(c8_go);
#pragma unroll
        for (int st = 0; st < 4; st++) step(st, [&] {
          if (st < 2) { put_part(aB, 2 * st, cb); put_part(aB, 2 * st + 1, cb); }
          if (st == 3 && sp > 0) fetch(2 * sp - 1); });
      }
      auto load_p = [&](int p, uint32_t* d) {
#pragma unroll
        for (int i = 0; i < 4; i++) ldg4(d + 4 * i, pr + ((j - p) & 7) * 8 * SLAB + i * 32);
      };
#pragma unroll
      for (int b = 0; b < 9; b++) {
        if (b == HOFF2 && w < 4) asm volatile("bar.sync 5, 256;" ::: "memory");
        box(b, [&] {
          if (b == 1) {
#pragma unroll
            for (int p = 0; p < 4; p++) put_part(aB, p, (j + 7) & 7);
          }
          if (b == 3) { load_p(5, X); load_p(6, X + 16); }
          if (b == 7 && EXP != 1) load_p(7, X + 32); });
        if (b == 7 && HOFF2 < 9 && w >= 4) asm volatile("bar.arrive 5, 256;" ::: "memory");
      }
      mbar_wait(res_full, layer);
      mbar_wait(pbar0 + w * 8, layer);
#pragma unroll
      for (int p = 1; p < 5; p++)
#pragma unroll
        for (int i = 0; i < 4; i++) lds4(slot(p) + lane2 * 16 + i * 512, X + 48 + 16 * p + 4 * i);
#pragma unroll
      for (int i = 0; i < 4; i++) {
        const bool split = j == 2 * i + 1;
        const uint32_t a = slot(0) + i * 512 + (split ? lane2 * 8 : lane2 * 16);
        lds2(a, X + 48 + 4 * i); lds2(a + (split ? 256 : 8), X + 50 + 4 * i);
      }
      wg_wait<0>();
      release(rg.st); rg.next();
      pin(aA);
      STAMP(22);
      GSTAMP(20);
      {
        const uint32_t lane = lane2, r = lane >> 2, q = lane & 3;
        const uint32_t eye = r == 2 * q ? 0x3f80u : r == 2 * q + 1 ? 0x3f800000u : 0u;
        auto bad = [&](const uint32_t* d) { return diff2(d[0], d[4], tag) | diff2(d[8], d[12], tag); };
        auto add = [&](const uint32_t* d) {
#pragma unroll
          for (int g = 0; g < 8; g++) mma8(aA + 4 * g, d[2 * g], d[2 * g + 1], eye);
        };
        int n = 0;
        while (!__all_sync(~0u, ((or3(bad(X), bad(X + 16), bad(X + 64)) | or3(bad(X + 80), bad(X + 96), bad(X + 112))) & 1u) == 0u)) {
          SPIN_GUARD(n);
          load_p(5, X); load_p(6, X + 16);
#pragma unroll
          for (int p = 1; p < 5; p++) load_p(p, X + 48 + 16 * p);
        }
        add(X); add(X + 16);
#pragma unroll
        for (int p = 4; p >= 0; p--) add(X + 48 + 16 * ((p + 1) % 5));
        STAMP(11);
        if (EXP != 1) while (!__all_sync(~0u, (bad(X + 32) & 1u) == 0u)) { SPIN_GUARD(n); load_p(7, X + 32); }
        add(X + 32);
        STAMP(12);
        uint32_t res[16];
#pragma unroll
        for (int i = 0; i < 16; i++) res[i] = pack_bf16(aA[2 * i], aA[2 * i + 1]);
        if (layer == 0) {
          uint4* p = xbase + 8 * SLAB + 4 * j * 32 + lane;
          auto put = [&] {
#pragma unroll
            for (int i = 0; i < 4; i++) stg4(p + i * 32, nz(res[4 * i]), res[4 * i + 1], nz(res[4 * i + 2]), res[4 * i + 3]);
          };
          if (j < PRI) put();
          publish_stats<8>(scr + OFF_S + w * 96 + j * 8, aA, 0u, lane);
          if (j >= PRI) put();
          if (lane == 0) mbar_arrive(kv_free);
        } else {
          const uint32_t tb = slot(0);
          __syncwarp();
#pragma unroll
          for (int i = 0; i < 4; i++) {
            const uint32_t row = (lane2 & 7) + (lane2 & 8), g = 2 * i + (lane2 >> 4);
            asm volatile("stmatrix.sync.aligned.m8n8.x4.shared.b16 [%0], {%1,%2,%3,%4};"
                         :: "r"(tb + row * 128 + ((g ^ (row & 7)) << 4)), "r"(res[4 * i]), "r"(res[4 * i + 1]), "r"(res[4 * i + 2]), "r"(res[4 * i + 3]) : "memory");
          }
          __syncwarp();
#pragma unroll
          for (int i = 0; i < 4; i++) {
            const uint32_t row = 4 * i + (lane2 >> 3), g = lane2 & 7;
            uint32_t v[4];
            lds4(tb + row * 128 + ((g ^ (row & 7)) << 4), v);
            *(uint4*)(out + (128 * t + 32 * (w >> 1) + 2 * row + (w & 1)) * 576 + 64 * j + 8 * g) = make_uint4(v[0], v[1], v[2], v[3]);
          }
        }
      }
      STAMP(23);
    }
  }
}

typedef CUresult (*EncodeFn)(CUtensorMap*, CUtensorMapDataType, cuuint32_t, void*, const cuuint64_t*, const cuuint64_t*,
                             const cuuint32_t*, const cuuint32_t*, CUtensorMapInterleave, CUtensorMapSwizzle,
                             CUtensorMapL2promotion, CUtensorMapFloatOOBfill);

CUtensorMap make_map(EncodeFn f, const void* p, uint64_t cols, uint64_t rows, bool rem = false) {
  CUtensorMap m;
  cuuint64_t dims[2] = {cols, rows};
  cuuint64_t str[1] = {cols * 2};
  cuuint32_t box[2] = {rem ? 8u : 64u, rem ? 144u : 64u};
  cuuint32_t es[2] = {1, 1};
  f(&m, CU_TENSOR_MAP_DATA_TYPE_BFLOAT16, 2, const_cast<void*>(p), dims, str, box, es, CU_TENSOR_MAP_INTERLEAVE_NONE,
    rem ? CU_TENSOR_MAP_SWIZZLE_NONE : CU_TENSOR_MAP_SWIZZLE_128B, CU_TENSOR_MAP_L2_PROMOTION_NONE, CU_TENSOR_MAP_FLOAT_OOB_FILL_NONE);
  return m;
}

}

extern "C" void kernel_launch(void* const* d_in, const int* in_sizes, int n_in, void* d_out, int out_size) {
  void* fn = nullptr;
  cudaDriverEntryPointQueryResult qr;
  cudaGetDriverEntryPoint("cuTensorMapEncodeTiled", &fn, cudaEnableDefault, &qr);
  EncodeFn enc = (EncodeFn)fn;
  Maps maps;
  maps.m[0] = make_map(enc, d_in[1], 1728, 576); maps.m[1] = make_map(enc, d_in[2], 576, 576);
  maps.m[2] = make_map(enc, d_in[4], 4608, 576); maps.m[3] = make_map(enc, d_in[5], 4608, 576); maps.m[4] = make_map(enc, d_in[6], 576, 4608);
  maps.m[5] = make_map(enc, d_in[1], 1728, 576, true); maps.m[6] = make_map(enc, d_in[2], 576, 576, true);
  void* scr = nullptr;
  cudaGetSymbolAddress(&scr, g_scratch);
  cudaFuncSetAttribute(mega_kernel, cudaFuncAttributeMaxDynamicSharedMemorySize, SMEM_BYTES);
  cudaLaunchConfig_t cfg = {};
  cfg.gridDim = dim3(128); cfg.blockDim = dim3(384); cfg.dynamicSmemBytes = SMEM_BYTES; cfg.stream = cudaStreamPerThread;
  cudaLaunchAttribute at[1];
  at[0].id = cudaLaunchAttributeClusterDimension; at[0].val.clusterDim.x = 2; at[0].val.clusterDim.y = 1; at[0].val.clusterDim.z = 1;
  cfg.attrs = at; cfg.numAttrs = 1;
  int dev = 0, sms = 0, clusters = 0;
  cudaGetDevice(&dev);
  cudaDeviceGetAttribute(&sms, cudaDevAttrMultiProcessorCount, dev);
  cudaOccupancyMaxActiveClusters(&clusters, mega_kernel, &cfg);
  if (sms == 132 && clusters == 66) cfg.gridDim = dim3(132);
  cudaLaunchKernelEx(&cfg, mega_kernel, maps, (uint4*)scr, (const __nv_bfloat16*)d_in[0], (__nv_bfloat16*)d_out);
}
```

```cpp
#include <cuda_runtime.h>
#include <cuda.h>
#include <cuda_bf16.h>
#include <stdint.h>

#define TRACE 0
#define GUARD 0
#define TRAPB 1
#define HOFF1 99
#define HOFF2 99
#define KLD 8
#define ZT 0
#define SLEEP 500
#define SPLITZ 1
#define C8 1
#define HOFF3 99
#define GO 3
#define EXP 0
#define FPOS 2

namespace {

constexpr int NST = 6;
constexpr int STAGE = 16384;
constexpr int PARK = NST * STAGE;
constexpr int REM = PARK + 49152;
constexpr int KVS = REM + 40960;
constexpr int HSTG = KVS + 16384;
constexpr int BARS = KVS + 41472;
constexpr int TRC = BARS + 256;
constexpr int SMEM_BYTES = TRC + (TRACE ? 512 : 0);
static_assert(NST == 6, "the producer addresses empty barriers as full + 48");
static_assert(BARS >= PARK + 131072, "barriers overlap park");
static_assert(SMEM_BYTES <= 232448, "smem");

constexpr int SLAB = 36 * 32;
constexpr int SPIN_MAX = 1 << 17;
constexpr uint32_t PRI = 3;
constexpr int GD = 3;
constexpr int OFF_S = 0;
constexpr int OFF_H = OFF_S + 3 * 8 * 96;
constexpr int OFF_X = OFF_H + 2 * 8 * 384;
constexpr int OFF_P = OFF_X + 6 * 8 * SLAB;
constexpr int TILE = OFF_P + 8 * 8 * SLAB;
constexpr int OFF_R = 16 * TILE;
constexpr int OFF_F = OFF_R + 8 * 2304;
constexpr int SCRATCH = OFF_F + 128 * 8;

}

__device__ uint4 g_scratch[SCRATCH];

namespace {

constexpr uint64_t DESC_HI = 0x4000004000000000ull;
constexpr uint64_t DESC_REM = (576ull << 32) | (8u << 16);
__device__ __forceinline__ void wgmma_rs_n64(float (&d)[32], const uint32_t* a, uint64_t desc, int scale_d) {
  asm volatile("{\n.reg .pred p;\nsetp.ne.b32 p, %37, 0;\n"
    "wgmma.mma_async.sync.aligned.m64n64k16.f32.bf16.bf16 "
    "{%0, %1, %2, %3, %4, %5, %6, %7, %8, %9, %10, %11, %12, %13, %14, %15, %16, %17, %18, %19, %20, %21, %22, %23, %24, %25, %26, %27, %28, %29, %30, %31}, "
    "{%32, %33, %34, %35}, %36, p, 1, 1, 1;\n}\n"
    : "+f"(d[0]), "+f"(d[1]), "+f"(d[2]), "+f"(d[3]), "+f"(d[4]), "+f"(d[5]), "+f"(d[6]), "+f"(d[7]), "+f"(d[8]), "+f"(d[9]), "+f"(d[10]), "+f"(d[11]), "+f"(d[12]), "+f"(d[13]), "+f"(d[14]), "+f"(d[15]), "+f"(d[16]), "+f"(d[17]), "+f"(d[18]), "+f"(d[19]), "+f"(d[20]), "+f"(d[21]), "+f"(d[22]), "+f"(d[23]), "+f"(d[24]), "+f"(d[25]), "+f"(d[26]), "+f"(d[27]), "+f"(d[28]), "+f"(d[29]), "+f"(d[30]), "+f"(d[31])
    : "r"(a[0]), "r"(a[1]), "r"(a[2]), "r"(a[3]), "l"(desc), "r"(scale_d));
}
__device__ __forceinline__ void wgmma_rs_n72(float (&d)[36], const uint32_t* a, uint64_t desc, int scale_d) {
  asm volatile("{\n.reg .pred p;\nsetp.ne.b32 p, %41, 0;\n"
    "wgmma.mma_async.sync.aligned.m64n72k16.f32.bf16.bf16 "
    "{%0, %1, %2, %3, %4, %5, %6, %7, %8, %9, %10, %11, %12, %13, %14, %15, %16, %17, %18, %19, %20, %21, %22, %23, %24, %25, %26, %27, %28, %29, %30, %31, %32, %33, %34, %35}, "
    "{%36, %37, %38, %39}, %40, p, 1, 1, 1;\n}\n"
    : "+f"(d[0]), "+f"(d[1]), "+f"(d[2]), "+f"(d[3]), "+f"(d[4]), "+f"(d[5]), "+f"(d[6]), "+f"(d[7]), "+f"(d[8]), "+f"(d[9]), "+f"(d[10]), "+f"(d[11]), "+f"(d[12]), "+f"(d[13]), "+f"(d[14]), "+f"(d[15]), "+f"(d[16]), "+f"(d[17]), "+f"(d[18]), "+f"(d[19]), "+f"(d[20]), "+f"(d[21]), "+f"(d[22]), "+f"(d[23]), "+f"(d[24]), "+f"(d[25]), "+f"(d[26]), "+f"(d[27]), "+f"(d[28]), "+f"(d[29]), "+f"(d[30]), "+f"(d[31]), "+f"(d[32]), "+f"(d[33]), "+f"(d[34]), "+f"(d[35])
    : "r"(a[0]), "r"(a[1]), "r"(a[2]), "r"(a[3]), "l"(desc), "r"(scale_d));
}
__device__ __forceinline__ void wgmma_rs_n24(float (&d)[12], const uint32_t* a, uint64_t desc, int scale_d) {
  asm volatile("{\n.reg .pred p;\nsetp.ne.b32 p, %17, 0;\n"
    "wgmma.mma_async.sync.aligned.m64n24k16.f32.bf16.bf16 "
    "{%0, %1, %2, %3, %4, %5, %6, %7, %8, %9, %10, %11}, "
    "{%12, %13, %14, %15}, %16, p, 1, 1, 1;\n}\n"
    : "+f"(d[0]), "+f"(d[1]), "+f"(d[2]), "+f"(d[3]), "+f"(d[4]), "+f"(d[5]), "+f"(d[6]), "+f"(d[7]), "+f"(d[8]), "+f"(d[9]), "+f"(d[10]), "+f"(d[11])
    : "r"(a[0]), "r"(a[1]), "r"(a[2]), "r"(a[3]), "l"(desc), "r"(scale_d));
}

__device__ __forceinline__ void mbar_init(uint32_t a, uint32_t c) { asm volatile("mbarrier.init.shared::cta.b64 [%0], %1;" :: "r"(a), "r"(c)); }
__device__ __forceinline__ void mbar_arrive(uint32_t a) { asm volatile("mbarrier.arrive.shared::cta.b64 _, [%0];" :: "r"(a) : "memory"); }
__device__ __forceinline__ void mbar_wait_trap(uint32_t a, uint32_t ph) {
  asm volatile("{\n.reg .pred p;\n.reg .u32 n;\nmov.u32 n, 0;\n"
               "W: mbarrier.try_wait.parity.shared::cta.b64 p, [%0], %1;\n@p bra D;\n"
               "add.u32 n, n, 1;\nsetp.lt.u32 p, n, 4194304;\n@p bra W;\ntrap;\nD:\n}" :: "r"(a), "r"(ph) : "memory");
}
__device__ __forceinline__ void mbar_wait(uint32_t a, uint32_t ph) {
  asm volatile("{\n.reg .pred p;\nW: mbarrier.try_wait.parity.shared::cta.b64 p, [%0], %1;\n@!p bra W;\n}" :: "r"(a), "r"(ph) : "memory");
}
__device__ __forceinline__ void mbar_wait_sleep(uint32_t a, uint32_t ph) {
  asm volatile("{\n.reg .pred p;\nW: mbarrier.test_wait.parity.shared::cta.b64 p, [%0], %1;\n@p bra D;\nnanosleep.u32 %2;\nbra W;\nD:\n}" :: "r"(a), "r"(ph), "n"(SLEEP) : "memory");
}
__device__ __forceinline__ void wg_fence() { asm volatile("wgmma.fence.sync.aligned;" ::: "memory"); }
__device__ __forceinline__ void wg_commit() { asm volatile("wgmma.commit_group.sync.aligned;" ::: "memory"); }
template <int N> __device__ __forceinline__ void wg_wait() { asm volatile("wgmma.wait_group.sync.aligned %0;" :: "n"(N) : "memory"); }
__device__ __forceinline__ float tanh_ap(float x) { float y; asm("tanh.approx.f32 %0, %1;" : "=f"(y) : "f"(x)); return y; }
__device__ __forceinline__ float ex2(float x) { float y; asm("ex2.approx.ftz.f32 %0, %1;" : "=f"(y) : "f"(x)); return y; }
__device__ __forceinline__ uint32_t pack_bf16(float lo, float hi) { uint32_t r; asm("cvt.rn.bf16x2.f32 %0, %1, %2;" : "=r"(r) : "f"(hi), "f"(lo)); return r; }
__device__ __forceinline__ float bf_lo(uint32_t v) { return __uint_as_float(v << 16); }
__device__ __forceinline__ float bf_hi(uint32_t v) { return __uint_as_float(v & 0xffff0000u); }
__device__ __forceinline__ uint32_t sub_bf16x2(uint32_t a, uint32_t b) { uint32_t r; asm("sub.rn.bf16x2 %0, %1, %2;" : "=r"(r) : "r"(a), "r"(b)); return r; }
__device__ __forceinline__ uint32_t mul_bf16x2(uint32_t a, uint32_t b) { uint32_t r; asm("mul.rn.bf16x2 %0, %1, %2;" : "=r"(r) : "r"(a), "r"(b)); return r; }
__device__ __forceinline__ uint32_t diff2(uint32_t a, uint32_t b, uint32_t t) { uint32_t r; asm("lop3.b32 %0, %1, %2, %3, 0x7e;" : "=r"(r) : "r"(a), "r"(b), "r"(t)); return r; }
__device__ __forceinline__ uint32_t or3(uint32_t a, uint32_t b, uint32_t c) { uint32_t r; asm("lop3.b32 %0, %1, %2, %3, 0xfe;" : "=r"(r) : "r"(a), "r"(b), "r"(c)); return r; }
__device__ __forceinline__ uint32_t umin2(uint32_t a, uint32_t b) { uint32_t r; asm("min.u32 %0, %1, %2;" : "=r"(r) : "r"(a), "r"(b)); return r; }
__device__ __forceinline__ uint32_t bitmask(uint32_t v, int bit) { uint32_t r; asm("bfe.s32 %0, %1, %2, 1;" : "=r"(r) : "r"(v), "r"(bit)); return r; }
__device__ __forceinline__ uint32_t nz(uint32_t w) { return w == 0u ? 0x8000u : w; }

__device__ __forceinline__ void ldg4(uint32_t* d, const uint4* p) {
  asm volatile("ld.relaxed.gpu.global.v4.b32 {%0,%1,%2,%3}, [%4];" : "=r"(d[0]), "=r"(d[1]), "=r"(d[2]), "=r"(d[3]) : "l"(p) : "memory");
}
__device__ __forceinline__ void ldg2(uint32_t* d, const void* p) {
  asm volatile("ld.relaxed.gpu.global.v2.b32 {%0,%1}, [%2];" : "=r"(d[0]), "=r"(d[1]) : "l"(p) : "memory");
}
__device__ __forceinline__ void stg4(uint4* p, uint32_t a, uint32_t b, uint32_t c, uint32_t d) {
  asm volatile("st.relaxed.gpu.global.v4.b32 [%0], {%1,%2,%3,%4};" :: "l"(p), "r"(a), "r"(b), "r"(c), "r"(d) : "memory");
}
__device__ __forceinline__ void stg2(void* p, uint32_t a, uint32_t b) {
  asm volatile("st.relaxed.gpu.global.v2.b32 [%0], {%1,%2};" :: "l"(p), "r"(a), "r"(b) : "memory");
}
__device__ __forceinline__ void sts4(uint32_t a, const uint32_t* o) { asm volatile("st.shared.v4.b32 [%0], {%1,%2,%3,%4};" :: "r"(a), "r"(o[0]), "r"(o[1]), "r"(o[2]), "r"(o[3]) : "memory"); }
__device__ __forceinline__ void lds4(uint32_t a, uint32_t* o) { asm volatile("ld.shared.v4.b32 {%0,%1,%2,%3}, [%4];" : "=r"(o[0]), "=r"(o[1]), "=r"(o[2]), "=r"(o[3]) : "r"(a) : "memory"); }
__device__ __forceinline__ void lds2(uint32_t a, uint32_t* o) { asm volatile("ld.shared.v2.b32 {%0,%1}, [%2];" : "=r"(o[0]), "=r"(o[1]) : "r"(a) : "memory"); }
__device__ __forceinline__ float rcp(float x) { float y; asm("rcp.approx.ftz.f32 %0, %1;" : "=f"(y) : "f"(x)); return y; }
__device__ __forceinline__ void sts1(uint32_t a, uint32_t v) { asm volatile("st.shared.b32 [%0], %1;" :: "r"(a), "r"(v) : "memory"); }
__device__ __forceinline__ void ldsm4(uint32_t a, uint32_t& r0, uint32_t& r1, uint32_t& r2, uint32_t& r3) {
  asm volatile("ldmatrix.sync.aligned.m8n8.x4.shared.b16 {%0,%1,%2,%3}, [%4];" : "=r"(r0), "=r"(r1), "=r"(r2), "=r"(r3) : "r"(a) : "memory");
}
__device__ __forceinline__ void ldsm4t(uint32_t a, uint32_t& r0, uint32_t& r1, uint32_t& r2, uint32_t& r3) {
  asm volatile("ldmatrix.sync.aligned.m8n8.x4.trans.shared.b16 {%0,%1,%2,%3}, [%4];" : "=r"(r0), "=r"(r1), "=r"(r2), "=r"(r3) : "r"(a) : "memory");
}
__device__ __forceinline__ void mma16c(float* d, const uint32_t* a, uint32_t b0, uint32_t b1, float c01) {
  asm("mma.sync.aligned.m16n8k16.row.col.f32.bf16.bf16.f32 {%0,%1,%2,%3}, {%4,%5,%6,%7}, {%8,%9}, {%10,%10,%10,%10};"
    : "=f"(d[0]), "=f"(d[1]), "=f"(d[2]), "=f"(d[3]) : "r"(a[0]), "r"(a[1]), "r"(a[2]), "r"(a[3]), "r"(b0), "r"(b1), "f"(c01));
}
__device__ __forceinline__ void mma8(float* c, uint32_t a0, uint32_t a1, uint32_t b0) {
  asm("mma.sync.aligned.m16n8k8.row.col.f32.bf16.bf16.f32 {%0,%1,%2,%3}, {%4,%5}, {%6}, {%0,%1,%2,%3};"
    : "+f"(c[0]), "+f"(c[1]), "+f"(c[2]), "+f"(c[3]) : "r"(a0), "r"(a1), "r"(b0));
}
__device__ __forceinline__ uint32_t lane_id() { uint32_t l; asm volatile("mov.u32 %0, %%laneid;" : "=r"(l)); return l; }
__device__ __forceinline__ float quad_sum(float v) { v += __shfl_xor_sync(~0u, v, 1); v += __shfl_xor_sync(~0u, v, 2); return v; }
__device__ __forceinline__ float quad_max(float v) { v = fmaxf(v, __shfl_xor_sync(~0u, v, 1)); v = fmaxf(v, __shfl_xor_sync(~0u, v, 2)); return v; }
template <int N> __device__ __forceinline__ void pin(float (&d)[N]) {
#pragma unroll
  for (int i = 0; i < N; i++) asm volatile("" : "+f"(d[i]) :: "memory");
}
#define SPIN_GUARD(n) if (++(n) > SPIN_MAX) break

template <int NG> __device__ __forceinline__ void publish_stats(uint4* dst, const float* y, uint32_t tag, uint32_t lane) {
  float s0 = 0.f, s1 = 0.f;
#pragma unroll
  for (int g = 0; g < NG; g++) { s0 += y[4 * g] + y[4 * g + 1]; s1 += y[4 * g + 2] + y[4 * g + 3]; }
  s0 = quad_sum(s0); s1 = quad_sum(s1);
  const float m0 = s0 * (1.f / (8 * NG)), m1 = s1 * (1.f / (8 * NG));
  float q0 = 0.f, q1 = 0.f, q2 = 0.f, q3 = 0.f;
#pragma unroll
  for (int g = 0; g < NG; g++) {
    const float a = y[4 * g] - m0, b = y[4 * g + 1] - m0, c = y[4 * g + 2] - m1, d = y[4 * g + 3] - m1;
    q0 = fmaf(a, a, q0); q1 = fmaf(b, b, q1); q2 = fmaf(c, c, q2); q3 = fmaf(d, d, q3);
  }
  q0 = quad_sum(q0 + q1); q2 = quad_sum(q2 + q3);
  if ((lane & 3) == 0)
    stg4(dst + (lane >> 2), (__float_as_uint(s0) & ~1u) | tag, __float_as_uint(q0), __float_as_uint(s1), __float_as_uint(q2));
}

__device__ __forceinline__ void put72(uint4* slab, uint32_t j, uint32_t lane, const uint32_t* v, uint32_t r0, uint32_t r1) {
  uint4* p = slab + ((9 * j + 1) >> 1) * 32;
#pragma unroll
  for (int i = 0; i < 4; i++) stg4(p + lane + i * 32, nz(v[4 * i]), v[4 * i + 1], v[4 * i + 2], v[4 * i + 3]);
  stg2((char*)((j & 1) ? p - 16 : p + 4 * 32) + lane * 8, nz(r0), r1);
}
__device__ __forceinline__ void zero_share(uint4* slab, uint32_t j, uint32_t lane) {
  uint4* p = slab + j * 144 + lane;
#pragma unroll
  for (int i = 0; i < 4; i++) stg4(p + i * 32, 0u, 0u, 0u, 0u);
  if (lane < 16) stg4(p + 128, 0u, 0u, 0u, 0u);
}

struct Maps { CUtensorMap m[7]; };

struct Ring {
  uint32_t st, ph;
  __device__ __forceinline__ void next() { if (++st == NST) { st = 0; ph ^= 1; } }
};

#define GSTAMP(i) do {} while (0)
#define STAMP(i) do {} while (0)
#define ZSTAMP(m, i) do {} while (0)

__device__ __forceinline__ void tma_box(uint32_t dst, const CUtensorMap* m, int col, int row, uint32_t bar, uint32_t expect) {
  asm volatile("{\n.reg .pred e, h;\nelect.sync _|e, 0xffffffff;\nsetp.ne.and.u32 h, %5, 0, e;\n"
               "@h mbarrier.arrive.expect_tx.shared::cta.b64 _, [%2], %5;\n"
               "@e cp.async.bulk.tensor.2d.shared::cluster.global.mbarrier::complete_tx::bytes [%0], [%1, {%3, %4}], [%2];\n}"
               :: "r"(dst), "l"(m), "r"(bar), "r"(col), "r"(row), "r"(expect) : "memory");
}

__device__ __forceinline__ void bulk_load(uint32_t dst, const void* src, uint32_t bytes, uint32_t bar, bool arm) {
  asm volatile("{\n.reg .pred e, h;\nelect.sync _|e, 0xffffffff;\nsetp.ne.and.u32 h, %4, 0, e;\n"
               "@h mbarrier.arrive.expect_tx.shared::cta.b64 _, [%3], %2;\n"
               "@e cp.async.bulk.shared::cluster.global.mbarrier::complete_tx::bytes [%0], [%1], %2, [%3];\n}"
               :: "r"(dst), "l"(src), "r"(bytes), "r"(bar), "r"((uint32_t)arm) : "memory");
}

__global__ void __launch_bounds__(384, 1) mega_kernel(
    const __grid_constant__ Maps maps, uint4* __restrict__ scratch,
    const __nv_bfloat16* __restrict__ x_in, __nv_bfloat16* __restrict__ out) {
  extern __shared__ __align__(1024) uint8_t smem[];
  const uint32_t sb = (uint32_t)__cvta_generic_to_shared(smem);
  const uint32_t full0 = sb + BARS, empty0 = full0 + 8 * NST, rem_full = empty0 + 8 * NST, park_free = rem_full + 8, kv_free = park_free + 8;
  const uint32_t c8_go = kv_free + 8, c8_done = c8_go + 8, c8_full = c8_done + 8, remo_full = c8_full + 8, piece_full = remo_full + 8, xb_done = piece_full + 8, res_full = xb_done + 8, pbar0 = res_full + 8;
  const uint32_t w = __shfl_sync(~0u, threadIdx.x >> 5, 0);
  uint32_t pair = blockIdx.x >> 1;
  if (gridDim.x == 132) {
    uint32_t smid;
    asm("mov.u32 %0, %%smid;" : "=r"(smid));
    const uint32_t tpc = smid >> 1;
    if (tpc == 60 || tpc == 61) { if (threadIdx.x == 0) { __nanosleep(20000); } return; }
    pair = tpc < 32 ? tpc : tpc >= 62 ? (tpc - 58) * 8 : 33 + (tpc - 32) / 7 * 8 + (tpc - 32) % 7;
  }
  const uint32_t rank = blockIdx.x & 1, t = (pair & 7) * 2 + rank, j = pair >> 3;
  const uint32_t sd = sb & 0x3ffff;
  const uint32_t odd = j & 1;
  uint4* const scr = scratch + t * TILE;
  {
    const uint32_t lane = lane_id(), r = lane >> 2, q = lane & 3;
    const uint32_t sl = w < 8 ? w : j, ch = w < 8 ? j : 8;
    if (w < 8 || w == 9) {
      uint32_t v[16];
      const uint4* xr = (const uint4*)(x_in + (128 * t + 32 * (sl >> 1) + 2 * (lane >> 3) + (sl & 1)) * 576 + 64 * ch) + (lane & 7);
#pragma unroll
      for (int i = 0; i < 4; i++)
        asm volatile("ld.global.nc.v4.b32 {%0,%1,%2,%3}, [%4];" : "=r"(v[4 * i]), "=r"(v[4 * i + 1]), "=r"(v[4 * i + 2]), "=r"(v[4 * i + 3]) : "l"(xr + i * 576));
      if (q == 0) {
#pragma unroll
        for (int k = 0; k < 3; k++) stg4(scr + OFF_S + (k * 8 + sl) * 96 + ch * 8 + r, 0u, 0u, 0u, 0u);
      }
      asm volatile("bar.sync 0, 384;" ::: "memory");
      asm volatile("barrier.cluster.arrive.relaxed.aligned;" ::: "memory");
      const uint32_t tb = sb + PARK + 4096 + w * 2048;
#pragma unroll
      for (int i = 0; i < 4; i++) { const uint32_t row = 4 * i + (lane >> 3); sts4(tb + row * 128 + (((lane & 7) ^ (row & 7)) << 4), v + 4 * i); }
      __syncwarp();
#pragma unroll
      for (int i = 0; i < 4; i++) {
        const uint32_t row = lane & 15, g = 2 * i + (lane >> 4);
        ldsm4(tb + row * 128 + ((g ^ (row & 7)) << 4), v[4 * i], v[4 * i + 1], v[4 * i + 2], v[4 * i + 3]);
      }
      uint4* p = scr + OFF_X + sl * SLAB + 4 * ch * 32 + lane;
      auto put = [&] {
#pragma unroll
        for (int i = 0; i < 4; i++) stg4(p + i * 32, nz(v[4 * i]), v[4 * i + 1], nz(v[4 * i + 2]), v[4 * i + 3]);
      };
      if (ch < PRI) put();
      float y[32];
#pragma unroll
      for (int i = 0; i < 16; i++) { y[2 * i] = bf_lo(v[i]); y[2 * i + 1] = bf_hi(v[i]); }
      publish_stats<8>(scr + OFF_S + sl * 96 + ch * 8, y, 1u, lane);
      if (ch >= PRI) put();
    } else {
      if (threadIdx.x == 256) {
        for (int i = 0; i < NST; i++) { mbar_init(full0 + 8 * i, 1); mbar_init(empty0 + 8 * i, 16); }
        mbar_init(rem_full, 1); mbar_init(park_free, 8); mbar_init(kv_free, 8); mbar_init(c8_go, 8); mbar_init(c8_done, 2); mbar_init(c8_full, 1); mbar_init(remo_full, 64); mbar_init(piece_full, 1); mbar_init(xb_done, 8); mbar_init(res_full, 8);
        for (int i = 0; i < 8; i++) mbar_init(pbar0 + 8 * i, 4);
        asm volatile("fence.mbarrier_init.release.cluster;" ::: "memory");
      }
      __syncwarp();
      asm volatile("bar.sync 0, 384;" ::: "memory");
      asm volatile("barrier.cluster.arrive.relaxed.aligned;" ::: "memory");
    }
    asm volatile("barrier.cluster.wait.aligned;" ::: "memory");
  }

  if (w >= 8) {
    asm volatile("setmaxnreg.dec.sync.aligned.u32 24;");
    if (w == 8) {
      uint32_t dst = sb, bar = full0, ph = 1;
#pragma unroll 1
      for (int seg = 0; seg < 34; seg++) {
        const int n = seg >= 17 ? seg - 17 : seg;
        int ma, mb, ca, cb, row = 0;
        if (n < 3) { ma = mb = n == 2; ca = 72 * j + 8 * odd + (n == 0 ? 576 : 0); cb = ca + 576; }
        else if (n < 12) { ma = 3; mb = 2; ca = cb = 576 * j + 64 * (n - 3); }
        else { ma = mb = 4; ca = n == 12 ? 512 : ((j + 2 * n) & 7) * 64; cb = ((j + 2 * n + 1) & 7) * 64; row = 576 * j; }
        const bool zip = n == 0 || n == 3, solo = n == 1 || n == 2 || n == 16;
        const CUtensorMap *pa = &maps.m[ma], *pb = &maps.m[mb];
#pragma unroll 1
        for (int st = 0; st < (solo ? 5 : 9); st++) {
          const bool s0 = !zip && st > 4, s1 = zip || st >= 4;
          const int r0 = row + (zip ? 64 * st : s0 ? 128 * st - 576 : 128 * st), r1 = zip ? r0 : st == 4 ? row : r0 + 64;
          const bool rk = rank, sm = rk ? s1 : s0;
          asm volatile("{\n.reg .pred p, e, f;\n.reg .u32 n;\nelect.sync _|e, 0xffffffff;\nsetp.ne.and.u32 f, %7, 0, e;\nmov.u32 n, 0;\n"
                       "W: mbarrier.try_wait.parity.shared::cta.b64 p, [%1+48], %2;\n@p bra D;\n"
                       "add.u32 n, n, 1;\nsetp.lt.u32 p, n, 4194304;\n@p bra W;\ntrap;\n"
                       "D: @e mbarrier.arrive.expect_tx.shared::cta.b64 _, [%1], %6;\n"
                       "@f cp.async.bulk.tensor.2d.shared::cluster.global.mbarrier::complete_tx::bytes.multicast::cluster [%0], [%3, {%4, %5}], [%1], 3;\n}"
                       :: "r"(dst + rk * 8192), "r"(bar), "r"(ph), "l"(sm ? pb : pa), "r"(sm ? cb : ca), "r"(rk ? r1 : r0),
                          "r"(solo && st == 4 ? STAGE / 2 : STAGE), "r"((uint32_t)!(rk && solo && st == 4)) : "memory");
          dst += STAGE; bar += 8;
          if (bar == full0 + 8 * NST) { dst = sb; bar = full0; ph ^= 1; }
        }
      }
      {
#pragma unroll 1
        for (int i = 0; i < NST; i++) {
          mbar_wait_trap(bar + 48, ph);
          bar += 8;
          if (bar == full0 + 8 * NST) { bar = full0; ph ^= 1; }
        }
      }
    } else if (w == 9) {
      const uint32_t lane = lane_id();
      const uint32_t stg = sb + HSTG + lane * 16;
      uint32_t fph = 0;
#pragma unroll 1
      for (uint32_t layer = 0; layer < 2; layer++) {
        uint4* xb = scr + OFF_X + ((4 + layer) * 8 + j) * SLAB + 32 * 32;
        mbar_wait_sleep(c8_go, layer);
        int n = 0;
        while (true) {
          if (lane == 0) asm volatile("mbarrier.arrive.expect_tx.shared::cta.b64 _, [%0], 18432;" :: "r"(c8_full) : "memory");
          __syncwarp();
#pragma unroll 1
          for (uint32_t s = 0; s < 9; s++)
            bulk_load(sb + HSTG + s * 2048, s < 8 ? scr + OFF_P + (j + s * 8) * SLAB + 32 * 32 : xb, 2048, c8_full, false);
          mbar_wait(c8_full, fph); fph ^= 1;
          uint32_t bad = 0;
#pragma unroll 8
          for (int s = 0; s < 32; s++) { uint32_t v; asm volatile("ld.shared.b32 %0, [%1];" : "=r"(v) : "r"(stg + s * 512) : "memory"); bad |= v ^ (1 - layer); }
          if (__all_sync(~0u, (bad & 1u) == 0u)) break;
          __nanosleep(300);
          SPIN_GUARD(n);
        }
        asm volatile("bar.arrive 7, 96;" ::: "memory");
        float s0 = 0.f, s1 = 0.f;
#pragma unroll 1
        for (int g = 0; g < 8; g++) {
          const uint32_t a = stg + (g >> 1) * 512 + (g & 1) * 8;
          float a0 = 0.f, a1 = 0.f, a2 = 0.f, a3 = 0.f;
#pragma unroll 1
          for (int b = 0; b < 3; b++) {
            uint32_t v[6];
#pragma unroll
            for (int s = 0; s < 3; s++) lds2(a + (3 * b + s) * 2048, v + 2 * s);
#pragma unroll
            for (int s = 0; s < 3; s++) { a0 += bf_lo(v[2 * s]); a1 += bf_hi(v[2 * s]); a2 += bf_lo(v[2 * s + 1]); a3 += bf_hi(v[2 * s + 1]); }
          }
          sts1(a + 18432, pack_bf16(a0, a1)); sts1(a + 18436, pack_bf16(a2, a3));
          s0 += a0 + a1; s1 += a2 + a3;
        }
        __syncwarp();
        if (lane == 0) mbar_arrive(c8_done);
        s0 = quad_sum(s0); s1 = quad_sum(s1);
        float q0 = 0.f, q1 = 0.f;
        const uint32_t ln = lane_id();
#pragma unroll 1
        for (uint32_t i = 0; i < 4; i++) {
          uint32_t x[4];
          lds4(stg + 18432 + i * 512, x);
          stg4(xb + i * 32 + ln, 0u, 0u, 0u, 0u);
          if (layer == 0) {
            stg4(xb - 3 * 8 * SLAB + i * 32 + ln, nz(x[0]), x[1], x[2], x[3]);
#pragma unroll
            for (int e = 0; e < 4; e++) {
              const float m = (e & 1) ? s1 : s0, c = fmaf(m, -1.f / 64, bf_lo(x[e])), d = fmaf(m, -1.f / 64, bf_hi(x[e]));
              if (e & 1) q1 = fmaf(c, c, fmaf(d, d, q1)); else q0 = fmaf(c, c, fmaf(d, d, q0));
            }
          } else {
            uint32_t* o = (uint32_t*)(out + (128 * t + 32 * (j >> 1) + 2 * (ln >> 2) + (j & 1)) * 576 + 512 + 16 * i + 2 * (ln & 3));
            o[0] = x[0]; o[8 * 576] = x[1]; o[4] = x[2]; o[8 * 576 + 4] = x[3];
          }
        }
        if (layer == 0) {
          q0 = quad_sum(q0); q1 = quad_sum(q1);
          if ((ln & 3) == 0) stg4(scr + OFF_S + j * 96 + 64 + (ln >> 2), __float_as_uint(s0) & ~1u, __float_as_uint(q0), __float_as_uint(s1), __float_as_uint(q1));
        }
      }
    } else {
      auto phase2_duties = [&](uint32_t layer) {
        const uint32_t lane = lane_id();
        asm volatile("bar.sync 7, 96;" ::: "memory");
        if (w == 11) {
          if (layer == 0) {
#pragma unroll 1
            for (uint32_t k = 0; k < 6; k++) stg4(scr + OFF_S + (k * 4 + (lane >> 3)) * 96 + j * 8 + (lane & 7), 1u, 0u, 0u, 0u);
          }
          __syncwarp();
          if (lane == 0) mbar_arrive(c8_done);
        }
        mbar_wait_sleep(res_full, layer);
#pragma unroll 1
        for (uint32_t i = 0; i < 4; i++) {
          uint4* z = scr + OFF_X + ((4 + layer) * 8 + (w - 10) * 4 + i) * SLAB + 4 * j * 32 + lane;
#pragma unroll
          for (int k = 0; k < 4; k++) stg4(z + k * 32, 0u, 0u, 0u, 0u);
          __nanosleep(300);
        }
      };
#pragma unroll 1
      for (uint32_t layer = 0; layer < 2; layer++) {
        if (w == 10) {
          if (layer == 0) {
            const uint32_t lane = lane_id();
            const uint32_t p = t >> 2;
            tma_box(sb + PARK, &maps.m[p == 3 ? 6 : 5], 72 * j + (odd ? 0 : 64) + (p < 2 ? 576 * (p + 1) : 0), 144 * (t & 3), piece_full, 2304);
            uint32_t* fl = (uint32_t*)(scratch + OFF_F + (t * 8 + j) * 8) + (lane & 15);
            uint32_t v;
            asm volatile("ld.relaxed.gpu.global.b32 %0, [%1];" : "=r"(v) : "l"(fl) : "memory");
            mbar_wait(piece_full, 0);
            asm volatile("{\n.reg .pred e;\nelect.sync _|e, 0xffffffff;\n@e cp.async.bulk.global.shared::cta.bulk_group [%0], [%1], 2304;\n}\n"
                         "cp.async.bulk.commit_group;\ncp.async.bulk.wait_group 0;\nfence.proxy.async;"
                         :: "l"(scratch + OFF_R + j * 2304 + t * 144), "r"(sb + PARK) : "memory");
            __syncwarp();
            if (lane < 16) asm volatile("st.release.gpu.global.b32 [%0], 1;" :: "l"((uint32_t*)(scratch + OFF_F + (lane * 8 + j) * 8) + t) : "memory");
            int n = 0;
            while (!__all_sync(~0u, v != 0u)) {
              __nanosleep(100);
              SPIN_GUARD(n);
              asm volatile("ld.relaxed.gpu.global.b32 %0, [%1];" : "=r"(v) : "l"(fl) : "memory");
            }
            asm volatile("st.relaxed.gpu.global.b32 [%0], 0;" :: "l"(fl) : "memory");
          } else {
            mbar_wait_sleep(park_free, 0);
          }
          bulk_load(sb + REM, scratch + OFF_R + j * 2304, 36864, rem_full, true);
        }
        mbar_wait_sleep(rem_full, layer);
#pragma unroll 1
        for (uint32_t b = 0; b < 5; b++) {
          const uint32_t blk = sb + REM + 27648 + b * 2048, k = (w - 10) * 32 + lane_id(), rr = k & 7;
          const uint32_t dst = blk + ((k >> 3) & 1) * 1024 + rr * 128 + (((k >> 4) ^ rr) << 4);
          uint32_t v[8];
          lds4(blk + k * 16, v); lds4(blk + 1024 + k * 16, v + 4);
          asm volatile("bar.sync 3, 64;" ::: "memory");
          sts4(dst, v); sts4(dst ^ 64, v + 4);
        }
        asm volatile("fence.proxy.async.shared::cta;" ::: "memory");
        mbar_arrive(remo_full);
        if (layer) { phase2_duties(0); mbar_wait_sleep(kv_free, 0); }
        if (t > 0) {
          const uint32_t lane = lane_id(), r = lane >> 2, q = lane & 3;
#pragma unroll 1
          for (uint32_t pc = 0; pc < 3; pc++) {
            uint4* hp = scr + OFF_H + ((layer * 8 + j) * 2 + (w - 10)) * 192 + pc * 64 + lane;
            uint32_t hl[8];
            int n = 0;
            hl[4] = 1u;
            while (true) {
              ldg4(hl, hp);
              if (pc < 2) ldg4(hl + 4, hp + 32);
              if (__all_sync(~0u, hl[0] != 0u && hl[4] != 0u)) break;
              __nanosleep(100);
              SPIN_GUARD(n);
            }
            const uint32_t dst = sb + KVS + (w - 10) * 10368 + r * 144 + q * 4;
            if (pc < 2) {
#pragma unroll
              for (int g = 0; g < 8; g++) sts1(dst + pc * 20736 + odd * 16 + g * 16, hl[g]);
              stg4(hp + 32, 0u, 0u, 0u, 0u);
            } else {
              sts1(dst + (odd ? 0 : 128), hl[0]); sts1(dst + 20736 + (odd ? 0 : 128), hl[1]);
            }
            stg4(hp, 0u, 0u, 0u, 0u);
          }
        }
        asm volatile("bar.arrive 1, 192;" ::: "memory");
        mbar_wait_sleep(xb_done, layer);
#pragma unroll 1
        for (uint32_t i = 0; i < 8; i++) {
          zero_share(scr + OFF_X + ((w - 10) * 16 + layer * 8 + i) * SLAB, j, lane_id());
          __nanosleep(500);
        }
      }
      phase2_duties(1);
    }
  } else {
    asm volatile("setmaxnreg.inc.sync.aligned.u32 240;");
    const bool lead = lane_id() == 0;
    Ring rg{0, 0};
    uint32_t prev = 0;
    uint32_t X[144];
    float rs0, rs1;
    uint32_t mean0, mean1;
    const bool lead2 = lane_id() < 2;
    uint32_t empty_at;
    asm volatile("mapa.shared::cluster.u32 %0, %1, %2;" : "=r"(empty_at) : "r"(empty0), "r"(lane_id() & 1));
    auto release = [&](uint32_t st) { if (lead2) asm volatile("mbarrier.arrive.shared::cluster.b64 _, [%0];" :: "r"(empty_at + st * 8) : "memory"); };
    auto load_kb = [&](int kb, const uint4* src, const char* lo, uint32_t hoff) {
#pragma unroll
      for (int k = 4 * kb; k < 4 * kb + 4; k++) {
        if (k % 9 == 4) { ldg2(X + 4 * k, lo + k * 512); ldg2(X + 4 * k + 2, lo + hoff + k * 512); }
        else ldg4(X + 4 * k, src + k * 32);
      }
    };
    auto next_kb = [&](bool center, int kb, const uint4* src, const char* lo, uint32_t hoff) {
      int n = 0;
      while (true) {
        uint32_t m = umin2(umin2(X[16 * kb], X[16 * kb + 4]), umin2(X[16 * kb + 8], X[16 * kb + 12]));
        if (kb & 1) m = umin2(m, X[16 * kb + 4 * (kb >> 1) + 2]);
        if (__all_sync(~0u, m != 0u)) break;
        SPIN_GUARD(n);
        load_kb(kb, src, lo, hoff);
      }
      if (kb + (center ? GD : GO) < 9) load_kb(kb + (center ? GD : GO), src, lo, hoff);
      if (center) {
#pragma unroll
        for (int i = 16 * kb; i < 16 * kb + 16; i++) X[i] = sub_bf16x2(X[i], (i & 1) ? mean1 : mean0);
      }
    };
#pragma unroll 1
    for (uint32_t hf = 0; hf < 4; hf++) {
      const uint32_t layer = hf >> 1;
      const bool ffn = hf & 1;
      const uint32_t tag = 1 - layer;
      uint4* const xbase = scr + OFF_X + (layer * 8 + w) * SLAB;
      float aA[32], aB[32];
      {
        const uint32_t lane = lane_id(), r = lane >> 2, q = lane & 3;
        const uint4* src = xbase + (ffn ? 32 * SLAB : 0) + lane;
        const char* lo = (const char*)src - (ffn ? lane * 8 : 0);
        const uint32_t hoff = ffn ? 256 : 8;
        uint32_t s[3][4];
        const uint4* p = scr + OFF_S + ((ffn ? 16 : 0) + w) * 96 + q * 8 + r;
        const bool third = !ffn && q == 0;
        int n = 0;
        s[2][0] = tag; s[2][1] = s[2][2] = s[2][3] = 0u;
        STAMP(ffn * 16 + 0);
        while (true) {
          ldg4(s[0], p); ldg4(s[1], p + 32);
          if (third) ldg4(s[2], p + 64);
          if (__all_sync(~0u, ((diff2(s[0][0], s[1][0], tag) | diff2(s[1][0], s[2][0], tag)) & 1u) == 0u)) break;
          SPIN_GUARD(n);
        }
        STAMP(ffn * 16 + 1);
        ZSTAMP(1 + ffn, 0);
        GSTAMP(14 + ffn);
#pragma unroll
        for (int kb = 0; kb < GD; kb++) load_kb(kb, src, lo, hoff);
        float t0 = 0.f, t1 = 0.f;
#pragma unroll
        for (int i = 0; i < 3; i++) { t0 += __uint_as_float(s[i][0]); t1 += __uint_as_float(s[i][2]); }
        const float m0 = quad_sum(t0) * (1.f / 576), m1 = quad_sum(t1) * (1.f / 576);
        const float cnt = ffn ? 72.f : 64.f, inv = ffn ? 1.f / 72 : 1.f / 64;
        float v0 = 0.f, v1 = 0.f;
#pragma unroll
        for (int i = 0; i < 3; i++) {
          const float c = (i < 2 || third) ? cnt : 0.f;
          const float d0 = fmaf(__uint_as_float(s[i][0]), inv, -m0), d1 = fmaf(__uint_as_float(s[i][2]), inv, -m1);
          v0 += fmaf(d0 * d0, c, __uint_as_float(s[i][1])); v1 += fmaf(d1 * d1, c, __uint_as_float(s[i][3]));
        }
        rs0 = rsqrtf(fmaf(quad_sum(v0), 1.f / 576, 1e-5f)); rs1 = rsqrtf(fmaf(quad_sum(v1), 1.f / 576, 1e-5f));
        mean0 = pack_bf16(m0, m0); mean1 = pack_bf16(m1, m1);
#pragma unroll
        for (int kb = 0; kb < 9; kb++) {
          next_kb(true, kb, src, lo, hoff);
          ZSTAMP(1 + ffn, 1 + 3 * kb);
          mbar_wait(full0 + rg.st * 8, rg.ph);
          ZSTAMP(1 + ffn, 2 + 3 * kb);
          const uint64_t desc = DESC_HI | ((sd + rg.st * STAGE) >> 4);
          wg_fence();
#pragma unroll
          for (int i = 0; i < 4; i++) wgmma_rs_n64(aA, X + 4 * (4 * kb + i), desc + i * 128, kb + i != 0);
          if (SPLITZ && kb == 8) { wg_commit(); wg_wait<1>(); wg_fence(); }
#pragma unroll
          for (int i = 0; i < 4; i++) wgmma_rs_n64(aB, X + 4 * (4 * kb + i), desc + 512 + i * 128, kb + i != 0);
          wg_commit();
          wg_wait<1>();
          ZSTAMP(1 + ffn, 3 + 3 * kb);
          if (kb > 0) release(prev);
          prev = rg.st; rg.next();
        }
        if (!SPLITZ) wg_wait<0>();
        ZSTAMP(1 + ffn, 28);
        ZSTAMP(4, 0);
        STAMP(ffn * 16 + 2);
      }
      if (!ffn) {
      const uint32_t lane = lane_id(), r = lane >> 2, q = lane & 3;
      const uint32_t kvrow = sb + KVS + (w & 1) * 10368 + (16 * (w >> 1)) * 144;
      uint32_t Q[18], Km[3][8], Ke[3][4];
      const bool edge = (t == 0 && w < 2);
      const uint32_t row0 = edge ? sb + KVS + 8 * 144 : kvrow + (lane & 7) * 144, row1 = kvrow + (8 + (lane & 7)) * 144;
      {
        const uint32_t dst = kvrow + (8 + r) * 144 + q * 4 + odd * 16, dstr = dst + (odd ? -16 : 128);
        const bool edge_out = w >= 6 && t < 15;
        uint4* const hp = scr + TILE + OFF_H + ((layer * 8 + j) * 2 + (w & 1)) * 192 + lane;
        auto put_kv = [&](float (&a)[32], int part) {
          pin(a);
          uint32_t hl[8];
#pragma unroll
          for (int g = 0; g < 8; g++) {
            hl[g] = pack_bf16(a[4 * g + 2] * rs1, a[4 * g + 3] * rs1);
            sts1(dst + part * 20736 + g * 16, pack_bf16(a[4 * g] * rs0, a[4 * g + 1] * rs0)); sts1(dst + part * 20736 + 8 * 144 + g * 16, hl[g]);
          }
          if (edge_out) { stg4(hp + part * 64, nz(hl[0]), hl[1], hl[2], hl[3]); stg4(hp + part * 64 + 32, nz(hl[4]), hl[5], hl[6], hl[7]); }
        };
        put_kv(aA, 0);
        wg_wait<0>();
        release(prev);
        float aR[12];
        mbar_wait(rem_full, layer);
        const uint64_t dr = DESC_REM | ((sd + REM) >> 4);
        wg_fence();
#pragma unroll
        for (int s = 0; s < 36; s++) {
          wgmma_rs_n24(aR, X + 4 * s, dr + s * 16, s != 0);
          if (s == 4) put_kv(aB, 1);
        }
        wg_commit();
#pragma unroll
        for (int kb = 0; kb < 9; kb++) {
          if (kb == HOFF1 && w < 4) asm volatile("bar.sync 4, 256;" ::: "memory");
          if (kb == 8 && HOFF1 < 9 && w >= 4) asm volatile("bar.arrive 4, 256;" ::: "memory");
          if (!(kb & 1)) mbar_wait(full0 + rg.st * 8, rg.ph);
          const uint64_t desc = DESC_HI | ((sd + rg.st * STAGE + (kb & 1) * 8192) >> 4);
          wg_fence();
#pragma unroll
          for (int i = 0; i < 4; i++) wgmma_rs_n64(aB, X + 4 * (4 * kb + i), desc + i * 128, kb + i != 0);
          wg_commit();
          wg_wait<1>();
          if (kb > 0 && !(kb & 1)) release(prev);
          if ((kb & 1) || kb == 8) { prev = rg.st; rg.next(); }
          if (kb == 0) {
            pin(aR);
            const uint32_t k1 = pack_bf16(aR[2] * rs1, aR[3] * rs1), v1 = pack_bf16(aR[6] * rs1, aR[7] * rs1);
            if (edge_out) stg4(hp + 128, nz(k1), v1, 0u, 0u);
            sts1(dstr, pack_bf16(aR[0] * rs0, aR[1] * rs0)); sts1(dstr + 8 * 144, k1);
            sts1(dstr + 20736, pack_bf16(aR[4] * rs0, aR[5] * rs0)); sts1(dstr + 20736 + 8 * 144, v1);
            Q[16] = pack_bf16(aR[8], aR[9]); Q[17] = pack_bf16(aR[10], aR[11]);
            if (w < 4) asm volatile("bar.arrive 2, 256;" ::: "memory");
          }
          if (kb == KLD) {
            if (w < 4) asm volatile("bar.sync 1, 192;" ::: "memory");
            else asm volatile("bar.sync 2, 256;" ::: "memory");
#pragma unroll
            for (int nt = 0; nt < 3; nt++) {
              const uint32_t ra = (nt == 0 ? row0 : row1 + (nt - 1) * 8 * 144);
              ldsm4(ra + odd * 16 + (lane >> 3) * 16, Km[nt][0], Km[nt][1], Km[nt][2], Km[nt][3]);
              ldsm4(ra + odd * 16 + 64 + (lane >> 3) * 16, Km[nt][4], Km[nt][5], Km[nt][6], Km[nt][7]);
              ldsm4(ra + (odd ? 0 : 32) + (lane >> 3) * 32, Ke[nt][0], Ke[nt][1], Ke[nt][2], Ke[nt][3]);
            }
            const uint32_t ge = (2u << q) - 1, le = 0xfu << q, on = edge ? 0u : ~0u;
            const uint32_t bits = odd ? 0xfu | ((le & 0xfu) << 4) | (ge << 8) : ge | 0xf0u | (le << 8);
#pragma unroll
            for (int h = 0; h < 4; h++) {
              const uint32_t ma = bitmask(bits, h), mb = bitmask(bits, 4 + h), mc = bitmask(bits, 8 + h);
              Km[0][2 * h] &= ma & on; Km[0][2 * h + 1] &= mb & on; Ke[0][h] &= mc & on;
#pragma unroll
              for (int nt = 1; nt < 3; nt++) { Km[nt][2 * h] &= ma; Km[nt][2 * h + 1] &= mb; Ke[nt][h] &= mc; }
            }
          }
        }
        wg_wait<0>();
        release(prev);
        pin(aB);
        STAMP(3);
#pragma unroll
        for (int i = 0; i < 16; i++) Q[i] = pack_bf16(aB[2 * i], aB[2 * i + 1]);
      }
      {
        uint32_t V01[12][2], V2[12];
        const uint32_t rv = ((lane & 8) ? row1 : row0) + 20736, rw = row1 + 8 * 144 + 20736;
#pragma unroll
        for (int i = 0; i < 4; i++) ldsm4t(rv + odd * 16 + i * 32 + (lane >> 4) * 16, V01[2 * i][0], V01[2 * i][1], V01[2 * i + 1][0], V01[2 * i + 1][1]);
#pragma unroll
        for (int i = 0; i < 2; i++) ldsm4t(rv + (odd ? 0 : 32) + i * 64 + (lane >> 4) * 32, V01[8 + 2 * i][0], V01[8 + 2 * i][1], V01[9 + 2 * i][0], V01[9 + 2 * i][1]);
        ldsm4t(rw + odd * 16 + (lane >> 3) * 16, V2[0], V2[1], V2[2], V2[3]);
        ldsm4t(rw + odd * 16 + 64 + (lane >> 3) * 16, V2[4], V2[5], V2[6], V2[7]);
        ldsm4t(rw + (odd ? 0 : 32) + (lane >> 3) * 32, V2[8], V2[9], V2[10], V2[11]);
        const bool up0 = 2 * q > r, up1 = 2 * q + 1 > r;
        const uint32_t upm = (up0 ? 0xffffu : 0u) | (up1 ? 0xffff0000u : 0u);
        const float c0 = 0.23570226039551584f * 1.4426950408889634f * rs0, c1 = 0.23570226039551584f * 1.4426950408889634f * rs1;
        const float masked = edge ? -1e9f * 1.4426950408889634f * rcp(c0) : 0.f;
        uint32_t Om[16], Oe[8];
#pragma unroll
        for (int h = 0; h < 4; h++) {
          const uint32_t e0 = odd ? Q[(4 * h + 16) % 18] : Q[4 * h + 4], e1 = odd ? Q[(4 * h + 17) % 18] : Q[4 * h + 5];
          float S[3][4];
#pragma unroll
          for (int nt = 0; nt < 3; nt++) {
            mma16c(S[nt], Q + 4 * h, Km[nt][2 * h], Km[nt][2 * h + 1], nt == 0 ? masked : 0.f);
            mma8(S[nt], e0, e1, Ke[nt][h]);
          }
          const float s00 = up0 ? S[0][0] : S[1][0], s01 = up1 ? S[0][1] : S[1][1];
          const float s10 = up0 ? S[1][2] : S[2][2], s11 = up1 ? S[1][3] : S[2][3];
          const float m0 = quad_max(fmaxf(s00, s01)) * c0, m1 = quad_max(fmaxf(s10, s11)) * c1;
          const float p00 = ex2(fmaf(s00, c0, -m0)), p01 = ex2(fmaf(s01, c0, -m0)), p10 = ex2(fmaf(s10, c1, -m1)), p11 = ex2(fmaf(s11, c1, -m1));
          const float i0 = rcp(quad_sum(p00 + p01)), i1 = rcp(quad_sum(p10 + p11));
          const uint32_t p0 = pack_bf16(p00 * i0, p01 * i0), p1 = pack_bf16(p10 * i1, p11 * i1);
          const uint32_t pf[4] = {p0 & upm, 0u, p0 & ~upm, p1 & upm};
#pragma unroll
          for (int gi = 0; gi < 3; gi++) {
            const int g = gi < 2 ? 2 * h + gi : 8 + h;
            float o[4];
            mma16c(o, pf, V01[g][0], V01[g][1], 0.f);
            mma8(o, 0u, p1 & ~upm, V2[g]);
            uint32_t* d = gi < 2 ? Om + 2 * g : Oe + 2 * h;
            d[0] = pack_bf16(o[0], o[1]); d[1] = pack_bf16(o[2], o[3]);
          }
        }
#pragma unroll
        for (int h = 0; h < 4; h++)
#pragma unroll
          for (int e = 0; e < 2; e++) {
            if (h > 0 && !odd && q < h) Om[4 * h + e] = Oe[2 * h - 2 + e];
            if (h < 3 && odd && q > h) Om[4 * h + 2 + e] = Oe[2 * h + 2 + e];
          }
        STAMP(4);
        if (j >= PRI && lane == 0) asm volatile("st.relaxed.gpu.global.b32 [%0], %1;" :: "l"(scr + OFF_S + (8 + w) * 96 + j * 8), "r"(tag) : "memory");
        put72(xbase + 16 * SLAB, j, lane, Om, odd ? Oe[0] : Oe[6], odd ? Oe[1] : Oe[7]);
      }
      if (j < PRI && lane == 0) asm volatile("st.relaxed.gpu.global.b32 [%0], %1;" :: "l"(scr + OFF_S + (8 + w) * 96 + j * 8), "r"(tag) : "memory");
      {
        uint32_t res[18];
        const uint4* p = xbase + ((9 * j + 1) >> 1) * 32 + lane;
#pragma unroll
        for (int i = 0; i < 4; i++) ldg4(res + 4 * i, p + i * 32);
        ldg2(res + 16, odd ? (const char*)(p - 32) + 8 : (const char*)(p + 4 * 32));
        const uint4* src = xbase + 16 * SLAB + lane;
        {
          const uint4* fp = scr + OFF_S + (8 + w) * 96 + (lane & 7) * 8;
          int n = 0;
          mbar_wait(remo_full, layer);
          STAMP(8);
          while (true) {
            uint32_t f;
            asm volatile("ld.relaxed.gpu.global.b32 %0, [%1];" : "=r"(f) : "l"(fp) : "memory");
            if (__all_sync(~0u, f == tag)) break;
            SPIN_GUARD(n);
          }
          STAMP(9);
        }
        if (HOFF3 < 9 && w < 4) asm volatile("bar.sync 6, 256;" ::: "memory");
#pragma unroll
        for (int kb = 0; kb < GO; kb++) load_kb(kb, src, (const char*)src - lane * 8, 256);
        float acc[36];
#pragma unroll
        for (int i = 0; i < 18; i++) { acc[2 * i] = bf_lo(res[i]); acc[2 * i + 1] = bf_hi(res[i]); }
#pragma unroll
        for (int kb = 0; kb < 9; kb++) {
          next_kb(false, kb, src, (const char*)src - lane * 8, 256);
          if (kb == HOFF3 && w >= 4) asm volatile("bar.arrive 6, 256;" ::: "memory");
          if (!(kb & 1)) mbar_wait(full0 + rg.st * 8, rg.ph);
          const uint32_t base = sd + rg.st * STAGE + (kb & 1) * 8192;
          const uint64_t d0 = DESC_HI | ((base >> 4) + (((sd + REM + 27648 + (kb >> 1) * 2048 + (kb & 1) * 64 - base) >> 4) << 16));
          wg_fence();
#pragma unroll
          for (int i = 0; i < 4; i++) wgmma_rs_n72(acc, X + 4 * (4 * kb + i), d0 - (uint64_t)(i * ((127u << 16) - 128u)), 1);
          wg_commit();
          wg_wait<1>();
          if (kb > 0 && !(kb & 1)) release(prev);
          if ((kb & 1) || kb == 8) { prev = rg.st; rg.next(); }
        }
        wg_wait<0>();
        release(prev);
        pin(acc);
        STAMP(10);
#pragma unroll
        for (int i = 0; i < 18; i++) res[i] = pack_bf16(acc[2 * i], acc[2 * i + 1]);
        if (j < PRI) put72(xbase + 32 * SLAB, j, lane, res, res[16], res[17]);
        publish_stats<9>(scr + OFF_S + (16 + w) * 96 + j * 8, acc, tag, lane);
        if (j >= PRI) put72(xbase + 32 * SLAB, j, lane, res, res[16], res[17]);
      }
      continue;
      }
      const uint32_t hp = sb + PARK + w * 512 + lane_id() * 16;
      auto pack8 = [&](float (&a)[32], int p, uint32_t* o) {
#pragma unroll
        for (int e = 0; e < 8; e++) asm volatile("" : "+f"(a[8 * p + e]) :: "memory");
#pragma unroll
        for (int e = 0; e < 4; e++) o[e] = pack_bf16(a[8 * p + 2 * e], a[8 * p + 2 * e + 1]);
      };
      const float ka0 = 0.7978845608028654f * rs0, kb0 = 0.044715f * ka0 * rs0 * rs0, ku0 = 0.5f * rs0 * rs0;
      const float ka1 = 0.7978845608028654f * rs1, kb1 = 0.044715f * ka1 * rs1 * rs1, ku1 = 0.5f * rs1 * rs1;
      auto packu8 = [&](int p, uint32_t* o) {
#pragma unroll
        for (int e = 0; e < 8; e++) asm volatile("" : "+f"(aA[8 * p + e]) :: "memory");
#pragma unroll
        for (int e = 0; e < 4; e++) o[e] = pack_bf16(aA[8 * p + 2 * e] * ((e & 1) ? ku1 : ku0), aA[8 * p + 2 * e + 1] * ((e & 1) ? ku1 : ku0));
      };
      auto geglu8 = [&](int p, uint32_t* u) {
#pragma unroll
        for (int e = 0; e < 8; e++) asm volatile("" : "+f"(aB[8 * p + e]) :: "memory");
        float h[8];
#pragma unroll
        for (int e = 0; e < 8; e++) {
          const float g = aB[8 * p + e];
          h[e] = fmaf(g, tanh_ap(g * fmaf(g * g, (e & 2) ? kb1 : kb0, (e & 2) ? ka1 : ka0)), g);
        }
#pragma unroll
        for (int e = 0; e < 4; e++) u[e] = mul_bf16x2(pack_bf16(h[2 * e], h[2 * e + 1]), u[e]);
      };
      auto box = [&](int b, auto&& filler) {
        const int kb = b < 9 ? b : b - 9;
        if (!(b & 1)) { if ((TRAPB >> (b >> 1)) & 1) mbar_wait_trap(full0 + rg.st * 8, rg.ph); else mbar_wait(full0 + rg.st * 8, rg.ph); }
        const uint64_t desc = DESC_HI | ((sd + rg.st * STAGE + (b & 1) * 8192) >> 4);
        wg_fence();
#pragma unroll
        for (int i = 0; i < 4; i++) {
          if (b < 9) wgmma_rs_n64(aA, X + 4 * (4 * kb + i), desc + i * 128, kb + i != 0);
          else wgmma_rs_n64(aB, X + 4 * (4 * kb + i), desc + i * 128, kb + i != 0);
          if (i == FPOS) filler();
        }
        wg_commit();
        if (b & 1) { prev = rg.st; rg.next(); } else { wg_wait<1>(); release(prev); }
      };
      auto nop = [] {};
      auto step = [&](int st, auto&& filler) { box(2 * st, nop); box(2 * st + 1, filler); };
#pragma unroll
      for (int p = 0; p < 4; p++) { uint32_t o[4]; packu8(p, o); sts4(hp + p * 4096, o); }
      box(0, nop);
      if (lead) mbar_arrive(xb_done);
#pragma unroll 1
      for (int c = 1;; c++) {
        const uint32_t hc = hp + c * 4 * 4096;
#pragma unroll
        for (int b = 1; b < 18; b++) box(b, [&] {
          if ((b & 1) && b < 8) { uint32_t o[4]; const uint32_t a = hc - (4 - (b >> 1)) * 4096; lds4(a, o); geglu8(b >> 1, o); sts4(a, o); }
          if ((b & 1) && b > 10) { uint32_t o[4]; packu8((b - 11) >> 1, o); if (c < 8) sts4(hc + ((b - 11) >> 1) * 4096, o); } });
        ZSTAMP(4, c);
        if (c == 8) break;
        box(0, nop);
      }
      wg_wait<0>();
      STAMP(21);
      GSTAMP(19);
      auto unpark = [&](int kb) {
#pragma unroll
        for (int s = 4 * kb; s < 4 * kb + 4; s++) lds4(hp + s * 4096, X + 4 * s);
      };
      unpark(0);
      uint32_t U[16];
#pragma unroll
      for (int p = 0; p < 4; p++) packu8(p, U + 4 * p);
#pragma unroll
      for (int b = 0; b < 8; b++) box(b, [&] {
        if (b < 7) unpark(b + 1);
        if (b & 1) {
          geglu8(b >> 1, U + 2 * (b - 1));
          if (rg.ph > 1) sts4(hp, U + 2 * (b - 1));
#pragma unroll
          for (int i = 0; i < 4; i++) X[128 + 2 * (b - 1) + i] = U[2 * (b - 1) + i];
        } });
      STAMP(24);
      if (layer == 0 && lead) mbar_arrive(park_free);
      const uint32_t lane2 = lane_id();
      uint4* const pw = scr + OFF_P + (j * 8 + w) * SLAB + lane2;
      const uint4* const pr = scr + OFF_P + w * SLAB + 4 * j * 32 + lane2;
      auto put_part = [&](float (&a)[32], int p, uint32_t chunk) {
        uint32_t o[4];
        pack8(a, p, o);
        stg4(pw + (chunk * 4 + p) * 32, (o[0] & ~1u) | tag, o[1], o[2], o[3]);
      };
      uint4* const xb = xbase + 32 * SLAB + 4 * j * 32;
      auto slot = [&](int p) { return sb + w * 2048 + (p < 3 ? PARK + p * 16384 : KVS + (p - 3) * 16384); };
      auto fetch = [&](int p) {
        bulk_load(slot(p), p ? scr + OFF_P + (((j - p) & 7) * 8 + w) * SLAB + 4 * j * 32 : xb, 2048, p ? pbar0 + w * 8 : res_full, true);
      };
#pragma unroll 1
      for (int sp = 0;; sp++) {
        const uint32_t ca = sp == 0 ? 8 : ((j + 2 * sp) & 7), cb = (j + 2 * sp + 1) & 7;
        if (C8 == 1 && sp == 1 && lead) mbar_arrive(c8_go);
#pragma unroll
        for (int st = 4; st < 9; st++) step(st, [&] {
          if (st == 5 || st == 6) { put_part(aA, 2 * (st - 5), ca); put_part(aA, 2 * (st - 5) + 1, ca); }
          if (st == 8 && sp > 0) { if (sp == 3) mbar_wait(c8_done, layer); fetch(2 * sp - 2); } });
        STAMP(25 + sp);
        if (sp == 3) break;
        if (C8 == 0 && sp == 0 && lead) mbar_arrive(c8_go);
#pragma unroll
        for (int st = 0; st < 4; st++) step(st, [&] {
          if (st < 2) { put_part(aB, 2 * st, cb); put_part(aB, 2 * st + 1, cb); }
          if (st == 3 && sp > 0) fetch(2 * sp - 1); });
      }
      auto load_p = [&](int p, uint32_t* d) {
#pragma unroll
        for (int i = 0; i < 4; i++) ldg4(d + 4 * i, pr + ((j - p) & 7) * 8 * SLAB + i * 32);
      };
#pragma unroll
      for (int b = 0; b < 9; b++) {
        if (b == HOFF2 && w < 4) asm volatile("bar.sync 5, 256;" ::: "memory");
        box(b, [&] {
          if (b == 1) {
#pragma unroll
            for (int p = 0; p < 4; p++) put_part(aB, p, (j + 7) & 7);
          }
          if (b == 3) { load_p(5, X); load_p(6, X + 16); }
          if (b == 7 && EXP != 1) load_p(7, X + 32); });
        if (b == 7 && HOFF2 < 9 && w >= 4) asm volatile("bar.arrive 5, 256;" ::: "memory");
      }
      mbar_wait(res_full, layer);
      mbar_wait(pbar0 + w * 8, layer);
#pragma unroll
      for (int p = 1; p < 5; p++)
#pragma unroll
        for (int i = 0; i < 4; i++) lds4(slot(p) + lane2 * 16 + i * 512, X + 48 + 16 * p + 4 * i);
#pragma unroll
      for (int i = 0; i < 4; i++) {
        const bool split = j == 2 * i + 1;
        const uint32_t a = slot(0) + i * 512 + (split ? lane2 * 8 : lane2 * 16);
        lds2(a, X + 48 + 4 * i); lds2(a + (split ? 256 : 8), X + 50 + 4 * i);
      }
      wg_wait<0>();
      release(rg.st); rg.next();
      pin(aA);
      STAMP(22);
      GSTAMP(20);
      {
        const uint32_t lane = lane2, r = lane >> 2, q = lane & 3;
        const uint32_t eye = r == 2 * q ? 0x3f80u : r == 2 * q + 1 ? 0x3f800000u : 0u;
        auto bad = [&](const uint32_t* d) { return diff2(d[0], d[4], tag) | diff2(d[8], d[12], tag); };
        auto add = [&](const uint32_t* d) {
#pragma unroll
          for (int g = 0; g < 8; g++) mma8(aA + 4 * g, d[2 * g], d[2 * g + 1], eye);
        };
        int n = 0;
        while (!__all_sync(~0u, ((or3(bad(X), bad(X + 16), bad(X + 64)) | or3(bad(X + 80), bad(X + 96), bad(X + 112))) & 1u) == 0u)) {
          SPIN_GUARD(n);
          load_p(5, X); load_p(6, X + 16);
#pragma unroll
          for (int p = 1; p < 5; p++) load_p(p, X + 48 + 16 * p);
        }
        add(X); add(X + 16);
#pragma unroll
        for (int p = 4; p >= 0; p--) add(X + 48 + 16 * ((p + 1) % 5));
        STAMP(11);
        if (EXP != 1) while (!__all_sync(~0u, (bad(X + 32) & 1u) == 0u)) { SPIN_GUARD(n); load_p(7, X + 32); }
        add(X + 32);
        STAMP(12);
        uint32_t res[16];
#pragma unroll
        for (int i = 0; i < 16; i++) res[i] = pack_bf16(aA[2 * i], aA[2 * i + 1]);
        if (layer == 0) {
          uint4* p = xbase + 8 * SLAB + 4 * j * 32 + lane;
          auto put = [&] {
#pragma unroll
            for (int i = 0; i < 4; i++) stg4(p + i * 32, nz(res[4 * i]), res[4 * i + 1], nz(res[4 * i + 2]), res[4 * i + 3]);
          };
          if (j < PRI) put();
          publish_stats<8>(scr + OFF_S + w * 96 + j * 8, aA, 0u, lane);
          if (j >= PRI) put();
          if (lane == 0) mbar_arrive(kv_free);
        } else {
          const uint32_t tb = slot(0);
          __syncwarp();
#pragma unroll
          for (int i = 0; i < 4; i++) {
            const uint32_t row = (lane2 & 7) + (lane2 & 8), g = 2 * i + (lane2 >> 4);
            asm volatile("stmatrix.sync.aligned.m8n8.x4.shared.b16 [%0], {%1,%2,%3,%4};"
                         :: "r"(tb + row * 128 + ((g ^ (row & 7)) << 4)), "r"(res[4 * i]), "r"(res[4 * i + 1]), "r"(res[4 * i + 2]), "r"(res[4 * i + 3]) : "memory");
          }
          __syncwarp();
#pragma unroll
          for (int i = 0; i < 4; i++) {
            const uint32_t row = 4 * i + (lane2 >> 3), g = lane2 & 7;
            uint32_t v[4];
            lds4(tb + row * 128 + ((g ^ (row & 7)) << 4), v);
            *(uint4*)(out + (128 * t + 32 * (w >> 1) + 2 * row + (w & 1)) * 576 + 64 * j + 8 * g) = make_uint4(v[0], v[1], v[2], v[3]);
          }
        }
      }
      STAMP(23);
    }
  }
}

typedef CUresult (*EncodeFn)(CUtensorMap*, CUtensorMapDataType, cuuint32_t, void*, const cuuint64_t*, const cuuint64_t*,
                             const cuuint32_t*, const cuuint32_t*, CUtensorMapInterleave, CUtensorMapSwizzle,
                             CUtensorMapL2promotion, CUtensorMapFloatOOBfill);

CUtensorMap make_map(EncodeFn f, const void* p, uint64_t cols, uint64_t rows, bool rem = false) {
  CUtensorMap m;
  cuuint64_t dims[2] = {cols, rows};
  cuuint64_t str[1] = {cols * 2};
  cuuint32_t box[2] = {rem ? 8u : 64u, rem ? 144u : 64u};
  cuuint32_t es[2] = {1, 1};
  f(&m, CU_TENSOR_MAP_DATA_TYPE_BFLOAT16, 2, const_cast<void*>(p), dims, str, box, es, CU_TENSOR_MAP_INTERLEAVE_NONE,
    rem ? CU_TENSOR_MAP_SWIZZLE_NONE : CU_TENSOR_MAP_SWIZZLE_128B, CU_TENSOR_MAP_L2_PROMOTION_NONE, CU_TENSOR_MAP_FLOAT_OOB_FILL_NONE);
  return m;
}

}

extern "C" void kernel_launch(void* const* d_in, const int* in_sizes, int n_in, void* d_out, int out_size) {
  void* fn = nullptr;
  cudaDriverEntryPointQueryResult qr;
  cudaGetDriverEntryPoint("cuTensorMapEncodeTiled", &fn, cudaEnableDefault, &qr);
  EncodeFn enc = (EncodeFn)fn;
  Maps maps;
  maps.m[0] = make_map(enc, d_in[1], 1728, 576); maps.m[1] = make_map(enc, d_in[2], 576, 576);
  maps.m[2] = make_map(enc, d_in[4], 4608, 576); maps.m[3] = make_map(enc, d_in[5], 4608, 576); maps.m[4] = make_map(enc, d_in[6], 576, 4608);
  maps.m[5] = make_map(enc, d_in[1], 1728, 576, true); maps.m[6] = make_map(enc, d_in[2], 576, 576, true);
  void* scr = nullptr;
  cudaGetSymbolAddress(&scr, g_scratch);
  cudaFuncSetAttribute(mega_kernel, cudaFuncAttributeMaxDynamicSharedMemorySize, SMEM_BYTES);
  cudaLaunchConfig_t cfg = {};
  cfg.gridDim = dim3(128); cfg.blockDim = dim3(384); cfg.dynamicSmemBytes = SMEM_BYTES; cfg.stream = cudaStreamPerThread;
  cudaLaunchAttribute at[1];
  at[0].id = cudaLaunchAttributeClusterDimension; at[0].val.clusterDim.x = 2; at[0].val.clusterDim.y = 1; at[0].val.clusterDim.z = 1;
  cfg.attrs = at; cfg.numAttrs = 1;
  int dev = 0, sms = 0, clusters = 0;
  cudaGetDevice(&dev);
  cudaDeviceGetAttribute(&sms, cudaDevAttrMultiProcessorCount, dev);
  cudaOccupancyMaxActiveClusters(&clusters, mega_kernel, &cfg);
  if (sms == 132 && clusters == 66) cfg.gridDim = dim3(132);
  cudaLaunchKernelEx(&cfg, mega_kernel, maps, (uint4*)scr, (const __nv_bfloat16*)d_in[0], (__nv_bfloat16*)d_out);
}
```

```cpp
#include <cuda_runtime.h>
#include <cuda.h>
#include <cuda_bf16.h>
#include <stdint.h>

#define TRACE 0
#define GUARD 0
#define TRAPB 1
#define HOFF1 99
#define HOFF2 99
#define KLD 8
#define ZT 0
#define SLEEP 500
#define SPLITZ 1
#define C8 1
#define HOFF3 99
#define GO 3
#define EXP 0
#define FPOS 2

namespace {

constexpr int NST = 6;
constexpr int STAGE = 16384;
constexpr int PARK = NST * STAGE;
constexpr int REM = PARK + 49152;
constexpr int KVS = REM + 40960;
constexpr int HSTG = KVS + 16384;
constexpr int BARS = KVS + 41472;
constexpr int TRC = BARS + 512;
constexpr int SMEM_BYTES = TRC + (TRACE ? 512 : 0);
static_assert(NST == 6, "the producer addresses empty barriers as full + 48");
static_assert(BARS >= PARK + 131072, "barriers overlap park");
static_assert(SMEM_BYTES <= 232448, "smem");

constexpr int SLAB = 36 * 32;
constexpr int SPIN_MAX = 1 << 17;
constexpr uint32_t PRI = 3;
constexpr int GD = 3;
constexpr int OFF_S = 0;
constexpr int OFF_H = OFF_S + 3 * 8 * 96;
constexpr int OFF_X = OFF_H + 2 * 8 * 384;
constexpr int OFF_P = OFF_X + 6 * 8 * SLAB;
constexpr int TILE = OFF_P + 8 * 8 * SLAB;
constexpr int OFF_R = 16 * TILE;
constexpr int OFF_F = OFF_R + 8 * 2304;
constexpr int SCRATCH = OFF_F + 128 * 8;

}

__device__ uint4 g_scratch[SCRATCH];

namespace {

constexpr uint64_t DESC_HI = 0x4000004000000000ull;
constexpr uint64_t DESC_REM = (576ull << 32) | (8u << 16);
__device__ __forceinline__ void wgmma_rs_n64(float (&d)[32], const uint32_t* a, uint64_t desc, int scale_d) {
  asm volatile("{\n.reg .pred p;\nsetp.ne.b32 p, %37, 0;\n"
    "wgmma.mma_async.sync.aligned.m64n64k16.f32.bf16.bf16 "
    "{%0, %1, %2, %3, %4, %5, %6, %7, %8, %9, %10, %11, %12, %13, %14, %15, %16, %17, %18, %19, %20, %21, %22, %23, %24, %25, %26, %27, %28, %29, %30, %31}, "
    "{%32, %33, %34, %35}, %36, p, 1, 1, 1;\n}\n"
    : "+f"(d[0]), "+f"(d[1]), "+f"(d[2]), "+f"(d[3]), "+f"(d[4]), "+f"(d[5]), "+f"(d[6]), "+f"(d[7]), "+f"(d[8]), "+f"(d[9]), "+f"(d[10]), "+f"(d[11]), "+f"(d[12]), "+f"(d[13]), "+f"(d[14]), "+f"(d[15]), "+f"(d[16]), "+f"(d[17]), "+f"(d[18]), "+f"(d[19]), "+f"(d[20]), "+f"(d[21]), "+f"(d[22]), "+f"(d[23]), "+f"(d[24]), "+f"(d[25]), "+f"(d[26]), "+f"(d[27]), "+f"(d[28]), "+f"(d[29]), "+f"(d[30]), "+f"(d[31])
    : "r"(a[0]), "r"(a[1]), "r"(a[2]), "r"(a[3]), "l"(desc), "r"(scale_d));
}
__device__ __forceinline__ void wgmma_rs_n72(float (&d)[36], const uint32_t* a, uint64_t desc, int scale_d) {
  asm volatile("{\n.reg .pred p;\nsetp.ne.b32 p, %41, 0;\n"
    "wgmma.mma_async.sync.aligned.m64n72k16.f32.bf16.bf16 "
    "{%0, %1, %2, %3, %4, %5, %6, %7, %8, %9, %10, %11, %12, %13, %14, %15, %16, %17, %18, %19, %20, %21, %22, %23, %24, %25, %26, %27, %28, %29, %30, %31, %32, %33, %34, %35}, "
    "{%36, %37, %38, %39}, %40, p, 1, 1, 1;\n}\n"
    : "+f"(d[0]), "+f"(d[1]), "+f"(d[2]), "+f"(d[3]), "+f"(d[4]), "+f"(d[5]), "+f"(d[6]), "+f"(d[7]), "+f"(d[8]), "+f"(d[9]), "+f"(d[10]), "+f"(d[11]), "+f"(d[12]), "+f"(d[13]), "+f"(d[14]), "+f"(d[15]), "+f"(d[16]), "+f"(d[17]), "+f"(d[18]), "+f"(d[19]), "+f"(d[20]), "+f"(d[21]), "+f"(d[22]), "+f"(d[23]), "+f"(d[24]), "+f"(d[25]), "+f"(d[26]), "+f"(d[27]), "+f"(d[28]), "+f"(d[29]), "+f"(d[30]), "+f"(d[31]), "+f"(d[32]), "+f"(d[33]), "+f"(d[34]), "+f"(d[35])
    : "r"(a[0]), "r"(a[1]), "r"(a[2]), "r"(a[3]), "l"(desc), "r"(scale_d));
}
__device__ __forceinline__ void wgmma_rs_n24(float (&d)[12], const uint32_t* a, uint64_t desc, int scale_d) {
  asm volatile("{\n.reg .pred p;\nsetp.ne.b32 p, %17, 0;\n"
    "wgmma.mma_async.sync.aligned.m64n24k16.f32.bf16.bf16 "
    "{%0, %1, %2, %3, %4, %5, %6, %7, %8, %9, %10, %11}, "
    "{%12, %13, %14, %15}, %16, p, 1, 1, 1;\n}\n"
    : "+f"(d[0]), "+f"(d[1]), "+f"(d[2]), "+f"(d[3]), "+f"(d[4]), "+f"(d[5]), "+f"(d[6]), "+f"(d[7]), "+f"(d[8]), "+f"(d[9]), "+f"(d[10]), "+f"(d[11])
    : "r"(a[0]), "r"(a[1]), "r"(a[2]), "r"(a[3]), "l"(desc), "r"(scale_d));
}

__device__ __forceinline__ void mbar_init(uint32_t a, uint32_t c) { asm volatile("mbarrier.init.shared::cta.b64 [%0], %1;" :: "r"(a), "r"(c)); }
__device__ __forceinline__ void mbar_arrive(uint32_t a) { asm volatile("mbarrier.arrive.shared::cta.b64 _, [%0];" :: "r"(a) : "memory"); }
__device__ __forceinline__ void mbar_wait_trap(uint32_t a, uint32_t ph) {
  asm volatile("{\n.reg .pred p;\n.reg .u32 n;\nmov.u32 n, 0;\n"
               "W: mbarrier.try_wait.parity.shared::cta.b64 p, [%0], %1;\n@p bra D;\n"
               "add.u32 n, n, 1;\nsetp.lt.u32 p, n, 4194304;\n@p bra W;\ntrap;\nD:\n}" :: "r"(a), "r"(ph) : "memory");
}
__device__ __forceinline__ void mbar_wait(uint32_t a, uint32_t ph) {
  asm volatile("{\n.reg .pred p;\nW: mbarrier.try_wait.parity.shared::cta.b64 p, [%0], %1;\n@!p bra W;\n}" :: "r"(a), "r"(ph) : "memory");
}
__device__ __forceinline__ void mbar_wait_sleep(uint32_t a, uint32_t ph) {
  asm volatile("{\n.reg .pred p;\nW: mbarrier.test_wait.parity.shared::cta.b64 p, [%0], %1;\n@p bra D;\nnanosleep.u32 %2;\nbra W;\nD:\n}" :: "r"(a), "r"(ph), "n"(SLEEP) : "memory");
}
__device__ __forceinline__ void wg_fence() { asm volatile("wgmma.fence.sync.aligned;" ::: "memory"); }
__device__ __forceinline__ void wg_commit() { asm volatile("wgmma.commit_group.sync.aligned;" ::: "memory"); }
template <int N> __device__ __forceinline__ void wg_wait() { asm volatile("wgmma.wait_group.sync.aligned %0;" :: "n"(N) : "memory"); }
__device__ __forceinline__ float tanh_ap(float x) { float y; asm("tanh.approx.f32 %0, %1;" : "=f"(y) : "f"(x)); return y; }
__device__ __forceinline__ float ex2(float x) { float y; asm("ex2.approx.ftz.f32 %0, %1;" : "=f"(y) : "f"(x)); return y; }
__device__ __forceinline__ uint32_t pack_bf16(float lo, float hi) { uint32_t r; asm("cvt.rn.bf16x2.f32 %0, %1, %2;" : "=r"(r) : "f"(hi), "f"(lo)); return r; }
__device__ __forceinline__ float bf_lo(uint32_t v) { return __uint_as_float(v << 16); }
__device__ __forceinline__ float bf_hi(uint32_t v) { return __uint_as_float(v & 0xffff0000u); }
__device__ __forceinline__ uint32_t sub_bf16x2(uint32_t a, uint32_t b) { uint32_t r; asm("sub.rn.bf16x2 %0, %1, %2;" : "=r"(r) : "r"(a), "r"(b)); return r; }
__device__ __forceinline__ uint32_t mul_bf16x2(uint32_t a, uint32_t b) { uint32_t r; asm("mul.rn.bf16x2 %0, %1, %2;" : "=r"(r) : "r"(a), "r"(b)); return r; }
__device__ __forceinline__ uint32_t diff2(uint32_t a, uint32_t b, uint32_t t) { uint32_t r; asm("lop3.b32 %0, %1, %2, %3, 0x7e;" : "=r"(r) : "r"(a), "r"(b), "r"(t)); return r; }
__device__ __forceinline__ uint32_t or3(uint32_t a, uint32_t b, uint32_t c) { uint32_t r; asm("lop3.b32 %0, %1, %2, %3, 0xfe;" : "=r"(r) : "r"(a), "r"(b), "r"(c)); return r; }
__device__ __forceinline__ uint32_t umin2(uint32_t a, uint32_t b) { uint32_t r; asm("min.u32 %0, %1, %2;" : "=r"(r) : "r"(a), "r"(b)); return r; }
__device__ __forceinline__ uint32_t bitmask(uint32_t v, int bit) { uint32_t r; asm("bfe.s32 %0, %1, %2, 1;" : "=r"(r) : "r"(v), "r"(bit)); return r; }
__device__ __forceinline__ uint32_t nz(uint32_t w) { return w == 0u ? 0x8000u : w; }

__device__ __forceinline__ void ldg4(uint32_t* d, const uint4* p) {
  asm volatile("ld.relaxed.gpu.global.v4.b32 {%0,%1,%2,%3}, [%4];" : "=r"(d[0]), "=r"(d[1]), "=r"(d[2]), "=r"(d[3]) : "l"(p) : "memory");
}
__device__ __forceinline__ void ldg2(uint32_t* d, const void* p) {
  asm volatile("ld.relaxed.gpu.global.v2.b32 {%0,%1}, [%2];" : "=r"(d[0]), "=r"(d[1]) : "l"(p) : "memory");
}
__device__ __forceinline__ void stg4(uint4* p, uint32_t a, uint32_t b, uint32_t c, uint32_t d) {
  asm volatile("st.relaxed.gpu.global.v4.b32 [%0], {%1,%2,%3,%4};" :: "l"(p), "r"(a), "r"(b), "r"(c), "r"(d) : "memory");
}
__device__ __forceinline__ void stg2(void* p, uint32_t a, uint32_t b) {
  asm volatile("st.relaxed.gpu.global.v2.b32 [%0], {%1,%2};" :: "l"(p), "r"(a), "r"(b) : "memory");
}
__device__ __forceinline__ void sts4(uint32_t a, const uint32_t* o) { asm volatile("st.shared.v4.b32 [%0], {%1,%2,%3,%4};" :: "r"(a), "r"(o[0]), "r"(o[1]), "r"(o[2]), "r"(o[3]) : "memory"); }
__device__ __forceinline__ void lds4(uint32_t a, uint32_t* o) { asm volatile("ld.shared.v4.b32 {%0,%1,%2,%3}, [%4];" : "=r"(o[0]), "=r"(o[1]), "=r"(o[2]), "=r"(o[3]) : "r"(a) : "memory"); }
__device__ __forceinline__ void lds2(uint32_t a, uint32_t* o) { asm volatile("ld.shared.v2.b32 {%0,%1}, [%2];" : "=r"(o[0]), "=r"(o[1]) : "r"(a) : "memory"); }
__device__ __forceinline__ float rcp(float x) { float y; asm("rcp.approx.ftz.f32 %0, %1;" : "=f"(y) : "f"(x)); return y; }
__device__ __forceinline__ void sts1(uint32_t a, uint32_t v) { asm volatile("st.shared.b32 [%0], %1;" :: "r"(a), "r"(v) : "memory"); }
__device__ __forceinline__ void ldsm4(uint32_t a, uint32_t& r0, uint32_t& r1, uint32_t& r2, uint32_t& r3) {
  asm volatile("ldmatrix.sync.aligned.m8n8.x4.shared.b16 {%0,%1,%2,%3}, [%4];" : "=r"(r0), "=r"(r1), "=r"(r2), "=r"(r3) : "r"(a) : "memory");
}
__device__ __forceinline__ void ldsm4t(uint32_t a, uint32_t& r0, uint32_t& r1, uint32_t& r2, uint32_t& r3) {
  asm volatile("ldmatrix.sync.aligned.m8n8.x4.trans.shared.b16 {%0,%1,%2,%3}, [%4];" : "=r"(r0), "=r"(r1), "=r"(r2), "=r"(r3) : "r"(a) : "memory");
}
__device__ __forceinline__ void mma16c(float* d, const uint32_t* a, uint32_t b0, uint32_t b1, float c01) {
  asm("mma.sync.aligned.m16n8k16.row.col.f32.bf16.bf16.f32 {%0,%1,%2,%3}, {%4,%5,%6,%7}, {%8,%9}, {%10,%10,%10,%10};"
    : "=f"(d[0]), "=f"(d[1]), "=f"(d[2]), "=f"(d[3]) : "r"(a[0]), "r"(a[1]), "r"(a[2]), "r"(a[3]), "r"(b0), "r"(b1), "f"(c01));
}
__device__ __forceinline__ void mma8(float* c, uint32_t a0, uint32_t a1, uint32_t b0) {
  asm("mma.sync.aligned.m16n8k8.row.col.f32.bf16.bf16.f32 {%0,%1,%2,%3}, {%4,%5}, {%6}, {%0,%1,%2,%3};"
    : "+f"(c[0]), "+f"(c[1]), "+f"(c[2]), "+f"(c[3]) : "r"(a0), "r"(a1), "r"(b0));
}
__device__ __forceinline__ uint32_t lane_id() { uint32_t l; asm volatile("mov.u32 %0, %%laneid;" : "=r"(l)); return l; }
__device__ __forceinline__ float quad_sum(float v) { v += __shfl_xor_sync(~0u, v, 1); v += __shfl_xor_sync(~0u, v, 2); return v; }
__device__ __forceinline__ float quad_max(float v) { v = fmaxf(v, __shfl_xor_sync(~0u, v, 1)); v = fmaxf(v, __shfl_xor_sync(~0u, v, 2)); return v; }
template <int N> __device__ __forceinline__ void pin(float (&d)[N]) {
#pragma unroll
  for (int i = 0; i < N; i++) asm volatile("" : "+f"(d[i]) :: "memory");
}
#define SPIN_GUARD(n) if (++(n) > SPIN_MAX) break

template <int NG> __device__ __forceinline__ void publish_stats(uint4* dst, const float* y, uint32_t tag, uint32_t lane) {
  float s0 = 0.f, s1 = 0.f;
#pragma unroll
  for (int g = 0; g < NG; g++) { s0 += y[4 * g] + y[4 * g + 1]; s1 += y[4 * g + 2] + y[4 * g + 3]; }
  s0 = quad_sum(s0); s1 = quad_sum(s1);
  const float m0 = s0 * (1.f / (8 * NG)), m1 = s1 * (1.f / (8 * NG));
  float q0 = 0.f, q1 = 0.f, q2 = 0.f, q3 = 0.f;
#pragma unroll
  for (int g = 0; g < NG; g++) {
    const float a = y[4 * g] - m0, b = y[4 * g + 1] - m0, c = y[4 * g + 2] - m1, d = y[4 * g + 3] - m1;
    q0 = fmaf(a, a, q0); q1 = fmaf(b, b, q1); q2 = fmaf(c, c, q2); q3 = fmaf(d, d, q3);
  }
  q0 = quad_sum(q0 + q1); q2 = quad_sum(q2 + q3);
  if ((lane & 3) == 0)
    stg4(dst + (lane >> 2), (__float_as_uint(s0) & ~1u) | tag, __float_as_uint(q0), __float_as_uint(s1), __float_as_uint(q2));
}

__device__ __forceinline__ void put72(uint4* slab, uint32_t j, uint32_t lane, const uint32_t* v, uint32_t r0, uint32_t r1) {
  uint4* p = slab + ((9 * j + 1) >> 1) * 32;
#pragma unroll
  for (int i = 0; i < 4; i++) stg4(p + lane + i * 32, nz(v[4 * i]), v[4 * i + 1], v[4 * i + 2], v[4 * i + 3]);
  stg2((char*)((j & 1) ? p - 16 : p + 4 * 32) + lane * 8, nz(r0), r1);
}
__device__ __forceinline__ void zero_share(uint4* slab, uint32_t j, uint32_t lane) {
  uint4* p = slab + j * 144 + lane;
#pragma unroll
  for (int i = 0; i < 4; i++) stg4(p + i * 32, 0u, 0u, 0u, 0u);
  if (lane < 16) stg4(p + 128, 0u, 0u, 0u, 0u);
}

struct Maps { CUtensorMap m[8]; };

struct Ring {
  uint32_t st, ph;
  __device__ __forceinline__ void next() { if (++st == NST) { st = 0; ph ^= 1; } }
};

#define GSTAMP(i) do {} while (0)
#define STAMP(i) do {} while (0)
#define ZSTAMP(m, i) do {} while (0)

__device__ __forceinline__ void tma_box(uint32_t dst, const CUtensorMap* m, int col, int row, uint32_t bar, uint32_t expect) {
  asm volatile("{\n.reg .pred e, h;\nelect.sync _|e, 0xffffffff;\nsetp.ne.and.u32 h, %5, 0, e;\n"
               "@h mbarrier.arrive.expect_tx.shared::cta.b64 _, [%2], %5;\n"
               "@e cp.async.bulk.tensor.2d.shared::cluster.global.mbarrier::complete_tx::bytes [%0], [%1, {%3, %4}], [%2];\n}"
               :: "r"(dst), "l"(m), "r"(bar), "r"(col), "r"(row), "r"(expect) : "memory");
}

__device__ __forceinline__ void bulk_load(uint32_t dst, const void* src, uint32_t bytes, uint32_t bar, bool arm) {
  asm volatile("{\n.reg .pred e, h;\nelect.sync _|e, 0xffffffff;\nsetp.ne.and.u32 h, %4, 0, e;\n"
               "@h mbarrier.arrive.expect_tx.shared::cta.b64 _, [%3], %2;\n"
               "@e cp.async.bulk.shared::cluster.global.mbarrier::complete_tx::bytes [%0], [%1], %2, [%3];\n}"
               :: "r"(dst), "l"(src), "r"(bytes), "r"(bar), "r"((uint32_t)arm) : "memory");
}

__global__ void __launch_bounds__(384, 1) mega_kernel(
    const __grid_constant__ Maps maps, uint4* __restrict__ scratch,
    const __nv_bfloat16* __restrict__ x_in, __nv_bfloat16* __restrict__ out) {
  extern __shared__ __align__(1024) uint8_t smem[];
  const uint32_t sb = (uint32_t)__cvta_generic_to_shared(smem);
  const uint32_t full0 = sb + BARS, empty0 = full0 + 8 * NST, rem_full = empty0 + 8 * NST, park_free = rem_full + 8, kv_free = park_free + 8;
  const uint32_t c8_go = kv_free + 8, c8_done = c8_go + 8, c8_full = c8_done + 8, remo_full = c8_full + 8, piece_full = remo_full + 8, xb_done = piece_full + 8, res_full = xb_done + 8, pbar0 = res_full + 8;
  const uint32_t x_done = pbar0 + 64, xbar0 = x_done + 8;
  const uint32_t w = __shfl_sync(~0u, threadIdx.x >> 5, 0);
  uint32_t pair = blockIdx.x >> 1;
  if (gridDim.x == 132) {
    uint32_t smid;
    asm("mov.u32 %0, %%smid;" : "=r"(smid));
    const uint32_t tpc = smid >> 1;
    if (tpc == 60 || tpc == 61) { if (threadIdx.x == 0) { __nanosleep(20000); } return; }
    pair = tpc < 32 ? tpc : tpc >= 62 ? (tpc - 58) * 8 : 33 + (tpc - 32) / 7 * 8 + (tpc - 32) % 7;
  }
  const uint32_t rank = blockIdx.x & 1, t = (pair & 7) * 2 + rank, j = pair >> 3;
  const uint32_t sd = sb & 0x3ffff;
  const uint32_t odd = j & 1;
  uint4* const scr = scratch + t * TILE;
  auto xblock = [&](uint32_t b) { return sb + (b < 2 ? b * STAGE : PARK + (b - 1) * STAGE); };
  auto xbar = [&](uint32_t b) { return b < 2 ? full0 + 8 * b : xbar0 + 8 * (b - 2); };
  if (w == 8) {
    if (threadIdx.x == 256) {
      for (int i = 0; i < NST; i++) { mbar_init(full0 + 8 * i, 1); mbar_init(empty0 + 8 * i, 16); }
      mbar_init(rem_full, 1); mbar_init(park_free, 8); mbar_init(kv_free, 8); mbar_init(c8_go, 8); mbar_init(c8_done, 2); mbar_init(c8_full, 1);
      mbar_init(remo_full, 64); mbar_init(piece_full, 1); mbar_init(xb_done, 8); mbar_init(res_full, 8); mbar_init(x_done, 8);
      for (int i = 0; i < 8; i++) mbar_init(pbar0 + 8 * i, 4);
      for (int i = 0; i < 7; i++) mbar_init(xbar0 + 8 * i, 1);
      asm volatile("fence.mbarrier_init.release.cluster;" ::: "memory");
    }
    __syncwarp();
    asm volatile("barrier.cluster.arrive.relaxed.aligned;" ::: "memory");
    const uint32_t p = t >> 2;
    tma_box(sb + PARK, &maps.m[p == 3 ? 6 : 5], 72 * j + (odd ? 0 : 64) + (p < 2 ? 576 * (p + 1) : 0), 144 * (t & 3), piece_full, 2304);
#pragma unroll 1
    for (uint32_t b = 0; b < 9; b++)
      asm volatile("{\n.reg .pred e;\nelect.sync _|e, 0xffffffff;\n@e mbarrier.arrive.expect_tx.shared::cta.b64 _, [%2], 16384;\n"
                   "@e cp.async.bulk.tensor.3d.shared::cluster.global.mbarrier::complete_tx::bytes [%0], [%1, {%3, %4, 0}], [%2];\n}"
                   :: "r"(xblock(b)), "l"(&maps.m[7]), "r"(xbar(b)), "r"(64 * b), "r"(64 * t) : "memory");
  } else {
    asm volatile("barrier.cluster.arrive.relaxed.aligned;" ::: "memory");
  }
  asm volatile("barrier.cluster.wait.aligned;" ::: "memory");

  if (w >= 8) {
    asm volatile("setmaxnreg.dec.sync.aligned.u32 24;");
    if (w == 8) {
      uint32_t dst = sb + 2 * STAGE, bar = full0 + 16, ph = 1;
#pragma unroll 1
      for (int seg = 0; seg < 34; seg++) {
        const int n = seg >= 17 ? seg - 17 : seg;
        int ma, mb, ca, cb, row = 0;
        if (n < 3) { ma = mb = n == 2; ca = 72 * j + 8 * odd + (n == 0 ? 576 : 0); cb = ca + 576; }
        else if (n < 12) { ma = 3; mb = 2; ca = cb = 576 * j + 64 * (n - 3); }
        else { ma = mb = 4; ca = n == 12 ? 512 : ((j + 2 * n) & 7) * 64; cb = ((j + 2 * n + 1) & 7) * 64; row = 576 * j; }
        const bool zip = n == 0 || n == 3, solo = n == 1 || n == 2 || n == 16;
        const CUtensorMap *pa = &maps.m[ma], *pb = &maps.m[mb];
#pragma unroll 1
        for (int st = 0; st < (solo ? 5 : 9); st++) {
          const bool s0 = !zip && st > 4, s1 = zip || st >= 4;
          const int r0 = row + (zip ? 64 * st : s0 ? 128 * st - 576 : 128 * st), r1 = zip ? r0 : st == 4 ? row : r0 + 64;
          const bool rk = rank, sm = rk ? s1 : s0;
          asm volatile("{\n.reg .pred p, e, f;\n.reg .u32 n;\nelect.sync _|e, 0xffffffff;\nsetp.ne.and.u32 f, %7, 0, e;\nmov.u32 n, 0;\n"
                       "W: mbarrier.try_wait.parity.shared::cta.b64 p, [%1+48], %2;\n@p bra D;\n"
                       "add.u32 n, n, 1;\nsetp.lt.u32 p, n, 4194304;\n@p bra W;\ntrap;\n"
                       "D: @e mbarrier.arrive.expect_tx.shared::cta.b64 _, [%1], %6;\n"
                       "@f cp.async.bulk.tensor.2d.shared::cluster.global.mbarrier::complete_tx::bytes.multicast::cluster [%0], [%3, {%4, %5}], [%1], 3;\n}"
                       :: "r"(dst + rk * 8192), "r"(bar), "r"(ph), "l"(sm ? pb : pa), "r"(sm ? cb : ca), "r"(rk ? r1 : r0),
                          "r"(solo && st == 4 ? STAGE / 2 : STAGE), "r"((uint32_t)!(rk && solo && st == 4)) : "memory");
          dst += STAGE; bar += 8;
          if (bar == full0 + 8 * NST) { dst = sb; bar = full0; ph ^= 1; }
        }
      }
      {
#pragma unroll 1
        for (int i = 0; i < NST; i++) {
          mbar_wait_trap(bar + 48, ph);
          bar += 8;
          if (bar == full0 + 8 * NST) { bar = full0; ph ^= 1; }
        }
      }
    } else if (w == 9) {
      const uint32_t lane = lane_id();
      const uint32_t stg = sb + HSTG + lane * 16;
      uint32_t fph = 0;
#pragma unroll 1
      for (uint32_t layer = 0; layer < 2; layer++) {
        uint4* xb = scr + OFF_X + ((4 + layer) * 8 + j) * SLAB + 32 * 32;
        mbar_wait_sleep(c8_go, layer);
        int n = 0;
        while (true) {
          if (lane == 0) asm volatile("mbarrier.arrive.expect_tx.shared::cta.b64 _, [%0], 18432;" :: "r"(c8_full) : "memory");
          __syncwarp();
#pragma unroll 1
          for (uint32_t s = 0; s < 9; s++)
            bulk_load(sb + HSTG + s * 2048, s < 8 ? scr + OFF_P + (j + s * 8) * SLAB + 32 * 32 : xb, 2048, c8_full, false);
          mbar_wait(c8_full, fph); fph ^= 1;
          uint32_t bad = 0;
#pragma unroll 8
          for (int s = 0; s < 32; s++) { uint32_t v; asm volatile("ld.shared.b32 %0, [%1];" : "=r"(v) : "r"(stg + s * 512) : "memory"); bad |= v ^ (1 - layer); }
          if (__all_sync(~0u, (bad & 1u) == 0u)) break;
          __nanosleep(300);
          SPIN_GUARD(n);
        }
        asm volatile("bar.arrive 7, 96;" ::: "memory");
        float s0 = 0.f, s1 = 0.f;
#pragma unroll 1
        for (int g = 0; g < 8; g++) {
          const uint32_t a = stg + (g >> 1) * 512 + (g & 1) * 8;
          float a0 = 0.f, a1 = 0.f, a2 = 0.f, a3 = 0.f;
#pragma unroll 1
          for (int b = 0; b < 3; b++) {
            uint32_t v[6];
#pragma unroll
            for (int s = 0; s < 3; s++) lds2(a + (3 * b + s) * 2048, v + 2 * s);
#pragma unroll
            for (int s = 0; s < 3; s++) { a0 += bf_lo(v[2 * s]); a1 += bf_hi(v[2 * s]); a2 += bf_lo(v[2 * s + 1]); a3 += bf_hi(v[2 * s + 1]); }
          }
          sts1(a + 18432, pack_bf16(a0, a1)); sts1(a + 18436, pack_bf16(a2, a3));
          s0 += a0 + a1; s1 += a2 + a3;
        }
        __syncwarp();
        if (lane == 0) mbar_arrive(c8_done);
        s0 = quad_sum(s0); s1 = quad_sum(s1);
        float q0 = 0.f, q1 = 0.f;
        const uint32_t ln = lane_id();
#pragma unroll 1
        for (uint32_t i = 0; i < 4; i++) {
          uint32_t x[4];
          lds4(stg + 18432 + i * 512, x);
          stg4(xb + i * 32 + ln, 0u, 0u, 0u, 0u);
          if (layer == 0) {
            stg4(xb - 3 * 8 * SLAB + i * 32 + ln, nz(x[0]), x[1], x[2], x[3]);
#pragma unroll
            for (int e = 0; e < 4; e++) {
              const float m = (e & 1) ? s1 : s0, c = fmaf(m, -1.f / 64, bf_lo(x[e])), d = fmaf(m, -1.f / 64, bf_hi(x[e]));
              if (e & 1) q1 = fmaf(c, c, fmaf(d, d, q1)); else q0 = fmaf(c, c, fmaf(d, d, q0));
            }
          } else {
            uint32_t* o = (uint32_t*)(out + (128 * t + 32 * (j >> 1) + 2 * (ln >> 2) + (j & 1)) * 576 + 512 + 16 * i + 2 * (ln & 3));
            o[0] = x[0]; o[8 * 576] = x[1]; o[4] = x[2]; o[8 * 576 + 4] = x[3];
          }
        }
        if (layer == 0) {
          q0 = quad_sum(q0); q1 = quad_sum(q1);
          if ((ln & 3) == 0) stg4(scr + OFF_S + j * 96 + 64 + (ln >> 2), __float_as_uint(s0) | 1u, __float_as_uint(q0), __float_as_uint(s1), __float_as_uint(q1));
        }
      }
    } else {
      auto mark = [&](uint32_t k0, uint32_t v) {
        const uint32_t lane = lane_id();
#pragma unroll 1
        for (uint32_t k = k0; k < 6; k++) stg4(scr + OFF_S + (k * 4 + (lane >> 3)) * 96 + j * 8 + (lane & 7), k < 2 ? 0u : v, 0u, 0u, 0u);
      };
      if (w == 11) mark(2, 0u);
      auto phase2_duties = [&](uint32_t layer) {
        const uint32_t lane = lane_id();
        asm volatile("bar.sync 7, 96;" ::: "memory");
        if (w == 11) {
          if (layer == 0) mark(0, 1u);
          __syncwarp();
          if (lane == 0) mbar_arrive(c8_done);
        }
        mbar_wait_sleep(res_full, layer);
#pragma unroll 1
        for (uint32_t i = 0; i < 4; i++) {
          uint4* z = scr + OFF_X + ((4 + layer) * 8 + (w - 10) * 4 + i) * SLAB + 4 * j * 32 + lane;
#pragma unroll
          for (int k = 0; k < 4; k++) stg4(z + k * 32, 0u, 0u, 0u, 0u);
          __nanosleep(300);
        }
      };
#pragma unroll 1
      for (uint32_t layer = 0; layer < 2; layer++) {
        if (w == 10) {
          if (layer == 0) {
            const uint32_t lane = lane_id();
            uint32_t* fl = (uint32_t*)(scratch + OFF_F + (t * 8 + j) * 8) + (lane & 15);
            uint32_t v;
            asm volatile("ld.relaxed.gpu.global.b32 %0, [%1];" : "=r"(v) : "l"(fl) : "memory");
            mbar_wait(piece_full, 0);
            asm volatile("{\n.reg .pred e;\nelect.sync _|e, 0xffffffff;\n@e cp.async.bulk.global.shared::cta.bulk_group [%0], [%1], 2304;\n}\n"
                         "cp.async.bulk.commit_group;\ncp.async.bulk.wait_group 0;\nfence.proxy.async;"
                         :: "l"(scratch + OFF_R + j * 2304 + t * 144), "r"(sb + PARK) : "memory");
            __syncwarp();
            if (lane < 16) asm volatile("st.release.gpu.global.b32 [%0], 1;" :: "l"((uint32_t*)(scratch + OFF_F + (lane * 8 + j) * 8) + t) : "memory");
            int n = 0;
            while (!__all_sync(~0u, v != 0u)) {
              __nanosleep(100);
              SPIN_GUARD(n);
              asm volatile("ld.relaxed.gpu.global.b32 %0, [%1];" : "=r"(v) : "l"(fl) : "memory");
            }
            asm volatile("st.relaxed.gpu.global.b32 [%0], 0;" :: "l"(fl) : "memory");
            mbar_wait(x_done, 0);
          } else {
            mbar_wait_sleep(park_free, 0);
          }
          bulk_load(sb + REM, scratch + OFF_R + j * 2304, 36864, rem_full, true);
        }
        mbar_wait_sleep(rem_full, layer);
#pragma unroll 1
        for (uint32_t b = 0; b < 5; b++) {
          const uint32_t blk = sb + REM + 27648 + b * 2048, k = (w - 10) * 32 + lane_id(), rr = k & 7;
          const uint32_t dst = blk + ((k >> 3) & 1) * 1024 + rr * 128 + (((k >> 4) ^ rr) << 4);
          uint32_t v[8];
          lds4(blk + k * 16, v); lds4(blk + 1024 + k * 16, v + 4);
          asm volatile("bar.sync 3, 64;" ::: "memory");
          sts4(dst, v); sts4(dst ^ 64, v + 4);
        }
        asm volatile("fence.proxy.async.shared::cta;" ::: "memory");
        mbar_arrive(remo_full);
        if (layer) { phase2_duties(0); mbar_wait_sleep(kv_free, 0); }
        if (t > 0) {
          const uint32_t lane = lane_id(), r = lane >> 2, q = lane & 3;
#pragma unroll 1
          for (uint32_t pc = 0; pc < 3; pc++) {
            uint4* hp = scr + OFF_H + ((layer * 8 + j) * 2 + (w - 10)) * 192 + pc * 64 + lane;
            uint32_t hl[8];
            int n = 0;
            hl[4] = 1u;
            while (true) {
              ldg4(hl, hp);
              if (pc < 2) ldg4(hl + 4, hp + 32);
              if (__all_sync(~0u, hl[0] != 0u && hl[4] != 0u)) break;
              __nanosleep(100);
              SPIN_GUARD(n);
            }
            const uint32_t dst = sb + KVS + (w - 10) * 10368 + r * 144 + q * 4;
            if (pc < 2) {
#pragma unroll
              for (int g = 0; g < 8; g++) sts1(dst + pc * 20736 + odd * 16 + g * 16, hl[g]);
              stg4(hp + 32, 0u, 0u, 0u, 0u);
            } else {
              sts1(dst + (odd ? 0 : 128), hl[0]); sts1(dst + 20736 + (odd ? 0 : 128), hl[1]);
            }
            stg4(hp, 0u, 0u, 0u, 0u);
          }
        }
        asm volatile("bar.arrive 1, 192;" ::: "memory");
        mbar_wait_sleep(xb_done, layer);
        if (w == 10 && layer == 1) {
          const uint32_t lane = lane_id();
          stg4(scr + OFF_S + (lane >> 3) * 96 + j * 8 + (lane & 7), 0u, 0u, 0u, 0u);
          stg4(scr + OFF_S + (4 + (lane >> 3)) * 96 + j * 8 + (lane & 7), 0u, 0u, 0u, 0u);
          if (lane < 8) stg4(scr + OFF_S + j * 96 + 64 + lane, 0u, 0u, 0u, 0u);
        }
#pragma unroll 1
        for (uint32_t i = 0; i < 8 && (w == 11 || layer == 1); i++) {
          zero_share(scr + OFF_X + ((w - 10) * 16 + layer * 8 + i) * SLAB, j, lane_id());
          __nanosleep(500);
        }
      }
      phase2_duties(1);
    }
  } else {
    asm volatile("setmaxnreg.inc.sync.aligned.u32 240;");
    const bool lead = lane_id() == 0;
    Ring rg{2, 0};
    uint32_t prev = 0;
    uint32_t X[144];
    float rs0, rs1;
    const bool lead2 = lane_id() < 2;
    uint32_t empty_at;
    asm volatile("mapa.shared::cluster.u32 %0, %1, %2;" : "=r"(empty_at) : "r"(empty0), "r"(lane_id() & 1));
    auto release = [&](uint32_t st) { if (lead2) asm volatile("mbarrier.arrive.shared::cluster.b64 _, [%0];" :: "r"(empty_at + st * 8) : "memory"); };
    auto load_kb = [&](int kb, const uint4* src, const char* lo, uint32_t hoff) {
#pragma unroll
      for (int k = 4 * kb; k < 4 * kb + 4; k++) {
        if (k % 9 == 4) { ldg2(X + 4 * k, lo + k * 512); ldg2(X + 4 * k + 2, lo + hoff + k * 512); }
        else ldg4(X + 4 * k, src + k * 32);
      }
    };
    auto check_kb = [&](bool skip, int kb, const uint4* src, const char* lo, uint32_t hoff) {
      int n = 0;
      while (true) {
        uint32_t m = umin2(umin2(X[16 * kb], X[16 * kb + 4]), umin2(X[16 * kb + 8], X[16 * kb + 12]));
        if (kb & 1) m = umin2(m, X[16 * kb + 4 * (kb >> 1) + 2]);
        if (__all_sync(~0u, m != 0u || skip)) break;
        SPIN_GUARD(n);
        load_kb(kb, src, lo, hoff);
      }
    };
#pragma unroll 1
    for (uint32_t hf = 0; hf < 4; hf++) {
      const uint32_t layer = hf >> 1;
      const bool ffn = hf & 1;
      const uint32_t tag = 1 - layer;
      uint4* const xbase = scr + OFF_X + (layer * 8 + w) * SLAB;
      float aA[32], aB[32];
      {
        const uint32_t lane = lane_id(), r = lane >> 2, q = lane & 3;
        const uint4* src = xbase + (ffn ? 32 * SLAB : 0) + lane;
        const char* lo = (const char*)src - (ffn ? lane * 8 : 0);
        const uint32_t hoff = ffn ? 256 : 8;
        const uint32_t xoff = (w & 1) * 8192 + (16 * (w >> 1) + (lane & 15)) * 128 + (((lane >> 4) ^ (lane & 7)) << 4);
        auto load_x = [&](uint32_t b, uint32_t* d) {
#pragma unroll
          for (int i = 0; i < 4; i++) ldsm4(xblock(b) + (xoff ^ (32 * i)), d[4 * i], d[4 * i + 1], d[4 * i + 2], d[4 * i + 3]);
        };
        auto load_any = [&](int kb) { if (hf == 0) load_x(kb, X + 16 * kb); else load_kb(kb, src, lo, hoff); };
        float m0, m1, v0, v1;
        STAMP(ffn * 16 + 0);
        if (hf == 0) {
          float sum[4] = {0.f, 0.f, 0.f, 0.f}, sq0[4] = {0.f, 0.f, 0.f, 0.f}, sq1[4] = {0.f, 0.f, 0.f, 0.f};
          uint32_t p0 = 0, p1 = 0;
#pragma unroll 1
          for (uint32_t b = 0; b < 9; b++) {
            uint32_t d[16];
            mbar_wait(xbar(b), 0);
            load_x(b, d);
            if (b == 0) { p0 = __byte_perm(__shfl_sync(~0u, d[0], lane & 28), 0, 0x1010); p1 = __byte_perm(__shfl_sync(~0u, d[1], lane & 28), 0, 0x1010); }
#pragma unroll
            for (int i = 0; i < 16; i++) d[i] = sub_bf16x2(d[i], (i & 1) ? p1 : p0);
#pragma unroll
            for (int g = 0; g < 8; g++) {
              mma8(sum, d[2 * g], d[2 * g + 1], 0x3f803f80u);
              mma8(sq0, d[2 * g], d[2 * g + 1], d[2 * g]); mma8(sq1, d[2 * g], d[2 * g + 1], d[2 * g + 1]);
            }
          }
          STAMP(1);
          GSTAMP(14);
#pragma unroll
          for (int kb = 0; kb < GD; kb++) load_x(kb, X + 16 * kb);
          const float a0 = sum[0] * (1.f / 576), a1 = sum[2] * (1.f / 576);
          const uint32_t dg = (lane & 28) + (r >> 1);
          v0 = fmaxf(fmaf(__shfl_sync(~0u, (r & 1) ? sq0[1] : sq0[0], dg), 1.f / 576, -a0 * a0), 0.f);
          v1 = fmaxf(fmaf(__shfl_sync(~0u, (r & 1) ? sq1[3] : sq1[2], dg), 1.f / 576, -a1 * a1), 0.f);
          m0 = bf_lo(p0) + a0; m1 = bf_lo(p1) + a1;
        } else {
          uint32_t s[3][4];
          const uint4* p = scr + OFF_S + ((ffn ? 16 : 0) + w) * 96 + q * 8 + r;
          const bool third = !ffn && q == 0;
          const uint32_t rdy = ffn ? tag : 1u;
          int n = 0;
          s[2][0] = rdy; s[2][1] = s[2][2] = s[2][3] = 0u;
          while (true) {
            ldg4(s[0], p); ldg4(s[1], p + 32);
            if (third) ldg4(s[2], p + 64);
            if (__all_sync(~0u, ((diff2(s[0][0], s[1][0], rdy) | diff2(s[1][0], s[2][0], rdy)) & 1u) == 0u)) break;
            SPIN_GUARD(n);
          }
          STAMP(ffn * 16 + 1);
          ZSTAMP(1 + ffn, 0);
          GSTAMP(14 + ffn);
#pragma unroll
          for (int kb = 0; kb < GD; kb++) load_kb(kb, src, lo, hoff);
          float t0 = 0.f, t1 = 0.f;
#pragma unroll
          for (int i = 0; i < 3; i++) { t0 += __uint_as_float(s[i][0]); t1 += __uint_as_float(s[i][2]); }
          m0 = quad_sum(t0) * (1.f / 576); m1 = quad_sum(t1) * (1.f / 576);
          const float cnt = ffn ? 72.f : 64.f, inv = ffn ? 1.f / 72 : 1.f / 64;
          v0 = 0.f; v1 = 0.f;
#pragma unroll
          for (int i = 0; i < 3; i++) {
            const float c = (i < 2 || third) ? cnt : 0.f;
            const float d0 = fmaf(__uint_as_float(s[i][0]), inv, -m0), d1 = fmaf(__uint_as_float(s[i][2]), inv, -m1);
            v0 += fmaf(d0 * d0, c, __uint_as_float(s[i][1])); v1 += fmaf(d1 * d1, c, __uint_as_float(s[i][3]));
          }
          v0 = quad_sum(v0) * (1.f / 576); v1 = quad_sum(v1) * (1.f / 576);
        }
        rs0 = rsqrtf(v0 + 1e-5f); rs1 = rsqrtf(v1 + 1e-5f);
        const uint32_t mean0 = pack_bf16(m0, m0), mean1 = pack_bf16(m1, m1);
#pragma unroll
        for (int kb = 0; kb < 9; kb++) {
          check_kb(hf == 0, kb, src, lo, hoff);
          if (kb < 2 && hf == 0) release(kb);
          if (kb + GD < 9) load_any(kb + GD);
          if (kb + GD == 8 && hf == 0 && lead) mbar_arrive(x_done);
#pragma unroll
          for (int i = 16 * kb; i < 16 * kb + 16; i++) X[i] = sub_bf16x2(X[i], (i & 1) ? mean1 : mean0);
          ZSTAMP(1 + ffn, 1 + 3 * kb);
          mbar_wait(full0 + rg.st * 8, rg.ph);
          ZSTAMP(1 + ffn, 2 + 3 * kb);
          const uint64_t desc = DESC_HI | ((sd + rg.st * STAGE) >> 4);
          wg_fence();
#pragma unroll
          for (int i = 0; i < 4; i++) wgmma_rs_n64(aA, X + 4 * (4 * kb + i), desc + i * 128, kb + i != 0);
          if (SPLITZ && kb == 8) { wg_commit(); wg_wait<1>(); wg_fence(); }
#pragma unroll
          for (int i = 0; i < 4; i++) wgmma_rs_n64(aB, X + 4 * (4 * kb + i), desc + 512 + i * 128, kb + i != 0);
          wg_commit();
          wg_wait<1>();
          ZSTAMP(1 + ffn, 3 + 3 * kb);
          if (kb > 0) release(prev);
          prev = rg.st; rg.next();
        }
        if (!SPLITZ) wg_wait<0>();
        ZSTAMP(1 + ffn, 28);
        ZSTAMP(4, 0);
        STAMP(ffn * 16 + 2);
      }
      if (!ffn) {
      const uint32_t lane = lane_id(), r = lane >> 2, q = lane & 3;
      const uint32_t kvrow = sb + KVS + (w & 1) * 10368 + (16 * (w >> 1)) * 144;
      uint32_t Q[18], Km[3][8], Ke[3][4];
      const bool edge = (t == 0 && w < 2);
      const uint32_t row0 = edge ? sb + KVS + 8 * 144 : kvrow + (lane & 7) * 144, row1 = kvrow + (8 + (lane & 7)) * 144;
      {
        const uint32_t dst = kvrow + (8 + r) * 144 + q * 4 + odd * 16, dstr = dst + (odd ? -16 : 128);
        const bool edge_out = w >= 6 && t < 15;
        uint4* const hp = scr + TILE + OFF_H + ((layer * 8 + j) * 2 + (w & 1)) * 192 + lane;
        auto put_kv = [&](float (&a)[32], int part) {
          pin(a);
          uint32_t hl[8];
#pragma unroll
          for (int g = 0; g < 8; g++) {
            hl[g] = pack_bf16(a[4 * g + 2] * rs1, a[4 * g + 3] * rs1);
            sts1(dst + part * 20736 + g * 16, pack_bf16(a[4 * g] * rs0, a[4 * g + 1] * rs0)); sts1(dst + part * 20736 + 8 * 144 + g * 16, hl[g]);
          }
          if (edge_out) { stg4(hp + part * 64, nz(hl[0]), hl[1], hl[2], hl[3]); stg4(hp + part * 64 + 32, nz(hl[4]), hl[5], hl[6], hl[7]); }
        };
        put_kv(aA, 0);
        wg_wait<0>();
        release(prev);
        float aR[12];
        mbar_wait(rem_full, layer);
        const uint64_t dr = DESC_REM | ((sd + REM) >> 4);
        wg_fence();
#pragma unroll
        for (int s = 0; s < 36; s++) {
          wgmma_rs_n24(aR, X + 4 * s, dr + s * 16, s != 0);
          if (s == 4) put_kv(aB, 1);
        }
        wg_commit();
#pragma unroll
        for (int kb = 0; kb < 9; kb++) {
          if (kb == HOFF1 && w < 4) asm volatile("bar.sync 4, 256;" ::: "memory");
          if (kb == 8 && HOFF1 < 9 && w >= 4) asm volatile("bar.arrive 4, 256;" ::: "memory");
          if (!(kb & 1)) mbar_wait(full0 + rg.st * 8, rg.ph);
          const uint64_t desc = DESC_HI | ((sd + rg.st * STAGE + (kb & 1) * 8192) >> 4);
          wg_fence();
#pragma unroll
          for (int i = 0; i < 4; i++) wgmma_rs_n64(aB, X + 4 * (4 * kb + i), desc + i * 128, kb + i != 0);
          wg_commit();
          wg_wait<1>();
          if (kb > 0 && !(kb & 1)) release(prev);
          if ((kb & 1) || kb == 8) { prev = rg.st; rg.next(); }
          if (kb == 0) {
            pin(aR);
            const uint32_t k1 = pack_bf16(aR[2] * rs1, aR[3] * rs1), v1 = pack_bf16(aR[6] * rs1, aR[7] * rs1);
            if (edge_out) stg4(hp + 128, nz(k1), v1, 0u, 0u);
            sts1(dstr, pack_bf16(aR[0] * rs0, aR[1] * rs0)); sts1(dstr + 8 * 144, k1);
            sts1(dstr + 20736, pack_bf16(aR[4] * rs0, aR[5] * rs0)); sts1(dstr + 20736 + 8 * 144, v1);
            Q[16] = pack_bf16(aR[8], aR[9]); Q[17] = pack_bf16(aR[10], aR[11]);
            if (w < 4) asm volatile("bar.arrive 2, 256;" ::: "memory");
          }
          if (kb == KLD - 2) mbar_wait(remo_full, layer);
          if (kb == KLD) {
            if (w < 4) asm volatile("bar.sync 1, 192;" ::: "memory");
            else asm volatile("bar.sync 2, 256;" ::: "memory");
#pragma unroll
            for (int nt = 0; nt < 3; nt++) {
              const uint32_t ra = (nt == 0 ? row0 : row1 + (nt - 1) * 8 * 144);
              ldsm4(ra + odd * 16 + (lane >> 3) * 16, Km[nt][0], Km[nt][1], Km[nt][2], Km[nt][3]);
              ldsm4(ra + odd * 16 + 64 + (lane >> 3) * 16, Km[nt][4], Km[nt][5], Km[nt][6], Km[nt][7]);
              ldsm4(ra + (odd ? 0 : 32) + (lane >> 3) * 32, Ke[nt][0], Ke[nt][1], Ke[nt][2], Ke[nt][3]);
            }
            const uint32_t ge = (2u << q) - 1, le = 0xfu << q, on = edge ? 0u : ~0u;
            const uint32_t bits = odd ? 0xfu | ((le & 0xfu) << 4) | (ge << 8) : ge | 0xf0u | (le << 8);
#pragma unroll
            for (int h = 0; h < 4; h++) {
              const uint32_t ma = bitmask(bits, h), mb = bitmask(bits, 4 + h), mc = bitmask(bits, 8 + h);
              Km[0][2 * h] &= ma & on; Km[0][2 * h + 1] &= mb & on; Ke[0][h] &= mc & on;
#pragma unroll
              for (int nt = 1; nt < 3; nt++) { Km[nt][2 * h] &= ma; Km[nt][2 * h + 1] &= mb; Ke[nt][h] &= mc; }
            }
          }
        }
        wg_wait<0>();
        release(prev);
        pin(aB);
        STAMP(3);
#pragma unroll
        for (int i = 0; i < 16; i++) Q[i] = pack_bf16(aB[2 * i], aB[2 * i + 1]);
      }
      {
        uint32_t V01[12][2], V2[12];
        const uint32_t rv = ((lane & 8) ? row1 : row0) + 20736, rw = row1 + 8 * 144 + 20736;
#pragma unroll
        for (int i = 0; i < 4; i++) ldsm4t(rv + odd * 16 + i * 32 + (lane >> 4) * 16, V01[2 * i][0], V01[2 * i][1], V01[2 * i + 1][0], V01[2 * i + 1][1]);
#pragma unroll
        for (int i = 0; i < 2; i++) ldsm4t(rv + (odd ? 0 : 32) + i * 64 + (lane >> 4) * 32, V01[8 + 2 * i][0], V01[8 + 2 * i][1], V01[9 + 2 * i][0], V01[9 + 2 * i][1]);
        ldsm4t(rw + odd * 16 + (lane >> 3) * 16, V2[0], V2[1], V2[2], V2[3]);
        ldsm4t(rw + odd * 16 + 64 + (lane >> 3) * 16, V2[4], V2[5], V2[6], V2[7]);
        ldsm4t(rw + (odd ? 0 : 32) + (lane >> 3) * 32, V2[8], V2[9], V2[10], V2[11]);
        const bool up0 = 2 * q > r, up1 = 2 * q + 1 > r;
        const uint32_t upm = (up0 ? 0xffffu : 0u) | (up1 ? 0xffff0000u : 0u);
        const float c0 = 0.23570226039551584f * 1.4426950408889634f * rs0, c1 = 0.23570226039551584f * 1.4426950408889634f * rs1;
        const float masked = edge ? -1e9f * 1.4426950408889634f * rcp(c0) : 0.f;
        uint32_t Om[16], Oe[8];
#pragma unroll
        for (int h = 0; h < 4; h++) {
          const uint32_t e0 = odd ? Q[(4 * h + 16) % 18] : Q[4 * h + 4], e1 = odd ? Q[(4 * h + 17) % 18] : Q[4 * h + 5];
          float S[3][4];
#pragma unroll
          for (int nt = 0; nt < 3; nt++) {
            mma16c(S[nt], Q + 4 * h, Km[nt][2 * h], Km[nt][2 * h + 1], nt == 0 ? masked : 0.f);
            mma8(S[nt], e0, e1, Ke[nt][h]);
          }
          const float s00 = up0 ? S[0][0] : S[1][0], s01 = up1 ? S[0][1] : S[1][1];
          const float s10 = up0 ? S[1][2] : S[2][2], s11 = up1 ? S[1][3] : S[2][3];
          const float m0 = quad_max(fmaxf(s00, s01)) * c0, m1 = quad_max(fmaxf(s10, s11)) * c1;
          const float p00 = ex2(fmaf(s00, c0, -m0)), p01 = ex2(fmaf(s01, c0, -m0)), p10 = ex2(fmaf(s10, c1, -m1)), p11 = ex2(fmaf(s11, c1, -m1));
          const float i0 = rcp(quad_sum(p00 + p01)), i1 = rcp(quad_sum(p10 + p11));
          const uint32_t p0 = pack_bf16(p00 * i0, p01 * i0), p1 = pack_bf16(p10 * i1, p11 * i1);
          const uint32_t pf[4] = {p0 & upm, 0u, p0 & ~upm, p1 & upm};
#pragma unroll
          for (int gi = 0; gi < 3; gi++) {
            const int g = gi < 2 ? 2 * h + gi : 8 + h;
            float o[4];
            mma16c(o, pf, V01[g][0], V01[g][1], 0.f);
            mma8(o, 0u, p1 & ~upm, V2[g]);
            uint32_t* d = gi < 2 ? Om + 2 * g : Oe + 2 * h;
            d[0] = pack_bf16(o[0], o[1]); d[1] = pack_bf16(o[2], o[3]);
          }
        }
#pragma unroll
        for (int h = 0; h < 4; h++)
#pragma unroll
          for (int e = 0; e < 2; e++) {
            if (h > 0 && !odd && q < h) Om[4 * h + e] = Oe[2 * h - 2 + e];
            if (h < 3 && odd && q > h) Om[4 * h + 2 + e] = Oe[2 * h + 2 + e];
          }
        STAMP(4);
        if (j >= PRI && lane == 0) asm volatile("st.relaxed.gpu.global.b32 [%0], %1;" :: "l"(scr + OFF_S + (8 + w) * 96 + j * 8), "r"(tag) : "memory");
        put72(xbase + 16 * SLAB, j, lane, Om, odd ? Oe[0] : Oe[6], odd ? Oe[1] : Oe[7]);
      }
      if (j < PRI && lane == 0) asm volatile("st.relaxed.gpu.global.b32 [%0], %1;" :: "l"(scr + OFF_S + (8 + w) * 96 + j * 8), "r"(tag) : "memory");
      {
        uint32_t res[18];
        if (layer == 0) {
          const uint32_t* xr = (const uint32_t*)(x_in + (128 * t + 32 * (w >> 1) + 2 * r + (w & 1)) * 576 + 72 * j + 8 * odd) + q;
#pragma unroll
          for (int i = 0; i < 18; i++)
            asm volatile("ld.global.nc.b32 %0, [%1];" : "=r"(res[i]) : "l"(xr + (i & 1) * 8 * 576 + (i < 16 ? 4 * (i >> 1) : odd ? -4 : 32)));
        } else {
          const uint4* p = xbase + ((9 * j + 1) >> 1) * 32 + lane;
#pragma unroll
          for (int i = 0; i < 4; i++) ldg4(res + 4 * i, p + i * 32);
          ldg2(res + 16, odd ? (const char*)(p - 32) + 8 : (const char*)(p + 4 * 32));
        }
        const uint4* src = xbase + 16 * SLAB + lane;
        {
          const uint4* fp = scr + OFF_S + (8 + w) * 96 + (lane & 7) * 8;
          int n = 0;
          STAMP(8);
          while (true) {
            uint32_t f;
            asm volatile("ld.relaxed.gpu.global.b32 %0, [%1];" : "=r"(f) : "l"(fp) : "memory");
            if (__all_sync(~0u, f == tag)) break;
            SPIN_GUARD(n);
          }
          STAMP(9);
        }
        if (HOFF3 < 9 && w < 4) asm volatile("bar.sync 6, 256;" ::: "memory");
#pragma unroll
        for (int kb = 0; kb < GO; kb++) load_kb(kb, src, (const char*)src - lane * 8, 256);
        float acc[36];
#pragma unroll
        for (int i = 0; i < 18; i++) { acc[2 * i] = bf_lo(res[i]); acc[2 * i + 1] = bf_hi(res[i]); }
#pragma unroll
        for (int kb = 0; kb < 9; kb++) {
          check_kb(false, kb, src, (const char*)src - lane * 8, 256);
          if (kb + GO < 9) load_kb(kb + GO, src, (const char*)src - lane * 8, 256);
          if (kb == HOFF3 && w >= 4) asm volatile("bar.arrive 6, 256;" ::: "memory");
          if (!(kb & 1)) mbar_wait(full0 + rg.st * 8, rg.ph);
          const uint32_t base = sd + rg.st * STAGE + (kb & 1) * 8192;
          const uint64_t d0 = DESC_HI | ((base >> 4) + (((sd + REM + 27648 + (kb >> 1) * 2048 + (kb & 1) * 64 - base) >> 4) << 16));
          wg_fence();
#pragma unroll
          for (int i = 0; i < 4; i++) wgmma_rs_n72(acc, X + 4 * (4 * kb + i), d0 - (uint64_t)(i * ((127u << 16) - 128u)), 1);
          wg_commit();
          wg_wait<1>();
          if (kb > 0 && !(kb & 1)) release(prev);
          if ((kb & 1) || kb == 8) { prev = rg.st; rg.next(); }
        }
        wg_wait<0>();
        release(prev);
        pin(acc);
        STAMP(10);
#pragma unroll
        for (int i = 0; i < 18; i++) res[i] = pack_bf16(acc[2 * i], acc[2 * i + 1]);
        if (j < PRI) put72(xbase + 32 * SLAB, j, lane, res, res[16], res[17]);
        publish_stats<9>(scr + OFF_S + (16 + w) * 96 + j * 8, acc, tag, lane);
        if (j >= PRI) put72(xbase + 32 * SLAB, j, lane, res, res[16], res[17]);
      }
      continue;
      }
      const uint32_t hp = sb + PARK + w * 512 + lane_id() * 16;
      auto pack8 = [&](float (&a)[32], int p, uint32_t* o) {
#pragma unroll
        for (int e = 0; e < 8; e++) asm volatile("" : "+f"(a[8 * p + e]) :: "memory");
#pragma unroll
        for (int e = 0; e < 4; e++) o[e] = pack_bf16(a[8 * p + 2 * e], a[8 * p + 2 * e + 1]);
      };
      const float ka0 = 0.7978845608028654f * rs0, kb0 = 0.044715f * ka0 * rs0 * rs0, ku0 = 0.5f * rs0 * rs0;
      const float ka1 = 0.7978845608028654f * rs1, kb1 = 0.044715f * ka1 * rs1 * rs1, ku1 = 0.5f * rs1 * rs1;
      auto packu8 = [&](int p, uint32_t* o) {
#pragma unroll
        for (int e = 0; e < 8; e++) asm volatile("" : "+f"(aA[8 * p + e]) :: "memory");
#pragma unroll
        for (int e = 0; e < 4; e++) o[e] = pack_bf16(aA[8 * p + 2 * e] * ((e & 1) ? ku1 : ku0), aA[8 * p + 2 * e + 1] * ((e & 1) ? ku1 : ku0));
      };
      auto geglu8 = [&](int p, uint32_t* u) {
#pragma unroll
        for (int e = 0; e < 8; e++) asm volatile("" : "+f"(aB[8 * p + e]) :: "memory");
        float h[8];
#pragma unroll
        for (int e = 0; e < 8; e++) {
          const float g = aB[8 * p + e];
          h[e] = fmaf(g, tanh_ap(g * fmaf(g * g, (e & 2) ? kb1 : kb0, (e & 2) ? ka1 : ka0)), g);
        }
#pragma unroll
        for (int e = 0; e < 4; e++) u[e] = mul_bf16x2(pack_bf16(h[2 * e], h[2 * e + 1]), u[e]);
      };
      auto box = [&](int b, auto&& filler) {
        const int kb = b < 9 ? b : b - 9;
        if (!(b & 1)) { if ((TRAPB >> (b >> 1)) & 1) mbar_wait_trap(full0 + rg.st * 8, rg.ph); else mbar_wait(full0 + rg.st * 8, rg.ph); }
        const uint64_t desc = DESC_HI | ((sd + rg.st * STAGE + (b & 1) * 8192) >> 4);
        wg_fence();
#pragma unroll
        for (int i = 0; i < 4; i++) {
          if (b < 9) wgmma_rs_n64(aA, X + 4 * (4 * kb + i), desc + i * 128, kb + i != 0);
          else wgmma_rs_n64(aB, X + 4 * (4 * kb + i), desc + i * 128, kb + i != 0);
          if (i == FPOS) filler();
        }
        wg_commit();
        if (b & 1) { prev = rg.st; rg.next(); } else { wg_wait<1>(); release(prev); }
      };
      auto nop = [] {};
      auto step = [&](int st, auto&& filler) { box(2 * st, nop); box(2 * st + 1, filler); };
#pragma unroll
      for (int p = 0; p < 4; p++) { uint32_t o[4]; packu8(p, o); sts4(hp + p * 4096, o); }
      box(0, nop);
      if (lead) mbar_arrive(xb_done);
#pragma unroll 1
      for (int c = 1;; c++) {
        const uint32_t hc = hp + c * 4 * 4096;
#pragma unroll
        for (int b = 1; b < 18; b++) box(b, [&] {
          if ((b & 1) && b < 8) { uint32_t o[4]; const uint32_t a = hc - (4 - (b >> 1)) * 4096; lds4(a, o); geglu8(b >> 1, o); sts4(a, o); }
          if ((b & 1) && b > 10) { uint32_t o[4]; packu8((b - 11) >> 1, o); if (c < 8) sts4(hc + ((b - 11) >> 1) * 4096, o); } });
        ZSTAMP(4, c);
        if (c == 8) break;
        box(0, nop);
      }
      wg_wait<0>();
      STAMP(21);
      GSTAMP(19);
      auto unpark = [&](int kb) {
#pragma unroll
        for (int s = 4 * kb; s < 4 * kb + 4; s++) lds4(hp + s * 4096, X + 4 * s);
      };
      unpark(0);
      uint32_t U[16];
#pragma unroll
      for (int p = 0; p < 4; p++) packu8(p, U + 4 * p);
#pragma unroll
      for (int b = 0; b < 8; b++) box(b, [&] {
        if (b < 7) unpark(b + 1);
        if (b & 1) {
          geglu8(b >> 1, U + 2 * (b - 1));
          if (rg.ph > 1) sts4(hp, U + 2 * (b - 1));
#pragma unroll
          for (int i = 0; i < 4; i++) X[128 + 2 * (b - 1) + i] = U[2 * (b - 1) + i];
        } });
      STAMP(24);
      if (layer == 0 && lead) mbar_arrive(park_free);
      const uint32_t lane2 = lane_id();
      uint4* const pw = scr + OFF_P + (j * 8 + w) * SLAB + lane2;
      const uint4* const pr = scr + OFF_P + w * SLAB + 4 * j * 32 + lane2;
      auto put_part = [&](float (&a)[32], int p, uint32_t chunk) {
        uint32_t o[4];
        pack8(a, p, o);
        stg4(pw + (chunk * 4 + p) * 32, (o[0] & ~1u) | tag, o[1], o[2], o[3]);
      };
      uint4* const xb = xbase + 32 * SLAB + 4 * j * 32;
      auto slot = [&](int p) { return sb + w * 2048 + (p < 3 ? PARK + p * 16384 : KVS + (p - 3) * 16384); };
      auto fetch = [&](int p) {
        bulk_load(slot(p), p ? scr + OFF_P + (((j - p) & 7) * 8 + w) * SLAB + 4 * j * 32 : xb, 2048, p ? pbar0 + w * 8 : res_full, true);
      };
#pragma unroll 1
      for (int sp = 0;; sp++) {
        const uint32_t ca = sp == 0 ? 8 : ((j + 2 * sp) & 7), cb = (j + 2 * sp + 1) & 7;
        if (C8 == 1 && sp == 1 && lead) mbar_arrive(c8_go);
#pragma unroll
        for (int st = 4; st < 9; st++) step(st, [&] {
          if (st == 5 || st == 6) { put_part(aA, 2 * (st - 5), ca); put_part(aA, 2 * (st - 5) + 1, ca); }
          if (st == 8 && sp > 0) { if (sp == 3) mbar_wait(c8_done, layer); fetch(2 * sp - 2); } });
        STAMP(25 + sp);
        if (sp == 3) break;
        if (C8 == 0 && sp == 0 && lead) mbar_arrive(c8_go);
#pragma unroll
        for (int st = 0; st < 4; st++) step(st, [&] {
          if (st < 2) { put_part(aB, 2 * st, cb); put_part(aB, 2 * st + 1, cb); }
          if (st == 3 && sp > 0) fetch(2 * sp - 1); });
      }
      auto load_p = [&](int p, uint32_t* d) {
#pragma unroll
        for (int i = 0; i < 4; i++) ldg4(d + 4 * i, pr + ((j - p) & 7) * 8 * SLAB + i * 32);
      };
#pragma unroll
      for (int b = 0; b < 9; b++) {
        if (b == HOFF2 && w < 4) asm volatile("bar.sync 5, 256;" ::: "memory");
        box(b, [&] {
          if (b == 1) {
#pragma unroll
            for (int p = 0; p < 4; p++) put_part(aB, p, (j + 7) & 7);
          }
          if (b == 3) { load_p(5, X); load_p(6, X + 16); }
          if (b == 7 && EXP != 1) load_p(7, X + 32); });
        if (b == 7 && HOFF2 < 9 && w >= 4) asm volatile("bar.arrive 5, 256;" ::: "memory");
      }
      mbar_wait(res_full, layer);
      mbar_wait(pbar0 + w * 8, layer);
#pragma unroll
      for (int p = 1; p < 5; p++)
#pragma unroll
        for (int i = 0; i < 4; i++) lds4(slot(p) + lane2 * 16 + i * 512, X + 48 + 16 * p + 4 * i);
#pragma unroll
      for (int i = 0; i < 4; i++) {
        const bool split = j == 2 * i + 1;
        const uint32_t a = slot(0) + i * 512 + (split ? lane2 * 8 : lane2 * 16);
        lds2(a, X + 48 + 4 * i); lds2(a + (split ? 256 : 8), X + 50 + 4 * i);
      }
      wg_wait<0>();
      release(rg.st); rg.next();
      pin(aA);
      STAMP(22);
      GSTAMP(20);
      {
        const uint32_t lane = lane2, r = lane >> 2, q = lane & 3;
        const uint32_t eye = r == 2 * q ? 0x3f80u : r == 2 * q + 1 ? 0x3f800000u : 0u;
        auto bad = [&](const uint32_t* d) { return diff2(d[0], d[4], tag) | diff2(d[8], d[12], tag); };
        auto add = [&](const uint32_t* d) {
#pragma unroll
          for (int g = 0; g < 8; g++) mma8(aA + 4 * g, d[2 * g], d[2 * g + 1], eye);
        };
        int n = 0;
        while (!__all_sync(~0u, ((or3(bad(X), bad(X + 16), bad(X + 64)) | or3(bad(X + 80), bad(X + 96), bad(X + 112))) & 1u) == 0u)) {
          SPIN_GUARD(n);
          load_p(5, X); load_p(6, X + 16);
#pragma unroll
          for (int p = 1; p < 5; p++) load_p(p, X + 48 + 16 * p);
        }
        add(X); add(X + 16);
#pragma unroll
        for (int p = 4; p >= 0; p--) add(X + 48 + 16 * ((p + 1) % 5));
        STAMP(11);
        if (EXP != 1) while (!__all_sync(~0u, (bad(X + 32) & 1u) == 0u)) { SPIN_GUARD(n); load_p(7, X + 32); }
        add(X + 32);
        STAMP(12);
        uint32_t res[16];
#pragma unroll
        for (int i = 0; i < 16; i++) res[i] = pack_bf16(aA[2 * i], aA[2 * i + 1]);
        if (layer == 0) {
          uint4* p = xbase + 8 * SLAB + 4 * j * 32 + lane;
          auto put = [&] {
#pragma unroll
            for (int i = 0; i < 4; i++) stg4(p + i * 32, nz(res[4 * i]), res[4 * i + 1], nz(res[4 * i + 2]), res[4 * i + 3]);
          };
          if (j < PRI) put();
          publish_stats<8>(scr + OFF_S + w * 96 + j * 8, aA, 1u, lane);
          if (j >= PRI) put();
          if (lane == 0) mbar_arrive(kv_free);
        } else {
          const uint32_t tb = slot(0);
          __syncwarp();
#pragma unroll
          for (int i = 0; i < 4; i++) {
            const uint32_t row = (lane2 & 7) + (lane2 & 8), g = 2 * i + (lane2 >> 4);
            asm volatile("stmatrix.sync.aligned.m8n8.x4.shared.b16 [%0], {%1,%2,%3,%4};"
                         :: "r"(tb + row * 128 + ((g ^ (row & 7)) << 4)), "r"(res[4 * i]), "r"(res[4 * i + 1]), "r"(res[4 * i + 2]), "r"(res[4 * i + 3]) : "memory");
          }
          __syncwarp();
#pragma unroll
          for (int i = 0; i < 4; i++) {
            const uint32_t row = 4 * i + (lane2 >> 3), g = lane2 & 7;
            uint32_t v[4];
            lds4(tb + row * 128 + ((g ^ (row & 7)) << 4), v);
            *(uint4*)(out + (128 * t + 32 * (w >> 1) + 2 * row + (w & 1)) * 576 + 64 * j + 8 * g) = make_uint4(v[0], v[1], v[2], v[3]);
          }
        }
      }
      STAMP(23);
    }
  }
}

typedef CUresult (*EncodeFn)(CUtensorMap*, CUtensorMapDataType, cuuint32_t, void*, const cuuint64_t*, const cuuint64_t*,
                             const cuuint32_t*, const cuuint32_t*, CUtensorMapInterleave, CUtensorMapSwizzle,
                             CUtensorMapL2promotion, CUtensorMapFloatOOBfill);

CUtensorMap make_map(EncodeFn f, const void* p, uint64_t cols, uint64_t rows, bool rem = false) {
  CUtensorMap m;
  cuuint64_t dims[2] = {cols, rows};
  cuuint64_t str[1] = {cols * 2};
  cuuint32_t box[2] = {rem ? 8u : 64u, rem ? 144u : 64u};
  cuuint32_t es[2] = {1, 1};
  f(&m, CU_TENSOR_MAP_DATA_TYPE_BFLOAT16, 2, const_cast<void*>(p), dims, str, box, es, CU_TENSOR_MAP_INTERLEAVE_NONE,
    rem ? CU_TENSOR_MAP_SWIZZLE_NONE : CU_TENSOR_MAP_SWIZZLE_128B, CU_TENSOR_MAP_L2_PROMOTION_NONE, CU_TENSOR_MAP_FLOAT_OOB_FILL_NONE);
  return m;
}

}

extern "C" void kernel_launch(void* const* d_in, const int* in_sizes, int n_in, void* d_out, int out_size) {
  void* fn = nullptr;
  cudaDriverEntryPointQueryResult qr;
  cudaGetDriverEntryPoint("cuTensorMapEncodeTiled", &fn, cudaEnableDefault, &qr);
  EncodeFn enc = (EncodeFn)fn;
  Maps maps;
  maps.m[0] = make_map(enc, d_in[1], 1728, 576); maps.m[1] = make_map(enc, d_in[2], 576, 576);
  maps.m[2] = make_map(enc, d_in[4], 4608, 576); maps.m[3] = make_map(enc, d_in[5], 4608, 576); maps.m[4] = make_map(enc, d_in[6], 576, 4608);
  maps.m[5] = make_map(enc, d_in[1], 1728, 576, true); maps.m[6] = make_map(enc, d_in[2], 576, 576, true);
  {
    cuuint64_t dims[3] = {576, 1024, 2}, str[2] = {2304, 1152};
    cuuint32_t box[3] = {64, 64, 2}, es[3] = {1, 1, 1};
    enc(&maps.m[7], CU_TENSOR_MAP_DATA_TYPE_BFLOAT16, 3, d_in[0], dims, str, box, es, CU_TENSOR_MAP_INTERLEAVE_NONE,
        CU_TENSOR_MAP_SWIZZLE_128B, CU_TENSOR_MAP_L2_PROMOTION_NONE, CU_TENSOR_MAP_FLOAT_OOB_FILL_NONE);
  }
  void* scr = nullptr;
  cudaGetSymbolAddress(&scr, g_scratch);
  cudaFuncSetAttribute(mega_kernel, cudaFuncAttributeMaxDynamicSharedMemorySize, SMEM_BYTES);
  cudaLaunchConfig_t cfg = {};
  cfg.gridDim = dim3(128); cfg.blockDim = dim3(384); cfg.dynamicSmemBytes = SMEM_BYTES; cfg.stream = cudaStreamPerThread;
  cudaLaunchAttribute at[1];
  at[0].id = cudaLaunchAttributeClusterDimension; at[0].val.clusterDim.x = 2; at[0].val.clusterDim.y = 1; at[0].val.clusterDim.z = 1;
  cfg.attrs = at; cfg.numAttrs = 1;
  int dev = 0, sms = 0, clusters = 0;
  cudaGetDevice(&dev);
  cudaDeviceGetAttribute(&sms, cudaDevAttrMultiProcessorCount, dev);
  cudaOccupancyMaxActiveClusters(&clusters, mega_kernel, &cfg);
  if (sms == 132 && clusters == 66) cfg.gridDim = dim3(132);
  cudaLaunchKernelEx(&cfg, mega_kernel, maps, (uint4*)scr, (const __nv_bfloat16*)d_in[0], (__nv_bfloat16*)d_out);
}
```

```cpp
#include <cuda_runtime.h>
#include <cuda.h>
#include <cuda_bf16.h>
#include <stdint.h>

#define TRACE 0
#define GUARD 0
#define TRAPB 1
#define HOFF1 99
#define HOFF2 99
#define KLD 8
#define ZT 0
#define SLEEP 500
#define SPLITZ 1
#define C8 1
#define HOFF3 99
#define GO 3
#define PCB 2
#define EXP 0
#define FPOS 2

namespace {

constexpr int NST = 6;
constexpr int STAGE = 16384;
constexpr int PARK = NST * STAGE;
constexpr int REM = PARK + 49152;
constexpr int KVS = REM + 40960;
constexpr int HSTG = KVS + 16384;
constexpr int BARS = KVS + 41472;
constexpr int TRC = BARS + 512;
constexpr int SMEM_BYTES = TRC + (TRACE ? 512 : 0);
static_assert(NST == 6, "the producer addresses empty barriers as full + 48");
static_assert(BARS >= PARK + 131072, "barriers overlap park");
static_assert(SMEM_BYTES <= 232448, "smem");

constexpr int SLAB = 36 * 32;
constexpr int SPIN_MAX = 1 << 17;
constexpr uint32_t PRI = 3;
constexpr int GD = 3;
constexpr int OFF_S = 0;
constexpr int OFF_H = OFF_S + 3 * 8 * 96;
constexpr int OFF_X = OFF_H + 2 * 8 * 384;
constexpr int OFF_P = OFF_X + 6 * 8 * SLAB;
constexpr int TILE = OFF_P + 8 * 8 * SLAB;
constexpr int OFF_R = 16 * TILE;
constexpr int OFF_F = OFF_R + 8 * 2304;
constexpr int SCRATCH = OFF_F + 128 * 8;

}

__device__ uint4 g_scratch[SCRATCH];

namespace {

constexpr uint64_t DESC_HI = 0x4000004000000000ull;
constexpr uint64_t DESC_REM = (576ull << 32) | (8u << 16);
__device__ __forceinline__ void wgmma_rs_n64(float (&d)[32], const uint32_t* a, uint64_t desc, int scale_d) {
  asm volatile("{\n.reg .pred p;\nsetp.ne.b32 p, %37, 0;\n"
    "wgmma.mma_async.sync.aligned.m64n64k16.f32.bf16.bf16 "
    "{%0, %1, %2, %3, %4, %5, %6, %7, %8, %9, %10, %11, %12, %13, %14, %15, %16, %17, %18, %19, %20, %21, %22, %23, %24, %25, %26, %27, %28, %29, %30, %31}, "
    "{%32, %33, %34, %35}, %36, p, 1, 1, 1;\n}\n"
    : "+f"(d[0]), "+f"(d[1]), "+f"(d[2]), "+f"(d[3]), "+f"(d[4]), "+f"(d[5]), "+f"(d[6]), "+f"(d[7]), "+f"(d[8]), "+f"(d[9]), "+f"(d[10]), "+f"(d[11]), "+f"(d[12]), "+f"(d[13]), "+f"(d[14]), "+f"(d[15]), "+f"(d[16]), "+f"(d[17]), "+f"(d[18]), "+f"(d[19]), "+f"(d[20]), "+f"(d[21]), "+f"(d[22]), "+f"(d[23]), "+f"(d[24]), "+f"(d[25]), "+f"(d[26]), "+f"(d[27]), "+f"(d[28]), "+f"(d[29]), "+f"(d[30]), "+f"(d[31])
    : "r"(a[0]), "r"(a[1]), "r"(a[2]), "r"(a[3]), "l"(desc), "r"(scale_d));
}
__device__ __forceinline__ void wgmma_rs_n72(float (&d)[36], const uint32_t* a, uint64_t desc, int scale_d) {
  asm volatile("{\n.reg .pred p;\nsetp.ne.b32 p, %41, 0;\n"
    "wgmma.mma_async.sync.aligned.m64n72k16.f32.bf16.bf16 "
    "{%0, %1, %2, %3, %4, %5, %6, %7, %8, %9, %10, %11, %12, %13, %14, %15, %16, %17, %18, %19, %20, %21, %22, %23, %24, %25, %26, %27, %28, %29, %30, %31, %32, %33, %34, %35}, "
    "{%36, %37, %38, %39}, %40, p, 1, 1, 1;\n}\n"
    : "+f"(d[0]), "+f"(d[1]), "+f"(d[2]), "+f"(d[3]), "+f"(d[4]), "+f"(d[5]), "+f"(d[6]), "+f"(d[7]), "+f"(d[8]), "+f"(d[9]), "+f"(d[10]), "+f"(d[11]), "+f"(d[12]), "+f"(d[13]), "+f"(d[14]), "+f"(d[15]), "+f"(d[16]), "+f"(d[17]), "+f"(d[18]), "+f"(d[19]), "+f"(d[20]), "+f"(d[21]), "+f"(d[22]), "+f"(d[23]), "+f"(d[24]), "+f"(d[25]), "+f"(d[26]), "+f"(d[27]), "+f"(d[28]), "+f"(d[29]), "+f"(d[30]), "+f"(d[31]), "+f"(d[32]), "+f"(d[33]), "+f"(d[34]), "+f"(d[35])
    : "r"(a[0]), "r"(a[1]), "r"(a[2]), "r"(a[3]), "l"(desc), "r"(scale_d));
}
__device__ __forceinline__ void wgmma_rs_n24(float (&d)[12], const uint32_t* a, uint64_t desc, int scale_d) {
  asm volatile("{\n.reg .pred p;\nsetp.ne.b32 p, %17, 0;\n"
    "wgmma.mma_async.sync.aligned.m64n24k16.f32.bf16.bf16 "
    "{%0, %1, %2, %3, %4, %5, %6, %7, %8, %9, %10, %11}, "
    "{%12, %13, %14, %15}, %16, p, 1, 1, 1;\n}\n"
    : "+f"(d[0]), "+f"(d[1]), "+f"(d[2]), "+f"(d[3]), "+f"(d[4]), "+f"(d[5]), "+f"(d[6]), "+f"(d[7]), "+f"(d[8]), "+f"(d[9]), "+f"(d[10]), "+f"(d[11])
    : "r"(a[0]), "r"(a[1]), "r"(a[2]), "r"(a[3]), "l"(desc), "r"(scale_d));
}

__device__ __forceinline__ void mbar_init(uint32_t a, uint32_t c) { asm volatile("mbarrier.init.shared::cta.b64 [%0], %1;" :: "r"(a), "r"(c)); }
__device__ __forceinline__ void mbar_arrive(uint32_t a) { asm volatile("mbarrier.arrive.shared::cta.b64 _, [%0];" :: "r"(a) : "memory"); }
__device__ __forceinline__ void mbar_wait_trap(uint32_t a, uint32_t ph) {
  asm volatile("{\n.reg .pred p;\n.reg .u32 n;\nmov.u32 n, 0;\n"
               "W: mbarrier.try_wait.parity.shared::cta.b64 p, [%0], %1;\n@p bra D;\n"
               "add.u32 n, n, 1;\nsetp.lt.u32 p, n, 4194304;\n@p bra W;\ntrap;\nD:\n}" :: "r"(a), "r"(ph) : "memory");
}
__device__ __forceinline__ void mbar_wait(uint32_t a, uint32_t ph) {
  asm volatile("{\n.reg .pred p;\nW: mbarrier.try_wait.parity.shared::cta.b64 p, [%0], %1;\n@!p bra W;\n}" :: "r"(a), "r"(ph) : "memory");
}
__device__ __forceinline__ void mbar_wait_sleep(uint32_t a, uint32_t ph) {
  asm volatile("{\n.reg .pred p;\nW: mbarrier.test_wait.parity.shared::cta.b64 p, [%0], %1;\n@p bra D;\nnanosleep.u32 %2;\nbra W;\nD:\n}" :: "r"(a), "r"(ph), "n"(SLEEP) : "memory");
}
__device__ __forceinline__ void wg_fence() { asm volatile("wgmma.fence.sync.aligned;" ::: "memory"); }
__device__ __forceinline__ void wg_commit() { asm volatile("wgmma.commit_group.sync.aligned;" ::: "memory"); }
template <int N> __device__ __forceinline__ void wg_wait() { asm volatile("wgmma.wait_group.sync.aligned %0;" :: "n"(N) : "memory"); }
__device__ __forceinline__ float tanh_ap(float x) { float y; asm("tanh.approx.f32 %0, %1;" : "=f"(y) : "f"(x)); return y; }
__device__ __forceinline__ float ex2(float x) { float y; asm("ex2.approx.ftz.f32 %0, %1;" : "=f"(y) : "f"(x)); return y; }
__device__ __forceinline__ uint32_t pack_bf16(float lo, float hi) { uint32_t r; asm("cvt.rn.bf16x2.f32 %0, %1, %2;" : "=r"(r) : "f"(hi), "f"(lo)); return r; }
__device__ __forceinline__ float bf_lo(uint32_t v) { return __uint_as_float(v << 16); }
__device__ __forceinline__ float bf_hi(uint32_t v) { return __uint_as_float(v & 0xffff0000u); }
__device__ __forceinline__ uint32_t sub_bf16x2(uint32_t a, uint32_t b) { uint32_t r; asm("sub.rn.bf16x2 %0, %1, %2;" : "=r"(r) : "r"(a), "r"(b)); return r; }
__device__ __forceinline__ uint32_t mul_bf16x2(uint32_t a, uint32_t b) { uint32_t r; asm("mul.rn.bf16x2 %0, %1, %2;" : "=r"(r) : "r"(a), "r"(b)); return r; }
__device__ __forceinline__ uint32_t diff2(uint32_t a, uint32_t b, uint32_t t) { uint32_t r; asm("lop3.b32 %0, %1, %2, %3, 0x7e;" : "=r"(r) : "r"(a), "r"(b), "r"(t)); return r; }
__device__ __forceinline__ uint32_t or3(uint32_t a, uint32_t b, uint32_t c) { uint32_t r; asm("lop3.b32 %0, %1, %2, %3, 0xfe;" : "=r"(r) : "r"(a), "r"(b), "r"(c)); return r; }
__device__ __forceinline__ uint32_t umin2(uint32_t a, uint32_t b) { uint32_t r; asm("min.u32 %0, %1, %2;" : "=r"(r) : "r"(a), "r"(b)); return r; }
__device__ __forceinline__ uint32_t bitmask(uint32_t v, int bit) { uint32_t r; asm("bfe.s32 %0, %1, %2, 1;" : "=r"(r) : "r"(v), "r"(bit)); return r; }
__device__ __forceinline__ uint32_t nz(uint32_t w) { return w == 0u ? 0x8000u : w; }

__device__ __forceinline__ void ldg4(uint32_t* d, const uint4* p) {
  asm volatile("ld.relaxed.gpu.global.v4.b32 {%0,%1,%2,%3}, [%4];" : "=r"(d[0]), "=r"(d[1]), "=r"(d[2]), "=r"(d[3]) : "l"(p) : "memory");
}
__device__ __forceinline__ void ldg2(uint32_t* d, const void* p) {
  asm volatile("ld.relaxed.gpu.global.v2.b32 {%0,%1}, [%2];" : "=r"(d[0]), "=r"(d[1]) : "l"(p) : "memory");
}
__device__ __forceinline__ void stg4(uint4* p, uint32_t a, uint32_t b, uint32_t c, uint32_t d) {
  asm volatile("st.relaxed.gpu.global.v4.b32 [%0], {%1,%2,%3,%4};" :: "l"(p), "r"(a), "r"(b), "r"(c), "r"(d) : "memory");
}
__device__ __forceinline__ void stg2(void* p, uint32_t a, uint32_t b) {
  asm volatile("st.relaxed.gpu.global.v2.b32 [%0], {%1,%2};" :: "l"(p), "r"(a), "r"(b) : "memory");
}
__device__ __forceinline__ void sts4(uint32_t a, const uint32_t* o) { asm volatile("st.shared.v4.b32 [%0], {%1,%2,%3,%4};" :: "r"(a), "r"(o[0]), "r"(o[1]), "r"(o[2]), "r"(o[3]) : "memory"); }
__device__ __forceinline__ void lds4(uint32_t a, uint32_t* o) { asm volatile("ld.shared.v4.b32 {%0,%1,%2,%3}, [%4];" : "=r"(o[0]), "=r"(o[1]), "=r"(o[2]), "=r"(o[3]) : "r"(a) : "memory"); }
__device__ __forceinline__ void lds2(uint32_t a, uint32_t* o) { asm volatile("ld.shared.v2.b32 {%0,%1}, [%2];" : "=r"(o[0]), "=r"(o[1]) : "r"(a) : "memory"); }
__device__ __forceinline__ float rcp(float x) { float y; asm("rcp.approx.ftz.f32 %0, %1;" : "=f"(y) : "f"(x)); return y; }
__device__ __forceinline__ void sts1(uint32_t a, uint32_t v) { asm volatile("st.shared.b32 [%0], %1;" :: "r"(a), "r"(v) : "memory"); }
__device__ __forceinline__ void ldsm4(uint32_t a, uint32_t& r0, uint32_t& r1, uint32_t& r2, uint32_t& r3) {
  asm volatile("ldmatrix.sync.aligned.m8n8.x4.shared.b16 {%0,%1,%2,%3}, [%4];" : "=r"(r0), "=r"(r1), "=r"(r2), "=r"(r3) : "r"(a) : "memory");
}
__device__ __forceinline__ void ldsm4t(uint32_t a, uint32_t& r0, uint32_t& r1, uint32_t& r2, uint32_t& r3) {
  asm volatile("ldmatrix.sync.aligned.m8n8.x4.trans.shared.b16 {%0,%1,%2,%3}, [%4];" : "=r"(r0), "=r"(r1), "=r"(r2), "=r"(r3) : "r"(a) : "memory");
}
__device__ __forceinline__ void mma16(float* c, uint32_t a0, uint32_t a1, uint32_t a2, uint32_t a3, uint32_t b0, uint32_t b1) {
  asm("mma.sync.aligned.m16n8k16.row.col.f32.bf16.bf16.f32 {%0,%1,%2,%3}, {%4,%5,%6,%7}, {%8,%9}, {%0,%1,%2,%3};"
    : "+f"(c[0]), "+f"(c[1]), "+f"(c[2]), "+f"(c[3]) : "r"(a0), "r"(a1), "r"(a2), "r"(a3), "r"(b0), "r"(b1));
}
__device__ __forceinline__ void mma16c(float* d, const uint32_t* a, uint32_t b0, uint32_t b1, float c01) {
  asm("mma.sync.aligned.m16n8k16.row.col.f32.bf16.bf16.f32 {%0,%1,%2,%3}, {%4,%5,%6,%7}, {%8,%9}, {%10,%10,%10,%10};"
    : "=f"(d[0]), "=f"(d[1]), "=f"(d[2]), "=f"(d[3]) : "r"(a[0]), "r"(a[1]), "r"(a[2]), "r"(a[3]), "r"(b0), "r"(b1), "f"(c01));
}
__device__ __forceinline__ void mma8(float* c, uint32_t a0, uint32_t a1, uint32_t b0) {
  asm("mma.sync.aligned.m16n8k8.row.col.f32.bf16.bf16.f32 {%0,%1,%2,%3}, {%4,%5}, {%6}, {%0,%1,%2,%3};"
    : "+f"(c[0]), "+f"(c[1]), "+f"(c[2]), "+f"(c[3]) : "r"(a0), "r"(a1), "r"(b0));
}
__device__ __forceinline__ uint32_t lane_id() { uint32_t l; asm volatile("mov.u32 %0, %%laneid;" : "=r"(l)); return l; }
__device__ __forceinline__ float quad_sum(float v) { v += __shfl_xor_sync(~0u, v, 1); v += __shfl_xor_sync(~0u, v, 2); return v; }
__device__ __forceinline__ float quad_max(float v) { v = fmaxf(v, __shfl_xor_sync(~0u, v, 1)); v = fmaxf(v, __shfl_xor_sync(~0u, v, 2)); return v; }
template <int N> __device__ __forceinline__ void pin(float (&d)[N]) {
#pragma unroll
  for (int i = 0; i < N; i++) asm volatile("" : "+f"(d[i]) :: "memory");
}
#define SPIN_GUARD(n) if (++(n) > SPIN_MAX) break

template <int NG> __device__ __forceinline__ void publish_stats(uint4* dst, const float* y, uint32_t tag, uint32_t lane) {
  float s0 = 0.f, s1 = 0.f;
#pragma unroll
  for (int g = 0; g < NG; g++) { s0 += y[4 * g] + y[4 * g + 1]; s1 += y[4 * g + 2] + y[4 * g + 3]; }
  s0 = quad_sum(s0); s1 = quad_sum(s1);
  const float m0 = s0 * (1.f / (8 * NG)), m1 = s1 * (1.f / (8 * NG));
  float q0 = 0.f, q1 = 0.f, q2 = 0.f, q3 = 0.f;
#pragma unroll
  for (int g = 0; g < NG; g++) {
    const float a = y[4 * g] - m0, b = y[4 * g + 1] - m0, c = y[4 * g + 2] - m1, d = y[4 * g + 3] - m1;
    q0 = fmaf(a, a, q0); q1 = fmaf(b, b, q1); q2 = fmaf(c, c, q2); q3 = fmaf(d, d, q3);
  }
  q0 = quad_sum(q0 + q1); q2 = quad_sum(q2 + q3);
  if ((lane & 3) == 0)
    stg4(dst + (lane >> 2), (__float_as_uint(s0) & ~1u) | tag, __float_as_uint(q0), __float_as_uint(s1), __float_as_uint(q2));
}

__device__ __forceinline__ void put72(uint4* slab, uint32_t j, uint32_t lane, const uint32_t* v, uint32_t r0, uint32_t r1) {
  uint4* p = slab + ((9 * j + 1) >> 1) * 32;
#pragma unroll
  for (int i = 0; i < 4; i++) stg4(p + lane + i * 32, nz(v[4 * i]), v[4 * i + 1], v[4 * i + 2], v[4 * i + 3]);
  stg2((char*)((j & 1) ? p - 16 : p + 4 * 32) + lane * 8, nz(r0), r1);
}
__device__ __forceinline__ void zero_share(uint4* slab, uint32_t j, uint32_t lane) {
  uint4* p = slab + j * 144 + lane;
#pragma unroll
  for (int i = 0; i < 4; i++) stg4(p + i * 32, 0u, 0u, 0u, 0u);
  if (lane < 16) stg4(p + 128, 0u, 0u, 0u, 0u);
}

struct Maps { CUtensorMap m[8]; };

struct Ring {
  uint32_t st, ph;
  __device__ __forceinline__ void next() { if (++st == NST) { st = 0; ph ^= 1; } }
};

#define GSTAMP(i) do {} while (0)
#define STAMP(i) do {} while (0)
#define ZSTAMP(m, i) do {} while (0)

__device__ __forceinline__ void tma_box(uint32_t dst, const CUtensorMap* m, int col, int row, uint32_t bar, uint32_t expect) {
  asm volatile("{\n.reg .pred e, h;\nelect.sync _|e, 0xffffffff;\nsetp.ne.and.u32 h, %5, 0, e;\n"
               "@h mbarrier.arrive.expect_tx.shared::cta.b64 _, [%2], %5;\n"
               "@e cp.async.bulk.tensor.2d.shared::cluster.global.mbarrier::complete_tx::bytes [%0], [%1, {%3, %4}], [%2];\n}"
               :: "r"(dst), "l"(m), "r"(bar), "r"(col), "r"(row), "r"(expect) : "memory");
}

__device__ __forceinline__ void bulk_load(uint32_t dst, const void* src, uint32_t bytes, uint32_t bar, bool arm) {
  asm volatile("{\n.reg .pred e, h;\nelect.sync _|e, 0xffffffff;\nsetp.ne.and.u32 h, %4, 0, e;\n"
               "@h mbarrier.arrive.expect_tx.shared::cta.b64 _, [%3], %2;\n"
               "@e cp.async.bulk.shared::cluster.global.mbarrier::complete_tx::bytes [%0], [%1], %2, [%3];\n}"
               :: "r"(dst), "l"(src), "r"(bytes), "r"(bar), "r"((uint32_t)arm) : "memory");
}

__global__ void __launch_bounds__(384, 1) mega_kernel(
    const __grid_constant__ Maps maps, uint4* __restrict__ scratch,
    __nv_bfloat16* __restrict__ out) {
  extern __shared__ __align__(1024) uint8_t smem[];
  const uint32_t sb = (uint32_t)__cvta_generic_to_shared(smem);
  const uint32_t full0 = sb + BARS, empty0 = full0 + 8 * NST, rem_full = empty0 + 8 * NST, park_free = rem_full + 8, kv_free = park_free + 8;
  const uint32_t c8_go = kv_free + 8, c8_done = c8_go + 8, c8_full = c8_done + 8, remo_full = c8_full + 8, piece_full = remo_full + 8, xb_done = piece_full + 8, res_full = xb_done + 8, pbar0 = res_full + 8;
  const uint32_t x_done = pbar0 + 64, xbar0 = x_done + 8;
  const uint32_t w = __shfl_sync(~0u, threadIdx.x >> 5, 0);
  uint32_t pair = blockIdx.x >> 1;
  if (gridDim.x == 132) {
    uint32_t smid;
    asm("mov.u32 %0, %%smid;" : "=r"(smid));
    const uint32_t tpc = smid >> 1;
    if (tpc == 60 || tpc == 61) { if (threadIdx.x == 0) { __nanosleep(20000); } return; }
    pair = tpc < 32 ? tpc : tpc >= 62 ? (tpc - 58) * 8 : 33 + (tpc - 32) / 7 * 8 + (tpc - 32) % 7;
  }
  const uint32_t rank = blockIdx.x & 1, t = (pair & 7) * 2 + rank, j = pair >> 3;
  const uint32_t sd = sb & 0x3ffff;
  const uint32_t odd = j & 1;
  uint4* const scr = scratch + t * TILE;
  auto xblock = [&](uint32_t b) { return sb + (b < 2 ? b * STAGE : PARK + (b - 1) * STAGE); };
  auto xbar = [&](uint32_t b) { return b < 2 ? full0 + 8 * b : xbar0 + 8 * (b - 2); };
  if (w == 8) {
    const uint32_t l = lane_id();
    const uint64_t lg = l < 16 ? 0x3330444444000000ull : 0x0322222222330601ull;
    mbar_init(full0 + 8 * l, 1u << ((lg >> (4 * (l & 15))) & 15));
    if (l < 6) mbar_init(full0 + 256 + 8 * l, 1);
    asm volatile("fence.mbarrier_init.release.cluster;" ::: "memory");
    __syncwarp();
  }
  asm volatile("barrier.cluster.arrive.relaxed.aligned;" ::: "memory");
  if (w != 8) asm volatile("barrier.cluster.wait.aligned;" ::: "memory");

  if (w >= 8) {
    asm volatile("setmaxnreg.dec.sync.aligned.u32 24;");
    if (w == 8) {
#pragma unroll 1
      for (uint32_t b = 0; b < 9; b++) {
        asm volatile("{\n.reg .pred e;\nelect.sync _|e, 0xffffffff;\n@e mbarrier.arrive.expect_tx.shared::cta.b64 _, [%2], 16384;\n"
                     "@e cp.async.bulk.tensor.3d.shared::cluster.global.mbarrier::complete_tx::bytes [%0], [%1, {%3, %4, 0}], [%2];\n}"
                     :: "r"(xblock(b)), "l"(&maps.m[7]), "r"(xbar(b)), "r"(64 * b), "r"(64 * t) : "memory");
        const uint32_t p = t >> 2;
        if (b == PCB) tma_box(sb + PARK, &maps.m[p == 3 ? 6 : 5], 72 * j + (odd ? 0 : 64) + (p < 2 ? 576 * (p + 1) : 0), 144 * (t & 3), piece_full, 2304);
      }
      asm volatile("barrier.cluster.wait.aligned;" ::: "memory");
      uint32_t dst = sb + 2 * STAGE, bar = full0 + 16, ph = 1;
#pragma unroll 1
      for (int seg = 0; seg < 34; seg++) {
        const int n = seg >= 17 ? seg - 17 : seg;
        int ma, mb, ca, cb, row = 0;
        if (n < 3) { ma = mb = n == 2; ca = 72 * j + 8 * odd + (n == 0 ? 576 : 0); cb = ca + 576; }
        else if (n < 12) { ma = 3; mb = 2; ca = cb = 576 * j + 64 * (n - 3); }
        else { ma = mb = 4; ca = n == 12 ? 512 : ((j + 2 * n) & 7) * 64; cb = ((j + 2 * n + 1) & 7) * 64; row = 576 * j; }
        const bool zip = n == 0 || n == 3, solo = n == 1 || n == 2 || n == 16;
        const CUtensorMap *pa = &maps.m[ma], *pb = &maps.m[mb];
#pragma unroll 1
        for (int st = 0; st < (solo ? 5 : 9); st++) {
          const bool s0 = !zip && st > 4, s1 = zip || st >= 4;
          const int r0 = row + (zip ? 64 * st : s0 ? 128 * st - 576 : 128 * st), r1 = zip ? r0 : st == 4 ? row : r0 + 64;
          const bool rk = rank, sm = rk ? s1 : s0;
          asm volatile("{\n.reg .pred p, e, f;\n.reg .u32 n;\nelect.sync _|e, 0xffffffff;\nsetp.ne.and.u32 f, %7, 0, e;\nmov.u32 n, 0;\n"
                       "W: mbarrier.try_wait.parity.shared::cta.b64 p, [%1+48], %2;\n@p bra D;\n"
                       "add.u32 n, n, 1;\nsetp.lt.u32 p, n, 4194304;\n@p bra W;\ntrap;\n"
                       "D: @e mbarrier.arrive.expect_tx.shared::cta.b64 _, [%1], %6;\n"
                       "@f cp.async.bulk.tensor.2d.shared::cluster.global.mbarrier::complete_tx::bytes.multicast::cluster [%0], [%3, {%4, %5}], [%1], 3;\n}"
                       :: "r"(dst + rk * 8192), "r"(bar), "r"(ph), "l"(sm ? pb : pa), "r"(sm ? cb : ca), "r"(rk ? r1 : r0),
                          "r"(solo && st == 4 ? STAGE / 2 : STAGE), "r"((uint32_t)!(rk && solo && st == 4)) : "memory");
          dst += STAGE; bar += 8;
          if (bar == full0 + 8 * NST) { dst = sb; bar = full0; ph ^= 1; }
        }
      }
      {
#pragma unroll 1
        for (int i = 0; i < NST; i++) {
          mbar_wait_trap(bar + 48, ph);
          bar += 8;
          if (bar == full0 + 8 * NST) { bar = full0; ph ^= 1; }
        }
      }
    } else if (w == 9) {
      const uint32_t lane = lane_id();
      const uint32_t stg = sb + HSTG + lane * 16;
      uint32_t fph = 0;
#pragma unroll 1
      for (uint32_t layer = 0; layer < 2; layer++) {
        uint4* xb = scr + OFF_X + ((4 + layer) * 8 + j) * SLAB + 32 * 32;
        mbar_wait_sleep(c8_go, layer);
        int n = 0;
        while (true) {
          if (lane == 0) asm volatile("mbarrier.arrive.expect_tx.shared::cta.b64 _, [%0], 18432;" :: "r"(c8_full) : "memory");
          __syncwarp();
#pragma unroll 1
          for (uint32_t s = 0; s < 9; s++)
            bulk_load(sb + HSTG + s * 2048, s < 8 ? scr + OFF_P + (j + s * 8) * SLAB + 32 * 32 : xb, 2048, c8_full, false);
          mbar_wait(c8_full, fph); fph ^= 1;
          uint32_t bad = 0;
#pragma unroll 8
          for (int s = 0; s < 32; s++) { uint32_t v; asm volatile("ld.shared.b32 %0, [%1];" : "=r"(v) : "r"(stg + s * 512) : "memory"); bad |= v ^ (1 - layer); }
          if (__all_sync(~0u, (bad & 1u) == 0u)) break;
          __nanosleep(300);
          SPIN_GUARD(n);
        }
        asm volatile("bar.arrive 7, 96;" ::: "memory");
        float s0 = 0.f, s1 = 0.f;
#pragma unroll 1
        for (int g = 0; g < 8; g++) {
          const uint32_t a = stg + (g >> 1) * 512 + (g & 1) * 8;
          float a0 = 0.f, a1 = 0.f, a2 = 0.f, a3 = 0.f;
#pragma unroll 1
          for (int b = 0; b < 3; b++) {
            uint32_t v[6];
#pragma unroll
            for (int s = 0; s < 3; s++) lds2(a + (3 * b + s) * 2048, v + 2 * s);
#pragma unroll
            for (int s = 0; s < 3; s++) { a0 += bf_lo(v[2 * s]); a1 += bf_hi(v[2 * s]); a2 += bf_lo(v[2 * s + 1]); a3 += bf_hi(v[2 * s + 1]); }
          }
          sts1(a + 18432, pack_bf16(a0, a1)); sts1(a + 18436, pack_bf16(a2, a3));
          s0 += a0 + a1; s1 += a2 + a3;
        }
        __syncwarp();
        if (lane == 0) mbar_arrive(c8_done);
        s0 = quad_sum(s0); s1 = quad_sum(s1);
        float q0 = 0.f, q1 = 0.f;
        const uint32_t ln = lane_id();
#pragma unroll 1
        for (uint32_t i = 0; i < 4; i++) {
          uint32_t x[4];
          lds4(stg + 18432 + i * 512, x);
          stg4(xb + i * 32 + ln, 0u, 0u, 0u, 0u);
          if (layer == 0) {
            stg4(xb - 3 * 8 * SLAB + i * 32 + ln, nz(x[0]), x[1], x[2], x[3]);
#pragma unroll
            for (int e = 0; e < 4; e++) {
              const float m = (e & 1) ? s1 : s0, c = fmaf(m, -1.f / 64, bf_lo(x[e])), d = fmaf(m, -1.f / 64, bf_hi(x[e]));
              if (e & 1) q1 = fmaf(c, c, fmaf(d, d, q1)); else q0 = fmaf(c, c, fmaf(d, d, q0));
            }
          } else {
            uint32_t* o = (uint32_t*)(out + (128 * t + 32 * (j >> 1) + 2 * (ln >> 2) + (j & 1)) * 576 + 512 + 16 * i + 2 * (ln & 3));
            o[0] = x[0]; o[8 * 576] = x[1]; o[4] = x[2]; o[8 * 576 + 4] = x[3];
          }
        }
        if (layer == 0) {
          q0 = quad_sum(q0); q1 = quad_sum(q1);
          if ((ln & 3) == 0) stg4(scr + OFF_S + j * 96 + 64 + (ln >> 2), __float_as_uint(s0) | 1u, __float_as_uint(q0), __float_as_uint(s1), __float_as_uint(q1));
        }
      }
    } else {
      auto mark = [&](uint32_t k0, uint32_t v) {
        const uint32_t lane = lane_id();
#pragma unroll 1
        for (uint32_t k = k0; k < 6; k++) stg4(scr + OFF_S + (k * 4 + (lane >> 3)) * 96 + j * 8 + (lane & 7), k < 2 ? 0u : v, 0u, 0u, 0u);
      };
      if (w == 11) mark(2, 0u);
      auto phase2_duties = [&](uint32_t layer) {
        const uint32_t lane = lane_id();
        asm volatile("bar.sync 7, 96;" ::: "memory");
        if (w == 11) {
          if (layer == 0) mark(0, 1u);
          __syncwarp();
          if (lane == 0) mbar_arrive(c8_done);
        }
        mbar_wait_sleep(res_full, layer);
#pragma unroll 1
        for (uint32_t i = 0; i < 4; i++) {
          uint4* z = scr + OFF_X + ((4 + layer) * 8 + (w - 10) * 4 + i) * SLAB + 4 * j * 32 + lane;
#pragma unroll
          for (int k = 0; k < 4; k++) stg4(z + k * 32, 0u, 0u, 0u, 0u);
          __nanosleep(300);
        }
      };
#pragma unroll 1
      for (uint32_t layer = 0; layer < 2; layer++) {
        if (w == 10) {
          if (layer == 0) {
            const uint32_t lane = lane_id();
            uint32_t* fl = (uint32_t*)(scratch + OFF_F + (t * 8 + j) * 8) + (lane & 15);
            uint32_t v;
            asm volatile("ld.relaxed.gpu.global.b32 %0, [%1];" : "=r"(v) : "l"(fl) : "memory");
            mbar_wait(piece_full, 0);
            asm volatile("{\n.reg .pred e;\nelect.sync _|e, 0xffffffff;\n@e cp.async.bulk.global.shared::cta.bulk_group [%0], [%1], 2304;\n}\n"
                         "cp.async.bulk.commit_group;\ncp.async.bulk.wait_group 0;\nfence.proxy.async;"
                         :: "l"(scratch + OFF_R + j * 2304 + t * 144), "r"(sb + PARK) : "memory");
            __syncwarp();
            if (lane < 16) asm volatile("st.release.gpu.global.b32 [%0], 1;" :: "l"((uint32_t*)(scratch + OFF_F + (lane * 8 + j) * 8) + t) : "memory");
            int n = 0;
            while (!__all_sync(~0u, v != 0u)) {
              __nanosleep(100);
              SPIN_GUARD(n);
              asm volatile("ld.relaxed.gpu.global.b32 %0, [%1];" : "=r"(v) : "l"(fl) : "memory");
            }
            asm volatile("st.relaxed.gpu.global.b32 [%0], 0;" :: "l"(fl) : "memory");
            mbar_wait(x_done, 0);
          } else {
            mbar_wait_sleep(park_free, 0);
          }
          bulk_load(sb + REM, scratch + OFF_R + j * 2304, 36864, rem_full, true);
        }
        mbar_wait_sleep(rem_full, layer);
#pragma unroll 1
        for (uint32_t b = 0; b < 5; b++) {
          const uint32_t blk = sb + REM + 27648 + b * 2048, k = (w - 10) * 32 + lane_id(), rr = k & 7;
          const uint32_t dst = blk + ((k >> 3) & 1) * 1024 + rr * 128 + (((k >> 4) ^ rr) << 4);
          uint32_t v[8];
          lds4(blk + k * 16, v); lds4(blk + 1024 + k * 16, v + 4);
          asm volatile("bar.sync 3, 64;" ::: "memory");
          sts4(dst, v); sts4(dst ^ 64, v + 4);
        }
        asm volatile("fence.proxy.async.shared::cta;" ::: "memory");
        mbar_arrive(remo_full);
        if (layer) { phase2_duties(0); mbar_wait_sleep(kv_free, 0); }
        if (t > 0) {
          const uint32_t lane = lane_id(), r = lane >> 2, q = lane & 3;
#pragma unroll 1
          for (uint32_t pc = 0; pc < 3; pc++) {
            uint4* hp = scr + OFF_H + ((layer * 8 + j) * 2 + (w - 10)) * 192 + pc * 64 + lane;
            uint32_t hl[8];
            int n = 0;
            hl[4] = 1u;
            while (true) {
              ldg4(hl, hp);
              if (pc < 2) ldg4(hl + 4, hp + 32);
              if (__all_sync(~0u, hl[0] != 0u && hl[4] != 0u)) break;
              __nanosleep(100);
              SPIN_GUARD(n);
            }
            const uint32_t dst = sb + KVS + (w - 10) * 10368 + r * 144 + q * 4;
            if (pc < 2) {
#pragma unroll
              for (int g = 0; g < 8; g++) sts1(dst + pc * 20736 + odd * 16 + g * 16, hl[g]);
              stg4(hp + 32, 0u, 0u, 0u, 0u);
            } else {
              sts1(dst + (odd ? 0 : 128), hl[0]); sts1(dst + 20736 + (odd ? 0 : 128), hl[1]);
            }
            stg4(hp, 0u, 0u, 0u, 0u);
          }
        }
        asm volatile("bar.arrive 1, 192;" ::: "memory");
        mbar_wait_sleep(xb_done, layer);
        if (w == 10 && layer == 1) {
          const uint32_t lane = lane_id();
          stg4(scr + OFF_S + (lane >> 3) * 96 + j * 8 + (lane & 7), 0u, 0u, 0u, 0u);
          stg4(scr + OFF_S + (4 + (lane >> 3)) * 96 + j * 8 + (lane & 7), 0u, 0u, 0u, 0u);
          if (lane < 8) stg4(scr + OFF_S + j * 96 + 64 + lane, 0u, 0u, 0u, 0u);
        }
#pragma unroll 1
        for (uint32_t i = 0; i < 8 && (w == 11 || layer == 1); i++) {
          zero_share(scr + OFF_X + ((w - 10) * 16 + layer * 8 + i) * SLAB, j, lane_id());
          __nanosleep(500);
        }
      }
      phase2_duties(1);
    }
  } else {
    asm volatile("setmaxnreg.inc.sync.aligned.u32 240;");
    const bool lead = lane_id() == 0;
    Ring rg{2, 0};
    uint32_t prev = 0;
    uint32_t X[144];
    float rs0, rs1;
    const bool lead2 = lane_id() < 2;
    uint32_t empty_at;
    asm volatile("mapa.shared::cluster.u32 %0, %1, %2;" : "=r"(empty_at) : "r"(empty0), "r"(lane_id() & 1));
    auto release = [&](uint32_t st) { if (lead2) asm volatile("mbarrier.arrive.shared::cluster.b64 _, [%0];" :: "r"(empty_at + st * 8) : "memory"); };
    auto load_kb = [&](int kb, const uint4* src, const char* lo, uint32_t hoff) {
#pragma unroll
      for (int k = 4 * kb; k < 4 * kb + 4; k++) {
        if (k % 9 == 4) { ldg2(X + 4 * k, lo + k * 512); ldg2(X + 4 * k + 2, lo + hoff + k * 512); }
        else ldg4(X + 4 * k, src + k * 32);
      }
    };
    auto check_kb = [&](bool skip, int kb, const uint4* src, const char* lo, uint32_t hoff) {
      int n = 0;
      while (true) {
        uint32_t m = umin2(umin2(X[16 * kb], X[16 * kb + 4]), umin2(X[16 * kb + 8], X[16 * kb + 12]));
        if (kb & 1) m = umin2(m, X[16 * kb + 4 * (kb >> 1) + 2]);
        if (__all_sync(~0u, m != 0u || skip)) break;
        SPIN_GUARD(n);
        load_kb(kb, src, lo, hoff);
      }
    };
#pragma unroll 1
    for (uint32_t hf = 0; hf < 4; hf++) {
      const uint32_t layer = hf >> 1;
      const bool ffn = hf & 1;
      const uint32_t tag = 1 - layer;
      uint4* const xbase = scr + OFF_X + (layer * 8 + w) * SLAB;
      float aA[32], aB[32];
      {
        const uint32_t lane = lane_id(), r = lane >> 2, q = lane & 3;
        const uint4* src = xbase + (ffn ? 32 * SLAB : 0) + lane;
        const char* lo = (const char*)src - (ffn ? lane * 8 : 0);
        const uint32_t hoff = ffn ? 256 : 8;
        const uint32_t xoff = (w & 1) * 8192 + (16 * (w >> 1) + (lane & 15)) * 128 + (((lane >> 4) ^ (lane & 7)) << 4);
        auto load_x = [&](uint32_t b, uint32_t* d) {
#pragma unroll
          for (int i = 0; i < 4; i++) ldsm4(xblock(b) + (xoff ^ (32 * i)), d[4 * i], d[4 * i + 1], d[4 * i + 2], d[4 * i + 3]);
        };
        auto load_any = [&](int kb) { if (hf == 0) load_x(kb, X + 16 * kb); else load_kb(kb, src, lo, hoff); };
        float m0, m1, v0, v1;
        STAMP(ffn * 16 + 0);
        if (hf == 0) {
          float sum[2][4] = {}, sq[4][4] = {};
          uint32_t p0 = 0, p1 = 0;
#pragma unroll 1
          for (uint32_t b = 0; b < 9; b++) {
            uint32_t d[16];
            mbar_wait(xbar(b), 0);
            ZSTAMP(5, b);
            load_x(b, d);
            if (b == 0) { p0 = __byte_perm(__shfl_sync(~0u, d[0], lane & 28), 0, 0x1010); p1 = __byte_perm(__shfl_sync(~0u, d[1], lane & 28), 0, 0x1010); }
#pragma unroll
            for (int i = 0; i < 16; i++) d[i] = sub_bf16x2(d[i], (i & 1) ? p1 : p0);
#pragma unroll
            for (int g = 0; g < 8; g++) {
              if (!(g & 1)) mma16(sum[(g >> 1) & 1], d[2 * g], d[2 * g + 1], d[2 * g + 2], d[2 * g + 3], 0x3f803f80u, 0x3f803f80u);
              mma16(sq[g & 3], d[2 * g], 0u, 0u, d[2 * g + 1], d[2 * g], d[2 * g + 1]);
            }
            if (b == j + 1) {
              const uint32_t k0 = (9 * j) >> 1;
#pragma unroll
              for (int e = 0; e < 5; e++) {
                const uint32_t k = k0 + e;
                ldsm4(xblock(k >> 2) + (xoff ^ (32 * (k & 3))), d[0], d[1], d[2], d[3]);
                stg4(xbase + k * 32 + lane, d[0], d[1], d[2], d[3]);
              }
            }
          }
          STAMP(1);
          GSTAMP(14);
#pragma unroll
          for (int kb = 0; kb < GD; kb++) load_x(kb, X + 16 * kb);
          auto tot = [&](int e) { return (sq[0][e] + sq[1][e]) + (sq[2][e] + sq[3][e]); };
          const float a0 = (sum[0][0] + sum[1][0]) * (1.f / 576), a1 = (sum[0][2] + sum[1][2]) * (1.f / 576);
          const uint32_t dg = (lane & 28) + (r >> 1);
          v0 = fmaxf(fmaf(__shfl_sync(~0u, (r & 1) ? tot(1) : tot(0), dg), 1.f / 576, -a0 * a0), 0.f);
          v1 = fmaxf(fmaf(__shfl_sync(~0u, (r & 1) ? tot(3) : tot(2), dg), 1.f / 576, -a1 * a1), 0.f);
          m0 = bf_lo(p0) + a0; m1 = bf_lo(p1) + a1;
        } else {
          uint32_t s[3][4];
          const uint4* p = scr + OFF_S + ((ffn ? 16 : 0) + w) * 96 + q * 8 + r;
          const bool third = !ffn && q == 0;
          const uint32_t rdy = ffn ? tag : 1u;
          int n = 0;
          s[2][0] = rdy; s[2][1] = s[2][2] = s[2][3] = 0u;
          while (true) {
            ldg4(s[0], p); ldg4(s[1], p + 32);
            if (third) ldg4(s[2], p + 64);
            if (__all_sync(~0u, ((diff2(s[0][0], s[1][0], rdy) | diff2(s[1][0], s[2][0], rdy)) & 1u) == 0u)) break;
            SPIN_GUARD(n);
          }
          STAMP(ffn * 16 + 1);
          ZSTAMP(1 + ffn, 0);
          GSTAMP(14 + ffn);
#pragma unroll
          for (int kb = 0; kb < GD; kb++) load_kb(kb, src, lo, hoff);
          float t0 = 0.f, t1 = 0.f;
#pragma unroll
          for (int i = 0; i < 3; i++) { t0 += __uint_as_float(s[i][0]); t1 += __uint_as_float(s[i][2]); }
          m0 = quad_sum(t0) * (1.f / 576); m1 = quad_sum(t1) * (1.f / 576);
          const float cnt = ffn ? 72.f : 64.f, inv = ffn ? 1.f / 72 : 1.f / 64;
          v0 = 0.f; v1 = 0.f;
#pragma unroll
          for (int i = 0; i < 3; i++) {
            const float c = (i < 2 || third) ? cnt : 0.f;
            const float d0 = fmaf(__uint_as_float(s[i][0]), inv, -m0), d1 = fmaf(__uint_as_float(s[i][2]), inv, -m1);
            v0 += fmaf(d0 * d0, c, __uint_as_float(s[i][1])); v1 += fmaf(d1 * d1, c, __uint_as_float(s[i][3]));
          }
          v0 = quad_sum(v0) * (1.f / 576); v1 = quad_sum(v1) * (1.f / 576);
        }
        rs0 = rsqrtf(v0 + 1e-5f); rs1 = rsqrtf(v1 + 1e-5f);
        const uint32_t mean0 = pack_bf16(m0, m0), mean1 = pack_bf16(m1, m1);
#pragma unroll
        for (int kb = 0; kb < 9; kb++) {
          check_kb(hf == 0, kb, src, lo, hoff);
          if (kb < 2 && hf == 0) release(kb);
          if (kb + GD < 9) load_any(kb + GD);
          if (kb + GD == 8 && hf == 0 && lead) mbar_arrive(x_done);
#pragma unroll
          for (int i = 16 * kb; i < 16 * kb + 16; i++) X[i] = sub_bf16x2(X[i], (i & 1) ? mean1 : mean0);
          ZSTAMP(1 + ffn, 1 + 3 * kb);
          mbar_wait(full0 + rg.st * 8, rg.ph);
          ZSTAMP(1 + ffn, 2 + 3 * kb);
          const uint64_t desc = DESC_HI | ((sd + rg.st * STAGE) >> 4);
          wg_fence();
#pragma unroll
          for (int i = 0; i < 4; i++) wgmma_rs_n64(aA, X + 4 * (4 * kb + i), desc + i * 128, kb + i != 0);
          if (SPLITZ && kb == 8) { wg_commit(); wg_wait<1>(); wg_fence(); }
#pragma unroll
          for (int i = 0; i < 4; i++) wgmma_rs_n64(aB, X + 4 * (4 * kb + i), desc + 512 + i * 128, kb + i != 0);
          wg_commit();
          wg_wait<1>();
          ZSTAMP(1 + ffn, 3 + 3 * kb);
          if (kb > 0) release(prev);
          prev = rg.st; rg.next();
        }
        if (!SPLITZ) wg_wait<0>();
        ZSTAMP(1 + ffn, 28);
        ZSTAMP(4, 0);
        STAMP(ffn * 16 + 2);
      }
      if (!ffn) {
      const uint32_t lane = lane_id(), r = lane >> 2, q = lane & 3;
      const uint32_t kvrow = sb + KVS + (w & 1) * 10368 + (16 * (w >> 1)) * 144;
      uint32_t Q[18], Km[3][8], Ke[3][4];
      const bool edge = (t == 0 && w < 2);
      const uint32_t row0 = edge ? sb + KVS + 8 * 144 : kvrow + (lane & 7) * 144, row1 = kvrow + (8 + (lane & 7)) * 144;
      {
        const uint32_t dst = kvrow + (8 + r) * 144 + q * 4 + odd * 16, dstr = dst + (odd ? -16 : 128);
        const bool edge_out = w >= 6 && t < 15;
        uint4* const hp = scr + TILE + OFF_H + ((layer * 8 + j) * 2 + (w & 1)) * 192 + lane;
        auto put_kv = [&](float (&a)[32], int part) {
          pin(a);
          uint32_t hl[8];
#pragma unroll
          for (int g = 0; g < 8; g++) {
            hl[g] = pack_bf16(a[4 * g + 2] * rs1, a[4 * g + 3] * rs1);
            sts1(dst + part * 20736 + g * 16, pack_bf16(a[4 * g] * rs0, a[4 * g + 1] * rs0)); sts1(dst + part * 20736 + 8 * 144 + g * 16, hl[g]);
          }
          if (edge_out) { stg4(hp + part * 64, nz(hl[0]), hl[1], hl[2], hl[3]); stg4(hp + part * 64 + 32, nz(hl[4]), hl[5], hl[6], hl[7]); }
        };
        put_kv(aA, 0);
        wg_wait<0>();
        release(prev);
        float aR[12];
        mbar_wait(rem_full, layer);
        const uint64_t dr = DESC_REM | ((sd + REM) >> 4);
        wg_fence();
#pragma unroll
        for (int s = 0; s < 36; s++) {
          wgmma_rs_n24(aR, X + 4 * s, dr + s * 16, s != 0);
          if (s == 4) put_kv(aB, 1);
        }
        wg_commit();
#pragma unroll
        for (int kb = 0; kb < 9; kb++) {
          if (kb == HOFF1 && w < 4) asm volatile("bar.sync 4, 256;" ::: "memory");
          if (kb == 8 && HOFF1 < 9 && w >= 4) asm volatile("bar.arrive 4, 256;" ::: "memory");
          if (!(kb & 1)) mbar_wait(full0 + rg.st * 8, rg.ph);
          const uint64_t desc = DESC_HI | ((sd + rg.st * STAGE + (kb & 1) * 8192) >> 4);
          wg_fence();
#pragma unroll
          for (int i = 0; i < 4; i++) wgmma_rs_n64(aB, X + 4 * (4 * kb + i), desc + i * 128, kb + i != 0);
          wg_commit();
          wg_wait<1>();
          if (kb > 0 && !(kb & 1)) release(prev);
          if ((kb & 1) || kb == 8) { prev = rg.st; rg.next(); }
          if (kb == 0) {
            pin(aR);
            const uint32_t k1 = pack_bf16(aR[2] * rs1, aR[3] * rs1), v1 = pack_bf16(aR[6] * rs1, aR[7] * rs1);
            if (edge_out) stg4(hp + 128, nz(k1), v1, 0u, 0u);
            sts1(dstr, pack_bf16(aR[0] * rs0, aR[1] * rs0)); sts1(dstr + 8 * 144, k1);
            sts1(dstr + 20736, pack_bf16(aR[4] * rs0, aR[5] * rs0)); sts1(dstr + 20736 + 8 * 144, v1);
            Q[16] = pack_bf16(aR[8], aR[9]); Q[17] = pack_bf16(aR[10], aR[11]);
            if (w < 4) asm volatile("bar.arrive 2, 256;" ::: "memory");
          }
          if (kb == KLD - 2) mbar_wait(remo_full, layer);
          if (kb == KLD) {
            if (w < 4) asm volatile("bar.sync 1, 192;" ::: "memory");
            else asm volatile("bar.sync 2, 256;" ::: "memory");
#pragma unroll
            for (int nt = 0; nt < 3; nt++) {
              const uint32_t ra = (nt == 0 ? row0 : row1 + (nt - 1) * 8 * 144);
              ldsm4(ra + odd * 16 + (lane >> 3) * 16, Km[nt][0], Km[nt][1], Km[nt][2], Km[nt][3]);
              ldsm4(ra + odd * 16 + 64 + (lane >> 3) * 16, Km[nt][4], Km[nt][5], Km[nt][6], Km[nt][7]);
              ldsm4(ra + (odd ? 0 : 32) + (lane >> 3) * 32, Ke[nt][0], Ke[nt][1], Ke[nt][2], Ke[nt][3]);
            }
            const uint32_t ge = (2u << q) - 1, le = 0xfu << q, on = edge ? 0u : ~0u;
            const uint32_t bits = odd ? 0xfu | ((le & 0xfu) << 4) | (ge << 8) : ge | 0xf0u | (le << 8);
#pragma unroll
            for (int h = 0; h < 4; h++) {
              const uint32_t ma = bitmask(bits, h), mb = bitmask(bits, 4 + h), mc = bitmask(bits, 8 + h);
              Km[0][2 * h] &= ma & on; Km[0][2 * h + 1] &= mb & on; Ke[0][h] &= mc & on;
#pragma unroll
              for (int nt = 1; nt < 3; nt++) { Km[nt][2 * h] &= ma; Km[nt][2 * h + 1] &= mb; Ke[nt][h] &= mc; }
            }
          }
        }
        wg_wait<0>();
        release(prev);
        pin(aB);
        STAMP(3);
#pragma unroll
        for (int i = 0; i < 16; i++) Q[i] = pack_bf16(aB[2 * i], aB[2 * i + 1]);
      }
      {
        uint32_t V01[12][2], V2[12];
        const uint32_t rv = ((lane & 8) ? row1 : row0) + 20736, rw = row1 + 8 * 144 + 20736;
#pragma unroll
        for (int i = 0; i < 4; i++) ldsm4t(rv + odd * 16 + i * 32 + (lane >> 4) * 16, V01[2 * i][0], V01[2 * i][1], V01[2 * i + 1][0], V01[2 * i + 1][1]);
#pragma unroll
        for (int i = 0; i < 2; i++) ldsm4t(rv + (odd ? 0 : 32) + i * 64 + (lane >> 4) * 32, V01[8 + 2 * i][0], V01[8 + 2 * i][1], V01[9 + 2 * i][0], V01[9 + 2 * i][1]);
        ldsm4t(rw + odd * 16 + (lane >> 3) * 16, V2[0], V2[1], V2[2], V2[3]);
        ldsm4t(rw + odd * 16 + 64 + (lane >> 3) * 16, V2[4], V2[5], V2[6], V2[7]);
        ldsm4t(rw + (odd ? 0 : 32) + (lane >> 3) * 32, V2[8], V2[9], V2[10], V2[11]);
        const bool up0 = 2 * q > r, up1 = 2 * q + 1 > r;
        const uint32_t upm = (up0 ? 0xffffu : 0u) | (up1 ? 0xffff0000u : 0u);
        const float c0 = 0.23570226039551584f * 1.4426950408889634f * rs0, c1 = 0.23570226039551584f * 1.4426950408889634f * rs1;
        const float masked = edge ? -1e9f * 1.4426950408889634f * rcp(c0) : 0.f;
        uint32_t Om[16], Oe[8];
#pragma unroll
        for (int h = 0; h < 4; h++) {
          const uint32_t e0 = odd ? Q[(4 * h + 16) % 18] : Q[4 * h + 4], e1 = odd ? Q[(4 * h + 17) % 18] : Q[4 * h + 5];
          float S[3][4];
#pragma unroll
          for (int nt = 0; nt < 3; nt++) {
            mma16c(S[nt], Q + 4 * h, Km[nt][2 * h], Km[nt][2 * h + 1], nt == 0 ? masked : 0.f);
            mma8(S[nt], e0, e1, Ke[nt][h]);
          }
          const float s00 = up0 ? S[0][0] : S[1][0], s01 = up1 ? S[0][1] : S[1][1];
          const float s10 = up0 ? S[1][2] : S[2][2], s11 = up1 ? S[1][3] : S[2][3];
          const float m0 = quad_max(fmaxf(s00, s01)) * c0, m1 = quad_max(fmaxf(s10, s11)) * c1;
          const float p00 = ex2(fmaf(s00, c0, -m0)), p01 = ex2(fmaf(s01, c0, -m0)), p10 = ex2(fmaf(s10, c1, -m1)), p11 = ex2(fmaf(s11, c1, -m1));
          const float i0 = rcp(quad_sum(p00 + p01)), i1 = rcp(quad_sum(p10 + p11));
          const uint32_t p0 = pack_bf16(p00 * i0, p01 * i0), p1 = pack_bf16(p10 * i1, p11 * i1);
          const uint32_t pf[4] = {p0 & upm, 0u, p0 & ~upm, p1 & upm};
#pragma unroll
          for (int gi = 0; gi < 3; gi++) {
            const int g = gi < 2 ? 2 * h + gi : 8 + h;
            float o[4];
            mma16c(o, pf, V01[g][0], V01[g][1], 0.f);
            mma8(o, 0u, p1 & ~upm, V2[g]);
            uint32_t* d = gi < 2 ? Om + 2 * g : Oe + 2 * h;
            d[0] = pack_bf16(o[0], o[1]); d[1] = pack_bf16(o[2], o[3]);
          }
        }
#pragma unroll
        for (int h = 0; h < 4; h++)
#pragma unroll
          for (int e = 0; e < 2; e++) {
            if (h > 0 && !odd && q < h) Om[4 * h + e] = Oe[2 * h - 2 + e];
            if (h < 3 && odd && q > h) Om[4 * h + 2 + e] = Oe[2 * h + 2 + e];
          }
        STAMP(4);
        if (j >= PRI && lane == 0) asm volatile("st.relaxed.gpu.global.b32 [%0], %1;" :: "l"(scr + OFF_S + (8 + w) * 96 + j * 8), "r"(tag) : "memory");
        put72(xbase + 16 * SLAB, j, lane, Om, odd ? Oe[0] : Oe[6], odd ? Oe[1] : Oe[7]);
      }
      if (j < PRI && lane == 0) asm volatile("st.relaxed.gpu.global.b32 [%0], %1;" :: "l"(scr + OFF_S + (8 + w) * 96 + j * 8), "r"(tag) : "memory");
      {
        uint32_t res[18];
        const uint4* p = xbase + ((9 * j + 1) >> 1) * 32 + lane;
#pragma unroll
        for (int i = 0; i < 4; i++) ldg4(res + 4 * i, p + i * 32);
        ldg2(res + 16, odd ? (const char*)(p - 32) + 8 : (const char*)(p + 4 * 32));
        const uint4* src = xbase + 16 * SLAB + lane;
        {
          const uint4* fp = scr + OFF_S + (8 + w) * 96 + (lane & 7) * 8;
          int n = 0;
          STAMP(8);
          while (true) {
            uint32_t f;
            asm volatile("ld.relaxed.gpu.global.b32 %0, [%1];" : "=r"(f) : "l"(fp) : "memory");
            if (__all_sync(~0u, f == tag)) break;
            SPIN_GUARD(n);
          }
          STAMP(9);
        }
        if (HOFF3 < 9 && w < 4) asm volatile("bar.sync 6, 256;" ::: "memory");
#pragma unroll
        for (int kb = 0; kb < GO; kb++) load_kb(kb, src, (const char*)src - lane * 8, 256);
        float acc[36];
#pragma unroll
        for (int i = 0; i < 18; i++) { acc[2 * i] = bf_lo(res[i]); acc[2 * i + 1] = bf_hi(res[i]); }
#pragma unroll
        for (int kb = 0; kb < 9; kb++) {
          check_kb(false, kb, src, (const char*)src - lane * 8, 256);
          if (kb + GO < 9) load_kb(kb + GO, src, (const char*)src - lane * 8, 256);
          if (kb == HOFF3 && w >= 4) asm volatile("bar.arrive 6, 256;" ::: "memory");
          if (!(kb & 1)) mbar_wait(full0 + rg.st * 8, rg.ph);
          const uint32_t base = sd + rg.st * STAGE + (kb & 1) * 8192;
          const uint64_t d0 = DESC_HI | ((base >> 4) + (((sd + REM + 27648 + (kb >> 1) * 2048 + (kb & 1) * 64 - base) >> 4) << 16));
          wg_fence();
#pragma unroll
          for (int i = 0; i < 4; i++) wgmma_rs_n72(acc, X + 4 * (4 * kb + i), d0 - (uint64_t)(i * ((127u << 16) - 128u)), 1);
          wg_commit();
          wg_wait<1>();
          if (kb > 0 && !(kb & 1)) release(prev);
          if ((kb & 1) || kb == 8) { prev = rg.st; rg.next(); }
        }
        wg_wait<0>();
        release(prev);
        pin(acc);
        STAMP(10);
#pragma unroll
        for (int i = 0; i < 18; i++) res[i] = pack_bf16(acc[2 * i], acc[2 * i + 1]);
        if (j < PRI) put72(xbase + 32 * SLAB, j, lane, res, res[16], res[17]);
        publish_stats<9>(scr + OFF_S + (16 + w) * 96 + j * 8, acc, tag, lane);
        if (j >= PRI) put72(xbase + 32 * SLAB, j, lane, res, res[16], res[17]);
      }
      continue;
      }
      const uint32_t hp = sb + PARK + w * 512 + lane_id() * 16;
      auto pack8 = [&](float (&a)[32], int p, uint32_t* o) {
#pragma unroll
        for (int e = 0; e < 8; e++) asm volatile("" : "+f"(a[8 * p + e]) :: "memory");
#pragma unroll
        for (int e = 0; e < 4; e++) o[e] = pack_bf16(a[8 * p + 2 * e], a[8 * p + 2 * e + 1]);
      };
      const float ka0 = 0.7978845608028654f * rs0, kb0 = 0.044715f * ka0 * rs0 * rs0, ku0 = 0.5f * rs0 * rs0;
      const float ka1 = 0.7978845608028654f * rs1, kb1 = 0.044715f * ka1 * rs1 * rs1, ku1 = 0.5f * rs1 * rs1;
      auto packu8 = [&](int p, uint32_t* o) {
#pragma unroll
        for (int e = 0; e < 8; e++) asm volatile("" : "+f"(aA[8 * p + e]) :: "memory");
#pragma unroll
        for (int e = 0; e < 4; e++) o[e] = pack_bf16(aA[8 * p + 2 * e] * ((e & 1) ? ku1 : ku0), aA[8 * p + 2 * e + 1] * ((e & 1) ? ku1 : ku0));
      };
      auto geglu8 = [&](int p, uint32_t* u) {
#pragma unroll
        for (int e = 0; e < 8; e++) asm volatile("" : "+f"(aB[8 * p + e]) :: "memory");
        float h[8];
#pragma unroll
        for (int e = 0; e < 8; e++) {
          const float g = aB[8 * p + e];
          h[e] = fmaf(g, tanh_ap(g * fmaf(g * g, (e & 2) ? kb1 : kb0, (e & 2) ? ka1 : ka0)), g);
        }
#pragma unroll
        for (int e = 0; e < 4; e++) u[e] = mul_bf16x2(pack_bf16(h[2 * e], h[2 * e + 1]), u[e]);
      };
      auto box = [&](int b, auto&& filler) {
        const int kb = b < 9 ? b : b - 9;
        if (!(b & 1)) { if ((TRAPB >> (b >> 1)) & 1) mbar_wait_trap(full0 + rg.st * 8, rg.ph); else mbar_wait(full0 + rg.st * 8, rg.ph); }
        const uint64_t desc = DESC_HI | ((sd + rg.st * STAGE + (b & 1) * 8192) >> 4);
        wg_fence();
#pragma unroll
        for (int i = 0; i < 4; i++) {
          if (b < 9) wgmma_rs_n64(aA, X + 4 * (4 * kb + i), desc + i * 128, kb + i != 0);
          else wgmma_rs_n64(aB, X + 4 * (4 * kb + i), desc + i * 128, kb + i != 0);
          if (i == FPOS) filler();
        }
        wg_commit();
        if (b & 1) { prev = rg.st; rg.next(); } else { wg_wait<1>(); release(prev); }
      };
      auto nop = [] {};
      auto step = [&](int st, auto&& filler) { box(2 * st, nop); box(2 * st + 1, filler); };
#pragma unroll
      for (int p = 0; p < 4; p++) { uint32_t o[4]; packu8(p, o); sts4(hp + p * 4096, o); }
      box(0, nop);
      if (lead) mbar_arrive(xb_done);
#pragma unroll 1
      for (int c = 1;; c++) {
        const uint32_t hc = hp + c * 4 * 4096;
#pragma unroll
        for (int b = 1; b < 18; b++) box(b, [&] {
          if ((b & 1) && b < 8) { uint32_t o[4]; const uint32_t a = hc - (4 - (b >> 1)) * 4096; lds4(a, o); geglu8(b >> 1, o); sts4(a, o); }
          if ((b & 1) && b > 10) { uint32_t o[4]; packu8((b - 11) >> 1, o); if (c < 8) sts4(hc + ((b - 11) >> 1) * 4096, o); } });
        ZSTAMP(4, c);
        if (c == 8) break;
        box(0, nop);
      }
      wg_wait<0>();
      STAMP(21);
      GSTAMP(19);
      auto unpark = [&](int kb) {
#pragma unroll
        for (int s = 4 * kb; s < 4 * kb + 4; s++) lds4(hp + s * 4096, X + 4 * s);
      };
      unpark(0);
      uint32_t U[16];
#pragma unroll
      for (int p = 0; p < 4; p++) packu8(p, U + 4 * p);
#pragma unroll
      for (int b = 0; b < 8; b++) box(b, [&] {
        if (b < 7) unpark(b + 1);
        if (b & 1) {
          geglu8(b >> 1, U + 2 * (b - 1));
          if (rg.ph > 1) sts4(hp, U + 2 * (b - 1));
#pragma unroll
          for (int i = 0; i < 4; i++) X[128 + 2 * (b - 1) + i] = U[2 * (b - 1) + i];
        } });
      STAMP(24);
      if (layer == 0 && lead) mbar_arrive(park_free);
      const uint32_t lane2 = lane_id();
      uint4* const pw = scr + OFF_P + (j * 8 + w) * SLAB + lane2;
      const uint4* const pr = scr + OFF_P + w * SLAB + 4 * j * 32 + lane2;
      auto put_part = [&](float (&a)[32], int p, uint32_t chunk) {
        uint32_t o[4];
        pack8(a, p, o);
        stg4(pw + (chunk * 4 + p) * 32, (o[0] & ~1u) | tag, o[1], o[2], o[3]);
      };
      uint4* const xb = xbase + 32 * SLAB + 4 * j * 32;
      auto slot = [&](int p) { return sb + w * 2048 + (p < 3 ? PARK + p * 16384 : KVS + (p - 3) * 16384); };
      auto fetch = [&](int p) {
        bulk_load(slot(p), p ? scr + OFF_P + (((j - p) & 7) * 8 + w) * SLAB + 4 * j * 32 : xb, 2048, p ? pbar0 + w * 8 : res_full, true);
      };
#pragma unroll 1
      for (int sp = 0;; sp++) {
        const uint32_t ca = sp == 0 ? 8 : ((j + 2 * sp) & 7), cb = (j + 2 * sp + 1) & 7;
        if (C8 == 1 && sp == 1 && lead) mbar_arrive(c8_go);
#pragma unroll
        for (int st = 4; st < 9; st++) step(st, [&] {
          if (st == 5 || st == 6) { put_part(aA, 2 * (st - 5), ca); put_part(aA, 2 * (st - 5) + 1, ca); }
          if (st == 8 && sp > 0) { if (sp == 3) mbar_wait(c8_done, layer); fetch(2 * sp - 2); } });
        STAMP(25 + sp);
        if (sp == 3) break;
        if (C8 == 0 && sp == 0 && lead) mbar_arrive(c8_go);
#pragma unroll
        for (int st = 0; st < 4; st++) step(st, [&] {
          if (st < 2) { put_part(aB, 2 * st, cb); put_part(aB, 2 * st + 1, cb); }
          if (st == 3 && sp > 0) fetch(2 * sp - 1); });
      }
      auto load_p = [&](int p, uint32_t* d) {
#pragma unroll
        for (int i = 0; i < 4; i++) ldg4(d + 4 * i, pr + ((j - p) & 7) * 8 * SLAB + i * 32);
      };
#pragma unroll
      for (int b = 0; b < 9; b++) {
        if (b == HOFF2 && w < 4) asm volatile("bar.sync 5, 256;" ::: "memory");
        box(b, [&] {
          if (b == 1) {
#pragma unroll
            for (int p = 0; p < 4; p++) put_part(aB, p, (j + 7) & 7);
          }
          if (b == 3) { load_p(5, X); load_p(6, X + 16); }
          if (b == 7 && EXP != 1) load_p(7, X + 32); });
        if (b == 7 && HOFF2 < 9 && w >= 4) asm volatile("bar.arrive 5, 256;" ::: "memory");
      }
      mbar_wait(res_full, layer);
      mbar_wait(pbar0 + w * 8, layer);
#pragma unroll
      for (int p = 1; p < 5; p++)
#pragma unroll
        for (int i = 0; i < 4; i++) lds4(slot(p) + lane2 * 16 + i * 512, X + 48 + 16 * p + 4 * i);
#pragma unroll
      for (int i = 0; i < 4; i++) {
        const bool split = j == 2 * i + 1;
        const uint32_t a = slot(0) + i * 512 + (split ? lane2 * 8 : lane2 * 16);
        lds2(a, X + 48 + 4 * i); lds2(a + (split ? 256 : 8), X + 50 + 4 * i);
      }
      wg_wait<0>();
      release(rg.st); rg.next();
      pin(aA);
      STAMP(22);
      GSTAMP(20);
      {
        const uint32_t lane = lane2, r = lane >> 2, q = lane & 3;
        const uint32_t eye = r == 2 * q ? 0x3f80u : r == 2 * q + 1 ? 0x3f800000u : 0u;
        auto bad = [&](const uint32_t* d) { return diff2(d[0], d[4], tag) | diff2(d[8], d[12], tag); };
        auto add = [&](const uint32_t* d) {
#pragma unroll
          for (int g = 0; g < 8; g++) mma8(aA + 4 * g, d[2 * g], d[2 * g + 1], eye);
        };
        int n = 0;
        while (!__all_sync(~0u, ((or3(bad(X), bad(X + 16), bad(X + 64)) | or3(bad(X + 80), bad(X + 96), bad(X + 112))) & 1u) == 0u)) {
          SPIN_GUARD(n);
          load_p(5, X); load_p(6, X + 16);
#pragma unroll
          for (int p = 1; p < 5; p++) load_p(p, X + 48 + 16 * p);
        }
        add(X); add(X + 16);
#pragma unroll
        for (int p = 4; p >= 0; p--) add(X + 48 + 16 * ((p + 1) % 5));
        STAMP(11);
        if (EXP != 1) while (!__all_sync(~0u, (bad(X + 32) & 1u) == 0u)) { SPIN_GUARD(n); load_p(7, X + 32); }
        add(X + 32);
        STAMP(12);
        uint32_t res[16];
#pragma unroll
        for (int i = 0; i < 16; i++) res[i] = pack_bf16(aA[2 * i], aA[2 * i + 1]);
        if (layer == 0) {
          uint4* p = xbase + 8 * SLAB + 4 * j * 32 + lane;
          auto put = [&] {
#pragma unroll
            for (int i = 0; i < 4; i++) stg4(p + i * 32, nz(res[4 * i]), res[4 * i + 1], nz(res[4 * i + 2]), res[4 * i + 3]);
          };
          if (j < PRI) put();
          publish_stats<8>(scr + OFF_S + w * 96 + j * 8, aA, 1u, lane);
          if (j >= PRI) put();
          if (lane == 0) mbar_arrive(kv_free);
        } else {
          const uint32_t tb = slot(0);
          __syncwarp();
#pragma unroll
          for (int i = 0; i < 4; i++) {
            const uint32_t row = (lane2 & 7) + (lane2 & 8), g = 2 * i + (lane2 >> 4);
            asm volatile("stmatrix.sync.aligned.m8n8.x4.shared.b16 [%0], {%1,%2,%3,%4};"
                         :: "r"(tb + row * 128 + ((g ^ (row & 7)) << 4)), "r"(res[4 * i]), "r"(res[4 * i + 1]), "r"(res[4 * i + 2]), "r"(res[4 * i + 3]) : "memory");
          }
          __syncwarp();
#pragma unroll
          for (int i = 0; i < 4; i++) {
            const uint32_t row = 4 * i + (lane2 >> 3), g = lane2 & 7;
            uint32_t v[4];
            lds4(tb + row * 128 + ((g ^ (row & 7)) << 4), v);
            *(uint4*)(out + (128 * t + 32 * (w >> 1) + 2 * row + (w & 1)) * 576 + 64 * j + 8 * g) = make_uint4(v[0], v[1], v[2], v[3]);
          }
        }
      }
      STAMP(23);
    }
  }
}

typedef CUresult (*EncodeFn)(CUtensorMap*, CUtensorMapDataType, cuuint32_t, void*, const cuuint64_t*, const cuuint64_t*,
                             const cuuint32_t*, const cuuint32_t*, CUtensorMapInterleave, CUtensorMapSwizzle,
                             CUtensorMapL2promotion, CUtensorMapFloatOOBfill);

CUtensorMap make_map(EncodeFn f, const void* p, uint64_t cols, uint64_t rows, bool rem = false) {
  CUtensorMap m;
  cuuint64_t dims[2] = {cols, rows};
  cuuint64_t str[1] = {cols * 2};
  cuuint32_t box[2] = {rem ? 8u : 64u, rem ? 144u : 64u};
  cuuint32_t es[2] = {1, 1};
  f(&m, CU_TENSOR_MAP_DATA_TYPE_BFLOAT16, 2, const_cast<void*>(p), dims, str, box, es, CU_TENSOR_MAP_INTERLEAVE_NONE,
    rem ? CU_TENSOR_MAP_SWIZZLE_NONE : CU_TENSOR_MAP_SWIZZLE_128B, CU_TENSOR_MAP_L2_PROMOTION_NONE, CU_TENSOR_MAP_FLOAT_OOB_FILL_NONE);
  return m;
}

}

extern "C" void kernel_launch(void* const* d_in, const int* in_sizes, int n_in, void* d_out, int out_size) {
  void* fn = nullptr;
  cudaDriverEntryPointQueryResult qr;
  cudaGetDriverEntryPoint("cuTensorMapEncodeTiled", &fn, cudaEnableDefault, &qr);
  EncodeFn enc = (EncodeFn)fn;
  Maps maps;
  maps.m[0] = make_map(enc, d_in[1], 1728, 576); maps.m[1] = make_map(enc, d_in[2], 576, 576);
  maps.m[2] = make_map(enc, d_in[4], 4608, 576); maps.m[3] = make_map(enc, d_in[5], 4608, 576); maps.m[4] = make_map(enc, d_in[6], 576, 4608);
  maps.m[5] = make_map(enc, d_in[1], 1728, 576, true); maps.m[6] = make_map(enc, d_in[2], 576, 576, true);
  {
    cuuint64_t dims[3] = {576, 1024, 2}, str[2] = {2304, 1152};
    cuuint32_t box[3] = {64, 64, 2}, es[3] = {1, 1, 1};
    enc(&maps.m[7], CU_TENSOR_MAP_DATA_TYPE_BFLOAT16, 3, d_in[0], dims, str, box, es, CU_TENSOR_MAP_INTERLEAVE_NONE,
        CU_TENSOR_MAP_SWIZZLE_128B, CU_TENSOR_MAP_L2_PROMOTION_NONE, CU_TENSOR_MAP_FLOAT_OOB_FILL_NONE);
  }
  void* scr = nullptr;
  cudaGetSymbolAddress(&scr, g_scratch);
  cudaFuncSetAttribute(mega_kernel, cudaFuncAttributeMaxDynamicSharedMemorySize, SMEM_BYTES);
  cudaLaunchConfig_t cfg = {};
  cfg.gridDim = dim3(128); cfg.blockDim = dim3(384); cfg.dynamicSmemBytes = SMEM_BYTES; cfg.stream = cudaStreamPerThread;
  cudaLaunchAttribute at[1];
  at[0].id = cudaLaunchAttributeClusterDimension; at[0].val.clusterDim.x = 2; at[0].val.clusterDim.y = 1; at[0].val.clusterDim.z = 1;
  cfg.attrs = at; cfg.numAttrs = 1;
  int dev = 0, sms = 0, clusters = 0;
  cudaGetDevice(&dev);
  cudaDeviceGetAttribute(&sms, cudaDevAttrMultiProcessorCount, dev);
  cudaOccupancyMaxActiveClusters(&clusters, mega_kernel, &cfg);
  if (sms == 132 && clusters == 66) cfg.gridDim = dim3(132);
  cudaLaunchKernelEx(&cfg, mega_kernel, maps, (uint4*)scr, (__nv_bfloat16*)d_out);
}
```

```cpp
#include <cuda_runtime.h>
#include <cuda.h>
#include <cuda_bf16.h>
#include <stdint.h>

#define TRACE 0
#define GUARD 0
#define TRAPB 1
#define HOFF1 99
#define HOFF2 99
#define KLD 8
#define ZT 0
#define SLEEP 500
#define SPLITZ 1
#define C8 1
#define HOFF3 99
#define GO 3
#define EXP 0
#define FPOS 2

namespace {

constexpr int NST = 6;
constexpr int STAGE = 16384;
constexpr int PARK = NST * STAGE;
constexpr int REM = PARK + 49152;
constexpr int KVS = REM + 40960;
constexpr int PIECE = PARK + 7 * STAGE;
constexpr int HSTG = KVS + 16384;
constexpr int BARS = KVS + 41472;
constexpr int TRC = BARS + 512;
constexpr int SMEM_BYTES = TRC + (TRACE ? 512 : 0);
static_assert(NST == 6, "the producer addresses empty barriers as full + 48");
static_assert(BARS >= PARK + 131072, "barriers overlap park");
static_assert(SMEM_BYTES <= 232448, "smem");

constexpr int SLAB = 36 * 32;
constexpr int SPIN_MAX = 1 << 17;
constexpr uint32_t PRI = 3;
constexpr int GD = 3;
constexpr int OFF_S = 0;
constexpr int OFF_H = OFF_S + 3 * 8 * 96;
constexpr int OFF_X = OFF_H + 2 * 8 * 384;
constexpr int OFF_P = OFF_X + 6 * 8 * SLAB;
constexpr int TILE = OFF_P + 8 * 8 * SLAB;
constexpr int OFF_R = 16 * TILE;
constexpr int OFF_F = OFF_R + 8 * 2304;
constexpr int SCRATCH = OFF_F + 128 * 8;

}

__device__ uint4 g_scratch[SCRATCH];

namespace {

constexpr uint64_t DESC_HI = 0x4000004000000000ull;
constexpr uint64_t DESC_REM = (576ull << 32) | (8u << 16);
__device__ __forceinline__ void wgmma_rs_n64(float (&d)[32], const uint32_t* a, uint64_t desc, int scale_d) {
  asm volatile("{\n.reg .pred p;\nsetp.ne.b32 p, %37, 0;\n"
    "wgmma.mma_async.sync.aligned.m64n64k16.f32.bf16.bf16 "
    "{%0, %1, %2, %3, %4, %5, %6, %7, %8, %9, %10, %11, %12, %13, %14, %15, %16, %17, %18, %19, %20, %21, %22, %23, %24, %25, %26, %27, %28, %29, %30, %31}, "
    "{%32, %33, %34, %35}, %36, p, 1, 1, 1;\n}\n"
    : "+f"(d[0]), "+f"(d[1]), "+f"(d[2]), "+f"(d[3]), "+f"(d[4]), "+f"(d[5]), "+f"(d[6]), "+f"(d[7]), "+f"(d[8]), "+f"(d[9]), "+f"(d[10]), "+f"(d[11]), "+f"(d[12]), "+f"(d[13]), "+f"(d[14]), "+f"(d[15]), "+f"(d[16]), "+f"(d[17]), "+f"(d[18]), "+f"(d[19]), "+f"(d[20]), "+f"(d[21]), "+f"(d[22]), "+f"(d[23]), "+f"(d[24]), "+f"(d[25]), "+f"(d[26]), "+f"(d[27]), "+f"(d[28]), "+f"(d[29]), "+f"(d[30]), "+f"(d[31])
    : "r"(a[0]), "r"(a[1]), "r"(a[2]), "r"(a[3]), "l"(desc), "r"(scale_d));
}
__device__ __forceinline__ void wgmma_rs_n72(float (&d)[36], const uint32_t* a, uint64_t desc, int scale_d) {
  asm volatile("{\n.reg .pred p;\nsetp.ne.b32 p, %41, 0;\n"
    "wgmma.mma_async.sync.aligned.m64n72k16.f32.bf16.bf16 "
    "{%0, %1, %2, %3, %4, %5, %6, %7, %8, %9, %10, %11, %12, %13, %14, %15, %16, %17, %18, %19, %20, %21, %22, %23, %24, %25, %26, %27, %28, %29, %30, %31, %32, %33, %34, %35}, "
    "{%36, %37, %38, %39}, %40, p, 1, 1, 1;\n}\n"
    : "+f"(d[0]), "+f"(d[1]), "+f"(d[2]), "+f"(d[3]), "+f"(d[4]), "+f"(d[5]), "+f"(d[6]), "+f"(d[7]), "+f"(d[8]), "+f"(d[9]), "+f"(d[10]), "+f"(d[11]), "+f"(d[12]), "+f"(d[13]), "+f"(d[14]), "+f"(d[15]), "+f"(d[16]), "+f"(d[17]), "+f"(d[18]), "+f"(d[19]), "+f"(d[20]), "+f"(d[21]), "+f"(d[22]), "+f"(d[23]), "+f"(d[24]), "+f"(d[25]), "+f"(d[26]), "+f"(d[27]), "+f"(d[28]), "+f"(d[29]), "+f"(d[30]), "+f"(d[31]), "+f"(d[32]), "+f"(d[33]), "+f"(d[34]), "+f"(d[35])
    : "r"(a[0]), "r"(a[1]), "r"(a[2]), "r"(a[3]), "l"(desc), "r"(scale_d));
}
__device__ __forceinline__ void wgmma_rs_n24(float (&d)[12], const uint32_t* a, uint64_t desc, int scale_d) {
  asm volatile("{\n.reg .pred p;\nsetp.ne.b32 p, %17, 0;\n"
    "wgmma.mma_async.sync.aligned.m64n24k16.f32.bf16.bf16 "
    "{%0, %1, %2, %3, %4, %5, %6, %7, %8, %9, %10, %11}, "
    "{%12, %13, %14, %15}, %16, p, 1, 1, 1;\n}\n"
    : "+f"(d[0]), "+f"(d[1]), "+f"(d[2]), "+f"(d[3]), "+f"(d[4]), "+f"(d[5]), "+f"(d[6]), "+f"(d[7]), "+f"(d[8]), "+f"(d[9]), "+f"(d[10]), "+f"(d[11])
    : "r"(a[0]), "r"(a[1]), "r"(a[2]), "r"(a[3]), "l"(desc), "r"(scale_d));
}

__device__ __forceinline__ void mbar_init(uint32_t a, uint32_t c) { asm volatile("mbarrier.init.shared::cta.b64 [%0], %1;" :: "r"(a), "r"(c)); }
__device__ __forceinline__ void mbar_arrive(uint32_t a) { asm volatile("mbarrier.arrive.shared::cta.b64 _, [%0];" :: "r"(a) : "memory"); }
__device__ __forceinline__ void mbar_wait_trap(uint32_t a, uint32_t ph) {
  asm volatile("{\n.reg .pred p;\n.reg .u32 n;\nmov.u32 n, 0;\n"
               "W: mbarrier.try_wait.parity.shared::cta.b64 p, [%0], %1;\n@p bra D;\n"
               "add.u32 n, n, 1;\nsetp.lt.u32 p, n, 4194304;\n@p bra W;\ntrap;\nD:\n}" :: "r"(a), "r"(ph) : "memory");
}
__device__ __forceinline__ void mbar_wait(uint32_t a, uint32_t ph) {
  asm volatile("{\n.reg .pred p;\nW: mbarrier.try_wait.parity.shared::cta.b64 p, [%0], %1;\n@!p bra W;\n}" :: "r"(a), "r"(ph) : "memory");
}
__device__ __forceinline__ void mbar_wait_sleep(uint32_t a, uint32_t ph) {
  asm volatile("{\n.reg .pred p;\nW: mbarrier.test_wait.parity.shared::cta.b64 p, [%0], %1;\n@p bra D;\nnanosleep.u32 %2;\nbra W;\nD:\n}" :: "r"(a), "r"(ph), "n"(SLEEP) : "memory");
}
__device__ __forceinline__ void wg_fence() { asm volatile("wgmma.fence.sync.aligned;" ::: "memory"); }
__device__ __forceinline__ void wg_commit() { asm volatile("wgmma.commit_group.sync.aligned;" ::: "memory"); }
template <int N> __device__ __forceinline__ void wg_wait() { asm volatile("wgmma.wait_group.sync.aligned %0;" :: "n"(N) : "memory"); }
__device__ __forceinline__ float tanh_ap(float x) { float y; asm("tanh.approx.f32 %0, %1;" : "=f"(y) : "f"(x)); return y; }
__device__ __forceinline__ float ex2(float x) { float y; asm("ex2.approx.ftz.f32 %0, %1;" : "=f"(y) : "f"(x)); return y; }
__device__ __forceinline__ uint32_t pack_bf16(float lo, float hi) { uint32_t r; asm("cvt.rn.bf16x2.f32 %0, %1, %2;" : "=r"(r) : "f"(hi), "f"(lo)); return r; }
__device__ __forceinline__ float bf_lo(uint32_t v) { return __uint_as_float(v << 16); }
__device__ __forceinline__ float bf_hi(uint32_t v) { return __uint_as_float(v & 0xffff0000u); }
__device__ __forceinline__ uint32_t sub_bf16x2(uint32_t a, uint32_t b) { uint32_t r; asm("sub.rn.bf16x2 %0, %1, %2;" : "=r"(r) : "r"(a), "r"(b)); return r; }
__device__ __forceinline__ uint32_t mul_bf16x2(uint32_t a, uint32_t b) { uint32_t r; asm("mul.rn.bf16x2 %0, %1, %2;" : "=r"(r) : "r"(a), "r"(b)); return r; }
__device__ __forceinline__ uint32_t diff2(uint32_t a, uint32_t b, uint32_t t) { uint32_t r; asm("lop3.b32 %0, %1, %2, %3, 0x7e;" : "=r"(r) : "r"(a), "r"(b), "r"(t)); return r; }
__device__ __forceinline__ uint32_t or3(uint32_t a, uint32_t b, uint32_t c) { uint32_t r; asm("lop3.b32 %0, %1, %2, %3, 0xfe;" : "=r"(r) : "r"(a), "r"(b), "r"(c)); return r; }
__device__ __forceinline__ uint32_t umin2(uint32_t a, uint32_t b) { uint32_t r; asm("min.u32 %0, %1, %2;" : "=r"(r) : "r"(a), "r"(b)); return r; }
__device__ __forceinline__ uint32_t bitmask(uint32_t v, int bit) { uint32_t r; asm("bfe.s32 %0, %1, %2, 1;" : "=r"(r) : "r"(v), "r"(bit)); return r; }
__device__ __forceinline__ uint32_t nz(uint32_t w) { return w == 0u ? 0x8000u : w; }

__device__ __forceinline__ void ldg4(uint32_t* d, const uint4* p) {
  asm volatile("ld.relaxed.gpu.global.v4.b32 {%0,%1,%2,%3}, [%4];" : "=r"(d[0]), "=r"(d[1]), "=r"(d[2]), "=r"(d[3]) : "l"(p) : "memory");
}
__device__ __forceinline__ void ldg2(uint32_t* d, const void* p) {
  asm volatile("ld.relaxed.gpu.global.v2.b32 {%0,%1}, [%2];" : "=r"(d[0]), "=r"(d[1]) : "l"(p) : "memory");
}
__device__ __forceinline__ void stg4(uint4* p, uint32_t a, uint32_t b, uint32_t c, uint32_t d) {
  asm volatile("st.relaxed.gpu.global.v4.b32 [%0], {%1,%2,%3,%4};" :: "l"(p), "r"(a), "r"(b), "r"(c), "r"(d) : "memory");
}
__device__ __forceinline__ void stg2(void* p, uint32_t a, uint32_t b) {
  asm volatile("st.relaxed.gpu.global.v2.b32 [%0], {%1,%2};" :: "l"(p), "r"(a), "r"(b) : "memory");
}
__device__ __forceinline__ void sts4(uint32_t a, const uint32_t* o) { asm volatile("st.shared.v4.b32 [%0], {%1,%2,%3,%4};" :: "r"(a), "r"(o[0]), "r"(o[1]), "r"(o[2]), "r"(o[3]) : "memory"); }
__device__ __forceinline__ void lds4(uint32_t a, uint32_t* o) { asm volatile("ld.shared.v4.b32 {%0,%1,%2,%3}, [%4];" : "=r"(o[0]), "=r"(o[1]), "=r"(o[2]), "=r"(o[3]) : "r"(a) : "memory"); }
__device__ __forceinline__ void lds2(uint32_t a, uint32_t* o) { asm volatile("ld.shared.v2.b32 {%0,%1}, [%2];" : "=r"(o[0]), "=r"(o[1]) : "r"(a) : "memory"); }
__device__ __forceinline__ float rcp(float x) { float y; asm("rcp.approx.ftz.f32 %0, %1;" : "=f"(y) : "f"(x)); return y; }
__device__ __forceinline__ void sts1(uint32_t a, uint32_t v) { asm volatile("st.shared.b32 [%0], %1;" :: "r"(a), "r"(v) : "memory"); }
__device__ __forceinline__ void ldsm4(uint32_t a, uint32_t& r0, uint32_t& r1, uint32_t& r2, uint32_t& r3) {
  asm volatile("ldmatrix.sync.aligned.m8n8.x4.shared.b16 {%0,%1,%2,%3}, [%4];" : "=r"(r0), "=r"(r1), "=r"(r2), "=r"(r3) : "r"(a) : "memory");
}
__device__ __forceinline__ void ldsm4t(uint32_t a, uint32_t& r0, uint32_t& r1, uint32_t& r2, uint32_t& r3) {
  asm volatile("ldmatrix.sync.aligned.m8n8.x4.trans.shared.b16 {%0,%1,%2,%3}, [%4];" : "=r"(r0), "=r"(r1), "=r"(r2), "=r"(r3) : "r"(a) : "memory");
}
__device__ __forceinline__ void mma16(float* c, uint32_t a0, uint32_t a1, uint32_t a2, uint32_t a3, uint32_t b0, uint32_t b1) {
  asm("mma.sync.aligned.m16n8k16.row.col.f32.bf16.bf16.f32 {%0,%1,%2,%3}, {%4,%5,%6,%7}, {%8,%9}, {%0,%1,%2,%3};"
    : "+f"(c[0]), "+f"(c[1]), "+f"(c[2]), "+f"(c[3]) : "r"(a0), "r"(a1), "r"(a2), "r"(a3), "r"(b0), "r"(b1));
}
__device__ __forceinline__ void mma16c(float* d, const uint32_t* a, uint32_t b0, uint32_t b1, float c01) {
  asm("mma.sync.aligned.m16n8k16.row.col.f32.bf16.bf16.f32 {%0,%1,%2,%3}, {%4,%5,%6,%7}, {%8,%9}, {%10,%10,%10,%10};"
    : "=f"(d[0]), "=f"(d[1]), "=f"(d[2]), "=f"(d[3]) : "r"(a[0]), "r"(a[1]), "r"(a[2]), "r"(a[3]), "r"(b0), "r"(b1), "f"(c01));
}
__device__ __forceinline__ void mma8(float* c, uint32_t a0, uint32_t a1, uint32_t b0) {
  asm("mma.sync.aligned.m16n8k8.row.col.f32.bf16.bf16.f32 {%0,%1,%2,%3}, {%4,%5}, {%6}, {%0,%1,%2,%3};"
    : "+f"(c[0]), "+f"(c[1]), "+f"(c[2]), "+f"(c[3]) : "r"(a0), "r"(a1), "r"(b0));
}
__device__ __forceinline__ uint32_t lane_id() { uint32_t l; asm volatile("mov.u32 %0, %%laneid;" : "=r"(l)); return l; }
__device__ __forceinline__ float quad_sum(float v) { v += __shfl_xor_sync(~0u, v, 1); v += __shfl_xor_sync(~0u, v, 2); return v; }
__device__ __forceinline__ float quad_max(float v) { v = fmaxf(v, __shfl_xor_sync(~0u, v, 1)); v = fmaxf(v, __shfl_xor_sync(~0u, v, 2)); return v; }
template <int N> __device__ __forceinline__ void pin(float (&d)[N]) {
#pragma unroll
  for (int i = 0; i < N; i++) asm volatile("" : "+f"(d[i]) :: "memory");
}
#define SPIN_GUARD(n) if (++(n) > SPIN_MAX) break

template <int NG> __device__ __forceinline__ void publish_stats(uint4* dst, const float* y, uint32_t tag, uint32_t lane) {
  float s0 = 0.f, s1 = 0.f;
#pragma unroll
  for (int g = 0; g < NG; g++) { s0 += y[4 * g] + y[4 * g + 1]; s1 += y[4 * g + 2] + y[4 * g + 3]; }
  s0 = quad_sum(s0); s1 = quad_sum(s1);
  const float m0 = s0 * (1.f / (8 * NG)), m1 = s1 * (1.f / (8 * NG));
  float q0 = 0.f, q1 = 0.f, q2 = 0.f, q3 = 0.f;
#pragma unroll
  for (int g = 0; g < NG; g++) {
    const float a = y[4 * g] - m0, b = y[4 * g + 1] - m0, c = y[4 * g + 2] - m1, d = y[4 * g + 3] - m1;
    q0 = fmaf(a, a, q0); q1 = fmaf(b, b, q1); q2 = fmaf(c, c, q2); q3 = fmaf(d, d, q3);
  }
  q0 = quad_sum(q0 + q1); q2 = quad_sum(q2 + q3);
  if ((lane & 3) == 0)
    stg4(dst + (lane >> 2), (__float_as_uint(s0) & ~1u) | tag, __float_as_uint(q0), __float_as_uint(s1), __float_as_uint(q2));
}

__device__ __forceinline__ void put72(uint4* slab, uint32_t j, uint32_t lane, const uint32_t* v, uint32_t r0, uint32_t r1) {
  uint4* p = slab + ((9 * j + 1) >> 1) * 32;
#pragma unroll
  for (int i = 0; i < 4; i++) stg4(p + lane + i * 32, nz(v[4 * i]), v[4 * i + 1], v[4 * i + 2], v[4 * i + 3]);
  stg2((char*)((j & 1) ? p - 16 : p + 4 * 32) + lane * 8, nz(r0), r1);
}
__device__ __forceinline__ void zero_share(uint4* slab, uint32_t j, uint32_t lane) {
  uint4* p = slab + j * 144 + lane;
#pragma unroll
  for (int i = 0; i < 4; i++) stg4(p + i * 32, 0u, 0u, 0u, 0u);
  if (lane < 16) stg4(p + 128, 0u, 0u, 0u, 0u);
}

struct Maps { CUtensorMap m[8]; };

struct Ring {
  uint32_t st, ph;
  __device__ __forceinline__ void next() { if (++st == NST) { st = 0; ph ^= 1; } }
};

#define GSTAMP(i) do {} while (0)
#define STAMP(i) do {} while (0)
#define ZSTAMP(m, i) do {} while (0)

__device__ __forceinline__ void tma_box(uint32_t dst, const CUtensorMap* m, int col, int row, uint32_t bar, uint32_t expect) {
  asm volatile("{\n.reg .pred e, h;\nelect.sync _|e, 0xffffffff;\nsetp.ne.and.u32 h, %5, 0, e;\n"
               "@h mbarrier.arrive.expect_tx.shared::cta.b64 _, [%2], %5;\n"
               "@e cp.async.bulk.tensor.2d.shared::cluster.global.mbarrier::complete_tx::bytes [%0], [%1, {%3, %4}], [%2];\n}"
               :: "r"(dst), "l"(m), "r"(bar), "r"(col), "r"(row), "r"(expect) : "memory");
}

__device__ __forceinline__ void bulk_load(uint32_t dst, const void* src, uint32_t bytes, uint32_t bar, bool arm) {
  asm volatile("{\n.reg .pred e, h;\nelect.sync _|e, 0xffffffff;\nsetp.ne.and.u32 h, %4, 0, e;\n"
               "@h mbarrier.arrive.expect_tx.shared::cta.b64 _, [%3], %2;\n"
               "@e cp.async.bulk.shared::cluster.global.mbarrier::complete_tx::bytes [%0], [%1], %2, [%3];\n}"
               :: "r"(dst), "l"(src), "r"(bytes), "r"(bar), "r"((uint32_t)arm) : "memory");
}

__global__ void __launch_bounds__(384, 1) mega_kernel(
    const __grid_constant__ Maps maps, uint4* __restrict__ scratch,
    __nv_bfloat16* __restrict__ out) {
  extern __shared__ __align__(1024) uint8_t smem[];
  const uint32_t sb = (uint32_t)__cvta_generic_to_shared(smem);
  const uint32_t full0 = sb + BARS, empty0 = full0 + 8 * NST, rem_full = empty0 + 8 * NST, park_free = rem_full + 8, kv_free = park_free + 8;
  const uint32_t c8_go = kv_free + 8, c8_done = c8_go + 8, c8_full = c8_done + 8, remo_full = c8_full + 8, piece_full = remo_full + 8, xb_done = piece_full + 8, res_full = xb_done + 8, pbar0 = res_full + 8;
  const uint32_t x_done = pbar0 + 64, x_ring = x_done + 8, xbar0 = x_ring + 8;
  const uint32_t w = __shfl_sync(~0u, threadIdx.x >> 5, 0);
  uint32_t pair = blockIdx.x >> 1;
  if (gridDim.x == 132) {
    uint32_t smid;
    asm("mov.u32 %0, %%smid;" : "=r"(smid));
    const uint32_t tpc = smid >> 1;
    if (tpc == 60 || tpc == 61) { if (threadIdx.x == 0) { __nanosleep(20000); } return; }
    pair = tpc < 32 ? tpc : tpc >= 62 ? (tpc - 58) * 8 : 33 + (tpc - 32) / 7 * 8 + (tpc - 32) % 7;
  }
  const uint32_t rank = blockIdx.x & 1, t = (pair & 7) * 2 + rank, j = pair >> 3;
  const uint32_t sd = sb & 0x3ffff;
  const uint32_t odd = j & 1;
  uint4* const scr = scratch + t * TILE;
  const uint32_t xs = sb + (NST - 2) * STAGE;
  if (w == 8) {
    if (threadIdx.x == 256) {
      for (int i = 0; i < NST; i++) { mbar_init(full0 + 8 * i, 1); mbar_init(empty0 + 8 * i, 16); }
      mbar_init(rem_full, 1); mbar_init(park_free, 8); mbar_init(kv_free, 8); mbar_init(c8_go, 8); mbar_init(c8_done, 2); mbar_init(c8_full, 1);
      mbar_init(remo_full, 64); mbar_init(piece_full, 1); mbar_init(xb_done, 8); mbar_init(res_full, 8); mbar_init(x_done, 8); mbar_init(x_ring, 16);
      for (int i = 0; i < 8; i++) mbar_init(pbar0 + 8 * i, 4);
      for (int i = 0; i < 9; i++) mbar_init(xbar0 + 8 * i, 1);
      asm volatile("fence.mbarrier_init.release.cluster;" ::: "memory");
    }
    __syncwarp();
  }
  asm volatile("barrier.cluster.arrive.relaxed.aligned;" ::: "memory");
  if (w != 8) asm volatile("barrier.cluster.wait.aligned;" ::: "memory");

  if (w >= 8) {
    asm volatile("setmaxnreg.dec.sync.aligned.u32 24;");
    if (w == 8) {
#pragma unroll 1
      for (uint32_t b = 0; b < 9; b++)
        asm volatile("{\n.reg .pred e;\nelect.sync _|e, 0xffffffff;\n@e mbarrier.arrive.expect_tx.shared::cta.b64 _, [%2], 16384;\n"
                     "@e cp.async.bulk.tensor.3d.shared::cluster.global.mbarrier::complete_tx::bytes [%0], [%1, {%3, %4, 0}], [%2];\n}"
                     :: "r"(xs + b * STAGE), "l"(&maps.m[7]), "r"(xbar0 + 8 * b), "r"(64 * b), "r"(64 * t) : "memory");
      tma_box(sb + PIECE, &maps.m[t >= 12 ? 6 : 5], 72 * j + (odd ? 0 : 64) + (t < 8 ? 576 * ((t >> 2) + 1) : 0), 144 * (t & 3), piece_full, 2304);
      asm volatile("barrier.cluster.wait.aligned;" ::: "memory");
      uint32_t dst = sb, bar = full0, ph = 1;
#pragma unroll 1
      for (int seg = 0; seg < 34; seg++) {
        const int n = seg >= 17 ? seg - 17 : seg;
        int ma, mb, ca, cb, row = 0;
        if (n < 3) { ma = mb = n == 2; ca = 72 * j + 8 * odd + (n == 0 ? 576 : 0); cb = ca + 576; }
        else if (n < 12) { ma = 3; mb = 2; ca = cb = 576 * j + 64 * (n - 3); }
        else { ma = mb = 4; ca = n == 12 ? 512 : ((j + 2 * n) & 7) * 64; cb = ((j + 2 * n + 1) & 7) * 64; row = 576 * j; }
        const bool zip = n == 0 || n == 3, solo = n == 1 || n == 2 || n == 16;
        const CUtensorMap *pa = &maps.m[ma], *pb = &maps.m[mb];
#pragma unroll 1
        for (int st = 0; st < (solo ? 5 : 9); st++) {
          if (seg == 0 && st == NST - 2) mbar_wait(x_ring, 0);
          const bool s0 = !zip && st > 4, s1 = zip || st >= 4;
          const int r0 = row + (zip ? 64 * st : s0 ? 128 * st - 576 : 128 * st), r1 = zip ? r0 : st == 4 ? row : r0 + 64;
          const bool rk = rank, sm = rk ? s1 : s0;
          asm volatile("{\n.reg .pred p, e, f;\n.reg .u32 n;\nelect.sync _|e, 0xffffffff;\nsetp.ne.and.u32 f, %7, 0, e;\nmov.u32 n, 0;\n"
                       "W: mbarrier.try_wait.parity.shared::cta.b64 p, [%1+48], %2;\n@p bra D;\n"
                       "add.u32 n, n, 1;\nsetp.lt.u32 p, n, 4194304;\n@p bra W;\ntrap;\n"
                       "D: @e mbarrier.arrive.expect_tx.shared::cta.b64 _, [%1], %6;\n"
                       "@f cp.async.bulk.tensor.2d.shared::cluster.global.mbarrier::complete_tx::bytes.multicast::cluster [%0], [%3, {%4, %5}], [%1], 3;\n}"
                       :: "r"(dst + rk * 8192), "r"(bar), "r"(ph), "l"(sm ? pb : pa), "r"(sm ? cb : ca), "r"(rk ? r1 : r0),
                          "r"(solo && st == 4 ? STAGE / 2 : STAGE), "r"((uint32_t)!(rk && solo && st == 4)) : "memory");
          dst += STAGE; bar += 8;
          if (bar == full0 + 8 * NST) { dst = sb; bar = full0; ph ^= 1; }
        }
      }
      {
#pragma unroll 1
        for (int i = 0; i < NST; i++) {
          mbar_wait_trap(bar + 48, ph);
          bar += 8;
          if (bar == full0 + 8 * NST) { bar = full0; ph ^= 1; }
        }
      }
    } else if (w == 9) {
      const uint32_t lane = lane_id();
      const uint32_t stg = sb + HSTG + lane * 16;
      uint32_t fph = 0;
#pragma unroll 1
      for (uint32_t layer = 0; layer < 2; layer++) {
        uint4* xb = scr + OFF_X + ((4 + layer) * 8 + j) * SLAB + 32 * 32;
        mbar_wait_sleep(c8_go, layer);
        int n = 0;
        while (true) {
          if (lane == 0) asm volatile("mbarrier.arrive.expect_tx.shared::cta.b64 _, [%0], 18432;" :: "r"(c8_full) : "memory");
          __syncwarp();
#pragma unroll 1
          for (uint32_t s = 0; s < 9; s++)
            bulk_load(sb + HSTG + s * 2048, s < 8 ? scr + OFF_P + (j + s * 8) * SLAB + 32 * 32 : xb, 2048, c8_full, false);
          mbar_wait(c8_full, fph); fph ^= 1;
          uint32_t bad = 0;
#pragma unroll 8
          for (int s = 0; s < 32; s++) { uint32_t v; asm volatile("ld.shared.b32 %0, [%1];" : "=r"(v) : "r"(stg + s * 512) : "memory"); bad |= v ^ (1 - layer); }
          if (__all_sync(~0u, (bad & 1u) == 0u)) break;
          __nanosleep(300);
          SPIN_GUARD(n);
        }
        asm volatile("bar.arrive 7, 96;" ::: "memory");
        float s0 = 0.f, s1 = 0.f;
#pragma unroll 1
        for (int g = 0; g < 8; g++) {
          const uint32_t a = stg + (g >> 1) * 512 + (g & 1) * 8;
          float a0 = 0.f, a1 = 0.f, a2 = 0.f, a3 = 0.f;
#pragma unroll 1
          for (int b = 0; b < 3; b++) {
            uint32_t v[6];
#pragma unroll
            for (int s = 0; s < 3; s++) lds2(a + (3 * b + s) * 2048, v + 2 * s);
#pragma unroll
            for (int s = 0; s < 3; s++) { a0 += bf_lo(v[2 * s]); a1 += bf_hi(v[2 * s]); a2 += bf_lo(v[2 * s + 1]); a3 += bf_hi(v[2 * s + 1]); }
          }
          sts1(a + 18432, pack_bf16(a0, a1)); sts1(a + 18436, pack_bf16(a2, a3));
          s0 += a0 + a1; s1 += a2 + a3;
        }
        __syncwarp();
        if (lane == 0) mbar_arrive(c8_done);
        s0 = quad_sum(s0); s1 = quad_sum(s1);
        float q0 = 0.f, q1 = 0.f;
        const uint32_t ln = lane_id();
#pragma unroll 1
        for (uint32_t i = 0; i < 4; i++) {
          uint32_t x[4];
          lds4(stg + 18432 + i * 512, x);
          stg4(xb + i * 32 + ln, 0u, 0u, 0u, 0u);
          if (layer == 0) {
            stg4(xb - 3 * 8 * SLAB + i * 32 + ln, nz(x[0]), x[1], x[2], x[3]);
#pragma unroll
            for (int e = 0; e < 4; e++) {
              const float m = (e & 1) ? s1 : s0, c = fmaf(m, -1.f / 64, bf_lo(x[e])), d = fmaf(m, -1.f / 64, bf_hi(x[e]));
              if (e & 1) q1 = fmaf(c, c, fmaf(d, d, q1)); else q0 = fmaf(c, c, fmaf(d, d, q0));
            }
          } else {
            uint32_t* o = (uint32_t*)(out + (128 * t + 32 * (j >> 1) + 2 * (ln >> 2) + (j & 1)) * 576 + 512 + 16 * i + 2 * (ln & 3));
            o[0] = x[0]; o[8 * 576] = x[1]; o[4] = x[2]; o[8 * 576 + 4] = x[3];
          }
        }
        if (layer == 0) {
          q0 = quad_sum(q0); q1 = quad_sum(q1);
          if ((ln & 3) == 0) stg4(scr + OFF_S + j * 96 + 64 + (ln >> 2), __float_as_uint(s0) | 1u, __float_as_uint(q0), __float_as_uint(s1), __float_as_uint(q1));
        }
      }
    } else {
      auto mark = [&](uint32_t k0, uint32_t v) {
        const uint32_t lane = lane_id();
#pragma unroll 1
        for (uint32_t k = k0; k < 6; k++) stg4(scr + OFF_S + (k * 4 + (lane >> 3)) * 96 + j * 8 + (lane & 7), k < 2 ? 0u : v, 0u, 0u, 0u);
      };
      if (w == 11) mark(2, 0u);
      auto phase2_duties = [&](uint32_t layer) {
        const uint32_t lane = lane_id();
        asm volatile("bar.sync 7, 96;" ::: "memory");
        if (w == 11) {
          if (layer == 0) mark(0, 1u);
          __syncwarp();
          if (lane == 0) mbar_arrive(c8_done);
        }
        mbar_wait_sleep(res_full, layer);
#pragma unroll 1
        for (uint32_t i = 0; i < 4; i++) {
          uint4* z = scr + OFF_X + ((4 + layer) * 8 + (w - 10) * 4 + i) * SLAB + 4 * j * 32 + lane;
#pragma unroll
          for (int k = 0; k < 4; k++) stg4(z + k * 32, 0u, 0u, 0u, 0u);
          __nanosleep(300);
        }
      };
#pragma unroll 1
      for (uint32_t layer = 0; layer < 2; layer++) {
        if (w == 10) {
          if (layer == 0) {
            const uint32_t lane = lane_id();
            uint32_t* fl = (uint32_t*)(scratch + OFF_F + (t * 8 + j) * 8) + (lane & 15);
            uint32_t v;
            asm volatile("ld.relaxed.gpu.global.b32 %0, [%1];" : "=r"(v) : "l"(fl) : "memory");
            mbar_wait(piece_full, 0);
            asm volatile("{\n.reg .pred e;\nelect.sync _|e, 0xffffffff;\n@e cp.async.bulk.global.shared::cta.bulk_group [%0], [%1], 2304;\n}\n"
                         "cp.async.bulk.commit_group;\ncp.async.bulk.wait_group 0;\nfence.proxy.async;"
                         :: "l"(scratch + OFF_R + j * 2304 + t * 144), "r"(sb + PIECE) : "memory");
            __syncwarp();
            if (lane < 16) asm volatile("st.release.gpu.global.b32 [%0], 1;" :: "l"((uint32_t*)(scratch + OFF_F + (lane * 8 + j) * 8) + t) : "memory");
            int n = 0;
            while (!__all_sync(~0u, v != 0u)) {
              __nanosleep(100);
              SPIN_GUARD(n);
              asm volatile("ld.relaxed.gpu.global.b32 %0, [%1];" : "=r"(v) : "l"(fl) : "memory");
            }
            asm volatile("st.relaxed.gpu.global.b32 [%0], 0;" :: "l"(fl) : "memory");
            mbar_wait(x_done, 0);
          } else {
            mbar_wait_sleep(park_free, 0);
          }
          bulk_load(sb + REM, scratch + OFF_R + j * 2304, 36864, rem_full, true);
        }
        mbar_wait_sleep(rem_full, layer);
#pragma unroll 1
        for (uint32_t b = 0; b < 5; b++) {
          const uint32_t blk = sb + REM + 27648 + b * 2048, k = (w - 10) * 32 + lane_id(), rr = k & 7;
          const uint32_t dst = blk + ((k >> 3) & 1) * 1024 + rr * 128 + (((k >> 4) ^ rr) << 4);
          uint32_t v[8];
          lds4(blk + k * 16, v); lds4(blk + 1024 + k * 16, v + 4);
          asm volatile("bar.sync 3, 64;" ::: "memory");
          sts4(dst, v); sts4(dst ^ 64, v + 4);
        }
        asm volatile("fence.proxy.async.shared::cta;" ::: "memory");
        mbar_arrive(remo_full);
        if (layer) { phase2_duties(0); mbar_wait_sleep(kv_free, 0); }
        if (t > 0) {
          const uint32_t lane = lane_id(), r = lane >> 2, q = lane & 3;
#pragma unroll 1
          for (uint32_t pc = 0; pc < 3; pc++) {
            uint4* hp = scr + OFF_H + ((layer * 8 + j) * 2 + (w - 10)) * 192 + pc * 64 + lane;
            uint32_t hl[8];
            int n = 0;
            hl[4] = 1u;
            while (true) {
              ldg4(hl, hp);
              if (pc < 2) ldg4(hl + 4, hp + 32);
              if (__all_sync(~0u, hl[0] != 0u && hl[4] != 0u)) break;
              __nanosleep(100);
              SPIN_GUARD(n);
            }
            const uint32_t dst = sb + KVS + (w - 10) * 10368 + r * 144 + q * 4;
            if (pc < 2) {
#pragma unroll
              for (int g = 0; g < 8; g++) sts1(dst + pc * 20736 + odd * 16 + g * 16, hl[g]);
              stg4(hp + 32, 0u, 0u, 0u, 0u);
            } else {
              sts1(dst + (odd ? 0 : 128), hl[0]); sts1(dst + 20736 + (odd ? 0 : 128), hl[1]);
            }
            stg4(hp, 0u, 0u, 0u, 0u);
          }
        }
        asm volatile("bar.arrive 1, 192;" ::: "memory");
        mbar_wait_sleep(xb_done, layer);
        if (w == 10 && layer == 1) {
          const uint32_t lane = lane_id();
          stg4(scr + OFF_S + (lane >> 3) * 96 + j * 8 + (lane & 7), 0u, 0u, 0u, 0u);
          stg4(scr + OFF_S + (4 + (lane >> 3)) * 96 + j * 8 + (lane & 7), 0u, 0u, 0u, 0u);
          if (lane < 8) stg4(scr + OFF_S + j * 96 + 64 + lane, 0u, 0u, 0u, 0u);
        }
#pragma unroll 1
        for (uint32_t i = 0; i < 8 && (w == 11 || layer == 1); i++) {
          zero_share(scr + OFF_X + ((w - 10) * 16 + layer * 8 + i) * SLAB, j, lane_id());
          __nanosleep(500);
        }
      }
      phase2_duties(1);
    }
  } else {
    asm volatile("setmaxnreg.inc.sync.aligned.u32 240;");
    const bool lead = lane_id() == 0;
    Ring rg{0, 0};
    uint32_t prev = 0;
    uint32_t X[144];
    float rs0, rs1;
    const bool lead2 = lane_id() < 2;
    uint32_t empty_at;
    asm volatile("mapa.shared::cluster.u32 %0, %1, %2;" : "=r"(empty_at) : "r"(empty0), "r"(lane_id() & 1));
    auto release = [&](uint32_t st) { if (lead2) asm volatile("mbarrier.arrive.shared::cluster.b64 _, [%0];" :: "r"(empty_at + st * 8) : "memory"); };
    auto load_kb = [&](int kb, const uint4* src, const char* lo, uint32_t hoff) {
#pragma unroll
      for (int k = 4 * kb; k < 4 * kb + 4; k++) {
        if (k % 9 == 4) { ldg2(X + 4 * k, lo + k * 512); ldg2(X + 4 * k + 2, lo + hoff + k * 512); }
        else ldg4(X + 4 * k, src + k * 32);
      }
    };
    auto check_kb = [&](bool skip, int kb, const uint4* src, const char* lo, uint32_t hoff) {
      int n = 0;
      while (true) {
        uint32_t m = umin2(umin2(X[16 * kb], X[16 * kb + 4]), umin2(X[16 * kb + 8], X[16 * kb + 12]));
        if (kb & 1) m = umin2(m, X[16 * kb + 4 * (kb >> 1) + 2]);
        if (__all_sync(~0u, m != 0u || skip)) break;
        SPIN_GUARD(n);
        load_kb(kb, src, lo, hoff);
      }
    };
#pragma unroll 1
    for (uint32_t hf = 0; hf < 4; hf++) {
      const uint32_t layer = hf >> 1;
      const bool ffn = hf & 1;
      const uint32_t tag = 1 - layer;
      uint4* const xbase = scr + OFF_X + (layer * 8 + w) * SLAB;
      float aA[32], aB[32];
      {
        const uint32_t lane = lane_id(), r = lane >> 2, q = lane & 3;
        const uint4* src = xbase + (ffn ? 32 * SLAB : 0) + lane;
        const char* lo = (const char*)src - (ffn ? lane * 8 : 0);
        const uint32_t hoff = ffn ? 256 : 8;
        const uint32_t xoff = (w & 1) * 8192 + (16 * (w >> 1) + (lane & 15)) * 128 + (((lane >> 4) ^ (lane & 7)) << 4);
        auto load_x = [&](uint32_t b, uint32_t* d) {
#pragma unroll
          for (int i = 0; i < 4; i++) ldsm4(xs + b * STAGE + (xoff ^ (32 * i)), d[4 * i], d[4 * i + 1], d[4 * i + 2], d[4 * i + 3]);
        };
        auto load_any = [&](int kb) { if (hf == 0) load_x(kb, X + 16 * kb); else load_kb(kb, src, lo, hoff); };
        float m0, m1, v0, v1;
        STAMP(ffn * 16 + 0);
        if (hf == 0) {
          float sum[2][4] = {}, sq0[4][4] = {}, sq1[4][4] = {};
          uint32_t p0, p1;
          mbar_wait(xbar0, 0);
          ldsm4(xs + xoff, p0, p1, X[0], X[1]);
          p0 = __byte_perm(__shfl_sync(~0u, p0, lane & 28), 0, 0x1010); p1 = __byte_perm(__shfl_sync(~0u, p1, lane & 28), 0, 0x1010);
#pragma unroll 3
          for (uint32_t b = 0; b < 9; b++) {
            uint32_t d[16];
            mbar_wait(xbar0 + 8 * b, 0);
            load_x(b, d);
#pragma unroll
            for (int i = 0; i < 16; i++) d[i] = sub_bf16x2(d[i], (i & 1) ? p1 : p0);
#pragma unroll
            for (int g = 0; g < 8; g++) {
              if (!(g & 1)) mma16(sum[(g >> 1) & 1], d[2 * g], d[2 * g + 1], d[2 * g + 2], d[2 * g + 3], 0x3f803f80u, 0x3f803f80u);
              mma8(sq0[g & 3], d[2 * g], d[2 * g + 1], d[2 * g]); mma8(sq1[g & 3], d[2 * g], d[2 * g + 1], d[2 * g + 1]);
            }
          }
          STAMP(1);
          GSTAMP(14);
#pragma unroll
          for (int kb = 0; kb < GD; kb++) load_x(kb, X + 16 * kb);
#pragma unroll
          for (int e = 0; e < 5; e++) {
            const uint32_t k = ((9 * j) >> 1) + e;
            uint32_t d[4];
            ldsm4(xs + (k >> 2) * STAGE + (xoff ^ (32 * (k & 3))), d[0], d[1], d[2], d[3]);
            stg4(xbase + k * 32 + lane, d[0], d[1], d[2], d[3]);
          }
          release((x_ring - empty0) / 8);
          auto tot = [](float (&c)[4][4], int e) { return (c[0][e] + c[1][e]) + (c[2][e] + c[3][e]); };
          const float a0 = (sum[0][0] + sum[1][0]) * (1.f / 576), a1 = (sum[0][2] + sum[1][2]) * (1.f / 576);
          const uint32_t dg = (lane & 28) + (r >> 1);
          v0 = fmaxf(fmaf(__shfl_sync(~0u, (r & 1) ? tot(sq0, 1) : tot(sq0, 0), dg), 1.f / 576, -a0 * a0), 0.f);
          v1 = fmaxf(fmaf(__shfl_sync(~0u, (r & 1) ? tot(sq1, 3) : tot(sq1, 2), dg), 1.f / 576, -a1 * a1), 0.f);
          m0 = bf_lo(p0) + a0; m1 = bf_lo(p1) + a1;
        } else {
          uint32_t s[3][4];
          const uint4* p = scr + OFF_S + ((ffn ? 16 : 0) + w) * 96 + q * 8 + r;
          const bool third = !ffn && q == 0;
          const uint32_t rdy = ffn ? tag : 1u;
          int n = 0;
          s[2][0] = rdy; s[2][1] = s[2][2] = s[2][3] = 0u;
          while (true) {
            ldg4(s[0], p); ldg4(s[1], p + 32);
            if (third) ldg4(s[2], p + 64);
            if (__all_sync(~0u, ((diff2(s[0][0], s[1][0], rdy) | diff2(s[1][0], s[2][0], rdy)) & 1u) == 0u)) break;
            SPIN_GUARD(n);
          }
          STAMP(ffn * 16 + 1);
          ZSTAMP(1 + ffn, 0);
          GSTAMP(14 + ffn);
#pragma unroll
          for (int kb = 0; kb < GD; kb++) load_kb(kb, src, lo, hoff);
          float t0 = 0.f, t1 = 0.f;
#pragma unroll
          for (int i = 0; i < 3; i++) { t0 += __uint_as_float(s[i][0]); t1 += __uint_as_float(s[i][2]); }
          m0 = quad_sum(t0) * (1.f / 576); m1 = quad_sum(t1) * (1.f / 576);
          const float cnt = ffn ? 72.f : 64.f, inv = ffn ? 1.f / 72 : 1.f / 64;
          v0 = 0.f; v1 = 0.f;
#pragma unroll
          for (int i = 0; i < 3; i++) {
            const float c = (i < 2 || third) ? cnt : 0.f;
            const float d0 = fmaf(__uint_as_float(s[i][0]), inv, -m0), d1 = fmaf(__uint_as_float(s[i][2]), inv, -m1);
            v0 += fmaf(d0 * d0, c, __uint_as_float(s[i][1])); v1 += fmaf(d1 * d1, c, __uint_as_float(s[i][3]));
          }
          v0 = quad_sum(v0) * (1.f / 576); v1 = quad_sum(v1) * (1.f / 576);
        }
        rs0 = rsqrtf(v0 + 1e-5f); rs1 = rsqrtf(v1 + 1e-5f);
        const uint32_t mean0 = pack_bf16(m0, m0), mean1 = pack_bf16(m1, m1);
#pragma unroll
        for (int kb = 0; kb < 9; kb++) {
          check_kb(hf == 0, kb, src, lo, hoff);
          if (kb + GD < 9) load_any(kb + GD);
          if (kb + GD == 8 && hf == 0 && lead) mbar_arrive(x_done);
#pragma unroll
          for (int i = 16 * kb; i < 16 * kb + 16; i++) X[i] = sub_bf16x2(X[i], (i & 1) ? mean1 : mean0);
          ZSTAMP(1 + ffn, 1 + 3 * kb);
          mbar_wait(full0 + rg.st * 8, rg.ph);
          ZSTAMP(1 + ffn, 2 + 3 * kb);
          const uint64_t desc = DESC_HI | ((sd + rg.st * STAGE) >> 4);
          wg_fence();
#pragma unroll
          for (int i = 0; i < 4; i++) wgmma_rs_n64(aA, X + 4 * (4 * kb + i), desc + i * 128, kb + i != 0);
          if (SPLITZ && kb == 8) { wg_commit(); wg_wait<1>(); wg_fence(); }
#pragma unroll
          for (int i = 0; i < 4; i++) wgmma_rs_n64(aB, X + 4 * (4 * kb + i), desc + 512 + i * 128, kb + i != 0);
          wg_commit();
          wg_wait<1>();
          ZSTAMP(1 + ffn, 3 + 3 * kb);
          if (kb > 0) release(prev);
          prev = rg.st; rg.next();
        }
        if (!SPLITZ) wg_wait<0>();
        ZSTAMP(1 + ffn, 28);
        ZSTAMP(4, 0);
        STAMP(ffn * 16 + 2);
      }
      if (!ffn) {
      const uint32_t lane = lane_id(), r = lane >> 2, q = lane & 3;
      const uint32_t kvrow = sb + KVS + (w & 1) * 10368 + (16 * (w >> 1)) * 144;
      uint32_t Q[18], Km[3][8], Ke[3][4];
      const bool edge = (t == 0 && w < 2);
      const uint32_t row0 = edge ? sb + KVS + 8 * 144 : kvrow + (lane & 7) * 144, row1 = kvrow + (8 + (lane & 7)) * 144;
      {
        const uint32_t dst = kvrow + (8 + r) * 144 + q * 4 + odd * 16, dstr = dst + (odd ? -16 : 128);
        const bool edge_out = w >= 6 && t < 15;
        uint4* const hp = scr + TILE + OFF_H + ((layer * 8 + j) * 2 + (w & 1)) * 192 + lane;
        auto put_kv = [&](float (&a)[32], int part) {
          pin(a);
          uint32_t hl[8];
#pragma unroll
          for (int g = 0; g < 8; g++) {
            hl[g] = pack_bf16(a[4 * g + 2] * rs1, a[4 * g + 3] * rs1);
            sts1(dst + part * 20736 + g * 16, pack_bf16(a[4 * g] * rs0, a[4 * g + 1] * rs0)); sts1(dst + part * 20736 + 8 * 144 + g * 16, hl[g]);
          }
          if (edge_out) { stg4(hp + part * 64, nz(hl[0]), hl[1], hl[2], hl[3]); stg4(hp + part * 64 + 32, nz(hl[4]), hl[5], hl[6], hl[7]); }
        };
        put_kv(aA, 0);
        wg_wait<0>();
        release(prev);
        float aR[12];
        mbar_wait(rem_full, layer);
        const uint64_t dr = DESC_REM | ((sd + REM) >> 4);
        wg_fence();
#pragma unroll
        for (int s = 0; s < 36; s++) {
          wgmma_rs_n24(aR, X + 4 * s, dr + s * 16, s != 0);
          if (s == 4) put_kv(aB, 1);
        }
        wg_commit();
#pragma unroll
        for (int kb = 0; kb < 9; kb++) {
          if (kb == HOFF1 && w < 4) asm volatile("bar.sync 4, 256;" ::: "memory");
          if (kb == 8 && HOFF1 < 9 && w >= 4) asm volatile("bar.arrive 4, 256;" ::: "memory");
          if (!(kb & 1)) mbar_wait(full0 + rg.st * 8, rg.ph);
          const uint64_t desc = DESC_HI | ((sd + rg.st * STAGE + (kb & 1) * 8192) >> 4);
          wg_fence();
#pragma unroll
          for (int i = 0; i < 4; i++) wgmma_rs_n64(aB, X + 4 * (4 * kb + i), desc + i * 128, kb + i != 0);
          wg_commit();
          wg_wait<1>();
          if (kb > 0 && !(kb & 1)) release(prev);
          if ((kb & 1) || kb == 8) { prev = rg.st; rg.next(); }
          if (kb == 0) {
            pin(aR);
            const uint32_t k1 = pack_bf16(aR[2] * rs1, aR[3] * rs1), v1 = pack_bf16(aR[6] * rs1, aR[7] * rs1);
            if (edge_out) stg4(hp + 128, nz(k1), v1, 0u, 0u);
            sts1(dstr, pack_bf16(aR[0] * rs0, aR[1] * rs0)); sts1(dstr + 8 * 144, k1);
            sts1(dstr + 20736, pack_bf16(aR[4] * rs0, aR[5] * rs0)); sts1(dstr + 20736 + 8 * 144, v1);
            Q[16] = pack_bf16(aR[8], aR[9]); Q[17] = pack_bf16(aR[10], aR[11]);
            if (w < 4) asm volatile("bar.arrive 2, 256;" ::: "memory");
          }
          if (kb == KLD - 2) mbar_wait(remo_full, layer);
          if (kb == KLD) {
            if (w < 4) asm volatile("bar.sync 1, 192;" ::: "memory");
            else asm volatile("bar.sync 2, 256;" ::: "memory");
#pragma unroll
            for (int nt = 0; nt < 3; nt++) {
              const uint32_t ra = (nt == 0 ? row0 : row1 + (nt - 1) * 8 * 144);
              ldsm4(ra + odd * 16 + (lane >> 3) * 16, Km[nt][0], Km[nt][1], Km[nt][2], Km[nt][3]);
              ldsm4(ra + odd * 16 + 64 + (lane >> 3) * 16, Km[nt][4], Km[nt][5], Km[nt][6], Km[nt][7]);
              ldsm4(ra + (odd ? 0 : 32) + (lane >> 3) * 32, Ke[nt][0], Ke[nt][1], Ke[nt][2], Ke[nt][3]);
            }
            const uint32_t ge = (2u << q) - 1, le = 0xfu << q, on = edge ? 0u : ~0u;
            const uint32_t bits = odd ? 0xfu | ((le & 0xfu) << 4) | (ge << 8) : ge | 0xf0u | (le << 8);
#pragma unroll
            for (int h = 0; h < 4; h++) {
              const uint32_t ma = bitmask(bits, h), mb = bitmask(bits, 4 + h), mc = bitmask(bits, 8 + h);
              Km[0][2 * h] &= ma & on; Km[0][2 * h + 1] &= mb & on; Ke[0][h] &= mc & on;
#pragma unroll
              for (int nt = 1; nt < 3; nt++) { Km[nt][2 * h] &= ma; Km[nt][2 * h + 1] &= mb; Ke[nt][h] &= mc; }
            }
          }
        }
        wg_wait<0>();
        release(prev);
        pin(aB);
        STAMP(3);
#pragma unroll
        for (int i = 0; i < 16; i++) Q[i] = pack_bf16(aB[2 * i], aB[2 * i + 1]);
      }
      {
        uint32_t V01[12][2], V2[12];
        const uint32_t rv = ((lane & 8) ? row1 : row0) + 20736, rw = row1 + 8 * 144 + 20736;
#pragma unroll
        for (int i = 0; i < 4; i++) ldsm4t(rv + odd * 16 + i * 32 + (lane >> 4) * 16, V01[2 * i][0], V01[2 * i][1], V01[2 * i + 1][0], V01[2 * i + 1][1]);
#pragma unroll
        for (int i = 0; i < 2; i++) ldsm4t(rv + (odd ? 0 : 32) + i * 64 + (lane >> 4) * 32, V01[8 + 2 * i][0], V01[8 + 2 * i][1], V01[9 + 2 * i][0], V01[9 + 2 * i][1]);
        ldsm4t(rw + odd * 16 + (lane >> 3) * 16, V2[0], V2[1], V2[2], V2[3]);
        ldsm4t(rw + odd * 16 + 64 + (lane >> 3) * 16, V2[4], V2[5], V2[6], V2[7]);
        ldsm4t(rw + (odd ? 0 : 32) + (lane >> 3) * 32, V2[8], V2[9], V2[10], V2[11]);
        const bool up0 = 2 * q > r, up1 = 2 * q + 1 > r;
        const uint32_t upm = (up0 ? 0xffffu : 0u) | (up1 ? 0xffff0000u : 0u);
        const float c0 = 0.23570226039551584f * 1.4426950408889634f * rs0, c1 = 0.23570226039551584f * 1.4426950408889634f * rs1;
        const float masked = edge ? -1e9f * 1.4426950408889634f * rcp(c0) : 0.f;
        uint32_t Om[16], Oe[8];
#pragma unroll
        for (int h = 0; h < 4; h++) {
          const uint32_t e0 = odd ? Q[(4 * h + 16) % 18] : Q[4 * h + 4], e1 = odd ? Q[(4 * h + 17) % 18] : Q[4 * h + 5];
          float S[3][4];
#pragma unroll
          for (int nt = 0; nt < 3; nt++) {
            mma16c(S[nt], Q + 4 * h, Km[nt][2 * h], Km[nt][2 * h + 1], nt == 0 ? masked : 0.f);
            mma8(S[nt], e0, e1, Ke[nt][h]);
          }
          const float s00 = up0 ? S[0][0] : S[1][0], s01 = up1 ? S[0][1] : S[1][1];
          const float s10 = up0 ? S[1][2] : S[2][2], s11 = up1 ? S[1][3] : S[2][3];
          const float m0 = quad_max(fmaxf(s00, s01)) * c0, m1 = quad_max(fmaxf(s10, s11)) * c1;
          const float p00 = ex2(fmaf(s00, c0, -m0)), p01 = ex2(fmaf(s01, c0, -m0)), p10 = ex2(fmaf(s10, c1, -m1)), p11 = ex2(fmaf(s11, c1, -m1));
          const float i0 = rcp(quad_sum(p00 + p01)), i1 = rcp(quad_sum(p10 + p11));
          const uint32_t p0 = pack_bf16(p00 * i0, p01 * i0), p1 = pack_bf16(p10 * i1, p11 * i1);
          const uint32_t pf[4] = {p0 & upm, 0u, p0 & ~upm, p1 & upm};
#pragma unroll
          for (int gi = 0; gi < 3; gi++) {
            const int g = gi < 2 ? 2 * h + gi : 8 + h;
            float o[4];
            mma16c(o, pf, V01[g][0], V01[g][1], 0.f);
            mma8(o, 0u, p1 & ~upm, V2[g]);
            uint32_t* d = gi < 2 ? Om + 2 * g : Oe + 2 * h;
            d[0] = pack_bf16(o[0], o[1]); d[1] = pack_bf16(o[2], o[3]);
          }
        }
#pragma unroll
        for (int h = 0; h < 4; h++)
#pragma unroll
          for (int e = 0; e < 2; e++) {
            if (h > 0 && !odd && q < h) Om[4 * h + e] = Oe[2 * h - 2 + e];
            if (h < 3 && odd && q > h) Om[4 * h + 2 + e] = Oe[2 * h + 2 + e];
          }
        STAMP(4);
        if (j >= PRI && lane == 0) asm volatile("st.relaxed.gpu.global.b32 [%0], %1;" :: "l"(scr + OFF_S + (8 + w) * 96 + j * 8), "r"(tag) : "memory");
        put72(xbase + 16 * SLAB, j, lane, Om, odd ? Oe[0] : Oe[6], odd ? Oe[1] : Oe[7]);
      }
      if (j < PRI && lane == 0) asm volatile("st.relaxed.gpu.global.b32 [%0], %1;" :: "l"(scr + OFF_S + (8 + w) * 96 + j * 8), "r"(tag) : "memory");
      {
        uint32_t res[18];
        const uint4* p = xbase + ((9 * j + 1) >> 1) * 32 + lane;
#pragma unroll
        for (int i = 0; i < 4; i++) ldg4(res + 4 * i, p + i * 32);
        ldg2(res + 16, odd ? (const char*)(p - 32) + 8 : (const char*)(p + 4 * 32));
        const uint4* src = xbase + 16 * SLAB + lane;
        {
          const uint4* fp = scr + OFF_S + (8 + w) * 96 + (lane & 7) * 8;
          int n = 0;
          STAMP(8);
          while (true) {
            uint32_t f;
            asm volatile("ld.relaxed.gpu.global.b32 %0, [%1];" : "=r"(f) : "l"(fp) : "memory");
            if (__all_sync(~0u, f == tag)) break;
            SPIN_GUARD(n);
          }
          STAMP(9);
        }
        if (HOFF3 < 9 && w < 4) asm volatile("bar.sync 6, 256;" ::: "memory");
#pragma unroll
        for (int kb = 0; kb < GO; kb++) load_kb(kb, src, (const char*)src - lane * 8, 256);
        float acc[36];
#pragma unroll
        for (int i = 0; i < 18; i++) { acc[2 * i] = bf_lo(res[i]); acc[2 * i + 1] = bf_hi(res[i]); }
#pragma unroll
        for (int kb = 0; kb < 9; kb++) {
          check_kb(false, kb, src, (const char*)src - lane * 8, 256);
          if (kb + GO < 9) load_kb(kb + GO, src, (const char*)src - lane * 8, 256);
          if (kb == HOFF3 && w >= 4) asm volatile("bar.arrive 6, 256;" ::: "memory");
          if (!(kb & 1)) mbar_wait(full0 + rg.st * 8, rg.ph);
          const uint32_t base = sd + rg.st * STAGE + (kb & 1) * 8192;
          const uint64_t d0 = DESC_HI | ((base >> 4) + (((sd + REM + 27648 + (kb >> 1) * 2048 + (kb & 1) * 64 - base) >> 4) << 16));
          wg_fence();
#pragma unroll
          for (int i = 0; i < 4; i++) wgmma_rs_n72(acc, X + 4 * (4 * kb + i), d0 - (uint64_t)(i * ((127u << 16) - 128u)), 1);
          wg_commit();
          wg_wait<1>();
          if (kb > 0 && !(kb & 1)) release(prev);
          if ((kb & 1) || kb == 8) { prev = rg.st; rg.next(); }
        }
        wg_wait<0>();
        release(prev);
        pin(acc);
        STAMP(10);
#pragma unroll
        for (int i = 0; i < 18; i++) res[i] = pack_bf16(acc[2 * i], acc[2 * i + 1]);
        if (j < PRI) put72(xbase + 32 * SLAB, j, lane, res, res[16], res[17]);
        publish_stats<9>(scr + OFF_S + (16 + w) * 96 + j * 8, acc, tag, lane);
        if (j >= PRI) put72(xbase + 32 * SLAB, j, lane, res, res[16], res[17]);
      }
      continue;
      }
      const uint32_t hp = sb + PARK + w * 512 + lane_id() * 16;
      auto pack8 = [&](float (&a)[32], int p, uint32_t* o) {
#pragma unroll
        for (int e = 0; e < 8; e++) asm volatile("" : "+f"(a[8 * p + e]) :: "memory");
#pragma unroll
        for (int e = 0; e < 4; e++) o[e] = pack_bf16(a[8 * p + 2 * e], a[8 * p + 2 * e + 1]);
      };
      const float ka0 = 0.7978845608028654f * rs0, kb0 = 0.044715f * ka0 * rs0 * rs0, ku0 = 0.5f * rs0 * rs0;
      const float ka1 = 0.7978845608028654f * rs1, kb1 = 0.044715f * ka1 * rs1 * rs1, ku1 = 0.5f * rs1 * rs1;
      auto packu8 = [&](int p, uint32_t* o) {
#pragma unroll
        for (int e = 0; e < 8; e++) asm volatile("" : "+f"(aA[8 * p + e]) :: "memory");
#pragma unroll
        for (int e = 0; e < 4; e++) o[e] = pack_bf16(aA[8 * p + 2 * e] * ((e & 1) ? ku1 : ku0), aA[8 * p + 2 * e + 1] * ((e & 1) ? ku1 : ku0));
      };
      auto geglu8 = [&](int p, uint32_t* u) {
#pragma unroll
        for (int e = 0; e < 8; e++) asm volatile("" : "+f"(aB[8 * p + e]) :: "memory");
        float h[8];
#pragma unroll
        for (int e = 0; e < 8; e++) {
          const float g = aB[8 * p + e];
          h[e] = fmaf(g, tanh_ap(g * fmaf(g * g, (e & 2) ? kb1 : kb0, (e & 2) ? ka1 : ka0)), g);
        }
#pragma unroll
        for (int e = 0; e < 4; e++) u[e] = mul_bf16x2(pack_bf16(h[2 * e], h[2 * e + 1]), u[e]);
      };
      auto box = [&](int b, auto&& filler) {
        const int kb = b < 9 ? b : b - 9;
        if (!(b & 1)) { if ((TRAPB >> (b >> 1)) & 1) mbar_wait_trap(full0 + rg.st * 8, rg.ph); else mbar_wait(full0 + rg.st * 8, rg.ph); }
        const uint64_t desc = DESC_HI | ((sd + rg.st * STAGE + (b & 1) * 8192) >> 4);
        wg_fence();
#pragma unroll
        for (int i = 0; i < 4; i++) {
          if (b < 9) wgmma_rs_n64(aA, X + 4 * (4 * kb + i), desc + i * 128, kb + i != 0);
          else wgmma_rs_n64(aB, X + 4 * (4 * kb + i), desc + i * 128, kb + i != 0);
          if (i == FPOS) filler();
        }
        wg_commit();
        if (b & 1) { prev = rg.st; rg.next(); } else { wg_wait<1>(); release(prev); }
      };
      auto nop = [] {};
      auto step = [&](int st, auto&& filler) { box(2 * st, nop); box(2 * st + 1, filler); };
#pragma unroll
      for (int p = 0; p < 4; p++) { uint32_t o[4]; packu8(p, o); sts4(hp + p * 4096, o); }
      box(0, nop);
      if (lead) mbar_arrive(xb_done);
#pragma unroll 1
      for (int c = 1;; c++) {
        const uint32_t hc = hp + c * 4 * 4096;
#pragma unroll
        for (int b = 1; b < 18; b++) box(b, [&] {
          if ((b & 1) && b < 8) { uint32_t o[4]; const uint32_t a = hc - (4 - (b >> 1)) * 4096; lds4(a, o); geglu8(b >> 1, o); sts4(a, o); }
          if ((b & 1) && b > 10) { uint32_t o[4]; packu8((b - 11) >> 1, o); if (c < 8) sts4(hc + ((b - 11) >> 1) * 4096, o); } });
        ZSTAMP(4, c);
        if (c == 8) break;
        box(0, nop);
      }
      wg_wait<0>();
      STAMP(21);
      GSTAMP(19);
      auto unpark = [&](int kb) {
#pragma unroll
        for (int s = 4 * kb; s < 4 * kb + 4; s++) lds4(hp + s * 4096, X + 4 * s);
      };
      unpark(0);
      uint32_t U[16];
#pragma unroll
      for (int p = 0; p < 4; p++) packu8(p, U + 4 * p);
#pragma unroll
      for (int b = 0; b < 8; b++) box(b, [&] {
        if (b < 7) unpark(b + 1);
        if (b & 1) {
          geglu8(b >> 1, U + 2 * (b - 1));
          if (rg.ph > 1) sts4(hp, U + 2 * (b - 1));
#pragma unroll
          for (int i = 0; i < 4; i++) X[128 + 2 * (b - 1) + i] = U[2 * (b - 1) + i];
        } });
      STAMP(24);
      if (layer == 0 && lead) mbar_arrive(park_free);
      const uint32_t lane2 = lane_id();
      uint4* const pw = scr + OFF_P + (j * 8 + w) * SLAB + lane2;
      const uint4* const pr = scr + OFF_P + w * SLAB + 4 * j * 32 + lane2;
      auto put_part = [&](float (&a)[32], int p, uint32_t chunk) {
        uint32_t o[4];
        pack8(a, p, o);
        stg4(pw + (chunk * 4 + p) * 32, (o[0] & ~1u) | tag, o[1], o[2], o[3]);
      };
      uint4* const xb = xbase + 32 * SLAB + 4 * j * 32;
      auto slot = [&](int p) { return sb + w * 2048 + (p < 3 ? PARK + p * 16384 : KVS + (p - 3) * 16384); };
      auto fetch = [&](int p) {
        bulk_load(slot(p), p ? scr + OFF_P + (((j - p) & 7) * 8 + w) * SLAB + 4 * j * 32 : xb, 2048, p ? pbar0 + w * 8 : res_full, true);
      };
#pragma unroll 1
      for (int sp = 0;; sp++) {
        const uint32_t ca = sp == 0 ? 8 : ((j + 2 * sp) & 7), cb = (j + 2 * sp + 1) & 7;
        if (C8 == 1 && sp == 1 && lead) mbar_arrive(c8_go);
#pragma unroll
        for (int st = 4; st < 9; st++) step(st, [&] {
          if (st == 5 || st == 6) { put_part(aA, 2 * (st - 5), ca); put_part(aA, 2 * (st - 5) + 1, ca); }
          if (st == 8 && sp > 0) { if (sp == 3) mbar_wait(c8_done, layer); fetch(2 * sp - 2); } });
        STAMP(25 + sp);
        if (sp == 3) break;
        if (C8 == 0 && sp == 0 && lead) mbar_arrive(c8_go);
#pragma unroll
        for (int st = 0; st < 4; st++) step(st, [&] {
          if (st < 2) { put_part(aB, 2 * st, cb); put_part(aB, 2 * st + 1, cb); }
          if (st == 3 && sp > 0) fetch(2 * sp - 1); });
      }
      auto load_p = [&](int p, uint32_t* d) {
#pragma unroll
        for (int i = 0; i < 4; i++) ldg4(d + 4 * i, pr + ((j - p) & 7) * 8 * SLAB + i * 32);
      };
#pragma unroll
      for (int b = 0; b < 9; b++) {
        if (b == HOFF2 && w < 4) asm volatile("bar.sync 5, 256;" ::: "memory");
        box(b, [&] {
          if (b == 1) {
#pragma unroll
            for (int p = 0; p < 4; p++) put_part(aB, p, (j + 7) & 7);
          }
          if (b == 3) { load_p(5, X); load_p(6, X + 16); }
          if (b == 7 && EXP != 1) load_p(7, X + 32); });
        if (b == 7 && HOFF2 < 9 && w >= 4) asm volatile("bar.arrive 5, 256;" ::: "memory");
      }
      mbar_wait(res_full, layer);
      mbar_wait(pbar0 + w * 8, layer);
#pragma unroll
      for (int p = 1; p < 5; p++)
#pragma unroll
        for (int i = 0; i < 4; i++) lds4(slot(p) + lane2 * 16 + i * 512, X + 48 + 16 * p + 4 * i);
#pragma unroll
      for (int i = 0; i < 4; i++) {
        const bool split = j == 2 * i + 1;
        const uint32_t a = slot(0) + i * 512 + (split ? lane2 * 8 : lane2 * 16);
        lds2(a, X + 48 + 4 * i); lds2(a + (split ? 256 : 8), X + 50 + 4 * i);
      }
      wg_wait<0>();
      release(rg.st); rg.next();
      pin(aA);
      STAMP(22);
      GSTAMP(20);
      {
        const uint32_t lane = lane2, r = lane >> 2, q = lane & 3;
        const uint32_t eye = r == 2 * q ? 0x3f80u : r == 2 * q + 1 ? 0x3f800000u : 0u;
        auto bad = [&](const uint32_t* d) { return diff2(d[0], d[4], tag) | diff2(d[8], d[12], tag); };
        auto add = [&](const uint32_t* d) {
#pragma unroll
          for (int g = 0; g < 8; g++) mma8(aA + 4 * g, d[2 * g], d[2 * g + 1], eye);
        };
        int n = 0;
        while (!__all_sync(~0u, ((or3(bad(X), bad(X + 16), bad(X + 64)) | or3(bad(X + 80), bad(X + 96), bad(X + 112))) & 1u) == 0u)) {
          SPIN_GUARD(n);
          load_p(5, X); load_p(6, X + 16);
#pragma unroll
          for (int p = 1; p < 5; p++) load_p(p, X + 48 + 16 * p);
        }
        add(X); add(X + 16);
#pragma unroll
        for (int p = 4; p >= 0; p--) add(X + 48 + 16 * ((p + 1) % 5));
        STAMP(11);
        if (EXP != 1) while (!__all_sync(~0u, (bad(X + 32) & 1u) == 0u)) { SPIN_GUARD(n); load_p(7, X + 32); }
        add(X + 32);
        STAMP(12);
        uint32_t res[16];
#pragma unroll
        for (int i = 0; i < 16; i++) res[i] = pack_bf16(aA[2 * i], aA[2 * i + 1]);
        if (layer == 0) {
          uint4* p = xbase + 8 * SLAB + 4 * j * 32 + lane;
          auto put = [&] {
#pragma unroll
            for (int i = 0; i < 4; i++) stg4(p + i * 32, nz(res[4 * i]), res[4 * i + 1], nz(res[4 * i + 2]), res[4 * i + 3]);
          };
          if (j < PRI) put();
          publish_stats<8>(scr + OFF_S + w * 96 + j * 8, aA, 1u, lane);
          if (j >= PRI) put();
          if (lane == 0) mbar_arrive(kv_free);
        } else {
          const uint32_t tb = slot(0);
          __syncwarp();
#pragma unroll
          for (int i = 0; i < 4; i++) {
            const uint32_t row = (lane2 & 7) + (lane2 & 8), g = 2 * i + (lane2 >> 4);
            asm volatile("stmatrix.sync.aligned.m8n8.x4.shared.b16 [%0], {%1,%2,%3,%4};"
                         :: "r"(tb + row * 128 + ((g ^ (row & 7)) << 4)), "r"(res[4 * i]), "r"(res[4 * i + 1]), "r"(res[4 * i + 2]), "r"(res[4 * i + 3]) : "memory");
          }
          __syncwarp();
#pragma unroll
          for (int i = 0; i < 4; i++) {
            const uint32_t row = 4 * i + (lane2 >> 3), g = lane2 & 7;
            uint32_t v[4];
            lds4(tb + row * 128 + ((g ^ (row & 7)) << 4), v);
            *(uint4*)(out + (128 * t + 32 * (w >> 1) + 2 * row + (w & 1)) * 576 + 64 * j + 8 * g) = make_uint4(v[0], v[1], v[2], v[3]);
          }
        }
      }
      STAMP(23);
    }
  }
}

typedef CUresult (*EncodeFn)(CUtensorMap*, CUtensorMapDataType, cuuint32_t, void*, const cuuint64_t*, const cuuint64_t*,
                             const cuuint32_t*, const cuuint32_t*, CUtensorMapInterleave, CUtensorMapSwizzle,
                             CUtensorMapL2promotion, CUtensorMapFloatOOBfill);

CUtensorMap make_map(EncodeFn f, const void* p, uint64_t cols, uint64_t rows, bool rem = false) {
  CUtensorMap m;
  cuuint64_t dims[2] = {cols, rows};
  cuuint64_t str[1] = {cols * 2};
  cuuint32_t box[2] = {rem ? 8u : 64u, rem ? 144u : 64u};
  cuuint32_t es[2] = {1, 1};
  f(&m, CU_TENSOR_MAP_DATA_TYPE_BFLOAT16, 2, const_cast<void*>(p), dims, str, box, es, CU_TENSOR_MAP_INTERLEAVE_NONE,
    rem ? CU_TENSOR_MAP_SWIZZLE_NONE : CU_TENSOR_MAP_SWIZZLE_128B, CU_TENSOR_MAP_L2_PROMOTION_NONE, CU_TENSOR_MAP_FLOAT_OOB_FILL_NONE);
  return m;
}

}

extern "C" void kernel_launch(void* const* d_in, const int* in_sizes, int n_in, void* d_out, int out_size) {
  void* fn = nullptr;
  cudaDriverEntryPointQueryResult qr;
  cudaGetDriverEntryPoint("cuTensorMapEncodeTiled", &fn, cudaEnableDefault, &qr);
  EncodeFn enc = (EncodeFn)fn;
  Maps maps;
  maps.m[0] = make_map(enc, d_in[1], 1728, 576); maps.m[1] = make_map(enc, d_in[2], 576, 576);
  maps.m[2] = make_map(enc, d_in[4], 4608, 576); maps.m[3] = make_map(enc, d_in[5], 4608, 576); maps.m[4] = make_map(enc, d_in[6], 576, 4608);
  maps.m[5] = make_map(enc, d_in[1], 1728, 576, true); maps.m[6] = make_map(enc, d_in[2], 576, 576, true);
  {
    cuuint64_t dims[3] = {576, 1024, 2}, str[2] = {2304, 1152};
    cuuint32_t box[3] = {64, 64, 2}, es[3] = {1, 1, 1};
    enc(&maps.m[7], CU_TENSOR_MAP_DATA_TYPE_BFLOAT16, 3, d_in[0], dims, str, box, es, CU_TENSOR_MAP_INTERLEAVE_NONE,
        CU_TENSOR_MAP_SWIZZLE_128B, CU_TENSOR_MAP_L2_PROMOTION_NONE, CU_TENSOR_MAP_FLOAT_OOB_FILL_NONE);
  }
  void* scr = nullptr;
  cudaGetSymbolAddress(&scr, g_scratch);
  cudaFuncSetAttribute(mega_kernel, cudaFuncAttributeMaxDynamicSharedMemorySize, SMEM_BYTES);
  cudaLaunchConfig_t cfg = {};
  cfg.gridDim = dim3(128); cfg.blockDim = dim3(384); cfg.dynamicSmemBytes = SMEM_BYTES; cfg.stream = cudaStreamPerThread;
  cudaLaunchAttribute at[1];
  at[0].id = cudaLaunchAttributeClusterDimension; at[0].val.clusterDim.x = 2; at[0].val.clusterDim.y = 1; at[0].val.clusterDim.z = 1;
  cfg.attrs = at; cfg.numAttrs = 1;
  int dev = 0, sms = 0, clusters = 0;
  cudaGetDevice(&dev);
  cudaDeviceGetAttribute(&sms, cudaDevAttrMultiProcessorCount, dev);
  cudaOccupancyMaxActiveClusters(&clusters, mega_kernel, &cfg);
  if (sms == 132 && clusters == 66) cfg.gridDim = dim3(132);
  cudaLaunchKernelEx(&cfg, mega_kernel, maps, (uint4*)scr, (__nv_bfloat16*)d_out);
}
```

```cpp
#include <cuda_runtime.h>
#include <cuda.h>
#include <cuda_bf16.h>
#include <stdint.h>

#define TRACE 0
#define GUARD 0
#define TRAPB 1
#define HOFF1 99
#define HOFF2 99
#define KLD 8
#define ZT 0
#define SLEEP 500
#define SPLITZ 1
#define C8 1
#define HOFF3 99
#define GO 3
#define EXP 0
#define FPOS 2

namespace {

constexpr int NST = 6;
constexpr int STAGE = 16384;
constexpr int PARK = NST * STAGE;
constexpr int REM = PARK + 49152;
constexpr int KVS = REM + 40960;
constexpr int PIECE = PARK + 7 * STAGE;
constexpr int HSTG = KVS + 16384;
constexpr int BARS = KVS + 41472;
constexpr int TRC = BARS + 512;
constexpr int SMEM_BYTES = TRC + (TRACE ? 512 : 0);
static_assert(NST == 6, "the producer addresses empty barriers as full + 48");
static_assert(BARS >= PARK + 131072, "barriers overlap park");
static_assert(SMEM_BYTES <= 232448, "smem");

constexpr int SLAB = 36 * 32;
constexpr int SPIN_MAX = 1 << 17;
constexpr uint32_t PRI = 3;
constexpr int GD = 3;
constexpr int OFF_S = 0;
constexpr int OFF_H = OFF_S + 3 * 8 * 96;
constexpr int OFF_X = OFF_H + 2 * 8 * 384;
constexpr int OFF_P = OFF_X + 6 * 8 * SLAB;
constexpr int TILE = OFF_P + 8 * 8 * SLAB;
constexpr int OFF_R = 16 * TILE;
constexpr int OFF_F = OFF_R + 8 * 2304;
constexpr int SCRATCH = OFF_F + 128 * 8;

}

__device__ uint4 g_scratch[SCRATCH];

namespace {

constexpr uint64_t DESC_HI = 0x4000004000000000ull;
constexpr uint64_t DESC_REM = (576ull << 32) | (8u << 16);
__device__ __forceinline__ void wgmma_rs_n64(float (&d)[32], const uint32_t* a, uint64_t desc, int scale_d) {
  asm volatile("{\n.reg .pred p;\nsetp.ne.b32 p, %37, 0;\n"
    "wgmma.mma_async.sync.aligned.m64n64k16.f32.bf16.bf16 "
    "{%0, %1, %2, %3, %4, %5, %6, %7, %8, %9, %10, %11, %12, %13, %14, %15, %16, %17, %18, %19, %20, %21, %22, %23, %24, %25, %26, %27, %28, %29, %30, %31}, "
    "{%32, %33, %34, %35}, %36, p, 1, 1, 1;\n}\n"
    : "+f"(d[0]), "+f"(d[1]), "+f"(d[2]), "+f"(d[3]), "+f"(d[4]), "+f"(d[5]), "+f"(d[6]), "+f"(d[7]), "+f"(d[8]), "+f"(d[9]), "+f"(d[10]), "+f"(d[11]), "+f"(d[12]), "+f"(d[13]), "+f"(d[14]), "+f"(d[15]), "+f"(d[16]), "+f"(d[17]), "+f"(d[18]), "+f"(d[19]), "+f"(d[20]), "+f"(d[21]), "+f"(d[22]), "+f"(d[23]), "+f"(d[24]), "+f"(d[25]), "+f"(d[26]), "+f"(d[27]), "+f"(d[28]), "+f"(d[29]), "+f"(d[30]), "+f"(d[31])
    : "r"(a[0]), "r"(a[1]), "r"(a[2]), "r"(a[3]), "l"(desc), "r"(scale_d));
}
__device__ __forceinline__ void wgmma_rs_n72(float (&d)[36], const uint32_t* a, uint64_t desc, int scale_d) {
  asm volatile("{\n.reg .pred p;\nsetp.ne.b32 p, %41, 0;\n"
    "wgmma.mma_async.sync.aligned.m64n72k16.f32.bf16.bf16 "
    "{%0, %1, %2, %3, %4, %5, %6, %7, %8, %9, %10, %11, %12, %13, %14, %15, %16, %17, %18, %19, %20, %21, %22, %23, %24, %25, %26, %27, %28, %29, %30, %31, %32, %33, %34, %35}, "
    "{%36, %37, %38, %39}, %40, p, 1, 1, 1;\n}\n"
    : "+f"(d[0]), "+f"(d[1]), "+f"(d[2]), "+f"(d[3]), "+f"(d[4]), "+f"(d[5]), "+f"(d[6]), "+f"(d[7]), "+f"(d[8]), "+f"(d[9]), "+f"(d[10]), "+f"(d[11]), "+f"(d[12]), "+f"(d[13]), "+f"(d[14]), "+f"(d[15]), "+f"(d[16]), "+f"(d[17]), "+f"(d[18]), "+f"(d[19]), "+f"(d[20]), "+f"(d[21]), "+f"(d[22]), "+f"(d[23]), "+f"(d[24]), "+f"(d[25]), "+f"(d[26]), "+f"(d[27]), "+f"(d[28]), "+f"(d[29]), "+f"(d[30]), "+f"(d[31]), "+f"(d[32]), "+f"(d[33]), "+f"(d[34]), "+f"(d[35])
    : "r"(a[0]), "r"(a[1]), "r"(a[2]), "r"(a[3]), "l"(desc), "r"(scale_d));
}
__device__ __forceinline__ void wgmma_rs_n24(float (&d)[12], const uint32_t* a, uint64_t desc, int scale_d) {
  asm volatile("{\n.reg .pred p;\nsetp.ne.b32 p, %17, 0;\n"
    "wgmma.mma_async.sync.aligned.m64n24k16.f32.bf16.bf16 "
    "{%0, %1, %2, %3, %4, %5, %6, %7, %8, %9, %10, %11}, "
    "{%12, %13, %14, %15}, %16, p, 1, 1, 1;\n}\n"
    : "+f"(d[0]), "+f"(d[1]), "+f"(d[2]), "+f"(d[3]), "+f"(d[4]), "+f"(d[5]), "+f"(d[6]), "+f"(d[7]), "+f"(d[8]), "+f"(d[9]), "+f"(d[10]), "+f"(d[11])
    : "r"(a[0]), "r"(a[1]), "r"(a[2]), "r"(a[3]), "l"(desc), "r"(scale_d));
}

__device__ __forceinline__ void mbar_init(uint32_t a, uint32_t c) { asm volatile("mbarrier.init.shared::cta.b64 [%0], %1;" :: "r"(a), "r"(c)); }
__device__ __forceinline__ void mbar_arrive(uint32_t a) { asm volatile("mbarrier.arrive.shared::cta.b64 _, [%0];" :: "r"(a) : "memory"); }
__device__ __forceinline__ void mbar_wait_trap(uint32_t a, uint32_t ph) {
  asm volatile("{\n.reg .pred p;\n.reg .u32 n;\nmov.u32 n, 0;\n"
               "W: mbarrier.try_wait.parity.shared::cta.b64 p, [%0], %1;\n@p bra D;\n"
               "add.u32 n, n, 1;\nsetp.lt.u32 p, n, 4194304;\n@p bra W;\ntrap;\nD:\n}" :: "r"(a), "r"(ph) : "memory");
}
__device__ __forceinline__ void mbar_wait(uint32_t a, uint32_t ph) {
  asm volatile("{\n.reg .pred p;\nW: mbarrier.try_wait.parity.shared::cta.b64 p, [%0], %1;\n@!p bra W;\n}" :: "r"(a), "r"(ph) : "memory");
}
__device__ __forceinline__ void mbar_wait_sleep(uint32_t a, uint32_t ph) {
  asm volatile("{\n.reg .pred p;\nW: mbarrier.test_wait.parity.shared::cta.b64 p, [%0], %1;\n@p bra D;\nnanosleep.u32 %2;\nbra W;\nD:\n}" :: "r"(a), "r"(ph), "n"(SLEEP) : "memory");
}
__device__ __forceinline__ void wg_fence() { asm volatile("wgmma.fence.sync.aligned;" ::: "memory"); }
__device__ __forceinline__ void wg_commit() { asm volatile("wgmma.commit_group.sync.aligned;" ::: "memory"); }
template <int N> __device__ __forceinline__ void wg_wait() { asm volatile("wgmma.wait_group.sync.aligned %0;" :: "n"(N) : "memory"); }
__device__ __forceinline__ float tanh_ap(float x) { float y; asm("tanh.approx.f32 %0, %1;" : "=f"(y) : "f"(x)); return y; }
__device__ __forceinline__ float ex2(float x) { float y; asm("ex2.approx.ftz.f32 %0, %1;" : "=f"(y) : "f"(x)); return y; }
__device__ __forceinline__ uint32_t pack_bf16(float lo, float hi) { uint32_t r; asm("cvt.rn.bf16x2.f32 %0, %1, %2;" : "=r"(r) : "f"(hi), "f"(lo)); return r; }
__device__ __forceinline__ float bf_lo(uint32_t v) { return __uint_as_float(v << 16); }
__device__ __forceinline__ float bf_hi(uint32_t v) { return __uint_as_float(v & 0xffff0000u); }
__device__ __forceinline__ uint32_t sub_bf16x2(uint32_t a, uint32_t b) { uint32_t r; asm("sub.rn.bf16x2 %0, %1, %2;" : "=r"(r) : "r"(a), "r"(b)); return r; }
__device__ __forceinline__ uint32_t mul_bf16x2(uint32_t a, uint32_t b) { uint32_t r; asm("mul.rn.bf16x2 %0, %1, %2;" : "=r"(r) : "r"(a), "r"(b)); return r; }
__device__ __forceinline__ uint32_t diff2(uint32_t a, uint32_t b, uint32_t t) { uint32_t r; asm("lop3.b32 %0, %1, %2, %3, 0x7e;" : "=r"(r) : "r"(a), "r"(b), "r"(t)); return r; }
__device__ __forceinline__ uint32_t or3(uint32_t a, uint32_t b, uint32_t c) { uint32_t r; asm("lop3.b32 %0, %1, %2, %3, 0xfe;" : "=r"(r) : "r"(a), "r"(b), "r"(c)); return r; }
__device__ __forceinline__ uint32_t umin2(uint32_t a, uint32_t b) { uint32_t r; asm("min.u32 %0, %1, %2;" : "=r"(r) : "r"(a), "r"(b)); return r; }
__device__ __forceinline__ uint32_t bitmask(uint32_t v, int bit) { uint32_t r; asm("bfe.s32 %0, %1, %2, 1;" : "=r"(r) : "r"(v), "r"(bit)); return r; }
__device__ __forceinline__ uint32_t nz(uint32_t w) { return w == 0u ? 0x8000u : w; }

__device__ __forceinline__ void ldg4(uint32_t* d, const uint4* p) {
  asm volatile("ld.relaxed.gpu.global.v4.b32 {%0,%1,%2,%3}, [%4];" : "=r"(d[0]), "=r"(d[1]), "=r"(d[2]), "=r"(d[3]) : "l"(p) : "memory");
}
__device__ __forceinline__ void ldg2(uint32_t* d, const void* p) {
  asm volatile("ld.relaxed.gpu.global.v2.b32 {%0,%1}, [%2];" : "=r"(d[0]), "=r"(d[1]) : "l"(p) : "memory");
}
__device__ __forceinline__ void stg4(uint4* p, uint32_t a, uint32_t b, uint32_t c, uint32_t d) {
  asm volatile("st.relaxed.gpu.global.v4.b32 [%0], {%1,%2,%3,%4};" :: "l"(p), "r"(a), "r"(b), "r"(c), "r"(d) : "memory");
}
__device__ __forceinline__ void stg2(void* p, uint32_t a, uint32_t b) {
  asm volatile("st.relaxed.gpu.global.v2.b32 [%0], {%1,%2};" :: "l"(p), "r"(a), "r"(b) : "memory");
}
__device__ __forceinline__ void sts4(uint32_t a, const uint32_t* o) { asm volatile("st.shared.v4.b32 [%0], {%1,%2,%3,%4};" :: "r"(a), "r"(o[0]), "r"(o[1]), "r"(o[2]), "r"(o[3]) : "memory"); }
__device__ __forceinline__ void lds4(uint32_t a, uint32_t* o) { asm volatile("ld.shared.v4.b32 {%0,%1,%2,%3}, [%4];" : "=r"(o[0]), "=r"(o[1]), "=r"(o[2]), "=r"(o[3]) : "r"(a) : "memory"); }
__device__ __forceinline__ void lds2(uint32_t a, uint32_t* o) { asm volatile("ld.shared.v2.b32 {%0,%1}, [%2];" : "=r"(o[0]), "=r"(o[1]) : "r"(a) : "memory"); }
__device__ __forceinline__ float rcp(float x) { float y; asm("rcp.approx.ftz.f32 %0, %1;" : "=f"(y) : "f"(x)); return y; }
__device__ __forceinline__ void sts1(uint32_t a, uint32_t v) { asm volatile("st.shared.b32 [%0], %1;" :: "r"(a), "r"(v) : "memory"); }
__device__ __forceinline__ void ldsm4(uint32_t a, uint32_t& r0, uint32_t& r1, uint32_t& r2, uint32_t& r3) {
  asm volatile("ldmatrix.sync.aligned.m8n8.x4.shared.b16 {%0,%1,%2,%3}, [%4];" : "=r"(r0), "=r"(r1), "=r"(r2), "=r"(r3) : "r"(a) : "memory");
}
__device__ __forceinline__ void ldsm4t(uint32_t a, uint32_t& r0, uint32_t& r1, uint32_t& r2, uint32_t& r3) {
  asm volatile("ldmatrix.sync.aligned.m8n8.x4.trans.shared.b16 {%0,%1,%2,%3}, [%4];" : "=r"(r0), "=r"(r1), "=r"(r2), "=r"(r3) : "r"(a) : "memory");
}
__device__ __forceinline__ void mma16(float* c, uint32_t a0, uint32_t a1, uint32_t a2, uint32_t a3, uint32_t b0, uint32_t b1) {
  asm("mma.sync.aligned.m16n8k16.row.col.f32.bf16.bf16.f32 {%0,%1,%2,%3}, {%4,%5,%6,%7}, {%8,%9}, {%0,%1,%2,%3};"
    : "+f"(c[0]), "+f"(c[1]), "+f"(c[2]), "+f"(c[3]) : "r"(a0), "r"(a1), "r"(a2), "r"(a3), "r"(b0), "r"(b1));
}
__device__ __forceinline__ void mma16c(float* d, const uint32_t* a, uint32_t b0, uint32_t b1, float c01) {
  asm("mma.sync.aligned.m16n8k16.row.col.f32.bf16.bf16.f32 {%0,%1,%2,%3}, {%4,%5,%6,%7}, {%8,%9}, {%10,%10,%10,%10};"
    : "=f"(d[0]), "=f"(d[1]), "=f"(d[2]), "=f"(d[3]) : "r"(a[0]), "r"(a[1]), "r"(a[2]), "r"(a[3]), "r"(b0), "r"(b1), "f"(c01));
}
__device__ __forceinline__ void mma8(float* c, uint32_t a0, uint32_t a1, uint32_t b0) {
  asm("mma.sync.aligned.m16n8k8.row.col.f32.bf16.bf16.f32 {%0,%1,%2,%3}, {%4,%5}, {%6}, {%0,%1,%2,%3};"
    : "+f"(c[0]), "+f"(c[1]), "+f"(c[2]), "+f"(c[3]) : "r"(a0), "r"(a1), "r"(b0));
}
__device__ __forceinline__ uint32_t lane_id() { uint32_t l; asm volatile("mov.u32 %0, %%laneid;" : "=r"(l)); return l; }
__device__ __forceinline__ float quad_sum(float v) { v += __shfl_xor_sync(~0u, v, 1); v += __shfl_xor_sync(~0u, v, 2); return v; }
__device__ __forceinline__ float quad_max(float v) { v = fmaxf(v, __shfl_xor_sync(~0u, v, 1)); v = fmaxf(v, __shfl_xor_sync(~0u, v, 2)); return v; }
template <int N> __device__ __forceinline__ void pin(float (&d)[N]) {
#pragma unroll
  for (int i = 0; i < N; i++) asm volatile("" : "+f"(d[i]) :: "memory");
}
#define SPIN_GUARD(n) if (++(n) > SPIN_MAX) break

template <int NG> __device__ __forceinline__ void publish_stats(uint4* dst, const float* y, uint32_t tag, uint32_t lane) {
  float s0 = 0.f, s1 = 0.f;
#pragma unroll
  for (int g = 0; g < NG; g++) { s0 += y[4 * g] + y[4 * g + 1]; s1 += y[4 * g + 2] + y[4 * g + 3]; }
  s0 = quad_sum(s0); s1 = quad_sum(s1);
  const float m0 = s0 * (1.f / (8 * NG)), m1 = s1 * (1.f / (8 * NG));
  float q0 = 0.f, q1 = 0.f, q2 = 0.f, q3 = 0.f;
#pragma unroll
  for (int g = 0; g < NG; g++) {
    const float a = y[4 * g] - m0, b = y[4 * g + 1] - m0, c = y[4 * g + 2] - m1, d = y[4 * g + 3] - m1;
    q0 = fmaf(a, a, q0); q1 = fmaf(b, b, q1); q2 = fmaf(c, c, q2); q3 = fmaf(d, d, q3);
  }
  q0 = quad_sum(q0 + q1); q2 = quad_sum(q2 + q3);
  if ((lane & 3) == 0)
    stg4(dst + (lane >> 2), (__float_as_uint(s0) & ~1u) | tag, __float_as_uint(q0), __float_as_uint(s1), __float_as_uint(q2));
}

__device__ __forceinline__ void put72(uint4* slab, uint32_t j, uint32_t lane, const uint32_t* v, uint32_t r0, uint32_t r1) {
  uint4* p = slab + ((9 * j + 1) >> 1) * 32;
#pragma unroll
  for (int i = 0; i < 4; i++) stg4(p + lane + i * 32, nz(v[4 * i]), v[4 * i + 1], v[4 * i + 2], v[4 * i + 3]);
  stg2((char*)((j & 1) ? p - 16 : p + 4 * 32) + lane * 8, nz(r0), r1);
}
__device__ __forceinline__ void zero_share(uint4* slab, uint32_t j, uint32_t lane) {
  uint4* p = slab + j * 144 + lane;
#pragma unroll
  for (int i = 0; i < 4; i++) stg4(p + i * 32, 0u, 0u, 0u, 0u);
  if (lane < 16) stg4(p + 128, 0u, 0u, 0u, 0u);
}

struct Maps { CUtensorMap m[8]; };

struct Ring {
  uint32_t st, ph;
  __device__ __forceinline__ void next() { if (++st == NST) { st = 0; ph ^= 1; } }
};

#define GSTAMP(i) do {} while (0)
#define STAMP(i) do {} while (0)
#define ZSTAMP(m, i) do {} while (0)

__device__ __forceinline__ void tma_box(uint32_t dst, const CUtensorMap* m, int col, int row, uint32_t bar, uint32_t expect) {
  asm volatile("{\n.reg .pred e, h;\nelect.sync _|e, 0xffffffff;\nsetp.ne.and.u32 h, %5, 0, e;\n"
               "@h mbarrier.arrive.expect_tx.shared::cta.b64 _, [%2], %5;\n"
               "@e cp.async.bulk.tensor.2d.shared::cluster.global.mbarrier::complete_tx::bytes [%0], [%1, {%3, %4}], [%2];\n}"
               :: "r"(dst), "l"(m), "r"(bar), "r"(col), "r"(row), "r"(expect) : "memory");
}

__device__ __forceinline__ void bulk_load(uint32_t dst, const void* src, uint32_t bytes, uint32_t bar, bool arm) {
  asm volatile("{\n.reg .pred e, h;\nelect.sync _|e, 0xffffffff;\nsetp.ne.and.u32 h, %4, 0, e;\n"
               "@h mbarrier.arrive.expect_tx.shared::cta.b64 _, [%3], %2;\n"
               "@e cp.async.bulk.shared::cluster.global.mbarrier::complete_tx::bytes [%0], [%1], %2, [%3];\n}"
               :: "r"(dst), "l"(src), "r"(bytes), "r"(bar), "r"((uint32_t)arm) : "memory");
}

__global__ void __launch_bounds__(384, 1) mega_kernel(
    const __grid_constant__ Maps maps, uint4* __restrict__ scratch,
    __nv_bfloat16* __restrict__ out) {
  extern __shared__ __align__(1024) uint8_t smem[];
  const uint32_t sb = (uint32_t)__cvta_generic_to_shared(smem);
  const uint32_t full0 = sb + BARS, empty0 = full0 + 8 * NST, rem_full = empty0 + 8 * NST, park_free = rem_full + 8, kv_free = park_free + 8;
  const uint32_t c8_go = kv_free + 8, c8_done = c8_go + 8, c8_full = c8_done + 8, remo_full = c8_full + 8, piece_full = remo_full + 8, xb_done = piece_full + 8, res_full = xb_done + 8, pbar0 = res_full + 8;
  const uint32_t x_done = pbar0 + 64, x_ring = x_done + 8, xbar0 = x_ring + 8;
  const uint32_t w = __shfl_sync(~0u, threadIdx.x >> 5, 0);
  uint32_t pair = blockIdx.x >> 1;
  if (gridDim.x == 132) {
    uint32_t smid;
    asm("mov.u32 %0, %%smid;" : "=r"(smid));
    const uint32_t tpc = smid >> 1;
    if (tpc == 60 || tpc == 61) { if (threadIdx.x == 0) { __nanosleep(20000); } return; }
    pair = tpc < 32 ? tpc : tpc >= 62 ? (tpc - 58) * 8 : 33 + (tpc - 32) / 7 * 8 + (tpc - 32) % 7;
  }
  const uint32_t rank = blockIdx.x & 1, t = (pair & 7) * 2 + rank, j = pair >> 3;
  const uint32_t sd = sb & 0x3ffff;
  const uint32_t odd = j & 1;
  uint4* const scr = scratch + t * TILE;
  const uint32_t xs = sb + (NST - 2) * STAGE;
  auto fetch_x = [&](uint32_t dst, uint32_t b, uint32_t bar) {
    asm volatile("{\n.reg .pred e;\nelect.sync _|e, 0xffffffff;\n@e mbarrier.arrive.expect_tx.shared::cta.b64 _, [%2], 16384;\n"
                 "@e cp.async.bulk.tensor.3d.shared::cluster.global.mbarrier::complete_tx::bytes [%0], [%1, {%3, %4, 0}], [%2];\n}"
                 :: "r"(dst), "l"(&maps.m[7]), "r"(bar), "r"(64 * b), "r"(64 * t) : "memory");
  };
  if (w == 8) {
    if (threadIdx.x == 256) {
      for (int i = 0; i < NST; i++) { mbar_init(full0 + 8 * i, 1); mbar_init(empty0 + 8 * i, 16); }
      mbar_init(rem_full, 1); mbar_init(park_free, 8); mbar_init(kv_free, 8); mbar_init(c8_go, 8); mbar_init(c8_done, 2); mbar_init(c8_full, 1);
      mbar_init(remo_full, 64); mbar_init(piece_full, 1); mbar_init(xb_done, 8); mbar_init(res_full, 8); mbar_init(x_done, 8); mbar_init(x_ring, 16);
      for (int i = 0; i < 8; i++) mbar_init(pbar0 + 8 * i, 4);
      for (int i = 0; i < 9; i++) mbar_init(xbar0 + 8 * i, 1);
      asm volatile("fence.mbarrier_init.release.cluster;" ::: "memory");
    }
    __syncwarp();
  }
  asm volatile("barrier.cluster.arrive.relaxed.aligned;" ::: "memory");
  if (w != 8) asm volatile("barrier.cluster.wait.aligned;" ::: "memory");

  if (w >= 8) {
    asm volatile("setmaxnreg.dec.sync.aligned.u32 24;");
    if (w == 8) {
#pragma unroll 1
      for (uint32_t b = 0; b < 9; b++) fetch_x(xs + b * STAGE, b, xbar0 + 8 * b);
      tma_box(sb + PIECE, &maps.m[t >= 12 ? 6 : 5], 72 * j + (odd ? 0 : 64) + (t < 8 ? 576 * ((t >> 2) + 1) : 0), 144 * (t & 3), piece_full, 2304);
      asm volatile("barrier.cluster.wait.aligned;" ::: "memory");
      uint32_t dst = sb, bar = full0, ph = 1;
#pragma unroll 1
      for (int seg = 0; seg < 34; seg++) {
        const int n = seg >= 17 ? seg - 17 : seg;
        int ma, mb, ca, cb, row = 0;
        if (n < 3) { ma = mb = n == 2; ca = 72 * j + 8 * odd + (n == 0 ? 576 : 0); cb = ca + 576; }
        else if (n < 12) { ma = 3; mb = 2; ca = cb = 576 * j + 64 * (n - 3); }
        else { ma = mb = 4; ca = n == 12 ? 512 : ((j + 2 * n) & 7) * 64; cb = ((j + 2 * n + 1) & 7) * 64; row = 576 * j; }
        const bool zip = n == 0 || n == 3, solo = n == 1 || n == 2 || n == 16;
        const CUtensorMap *pa = &maps.m[ma], *pb = &maps.m[mb];
#pragma unroll 1
        for (int st = 0; st < (solo ? 5 : 9); st++) {
          if (seg == 0 && st == NST - 2) mbar_wait(x_ring, 0);
          const bool s0 = !zip && st > 4, s1 = zip || st >= 4;
          const int r0 = row + (zip ? 64 * st : s0 ? 128 * st - 576 : 128 * st), r1 = zip ? r0 : st == 4 ? row : r0 + 64;
          const bool rk = rank, sm = rk ? s1 : s0;
          asm volatile("{\n.reg .pred p, e, f;\n.reg .u32 n;\nelect.sync _|e, 0xffffffff;\nsetp.ne.and.u32 f, %7, 0, e;\nmov.u32 n, 0;\n"
                       "W: mbarrier.try_wait.parity.shared::cta.b64 p, [%1+48], %2;\n@p bra D;\n"
                       "add.u32 n, n, 1;\nsetp.lt.u32 p, n, 4194304;\n@p bra W;\ntrap;\n"
                       "D: @e mbarrier.arrive.expect_tx.shared::cta.b64 _, [%1], %6;\n"
                       "@f cp.async.bulk.tensor.2d.shared::cluster.global.mbarrier::complete_tx::bytes.multicast::cluster [%0], [%3, {%4, %5}], [%1], 3;\n}"
                       :: "r"(dst + rk * 8192), "r"(bar), "r"(ph), "l"(sm ? pb : pa), "r"(sm ? cb : ca), "r"(rk ? r1 : r0),
                          "r"(solo && st == 4 ? STAGE / 2 : STAGE), "r"((uint32_t)!(rk && solo && st == 4)) : "memory");
          dst += STAGE; bar += 8;
          if (bar == full0 + 8 * NST) { dst = sb; bar = full0; ph ^= 1; }
        }
      }
      {
#pragma unroll 1
        for (int i = 0; i < NST; i++) {
          mbar_wait_trap(bar + 48, ph);
          bar += 8;
          if (bar == full0 + 8 * NST) { bar = full0; ph ^= 1; }
        }
      }
    } else if (w == 9) {
      const uint32_t lane = lane_id();
      const uint32_t stg = sb + HSTG + lane * 16;
      uint32_t fph = 0;
#pragma unroll 1
      for (uint32_t layer = 0; layer < 2; layer++) {
        uint4* xb = scr + OFF_X + ((4 + layer) * 8 + j) * SLAB + 32 * 32;
        mbar_wait_sleep(c8_go, layer);
        int n = 0;
        while (true) {
          if (lane == 0) asm volatile("mbarrier.arrive.expect_tx.shared::cta.b64 _, [%0], 18432;" :: "r"(c8_full) : "memory");
          __syncwarp();
#pragma unroll 1
          for (uint32_t s = 0; s < 9; s++)
            bulk_load(sb + HSTG + s * 2048, s < 8 ? scr + OFF_P + (j + s * 8) * SLAB + 32 * 32 : xb, 2048, c8_full, false);
          mbar_wait(c8_full, fph); fph ^= 1;
          uint32_t bad = 0;
#pragma unroll 8
          for (int s = 0; s < 32; s++) { uint32_t v; asm volatile("ld.shared.b32 %0, [%1];" : "=r"(v) : "r"(stg + s * 512) : "memory"); bad |= v ^ (1 - layer); }
          if (__all_sync(~0u, (bad & 1u) == 0u)) break;
          __nanosleep(300);
          SPIN_GUARD(n);
        }
        asm volatile("bar.arrive 7, 96;" ::: "memory");
        float s0 = 0.f, s1 = 0.f;
#pragma unroll 1
        for (int g = 0; g < 8; g++) {
          const uint32_t a = stg + (g >> 1) * 512 + (g & 1) * 8;
          float a0 = 0.f, a1 = 0.f, a2 = 0.f, a3 = 0.f;
#pragma unroll 1
          for (int b = 0; b < 3; b++) {
            uint32_t v[6];
#pragma unroll
            for (int s = 0; s < 3; s++) lds2(a + (3 * b + s) * 2048, v + 2 * s);
#pragma unroll
            for (int s = 0; s < 3; s++) { a0 += bf_lo(v[2 * s]); a1 += bf_hi(v[2 * s]); a2 += bf_lo(v[2 * s + 1]); a3 += bf_hi(v[2 * s + 1]); }
          }
          sts1(a + 18432, pack_bf16(a0, a1)); sts1(a + 18436, pack_bf16(a2, a3));
          s0 += a0 + a1; s1 += a2 + a3;
        }
        __syncwarp();
        if (lane == 0) mbar_arrive(c8_done);
        s0 = quad_sum(s0); s1 = quad_sum(s1);
        float q0 = 0.f, q1 = 0.f;
        const uint32_t ln = lane_id();
#pragma unroll 1
        for (uint32_t i = 0; i < 4; i++) {
          uint32_t x[4];
          lds4(stg + 18432 + i * 512, x);
          stg4(xb + i * 32 + ln, 0u, 0u, 0u, 0u);
          if (layer == 0) {
            stg4(xb - 3 * 8 * SLAB + i * 32 + ln, nz(x[0]), x[1], x[2], x[3]);
#pragma unroll
            for (int e = 0; e < 4; e++) {
              const float m = (e & 1) ? s1 : s0, c = fmaf(m, -1.f / 64, bf_lo(x[e])), d = fmaf(m, -1.f / 64, bf_hi(x[e]));
              if (e & 1) q1 = fmaf(c, c, fmaf(d, d, q1)); else q0 = fmaf(c, c, fmaf(d, d, q0));
            }
          } else {
            uint32_t* o = (uint32_t*)(out + (128 * t + 32 * (j >> 1) + 2 * (ln >> 2) + (j & 1)) * 576 + 512 + 16 * i + 2 * (ln & 3));
            o[0] = x[0]; o[8 * 576] = x[1]; o[4] = x[2]; o[8 * 576 + 4] = x[3];
          }
        }
        if (layer == 0) {
          q0 = quad_sum(q0); q1 = quad_sum(q1);
          if ((ln & 3) == 0) stg4(scr + OFF_S + j * 96 + 64 + (ln >> 2), __float_as_uint(s0) | 1u, __float_as_uint(q0), __float_as_uint(s1), __float_as_uint(q1));
        }
      }
    } else {
      auto mark = [&](uint32_t k0, uint32_t v) {
        const uint32_t lane = lane_id();
#pragma unroll 1
        for (uint32_t k = k0; k < 6; k++) stg4(scr + OFF_S + (k * 4 + (lane >> 3)) * 96 + j * 8 + (lane & 7), k < 2 ? 0u : v, 0u, 0u, 0u);
      };
      if (w == 11) mark(2, 0u);
      auto phase2_duties = [&](uint32_t layer) {
        const uint32_t lane = lane_id();
        asm volatile("bar.sync 7, 96;" ::: "memory");
        if (w == 11) {
          if (layer == 0) mark(0, 1u);
          __syncwarp();
          if (lane == 0) mbar_arrive(c8_done);
        }
        mbar_wait_sleep(res_full, layer);
#pragma unroll 1
        for (uint32_t i = 0; i < 4; i++) {
          uint4* z = scr + OFF_X + ((4 + layer) * 8 + (w - 10) * 4 + i) * SLAB + 4 * j * 32 + lane;
#pragma unroll
          for (int k = 0; k < 4; k++) stg4(z + k * 32, 0u, 0u, 0u, 0u);
          __nanosleep(300);
        }
      };
      if (w == 10) {
        const uint32_t lane = lane_id();
        uint32_t* fl = (uint32_t*)(scratch + OFF_F + (t * 8 + j) * 8) + (lane & 15);
        uint32_t v;
        asm volatile("ld.relaxed.gpu.global.b32 %0, [%1];" : "=r"(v) : "l"(fl) : "memory");
        mbar_wait(piece_full, 0);
        asm volatile("{\n.reg .pred e;\nelect.sync _|e, 0xffffffff;\n@e cp.async.bulk.global.shared::cta.bulk_group [%0], [%1], 2304;\n}\n"
                     "cp.async.bulk.commit_group;\ncp.async.bulk.wait_group 0;\nfence.proxy.async;"
                     :: "l"(scratch + OFF_R + j * 2304 + t * 144), "r"(sb + PIECE) : "memory");
        __syncwarp();
        if (lane < 16) asm volatile("st.release.gpu.global.b32 [%0], 1;" :: "l"((uint32_t*)(scratch + OFF_F + (lane_id() * 8 + j) * 8) + t) : "memory");
        int n = 0;
        while (!__all_sync(~0u, v != 0u)) {
          __nanosleep(100);
          SPIN_GUARD(n);
          asm volatile("ld.relaxed.gpu.global.b32 %0, [%1];" : "=r"(v) : "l"(fl) : "memory");
        }
        asm volatile("st.relaxed.gpu.global.b32 [%0], 0;" :: "l"(fl) : "memory");
        mbar_wait(x_done, 0);
      }
#pragma unroll 1
      for (uint32_t layer = 0; layer < 2; layer++) {
        if (w == 10) {
          if (layer) mbar_wait_sleep(park_free, 0);
          bulk_load(sb + REM, scratch + OFF_R + j * 2304, 36864, rem_full, true);
          if (layer == 0) { fetch_x(sb + PARK, j, xbar0); fetch_x(sb + PARK + STAGE, j + 1, xbar0 + 8); }
        }
        mbar_wait_sleep(rem_full, layer);
#pragma unroll 1
        for (uint32_t b = 0; b < 5; b++) {
          const uint32_t blk = sb + REM + 27648 + b * 2048, k = (w - 10) * 32 + lane_id(), rr = k & 7;
          const uint32_t dst = blk + ((k >> 3) & 1) * 1024 + rr * 128 + (((k >> 4) ^ rr) << 4);
          uint32_t v[8];
          lds4(blk + k * 16, v); lds4(blk + 1024 + k * 16, v + 4);
          asm volatile("bar.sync 3, 64;" ::: "memory");
          sts4(dst, v); sts4(dst ^ 64, v + 4);
        }
        asm volatile("fence.proxy.async.shared::cta;" ::: "memory");
        mbar_arrive(remo_full);
        if (layer) { phase2_duties(0); mbar_wait_sleep(kv_free, 0); }
        if (t > 0) {
          const uint32_t lane = lane_id(), r = lane >> 2, q = lane & 3;
#pragma unroll 1
          for (uint32_t pc = 0; pc < 3; pc++) {
            uint4* hp = scr + OFF_H + ((layer * 8 + j) * 2 + (w - 10)) * 192 + pc * 64 + lane;
            uint32_t hl[8];
            int n = 0;
            hl[4] = 1u;
            while (true) {
              ldg4(hl, hp);
              if (pc < 2) ldg4(hl + 4, hp + 32);
              if (__all_sync(~0u, hl[0] != 0u && hl[4] != 0u)) break;
              __nanosleep(100);
              SPIN_GUARD(n);
            }
            const uint32_t dst = sb + KVS + (w - 10) * 10368 + r * 144 + q * 4;
            if (pc < 2) {
#pragma unroll
              for (int g = 0; g < 8; g++) sts1(dst + pc * 20736 + odd * 16 + g * 16, hl[g]);
              stg4(hp + 32, 0u, 0u, 0u, 0u);
            } else {
              sts1(dst + (odd ? 0 : 128), hl[0]); sts1(dst + 20736 + (odd ? 0 : 128), hl[1]);
            }
            stg4(hp, 0u, 0u, 0u, 0u);
          }
        }
        asm volatile("bar.arrive 1, 192;" ::: "memory");
        mbar_wait_sleep(xb_done, layer);
        if (w == 10 && layer == 1) {
          const uint32_t lane = lane_id();
          stg4(scr + OFF_S + (lane >> 3) * 96 + j * 8 + (lane & 7), 0u, 0u, 0u, 0u);
          stg4(scr + OFF_S + (4 + (lane >> 3)) * 96 + j * 8 + (lane & 7), 0u, 0u, 0u, 0u);
          if (lane < 8) stg4(scr + OFF_S + j * 96 + 64 + lane, 0u, 0u, 0u, 0u);
        }
#pragma unroll 1
        for (uint32_t i = 0; i < 8 && (w == 11 || layer == 1); i++) {
          zero_share(scr + OFF_X + ((w - 10) * 16 + layer * 8 + i) * SLAB, j, lane_id());
          __nanosleep(500);
        }
      }
      phase2_duties(1);
    }
  } else {
    asm volatile("setmaxnreg.inc.sync.aligned.u32 240;");
    const bool lead = lane_id() == 0;
    Ring rg{0, 0};
    uint32_t prev = 0;
    uint32_t X[144];
    float rs0, rs1;
    const bool lead2 = lane_id() < 2;
    uint32_t empty_at;
    asm volatile("mapa.shared::cluster.u32 %0, %1, %2;" : "=r"(empty_at) : "r"(empty0), "r"(lane_id() & 1));
    auto release = [&](uint32_t st) { if (lead2) asm volatile("mbarrier.arrive.shared::cluster.b64 _, [%0];" :: "r"(empty_at + st * 8) : "memory"); };
    auto load_kb = [&](int kb, const uint4* src, const char* lo, uint32_t hoff) {
#pragma unroll
      for (int k = 4 * kb; k < 4 * kb + 4; k++) {
        if (k % 9 == 4) { ldg2(X + 4 * k, lo + k * 512); ldg2(X + 4 * k + 2, lo + hoff + k * 512); }
        else ldg4(X + 4 * k, src + k * 32);
      }
    };
    auto check_kb = [&](bool skip, int kb, const uint4* src, const char* lo, uint32_t hoff) {
      int n = 0;
      while (true) {
        uint32_t m = umin2(umin2(X[16 * kb], X[16 * kb + 4]), umin2(X[16 * kb + 8], X[16 * kb + 12]));
        if (kb & 1) m = umin2(m, X[16 * kb + 4 * (kb >> 1) + 2]);
        if (__all_sync(~0u, m != 0u || skip)) break;
        SPIN_GUARD(n);
        load_kb(kb, src, lo, hoff);
      }
    };
#pragma unroll 1
    for (uint32_t hf = 0; hf < 4; hf++) {
      const uint32_t layer = hf >> 1;
      const bool ffn = hf & 1;
      const uint32_t tag = 1 - layer;
      uint4* const xbase = scr + OFF_X + (layer * 8 + w) * SLAB;
      float aA[32], aB[32];
      {
        const uint32_t lane = lane_id(), r = lane >> 2, q = lane & 3;
        const uint4* src = xbase + (ffn ? 32 * SLAB : 0) + lane;
        const char* lo = (const char*)src - (ffn ? lane * 8 : 0);
        const uint32_t hoff = ffn ? 256 : 8;
        const uint32_t xoff = (w & 1) * 8192 + (16 * (w >> 1) + (lane & 15)) * 128 + (((lane >> 4) ^ (lane & 7)) << 4);
        auto load_x = [&](uint32_t b, uint32_t* d) {
#pragma unroll
          for (int i = 0; i < 4; i++) ldsm4(xs + b * STAGE + (xoff ^ (32 * i)), d[4 * i], d[4 * i + 1], d[4 * i + 2], d[4 * i + 3]);
        };
        auto load_any = [&](int kb) { if (hf == 0) load_x(kb, X + 16 * kb); else load_kb(kb, src, lo, hoff); };
        float m0, m1, v0, v1;
        STAMP(ffn * 16 + 0);
        if (hf == 0) {
          float sum[2][4] = {}, sq0[4][4] = {}, sq1[4][4] = {};
          uint32_t p0, p1;
          mbar_wait(xbar0, 0);
          ldsm4(xs + xoff, p0, p1, X[0], X[1]);
          p0 = __byte_perm(__shfl_sync(~0u, p0, lane & 28), 0, 0x1010); p1 = __byte_perm(__shfl_sync(~0u, p1, lane & 28), 0, 0x1010);
#pragma unroll 3
          for (uint32_t b = 0; b < 9; b++) {
            uint32_t d[16];
            mbar_wait(xbar0 + 8 * b, 0);
            load_x(b, d);
#pragma unroll
            for (int i = 0; i < 16; i++) d[i] = sub_bf16x2(d[i], (i & 1) ? p1 : p0);
#pragma unroll
            for (int g = 0; g < 8; g++) {
              if (!(g & 1)) mma16(sum[(g >> 1) & 1], d[2 * g], d[2 * g + 1], d[2 * g + 2], d[2 * g + 3], 0x3f803f80u, 0x3f803f80u);
              mma8(sq0[g & 3], d[2 * g], d[2 * g + 1], d[2 * g]); mma8(sq1[g & 3], d[2 * g], d[2 * g + 1], d[2 * g + 1]);
            }
          }
          STAMP(1);
          GSTAMP(14);
#pragma unroll
          for (int kb = 0; kb < GD; kb++) load_x(kb, X + 16 * kb);
          release((x_ring - empty0) / 8);
          auto tot = [](float (&c)[4][4], int e) { return (c[0][e] + c[1][e]) + (c[2][e] + c[3][e]); };
          const float a0 = (sum[0][0] + sum[1][0]) * (1.f / 576), a1 = (sum[0][2] + sum[1][2]) * (1.f / 576);
          const uint32_t dg = (lane & 28) + (r >> 1);
          v0 = fmaxf(fmaf(__shfl_sync(~0u, (r & 1) ? tot(sq0, 1) : tot(sq0, 0), dg), 1.f / 576, -a0 * a0), 0.f);
          v1 = fmaxf(fmaf(__shfl_sync(~0u, (r & 1) ? tot(sq1, 3) : tot(sq1, 2), dg), 1.f / 576, -a1 * a1), 0.f);
          m0 = bf_lo(p0) + a0; m1 = bf_lo(p1) + a1;
        } else {
          uint32_t s[3][4];
          const uint4* p = scr + OFF_S + ((ffn ? 16 : 0) + w) * 96 + q * 8 + r;
          const bool third = !ffn && q == 0;
          const uint32_t rdy = ffn ? tag : 1u;
          int n = 0;
          s[2][0] = rdy; s[2][1] = s[2][2] = s[2][3] = 0u;
          while (true) {
            ldg4(s[0], p); ldg4(s[1], p + 32);
            if (third) ldg4(s[2], p + 64);
            if (__all_sync(~0u, ((diff2(s[0][0], s[1][0], rdy) | diff2(s[1][0], s[2][0], rdy)) & 1u) == 0u)) break;
            SPIN_GUARD(n);
          }
          STAMP(ffn * 16 + 1);
          ZSTAMP(1 + ffn, 0);
          GSTAMP(14 + ffn);
#pragma unroll
          for (int kb = 0; kb < GD; kb++) load_kb(kb, src, lo, hoff);
          float t0 = 0.f, t1 = 0.f;
#pragma unroll
          for (int i = 0; i < 3; i++) { t0 += __uint_as_float(s[i][0]); t1 += __uint_as_float(s[i][2]); }
          m0 = quad_sum(t0) * (1.f / 576); m1 = quad_sum(t1) * (1.f / 576);
          const float cnt = ffn ? 72.f : 64.f, inv = ffn ? 1.f / 72 : 1.f / 64;
          v0 = 0.f; v1 = 0.f;
#pragma unroll
          for (int i = 0; i < 3; i++) {
            const float c = (i < 2 || third) ? cnt : 0.f;
            const float d0 = fmaf(__uint_as_float(s[i][0]), inv, -m0), d1 = fmaf(__uint_as_float(s[i][2]), inv, -m1);
            v0 += fmaf(d0 * d0, c, __uint_as_float(s[i][1])); v1 += fmaf(d1 * d1, c, __uint_as_float(s[i][3]));
          }
          v0 = quad_sum(v0) * (1.f / 576); v1 = quad_sum(v1) * (1.f / 576);
        }
        rs0 = rsqrtf(v0 + 1e-5f); rs1 = rsqrtf(v1 + 1e-5f);
        const uint32_t mean0 = pack_bf16(m0, m0), mean1 = pack_bf16(m1, m1);
#pragma unroll
        for (int kb = 0; kb < 9; kb++) {
          check_kb(hf == 0, kb, src, lo, hoff);
          if (kb + GD < 9) load_any(kb + GD);
          if (kb + GD == 8 && hf == 0 && lead) mbar_arrive(x_done);
#pragma unroll
          for (int i = 16 * kb; i < 16 * kb + 16; i++) X[i] = sub_bf16x2(X[i], (i & 1) ? mean1 : mean0);
          ZSTAMP(1 + ffn, 1 + 3 * kb);
          mbar_wait(full0 + rg.st * 8, rg.ph);
          ZSTAMP(1 + ffn, 2 + 3 * kb);
          const uint64_t desc = DESC_HI | ((sd + rg.st * STAGE) >> 4);
          wg_fence();
#pragma unroll
          for (int i = 0; i < 4; i++) wgmma_rs_n64(aA, X + 4 * (4 * kb + i), desc + i * 128, kb + i != 0);
          if (SPLITZ && kb == 8) { wg_commit(); wg_wait<1>(); wg_fence(); }
#pragma unroll
          for (int i = 0; i < 4; i++) wgmma_rs_n64(aB, X + 4 * (4 * kb + i), desc + 512 + i * 128, kb + i != 0);
          wg_commit();
          wg_wait<1>();
          ZSTAMP(1 + ffn, 3 + 3 * kb);
          if (kb > 0) release(prev);
          prev = rg.st; rg.next();
        }
        if (!SPLITZ) wg_wait<0>();
        ZSTAMP(1 + ffn, 28);
        ZSTAMP(4, 0);
        STAMP(ffn * 16 + 2);
      }
      if (!ffn) {
      const uint32_t lane = lane_id(), r = lane >> 2, q = lane & 3;
      const uint32_t kvrow = sb + KVS + (w & 1) * 10368 + (16 * (w >> 1)) * 144;
      uint32_t Q[18], Km[3][8], Ke[3][4];
      const bool edge = (t == 0 && w < 2);
      const uint32_t row0 = edge ? sb + KVS + 8 * 144 : kvrow + (lane & 7) * 144, row1 = kvrow + (8 + (lane & 7)) * 144;
      {
        const uint32_t dst = kvrow + (8 + r) * 144 + q * 4 + odd * 16, dstr = dst + (odd ? -16 : 128);
        const bool edge_out = w >= 6 && t < 15;
        uint4* const hp = scr + TILE + OFF_H + ((layer * 8 + j) * 2 + (w & 1)) * 192 + lane;
        auto put_kv = [&](float (&a)[32], int part) {
          pin(a);
          uint32_t hl[8];
#pragma unroll
          for (int g = 0; g < 8; g++) {
            hl[g] = pack_bf16(a[4 * g + 2] * rs1, a[4 * g + 3] * rs1);
            sts1(dst + part * 20736 + g * 16, pack_bf16(a[4 * g] * rs0, a[4 * g + 1] * rs0)); sts1(dst + part * 20736 + 8 * 144 + g * 16, hl[g]);
          }
          if (edge_out) { stg4(hp + part * 64, nz(hl[0]), hl[1], hl[2], hl[3]); stg4(hp + part * 64 + 32, nz(hl[4]), hl[5], hl[6], hl[7]); }
        };
        put_kv(aA, 0);
        wg_wait<0>();
        release(prev);
        float aR[12];
        mbar_wait(rem_full, layer);
        const uint64_t dr = DESC_REM | ((sd + REM) >> 4);
        wg_fence();
#pragma unroll
        for (int s = 0; s < 36; s++) {
          wgmma_rs_n24(aR, X + 4 * s, dr + s * 16, s != 0);
          if (s == 4) put_kv(aB, 1);
        }
        wg_commit();
#pragma unroll
        for (int kb = 0; kb < 9; kb++) {
          if (kb == HOFF1 && w < 4) asm volatile("bar.sync 4, 256;" ::: "memory");
          if (kb == 8 && HOFF1 < 9 && w >= 4) asm volatile("bar.arrive 4, 256;" ::: "memory");
          if (!(kb & 1)) mbar_wait(full0 + rg.st * 8, rg.ph);
          const uint64_t desc = DESC_HI | ((sd + rg.st * STAGE + (kb & 1) * 8192) >> 4);
          wg_fence();
#pragma unroll
          for (int i = 0; i < 4; i++) wgmma_rs_n64(aB, X + 4 * (4 * kb + i), desc + i * 128, kb + i != 0);
          wg_commit();
          wg_wait<1>();
          if (kb > 0 && !(kb & 1)) release(prev);
          if ((kb & 1) || kb == 8) { prev = rg.st; rg.next(); }
          if (kb == 0) {
            pin(aR);
            const uint32_t k1 = pack_bf16(aR[2] * rs1, aR[3] * rs1), v1 = pack_bf16(aR[6] * rs1, aR[7] * rs1);
            if (edge_out) stg4(hp + 128, nz(k1), v1, 0u, 0u);
            sts1(dstr, pack_bf16(aR[0] * rs0, aR[1] * rs0)); sts1(dstr + 8 * 144, k1);
            sts1(dstr + 20736, pack_bf16(aR[4] * rs0, aR[5] * rs0)); sts1(dstr + 20736 + 8 * 144, v1);
            Q[16] = pack_bf16(aR[8], aR[9]); Q[17] = pack_bf16(aR[10], aR[11]);
            if (w < 4) asm volatile("bar.arrive 2, 256;" ::: "memory");
          }
          if (kb == KLD - 2) mbar_wait(remo_full, layer);
          if (kb == KLD) {
            if (w < 4) asm volatile("bar.sync 1, 192;" ::: "memory");
            else asm volatile("bar.sync 2, 256;" ::: "memory");
#pragma unroll
            for (int nt = 0; nt < 3; nt++) {
              const uint32_t ra = (nt == 0 ? row0 : row1 + (nt - 1) * 8 * 144);
              ldsm4(ra + odd * 16 + (lane >> 3) * 16, Km[nt][0], Km[nt][1], Km[nt][2], Km[nt][3]);
              ldsm4(ra + odd * 16 + 64 + (lane >> 3) * 16, Km[nt][4], Km[nt][5], Km[nt][6], Km[nt][7]);
              ldsm4(ra + (odd ? 0 : 32) + (lane >> 3) * 32, Ke[nt][0], Ke[nt][1], Ke[nt][2], Ke[nt][3]);
            }
            const uint32_t ge = (2u << q) - 1, le = 0xfu << q, on = edge ? 0u : ~0u;
            const uint32_t bits = odd ? 0xfu | ((le & 0xfu) << 4) | (ge << 8) : ge | 0xf0u | (le << 8);
#pragma unroll
            for (int h = 0; h < 4; h++) {
              const uint32_t ma = bitmask(bits, h), mb = bitmask(bits, 4 + h), mc = bitmask(bits, 8 + h);
              Km[0][2 * h] &= ma & on; Km[0][2 * h + 1] &= mb & on; Ke[0][h] &= mc & on;
#pragma unroll
              for (int nt = 1; nt < 3; nt++) { Km[nt][2 * h] &= ma; Km[nt][2 * h + 1] &= mb; Ke[nt][h] &= mc; }
            }
          }
        }
        wg_wait<0>();
        release(prev);
        pin(aB);
        STAMP(3);
#pragma unroll
        for (int i = 0; i < 16; i++) Q[i] = pack_bf16(aB[2 * i], aB[2 * i + 1]);
      }
      {
        uint32_t V01[12][2], V2[12];
        const uint32_t rv = ((lane & 8) ? row1 : row0) + 20736, rw = row1 + 8 * 144 + 20736;
#pragma unroll
        for (int i = 0; i < 4; i++) ldsm4t(rv + odd * 16 + i * 32 + (lane >> 4) * 16, V01[2 * i][0], V01[2 * i][1], V01[2 * i + 1][0], V01[2 * i + 1][1]);
#pragma unroll
        for (int i = 0; i < 2; i++) ldsm4t(rv + (odd ? 0 : 32) + i * 64 + (lane >> 4) * 32, V01[8 + 2 * i][0], V01[8 + 2 * i][1], V01[9 + 2 * i][0], V01[9 + 2 * i][1]);
        ldsm4t(rw + odd * 16 + (lane >> 3) * 16, V2[0], V2[1], V2[2], V2[3]);
        ldsm4t(rw + odd * 16 + 64 + (lane >> 3) * 16, V2[4], V2[5], V2[6], V2[7]);
        ldsm4t(rw + (odd ? 0 : 32) + (lane >> 3) * 32, V2[8], V2[9], V2[10], V2[11]);
        const bool up0 = 2 * q > r, up1 = 2 * q + 1 > r;
        const uint32_t upm = (up0 ? 0xffffu : 0u) | (up1 ? 0xffff0000u : 0u);
        const float c0 = 0.23570226039551584f * 1.4426950408889634f * rs0, c1 = 0.23570226039551584f * 1.4426950408889634f * rs1;
        const float masked = edge ? -1e9f * 1.4426950408889634f * rcp(c0) : 0.f;
        uint32_t Om[16], Oe[8];
#pragma unroll
        for (int h = 0; h < 4; h++) {
          const uint32_t e0 = odd ? Q[(4 * h + 16) % 18] : Q[4 * h + 4], e1 = odd ? Q[(4 * h + 17) % 18] : Q[4 * h + 5];
          float S[3][4];
#pragma unroll
          for (int nt = 0; nt < 3; nt++) {
            mma16c(S[nt], Q + 4 * h, Km[nt][2 * h], Km[nt][2 * h + 1], nt == 0 ? masked : 0.f);
            mma8(S[nt], e0, e1, Ke[nt][h]);
          }
          const float s00 = up0 ? S[0][0] : S[1][0], s01 = up1 ? S[0][1] : S[1][1];
          const float s10 = up0 ? S[1][2] : S[2][2], s11 = up1 ? S[1][3] : S[2][3];
          const float m0 = quad_max(fmaxf(s00, s01)) * c0, m1 = quad_max(fmaxf(s10, s11)) * c1;
          const float p00 = ex2(fmaf(s00, c0, -m0)), p01 = ex2(fmaf(s01, c0, -m0)), p10 = ex2(fmaf(s10, c1, -m1)), p11 = ex2(fmaf(s11, c1, -m1));
          const float i0 = rcp(quad_sum(p00 + p01)), i1 = rcp(quad_sum(p10 + p11));
          const uint32_t p0 = pack_bf16(p00 * i0, p01 * i0), p1 = pack_bf16(p10 * i1, p11 * i1);
          const uint32_t pf[4] = {p0 & upm, 0u, p0 & ~upm, p1 & upm};
#pragma unroll
          for (int gi = 0; gi < 3; gi++) {
            const int g = gi < 2 ? 2 * h + gi : 8 + h;
            float o[4];
            mma16c(o, pf, V01[g][0], V01[g][1], 0.f);
            mma8(o, 0u, p1 & ~upm, V2[g]);
            uint32_t* d = gi < 2 ? Om + 2 * g : Oe + 2 * h;
            d[0] = pack_bf16(o[0], o[1]); d[1] = pack_bf16(o[2], o[3]);
          }
        }
#pragma unroll
        for (int h = 0; h < 4; h++)
#pragma unroll
          for (int e = 0; e < 2; e++) {
            if (h > 0 && !odd && q < h) Om[4 * h + e] = Oe[2 * h - 2 + e];
            if (h < 3 && odd && q > h) Om[4 * h + 2 + e] = Oe[2 * h + 2 + e];
          }
        STAMP(4);
        if (j >= PRI && lane == 0) asm volatile("st.relaxed.gpu.global.b32 [%0], %1;" :: "l"(scr + OFF_S + (8 + w) * 96 + j * 8), "r"(tag) : "memory");
        put72(xbase + 16 * SLAB, j, lane, Om, odd ? Oe[0] : Oe[6], odd ? Oe[1] : Oe[7]);
      }
      if (j < PRI && lane == 0) asm volatile("st.relaxed.gpu.global.b32 [%0], %1;" :: "l"(scr + OFF_S + (8 + w) * 96 + j * 8), "r"(tag) : "memory");
      {
        uint32_t res[18];
        if (layer == 0) {
          const uint32_t xrow = (w & 1) * 8192 + (16 * (w >> 1) + (lane & 15)) * 128;
          uint32_t u0, u1;
          mbar_wait(xbar0, 1); mbar_wait(xbar0 + 8, 1);
#pragma unroll
          for (int i = 0; i < 5; i++) {
            const uint32_t g = i < 4 ? j + odd + 2 * i : j + (odd ? 0 : 8);
            const uint32_t a = sb + PARK + (g >> 3) * STAGE + xrow;
            if (i < 4) ldsm4(a + ((((g & 7) + (lane >> 4)) ^ (lane & 7)) << 4), res[4 * i], res[4 * i + 1], res[4 * i + 2], res[4 * i + 3]);
            else ldsm4(a + (((g & 7) ^ (lane & 7)) << 4), res[16], res[17], u0, u1);
          }
        } else {
          const uint4* p = xbase + ((9 * j + 1) >> 1) * 32 + lane;
#pragma unroll
          for (int i = 0; i < 4; i++) ldg4(res + 4 * i, p + i * 32);
          ldg2(res + 16, odd ? (const char*)(p - 32) + 8 : (const char*)(p + 4 * 32));
        }
        const uint4* src = xbase + 16 * SLAB + lane;
        {
          const uint4* fp = scr + OFF_S + (8 + w) * 96 + (lane & 7) * 8;
          int n = 0;
          STAMP(8);
          while (true) {
            uint32_t f;
            asm volatile("ld.relaxed.gpu.global.b32 %0, [%1];" : "=r"(f) : "l"(fp) : "memory");
            if (__all_sync(~0u, f == tag)) break;
            SPIN_GUARD(n);
          }
          STAMP(9);
        }
        if (HOFF3 < 9 && w < 4) asm volatile("bar.sync 6, 256;" ::: "memory");
#pragma unroll
        for (int kb = 0; kb < GO; kb++) load_kb(kb, src, (const char*)src - lane * 8, 256);
        float acc[36];
#pragma unroll
        for (int i = 0; i < 18; i++) { acc[2 * i] = bf_lo(res[i]); acc[2 * i + 1] = bf_hi(res[i]); }
#pragma unroll
        for (int kb = 0; kb < 9; kb++) {
          check_kb(false, kb, src, (const char*)src - lane * 8, 256);
          if (kb + GO < 9) load_kb(kb + GO, src, (const char*)src - lane * 8, 256);
          if (kb == HOFF3 && w >= 4) asm volatile("bar.arrive 6, 256;" ::: "memory");
          if (!(kb & 1)) mbar_wait(full0 + rg.st * 8, rg.ph);
          const uint32_t base = sd + rg.st * STAGE + (kb & 1) * 8192;
          const uint64_t d0 = DESC_HI | ((base >> 4) + (((sd + REM + 27648 + (kb >> 1) * 2048 + (kb & 1) * 64 - base) >> 4) << 16));
          wg_fence();
#pragma unroll
          for (int i = 0; i < 4; i++) wgmma_rs_n72(acc, X + 4 * (4 * kb + i), d0 - (uint64_t)(i * ((127u << 16) - 128u)), 1);
          wg_commit();
          wg_wait<1>();
          if (kb > 0 && !(kb & 1)) release(prev);
          if ((kb & 1) || kb == 8) { prev = rg.st; rg.next(); }
        }
        wg_wait<0>();
        release(prev);
        pin(acc);
        STAMP(10);
#pragma unroll
        for (int i = 0; i < 18; i++) res[i] = pack_bf16(acc[2 * i], acc[2 * i + 1]);
        if (j < PRI) put72(xbase + 32 * SLAB, j, lane, res, res[16], res[17]);
        publish_stats<9>(scr + OFF_S + (16 + w) * 96 + j * 8, acc, tag, lane);
        if (j >= PRI) put72(xbase + 32 * SLAB, j, lane, res, res[16], res[17]);
      }
      continue;
      }
      const uint32_t hp = sb + PARK + w * 512 + lane_id() * 16;
      auto pack8 = [&](float (&a)[32], int p, uint32_t* o) {
#pragma unroll
        for (int e = 0; e < 8; e++) asm volatile("" : "+f"(a[8 * p + e]) :: "memory");
#pragma unroll
        for (int e = 0; e < 4; e++) o[e] = pack_bf16(a[8 * p + 2 * e], a[8 * p + 2 * e + 1]);
      };
      const float ka0 = 0.7978845608028654f * rs0, kb0 = 0.044715f * ka0 * rs0 * rs0, ku0 = 0.5f * rs0 * rs0;
      const float ka1 = 0.7978845608028654f * rs1, kb1 = 0.044715f * ka1 * rs1 * rs1, ku1 = 0.5f * rs1 * rs1;
      auto packu8 = [&](int p, uint32_t* o) {
#pragma unroll
        for (int e = 0; e < 8; e++) asm volatile("" : "+f"(aA[8 * p + e]) :: "memory");
#pragma unroll
        for (int e = 0; e < 4; e++) o[e] = pack_bf16(aA[8 * p + 2 * e] * ((e & 1) ? ku1 : ku0), aA[8 * p + 2 * e + 1] * ((e & 1) ? ku1 : ku0));
      };
      auto geglu8 = [&](int p, uint32_t* u) {
#pragma unroll
        for (int e = 0; e < 8; e++) asm volatile("" : "+f"(aB[8 * p + e]) :: "memory");
        float h[8];
#pragma unroll
        for (int e = 0; e < 8; e++) {
          const float g = aB[8 * p + e];
          h[e] = fmaf(g, tanh_ap(g * fmaf(g * g, (e & 2) ? kb1 : kb0, (e & 2) ? ka1 : ka0)), g);
        }
#pragma unroll
        for (int e = 0; e < 4; e++) u[e] = mul_bf16x2(pack_bf16(h[2 * e], h[2 * e + 1]), u[e]);
      };
      auto box = [&](int b, auto&& filler) {
        const int kb = b < 9 ? b : b - 9;
        if (!(b & 1)) { if ((TRAPB >> (b >> 1)) & 1) mbar_wait_trap(full0 + rg.st * 8, rg.ph); else mbar_wait(full0 + rg.st * 8, rg.ph); }
        const uint64_t desc = DESC_HI | ((sd + rg.st * STAGE + (b & 1) * 8192) >> 4);
        wg_fence();
#pragma unroll
        for (int i = 0; i < 4; i++) {
          if (b < 9) wgmma_rs_n64(aA, X + 4 * (4 * kb + i), desc + i * 128, kb + i != 0);
          else wgmma_rs_n64(aB, X + 4 * (4 * kb + i), desc + i * 128, kb + i != 0);
          if (i == FPOS) filler();
        }
        wg_commit();
        if (b & 1) { prev = rg.st; rg.next(); } else { wg_wait<1>(); release(prev); }
      };
      auto nop = [] {};
      auto step = [&](int st, auto&& filler) { box(2 * st, nop); box(2 * st + 1, filler); };
#pragma unroll
      for (int p = 0; p < 4; p++) { uint32_t o[4]; packu8(p, o); sts4(hp + p * 4096, o); }
      box(0, nop);
      if (lead) mbar_arrive(xb_done);
#pragma unroll 1
      for (int c = 1;; c++) {
        const uint32_t hc = hp + c * 4 * 4096;
#pragma unroll
        for (int b = 1; b < 18; b++) box(b, [&] {
          if ((b & 1) && b < 8) { uint32_t o[4]; const uint32_t a = hc - (4 - (b >> 1)) * 4096; lds4(a, o); geglu8(b >> 1, o); sts4(a, o); }
          if ((b & 1) && b > 10) { uint32_t o[4]; packu8((b - 11) >> 1, o); if (c < 8) sts4(hc + ((b - 11) >> 1) * 4096, o); } });
        ZSTAMP(4, c);
        if (c == 8) break;
        box(0, nop);
      }
      wg_wait<0>();
      STAMP(21);
      GSTAMP(19);
      auto unpark = [&](int kb) {
#pragma unroll
        for (int s = 4 * kb; s < 4 * kb + 4; s++) lds4(hp + s * 4096, X + 4 * s);
      };
      unpark(0);
      uint32_t U[16];
#pragma unroll
      for (int p = 0; p < 4; p++) packu8(p, U + 4 * p);
#pragma unroll
      for (int b = 0; b < 8; b++) box(b, [&] {
        if (b < 7) unpark(b + 1);
        if (b & 1) {
          geglu8(b >> 1, U + 2 * (b - 1));
          if (rg.ph > 1) sts4(hp, U + 2 * (b - 1));
#pragma unroll
          for (int i = 0; i < 4; i++) X[128 + 2 * (b - 1) + i] = U[2 * (b - 1) + i];
        } });
      STAMP(24);
      if (layer == 0 && lead) mbar_arrive(park_free);
      const uint32_t lane2 = lane_id();
      uint4* const pw = scr + OFF_P + (j * 8 + w) * SLAB + lane2;
      const uint4* const pr = scr + OFF_P + w * SLAB + 4 * j * 32 + lane2;
      auto put_part = [&](float (&a)[32], int p, uint32_t chunk) {
        uint32_t o[4];
        pack8(a, p, o);
        stg4(pw + (chunk * 4 + p) * 32, (o[0] & ~1u) | tag, o[1], o[2], o[3]);
      };
      uint4* const xb = xbase + 32 * SLAB + 4 * j * 32;
      auto slot = [&](int p) { return sb + w * 2048 + (p < 3 ? PARK + p * 16384 : KVS + (p - 3) * 16384); };
      auto fetch = [&](int p) {
        bulk_load(slot(p), p ? scr + OFF_P + (((j - p) & 7) * 8 + w) * SLAB + 4 * j * 32 : xb, 2048, p ? pbar0 + w * 8 : res_full, true);
      };
#pragma unroll 1
      for (int sp = 0;; sp++) {
        const uint32_t ca = sp == 0 ? 8 : ((j + 2 * sp) & 7), cb = (j + 2 * sp + 1) & 7;
        if (C8 == 1 && sp == 1 && lead) mbar_arrive(c8_go);
#pragma unroll
        for (int st = 4; st < 9; st++) step(st, [&] {
          if (st == 5 || st == 6) { put_part(aA, 2 * (st - 5), ca); put_part(aA, 2 * (st - 5) + 1, ca); }
          if (st == 8 && sp > 0) { if (sp == 3) mbar_wait(c8_done, layer); fetch(2 * sp - 2); } });
        STAMP(25 + sp);
        if (sp == 3) break;
        if (C8 == 0 && sp == 0 && lead) mbar_arrive(c8_go);
#pragma unroll
        for (int st = 0; st < 4; st++) step(st, [&] {
          if (st < 2) { put_part(aB, 2 * st, cb); put_part(aB, 2 * st + 1, cb); }
          if (st == 3 && sp > 0) fetch(2 * sp - 1); });
      }
      auto load_p = [&](int p, uint32_t* d) {
#pragma unroll
        for (int i = 0; i < 4; i++) ldg4(d + 4 * i, pr + ((j - p) & 7) * 8 * SLAB + i * 32);
      };
#pragma unroll
      for (int b = 0; b < 9; b++) {
        if (b == HOFF2 && w < 4) asm volatile("bar.sync 5, 256;" ::: "memory");
        box(b, [&] {
          if (b == 1) {
#pragma unroll
            for (int p = 0; p < 4; p++) put_part(aB, p, (j + 7) & 7);
          }
          if (b == 3) { load_p(5, X); load_p(6, X + 16); }
          if (b == 7 && EXP != 1) load_p(7, X + 32); });
        if (b == 7 && HOFF2 < 9 && w >= 4) asm volatile("bar.arrive 5, 256;" ::: "memory");
      }
      mbar_wait(res_full, layer);
      mbar_wait(pbar0 + w * 8, layer);
#pragma unroll
      for (int p = 1; p < 5; p++)
#pragma unroll
        for (int i = 0; i < 4; i++) lds4(slot(p) + lane2 * 16 + i * 512, X + 48 + 16 * p + 4 * i);
#pragma unroll
      for (int i = 0; i < 4; i++) {
        const bool split = j == 2 * i + 1;
        const uint32_t a = slot(0) + i * 512 + (split ? lane2 * 8 : lane2 * 16);
        lds2(a, X + 48 + 4 * i); lds2(a + (split ? 256 : 8), X + 50 + 4 * i);
      }
      wg_wait<0>();
      release(rg.st); rg.next();
      pin(aA);
      STAMP(22);
      GSTAMP(20);
      {
        const uint32_t lane = lane2, r = lane >> 2, q = lane & 3;
        const uint32_t eye = r == 2 * q ? 0x3f80u : r == 2 * q + 1 ? 0x3f800000u : 0u;
        auto bad = [&](const uint32_t* d) { return diff2(d[0], d[4], tag) | diff2(d[8], d[12], tag); };
        auto add = [&](const uint32_t* d) {
#pragma unroll
          for (int g = 0; g < 8; g++) mma8(aA + 4 * g, d[2 * g], d[2 * g + 1], eye);
        };
        int n = 0;
        while (!__all_sync(~0u, ((or3(bad(X), bad(X + 16), bad(X + 64)) | or3(bad(X + 80), bad(X + 96), bad(X + 112))) & 1u) == 0u)) {
          SPIN_GUARD(n);
          load_p(5, X); load_p(6, X + 16);
#pragma unroll
          for (int p = 1; p < 5; p++) load_p(p, X + 48 + 16 * p);
        }
        add(X); add(X + 16);
#pragma unroll
        for (int p = 4; p >= 0; p--) add(X + 48 + 16 * ((p + 1) % 5));
        STAMP(11);
        if (EXP != 1) while (!__all_sync(~0u, (bad(X + 32) & 1u) == 0u)) { SPIN_GUARD(n); load_p(7, X + 32); }
        add(X + 32);
        STAMP(12);
        uint32_t res[16];
#pragma unroll
        for (int i = 0; i < 16; i++) res[i] = pack_bf16(aA[2 * i], aA[2 * i + 1]);
        if (layer == 0) {
          uint4* p = xbase + 8 * SLAB + 4 * j * 32 + lane;
          auto put = [&] {
#pragma unroll
            for (int i = 0; i < 4; i++) stg4(p + i * 32, nz(res[4 * i]), res[4 * i + 1], nz(res[4 * i + 2]), res[4 * i + 3]);
          };
          if (j < PRI) put();
          publish_stats<8>(scr + OFF_S + w * 96 + j * 8, aA, 1u, lane);
          if (j >= PRI) put();
          if (lane == 0) mbar_arrive(kv_free);
        } else {
          const uint32_t tb = slot(0);
          __syncwarp();
#pragma unroll
          for (int i = 0; i < 4; i++) {
            const uint32_t row = (lane2 & 7) + (lane2 & 8), g = 2 * i + (lane2 >> 4);
            asm volatile("stmatrix.sync.aligned.m8n8.x4.shared.b16 [%0], {%1,%2,%3,%4};"
                         :: "r"(tb + row * 128 + ((g ^ (row & 7)) << 4)), "r"(res[4 * i]), "r"(res[4 * i + 1]), "r"(res[4 * i + 2]), "r"(res[4 * i + 3]) : "memory");
          }
          __syncwarp();
#pragma unroll
          for (int i = 0; i < 4; i++) {
            const uint32_t row = 4 * i + (lane2 >> 3), g = lane2 & 7;
            uint32_t v[4];
            lds4(tb + row * 128 + ((g ^ (row & 7)) << 4), v);
            *(uint4*)(out + (128 * t + 32 * (w >> 1) + 2 * row + (w & 1)) * 576 + 64 * j + 8 * g) = make_uint4(v[0], v[1], v[2], v[3]);
          }
        }
      }
      STAMP(23);
    }
  }
}

typedef CUresult (*EncodeFn)(CUtensorMap*, CUtensorMapDataType, cuuint32_t, void*, const cuuint64_t*, const cuuint64_t*,
                             const cuuint32_t*, const cuuint32_t*, CUtensorMapInterleave, CUtensorMapSwizzle,
                             CUtensorMapL2promotion, CUtensorMapFloatOOBfill);

CUtensorMap make_map(EncodeFn f, const void* p, uint64_t cols, uint64_t rows, bool rem = false) {
  CUtensorMap m;
  cuuint64_t dims[2] = {cols, rows};
  cuuint64_t str[1] = {cols * 2};
  cuuint32_t box[2] = {rem ? 8u : 64u, rem ? 144u : 64u};
  cuuint32_t es[2] = {1, 1};
  f(&m, CU_TENSOR_MAP_DATA_TYPE_BFLOAT16, 2, const_cast<void*>(p), dims, str, box, es, CU_TENSOR_MAP_INTERLEAVE_NONE,
    rem ? CU_TENSOR_MAP_SWIZZLE_NONE : CU_TENSOR_MAP_SWIZZLE_128B, CU_TENSOR_MAP_L2_PROMOTION_NONE, CU_TENSOR_MAP_FLOAT_OOB_FILL_NONE);
  return m;
}

}

extern "C" void kernel_launch(void* const* d_in, const int* in_sizes, int n_in, void* d_out, int out_size) {
  void* fn = nullptr;
  cudaDriverEntryPointQueryResult qr;
  cudaGetDriverEntryPoint("cuTensorMapEncodeTiled", &fn, cudaEnableDefault, &qr);
  EncodeFn enc = (EncodeFn)fn;
  Maps maps;
  maps.m[0] = make_map(enc, d_in[1], 1728, 576); maps.m[1] = make_map(enc, d_in[2], 576, 576);
  maps.m[2] = make_map(enc, d_in[4], 4608, 576); maps.m[3] = make_map(enc, d_in[5], 4608, 576); maps.m[4] = make_map(enc, d_in[6], 576, 4608);
  maps.m[5] = make_map(enc, d_in[1], 1728, 576, true); maps.m[6] = make_map(enc, d_in[2], 576, 576, true);
  {
    cuuint64_t dims[3] = {576, 1024, 2}, str[2] = {2304, 1152};
    cuuint32_t box[3] = {64, 64, 2}, es[3] = {1, 1, 1};
    enc(&maps.m[7], CU_TENSOR_MAP_DATA_TYPE_BFLOAT16, 3, d_in[0], dims, str, box, es, CU_TENSOR_MAP_INTERLEAVE_NONE,
        CU_TENSOR_MAP_SWIZZLE_128B, CU_TENSOR_MAP_L2_PROMOTION_NONE, CU_TENSOR_MAP_FLOAT_OOB_FILL_NONE);
  }
  void* scr = nullptr;
  cudaGetSymbolAddress(&scr, g_scratch);
  cudaFuncSetAttribute(mega_kernel, cudaFuncAttributeMaxDynamicSharedMemorySize, SMEM_BYTES);
  cudaLaunchConfig_t cfg = {};
  cfg.gridDim = dim3(128); cfg.blockDim = dim3(384); cfg.dynamicSmemBytes = SMEM_BYTES; cfg.stream = cudaStreamPerThread;
  cudaLaunchAttribute at[1];
  at[0].id = cudaLaunchAttributeClusterDimension; at[0].val.clusterDim.x = 2; at[0].val.clusterDim.y = 1; at[0].val.clusterDim.z = 1;
  cfg.attrs = at; cfg.numAttrs = 1;
  int dev = 0, sms = 0, clusters = 0;
  cudaGetDevice(&dev);
  cudaDeviceGetAttribute(&sms, cudaDevAttrMultiProcessorCount, dev);
  cudaOccupancyMaxActiveClusters(&clusters, mega_kernel, &cfg);
  if (sms == 132 && clusters == 66) cfg.gridDim = dim3(132);
  cudaLaunchKernelEx(&cfg, mega_kernel, maps, (uint4*)scr, (__nv_bfloat16*)d_out);
}
```

```cpp
#include <cuda_runtime.h>
#include <cuda.h>
#include <cuda_bf16.h>
#include <stdint.h>

#define TRACE 0
#define GUARD 0
#define TRAPB 1
#define HOFF1 99
#define HOFF2 99
#define KLD 8
#define ZT 0
#define SLEEP 500
#define SPLITZ 1
#define C8 1
#define HOFF3 99
#define GO 3
#define EXP 0
#define FPOS 2

namespace {

constexpr int NST = 6;
constexpr int STAGE = 16384;
constexpr int PARK = NST * STAGE;
constexpr int REM = PARK + 49152;
constexpr int KVS = REM + 40960;
constexpr int PIECE = PARK + 7 * STAGE;
constexpr int HSTG = KVS + 16384;
constexpr int BARS = KVS + 41472;
constexpr int TRC = BARS + 512;
constexpr int SMEM_BYTES = TRC + (TRACE ? 512 : 0);
static_assert(NST == 6, "the producer addresses empty barriers as full + 48");
static_assert(BARS >= PARK + 131072, "barriers overlap park");
static_assert(SMEM_BYTES <= 232448, "smem");

constexpr int SLAB = 36 * 32;
constexpr int SPIN_MAX = 1 << 17;
constexpr uint32_t PRI = 3;
constexpr int GD = 3;
constexpr int OFF_S = 0;
constexpr int OFF_H = OFF_S + 3 * 8 * 96;
constexpr int OFF_X = OFF_H + 2 * 8 * 384;
constexpr int OFF_P = OFF_X + 6 * 8 * SLAB;
constexpr int TILE = OFF_P + 8 * 8 * SLAB;
constexpr int OFF_R = 16 * TILE;
constexpr int OFF_F = OFF_R + 8 * 2304;
constexpr int SCRATCH = OFF_F + 128 * 8;

}

__device__ uint4 g_scratch[SCRATCH];

namespace {

constexpr uint64_t DESC_HI = 0x4000004000000000ull;
constexpr uint64_t DESC_REM = (576ull << 32) | (8u << 16);
__device__ __forceinline__ void wgmma_rs_n64(float (&d)[32], const uint32_t* a, uint64_t desc, int scale_d) {
  asm volatile("{\n.reg .pred p;\nsetp.ne.b32 p, %37, 0;\n"
    "wgmma.mma_async.sync.aligned.m64n64k16.f32.bf16.bf16 "
    "{%0, %1, %2, %3, %4, %5, %6, %7, %8, %9, %10, %11, %12, %13, %14, %15, %16, %17, %18, %19, %20, %21, %22, %23, %24, %25, %26, %27, %28, %29, %30, %31}, "
    "{%32, %33, %34, %35}, %36, p, 1, 1, 1;\n}\n"
    : "+f"(d[0]), "+f"(d[1]), "+f"(d[2]), "+f"(d[3]), "+f"(d[4]), "+f"(d[5]), "+f"(d[6]), "+f"(d[7]), "+f"(d[8]), "+f"(d[9]), "+f"(d[10]), "+f"(d[11]), "+f"(d[12]), "+f"(d[13]), "+f"(d[14]), "+f"(d[15]), "+f"(d[16]), "+f"(d[17]), "+f"(d[18]), "+f"(d[19]), "+f"(d[20]), "+f"(d[21]), "+f"(d[22]), "+f"(d[23]), "+f"(d[24]), "+f"(d[25]), "+f"(d[26]), "+f"(d[27]), "+f"(d[28]), "+f"(d[29]), "+f"(d[30]), "+f"(d[31])
    : "r"(a[0]), "r"(a[1]), "r"(a[2]), "r"(a[3]), "l"(desc), "r"(scale_d));
}
__device__ __forceinline__ void wgmma_rs_n72(float (&d)[36], const uint32_t* a, uint64_t desc, int scale_d) {
  asm volatile("{\n.reg .pred p;\nsetp.ne.b32 p, %41, 0;\n"
    "wgmma.mma_async.sync.aligned.m64n72k16.f32.bf16.bf16 "
    "{%0, %1, %2, %3, %4, %5, %6, %7, %8, %9, %10, %11, %12, %13, %14, %15, %16, %17, %18, %19, %20, %21, %22, %23, %24, %25, %26, %27, %28, %29, %30, %31, %32, %33, %34, %35}, "
    "{%36, %37, %38, %39}, %40, p, 1, 1, 1;\n}\n"
    : "+f"(d[0]), "+f"(d[1]), "+f"(d[2]), "+f"(d[3]), "+f"(d[4]), "+f"(d[5]), "+f"(d[6]), "+f"(d[7]), "+f"(d[8]), "+f"(d[9]), "+f"(d[10]), "+f"(d[11]), "+f"(d[12]), "+f"(d[13]), "+f"(d[14]), "+f"(d[15]), "+f"(d[16]), "+f"(d[17]), "+f"(d[18]), "+f"(d[19]), "+f"(d[20]), "+f"(d[21]), "+f"(d[22]), "+f"(d[23]), "+f"(d[24]), "+f"(d[25]), "+f"(d[26]), "+f"(d[27]), "+f"(d[28]), "+f"(d[29]), "+f"(d[30]), "+f"(d[31]), "+f"(d[32]), "+f"(d[33]), "+f"(d[34]), "+f"(d[35])
    : "r"(a[0]), "r"(a[1]), "r"(a[2]), "r"(a[3]), "l"(desc), "r"(scale_d));
}
__device__ __forceinline__ void wgmma_rs_n24(float (&d)[12], const uint32_t* a, uint64_t desc, int scale_d) {
  asm volatile("{\n.reg .pred p;\nsetp.ne.b32 p, %17, 0;\n"
    "wgmma.mma_async.sync.aligned.m64n24k16.f32.bf16.bf16 "
    "{%0, %1, %2, %3, %4, %5, %6, %7, %8, %9, %10, %11}, "
    "{%12, %13, %14, %15}, %16, p, 1, 1, 1;\n}\n"
    : "+f"(d[0]), "+f"(d[1]), "+f"(d[2]), "+f"(d[3]), "+f"(d[4]), "+f"(d[5]), "+f"(d[6]), "+f"(d[7]), "+f"(d[8]), "+f"(d[9]), "+f"(d[10]), "+f"(d[11])
    : "r"(a[0]), "r"(a[1]), "r"(a[2]), "r"(a[3]), "l"(desc), "r"(scale_d));
}

__device__ __forceinline__ void mbar_init(uint32_t a, uint32_t c) { asm volatile("mbarrier.init.shared::cta.b64 [%0], %1;" :: "r"(a), "r"(c)); }
__device__ __forceinline__ void mbar_arrive(uint32_t a) { asm volatile("mbarrier.arrive.shared::cta.b64 _, [%0];" :: "r"(a) : "memory"); }
__device__ __forceinline__ void mbar_wait_trap(uint32_t a, uint32_t ph) {
  asm volatile("{\n.reg .pred p;\n.reg .u32 n;\nmov.u32 n, 0;\n"
               "W: mbarrier.try_wait.parity.shared::cta.b64 p, [%0], %1;\n@p bra D;\n"
               "add.u32 n, n, 1;\nsetp.lt.u32 p, n, 4194304;\n@p bra W;\ntrap;\nD:\n}" :: "r"(a), "r"(ph) : "memory");
}
__device__ __forceinline__ void mbar_wait(uint32_t a, uint32_t ph) {
  asm volatile("{\n.reg .pred p;\nW: mbarrier.try_wait.parity.shared::cta.b64 p, [%0], %1;\n@!p bra W;\n}" :: "r"(a), "r"(ph) : "memory");
}
__device__ __forceinline__ void mbar_wait_sleep(uint32_t a, uint32_t ph) {
  asm volatile("{\n.reg .pred p;\nW: mbarrier.test_wait.parity.shared::cta.b64 p, [%0], %1;\n@p bra D;\nnanosleep.u32 %2;\nbra W;\nD:\n}" :: "r"(a), "r"(ph), "n"(SLEEP) : "memory");
}
__device__ __forceinline__ void wg_fence() { asm volatile("wgmma.fence.sync.aligned;" ::: "memory"); }
__device__ __forceinline__ void wg_commit() { asm volatile("wgmma.commit_group.sync.aligned;" ::: "memory"); }
template <int N> __device__ __forceinline__ void wg_wait() { asm volatile("wgmma.wait_group.sync.aligned %0;" :: "n"(N) : "memory"); }
__device__ __forceinline__ float tanh_ap(float x) { float y; asm("tanh.approx.f32 %0, %1;" : "=f"(y) : "f"(x)); return y; }
__device__ __forceinline__ float ex2(float x) { float y; asm("ex2.approx.ftz.f32 %0, %1;" : "=f"(y) : "f"(x)); return y; }
__device__ __forceinline__ uint32_t pack_bf16(float lo, float hi) { uint32_t r; asm("cvt.rn.bf16x2.f32 %0, %1, %2;" : "=r"(r) : "f"(hi), "f"(lo)); return r; }
__device__ __forceinline__ float bf_lo(uint32_t v) { return __uint_as_float(v << 16); }
__device__ __forceinline__ float bf_hi(uint32_t v) { return __uint_as_float(v & 0xffff0000u); }
__device__ __forceinline__ uint32_t sub_bf16x2(uint32_t a, uint32_t b) { uint32_t r; asm("sub.rn.bf16x2 %0, %1, %2;" : "=r"(r) : "r"(a), "r"(b)); return r; }
__device__ __forceinline__ uint32_t mul_bf16x2(uint32_t a, uint32_t b) { uint32_t r; asm("mul.rn.bf16x2 %0, %1, %2;" : "=r"(r) : "r"(a), "r"(b)); return r; }
__device__ __forceinline__ uint32_t diff2(uint32_t a, uint32_t b, uint32_t t) { uint32_t r; asm("lop3.b32 %0, %1, %2, %3, 0x7e;" : "=r"(r) : "r"(a), "r"(b), "r"(t)); return r; }
__device__ __forceinline__ uint32_t or3(uint32_t a, uint32_t b, uint32_t c) { uint32_t r; asm("lop3.b32 %0, %1, %2, %3, 0xfe;" : "=r"(r) : "r"(a), "r"(b), "r"(c)); return r; }
__device__ __forceinline__ uint32_t umin2(uint32_t a, uint32_t b) { uint32_t r; asm("min.u32 %0, %1, %2;" : "=r"(r) : "r"(a), "r"(b)); return r; }
__device__ __forceinline__ uint32_t bitmask(uint32_t v, int bit) { uint32_t r; asm("bfe.s32 %0, %1, %2, 1;" : "=r"(r) : "r"(v), "r"(bit)); return r; }
__device__ __forceinline__ uint32_t nz(uint32_t w) { return w == 0u ? 0x8000u : w; }

__device__ __forceinline__ void ldg4(uint32_t* d, const uint4* p) {
  asm volatile("ld.relaxed.gpu.global.v4.b32 {%0,%1,%2,%3}, [%4];" : "=r"(d[0]), "=r"(d[1]), "=r"(d[2]), "=r"(d[3]) : "l"(p) : "memory");
}
__device__ __forceinline__ void ldg2(uint32_t* d, const void* p) {
  asm volatile("ld.relaxed.gpu.global.v2.b32 {%0,%1}, [%2];" : "=r"(d[0]), "=r"(d[1]) : "l"(p) : "memory");
}
__device__ __forceinline__ void stg4(uint4* p, uint32_t a, uint32_t b, uint32_t c, uint32_t d) {
  asm volatile("st.relaxed.gpu.global.v4.b32 [%0], {%1,%2,%3,%4};" :: "l"(p), "r"(a), "r"(b), "r"(c), "r"(d) : "memory");
}
__device__ __forceinline__ void stg2(void* p, uint32_t a, uint32_t b) {
  asm volatile("st.relaxed.gpu.global.v2.b32 [%0], {%1,%2};" :: "l"(p), "r"(a), "r"(b) : "memory");
}
__device__ __forceinline__ void sts4(uint32_t a, const uint32_t* o) { asm volatile("st.shared.v4.b32 [%0], {%1,%2,%3,%4};" :: "r"(a), "r"(o[0]), "r"(o[1]), "r"(o[2]), "r"(o[3]) : "memory"); }
__device__ __forceinline__ void lds4(uint32_t a, uint32_t* o) { asm volatile("ld.shared.v4.b32 {%0,%1,%2,%3}, [%4];" : "=r"(o[0]), "=r"(o[1]), "=r"(o[2]), "=r"(o[3]) : "r"(a) : "memory"); }
__device__ __forceinline__ void lds2(uint32_t a, uint32_t* o) { asm volatile("ld.shared.v2.b32 {%0,%1}, [%2];" : "=r"(o[0]), "=r"(o[1]) : "r"(a) : "memory"); }
__device__ __forceinline__ float rcp(float x) { float y; asm("rcp.approx.ftz.f32 %0, %1;" : "=f"(y) : "f"(x)); return y; }
__device__ __forceinline__ void sts1(uint32_t a, uint32_t v) { asm volatile("st.shared.b32 [%0], %1;" :: "r"(a), "r"(v) : "memory"); }
__device__ __forceinline__ void ldsm4(uint32_t a, uint32_t& r0, uint32_t& r1, uint32_t& r2, uint32_t& r3) {
  asm volatile("ldmatrix.sync.aligned.m8n8.x4.shared.b16 {%0,%1,%2,%3}, [%4];" : "=r"(r0), "=r"(r1), "=r"(r2), "=r"(r3) : "r"(a) : "memory");
}
__device__ __forceinline__ void ldsm4t(uint32_t a, uint32_t& r0, uint32_t& r1, uint32_t& r2, uint32_t& r3) {
  asm volatile("ldmatrix.sync.aligned.m8n8.x4.trans.shared.b16 {%0,%1,%2,%3}, [%4];" : "=r"(r0), "=r"(r1), "=r"(r2), "=r"(r3) : "r"(a) : "memory");
}
__device__ __forceinline__ void mma16(float* c, uint32_t a0, uint32_t a1, uint32_t a2, uint32_t a3, uint32_t b0, uint32_t b1) {
  asm("mma.sync.aligned.m16n8k16.row.col.f32.bf16.bf16.f32 {%0,%1,%2,%3}, {%4,%5,%6,%7}, {%8,%9}, {%0,%1,%2,%3};"
    : "+f"(c[0]), "+f"(c[1]), "+f"(c[2]), "+f"(c[3]) : "r"(a0), "r"(a1), "r"(a2), "r"(a3), "r"(b0), "r"(b1));
}
__device__ __forceinline__ void mma16c(float* d, const uint32_t* a, uint32_t b0, uint32_t b1, float c01) {
  asm("mma.sync.aligned.m16n8k16.row.col.f32.bf16.bf16.f32 {%0,%1,%2,%3}, {%4,%5,%6,%7}, {%8,%9}, {%10,%10,%10,%10};"
    : "=f"(d[0]), "=f"(d[1]), "=f"(d[2]), "=f"(d[3]) : "r"(a[0]), "r"(a[1]), "r"(a[2]), "r"(a[3]), "r"(b0), "r"(b1), "f"(c01));
}
__device__ __forceinline__ void mma8(float* c, uint32_t a0, uint32_t a1, uint32_t b0) {
  asm("mma.sync.aligned.m16n8k8.row.col.f32.bf16.bf16.f32 {%0,%1,%2,%3}, {%4,%5}, {%6}, {%0,%1,%2,%3};"
    : "+f"(c[0]), "+f"(c[1]), "+f"(c[2]), "+f"(c[3]) : "r"(a0), "r"(a1), "r"(b0));
}
__device__ __forceinline__ uint32_t lane_id() { uint32_t l; asm volatile("mov.u32 %0, %%laneid;" : "=r"(l)); return l; }
__device__ __forceinline__ float quad_sum(float v) { v += __shfl_xor_sync(~0u, v, 1); v += __shfl_xor_sync(~0u, v, 2); return v; }
__device__ __forceinline__ float quad_max(float v) { v = fmaxf(v, __shfl_xor_sync(~0u, v, 1)); v = fmaxf(v, __shfl_xor_sync(~0u, v, 2)); return v; }
template <int N> __device__ __forceinline__ void pin(float (&d)[N]) {
#pragma unroll
  for (int i = 0; i < N; i++) asm volatile("" : "+f"(d[i]) :: "memory");
}
#define SPIN_GUARD(n) if (++(n) > SPIN_MAX) break

template <int NG> __device__ __forceinline__ void publish_stats(uint4* dst, const float* y, uint32_t tag, uint32_t lane) {
  float s0 = 0.f, s1 = 0.f;
#pragma unroll
  for (int g = 0; g < NG; g++) { s0 += y[4 * g] + y[4 * g + 1]; s1 += y[4 * g + 2] + y[4 * g + 3]; }
  s0 = quad_sum(s0); s1 = quad_sum(s1);
  const float m0 = s0 * (1.f / (8 * NG)), m1 = s1 * (1.f / (8 * NG));
  float q0 = 0.f, q1 = 0.f, q2 = 0.f, q3 = 0.f;
#pragma unroll
  for (int g = 0; g < NG; g++) {
    const float a = y[4 * g] - m0, b = y[4 * g + 1] - m0, c = y[4 * g + 2] - m1, d = y[4 * g + 3] - m1;
    q0 = fmaf(a, a, q0); q1 = fmaf(b, b, q1); q2 = fmaf(c, c, q2); q3 = fmaf(d, d, q3);
  }
  q0 = quad_sum(q0 + q1); q2 = quad_sum(q2 + q3);
  if ((lane & 3) == 0)
    stg4(dst + (lane >> 2), (__float_as_uint(s0) & ~1u) | tag, __float_as_uint(q0), __float_as_uint(s1), __float_as_uint(q2));
}

__device__ __forceinline__ void put72(uint4* slab, uint32_t j, uint32_t lane, const uint32_t* v, uint32_t r0, uint32_t r1) {
  uint4* p = slab + ((9 * j + 1) >> 1) * 32;
#pragma unroll
  for (int i = 0; i < 4; i++) stg4(p + lane + i * 32, nz(v[4 * i]), v[4 * i + 1], v[4 * i + 2], v[4 * i + 3]);
  stg2((char*)((j & 1) ? p - 16 : p + 4 * 32) + lane * 8, nz(r0), r1);
}
__device__ __forceinline__ void zero_share(uint4* slab, uint32_t j, uint32_t lane) {
  uint4* p = slab + j * 144 + lane;
#pragma unroll
  for (int i = 0; i < 4; i++) stg4(p + i * 32, 0u, 0u, 0u, 0u);
  if (lane < 16) stg4(p + 128, 0u, 0u, 0u, 0u);
}

struct Maps { CUtensorMap m[8]; };

struct Ring {
  uint32_t st, ph;
  __device__ __forceinline__ void next() { if (++st == NST) { st = 0; ph ^= 1; } }
};

#define GSTAMP(i) do {} while (0)
#define STAMP(i) do {} while (0)
#define ZSTAMP(m, i) do {} while (0)

__device__ __forceinline__ void tma_box(uint32_t dst, const CUtensorMap* m, int col, int row, uint32_t bar, uint32_t expect) {
  asm volatile("{\n.reg .pred e, h;\nelect.sync _|e, 0xffffffff;\nsetp.ne.and.u32 h, %5, 0, e;\n"
               "@h mbarrier.arrive.expect_tx.shared::cta.b64 _, [%2], %5;\n"
               "@e cp.async.bulk.tensor.2d.shared::cluster.global.mbarrier::complete_tx::bytes [%0], [%1, {%3, %4}], [%2];\n}"
               :: "r"(dst), "l"(m), "r"(bar), "r"(col), "r"(row), "r"(expect) : "memory");
}

__device__ __forceinline__ void bulk_load(uint32_t dst, const void* src, uint32_t bytes, uint32_t bar, bool arm) {
  asm volatile("{\n.reg .pred e, h;\nelect.sync _|e, 0xffffffff;\nsetp.ne.and.u32 h, %4, 0, e;\n"
               "@h mbarrier.arrive.expect_tx.shared::cta.b64 _, [%3], %2;\n"
               "@e cp.async.bulk.shared::cluster.global.mbarrier::complete_tx::bytes [%0], [%1], %2, [%3];\n}"
               :: "r"(dst), "l"(src), "r"(bytes), "r"(bar), "r"((uint32_t)arm) : "memory");
}

__global__ void __launch_bounds__(384, 1) mega_kernel(
    const __grid_constant__ Maps maps, uint4* __restrict__ scratch,
    __nv_bfloat16* __restrict__ out) {
  extern __shared__ __align__(1024) uint8_t smem[];
  const uint32_t sb = (uint32_t)__cvta_generic_to_shared(smem);
  const uint32_t full0 = sb + BARS, empty0 = full0 + 8 * NST, rem_full = empty0 + 8 * NST, park_free = rem_full + 8, kv_free = park_free + 8;
  const uint32_t c8_go = kv_free + 8, c8_done = c8_go + 8, c8_full = c8_done + 8, remo_full = c8_full + 8, piece_full = remo_full + 8, xb_done = piece_full + 8, res_full = xb_done + 8, pbar0 = res_full + 8;
  const uint32_t x_done = pbar0 + 64, x_ring = x_done + 8, xbar0 = x_ring + 8;
  const uint32_t w = __shfl_sync(~0u, threadIdx.x >> 5, 0);
  uint32_t pair = blockIdx.x >> 1;
  if (gridDim.x == 132) {
    uint32_t smid;
    asm("mov.u32 %0, %%smid;" : "=r"(smid));
    const uint32_t tpc = smid >> 1;
    if (tpc == 60 || tpc == 61) { if (threadIdx.x == 0) { __nanosleep(20000); } return; }
    pair = tpc < 32 ? tpc : tpc >= 62 ? (tpc - 58) * 8 : 33 + (tpc - 32) / 7 * 8 + (tpc - 32) % 7;
  }
  const uint32_t rank = blockIdx.x & 1, t = (pair & 7) * 2 + rank, j = pair >> 3;
  const uint32_t sd = sb & 0x3ffff;
  const uint32_t odd = j & 1;
  uint4* const scr = scratch + t * TILE;
  const uint32_t xs = sb + (NST - 2) * STAGE;
  auto fetch_x = [&](uint32_t dst, uint32_t b, uint32_t bar) {
    asm volatile("{\n.reg .pred e;\nelect.sync _|e, 0xffffffff;\n@e mbarrier.arrive.expect_tx.shared::cta.b64 _, [%2], 16384;\n"
                 "@e cp.async.bulk.tensor.3d.shared::cluster.global.mbarrier::complete_tx::bytes [%0], [%1, {%3, %4, 0}], [%2];\n}"
                 :: "r"(dst), "l"(&maps.m[7]), "r"(bar), "r"(64 * b), "r"(64 * t) : "memory");
  };
  if (threadIdx.x == 256) {
    for (int i = 0; i < 9; i++) mbar_init(xbar0 + 8 * i, 1);
    mbar_init(piece_full, 1);
    asm volatile("fence.mbarrier_init.release.cluster;" ::: "memory");
  }
  if (threadIdx.x == 288) {
    for (int i = 0; i < NST; i++) { mbar_init(full0 + 8 * i, 1); mbar_init(empty0 + 8 * i, 16); }
    mbar_init(x_done, 8); mbar_init(x_ring, 16);
    asm volatile("fence.mbarrier_init.release.cluster;" ::: "memory");
  }
  if (threadIdx.x == 320) {
    mbar_init(rem_full, 1); mbar_init(park_free, 8); mbar_init(kv_free, 8); mbar_init(c8_go, 8); mbar_init(c8_done, 2); mbar_init(c8_full, 1);
    mbar_init(remo_full, 64); mbar_init(xb_done, 8); mbar_init(res_full, 8);
    for (int i = 0; i < 8; i++) mbar_init(pbar0 + 8 * i, 4);
    asm volatile("fence.mbarrier_init.release.cluster;" ::: "memory");
  }
  if (threadIdx.x == 352) {
    asm volatile("prefetch.tensormap [%0];" :: "l"(&maps.m[7]) : "memory");
    asm volatile("prefetch.tensormap [%0];" :: "l"(&maps.m[0]) : "memory");
  }
  __syncwarp();
  asm volatile("barrier.cluster.arrive.relaxed.aligned;" ::: "memory");
  if (w != 8) asm volatile("barrier.cluster.wait.aligned;" ::: "memory");

  if (w >= 8) {
    asm volatile("setmaxnreg.dec.sync.aligned.u32 24;");
    if (w == 8) {
#pragma unroll 1
      for (uint32_t b = 0; b < 9; b++) fetch_x(xs + b * STAGE, b, xbar0 + 8 * b);
      tma_box(sb + PIECE, &maps.m[t >= 12 ? 6 : 5], 72 * j + (odd ? 0 : 64) + (t < 8 ? 576 * ((t >> 2) + 1) : 0), 144 * (t & 3), piece_full, 2304);
      asm volatile("barrier.cluster.wait.aligned;" ::: "memory");
      uint32_t dst = sb, bar = full0, ph = 1;
#pragma unroll 1
      for (int seg = 0; seg < 34; seg++) {
        const int n = seg >= 17 ? seg - 17 : seg;
        int ma, mb, ca, cb, row = 0;
        if (n < 3) { ma = mb = n == 2; ca = 72 * j + 8 * odd + (n == 0 ? 576 : 0); cb = ca + 576; }
        else if (n < 12) { ma = 3; mb = 2; ca = cb = 576 * j + 64 * (n - 3); }
        else { ma = mb = 4; ca = n == 12 ? 512 : ((j + 2 * n) & 7) * 64; cb = ((j + 2 * n + 1) & 7) * 64; row = 576 * j; }
        const bool zip = n == 0 || n == 3, solo = n == 1 || n == 2 || n == 16;
        const CUtensorMap *pa = &maps.m[ma], *pb = &maps.m[mb];
#pragma unroll 1
        for (int st = 0; st < (solo ? 5 : 9); st++) {
          if (seg == 0 && st == NST - 2) mbar_wait(x_ring, 0);
          const bool s0 = !zip && st > 4, s1 = zip || st >= 4;
          const int r0 = row + (zip ? 64 * st : s0 ? 128 * st - 576 : 128 * st), r1 = zip ? r0 : st == 4 ? row : r0 + 64;
          const bool rk = rank, sm = rk ? s1 : s0;
          asm volatile("{\n.reg .pred p, e, f;\n.reg .u32 n;\nelect.sync _|e, 0xffffffff;\nsetp.ne.and.u32 f, %7, 0, e;\nmov.u32 n, 0;\n"
                       "W: mbarrier.try_wait.parity.shared::cta.b64 p, [%1+48], %2;\n@p bra D;\n"
                       "add.u32 n, n, 1;\nsetp.lt.u32 p, n, 4194304;\n@p bra W;\ntrap;\n"
                       "D: @e mbarrier.arrive.expect_tx.shared::cta.b64 _, [%1], %6;\n"
                       "@f cp.async.bulk.tensor.2d.shared::cluster.global.mbarrier::complete_tx::bytes.multicast::cluster [%0], [%3, {%4, %5}], [%1], 3;\n}"
                       :: "r"(dst + rk * 8192), "r"(bar), "r"(ph), "l"(sm ? pb : pa), "r"(sm ? cb : ca), "r"(rk ? r1 : r0),
                          "r"(solo && st == 4 ? STAGE / 2 : STAGE), "r"((uint32_t)!(rk && solo && st == 4)) : "memory");
          dst += STAGE; bar += 8;
          if (bar == full0 + 8 * NST) { dst = sb; bar = full0; ph ^= 1; }
        }
      }
      {
#pragma unroll 1
        for (int i = 0; i < NST; i++) {
          mbar_wait_trap(bar + 48, ph);
          bar += 8;
          if (bar == full0 + 8 * NST) { bar = full0; ph ^= 1; }
        }
      }
    } else if (w == 9) {
      const uint32_t lane = lane_id();
      const uint32_t stg = sb + HSTG + lane * 16;
      uint32_t fph = 0;
#pragma unroll 1
      for (uint32_t layer = 0; layer < 2; layer++) {
        uint4* xb = scr + OFF_X + ((4 + layer) * 8 + j) * SLAB + 32 * 32;
        mbar_wait_sleep(c8_go, layer);
        int n = 0;
        while (true) {
          if (lane == 0) asm volatile("mbarrier.arrive.expect_tx.shared::cta.b64 _, [%0], 18432;" :: "r"(c8_full) : "memory");
          __syncwarp();
#pragma unroll 1
          for (uint32_t s = 0; s < 9; s++)
            bulk_load(sb + HSTG + s * 2048, s < 8 ? scr + OFF_P + (j + s * 8) * SLAB + 32 * 32 : xb, 2048, c8_full, false);
          mbar_wait(c8_full, fph); fph ^= 1;
          uint32_t bad = 0;
#pragma unroll 8
          for (int s = 0; s < 32; s++) { uint32_t v; asm volatile("ld.shared.b32 %0, [%1];" : "=r"(v) : "r"(stg + s * 512) : "memory"); bad |= v ^ (1 - layer); }
          if (__all_sync(~0u, (bad & 1u) == 0u)) break;
          __nanosleep(300);
          SPIN_GUARD(n);
        }
        asm volatile("bar.arrive 7, 96;" ::: "memory");
        float s0 = 0.f, s1 = 0.f;
#pragma unroll 1
        for (int g = 0; g < 8; g++) {
          const uint32_t a = stg + (g >> 1) * 512 + (g & 1) * 8;
          float a0 = 0.f, a1 = 0.f, a2 = 0.f, a3 = 0.f;
#pragma unroll 1
          for (int b = 0; b < 3; b++) {
            uint32_t v[6];
#pragma unroll
            for (int s = 0; s < 3; s++) lds2(a + (3 * b + s) * 2048, v + 2 * s);
#pragma unroll
            for (int s = 0; s < 3; s++) { a0 += bf_lo(v[2 * s]); a1 += bf_hi(v[2 * s]); a2 += bf_lo(v[2 * s + 1]); a3 += bf_hi(v[2 * s + 1]); }
          }
          sts1(a + 18432, pack_bf16(a0, a1)); sts1(a + 18436, pack_bf16(a2, a3));
          s0 += a0 + a1; s1 += a2 + a3;
        }
        __syncwarp();
        if (lane == 0) mbar_arrive(c8_done);
        s0 = quad_sum(s0); s1 = quad_sum(s1);
        float q0 = 0.f, q1 = 0.f;
        const uint32_t ln = lane_id();
#pragma unroll 1
        for (uint32_t i = 0; i < 4; i++) {
          uint32_t x[4];
          lds4(stg + 18432 + i * 512, x);
          stg4(xb + i * 32 + ln, 0u, 0u, 0u, 0u);
          if (layer == 0) {
            stg4(xb - 3 * 8 * SLAB + i * 32 + ln, nz(x[0]), x[1], x[2], x[3]);
#pragma unroll
            for (int e = 0; e < 4; e++) {
              const float m = (e & 1) ? s1 : s0, c = fmaf(m, -1.f / 64, bf_lo(x[e])), d = fmaf(m, -1.f / 64, bf_hi(x[e]));
              if (e & 1) q1 = fmaf(c, c, fmaf(d, d, q1)); else q0 = fmaf(c, c, fmaf(d, d, q0));
            }
          } else {
            uint32_t* o = (uint32_t*)(out + (128 * t + 32 * (j >> 1) + 2 * (ln >> 2) + (j & 1)) * 576 + 512 + 16 * i + 2 * (ln & 3));
            o[0] = x[0]; o[8 * 576] = x[1]; o[4] = x[2]; o[8 * 576 + 4] = x[3];
          }
        }
        if (layer == 0) {
          q0 = quad_sum(q0); q1 = quad_sum(q1);
          if ((ln & 3) == 0) stg4(scr + OFF_S + j * 96 + 64 + (ln >> 2), __float_as_uint(s0) | 1u, __float_as_uint(q0), __float_as_uint(s1), __float_as_uint(q1));
        }
      }
    } else {
      auto mark = [&](uint32_t k0, uint32_t v) {
        const uint32_t lane = lane_id();
#pragma unroll 1
        for (uint32_t k = k0; k < 6; k++) stg4(scr + OFF_S + (k * 4 + (lane >> 3)) * 96 + j * 8 + (lane & 7), k < 2 ? 0u : v, 0u, 0u, 0u);
      };
      if (w == 11) mark(2, 0u);
      auto phase2_duties = [&](uint32_t layer) {
        const uint32_t lane = lane_id();
        asm volatile("bar.sync 7, 96;" ::: "memory");
        if (w == 11) {
          if (layer == 0) mark(0, 1u);
          __syncwarp();
          if (lane == 0) mbar_arrive(c8_done);
        }
        mbar_wait_sleep(res_full, layer);
#pragma unroll 1
        for (uint32_t i = 0; i < 4; i++) {
          uint4* z = scr + OFF_X + ((4 + layer) * 8 + (w - 10) * 4 + i) * SLAB + 4 * j * 32 + lane;
#pragma unroll
          for (int k = 0; k < 4; k++) stg4(z + k * 32, 0u, 0u, 0u, 0u);
          __nanosleep(300);
        }
      };
      if (w == 10) {
        const uint32_t lane = lane_id();
        uint32_t* fl = (uint32_t*)(scratch + OFF_F + (t * 8 + j) * 8) + (lane & 15);
        uint32_t v;
        asm volatile("ld.relaxed.gpu.global.b32 %0, [%1];" : "=r"(v) : "l"(fl) : "memory");
        mbar_wait(piece_full, 0);
        asm volatile("{\n.reg .pred e;\nelect.sync _|e, 0xffffffff;\n@e cp.async.bulk.global.shared::cta.bulk_group [%0], [%1], 2304;\n}\n"
                     "cp.async.bulk.commit_group;\ncp.async.bulk.wait_group 0;\nfence.proxy.async;"
                     :: "l"(scratch + OFF_R + j * 2304 + t * 144), "r"(sb + PIECE) : "memory");
        __syncwarp();
        if (lane < 16) asm volatile("st.release.gpu.global.b32 [%0], 1;" :: "l"((uint32_t*)(scratch + OFF_F + (lane_id() * 8 + j) * 8) + t) : "memory");
        int n = 0;
        while (!__all_sync(~0u, v != 0u)) {
          __nanosleep(100);
          SPIN_GUARD(n);
          asm volatile("ld.relaxed.gpu.global.b32 %0, [%1];" : "=r"(v) : "l"(fl) : "memory");
        }
        asm volatile("st.relaxed.gpu.global.b32 [%0], 0;" :: "l"(fl) : "memory");
        mbar_wait(x_done, 0);
      }
#pragma unroll 1
      for (uint32_t layer = 0; layer < 2; layer++) {
        if (w == 10) {
          if (layer) mbar_wait_sleep(park_free, 0);
          bulk_load(sb + REM, scratch + OFF_R + j * 2304, 36864, rem_full, true);
          if (layer == 0) { fetch_x(sb + PARK, j, xbar0); fetch_x(sb + PARK + STAGE, j + 1, xbar0 + 8); }
        }
        mbar_wait_sleep(rem_full, layer);
#pragma unroll 1
        for (uint32_t b = 0; b < 5; b++) {
          const uint32_t blk = sb + REM + 27648 + b * 2048, k = (w - 10) * 32 + lane_id(), rr = k & 7;
          const uint32_t dst = blk + ((k >> 3) & 1) * 1024 + rr * 128 + (((k >> 4) ^ rr) << 4);
          uint32_t v[8];
          lds4(blk + k * 16, v); lds4(blk + 1024 + k * 16, v + 4);
          asm volatile("bar.sync 3, 64;" ::: "memory");
          sts4(dst, v); sts4(dst ^ 64, v + 4);
        }
        asm volatile("fence.proxy.async.shared::cta;" ::: "memory");
        mbar_arrive(remo_full);
        if (layer) { phase2_duties(0); mbar_wait_sleep(kv_free, 0); }
        if (t > 0) {
          const uint32_t lane = lane_id(), r = lane >> 2, q = lane & 3;
#pragma unroll 1
          for (uint32_t pc = 0; pc < 3; pc++) {
            uint4* hp = scr + OFF_H + ((layer * 8 + j) * 2 + (w - 10)) * 192 + pc * 64 + lane;
            uint32_t hl[8];
            int n = 0;
            hl[4] = 1u;
            while (true) {
              ldg4(hl, hp);
              if (pc < 2) ldg4(hl + 4, hp + 32);
              if (__all_sync(~0u, hl[0] != 0u && hl[4] != 0u)) break;
              __nanosleep(100);
              SPIN_GUARD(n);
            }
            const uint32_t dst = sb + KVS + (w - 10) * 10368 + r * 144 + q * 4;
            if (pc < 2) {
#pragma unroll
              for (int g = 0; g < 8; g++) sts1(dst + pc * 20736 + odd * 16 + g * 16, hl[g]);
              stg4(hp + 32, 0u, 0u, 0u, 0u);
            } else {
              sts1(dst + (odd ? 0 : 128), hl[0]); sts1(dst + 20736 + (odd ? 0 : 128), hl[1]);
            }
            stg4(hp, 0u, 0u, 0u, 0u);
          }
        }
        asm volatile("bar.arrive 1, 192;" ::: "memory");
        mbar_wait_sleep(xb_done, layer);
        if (w == 10 && layer == 1) {
          const uint32_t lane = lane_id();
          stg4(scr + OFF_S + (lane >> 3) * 96 + j * 8 + (lane & 7), 0u, 0u, 0u, 0u);
          stg4(scr + OFF_S + (4 + (lane >> 3)) * 96 + j * 8 + (lane & 7), 0u, 0u, 0u, 0u);
          if (lane < 8) stg4(scr + OFF_S + j * 96 + 64 + lane, 0u, 0u, 0u, 0u);
        }
#pragma unroll 1
        for (uint32_t i = 0; i < 8 && (w == 11 || layer == 1); i++) {
          zero_share(scr + OFF_X + ((w - 10) * 16 + layer * 8 + i) * SLAB, j, lane_id());
          __nanosleep(500);
        }
      }
      phase2_duties(1);
    }
  } else {
    asm volatile("setmaxnreg.inc.sync.aligned.u32 240;");
    const bool lead = lane_id() == 0;
    Ring rg{0, 0};
    uint32_t prev = 0;
    uint32_t X[144];
    float rs0, rs1;
    const bool lead2 = lane_id() < 2;
    uint32_t empty_at;
    asm volatile("mapa.shared::cluster.u32 %0, %1, %2;" : "=r"(empty_at) : "r"(empty0), "r"(lane_id() & 1));
    auto release = [&](uint32_t st) { if (lead2) asm volatile("mbarrier.arrive.shared::cluster.b64 _, [%0];" :: "r"(empty_at + st * 8) : "memory"); };
    auto load_kb = [&](int kb, const uint4* src, const char* lo, uint32_t hoff) {
#pragma unroll
      for (int k = 4 * kb; k < 4 * kb + 4; k++) {
        if (k % 9 == 4) { ldg2(X + 4 * k, lo + k * 512); ldg2(X + 4 * k + 2, lo + hoff + k * 512); }
        else ldg4(X + 4 * k, src + k * 32);
      }
    };
    auto check_kb = [&](bool skip, int kb, const uint4* src, const char* lo, uint32_t hoff) {
      int n = 0;
      while (true) {
        uint32_t m = umin2(umin2(X[16 * kb], X[16 * kb + 4]), umin2(X[16 * kb + 8], X[16 * kb + 12]));
        if (kb & 1) m = umin2(m, X[16 * kb + 4 * (kb >> 1) + 2]);
        if (__all_sync(~0u, m != 0u || skip)) break;
        SPIN_GUARD(n);
        load_kb(kb, src, lo, hoff);
      }
    };
#pragma unroll 1
    for (uint32_t hf = 0; hf < 4; hf++) {
      const uint32_t layer = hf >> 1;
      const bool ffn = hf & 1;
      const uint32_t tag = 1 - layer;
      uint4* const xbase = scr + OFF_X + (layer * 8 + w) * SLAB;
      float aA[32], aB[32];
      {
        const uint32_t lane = lane_id(), r = lane >> 2, q = lane & 3;
        const uint4* src = xbase + (ffn ? 32 * SLAB : 0) + lane;
        const char* lo = (const char*)src - (ffn ? lane * 8 : 0);
        const uint32_t hoff = ffn ? 256 : 8;
        const uint32_t xoff = (w & 1) * 8192 + (16 * (w >> 1) + (lane & 15)) * 128 + (((lane >> 4) ^ (lane & 7)) << 4);
        auto load_x = [&](uint32_t b, uint32_t* d) {
#pragma unroll
          for (int i = 0; i < 4; i++) ldsm4(xs + b * STAGE + (xoff ^ (32 * i)), d[4 * i], d[4 * i + 1], d[4 * i + 2], d[4 * i + 3]);
        };
        auto load_any = [&](int kb) { if (hf == 0) load_x(kb, X + 16 * kb); else load_kb(kb, src, lo, hoff); };
        float m0, m1, v0, v1;
        STAMP(ffn * 16 + 0);
        if (hf == 0) {
          float sum[2][4] = {}, sq0[4][4] = {}, sq1[4][4] = {};
          uint32_t p0, p1;
          mbar_wait(xbar0, 0);
          ldsm4(xs + xoff, p0, p1, X[0], X[1]);
          p0 = __byte_perm(__shfl_sync(~0u, p0, lane & 28), 0, 0x1010); p1 = __byte_perm(__shfl_sync(~0u, p1, lane & 28), 0, 0x1010);
#pragma unroll 3
          for (uint32_t b = 0; b < 9; b++) {
            uint32_t d[16];
            mbar_wait(xbar0 + 8 * b, 0);
            load_x(b, d);
#pragma unroll
            for (int i = 0; i < 16; i++) d[i] = sub_bf16x2(d[i], (i & 1) ? p1 : p0);
#pragma unroll
            for (int g = 0; g < 8; g++) {
              if (!(g & 1)) mma16(sum[(g >> 1) & 1], d[2 * g], d[2 * g + 1], d[2 * g + 2], d[2 * g + 3], 0x3f803f80u, 0x3f803f80u);
              mma8(sq0[g & 3], d[2 * g], d[2 * g + 1], d[2 * g]); mma8(sq1[g & 3], d[2 * g], d[2 * g + 1], d[2 * g + 1]);
            }
          }
          STAMP(1);
          GSTAMP(14);
#pragma unroll
          for (int kb = 0; kb < GD; kb++) load_x(kb, X + 16 * kb);
          release((x_ring - empty0) / 8);
          auto tot = [](float (&c)[4][4], int e) { return (c[0][e] + c[1][e]) + (c[2][e] + c[3][e]); };
          const float a0 = (sum[0][0] + sum[1][0]) * (1.f / 576), a1 = (sum[0][2] + sum[1][2]) * (1.f / 576);
          const uint32_t dg = (lane & 28) + (r >> 1);
          v0 = fmaxf(fmaf(__shfl_sync(~0u, (r & 1) ? tot(sq0, 1) : tot(sq0, 0), dg), 1.f / 576, -a0 * a0), 0.f);
          v1 = fmaxf(fmaf(__shfl_sync(~0u, (r & 1) ? tot(sq1, 3) : tot(sq1, 2), dg), 1.f / 576, -a1 * a1), 0.f);
          m0 = bf_lo(p0) + a0; m1 = bf_lo(p1) + a1;
        } else {
          uint32_t s[3][4];
          const uint4* p = scr + OFF_S + ((ffn ? 16 : 0) + w) * 96 + q * 8 + r;
          const bool third = !ffn && q == 0;
          const uint32_t rdy = ffn ? tag : 1u;
          int n = 0;
          s[2][0] = rdy; s[2][1] = s[2][2] = s[2][3] = 0u;
          while (true) {
            ldg4(s[0], p); ldg4(s[1], p + 32);
            if (third) ldg4(s[2], p + 64);
            if (__all_sync(~0u, ((diff2(s[0][0], s[1][0], rdy) | diff2(s[1][0], s[2][0], rdy)) & 1u) == 0u)) break;
            SPIN_GUARD(n);
          }
          STAMP(ffn * 16 + 1);
          ZSTAMP(1 + ffn, 0);
          GSTAMP(14 + ffn);
#pragma unroll
          for (int kb = 0; kb < GD; kb++) load_kb(kb, src, lo, hoff);
          float t0 = 0.f, t1 = 0.f;
#pragma unroll
          for (int i = 0; i < 3; i++) { t0 += __uint_as_float(s[i][0]); t1 += __uint_as_float(s[i][2]); }
          m0 = quad_sum(t0) * (1.f / 576); m1 = quad_sum(t1) * (1.f / 576);
          const float cnt = ffn ? 72.f : 64.f, inv = ffn ? 1.f / 72 : 1.f / 64;
          v0 = 0.f; v1 = 0.f;
#pragma unroll
          for (int i = 0; i < 3; i++) {
            const float c = (i < 2 || third) ? cnt : 0.f;
            const float d0 = fmaf(__uint_as_float(s[i][0]), inv, -m0), d1 = fmaf(__uint_as_float(s[i][2]), inv, -m1);
            v0 += fmaf(d0 * d0, c, __uint_as_float(s[i][1])); v1 += fmaf(d1 * d1, c, __uint_as_float(s[i][3]));
          }
          v0 = quad_sum(v0) * (1.f / 576); v1 = quad_sum(v1) * (1.f / 576);
        }
        rs0 = rsqrtf(v0 + 1e-5f); rs1 = rsqrtf(v1 + 1e-5f);
        const uint32_t mean0 = pack_bf16(m0, m0), mean1 = pack_bf16(m1, m1);
#pragma unroll
        for (int kb = 0; kb < 9; kb++) {
          check_kb(hf == 0, kb, src, lo, hoff);
          if (kb + GD < 9) load_any(kb + GD);
          if (kb + GD == 8 && hf == 0 && lead) mbar_arrive(x_done);
#pragma unroll
          for (int i = 16 * kb; i < 16 * kb + 16; i++) X[i] = sub_bf16x2(X[i], (i & 1) ? mean1 : mean0);
          ZSTAMP(1 + ffn, 1 + 3 * kb);
          mbar_wait(full0 + rg.st * 8, rg.ph);
          ZSTAMP(1 + ffn, 2 + 3 * kb);
          const uint64_t desc = DESC_HI | ((sd + rg.st * STAGE) >> 4);
          wg_fence();
#pragma unroll
          for (int i = 0; i < 4; i++) wgmma_rs_n64(aA, X + 4 * (4 * kb + i), desc + i * 128, kb + i != 0);
          if (SPLITZ && kb == 8) { wg_commit(); wg_wait<1>(); wg_fence(); }
#pragma unroll
          for (int i = 0; i < 4; i++) wgmma_rs_n64(aB, X + 4 * (4 * kb + i), desc + 512 + i * 128, kb + i != 0);
          wg_commit();
          wg_wait<1>();
          ZSTAMP(1 + ffn, 3 + 3 * kb);
          if (kb > 0) release(prev);
          prev = rg.st; rg.next();
        }
        if (!SPLITZ) wg_wait<0>();
        ZSTAMP(1 + ffn, 28);
        ZSTAMP(4, 0);
        STAMP(ffn * 16 + 2);
      }
      if (!ffn) {
      const uint32_t lane = lane_id(), r = lane >> 2, q = lane & 3;
      const uint32_t kvrow = sb + KVS + (w & 1) * 10368 + (16 * (w >> 1)) * 144;
      uint32_t Q[18], Km[3][8], Ke[3][4];
      const bool edge = (t == 0 && w < 2);
      const uint32_t row0 = edge ? sb + KVS + 8 * 144 : kvrow + (lane & 7) * 144, row1 = kvrow + (8 + (lane & 7)) * 144;
      {
        const uint32_t dst = kvrow + (8 + r) * 144 + q * 4 + odd * 16, dstr = dst + (odd ? -16 : 128);
        const bool edge_out = w >= 6 && t < 15;
        uint4* const hp = scr + TILE + OFF_H + ((layer * 8 + j) * 2 + (w & 1)) * 192 + lane;
        auto put_kv = [&](float (&a)[32], int part) {
          pin(a);
          uint32_t hl[8];
#pragma unroll
          for (int g = 0; g < 8; g++) {
            hl[g] = pack_bf16(a[4 * g + 2] * rs1, a[4 * g + 3] * rs1);
            sts1(dst + part * 20736 + g * 16, pack_bf16(a[4 * g] * rs0, a[4 * g + 1] * rs0)); sts1(dst + part * 20736 + 8 * 144 + g * 16, hl[g]);
          }
          if (edge_out) { stg4(hp + part * 64, nz(hl[0]), hl[1], hl[2], hl[3]); stg4(hp + part * 64 + 32, nz(hl[4]), hl[5], hl[6], hl[7]); }
        };
        put_kv(aA, 0);
        wg_wait<0>();
        release(prev);
        float aR[12];
        mbar_wait(rem_full, layer);
        const uint64_t dr = DESC_REM | ((sd + REM) >> 4);
        wg_fence();
#pragma unroll
        for (int s = 0; s < 36; s++) {
          wgmma_rs_n24(aR, X + 4 * s, dr + s * 16, s != 0);
          if (s == 4) put_kv(aB, 1);
        }
        wg_commit();
#pragma unroll
        for (int kb = 0; kb < 9; kb++) {
          if (kb == HOFF1 && w < 4) asm volatile("bar.sync 4, 256;" ::: "memory");
          if (kb == 8 && HOFF1 < 9 && w >= 4) asm volatile("bar.arrive 4, 256;" ::: "memory");
          if (!(kb & 1)) mbar_wait(full0 + rg.st * 8, rg.ph);
          const uint64_t desc = DESC_HI | ((sd + rg.st * STAGE + (kb & 1) * 8192) >> 4);
          wg_fence();
#pragma unroll
          for (int i = 0; i < 4; i++) wgmma_rs_n64(aB, X + 4 * (4 * kb + i), desc + i * 128, kb + i != 0);
          wg_commit();
          wg_wait<1>();
          if (kb > 0 && !(kb & 1)) release(prev);
          if ((kb & 1) || kb == 8) { prev = rg.st; rg.next(); }
          if (kb == 0) {
            pin(aR);
            const uint32_t k1 = pack_bf16(aR[2] * rs1, aR[3] * rs1), v1 = pack_bf16(aR[6] * rs1, aR[7] * rs1);
            if (edge_out) stg4(hp + 128, nz(k1), v1, 0u, 0u);
            sts1(dstr, pack_bf16(aR[0] * rs0, aR[1] * rs0)); sts1(dstr + 8 * 144, k1);
            sts1(dstr + 20736, pack_bf16(aR[4] * rs0, aR[5] * rs0)); sts1(dstr + 20736 + 8 * 144, v1);
            Q[16] = pack_bf16(aR[8], aR[9]); Q[17] = pack_bf16(aR[10], aR[11]);
            if (w < 4) asm volatile("bar.arrive 2, 256;" ::: "memory");
          }
          if (kb == KLD - 2) mbar_wait(remo_full, layer);
          if (kb == KLD) {
            if (w < 4) asm volatile("bar.sync 1, 192;" ::: "memory");
            else asm volatile("bar.sync 2, 256;" ::: "memory");
#pragma unroll
            for (int nt = 0; nt < 3; nt++) {
              const uint32_t ra = (nt == 0 ? row0 : row1 + (nt - 1) * 8 * 144);
              ldsm4(ra + odd * 16 + (lane >> 3) * 16, Km[nt][0], Km[nt][1], Km[nt][2], Km[nt][3]);
              ldsm4(ra + odd * 16 + 64 + (lane >> 3) * 16, Km[nt][4], Km[nt][5], Km[nt][6], Km[nt][7]);
              ldsm4(ra + (odd ? 0 : 32) + (lane >> 3) * 32, Ke[nt][0], Ke[nt][1], Ke[nt][2], Ke[nt][3]);
            }
            const uint32_t ge = (2u << q) - 1, le = 0xfu << q, on = edge ? 0u : ~0u;
            const uint32_t bits = odd ? 0xfu | ((le & 0xfu) << 4) | (ge << 8) : ge | 0xf0u | (le << 8);
#pragma unroll
            for (int h = 0; h < 4; h++) {
              const uint32_t ma = bitmask(bits, h), mb = bitmask(bits, 4 + h), mc = bitmask(bits, 8 + h);
              Km[0][2 * h] &= ma & on; Km[0][2 * h + 1] &= mb & on; Ke[0][h] &= mc & on;
#pragma unroll
              for (int nt = 1; nt < 3; nt++) { Km[nt][2 * h] &= ma; Km[nt][2 * h + 1] &= mb; Ke[nt][h] &= mc; }
            }
          }
        }
        wg_wait<0>();
        release(prev);
        pin(aB);
        STAMP(3);
#pragma unroll
        for (int i = 0; i < 16; i++) Q[i] = pack_bf16(aB[2 * i], aB[2 * i + 1]);
      }
      uint32_t res[18] = {};
      if (layer) {
        const uint4* p = xbase + ((9 * j + 1) >> 1) * 32 + lane;
#pragma unroll
        for (int i = 0; i < 4; i++) ldg4(res + 4 * i, p + i * 32);
        ldg2(res + 16, odd ? (const char*)(p - 32) + 8 : (const char*)(p + 4 * 32));
      }
      {
        uint32_t V01[12][2], V2[12];
        const uint32_t rv = ((lane & 8) ? row1 : row0) + 20736, rw = row1 + 8 * 144 + 20736;
#pragma unroll
        for (int i = 0; i < 4; i++) ldsm4t(rv + odd * 16 + i * 32 + (lane >> 4) * 16, V01[2 * i][0], V01[2 * i][1], V01[2 * i + 1][0], V01[2 * i + 1][1]);
#pragma unroll
        for (int i = 0; i < 2; i++) ldsm4t(rv + (odd ? 0 : 32) + i * 64 + (lane >> 4) * 32, V01[8 + 2 * i][0], V01[8 + 2 * i][1], V01[9 + 2 * i][0], V01[9 + 2 * i][1]);
        ldsm4t(rw + odd * 16 + (lane >> 3) * 16, V2[0], V2[1], V2[2], V2[3]);
        ldsm4t(rw + odd * 16 + 64 + (lane >> 3) * 16, V2[4], V2[5], V2[6], V2[7]);
        ldsm4t(rw + (odd ? 0 : 32) + (lane >> 3) * 32, V2[8], V2[9], V2[10], V2[11]);
        const bool up0 = 2 * q > r, up1 = 2 * q + 1 > r;
        const uint32_t upm = (up0 ? 0xffffu : 0u) | (up1 ? 0xffff0000u : 0u);
        const float c0 = 0.23570226039551584f * 1.4426950408889634f * rs0, c1 = 0.23570226039551584f * 1.4426950408889634f * rs1;
        const float masked = edge ? -1e9f * 1.4426950408889634f * rcp(c0) : 0.f;
        uint32_t Om[16], Oe[8];
#pragma unroll
        for (int h = 0; h < 4; h++) {
          const uint32_t e0 = odd ? Q[(4 * h + 16) % 18] : Q[4 * h + 4], e1 = odd ? Q[(4 * h + 17) % 18] : Q[4 * h + 5];
          float S[3][4];
#pragma unroll
          for (int nt = 0; nt < 3; nt++) {
            mma16c(S[nt], Q + 4 * h, Km[nt][2 * h], Km[nt][2 * h + 1], nt == 0 ? masked : 0.f);
            mma8(S[nt], e0, e1, Ke[nt][h]);
          }
          const float s00 = up0 ? S[0][0] : S[1][0], s01 = up1 ? S[0][1] : S[1][1];
          const float s10 = up0 ? S[1][2] : S[2][2], s11 = up1 ? S[1][3] : S[2][3];
          const float m0 = quad_max(fmaxf(s00, s01)) * c0, m1 = quad_max(fmaxf(s10, s11)) * c1;
          const float p00 = ex2(fmaf(s00, c0, -m0)), p01 = ex2(fmaf(s01, c0, -m0)), p10 = ex2(fmaf(s10, c1, -m1)), p11 = ex2(fmaf(s11, c1, -m1));
          const float i0 = rcp(quad_sum(p00 + p01)), i1 = rcp(quad_sum(p10 + p11));
          const uint32_t p0 = pack_bf16(p00 * i0, p01 * i0), p1 = pack_bf16(p10 * i1, p11 * i1);
          const uint32_t pf[4] = {p0 & upm, 0u, p0 & ~upm, p1 & upm};
#pragma unroll
          for (int gi = 0; gi < 3; gi++) {
            const int g = gi < 2 ? 2 * h + gi : 8 + h;
            float o[4];
            mma16c(o, pf, V01[g][0], V01[g][1], 0.f);
            mma8(o, 0u, p1 & ~upm, V2[g]);
            uint32_t* d = gi < 2 ? Om + 2 * g : Oe + 2 * h;
            d[0] = pack_bf16(o[0], o[1]); d[1] = pack_bf16(o[2], o[3]);
          }
        }
#pragma unroll
        for (int h = 0; h < 4; h++)
#pragma unroll
          for (int e = 0; e < 2; e++) {
            if (h > 0 && !odd && q < h) Om[4 * h + e] = Oe[2 * h - 2 + e];
            if (h < 3 && odd && q > h) Om[4 * h + 2 + e] = Oe[2 * h + 2 + e];
          }
        STAMP(4);
        if (j >= PRI && lane == 0) asm volatile("st.relaxed.gpu.global.b32 [%0], %1;" :: "l"(scr + OFF_S + (8 + w) * 96 + j * 8), "r"(tag) : "memory");
        put72(xbase + 16 * SLAB, j, lane, Om, odd ? Oe[0] : Oe[6], odd ? Oe[1] : Oe[7]);
      }
      if (j < PRI && lane == 0) asm volatile("st.relaxed.gpu.global.b32 [%0], %1;" :: "l"(scr + OFF_S + (8 + w) * 96 + j * 8), "r"(tag) : "memory");
      {
        if (layer == 0) {
          const uint32_t xrow = (w & 1) * 8192 + (16 * (w >> 1) + (lane & 15)) * 128;
          uint32_t u0, u1;
          mbar_wait(xbar0, 1); mbar_wait(xbar0 + 8, 1);
#pragma unroll
          for (int i = 0; i < 5; i++) {
            const uint32_t g = i < 4 ? j + odd + 2 * i : j + (odd ? 0 : 8);
            const uint32_t a = sb + PARK + (g >> 3) * STAGE + xrow;
            if (i < 4) ldsm4(a + ((((g & 7) + (lane >> 4)) ^ (lane & 7)) << 4), res[4 * i], res[4 * i + 1], res[4 * i + 2], res[4 * i + 3]);
            else ldsm4(a + (((g & 7) ^ (lane & 7)) << 4), res[16], res[17], u0, u1);
          }
        }
        const uint4* src = xbase + 16 * SLAB + lane;
        {
          const uint4* fp = scr + OFF_S + (8 + w) * 96 + (lane & 7) * 8;
          int n = 0;
          STAMP(8);
          while (true) {
            uint32_t f;
            asm volatile("ld.relaxed.gpu.global.b32 %0, [%1];" : "=r"(f) : "l"(fp) : "memory");
            if (__all_sync(~0u, f == tag)) break;
            SPIN_GUARD(n);
          }
          STAMP(9);
        }
        if (HOFF3 < 9 && w < 4) asm volatile("bar.sync 6, 256;" ::: "memory");
#pragma unroll
        for (int kb = 0; kb < GO; kb++) load_kb(kb, src, (const char*)src - lane * 8, 256);
        float acc[36];
#pragma unroll
        for (int i = 0; i < 18; i++) { acc[2 * i] = bf_lo(res[i]); acc[2 * i + 1] = bf_hi(res[i]); }
#pragma unroll
        for (int kb = 0; kb < 9; kb++) {
          check_kb(false, kb, src, (const char*)src - lane * 8, 256);
          if (kb + GO < 9) load_kb(kb + GO, src, (const char*)src - lane * 8, 256);
          if (kb == HOFF3 && w >= 4) asm volatile("bar.arrive 6, 256;" ::: "memory");
          if (!(kb & 1)) mbar_wait(full0 + rg.st * 8, rg.ph);
          const uint32_t base = sd + rg.st * STAGE + (kb & 1) * 8192;
          const uint64_t d0 = DESC_HI | ((base >> 4) + (((sd + REM + 27648 + (kb >> 1) * 2048 + (kb & 1) * 64 - base) >> 4) << 16));
          wg_fence();
#pragma unroll
          for (int i = 0; i < 4; i++) wgmma_rs_n72(acc, X + 4 * (4 * kb + i), d0 - (uint64_t)(i * ((127u << 16) - 128u)), 1);
          wg_commit();
          wg_wait<1>();
          if (kb > 0 && !(kb & 1)) release(prev);
          if ((kb & 1) || kb == 8) { prev = rg.st; rg.next(); }
        }
        wg_wait<0>();
        release(prev);
        pin(acc);
        STAMP(10);
#pragma unroll
        for (int i = 0; i < 18; i++) res[i] = pack_bf16(acc[2 * i], acc[2 * i + 1]);
        if (j < PRI) put72(xbase + 32 * SLAB, j, lane, res, res[16], res[17]);
        publish_stats<9>(scr + OFF_S + (16 + w) * 96 + j * 8, acc, tag, lane);
        if (j >= PRI) put72(xbase + 32 * SLAB, j, lane, res, res[16], res[17]);
      }
      continue;
      }
      const uint32_t hp = sb + PARK + w * 512 + lane_id() * 16;
      auto pack8 = [&](float (&a)[32], int p, uint32_t* o) {
#pragma unroll
        for (int e = 0; e < 8; e++) asm volatile("" : "+f"(a[8 * p + e]) :: "memory");
#pragma unroll
        for (int e = 0; e < 4; e++) o[e] = pack_bf16(a[8 * p + 2 * e], a[8 * p + 2 * e + 1]);
      };
      const float ka0 = 0.7978845608028654f * rs0, kb0 = 0.044715f * ka0 * rs0 * rs0, ku0 = 0.5f * rs0 * rs0;
      const float ka1 = 0.7978845608028654f * rs1, kb1 = 0.044715f * ka1 * rs1 * rs1, ku1 = 0.5f * rs1 * rs1;
      auto packu8 = [&](int p, uint32_t* o) {
#pragma unroll
        for (int e = 0; e < 8; e++) asm volatile("" : "+f"(aA[8 * p + e]) :: "memory");
#pragma unroll
        for (int e = 0; e < 4; e++) o[e] = pack_bf16(aA[8 * p + 2 * e] * ((e & 1) ? ku1 : ku0), aA[8 * p + 2 * e + 1] * ((e & 1) ? ku1 : ku0));
      };
      auto geglu8 = [&](int p, uint32_t* u) {
#pragma unroll
        for (int e = 0; e < 8; e++) asm volatile("" : "+f"(aB[8 * p + e]) :: "memory");
        float h[8];
#pragma unroll
        for (int e = 0; e < 8; e++) {
          const float g = aB[8 * p + e];
          h[e] = fmaf(g, tanh_ap(g * fmaf(g * g, (e & 2) ? kb1 : kb0, (e & 2) ? ka1 : ka0)), g);
        }
#pragma unroll
        for (int e = 0; e < 4; e++) u[e] = mul_bf16x2(pack_bf16(h[2 * e], h[2 * e + 1]), u[e]);
      };
      auto box = [&](int b, auto&& filler) {
        const int kb = b < 9 ? b : b - 9;
        if (!(b & 1)) { if ((TRAPB >> (b >> 1)) & 1) mbar_wait_trap(full0 + rg.st * 8, rg.ph); else mbar_wait(full0 + rg.st * 8, rg.ph); }
        const uint64_t desc = DESC_HI | ((sd + rg.st * STAGE + (b & 1) * 8192) >> 4);
        wg_fence();
#pragma unroll
        for (int i = 0; i < 4; i++) {
          if (b < 9) wgmma_rs_n64(aA, X + 4 * (4 * kb + i), desc + i * 128, kb + i != 0);
          else wgmma_rs_n64(aB, X + 4 * (4 * kb + i), desc + i * 128, kb + i != 0);
          if (i == FPOS) filler();
        }
        wg_commit();
        if (b & 1) { prev = rg.st; rg.next(); } else { wg_wait<1>(); release(prev); }
      };
      auto nop = [] {};
      auto step = [&](int st, auto&& filler) { box(2 * st, nop); box(2 * st + 1, filler); };
#pragma unroll
      for (int p = 0; p < 4; p++) { uint32_t o[4]; packu8(p, o); sts4(hp + p * 4096, o); }
      box(0, nop);
      if (lead) mbar_arrive(xb_done);
#pragma unroll 1
      for (int c = 1;; c++) {
        const uint32_t hc = hp + c * 4 * 4096;
#pragma unroll
        for (int b = 1; b < 18; b++) box(b, [&] {
          if ((b & 1) && b < 8) { uint32_t o[4]; const uint32_t a = hc - (4 - (b >> 1)) * 4096; lds4(a, o); geglu8(b >> 1, o); sts4(a, o); }
          if ((b & 1) && b > 10) { uint32_t o[4]; packu8((b - 11) >> 1, o); if (c < 8) sts4(hc + ((b - 11) >> 1) * 4096, o); } });
        ZSTAMP(4, c);
        if (c == 8) break;
        box(0, nop);
      }
      wg_wait<0>();
      STAMP(21);
      GSTAMP(19);
      auto unpark = [&](int kb) {
#pragma unroll
        for (int s = 4 * kb; s < 4 * kb + 4; s++) lds4(hp + s * 4096, X + 4 * s);
      };
      unpark(0);
      uint32_t U[16];
#pragma unroll
      for (int p = 0; p < 4; p++) packu8(p, U + 4 * p);
#pragma unroll
      for (int b = 0; b < 8; b++) box(b, [&] {
        if (b < 7) unpark(b + 1);
        if (b & 1) {
          geglu8(b >> 1, U + 2 * (b - 1));
          if (rg.ph > 1) sts4(hp, U + 2 * (b - 1));
#pragma unroll
          for (int i = 0; i < 4; i++) X[128 + 2 * (b - 1) + i] = U[2 * (b - 1) + i];
        } });
      STAMP(24);
      if (layer == 0 && lead) mbar_arrive(park_free);
      const uint32_t lane2 = lane_id();
      uint4* const pw = scr + OFF_P + (j * 8 + w) * SLAB + lane2;
      const uint4* const pr = scr + OFF_P + w * SLAB + 4 * j * 32 + lane2;
      auto put_part = [&](float (&a)[32], int p, uint32_t chunk) {
        uint32_t o[4];
        pack8(a, p, o);
        stg4(pw + (chunk * 4 + p) * 32, (o[0] & ~1u) | tag, o[1], o[2], o[3]);
      };
      uint4* const xb = xbase + 32 * SLAB + 4 * j * 32;
      auto slot = [&](int p) { return sb + w * 2048 + (p < 3 ? PARK + p * 16384 : KVS + (p - 3) * 16384); };
      auto fetch = [&](int p) {
        bulk_load(slot(p), p ? scr + OFF_P + (((j - p) & 7) * 8 + w) * SLAB + 4 * j * 32 : xb, 2048, p ? pbar0 + w * 8 : res_full, true);
      };
#pragma unroll 1
      for (int sp = 0;; sp++) {
        const uint32_t ca = sp == 0 ? 8 : ((j + 2 * sp) & 7), cb = (j + 2 * sp + 1) & 7;
        if (C8 == 1 && sp == 1 && lead) mbar_arrive(c8_go);
#pragma unroll
        for (int st = 4; st < 9; st++) step(st, [&] {
          if (st == 5 || st == 6) { put_part(aA, 2 * (st - 5), ca); put_part(aA, 2 * (st - 5) + 1, ca); }
          if (st == 8 && sp > 0) { if (sp == 3) mbar_wait(c8_done, layer); fetch(2 * sp - 2); } });
        STAMP(25 + sp);
        if (sp == 3) break;
        if (C8 == 0 && sp == 0 && lead) mbar_arrive(c8_go);
#pragma unroll
        for (int st = 0; st < 4; st++) step(st, [&] {
          if (st < 2) { put_part(aB, 2 * st, cb); put_part(aB, 2 * st + 1, cb); }
          if (st == 3 && sp > 0) fetch(2 * sp - 1); });
      }
      auto load_p = [&](int p, uint32_t* d) {
#pragma unroll
        for (int i = 0; i < 4; i++) ldg4(d + 4 * i, pr + ((j - p) & 7) * 8 * SLAB + i * 32);
      };
#pragma unroll
      for (int b = 0; b < 9; b++) {
        if (b == HOFF2 && w < 4) asm volatile("bar.sync 5, 256;" ::: "memory");
        box(b, [&] {
          if (b == 1) {
#pragma unroll
            for (int p = 0; p < 4; p++) put_part(aB, p, (j + 7) & 7);
          }
          if (b == 3) { load_p(5, X); load_p(6, X + 16); }
          if (b == 7 && EXP != 1) load_p(7, X + 32); });
        if (b == 7 && HOFF2 < 9 && w >= 4) asm volatile("bar.arrive 5, 256;" ::: "memory");
      }
      mbar_wait(res_full, layer);
      mbar_wait(pbar0 + w * 8, layer);
#pragma unroll
      for (int p = 1; p < 5; p++)
#pragma unroll
        for (int i = 0; i < 4; i++) lds4(slot(p) + lane2 * 16 + i * 512, X + 48 + 16 * p + 4 * i);
#pragma unroll
      for (int i = 0; i < 4; i++) {
        const bool split = j == 2 * i + 1;
        const uint32_t a = slot(0) + i * 512 + (split ? lane2 * 8 : lane2 * 16);
        lds2(a, X + 48 + 4 * i); lds2(a + (split ? 256 : 8), X + 50 + 4 * i);
      }
      wg_wait<0>();
      release(rg.st); rg.next();
      pin(aA);
      STAMP(22);
      GSTAMP(20);
      {
        const uint32_t lane = lane2, r = lane >> 2, q = lane & 3;
        const uint32_t eye = r == 2 * q ? 0x3f80u : r == 2 * q + 1 ? 0x3f800000u : 0u;
        auto bad = [&](const uint32_t* d) { return diff2(d[0], d[4], tag) | diff2(d[8], d[12], tag); };
        auto add = [&](const uint32_t* d) {
#pragma unroll
          for (int g = 0; g < 8; g++) mma8(aA + 4 * g, d[2 * g], d[2 * g + 1], eye);
        };
        int n = 0;
        while (!__all_sync(~0u, ((or3(bad(X), bad(X + 16), bad(X + 64)) | or3(bad(X + 80), bad(X + 96), bad(X + 112))) & 1u) == 0u)) {
          SPIN_GUARD(n);
          load_p(5, X); load_p(6, X + 16);
#pragma unroll
          for (int p = 1; p < 5; p++) load_p(p, X + 48 + 16 * p);
        }
        add(X); add(X + 16);
#pragma unroll
        for (int p = 4; p >= 0; p--) add(X + 48 + 16 * ((p + 1) % 5));
        STAMP(11);
        if (EXP != 1) while (!__all_sync(~0u, (bad(X + 32) & 1u) == 0u)) { SPIN_GUARD(n); load_p(7, X + 32); }
        add(X + 32);
        STAMP(12);
        uint32_t res[16];
#pragma unroll
        for (int i = 0; i < 16; i++) res[i] = pack_bf16(aA[2 * i], aA[2 * i + 1]);
        if (layer == 0) {
          uint4* p = xbase + 8 * SLAB + 4 * j * 32 + lane;
          auto put = [&] {
#pragma unroll
            for (int i = 0; i < 4; i++) stg4(p + i * 32, nz(res[4 * i]), res[4 * i + 1], nz(res[4 * i + 2]), res[4 * i + 3]);
          };
          if (j < PRI) put();
          publish_stats<8>(scr + OFF_S + w * 96 + j * 8, aA, 1u, lane);
          if (j >= PRI) put();
          if (lane == 0) mbar_arrive(kv_free);
        } else {
          const uint32_t tb = slot(0);
          __syncwarp();
#pragma unroll
          for (int i = 0; i < 4; i++) {
            const uint32_t row = (lane2 & 7) + (lane2 & 8), g = 2 * i + (lane2 >> 4);
            asm volatile("stmatrix.sync.aligned.m8n8.x4.shared.b16 [%0], {%1,%2,%3,%4};"
                         :: "r"(tb + row * 128 + ((g ^ (row & 7)) << 4)), "r"(res[4 * i]), "r"(res[4 * i + 1]), "r"(res[4 * i + 2]), "r"(res[4 * i + 3]) : "memory");
          }
          __syncwarp();
#pragma unroll
          for (int i = 0; i < 4; i++) {
            const uint32_t row = 4 * i + (lane2 >> 3), g = lane2 & 7;
            uint32_t v[4];
            lds4(tb + row * 128 + ((g ^ (row & 7)) << 4), v);
            *(uint4*)(out + (128 * t + 32 * (w >> 1) + 2 * row + (w & 1)) * 576 + 64 * j + 8 * g) = make_uint4(v[0], v[1], v[2], v[3]);
          }
        }
      }
      STAMP(23);
    }
  }
}

typedef CUresult (*EncodeFn)(CUtensorMap*, CUtensorMapDataType, cuuint32_t, void*, const cuuint64_t*, const cuuint64_t*,
                             const cuuint32_t*, const cuuint32_t*, CUtensorMapInterleave, CUtensorMapSwizzle,
                             CUtensorMapL2promotion, CUtensorMapFloatOOBfill);

CUtensorMap make_map(EncodeFn f, const void* p, uint64_t cols, uint64_t rows, bool rem = false) {
  CUtensorMap m;
  cuuint64_t dims[2] = {cols, rows};
  cuuint64_t str[1] = {cols * 2};
  cuuint32_t box[2] = {rem ? 8u : 64u, rem ? 144u : 64u};
  cuuint32_t es[2] = {1, 1};
  f(&m, CU_TENSOR_MAP_DATA_TYPE_BFLOAT16, 2, const_cast<void*>(p), dims, str, box, es, CU_TENSOR_MAP_INTERLEAVE_NONE,
    rem ? CU_TENSOR_MAP_SWIZZLE_NONE : CU_TENSOR_MAP_SWIZZLE_128B, CU_TENSOR_MAP_L2_PROMOTION_NONE, CU_TENSOR_MAP_FLOAT_OOB_FILL_NONE);
  return m;
}

}

extern "C" void kernel_launch(void* const* d_in, const int* in_sizes, int n_in, void* d_out, int out_size) {
  void* fn = nullptr;
  cudaDriverEntryPointQueryResult qr;
  cudaGetDriverEntryPoint("cuTensorMapEncodeTiled", &fn, cudaEnableDefault, &qr);
  EncodeFn enc = (EncodeFn)fn;
  Maps maps;
  maps.m[0] = make_map(enc, d_in[1], 1728, 576); maps.m[1] = make_map(enc, d_in[2], 576, 576);
  maps.m[2] = make_map(enc, d_in[4], 4608, 576); maps.m[3] = make_map(enc, d_in[5], 4608, 576); maps.m[4] = make_map(enc, d_in[6], 576, 4608);
  maps.m[5] = make_map(enc, d_in[1], 1728, 576, true); maps.m[6] = make_map(enc, d_in[2], 576, 576, true);
  {
    cuuint64_t dims[3] = {576, 1024, 2}, str[2] = {2304, 1152};
    cuuint32_t box[3] = {64, 64, 2}, es[3] = {1, 1, 1};
    enc(&maps.m[7], CU_TENSOR_MAP_DATA_TYPE_BFLOAT16, 3, d_in[0], dims, str, box, es, CU_TENSOR_MAP_INTERLEAVE_NONE,
        CU_TENSOR_MAP_SWIZZLE_128B, CU_TENSOR_MAP_L2_PROMOTION_NONE, CU_TENSOR_MAP_FLOAT_OOB_FILL_NONE);
  }
  void* scr = nullptr;
  cudaGetSymbolAddress(&scr, g_scratch);
  cudaFuncSetAttribute(mega_kernel, cudaFuncAttributeMaxDynamicSharedMemorySize, SMEM_BYTES);
  cudaLaunchConfig_t cfg = {};
  cfg.gridDim = dim3(128); cfg.blockDim = dim3(384); cfg.dynamicSmemBytes = SMEM_BYTES; cfg.stream = cudaStreamPerThread;
  cudaLaunchAttribute at[1];
  at[0].id = cudaLaunchAttributeClusterDimension; at[0].val.clusterDim.x = 2; at[0].val.clusterDim.y = 1; at[0].val.clusterDim.z = 1;
  cfg.attrs = at; cfg.numAttrs = 1;
  int dev = 0, sms = 0, clusters = 0;
  cudaGetDevice(&dev);
  cudaDeviceGetAttribute(&sms, cudaDevAttrMultiProcessorCount, dev);
  cudaOccupancyMaxActiveClusters(&clusters, mega_kernel, &cfg);
  if (sms == 132 && clusters == 66) cfg.gridDim = dim3(132);
  cudaLaunchKernelEx(&cfg, mega_kernel, maps, (uint4*)scr, (__nv_bfloat16*)d_out);
}
```

```cpp
#include <cuda_runtime.h>
#include <cuda.h>
#include <cuda_bf16.h>
#include <stdint.h>

#define TRACE 0
#define GUARD 0
#define TRAPB 1
#define HOFF1 99
#define HOFF2 99
#define KLD 8
#define ZT 0
#define SLEEP 500
#define SPLITZ 1
#define C8 1
#define GO 3
#define EXP 0
#define FPOS 2

namespace {

constexpr int NST = 6;
constexpr int STAGE = 16384;
constexpr int PARK = NST * STAGE;
constexpr int REM = PARK + 49152;
constexpr int KVS = REM + 40960;
constexpr int PIECE = PARK + 7 * STAGE;
constexpr int HSTG = KVS + 16384;
constexpr int BARS = KVS + 41472;
constexpr int TRC = BARS + 512;
constexpr int SMEM_BYTES = TRC + (TRACE ? 512 : 0);
static_assert(NST == 6, "the producer addresses empty barriers as full + 48");
static_assert(BARS >= PARK + 131072, "barriers overlap park");
static_assert(SMEM_BYTES <= 232448, "smem");

constexpr int SLAB = 36 * 32;
constexpr int SPIN_MAX = 1 << 17;
constexpr uint32_t PRI = 3;
constexpr int GD = 3;
constexpr int OFF_S = 0;
constexpr int OFF_H = OFF_S + 3 * 8 * 96;
constexpr int OFF_X = OFF_H + 2 * 8 * 384;
constexpr int OFF_P = OFF_X + 6 * 8 * SLAB;
constexpr int TILE = OFF_P + 8 * 8 * SLAB;
constexpr int OFF_R = 16 * TILE;
constexpr int OFF_F = OFF_R + 8 * 2304;
constexpr int SCRATCH = OFF_F + 128 * 8;

}

__device__ uint4 g_scratch[SCRATCH];

namespace {

constexpr uint64_t DESC_HI = 0x4000004000000000ull;
constexpr uint64_t DESC_REM = (576ull << 32) | (8u << 16);
__device__ __forceinline__ void wgmma_rs_n64(float (&d)[32], const uint32_t* a, uint64_t desc, int scale_d) {
  asm volatile("{\n.reg .pred p;\nsetp.ne.b32 p, %37, 0;\n"
    "wgmma.mma_async.sync.aligned.m64n64k16.f32.bf16.bf16 "
    "{%0, %1, %2, %3, %4, %5, %6, %7, %8, %9, %10, %11, %12, %13, %14, %15, %16, %17, %18, %19, %20, %21, %22, %23, %24, %25, %26, %27, %28, %29, %30, %31}, "
    "{%32, %33, %34, %35}, %36, p, 1, 1, 1;\n}\n"
    : "+f"(d[0]), "+f"(d[1]), "+f"(d[2]), "+f"(d[3]), "+f"(d[4]), "+f"(d[5]), "+f"(d[6]), "+f"(d[7]), "+f"(d[8]), "+f"(d[9]), "+f"(d[10]), "+f"(d[11]), "+f"(d[12]), "+f"(d[13]), "+f"(d[14]), "+f"(d[15]), "+f"(d[16]), "+f"(d[17]), "+f"(d[18]), "+f"(d[19]), "+f"(d[20]), "+f"(d[21]), "+f"(d[22]), "+f"(d[23]), "+f"(d[24]), "+f"(d[25]), "+f"(d[26]), "+f"(d[27]), "+f"(d[28]), "+f"(d[29]), "+f"(d[30]), "+f"(d[31])
    : "r"(a[0]), "r"(a[1]), "r"(a[2]), "r"(a[3]), "l"(desc), "r"(scale_d));
}
__device__ __forceinline__ void wgmma_rs_n72(float (&d)[36], const uint32_t* a, uint64_t desc, int scale_d) {
  asm volatile("{\n.reg .pred p;\nsetp.ne.b32 p, %41, 0;\n"
    "wgmma.mma_async.sync.aligned.m64n72k16.f32.bf16.bf16 "
    "{%0, %1, %2, %3, %4, %5, %6, %7, %8, %9, %10, %11, %12, %13, %14, %15, %16, %17, %18, %19, %20, %21, %22, %23, %24, %25, %26, %27, %28, %29, %30, %31, %32, %33, %34, %35}, "
    "{%36, %37, %38, %39}, %40, p, 1, 1, 1;\n}\n"
    : "+f"(d[0]), "+f"(d[1]), "+f"(d[2]), "+f"(d[3]), "+f"(d[4]), "+f"(d[5]), "+f"(d[6]), "+f"(d[7]), "+f"(d[8]), "+f"(d[9]), "+f"(d[10]), "+f"(d[11]), "+f"(d[12]), "+f"(d[13]), "+f"(d[14]), "+f"(d[15]), "+f"(d[16]), "+f"(d[17]), "+f"(d[18]), "+f"(d[19]), "+f"(d[20]), "+f"(d[21]), "+f"(d[22]), "+f"(d[23]), "+f"(d[24]), "+f"(d[25]), "+f"(d[26]), "+f"(d[27]), "+f"(d[28]), "+f"(d[29]), "+f"(d[30]), "+f"(d[31]), "+f"(d[32]), "+f"(d[33]), "+f"(d[34]), "+f"(d[35])
    : "r"(a[0]), "r"(a[1]), "r"(a[2]), "r"(a[3]), "l"(desc), "r"(scale_d));
}
__device__ __forceinline__ void wgmma_rs_n24(float (&d)[12], const uint32_t* a, uint64_t desc, int scale_d) {
  asm volatile("{\n.reg .pred p;\nsetp.ne.b32 p, %17, 0;\n"
    "wgmma.mma_async.sync.aligned.m64n24k16.f32.bf16.bf16 "
    "{%0, %1, %2, %3, %4, %5, %6, %7, %8, %9, %10, %11}, "
    "{%12, %13, %14, %15}, %16, p, 1, 1, 1;\n}\n"
    : "+f"(d[0]), "+f"(d[1]), "+f"(d[2]), "+f"(d[3]), "+f"(d[4]), "+f"(d[5]), "+f"(d[6]), "+f"(d[7]), "+f"(d[8]), "+f"(d[9]), "+f"(d[10]), "+f"(d[11])
    : "r"(a[0]), "r"(a[1]), "r"(a[2]), "r"(a[3]), "l"(desc), "r"(scale_d));
}

__device__ __forceinline__ void mbar_init(uint32_t a, uint32_t c) { asm volatile("mbarrier.init.shared::cta.b64 [%0], %1;" :: "r"(a), "r"(c)); }
__device__ __forceinline__ void mbar_arrive(uint32_t a) { asm volatile("mbarrier.arrive.shared::cta.b64 _, [%0];" :: "r"(a) : "memory"); }
__device__ __forceinline__ void mbar_wait_trap(uint32_t a, uint32_t ph) {
  asm volatile("{\n.reg .pred p;\n.reg .u32 n;\nmov.u32 n, 0;\n"
               "W: mbarrier.try_wait.parity.shared::cta.b64 p, [%0], %1;\n@p bra D;\n"
               "add.u32 n, n, 1;\nsetp.lt.u32 p, n, 4194304;\n@p bra W;\ntrap;\nD:\n}" :: "r"(a), "r"(ph) : "memory");
}
__device__ __forceinline__ void mbar_wait(uint32_t a, uint32_t ph) {
  asm volatile("{\n.reg .pred p;\nW: mbarrier.try_wait.parity.shared::cta.b64 p, [%0], %1;\n@!p bra W;\n}" :: "r"(a), "r"(ph) : "memory");
}
__device__ __forceinline__ void mbar_wait_sleep(uint32_t a, uint32_t ph) {
  asm volatile("{\n.reg .pred p;\nW: mbarrier.test_wait.parity.shared::cta.b64 p, [%0], %1;\n@p bra D;\nnanosleep.u32 %2;\nbra W;\nD:\n}" :: "r"(a), "r"(ph), "n"(SLEEP) : "memory");
}
__device__ __forceinline__ void wg_fence() { asm volatile("wgmma.fence.sync.aligned;" ::: "memory"); }
__device__ __forceinline__ void wg_commit() { asm volatile("wgmma.commit_group.sync.aligned;" ::: "memory"); }
template <int N> __device__ __forceinline__ void wg_wait() { asm volatile("wgmma.wait_group.sync.aligned %0;" :: "n"(N) : "memory"); }
__device__ __forceinline__ float tanh_ap(float x) { float y; asm("tanh.approx.f32 %0, %1;" : "=f"(y) : "f"(x)); return y; }
__device__ __forceinline__ float ex2(float x) { float y; asm("ex2.approx.ftz.f32 %0, %1;" : "=f"(y) : "f"(x)); return y; }
__device__ __forceinline__ uint32_t pack_bf16(float lo, float hi) { uint32_t r; asm("cvt.rn.bf16x2.f32 %0, %1, %2;" : "=r"(r) : "f"(hi), "f"(lo)); return r; }
__device__ __forceinline__ float bf_lo(uint32_t v) { return __uint_as_float(v << 16); }
__device__ __forceinline__ float bf_hi(uint32_t v) { return __uint_as_float(v & 0xffff0000u); }
__device__ __forceinline__ uint32_t sub_bf16x2(uint32_t a, uint32_t b) { uint32_t r; asm("sub.rn.bf16x2 %0, %1, %2;" : "=r"(r) : "r"(a), "r"(b)); return r; }
__device__ __forceinline__ uint32_t mul_bf16x2(uint32_t a, uint32_t b) { uint32_t r; asm("mul.rn.bf16x2 %0, %1, %2;" : "=r"(r) : "r"(a), "r"(b)); return r; }
__device__ __forceinline__ uint32_t diff2(uint32_t a, uint32_t b, uint32_t t) { uint32_t r; asm("lop3.b32 %0, %1, %2, %3, 0x7e;" : "=r"(r) : "r"(a), "r"(b), "r"(t)); return r; }
__device__ __forceinline__ uint32_t or3(uint32_t a, uint32_t b, uint32_t c) { uint32_t r; asm("lop3.b32 %0, %1, %2, %3, 0xfe;" : "=r"(r) : "r"(a), "r"(b), "r"(c)); return r; }
__device__ __forceinline__ uint32_t umin2(uint32_t a, uint32_t b) { uint32_t r; asm("min.u32 %0, %1, %2;" : "=r"(r) : "r"(a), "r"(b)); return r; }
__device__ __forceinline__ uint32_t bitmask(uint32_t v, int bit) { uint32_t r; asm("bfe.s32 %0, %1, %2, 1;" : "=r"(r) : "r"(v), "r"(bit)); return r; }
__device__ __forceinline__ uint32_t nz(uint32_t w) { return w == 0u ? 0x8000u : w; }

__device__ __forceinline__ void ldg4(uint32_t* d, const uint4* p) {
  asm volatile("ld.relaxed.gpu.global.v4.b32 {%0,%1,%2,%3}, [%4];" : "=r"(d[0]), "=r"(d[1]), "=r"(d[2]), "=r"(d[3]) : "l"(p) : "memory");
}
__device__ __forceinline__ void ldg2(uint32_t* d, const void* p) {
  asm volatile("ld.relaxed.gpu.global.v2.b32 {%0,%1}, [%2];" : "=r"(d[0]), "=r"(d[1]) : "l"(p) : "memory");
}
__device__ __forceinline__ void stg4(uint4* p, uint32_t a, uint32_t b, uint32_t c, uint32_t d) {
  asm volatile("st.relaxed.gpu.global.v4.b32 [%0], {%1,%2,%3,%4};" :: "l"(p), "r"(a), "r"(b), "r"(c), "r"(d) : "memory");
}
__device__ __forceinline__ void stg2(void* p, uint32_t a, uint32_t b) {
  asm volatile("st.relaxed.gpu.global.v2.b32 [%0], {%1,%2};" :: "l"(p), "r"(a), "r"(b) : "memory");
}
__device__ __forceinline__ void sts4(uint32_t a, const uint32_t* o) { asm volatile("st.shared.v4.b32 [%0], {%1,%2,%3,%4};" :: "r"(a), "r"(o[0]), "r"(o[1]), "r"(o[2]), "r"(o[3]) : "memory"); }
__device__ __forceinline__ void lds4(uint32_t a, uint32_t* o) { asm volatile("ld.shared.v4.b32 {%0,%1,%2,%3}, [%4];" : "=r"(o[0]), "=r"(o[1]), "=r"(o[2]), "=r"(o[3]) : "r"(a) : "memory"); }
__device__ __forceinline__ void lds2(uint32_t a, uint32_t* o) { asm volatile("ld.shared.v2.b32 {%0,%1}, [%2];" : "=r"(o[0]), "=r"(o[1]) : "r"(a) : "memory"); }
__device__ __forceinline__ float rcp(float x) { float y; asm("rcp.approx.ftz.f32 %0, %1;" : "=f"(y) : "f"(x)); return y; }
__device__ __forceinline__ void sts1(uint32_t a, uint32_t v) { asm volatile("st.shared.b32 [%0], %1;" :: "r"(a), "r"(v) : "memory"); }
__device__ __forceinline__ void ldsm4(uint32_t a, uint32_t& r0, uint32_t& r1, uint32_t& r2, uint32_t& r3) {
  asm volatile("ldmatrix.sync.aligned.m8n8.x4.shared.b16 {%0,%1,%2,%3}, [%4];" : "=r"(r0), "=r"(r1), "=r"(r2), "=r"(r3) : "r"(a) : "memory");
}
__device__ __forceinline__ void ldsm4t(uint32_t a, uint32_t& r0, uint32_t& r1, uint32_t& r2, uint32_t& r3) {
  asm volatile("ldmatrix.sync.aligned.m8n8.x4.trans.shared.b16 {%0,%1,%2,%3}, [%4];" : "=r"(r0), "=r"(r1), "=r"(r2), "=r"(r3) : "r"(a) : "memory");
}
__device__ __forceinline__ void mma16(float* c, uint32_t a0, uint32_t a1, uint32_t a2, uint32_t a3, uint32_t b0, uint32_t b1) {
  asm("mma.sync.aligned.m16n8k16.row.col.f32.bf16.bf16.f32 {%0,%1,%2,%3}, {%4,%5,%6,%7}, {%8,%9}, {%0,%1,%2,%3};"
    : "+f"(c[0]), "+f"(c[1]), "+f"(c[2]), "+f"(c[3]) : "r"(a0), "r"(a1), "r"(a2), "r"(a3), "r"(b0), "r"(b1));
}
__device__ __forceinline__ void mma16c(float* d, const uint32_t* a, uint32_t b0, uint32_t b1, float c01) {
  asm("mma.sync.aligned.m16n8k16.row.col.f32.bf16.bf16.f32 {%0,%1,%2,%3}, {%4,%5,%6,%7}, {%8,%9}, {%10,%10,%10,%10};"
    : "=f"(d[0]), "=f"(d[1]), "=f"(d[2]), "=f"(d[3]) : "r"(a[0]), "r"(a[1]), "r"(a[2]), "r"(a[3]), "r"(b0), "r"(b1), "f"(c01));
}
__device__ __forceinline__ void mma8(float* c, uint32_t a0, uint32_t a1, uint32_t b0) {
  asm("mma.sync.aligned.m16n8k8.row.col.f32.bf16.bf16.f32 {%0,%1,%2,%3}, {%4,%5}, {%6}, {%0,%1,%2,%3};"
    : "+f"(c[0]), "+f"(c[1]), "+f"(c[2]), "+f"(c[3]) : "r"(a0), "r"(a1), "r"(b0));
}
__device__ __forceinline__ uint32_t lane_id() { uint32_t l; asm volatile("mov.u32 %0, %%laneid;" : "=r"(l)); return l; }
__device__ __forceinline__ float quad_sum(float v) { v += __shfl_xor_sync(~0u, v, 1); v += __shfl_xor_sync(~0u, v, 2); return v; }
__device__ __forceinline__ float quad_max(float v) { v = fmaxf(v, __shfl_xor_sync(~0u, v, 1)); v = fmaxf(v, __shfl_xor_sync(~0u, v, 2)); return v; }
template <int N> __device__ __forceinline__ void pin(float (&d)[N]) {
#pragma unroll
  for (int i = 0; i < N; i++) asm volatile("" : "+f"(d[i]) :: "memory");
}
#define SPIN_GUARD(n) if (++(n) > SPIN_MAX) break

template <int NG> __device__ __forceinline__ void publish_stats(uint4* dst, const float* y, uint32_t tag, uint32_t lane) {
  float s0 = 0.f, s1 = 0.f;
#pragma unroll
  for (int g = 0; g < NG; g++) { s0 += y[4 * g] + y[4 * g + 1]; s1 += y[4 * g + 2] + y[4 * g + 3]; }
  s0 = quad_sum(s0); s1 = quad_sum(s1);
  const float m0 = s0 * (1.f / (8 * NG)), m1 = s1 * (1.f / (8 * NG));
  float q0 = 0.f, q1 = 0.f, q2 = 0.f, q3 = 0.f;
#pragma unroll
  for (int g = 0; g < NG; g++) {
    const float a = y[4 * g] - m0, b = y[4 * g + 1] - m0, c = y[4 * g + 2] - m1, d = y[4 * g + 3] - m1;
    q0 = fmaf(a, a, q0); q1 = fmaf(b, b, q1); q2 = fmaf(c, c, q2); q3 = fmaf(d, d, q3);
  }
  q0 = quad_sum(q0 + q1); q2 = quad_sum(q2 + q3);
  if ((lane & 3) == 0)
    stg4(dst + (lane >> 2), (__float_as_uint(s0) & ~1u) | tag, __float_as_uint(q0), __float_as_uint(s1), __float_as_uint(q2));
}

__device__ __forceinline__ void put72(uint4* slab, uint32_t j, uint32_t lane, const uint32_t* v, uint32_t r0, uint32_t r1) {
  uint4* p = slab + ((9 * j + 1) >> 1) * 32;
#pragma unroll
  for (int i = 0; i < 4; i++) stg4(p + lane + i * 32, nz(v[4 * i]), v[4 * i + 1], v[4 * i + 2], v[4 * i + 3]);
  stg2((char*)((j & 1) ? p - 16 : p + 4 * 32) + lane * 8, nz(r0), r1);
}
__device__ __forceinline__ void zero_share(uint4* slab, uint32_t j, uint32_t lane) {
  uint4* p = slab + j * 144 + lane;
#pragma unroll
  for (int i = 0; i < 4; i++) stg4(p + i * 32, 0u, 0u, 0u, 0u);
  if (lane < 16) stg4(p + 128, 0u, 0u, 0u, 0u);
}

struct Maps { CUtensorMap m[8]; };

struct Ring {
  uint32_t st, ph;
  __device__ __forceinline__ void next() { if (++st == NST) { st = 0; ph ^= 1; } }
};

#define GSTAMP(i) do {} while (0)
#define STAMP(i) do {} while (0)
#define ZSTAMP(m, i) do {} while (0)

__device__ __forceinline__ void tma_box(uint32_t dst, const CUtensorMap* m, int col, int row, uint32_t bar, uint32_t expect) {
  asm volatile("{\n.reg .pred e, h;\nelect.sync _|e, 0xffffffff;\nsetp.ne.and.u32 h, %5, 0, e;\n"
               "@h mbarrier.arrive.expect_tx.shared::cta.b64 _, [%2], %5;\n"
               "@e cp.async.bulk.tensor.2d.shared::cluster.global.mbarrier::complete_tx::bytes [%0], [%1, {%3, %4}], [%2];\n}"
               :: "r"(dst), "l"(m), "r"(bar), "r"(col), "r"(row), "r"(expect) : "memory");
}

__device__ __forceinline__ void bulk_load(uint32_t dst, const void* src, uint32_t bytes, uint32_t bar, bool arm) {
  asm volatile("{\n.reg .pred e, h;\nelect.sync _|e, 0xffffffff;\nsetp.ne.and.u32 h, %4, 0, e;\n"
               "@h mbarrier.arrive.expect_tx.shared::cta.b64 _, [%3], %2;\n"
               "@e cp.async.bulk.shared::cluster.global.mbarrier::complete_tx::bytes [%0], [%1], %2, [%3];\n}"
               :: "r"(dst), "l"(src), "r"(bytes), "r"(bar), "r"((uint32_t)arm) : "memory");
}

__global__ void __launch_bounds__(384, 1) mega_kernel(
    const __grid_constant__ Maps maps, uint4* __restrict__ scratch,
    __nv_bfloat16* __restrict__ out) {
  extern __shared__ __align__(1024) uint8_t smem[];
  const uint32_t sb = (uint32_t)__cvta_generic_to_shared(smem);
  const uint32_t full0 = sb + BARS, empty0 = full0 + 8 * NST, rem_full = empty0 + 8 * NST, park_free = rem_full + 8, kv_free = park_free + 8;
  const uint32_t c8_go = kv_free + 8, c8_done = c8_go + 8, c8_full = c8_done + 8, remo_full = c8_full + 8, piece_full = remo_full + 8, xb_done = piece_full + 8, res_full = xb_done + 8, pbar0 = res_full + 8;
  const uint32_t x_done = pbar0 + 64, x_ring = x_done + 8, xbar0 = x_ring + 8;
  const uint32_t w = __shfl_sync(~0u, threadIdx.x >> 5, 0);
  uint32_t pair = blockIdx.x >> 1;
  if (gridDim.x == 132) {
    uint32_t smid;
    asm("mov.u32 %0, %%smid;" : "=r"(smid));
    const uint32_t tpc = smid >> 1;
    if (tpc == 60 || tpc == 61) { if (threadIdx.x == 0) { __nanosleep(20000); } return; }
    pair = tpc < 32 ? tpc : tpc >= 62 ? (tpc - 58) * 8 : 33 + (tpc - 32) / 7 * 8 + (tpc - 32) % 7;
  }
  const uint32_t rank = blockIdx.x & 1, t = (pair & 7) * 2 + rank, j = pair >> 3;
  const uint32_t sd = sb & 0x3ffff;
  const uint32_t odd = j & 1;
  uint4* const scr = scratch + t * TILE;
  const uint32_t xs = sb + (NST - 2) * STAGE;
  auto fetch_x = [&](uint32_t dst, uint32_t b, uint32_t bar) {
    asm volatile("{\n.reg .pred e;\nelect.sync _|e, 0xffffffff;\n@e mbarrier.arrive.expect_tx.shared::cta.b64 _, [%2], 16384;\n"
                 "@e cp.async.bulk.tensor.3d.shared::cluster.global.mbarrier::complete_tx::bytes [%0], [%1, {%3, %4, 0}], [%2];\n}"
                 :: "r"(dst), "l"(&maps.m[7]), "r"(bar), "r"(64 * b), "r"(64 * t) : "memory");
  };
  if (threadIdx.x == 256) {
    for (int i = 0; i < 9; i++) mbar_init(xbar0 + 8 * i, 1);
    mbar_init(piece_full, 1);
    asm volatile("fence.mbarrier_init.release.cluster;" ::: "memory");
  }
  if (threadIdx.x == 288) {
    for (int i = 0; i < NST; i++) { mbar_init(full0 + 8 * i, 1); mbar_init(empty0 + 8 * i, 16); }
    mbar_init(x_done, 8); mbar_init(x_ring, 16);
    asm volatile("fence.mbarrier_init.release.cluster;" ::: "memory");
  }
  if (threadIdx.x == 320) {
    mbar_init(rem_full, 1); mbar_init(park_free, 8); mbar_init(kv_free, 8); mbar_init(c8_go, 8); mbar_init(c8_done, 2); mbar_init(c8_full, 1);
    mbar_init(remo_full, 64); mbar_init(xb_done, 8); mbar_init(res_full, 8);
    for (int i = 0; i < 8; i++) mbar_init(pbar0 + 8 * i, 4);
    asm volatile("fence.mbarrier_init.release.cluster;" ::: "memory");
  }
  if (threadIdx.x == 352) {
    asm volatile("prefetch.tensormap [%0];" :: "l"(&maps.m[7]) : "memory");
    asm volatile("prefetch.tensormap [%0];" :: "l"(&maps.m[0]) : "memory");
  }
  __syncwarp();
  asm volatile("barrier.cluster.arrive.relaxed.aligned;" ::: "memory");
  if (w != 8) asm volatile("barrier.cluster.wait.aligned;" ::: "memory");

  if (w >= 8) {
    asm volatile("setmaxnreg.dec.sync.aligned.u32 24;");
    if (w == 8) {
#pragma unroll 1
      for (uint32_t b = 0; b < 9; b++) fetch_x(xs + b * STAGE, b, xbar0 + 8 * b);
      tma_box(sb + PIECE, &maps.m[t >= 12 ? 6 : 5], 72 * j + (odd ? 0 : 64) + (t < 8 ? 576 * ((t >> 2) + 1) : 0), 144 * (t & 3), piece_full, 2304);
      asm volatile("barrier.cluster.wait.aligned;" ::: "memory");
      uint32_t dst = sb, bar = full0, ph = 1;
#pragma unroll 1
      for (int seg = 0; seg < 34; seg++) {
        const int n = seg >= 17 ? seg - 17 : seg;
        int ma, mb, ca, cb, row = 0;
        if (n < 3) { ma = mb = n == 2; ca = 72 * j + 8 * odd + (n == 0 ? 576 : 0); cb = ca + 576; }
        else if (n < 12) { ma = 3; mb = 2; ca = cb = 576 * j + 64 * (n - 3); }
        else { ma = mb = 4; ca = n == 12 ? 512 : ((j + 2 * n) & 7) * 64; cb = ((j + 2 * n + 1) & 7) * 64; row = 576 * j; }
        const bool zip = n == 0 || n == 3, solo = n == 1 || n == 2 || n == 16;
        const CUtensorMap *pa = &maps.m[ma], *pb = &maps.m[mb];
#pragma unroll 1
        for (int st = 0; st < (solo ? 5 : 9); st++) {
          if (seg == 0 && st == NST - 2) mbar_wait(x_ring, 0);
          const bool s0 = !zip && st > 4, s1 = zip || st >= 4;
          const int r0 = row + (zip ? 64 * st : s0 ? 128 * st - 576 : 128 * st), r1 = zip ? r0 : st == 4 ? row : r0 + 64;
          const bool rk = rank, sm = rk ? s1 : s0;
          asm volatile("{\n.reg .pred p, e, f;\n.reg .u32 n;\nelect.sync _|e, 0xffffffff;\nsetp.ne.and.u32 f, %7, 0, e;\nmov.u32 n, 0;\n"
                       "W: mbarrier.try_wait.parity.shared::cta.b64 p, [%1+48], %2;\n@p bra D;\n"
                       "add.u32 n, n, 1;\nsetp.lt.u32 p, n, 4194304;\n@p bra W;\ntrap;\n"
                       "D: @e mbarrier.arrive.expect_tx.shared::cta.b64 _, [%1], %6;\n"
                       "@f cp.async.bulk.tensor.2d.shared::cluster.global.mbarrier::complete_tx::bytes.multicast::cluster [%0], [%3, {%4, %5}], [%1], 3;\n}"
                       :: "r"(dst + rk * 8192), "r"(bar), "r"(ph), "l"(sm ? pb : pa), "r"(sm ? cb : ca), "r"(rk ? r1 : r0),
                          "r"(solo && st == 4 ? STAGE / 2 : STAGE), "r"((uint32_t)!(rk && solo && st == 4)) : "memory");
          dst += STAGE; bar += 8;
          if (bar == full0 + 8 * NST) { dst = sb; bar = full0; ph ^= 1; }
        }
      }
      {
#pragma unroll 1
        for (int i = 0; i < NST; i++) {
          mbar_wait_trap(bar + 48, ph);
          bar += 8;
          if (bar == full0 + 8 * NST) { bar = full0; ph ^= 1; }
        }
      }
    } else if (w == 9) {
      const uint32_t lane = lane_id();
      const uint32_t stg = sb + HSTG + lane * 16;
      uint32_t fph = 0;
#pragma unroll 1
      for (uint32_t layer = 0; layer < 2; layer++) {
        uint4* xb = scr + OFF_X + ((4 + layer) * 8 + j) * SLAB + 32 * 32;
        mbar_wait_sleep(c8_go, layer);
        int n = 0;
        while (true) {
          if (lane == 0) asm volatile("mbarrier.arrive.expect_tx.shared::cta.b64 _, [%0], 18432;" :: "r"(c8_full) : "memory");
          __syncwarp();
#pragma unroll 1
          for (uint32_t s = 0; s < 9; s++)
            bulk_load(sb + HSTG + s * 2048, s < 8 ? scr + OFF_P + (j + s * 8) * SLAB + 32 * 32 : xb, 2048, c8_full, false);
          mbar_wait(c8_full, fph); fph ^= 1;
          uint32_t bad = 0;
#pragma unroll 8
          for (int s = 0; s < 32; s++) { uint32_t v; asm volatile("ld.shared.b32 %0, [%1];" : "=r"(v) : "r"(stg + s * 512) : "memory"); bad |= v ^ (1 - layer); }
          if (__all_sync(~0u, (bad & 1u) == 0u)) break;
          __nanosleep(300);
          SPIN_GUARD(n);
        }
        asm volatile("bar.arrive 7, 96;" ::: "memory");
        float s0 = 0.f, s1 = 0.f;
#pragma unroll 1
        for (int g = 0; g < 8; g++) {
          const uint32_t a = stg + (g >> 1) * 512 + (g & 1) * 8;
          float a0 = 0.f, a1 = 0.f, a2 = 0.f, a3 = 0.f;
#pragma unroll 1
          for (int b = 0; b < 3; b++) {
            uint32_t v[6];
#pragma unroll
            for (int s = 0; s < 3; s++) lds2(a + (3 * b + s) * 2048, v + 2 * s);
#pragma unroll
            for (int s = 0; s < 3; s++) { a0 += bf_lo(v[2 * s]); a1 += bf_hi(v[2 * s]); a2 += bf_lo(v[2 * s + 1]); a3 += bf_hi(v[2 * s + 1]); }
          }
          sts1(a + 18432, pack_bf16(a0, a1)); sts1(a + 18436, pack_bf16(a2, a3));
          s0 += a0 + a1; s1 += a2 + a3;
        }
        __syncwarp();
        if (lane == 0) mbar_arrive(c8_done);
        s0 = quad_sum(s0); s1 = quad_sum(s1);
        float q0 = 0.f, q1 = 0.f;
        const uint32_t ln = lane_id();
#pragma unroll 1
        for (uint32_t i = 0; i < 4; i++) {
          uint32_t x[4];
          lds4(stg + 18432 + i * 512, x);
          stg4(xb + i * 32 + ln, 0u, 0u, 0u, 0u);
          if (layer == 0) {
            stg4(xb - 3 * 8 * SLAB + i * 32 + ln, nz(x[0]), x[1], x[2], x[3]);
#pragma unroll
            for (int e = 0; e < 4; e++) {
              const float m = (e & 1) ? s1 : s0, c = fmaf(m, -1.f / 64, bf_lo(x[e])), d = fmaf(m, -1.f / 64, bf_hi(x[e]));
              if (e & 1) q1 = fmaf(c, c, fmaf(d, d, q1)); else q0 = fmaf(c, c, fmaf(d, d, q0));
            }
          } else {
            uint32_t* o = (uint32_t*)(out + (128 * t + 32 * (j >> 1) + 2 * (ln >> 2) + (j & 1)) * 576 + 512 + 16 * i + 2 * (ln & 3));
            o[0] = x[0]; o[8 * 576] = x[1]; o[4] = x[2]; o[8 * 576 + 4] = x[3];
          }
        }
        if (layer == 0) {
          q0 = quad_sum(q0); q1 = quad_sum(q1);
          if ((ln & 3) == 0) stg4(scr + OFF_S + j * 96 + 64 + (ln >> 2), __float_as_uint(s0) | 1u, __float_as_uint(q0), __float_as_uint(s1), __float_as_uint(q1));
        }
      }
    } else {
      auto mark = [&](uint32_t k0, uint32_t v) {
        const uint32_t lane = lane_id();
#pragma unroll 1
        for (uint32_t k = k0; k < 6; k++) stg4(scr + OFF_S + (k * 4 + (lane >> 3)) * 96 + j * 8 + (lane & 7), k < 2 ? 0u : v, 0u, 0u, 0u);
      };
      if (w == 11) mark(2, 0u);
      auto phase2_duties = [&](uint32_t layer) {
        const uint32_t lane = lane_id();
        asm volatile("bar.sync 7, 96;" ::: "memory");
        if (w == 11) {
          if (layer == 0) mark(0, 1u);
          __syncwarp();
          if (lane == 0) mbar_arrive(c8_done);
        }
        mbar_wait_sleep(res_full, layer);
#pragma unroll 1
        for (uint32_t i = 0; i < 4; i++) {
          uint4* z = scr + OFF_X + ((4 + layer) * 8 + (w - 10) * 4 + i) * SLAB + 4 * j * 32 + lane;
#pragma unroll
          for (int k = 0; k < 4; k++) stg4(z + k * 32, 0u, 0u, 0u, 0u);
          __nanosleep(300);
        }
      };
      if (w == 10) {
        const uint32_t lane = lane_id();
        uint32_t* fl = (uint32_t*)(scratch + OFF_F + (t * 8 + j) * 8) + (lane & 15);
        uint32_t v;
        asm volatile("ld.relaxed.gpu.global.b32 %0, [%1];" : "=r"(v) : "l"(fl) : "memory");
        mbar_wait(piece_full, 0);
        asm volatile("{\n.reg .pred e;\nelect.sync _|e, 0xffffffff;\n@e cp.async.bulk.global.shared::cta.bulk_group [%0], [%1], 2304;\n}\n"
                     "cp.async.bulk.commit_group;\ncp.async.bulk.wait_group 0;\nfence.proxy.async;"
                     :: "l"(scratch + OFF_R + j * 2304 + t * 144), "r"(sb + PIECE) : "memory");
        __syncwarp();
        if (lane < 16) asm volatile("st.release.gpu.global.b32 [%0], 1;" :: "l"((uint32_t*)(scratch + OFF_F + (lane_id() * 8 + j) * 8) + t) : "memory");
        int n = 0;
        while (!__all_sync(~0u, v != 0u)) {
          __nanosleep(100);
          SPIN_GUARD(n);
          asm volatile("ld.relaxed.gpu.global.b32 %0, [%1];" : "=r"(v) : "l"(fl) : "memory");
        }
        asm volatile("st.relaxed.gpu.global.b32 [%0], 0;" :: "l"(fl) : "memory");
        mbar_wait(x_done, 0);
      }
#pragma unroll 1
      for (uint32_t layer = 0; layer < 2; layer++) {
        if (w == 10) {
          if (layer) mbar_wait_sleep(park_free, 0);
          bulk_load(sb + REM, scratch + OFF_R + j * 2304, 36864, rem_full, true);
          if (layer == 0) { fetch_x(sb + PARK, j, xbar0); fetch_x(sb + PARK + STAGE, j + 1, xbar0 + 8); }
        }
        mbar_wait_sleep(rem_full, layer);
#pragma unroll 1
        for (uint32_t b = 0; b < 5; b++) {
          const uint32_t blk = sb + REM + 27648 + b * 2048, k = (w - 10) * 32 + lane_id(), rr = k & 7;
          const uint32_t dst = blk + ((k >> 3) & 1) * 1024 + rr * 128 + (((k >> 4) ^ rr) << 4);
          uint32_t v[8];
          lds4(blk + k * 16, v); lds4(blk + 1024 + k * 16, v + 4);
          asm volatile("bar.sync 3, 64;" ::: "memory");
          sts4(dst, v); sts4(dst ^ 64, v + 4);
        }
        asm volatile("fence.proxy.async.shared::cta;" ::: "memory");
        mbar_arrive(remo_full);
        if (layer) { phase2_duties(0); mbar_wait_sleep(kv_free, 0); }
        if (t > 0) {
          const uint32_t lane = lane_id(), r = lane >> 2, q = lane & 3;
#pragma unroll 1
          for (uint32_t pc = 0; pc < 3; pc++) {
            uint4* hp = scr + OFF_H + ((layer * 8 + j) * 2 + (w - 10)) * 192 + pc * 64 + lane;
            uint32_t hl[8];
            int n = 0;
            hl[4] = 1u;
            while (true) {
              ldg4(hl, hp);
              if (pc < 2) ldg4(hl + 4, hp + 32);
              if (__all_sync(~0u, hl[0] != 0u && hl[4] != 0u)) break;
              __nanosleep(100);
              SPIN_GUARD(n);
            }
            const uint32_t dst = sb + KVS + (w - 10) * 10368 + r * 144 + q * 4;
            if (pc < 2) {
#pragma unroll
              for (int g = 0; g < 8; g++) sts1(dst + pc * 20736 + odd * 16 + g * 16, hl[g]);
              stg4(hp + 32, 0u, 0u, 0u, 0u);
            } else {
              sts1(dst + (odd ? 0 : 128), hl[0]); sts1(dst + 20736 + (odd ? 0 : 128), hl[1]);
            }
            stg4(hp, 0u, 0u, 0u, 0u);
          }
        }
        asm volatile("bar.arrive 1, 192;" ::: "memory");
        mbar_wait_sleep(xb_done, layer);
        if (w == 10 && layer == 1) {
          const uint32_t lane = lane_id();
          stg4(scr + OFF_S + (lane >> 3) * 96 + j * 8 + (lane & 7), 0u, 0u, 0u, 0u);
          stg4(scr + OFF_S + (4 + (lane >> 3)) * 96 + j * 8 + (lane & 7), 0u, 0u, 0u, 0u);
          if (lane < 8) stg4(scr + OFF_S + j * 96 + 64 + lane, 0u, 0u, 0u, 0u);
        }
#pragma unroll 1
        for (uint32_t i = 0; i < 8 && (w == 11 || layer == 1); i++) {
          zero_share(scr + OFF_X + ((w - 10) * 16 + layer * 8 + i) * SLAB, j, lane_id());
          __nanosleep(500);
        }
      }
      phase2_duties(1);
    }
  } else {
    asm volatile("setmaxnreg.inc.sync.aligned.u32 240;");
    const bool lead = lane_id() == 0;
    Ring rg{0, 0};
    uint32_t prev = 0;
    uint32_t X[144];
    float rs0, rs1;
    const bool lead2 = lane_id() < 2;
    uint32_t empty_at;
    asm volatile("mapa.shared::cluster.u32 %0, %1, %2;" : "=r"(empty_at) : "r"(empty0), "r"(lane_id() & 1));
    auto release = [&](uint32_t st) { if (lead2) asm volatile("mbarrier.arrive.shared::cluster.b64 _, [%0];" :: "r"(empty_at + st * 8) : "memory"); };
    auto load_kb = [&](int kb, const uint4* src, const char* lo, uint32_t hoff) {
#pragma unroll
      for (int k = 4 * kb; k < 4 * kb + 4; k++) {
        if (k % 9 == 4) { ldg2(X + 4 * k, lo + k * 512); ldg2(X + 4 * k + 2, lo + hoff + k * 512); }
        else ldg4(X + 4 * k, src + k * 32);
      }
    };
    auto check_kb = [&](bool skip, int kb, const uint4* src, const char* lo, uint32_t hoff) {
      int n = 0;
      while (true) {
        uint32_t m = umin2(umin2(X[16 * kb], X[16 * kb + 4]), umin2(X[16 * kb + 8], X[16 * kb + 12]));
        if (kb & 1) m = umin2(m, X[16 * kb + 4 * (kb >> 1) + 2]);
        if (__all_sync(~0u, m != 0u || skip)) break;
        SPIN_GUARD(n);
        load_kb(kb, src, lo, hoff);
      }
    };
#pragma unroll 1
    for (uint32_t hf = 0; hf < 4; hf++) {
      const uint32_t layer = hf >> 1;
      const bool ffn = hf & 1;
      const uint32_t tag = 1 - layer;
      uint4* const xbase = scr + OFF_X + (layer * 8 + w) * SLAB;
      float aA[32], aB[32];
      {
        const uint32_t lane = lane_id(), r = lane >> 2, q = lane & 3;
        const uint4* src = xbase + (ffn ? 32 * SLAB : 0) + lane;
        const char* lo = (const char*)src - (ffn ? lane * 8 : 0);
        const uint32_t hoff = ffn ? 256 : 8;
        const uint32_t xoff = (w & 1) * 8192 + (16 * (w >> 1) + (lane & 15)) * 128 + (((lane >> 4) ^ (lane & 7)) << 4);
        auto load_x = [&](uint32_t b, uint32_t* d) {
#pragma unroll
          for (int i = 0; i < 4; i++) ldsm4(xs + b * STAGE + (xoff ^ (32 * i)), d[4 * i], d[4 * i + 1], d[4 * i + 2], d[4 * i + 3]);
        };
        auto load_any = [&](int kb) { if (hf == 0) load_x(kb, X + 16 * kb); else load_kb(kb, src, lo, hoff); };
        float m0, m1, v0, v1;
        STAMP(ffn * 16 + 0);
        if (hf == 0) {
          float sum[2][4] = {}, sq0[4][4] = {}, sq1[4][4] = {};
          uint32_t p0, p1;
          mbar_wait(xbar0, 0);
          ldsm4(xs + xoff, p0, p1, X[0], X[1]);
          p0 = __byte_perm(__shfl_sync(~0u, p0, lane & 28), 0, 0x1010); p1 = __byte_perm(__shfl_sync(~0u, p1, lane & 28), 0, 0x1010);
#pragma unroll 3
          for (uint32_t b = 0; b < 9; b++) {
            uint32_t d[16];
            mbar_wait(xbar0 + 8 * b, 0);
            load_x(b, d);
#pragma unroll
            for (int i = 0; i < 16; i++) d[i] = sub_bf16x2(d[i], (i & 1) ? p1 : p0);
#pragma unroll
            for (int g = 0; g < 8; g++) {
              if (!(g & 1)) mma16(sum[(g >> 1) & 1], d[2 * g], d[2 * g + 1], d[2 * g + 2], d[2 * g + 3], 0x3f803f80u, 0x3f803f80u);
              mma8(sq0[g & 3], d[2 * g], d[2 * g + 1], d[2 * g]); mma8(sq1[g & 3], d[2 * g], d[2 * g + 1], d[2 * g + 1]);
            }
          }
          STAMP(1);
          GSTAMP(14);
#pragma unroll
          for (int kb = 0; kb < GD; kb++) load_x(kb, X + 16 * kb);
          release((x_ring - empty0) / 8);
          auto tot = [](float (&c)[4][4], int e) { return (c[0][e] + c[1][e]) + (c[2][e] + c[3][e]); };
          const float a0 = (sum[0][0] + sum[1][0]) * (1.f / 576), a1 = (sum[0][2] + sum[1][2]) * (1.f / 576);
          const uint32_t dg = (lane & 28) + (r >> 1);
          v0 = fmaxf(fmaf(__shfl_sync(~0u, (r & 1) ? tot(sq0, 1) : tot(sq0, 0), dg), 1.f / 576, -a0 * a0), 0.f);
          v1 = fmaxf(fmaf(__shfl_sync(~0u, (r & 1) ? tot(sq1, 3) : tot(sq1, 2), dg), 1.f / 576, -a1 * a1), 0.f);
          m0 = bf_lo(p0) + a0; m1 = bf_lo(p1) + a1;
        } else {
          uint32_t s[3][4];
          const uint4* p = scr + OFF_S + ((ffn ? 16 : 0) + w) * 96 + q * 8 + r;
          const bool third = !ffn && q == 0;
          const uint32_t rdy = ffn ? tag : 1u;
          int n = 0;
          s[2][0] = rdy; s[2][1] = s[2][2] = s[2][3] = 0u;
          while (true) {
            ldg4(s[0], p); ldg4(s[1], p + 32);
            if (third) ldg4(s[2], p + 64);
            if (__all_sync(~0u, ((diff2(s[0][0], s[1][0], rdy) | diff2(s[1][0], s[2][0], rdy)) & 1u) == 0u)) break;
            SPIN_GUARD(n);
          }
          STAMP(ffn * 16 + 1);
          ZSTAMP(1 + ffn, 0);
          GSTAMP(14 + ffn);
#pragma unroll
          for (int kb = 0; kb < GD; kb++) load_kb(kb, src, lo, hoff);
          float t0 = 0.f, t1 = 0.f;
#pragma unroll
          for (int i = 0; i < 3; i++) { t0 += __uint_as_float(s[i][0]); t1 += __uint_as_float(s[i][2]); }
          m0 = quad_sum(t0) * (1.f / 576); m1 = quad_sum(t1) * (1.f / 576);
          const float cnt = ffn ? 72.f : 64.f, inv = ffn ? 1.f / 72 : 1.f / 64;
          v0 = 0.f; v1 = 0.f;
#pragma unroll
          for (int i = 0; i < 3; i++) {
            const float c = (i < 2 || third) ? cnt : 0.f;
            const float d0 = fmaf(__uint_as_float(s[i][0]), inv, -m0), d1 = fmaf(__uint_as_float(s[i][2]), inv, -m1);
            v0 += fmaf(d0 * d0, c, __uint_as_float(s[i][1])); v1 += fmaf(d1 * d1, c, __uint_as_float(s[i][3]));
          }
          v0 = quad_sum(v0) * (1.f / 576); v1 = quad_sum(v1) * (1.f / 576);
        }
        rs0 = rsqrtf(v0 + 1e-5f); rs1 = rsqrtf(v1 + 1e-5f);
        const uint32_t mean0 = pack_bf16(m0, m0), mean1 = pack_bf16(m1, m1);
#pragma unroll
        for (int kb = 0; kb < 9; kb++) {
          check_kb(hf == 0, kb, src, lo, hoff);
          if (kb + GD < 9) load_any(kb + GD);
          if (kb + GD == 8 && hf == 0 && lead) mbar_arrive(x_done);
#pragma unroll
          for (int i = 16 * kb; i < 16 * kb + 16; i++) X[i] = sub_bf16x2(X[i], (i & 1) ? mean1 : mean0);
          ZSTAMP(1 + ffn, 1 + 3 * kb);
          mbar_wait(full0 + rg.st * 8, rg.ph);
          ZSTAMP(1 + ffn, 2 + 3 * kb);
          const uint64_t desc = DESC_HI | ((sd + rg.st * STAGE) >> 4);
          wg_fence();
#pragma unroll
          for (int i = 0; i < 4; i++) wgmma_rs_n64(aA, X + 4 * (4 * kb + i), desc + i * 128, kb + i != 0);
          if (SPLITZ && kb == 8) { wg_commit(); wg_wait<1>(); wg_fence(); }
#pragma unroll
          for (int i = 0; i < 4; i++) wgmma_rs_n64(aB, X + 4 * (4 * kb + i), desc + 512 + i * 128, kb + i != 0);
          wg_commit();
          wg_wait<1>();
          ZSTAMP(1 + ffn, 3 + 3 * kb);
          if (kb > 0) release(prev);
          prev = rg.st; rg.next();
        }
        if (!SPLITZ) wg_wait<0>();
        ZSTAMP(1 + ffn, 28);
        ZSTAMP(4, 0);
        STAMP(ffn * 16 + 2);
      }
      if (!ffn) {
      const uint32_t lane = lane_id(), r = lane >> 2, q = lane & 3;
      const uint32_t kvrow = sb + KVS + (w & 1) * 10368 + (16 * (w >> 1)) * 144;
      uint32_t Q[18], Km[3][8], Ke[3][4];
      const bool edge = (t == 0 && w < 2);
      const uint32_t row0 = edge ? sb + KVS + 8 * 144 : kvrow + (lane & 7) * 144, row1 = kvrow + (8 + (lane & 7)) * 144;
      {
        const uint32_t dst = kvrow + (8 + r) * 144 + q * 4 + odd * 16, dstr = dst + (odd ? -16 : 128);
        const bool edge_out = w >= 6 && t < 15;
        uint4* const hp = scr + TILE + OFF_H + ((layer * 8 + j) * 2 + (w & 1)) * 192 + lane;
        auto put_kv = [&](float (&a)[32], int part, int half) {
          uint32_t hl[4];
#pragma unroll
          for (int i = 0; i < 16; i++) asm volatile("" : "+f"(a[16 * half + i]) :: "memory");
#pragma unroll
          for (int i = 0; i < 4; i++) {
            const int g = 4 * half + i;
            hl[i] = pack_bf16(a[4 * g + 2] * rs1, a[4 * g + 3] * rs1);
            sts1(dst + part * 20736 + g * 16, pack_bf16(a[4 * g] * rs0, a[4 * g + 1] * rs0)); sts1(dst + part * 20736 + 8 * 144 + g * 16, hl[i]);
          }
          if (edge_out) stg4(hp + part * 64 + half * 32, nz(hl[0]), hl[1], hl[2], hl[3]);
        };
        put_kv(aA, 0, 0); put_kv(aA, 0, 1);
        wg_wait<0>();
        release(prev);
        float aR[12];
        mbar_wait(rem_full, layer);
        const uint64_t dr = DESC_REM | ((sd + REM) >> 4);
        wg_fence();
#pragma unroll
        for (int s = 0; s < 36; s++) {
          wgmma_rs_n24(aR, X + 4 * s, dr + s * 16, s != 0);
          if (s == 4) put_kv(aB, 1, 0);
          if (s == 16) put_kv(aB, 1, 1);
        }
        wg_commit();
#pragma unroll
        for (int kb = 0; kb < 9; kb++) {
          if (kb == HOFF1 && w < 4) asm volatile("bar.sync 4, 256;" ::: "memory");
          if (kb == 8 && HOFF1 < 9 && w >= 4) asm volatile("bar.arrive 4, 256;" ::: "memory");
          if (!(kb & 1)) mbar_wait(full0 + rg.st * 8, rg.ph);
          const uint64_t desc = DESC_HI | ((sd + rg.st * STAGE + (kb & 1) * 8192) >> 4);
          wg_fence();
#pragma unroll
          for (int i = 0; i < 4; i++) wgmma_rs_n64(aB, X + 4 * (4 * kb + i), desc + i * 128, kb + i != 0);
          wg_commit();
          wg_wait<1>();
          if (kb > 0 && !(kb & 1)) release(prev);
          if ((kb & 1) || kb == 8) { prev = rg.st; rg.next(); }
          if (kb == 0) {
            pin(aR);
            const uint32_t k1 = pack_bf16(aR[2] * rs1, aR[3] * rs1), v1 = pack_bf16(aR[6] * rs1, aR[7] * rs1);
            if (edge_out) stg4(hp + 128, nz(k1), v1, 0u, 0u);
            sts1(dstr, pack_bf16(aR[0] * rs0, aR[1] * rs0)); sts1(dstr + 8 * 144, k1);
            sts1(dstr + 20736, pack_bf16(aR[4] * rs0, aR[5] * rs0)); sts1(dstr + 20736 + 8 * 144, v1);
            Q[16] = pack_bf16(aR[8], aR[9]); Q[17] = pack_bf16(aR[10], aR[11]);
            if (w < 4) asm volatile("bar.arrive 2, 256;" ::: "memory");
          }
          if (kb == KLD - 2) mbar_wait(remo_full, layer);
          if (kb == KLD) {
            if (w < 4) asm volatile("bar.sync 1, 192;" ::: "memory");
            else asm volatile("bar.sync 2, 256;" ::: "memory");
#pragma unroll
            for (int nt = 0; nt < 3; nt++) {
              const uint32_t ra = (nt == 0 ? row0 : row1 + (nt - 1) * 8 * 144);
              ldsm4(ra + odd * 16 + (lane >> 3) * 16, Km[nt][0], Km[nt][1], Km[nt][2], Km[nt][3]);
              ldsm4(ra + odd * 16 + 64 + (lane >> 3) * 16, Km[nt][4], Km[nt][5], Km[nt][6], Km[nt][7]);
              ldsm4(ra + (odd ? 0 : 32) + (lane >> 3) * 32, Ke[nt][0], Ke[nt][1], Ke[nt][2], Ke[nt][3]);
            }
            const uint32_t ge = (2u << q) - 1, le = 0xfu << q, on = edge ? 0u : ~0u;
            const uint32_t bits = odd ? 0xfu | ((le & 0xfu) << 4) | (ge << 8) : ge | 0xf0u | (le << 8);
#pragma unroll
            for (int h = 0; h < 4; h++) {
              const uint32_t ma = bitmask(bits, h), mb = bitmask(bits, 4 + h), mc = bitmask(bits, 8 + h);
              Km[0][2 * h] &= ma & on; Km[0][2 * h + 1] &= mb & on; Ke[0][h] &= mc & on;
#pragma unroll
              for (int nt = 1; nt < 3; nt++) { Km[nt][2 * h] &= ma; Km[nt][2 * h + 1] &= mb; Ke[nt][h] &= mc; }
            }
          }
        }
        wg_wait<0>();
        release(prev);
        pin(aB);
        STAMP(3);
#pragma unroll
        for (int i = 0; i < 16; i++) Q[i] = pack_bf16(aB[2 * i], aB[2 * i + 1]);
      }
      uint32_t res[18] = {};
      if (layer) {
        const uint4* p = xbase + ((9 * j + 1) >> 1) * 32 + lane;
#pragma unroll
        for (int i = 0; i < 4; i++) ldg4(res + 4 * i, p + i * 32);
        ldg2(res + 16, odd ? (const char*)(p - 32) + 8 : (const char*)(p + 4 * 32));
      }
      {
        uint32_t V01[12][2], V2[12];
        const uint32_t rv = ((lane & 8) ? row1 : row0) + 20736, rw = row1 + 8 * 144 + 20736;
#pragma unroll
        for (int i = 0; i < 4; i++) ldsm4t(rv + odd * 16 + i * 32 + (lane >> 4) * 16, V01[2 * i][0], V01[2 * i][1], V01[2 * i + 1][0], V01[2 * i + 1][1]);
#pragma unroll
        for (int i = 0; i < 2; i++) ldsm4t(rv + (odd ? 0 : 32) + i * 64 + (lane >> 4) * 32, V01[8 + 2 * i][0], V01[8 + 2 * i][1], V01[9 + 2 * i][0], V01[9 + 2 * i][1]);
        ldsm4t(rw + odd * 16 + (lane >> 3) * 16, V2[0], V2[1], V2[2], V2[3]);
        ldsm4t(rw + odd * 16 + 64 + (lane >> 3) * 16, V2[4], V2[5], V2[6], V2[7]);
        ldsm4t(rw + (odd ? 0 : 32) + (lane >> 3) * 32, V2[8], V2[9], V2[10], V2[11]);
        const bool up0 = 2 * q > r, up1 = 2 * q + 1 > r;
        const uint32_t upm = (up0 ? 0xffffu : 0u) | (up1 ? 0xffff0000u : 0u);
        const float c0 = 0.23570226039551584f * 1.4426950408889634f * rs0, c1 = 0.23570226039551584f * 1.4426950408889634f * rs1;
        const float masked = edge ? -1e9f * 1.4426950408889634f * rcp(c0) : 0.f;
        uint32_t Om[16], Oe[8];
#pragma unroll
        for (int h = 0; h < 4; h++) {
          const uint32_t e0 = odd ? Q[(4 * h + 16) % 18] : Q[4 * h + 4], e1 = odd ? Q[(4 * h + 17) % 18] : Q[4 * h + 5];
          float S[3][4];
#pragma unroll
          for (int nt = 0; nt < 3; nt++) {
            mma16c(S[nt], Q + 4 * h, Km[nt][2 * h], Km[nt][2 * h + 1], nt == 0 ? masked : 0.f);
            mma8(S[nt], e0, e1, Ke[nt][h]);
          }
          const float s00 = up0 ? S[0][0] : S[1][0], s01 = up1 ? S[0][1] : S[1][1];
          const float s10 = up0 ? S[1][2] : S[2][2], s11 = up1 ? S[1][3] : S[2][3];
          const float m0 = quad_max(fmaxf(s00, s01)) * c0, m1 = quad_max(fmaxf(s10, s11)) * c1;
          const float p00 = ex2(fmaf(s00, c0, -m0)), p01 = ex2(fmaf(s01, c0, -m0)), p10 = ex2(fmaf(s10, c1, -m1)), p11 = ex2(fmaf(s11, c1, -m1));
          const float i0 = rcp(quad_sum(p00 + p01)), i1 = rcp(quad_sum(p10 + p11));
          const uint32_t p0 = pack_bf16(p00 * i0, p01 * i0), p1 = pack_bf16(p10 * i1, p11 * i1);
          const uint32_t pf[4] = {p0 & upm, 0u, p0 & ~upm, p1 & upm};
#pragma unroll
          for (int gi = 0; gi < 3; gi++) {
            const int g = gi < 2 ? 2 * h + gi : 8 + h;
            float o[4];
            mma16c(o, pf, V01[g][0], V01[g][1], 0.f);
            mma8(o, 0u, p1 & ~upm, V2[g]);
            uint32_t* d = gi < 2 ? Om + 2 * g : Oe + 2 * h;
            d[0] = pack_bf16(o[0], o[1]); d[1] = pack_bf16(o[2], o[3]);
          }
        }
#pragma unroll
        for (int h = 0; h < 4; h++)
#pragma unroll
          for (int e = 0; e < 2; e++) {
            if (h > 0 && !odd && q < h) Om[4 * h + e] = Oe[2 * h - 2 + e];
            if (h < 3 && odd && q > h) Om[4 * h + 2 + e] = Oe[2 * h + 2 + e];
          }
        STAMP(4);
        if (j >= PRI && lane == 0) asm volatile("st.relaxed.gpu.global.b32 [%0], %1;" :: "l"(scr + OFF_S + (8 + w) * 96 + j * 8), "r"(tag) : "memory");
        put72(xbase + 16 * SLAB, j, lane, Om, odd ? Oe[0] : Oe[6], odd ? Oe[1] : Oe[7]);
      }
      if (j < PRI && lane == 0) asm volatile("st.relaxed.gpu.global.b32 [%0], %1;" :: "l"(scr + OFF_S + (8 + w) * 96 + j * 8), "r"(tag) : "memory");
      {
        if (layer == 0) {
          const uint32_t xrow = (w & 1) * 8192 + (16 * (w >> 1) + (lane & 15)) * 128;
          uint32_t u0, u1;
          mbar_wait(xbar0, 1); mbar_wait(xbar0 + 8, 1);
#pragma unroll
          for (int i = 0; i < 5; i++) {
            const uint32_t g = i < 4 ? j + odd + 2 * i : j + (odd ? 0 : 8);
            const uint32_t a = sb + PARK + (g >> 3) * STAGE + xrow;
            if (i < 4) ldsm4(a + ((((g & 7) + (lane >> 4)) ^ (lane & 7)) << 4), res[4 * i], res[4 * i + 1], res[4 * i + 2], res[4 * i + 3]);
            else ldsm4(a + (((g & 7) ^ (lane & 7)) << 4), res[16], res[17], u0, u1);
          }
        }
        const uint4* src = xbase + 16 * SLAB + lane;
        {
          const uint4* fp = scr + OFF_S + (8 + w) * 96 + (lane & 7) * 8;
          int n = 0;
          STAMP(8);
          while (true) {
            uint32_t f;
            asm volatile("ld.relaxed.gpu.global.b32 %0, [%1];" : "=r"(f) : "l"(fp) : "memory");
            if (__all_sync(~0u, f == tag)) break;
            SPIN_GUARD(n);
          }
          STAMP(9);
        }
#pragma unroll
        for (int kb = 0; kb < GO; kb++) load_kb(kb, src, (const char*)src - lane * 8, 256);
        float acc[36];
#pragma unroll
        for (int i = 0; i < 18; i++) { acc[2 * i] = bf_lo(res[i]); acc[2 * i + 1] = bf_hi(res[i]); }
#pragma unroll
        for (int kb = 0; kb < 9; kb++) {
          check_kb(false, kb, src, (const char*)src - lane * 8, 256);
          if (kb + GO < 9) load_kb(kb + GO, src, (const char*)src - lane * 8, 256);
          if (!(kb & 1)) mbar_wait(full0 + rg.st * 8, rg.ph);
          const uint32_t base = sd + rg.st * STAGE + (kb & 1) * 8192;
          const uint64_t d0 = DESC_HI | ((base >> 4) + (((sd + REM + 27648 + (kb >> 1) * 2048 + (kb & 1) * 64 - base) >> 4) << 16));
          wg_fence();
#pragma unroll
          for (int i = 0; i < 4; i++) wgmma_rs_n72(acc, X + 4 * (4 * kb + i), d0 - (uint64_t)(i * ((127u << 16) - 128u)), 1);
          wg_commit();
          wg_wait<1>();
          if (kb > 0 && !(kb & 1)) release(prev);
          if ((kb & 1) || kb == 8) { prev = rg.st; rg.next(); }
        }
        wg_wait<0>();
        release(prev);
        pin(acc);
        STAMP(10);
#pragma unroll
        for (int i = 0; i < 18; i++) res[i] = pack_bf16(acc[2 * i], acc[2 * i + 1]);
        if (j < PRI) put72(xbase + 32 * SLAB, j, lane, res, res[16], res[17]);
        publish_stats<9>(scr + OFF_S + (16 + w) * 96 + j * 8, acc, tag, lane);
        if (j >= PRI) put72(xbase + 32 * SLAB, j, lane, res, res[16], res[17]);
      }
      continue;
      }
      const uint32_t hp = sb + PARK + w * 512 + lane_id() * 16;
      auto pack8 = [&](float (&a)[32], int p, uint32_t* o) {
#pragma unroll
        for (int e = 0; e < 8; e++) asm volatile("" : "+f"(a[8 * p + e]) :: "memory");
#pragma unroll
        for (int e = 0; e < 4; e++) o[e] = pack_bf16(a[8 * p + 2 * e], a[8 * p + 2 * e + 1]);
      };
      const float ka0 = 0.7978845608028654f * rs0, kb0 = 0.044715f * ka0 * rs0 * rs0, ku0 = 0.5f * rs0 * rs0;
      const float ka1 = 0.7978845608028654f * rs1, kb1 = 0.044715f * ka1 * rs1 * rs1, ku1 = 0.5f * rs1 * rs1;
      auto packu8 = [&](int p, uint32_t* o) {
#pragma unroll
        for (int e = 0; e < 8; e++) asm volatile("" : "+f"(aA[8 * p + e]) :: "memory");
#pragma unroll
        for (int e = 0; e < 4; e++) o[e] = pack_bf16(aA[8 * p + 2 * e] * ((e & 1) ? ku1 : ku0), aA[8 * p + 2 * e + 1] * ((e & 1) ? ku1 : ku0));
      };
      auto geglu8 = [&](int p, uint32_t* u) {
#pragma unroll
        for (int e = 0; e < 8; e++) asm volatile("" : "+f"(aB[8 * p + e]) :: "memory");
        float h[8];
#pragma unroll
        for (int e = 0; e < 8; e++) {
          const float g = aB[8 * p + e];
          h[e] = fmaf(g, tanh_ap(g * fmaf(g * g, (e & 2) ? kb1 : kb0, (e & 2) ? ka1 : ka0)), g);
        }
#pragma unroll
        for (int e = 0; e < 4; e++) u[e] = mul_bf16x2(pack_bf16(h[2 * e], h[2 * e + 1]), u[e]);
      };
      auto box = [&](int b, auto&& filler) {
        const int kb = b < 9 ? b : b - 9;
        if (!(b & 1)) { if ((TRAPB >> (b >> 1)) & 1) mbar_wait_trap(full0 + rg.st * 8, rg.ph); else mbar_wait(full0 + rg.st * 8, rg.ph); }
        const uint64_t desc = DESC_HI | ((sd + rg.st * STAGE + (b & 1) * 8192) >> 4);
        wg_fence();
#pragma unroll
        for (int i = 0; i < 4; i++) {
          if (b < 9) wgmma_rs_n64(aA, X + 4 * (4 * kb + i), desc + i * 128, kb + i != 0);
          else wgmma_rs_n64(aB, X + 4 * (4 * kb + i), desc + i * 128, kb + i != 0);
          if (i == FPOS) filler();
        }
        wg_commit();
        if (b & 1) { prev = rg.st; rg.next(); } else { wg_wait<1>(); release(prev); }
      };
      auto nop = [] {};
      auto step = [&](int st, auto&& filler) { box(2 * st, nop); box(2 * st + 1, filler); };
#pragma unroll
      for (int p = 0; p < 4; p++) { uint32_t o[4]; packu8(p, o); sts4(hp + p * 4096, o); }
      box(0, nop);
      if (lead) mbar_arrive(xb_done);
#pragma unroll 1
      for (int c = 1;; c++) {
        const uint32_t hc = hp + c * 4 * 4096;
#pragma unroll
        for (int b = 1; b < 18; b++) box(b, [&] {
          if ((b & 1) && b < 8) { uint32_t o[4]; const uint32_t a = hc - (4 - (b >> 1)) * 4096; lds4(a, o); geglu8(b >> 1, o); sts4(a, o); }
          if ((b & 1) && b > 10) { uint32_t o[4]; packu8((b - 11) >> 1, o); if (c < 8) sts4(hc + ((b - 11) >> 1) * 4096, o); } });
        ZSTAMP(4, c);
        if (c == 8) break;
        box(0, nop);
      }
      wg_wait<0>();
      STAMP(21);
      GSTAMP(19);
      auto unpark = [&](int kb) {
#pragma unroll
        for (int s = 4 * kb; s < 4 * kb + 4; s++) lds4(hp + s * 4096, X + 4 * s);
      };
      unpark(0);
      uint32_t U[16];
#pragma unroll
      for (int p = 0; p < 4; p++) packu8(p, U + 4 * p);
#pragma unroll
      for (int b = 0; b < 8; b++) box(b, [&] {
        if (b < 7) unpark(b + 1);
        if (b & 1) {
          geglu8(b >> 1, U + 2 * (b - 1));
          if (rg.ph > 1) sts4(hp, U + 2 * (b - 1));
#pragma unroll
          for (int i = 0; i < 4; i++) X[128 + 2 * (b - 1) + i] = U[2 * (b - 1) + i];
        } });
      STAMP(24);
      if (layer == 0 && lead) mbar_arrive(park_free);
      const uint32_t lane2 = lane_id();
      uint4* const pw = scr + OFF_P + (j * 8 + w) * SLAB + lane2;
      const uint4* const pr = scr + OFF_P + w * SLAB + 4 * j * 32 + lane2;
      auto put_part = [&](float (&a)[32], int p, uint32_t chunk) {
        uint32_t o[4];
        pack8(a, p, o);
        stg4(pw + (chunk * 4 + p) * 32, (o[0] & ~1u) | tag, o[1], o[2], o[3]);
      };
      uint4* const xb = xbase + 32 * SLAB + 4 * j * 32;
      auto slot = [&](int p) { return sb + w * 2048 + (p < 3 ? PARK + p * 16384 : KVS + (p - 3) * 16384); };
      auto fetch = [&](int p) {
        bulk_load(slot(p), p ? scr + OFF_P + (((j - p) & 7) * 8 + w) * SLAB + 4 * j * 32 : xb, 2048, p ? pbar0 + w * 8 : res_full, true);
      };
#pragma unroll 1
      for (int sp = 0;; sp++) {
        const uint32_t ca = sp == 0 ? 8 : ((j + 2 * sp) & 7), cb = (j + 2 * sp + 1) & 7;
        if (C8 == 1 && sp == 1 && lead) mbar_arrive(c8_go);
#pragma unroll
        for (int st = 4; st < 9; st++) step(st, [&] {
          if (st == 5 || st == 6) { put_part(aA, 2 * (st - 5), ca); put_part(aA, 2 * (st - 5) + 1, ca); }
          if (st == 8 && sp > 0) { if (sp == 3) mbar_wait(c8_done, layer); fetch(2 * sp - 2); } });
        STAMP(25 + sp);
        if (sp == 3) break;
        if (C8 == 0 && sp == 0 && lead) mbar_arrive(c8_go);
#pragma unroll
        for (int st = 0; st < 4; st++) step(st, [&] {
          if (st < 2) { put_part(aB, 2 * st, cb); put_part(aB, 2 * st + 1, cb); }
          if (st == 3 && sp > 0) fetch(2 * sp - 1); });
      }
      auto load_p = [&](int p, uint32_t* d) {
#pragma unroll
        for (int i = 0; i < 4; i++) ldg4(d + 4 * i, pr + ((j - p) & 7) * 8 * SLAB + i * 32);
      };
#pragma unroll
      for (int b = 0; b < 9; b++) {
        if (b == HOFF2 && w < 4) asm volatile("bar.sync 5, 256;" ::: "memory");
        box(b, [&] {
          if (b == 1) {
#pragma unroll
            for (int p = 0; p < 4; p++) put_part(aB, p, (j + 7) & 7);
          }
          if (b == 3) { load_p(5, X); load_p(6, X + 16); }
          if (b == 7 && EXP != 1) load_p(7, X + 32); });
        if (b == 7 && HOFF2 < 9 && w >= 4) asm volatile("bar.arrive 5, 256;" ::: "memory");
      }
      mbar_wait(res_full, layer);
      mbar_wait(pbar0 + w * 8, layer);
#pragma unroll
      for (int p = 1; p < 5; p++)
#pragma unroll
        for (int i = 0; i < 4; i++) lds4(slot(p) + lane2 * 16 + i * 512, X + 48 + 16 * p + 4 * i);
#pragma unroll
      for (int i = 0; i < 4; i++) {
        const bool split = j == 2 * i + 1;
        const uint32_t a = slot(0) + i * 512 + (split ? lane2 * 8 : lane2 * 16);
        lds2(a, X + 48 + 4 * i); lds2(a + (split ? 256 : 8), X + 50 + 4 * i);
      }
      wg_wait<0>();
      release(rg.st); rg.next();
      pin(aA);
      STAMP(22);
      GSTAMP(20);
      {
        const uint32_t lane = lane2, r = lane >> 2, q = lane & 3;
        const uint32_t eye = r == 2 * q ? 0x3f80u : r == 2 * q + 1 ? 0x3f800000u : 0u;
        auto bad = [&](const uint32_t* d) { return diff2(d[0], d[4], tag) | diff2(d[8], d[12], tag); };
        auto add = [&](const uint32_t* d) {
#pragma unroll
          for (int g = 0; g < 8; g++) mma8(aA + 4 * g, d[2 * g], d[2 * g + 1], eye);
        };
        int n = 0;
        while (!__all_sync(~0u, ((or3(bad(X), bad(X + 16), bad(X + 64)) | or3(bad(X + 80), bad(X + 96), bad(X + 112))) & 1u) == 0u)) {
          SPIN_GUARD(n);
          load_p(5, X); load_p(6, X + 16);
#pragma unroll
          for (int p = 1; p < 5; p++) load_p(p, X + 48 + 16 * p);
        }
        add(X); add(X + 16);
#pragma unroll
        for (int p = 4; p >= 0; p--) add(X + 48 + 16 * ((p + 1) % 5));
        STAMP(11);
        if (EXP != 1) while (!__all_sync(~0u, (bad(X + 32) & 1u) == 0u)) { SPIN_GUARD(n); load_p(7, X + 32); }
        add(X + 32);
        STAMP(12);
        uint32_t res[16];
#pragma unroll
        for (int i = 0; i < 16; i++) res[i] = pack_bf16(aA[2 * i], aA[2 * i + 1]);
        if (layer == 0) {
          uint4* p = xbase + 8 * SLAB + 4 * j * 32 + lane;
          auto put = [&] {
#pragma unroll
            for (int i = 0; i < 4; i++) stg4(p + i * 32, nz(res[4 * i]), res[4 * i + 1], nz(res[4 * i + 2]), res[4 * i + 3]);
          };
          if (j < PRI) put();
          publish_stats<8>(scr + OFF_S + w * 96 + j * 8, aA, 1u, lane);
          if (j >= PRI) put();
          if (lane == 0) mbar_arrive(kv_free);
        } else {
          const uint32_t tb = slot(0);
          __syncwarp();
#pragma unroll
          for (int i = 0; i < 4; i++) {
            const uint32_t row = (lane2 & 7) + (lane2 & 8), g = 2 * i + (lane2 >> 4);
            asm volatile("stmatrix.sync.aligned.m8n8.x4.shared.b16 [%0], {%1,%2,%3,%4};"
                         :: "r"(tb + row * 128 + ((g ^ (row & 7)) << 4)), "r"(res[4 * i]), "r"(res[4 * i + 1]), "r"(res[4 * i + 2]), "r"(res[4 * i + 3]) : "memory");
          }
          __syncwarp();
#pragma unroll
          for (int i = 0; i < 4; i++) {
            const uint32_t row = 4 * i + (lane2 >> 3), g = lane2 & 7;
            uint32_t v[4];
            lds4(tb + row * 128 + ((g ^ (row & 7)) << 4), v);
            *(uint4*)(out + (128 * t + 32 * (w >> 1) + 2 * row + (w & 1)) * 576 + 64 * j + 8 * g) = make_uint4(v[0], v[1], v[2], v[3]);
          }
        }
      }
      STAMP(23);
    }
  }
}

typedef CUresult (*EncodeFn)(CUtensorMap*, CUtensorMapDataType, cuuint32_t, void*, const cuuint64_t*, const cuuint64_t*,
                             const cuuint32_t*, const cuuint32_t*, CUtensorMapInterleave, CUtensorMapSwizzle,
                             CUtensorMapL2promotion, CUtensorMapFloatOOBfill);

CUtensorMap make_map(EncodeFn f, const void* p, uint64_t cols, uint64_t rows, bool rem = false) {
  CUtensorMap m;
  cuuint64_t dims[2] = {cols, rows};
  cuuint64_t str[1] = {cols * 2};
  cuuint32_t box[2] = {rem ? 8u : 64u, rem ? 144u : 64u};
  cuuint32_t es[2] = {1, 1};
  f(&m, CU_TENSOR_MAP_DATA_TYPE_BFLOAT16, 2, const_cast<void*>(p), dims, str, box, es, CU_TENSOR_MAP_INTERLEAVE_NONE,
    rem ? CU_TENSOR_MAP_SWIZZLE_NONE : CU_TENSOR_MAP_SWIZZLE_128B, CU_TENSOR_MAP_L2_PROMOTION_NONE, CU_TENSOR_MAP_FLOAT_OOB_FILL_NONE);
  return m;
}

}

extern "C" void kernel_launch(void* const* d_in, const int* in_sizes, int n_in, void* d_out, int out_size) {
  void* fn = nullptr;
  cudaDriverEntryPointQueryResult qr;
  cudaGetDriverEntryPoint("cuTensorMapEncodeTiled", &fn, cudaEnableDefault, &qr);
  EncodeFn enc = (EncodeFn)fn;
  Maps maps;
  maps.m[0] = make_map(enc, d_in[1], 1728, 576); maps.m[1] = make_map(enc, d_in[2], 576, 576);
  maps.m[2] = make_map(enc, d_in[4], 4608, 576); maps.m[3] = make_map(enc, d_in[5], 4608, 576); maps.m[4] = make_map(enc, d_in[6], 576, 4608);
  maps.m[5] = make_map(enc, d_in[1], 1728, 576, true); maps.m[6] = make_map(enc, d_in[2], 576, 576, true);
  {
    cuuint64_t dims[3] = {576, 1024, 2}, str[2] = {2304, 1152};
    cuuint32_t box[3] = {64, 64, 2}, es[3] = {1, 1, 1};
    enc(&maps.m[7], CU_TENSOR_MAP_DATA_TYPE_BFLOAT16, 3, d_in[0], dims, str, box, es, CU_TENSOR_MAP_INTERLEAVE_NONE,
        CU_TENSOR_MAP_SWIZZLE_128B, CU_TENSOR_MAP_L2_PROMOTION_NONE, CU_TENSOR_MAP_FLOAT_OOB_FILL_NONE);
  }
  void* scr = nullptr;
  cudaGetSymbolAddress(&scr, g_scratch);
  cudaFuncSetAttribute(mega_kernel, cudaFuncAttributeMaxDynamicSharedMemorySize, SMEM_BYTES);
  cudaLaunchConfig_t cfg = {};
  cfg.gridDim = dim3(128); cfg.blockDim = dim3(384); cfg.dynamicSmemBytes = SMEM_BYTES; cfg.stream = cudaStreamPerThread;
  cudaLaunchAttribute at[1];
  at[0].id = cudaLaunchAttributeClusterDimension; at[0].val.clusterDim.x = 2; at[0].val.clusterDim.y = 1; at[0].val.clusterDim.z = 1;
  cfg.attrs = at; cfg.numAttrs = 1;
  int dev = 0, sms = 0, clusters = 0;
  cudaGetDevice(&dev);
  cudaDeviceGetAttribute(&sms, cudaDevAttrMultiProcessorCount, dev);
  cudaOccupancyMaxActiveClusters(&clusters, mega_kernel, &cfg);
  if (sms == 132 && clusters == 66) cfg.gridDim = dim3(132);
  cudaLaunchKernelEx(&cfg, mega_kernel, maps, (uint4*)scr, (__nv_bfloat16*)d_out);
}
```

```cpp
#include <cuda_runtime.h>
#include <cuda.h>
#include <cuda_bf16.h>
#include <stdint.h>

#define TRACE 0
#define GUARD 0
#define ZT 0

namespace {

constexpr int NST = 6;
constexpr int STAGE = 16384;
constexpr int PARK = NST * STAGE;
constexpr int REM = PARK + 49152;
constexpr int KVS = REM + 40960;
constexpr int PIECE = PARK + 7 * STAGE;
constexpr int HSTG = KVS + 16384;
constexpr int BARS = KVS + 41472;
constexpr int TRC = BARS + 512;
constexpr int SMEM_BYTES = TRC + (TRACE ? 512 : 0);
static_assert(NST == 6, "the producer addresses empty barriers as full + 48");
static_assert(BARS >= PARK + 131072, "barriers overlap park");
static_assert(SMEM_BYTES <= 232448, "smem");

constexpr int SLAB = 36 * 32;
constexpr int SPIN_MAX = 1 << 17;
constexpr uint32_t PRI = 3;
constexpr int GD = 3;
constexpr int OFF_S = 0;
constexpr int OFF_H = OFF_S + 3 * 8 * 96;
constexpr int OFF_X = OFF_H + 2 * 8 * 384;
constexpr int OFF_P = OFF_X + 6 * 8 * SLAB;
constexpr int TILE = OFF_P + 8 * 8 * SLAB;
constexpr int OFF_R = 16 * TILE;
constexpr int OFF_F = OFF_R + 8 * 2304;
constexpr int SCRATCH = OFF_F + 128 * 8;

}

__device__ uint4 g_scratch[SCRATCH];

namespace {

constexpr uint64_t DESC_HI = 0x4000004000000000ull;
constexpr uint64_t DESC_REM = (576ull << 32) | (8u << 16);
__device__ __forceinline__ void wgmma_rs_n64(float (&d)[32], const uint32_t* a, uint64_t desc, int scale_d) {
  asm volatile("{\n.reg .pred p;\nsetp.ne.b32 p, %37, 0;\n"
    "wgmma.mma_async.sync.aligned.m64n64k16.f32.bf16.bf16 "
    "{%0, %1, %2, %3, %4, %5, %6, %7, %8, %9, %10, %11, %12, %13, %14, %15, %16, %17, %18, %19, %20, %21, %22, %23, %24, %25, %26, %27, %28, %29, %30, %31}, "
    "{%32, %33, %34, %35}, %36, p, 1, 1, 1;\n}\n"
    : "+f"(d[0]), "+f"(d[1]), "+f"(d[2]), "+f"(d[3]), "+f"(d[4]), "+f"(d[5]), "+f"(d[6]), "+f"(d[7]), "+f"(d[8]), "+f"(d[9]), "+f"(d[10]), "+f"(d[11]), "+f"(d[12]), "+f"(d[13]), "+f"(d[14]), "+f"(d[15]), "+f"(d[16]), "+f"(d[17]), "+f"(d[18]), "+f"(d[19]), "+f"(d[20]), "+f"(d[21]), "+f"(d[22]), "+f"(d[23]), "+f"(d[24]), "+f"(d[25]), "+f"(d[26]), "+f"(d[27]), "+f"(d[28]), "+f"(d[29]), "+f"(d[30]), "+f"(d[31])
    : "r"(a[0]), "r"(a[1]), "r"(a[2]), "r"(a[3]), "l"(desc), "r"(scale_d));
}
__device__ __forceinline__ void wgmma_rs_n72(float (&d)[36], const uint32_t* a, uint64_t desc, int scale_d) {
  asm volatile("{\n.reg .pred p;\nsetp.ne.b32 p, %41, 0;\n"
    "wgmma.mma_async.sync.aligned.m64n72k16.f32.bf16.bf16 "
    "{%0, %1, %2, %3, %4, %5, %6, %7, %8, %9, %10, %11, %12, %13, %14, %15, %16, %17, %18, %19, %20, %21, %22, %23, %24, %25, %26, %27, %28, %29, %30, %31, %32, %33, %34, %35}, "
    "{%36, %37, %38, %39}, %40, p, 1, 1, 1;\n}\n"
    : "+f"(d[0]), "+f"(d[1]), "+f"(d[2]), "+f"(d[3]), "+f"(d[4]), "+f"(d[5]), "+f"(d[6]), "+f"(d[7]), "+f"(d[8]), "+f"(d[9]), "+f"(d[10]), "+f"(d[11]), "+f"(d[12]), "+f"(d[13]), "+f"(d[14]), "+f"(d[15]), "+f"(d[16]), "+f"(d[17]), "+f"(d[18]), "+f"(d[19]), "+f"(d[20]), "+f"(d[21]), "+f"(d[22]), "+f"(d[23]), "+f"(d[24]), "+f"(d[25]), "+f"(d[26]), "+f"(d[27]), "+f"(d[28]), "+f"(d[29]), "+f"(d[30]), "+f"(d[31]), "+f"(d[32]), "+f"(d[33]), "+f"(d[34]), "+f"(d[35])
    : "r"(a[0]), "r"(a[1]), "r"(a[2]), "r"(a[3]), "l"(desc), "r"(scale_d));
}
__device__ __forceinline__ void wgmma_rs_n24(float (&d)[12], const uint32_t* a, uint64_t desc, int scale_d) {
  asm volatile("{\n.reg .pred p;\nsetp.ne.b32 p, %17, 0;\n"
    "wgmma.mma_async.sync.aligned.m64n24k16.f32.bf16.bf16 "
    "{%0, %1, %2, %3, %4, %5, %6, %7, %8, %9, %10, %11}, "
    "{%12, %13, %14, %15}, %16, p, 1, 1, 1;\n}\n"
    : "+f"(d[0]), "+f"(d[1]), "+f"(d[2]), "+f"(d[3]), "+f"(d[4]), "+f"(d[5]), "+f"(d[6]), "+f"(d[7]), "+f"(d[8]), "+f"(d[9]), "+f"(d[10]), "+f"(d[11])
    : "r"(a[0]), "r"(a[1]), "r"(a[2]), "r"(a[3]), "l"(desc), "r"(scale_d));
}

__device__ __forceinline__ void mbar_init(uint32_t a, uint32_t c) { asm volatile("mbarrier.init.shared::cta.b64 [%0], %1;" :: "r"(a), "r"(c)); }
__device__ __forceinline__ void mbar_arrive(uint32_t a) { asm volatile("mbarrier.arrive.shared::cta.b64 _, [%0];" :: "r"(a) : "memory"); }
__device__ __forceinline__ void mbar_wait_trap(uint32_t a, uint32_t ph) {
  asm volatile("{\n.reg .pred p;\n.reg .u32 n;\nmov.u32 n, 0;\n"
               "W: mbarrier.try_wait.parity.shared::cta.b64 p, [%0], %1;\n@p bra D;\n"
               "add.u32 n, n, 1;\nsetp.lt.u32 p, n, 4194304;\n@p bra W;\ntrap;\nD:\n}" :: "r"(a), "r"(ph) : "memory");
}
__device__ __forceinline__ void mbar_wait(uint32_t a, uint32_t ph) {
  asm volatile("{\n.reg .pred p;\nW: mbarrier.try_wait.parity.shared::cta.b64 p, [%0], %1;\n@!p bra W;\n}" :: "r"(a), "r"(ph) : "memory");
}
__device__ __forceinline__ void mbar_wait_sleep(uint32_t a, uint32_t ph) {
  asm volatile("{\n.reg .pred p;\nW: mbarrier.test_wait.parity.shared::cta.b64 p, [%0], %1;\n@p bra D;\nnanosleep.u32 500;\nbra W;\nD:\n}" :: "r"(a), "r"(ph) : "memory");
}
__device__ __forceinline__ void wg_fence() { asm volatile("wgmma.fence.sync.aligned;" ::: "memory"); }
__device__ __forceinline__ void wg_commit() { asm volatile("wgmma.commit_group.sync.aligned;" ::: "memory"); }
template <int N> __device__ __forceinline__ void wg_wait() { asm volatile("wgmma.wait_group.sync.aligned %0;" :: "n"(N) : "memory"); }
__device__ __forceinline__ float tanh_ap(float x) { float y; asm("tanh.approx.f32 %0, %1;" : "=f"(y) : "f"(x)); return y; }
__device__ __forceinline__ float ex2(float x) { float y; asm("ex2.approx.ftz.f32 %0, %1;" : "=f"(y) : "f"(x)); return y; }
__device__ __forceinline__ uint32_t pack_bf16(float lo, float hi) { uint32_t r; asm("cvt.rn.bf16x2.f32 %0, %1, %2;" : "=r"(r) : "f"(hi), "f"(lo)); return r; }
__device__ __forceinline__ float bf_lo(uint32_t v) { return __uint_as_float(v << 16); }
__device__ __forceinline__ float bf_hi(uint32_t v) { return __uint_as_float(v & 0xffff0000u); }
__device__ __forceinline__ uint32_t sub_bf16x2(uint32_t a, uint32_t b) { uint32_t r; asm("sub.rn.bf16x2 %0, %1, %2;" : "=r"(r) : "r"(a), "r"(b)); return r; }
__device__ __forceinline__ uint32_t mul_bf16x2(uint32_t a, uint32_t b) { uint32_t r; asm("mul.rn.bf16x2 %0, %1, %2;" : "=r"(r) : "r"(a), "r"(b)); return r; }
__device__ __forceinline__ uint32_t diff2(uint32_t a, uint32_t b, uint32_t t) { uint32_t r; asm("lop3.b32 %0, %1, %2, %3, 0x7e;" : "=r"(r) : "r"(a), "r"(b), "r"(t)); return r; }
__device__ __forceinline__ uint32_t or3(uint32_t a, uint32_t b, uint32_t c) { uint32_t r; asm("lop3.b32 %0, %1, %2, %3, 0xfe;" : "=r"(r) : "r"(a), "r"(b), "r"(c)); return r; }
__device__ __forceinline__ uint32_t umin2(uint32_t a, uint32_t b) { uint32_t r; asm("min.u32 %0, %1, %2;" : "=r"(r) : "r"(a), "r"(b)); return r; }
__device__ __forceinline__ uint32_t bitmask(uint32_t v, int bit) { uint32_t r; asm("bfe.s32 %0, %1, %2, 1;" : "=r"(r) : "r"(v), "r"(bit)); return r; }
__device__ __forceinline__ uint32_t nz(uint32_t w) { return w == 0u ? 0x8000u : w; }

__device__ __forceinline__ void ldg4(uint32_t* d, const uint4* p) {
  asm volatile("ld.relaxed.gpu.global.v4.b32 {%0,%1,%2,%3}, [%4];" : "=r"(d[0]), "=r"(d[1]), "=r"(d[2]), "=r"(d[3]) : "l"(p) : "memory");
}
__device__ __forceinline__ void ldg2(uint32_t* d, const void* p) {
  asm volatile("ld.relaxed.gpu.global.v2.b32 {%0,%1}, [%2];" : "=r"(d[0]), "=r"(d[1]) : "l"(p) : "memory");
}
__device__ __forceinline__ void stg4(uint4* p, uint32_t a, uint32_t b, uint32_t c, uint32_t d) {
  asm volatile("st.relaxed.gpu.global.v4.b32 [%0], {%1,%2,%3,%4};" :: "l"(p), "r"(a), "r"(b), "r"(c), "r"(d) : "memory");
}
__device__ __forceinline__ void stg2(void* p, uint32_t a, uint32_t b) {
  asm volatile("st.relaxed.gpu.global.v2.b32 [%0], {%1,%2};" :: "l"(p), "r"(a), "r"(b) : "memory");
}
__device__ __forceinline__ void sts4(uint32_t a, const uint32_t* o) { asm volatile("st.shared.v4.b32 [%0], {%1,%2,%3,%4};" :: "r"(a), "r"(o[0]), "r"(o[1]), "r"(o[2]), "r"(o[3]) : "memory"); }
__device__ __forceinline__ void lds4(uint32_t a, uint32_t* o) { asm volatile("ld.shared.v4.b32 {%0,%1,%2,%3}, [%4];" : "=r"(o[0]), "=r"(o[1]), "=r"(o[2]), "=r"(o[3]) : "r"(a) : "memory"); }
__device__ __forceinline__ void lds2(uint32_t a, uint32_t* o) { asm volatile("ld.shared.v2.b32 {%0,%1}, [%2];" : "=r"(o[0]), "=r"(o[1]) : "r"(a) : "memory"); }
__device__ __forceinline__ float rcp(float x) { float y; asm("rcp.approx.ftz.f32 %0, %1;" : "=f"(y) : "f"(x)); return y; }
__device__ __forceinline__ void sts1(uint32_t a, uint32_t v) { asm volatile("st.shared.b32 [%0], %1;" :: "r"(a), "r"(v) : "memory"); }
__device__ __forceinline__ void ldsm4(uint32_t a, uint32_t& r0, uint32_t& r1, uint32_t& r2, uint32_t& r3) {
  asm volatile("ldmatrix.sync.aligned.m8n8.x4.shared.b16 {%0,%1,%2,%3}, [%4];" : "=r"(r0), "=r"(r1), "=r"(r2), "=r"(r3) : "r"(a) : "memory");
}
__device__ __forceinline__ void ldsm4t(uint32_t a, uint32_t& r0, uint32_t& r1, uint32_t& r2, uint32_t& r3) {
  asm volatile("ldmatrix.sync.aligned.m8n8.x4.trans.shared.b16 {%0,%1,%2,%3}, [%4];" : "=r"(r0), "=r"(r1), "=r"(r2), "=r"(r3) : "r"(a) : "memory");
}
__device__ __forceinline__ void mma16(float* c, uint32_t a0, uint32_t a1, uint32_t a2, uint32_t a3, uint32_t b0, uint32_t b1) {
  asm("mma.sync.aligned.m16n8k16.row.col.f32.bf16.bf16.f32 {%0,%1,%2,%3}, {%4,%5,%6,%7}, {%8,%9}, {%0,%1,%2,%3};"
    : "+f"(c[0]), "+f"(c[1]), "+f"(c[2]), "+f"(c[3]) : "r"(a0), "r"(a1), "r"(a2), "r"(a3), "r"(b0), "r"(b1));
}
__device__ __forceinline__ void mma16c(float* d, const uint32_t* a, uint32_t b0, uint32_t b1, float c01) {
  asm("mma.sync.aligned.m16n8k16.row.col.f32.bf16.bf16.f32 {%0,%1,%2,%3}, {%4,%5,%6,%7}, {%8,%9}, {%10,%10,%10,%10};"
    : "=f"(d[0]), "=f"(d[1]), "=f"(d[2]), "=f"(d[3]) : "r"(a[0]), "r"(a[1]), "r"(a[2]), "r"(a[3]), "r"(b0), "r"(b1), "f"(c01));
}
__device__ __forceinline__ void mma8(float* c, uint32_t a0, uint32_t a1, uint32_t b0) {
  asm("mma.sync.aligned.m16n8k8.row.col.f32.bf16.bf16.f32 {%0,%1,%2,%3}, {%4,%5}, {%6}, {%0,%1,%2,%3};"
    : "+f"(c[0]), "+f"(c[1]), "+f"(c[2]), "+f"(c[3]) : "r"(a0), "r"(a1), "r"(b0));
}
__device__ __forceinline__ uint32_t lane_id() { uint32_t l; asm volatile("mov.u32 %0, %%laneid;" : "=r"(l)); return l; }
__device__ __forceinline__ float quad_sum(float v) { v += __shfl_xor_sync(~0u, v, 1); v += __shfl_xor_sync(~0u, v, 2); return v; }
__device__ __forceinline__ float quad_max(float v) { v = fmaxf(v, __shfl_xor_sync(~0u, v, 1)); v = fmaxf(v, __shfl_xor_sync(~0u, v, 2)); return v; }
template <int N> __device__ __forceinline__ void pin(float (&d)[N]) {
#pragma unroll
  for (int i = 0; i < N; i++) asm volatile("" : "+f"(d[i]) :: "memory");
}
#define SPIN_GUARD(n) if (++(n) > SPIN_MAX) break

template <int NG> __device__ __forceinline__ void publish_stats(uint4* dst, const float* y, uint32_t tag, uint32_t lane) {
  float s0 = 0.f, s1 = 0.f;
#pragma unroll
  for (int g = 0; g < NG; g++) { s0 += y[4 * g] + y[4 * g + 1]; s1 += y[4 * g + 2] + y[4 * g + 3]; }
  s0 = quad_sum(s0); s1 = quad_sum(s1);
  const float m0 = s0 * (1.f / (8 * NG)), m1 = s1 * (1.f / (8 * NG));
  float q0 = 0.f, q1 = 0.f, q2 = 0.f, q3 = 0.f;
#pragma unroll
  for (int g = 0; g < NG; g++) {
    const float a = y[4 * g] - m0, b = y[4 * g + 1] - m0, c = y[4 * g + 2] - m1, d = y[4 * g + 3] - m1;
    q0 = fmaf(a, a, q0); q1 = fmaf(b, b, q1); q2 = fmaf(c, c, q2); q3 = fmaf(d, d, q3);
  }
  q0 = quad_sum(q0 + q1); q2 = quad_sum(q2 + q3);
  if ((lane & 3) == 0)
    stg4(dst + (lane >> 2), (__float_as_uint(s0) & ~1u) | tag, __float_as_uint(q0), __float_as_uint(s1), __float_as_uint(q2));
}

__device__ __forceinline__ void put72(uint4* slab, uint32_t j, uint32_t lane, const uint32_t* v, uint32_t r0, uint32_t r1) {
  uint4* p = slab + ((9 * j + 1) >> 1) * 32;
#pragma unroll
  for (int i = 0; i < 4; i++) stg4(p + lane + i * 32, nz(v[4 * i]), v[4 * i + 1], v[4 * i + 2], v[4 * i + 3]);
  stg2((char*)((j & 1) ? p - 16 : p + 4 * 32) + lane * 8, nz(r0), r1);
}
__device__ __forceinline__ void zero_share(uint4* slab, uint32_t j, uint32_t lane) {
  uint4* p = slab + j * 144 + lane;
#pragma unroll
  for (int i = 0; i < 4; i++) stg4(p + i * 32, 0u, 0u, 0u, 0u);
  if (lane < 16) stg4(p + 128, 0u, 0u, 0u, 0u);
}

struct Maps { CUtensorMap m[8]; };

struct Ring {
  uint32_t st, ph;
  __device__ __forceinline__ void next() { if (++st == NST) { st = 0; ph ^= 1; } }
};

#define GSTAMP(i) do {} while (0)
#define STAMP(i) do {} while (0)
#define ZSTAMP(m, i) do {} while (0)

__device__ __forceinline__ void tma_box(uint32_t dst, const CUtensorMap* m, int col, int row, uint32_t bar, uint32_t expect) {
  asm volatile("{\n.reg .pred e, h;\nelect.sync _|e, 0xffffffff;\nsetp.ne.and.u32 h, %5, 0, e;\n"
               "@h mbarrier.arrive.expect_tx.shared::cta.b64 _, [%2], %5;\n"
               "@e cp.async.bulk.tensor.2d.shared::cluster.global.mbarrier::complete_tx::bytes [%0], [%1, {%3, %4}], [%2];\n}"
               :: "r"(dst), "l"(m), "r"(bar), "r"(col), "r"(row), "r"(expect) : "memory");
}

__device__ __forceinline__ void bulk_load(uint32_t dst, const void* src, uint32_t bytes, uint32_t bar, bool arm) {
  asm volatile("{\n.reg .pred e, h;\nelect.sync _|e, 0xffffffff;\nsetp.ne.and.u32 h, %4, 0, e;\n"
               "@h mbarrier.arrive.expect_tx.shared::cta.b64 _, [%3], %2;\n"
               "@e cp.async.bulk.shared::cluster.global.mbarrier::complete_tx::bytes [%0], [%1], %2, [%3];\n}"
               :: "r"(dst), "l"(src), "r"(bytes), "r"(bar), "r"((uint32_t)arm) : "memory");
}

__global__ void __launch_bounds__(384, 1) mega_kernel(
    const __grid_constant__ Maps maps, uint4* __restrict__ scratch,
    __nv_bfloat16* __restrict__ out) {
  extern __shared__ __align__(1024) uint8_t smem[];
  const uint32_t sb = (uint32_t)__cvta_generic_to_shared(smem);
  const uint32_t full0 = sb + BARS, empty0 = full0 + 8 * NST, rem_full = empty0 + 8 * NST, park_free = rem_full + 8, kv_free = park_free + 8;
  const uint32_t c8_go = kv_free + 8, c8_done = c8_go + 8, c8_full = c8_done + 8, remo_full = c8_full + 8, piece_full = remo_full + 8, xb_done = piece_full + 8, res_full = xb_done + 8, pbar0 = res_full + 8;
  const uint32_t x_done = pbar0 + 64, x_ring = x_done + 8, xbar0 = x_ring + 8;
  const uint32_t w = __shfl_sync(~0u, threadIdx.x >> 5, 0);
  uint32_t pair = blockIdx.x >> 1;
  if (gridDim.x == 132) {
    uint32_t smid;
    asm("mov.u32 %0, %%smid;" : "=r"(smid));
    const uint32_t tpc = smid >> 1;
    if (tpc == 60 || tpc == 61) { if (threadIdx.x == 0) { __nanosleep(20000); } return; }
    pair = tpc < 32 ? tpc : tpc >= 62 ? (tpc - 58) * 8 : 33 + (tpc - 32) / 7 * 8 + (tpc - 32) % 7;
  }
  const uint32_t rank = blockIdx.x & 1, t = (pair & 7) * 2 + rank, j = pair >> 3;
  const uint32_t sd = sb & 0x3ffff;
  const uint32_t odd = j & 1;
  uint4* const scr = scratch + t * TILE;
  const uint32_t xs = sb + (NST - 2) * STAGE;
  auto fetch_x = [&](uint32_t dst, uint32_t b, uint32_t bar) {
    asm volatile("{\n.reg .pred e;\nelect.sync _|e, 0xffffffff;\n@e mbarrier.arrive.expect_tx.shared::cta.b64 _, [%2], 16384;\n"
                 "@e cp.async.bulk.tensor.3d.shared::cluster.global.mbarrier::complete_tx::bytes [%0], [%1, {%3, %4, 0}], [%2];\n}"
                 :: "r"(dst), "l"(&maps.m[7]), "r"(bar), "r"(64 * b), "r"(64 * t) : "memory");
  };
  if (threadIdx.x == 256) {
    for (int i = 0; i < 9; i++) mbar_init(xbar0 + 8 * i, 1);
    mbar_init(piece_full, 1);
    asm volatile("fence.mbarrier_init.release.cluster;" ::: "memory");
  }
  if (threadIdx.x == 288) {
    for (int i = 0; i < NST; i++) { mbar_init(full0 + 8 * i, 1); mbar_init(empty0 + 8 * i, 16); }
    mbar_init(x_done, 8); mbar_init(x_ring, 16);
    asm volatile("fence.mbarrier_init.release.cluster;" ::: "memory");
  }
  if (threadIdx.x == 320) {
    mbar_init(rem_full, 1); mbar_init(park_free, 8); mbar_init(kv_free, 8); mbar_init(c8_go, 8); mbar_init(c8_done, 2); mbar_init(c8_full, 1);
    mbar_init(remo_full, 64); mbar_init(xb_done, 8); mbar_init(res_full, 8);
    for (int i = 0; i < 8; i++) mbar_init(pbar0 + 8 * i, 4);
    asm volatile("fence.mbarrier_init.release.cluster;" ::: "memory");
  }
  if (threadIdx.x == 352) {
    asm volatile("prefetch.tensormap [%0];" :: "l"(&maps.m[7]) : "memory");
    asm volatile("prefetch.tensormap [%0];" :: "l"(&maps.m[0]) : "memory");
  }
  __syncwarp();
  asm volatile("barrier.cluster.arrive.relaxed.aligned;" ::: "memory");
  if (w != 8) asm volatile("barrier.cluster.wait.aligned;" ::: "memory");

  if (w >= 8) {
    asm volatile("setmaxnreg.dec.sync.aligned.u32 24;");
    if (w == 8) {
#pragma unroll 1
      for (uint32_t b = 0; b < 9; b++) fetch_x(xs + b * STAGE, b, xbar0 + 8 * b);
      tma_box(sb + PIECE, &maps.m[t >= 12 ? 6 : 5], 72 * j + (odd ? 0 : 64) + (t < 8 ? 576 * ((t >> 2) + 1) : 0), 144 * (t & 3), piece_full, 2304);
      asm volatile("barrier.cluster.wait.aligned;" ::: "memory");
      uint32_t dst = sb, bar = full0, ph = 1;
#pragma unroll 1
      for (int seg = 0; seg < 34; seg++) {
        const int n = seg >= 17 ? seg - 17 : seg;
        int ma, mb, ca, cb, row = 0;
        if (n < 3) { ma = mb = n == 2; ca = 72 * j + 8 * odd + (n == 0 ? 576 : 0); cb = ca + 576; }
        else if (n < 12) { ma = 3; mb = 2; ca = cb = 576 * j + 64 * (n - 3); }
        else { ma = mb = 4; ca = n == 12 ? 512 : ((j + 2 * n) & 7) * 64; cb = ((j + 2 * n + 1) & 7) * 64; row = 576 * j; }
        const bool zip = n == 0 || n == 3, solo = n == 1 || n == 2 || n == 16;
        const CUtensorMap *pa = &maps.m[ma], *pb = &maps.m[mb];
#pragma unroll 1
        for (int st = 0; st < (solo ? 5 : 9); st++) {
          if (seg == 0 && st == NST - 2) mbar_wait(x_ring, 0);
          const bool s0 = !zip && st > 4, s1 = zip || st >= 4;
          const int r0 = row + (zip ? 64 * st : s0 ? 128 * st - 576 : 128 * st), r1 = zip ? r0 : st == 4 ? row : r0 + 64;
          const bool rk = rank, sm = rk ? s1 : s0;
          asm volatile("{\n.reg .pred p, e, f;\n.reg .u32 n;\nelect.sync _|e, 0xffffffff;\nsetp.ne.and.u32 f, %7, 0, e;\nmov.u32 n, 0;\n"
                       "W: mbarrier.try_wait.parity.shared::cta.b64 p, [%1+48], %2;\n@p bra D;\n"
                       "add.u32 n, n, 1;\nsetp.lt.u32 p, n, 4194304;\n@p bra W;\ntrap;\n"
                       "D: @e mbarrier.arrive.expect_tx.shared::cta.b64 _, [%1], %6;\n"
                       "@f cp.async.bulk.tensor.2d.shared::cluster.global.mbarrier::complete_tx::bytes.multicast::cluster [%0], [%3, {%4, %5}], [%1], 3;\n}"
                       :: "r"(dst + rk * 8192), "r"(bar), "r"(ph), "l"(sm ? pb : pa), "r"(sm ? cb : ca), "r"(rk ? r1 : r0),
                          "r"(solo && st == 4 ? STAGE / 2 : STAGE), "r"((uint32_t)!(rk && solo && st == 4)) : "memory");
          dst += STAGE; bar += 8;
          if (bar == full0 + 8 * NST) { dst = sb; bar = full0; ph ^= 1; }
        }
      }
      {
#pragma unroll 1
        for (int i = 0; i < NST; i++) {
          mbar_wait_trap(bar + 48, ph);
          bar += 8;
          if (bar == full0 + 8 * NST) { bar = full0; ph ^= 1; }
        }
      }
    } else if (w == 9) {
      const uint32_t lane = lane_id();
      const uint32_t stg = sb + HSTG + lane * 16;
      uint32_t fph = 0;
#pragma unroll 1
      for (uint32_t layer = 0; layer < 2; layer++) {
        uint4* xb = scr + OFF_X + ((4 + layer) * 8 + j) * SLAB + 32 * 32;
        mbar_wait_sleep(c8_go, layer);
        int n = 0;
        while (true) {
          if (lane == 0) asm volatile("mbarrier.arrive.expect_tx.shared::cta.b64 _, [%0], 18432;" :: "r"(c8_full) : "memory");
          __syncwarp();
#pragma unroll 1
          for (uint32_t s = 0; s < 9; s++)
            bulk_load(sb + HSTG + s * 2048, s < 8 ? scr + OFF_P + (j + s * 8) * SLAB + 32 * 32 : xb, 2048, c8_full, false);
          mbar_wait(c8_full, fph); fph ^= 1;
          uint32_t bad = 0;
#pragma unroll 8
          for (int s = 0; s < 32; s++) { uint32_t v; asm volatile("ld.shared.b32 %0, [%1];" : "=r"(v) : "r"(stg + s * 512) : "memory"); bad |= v ^ (1 - layer); }
          if (__all_sync(~0u, (bad & 1u) == 0u)) break;
          __nanosleep(300);
          SPIN_GUARD(n);
        }
        asm volatile("bar.arrive 7, 96;" ::: "memory");
        float s0 = 0.f, s1 = 0.f;
#pragma unroll 1
        for (int g = 0; g < 8; g++) {
          const uint32_t a = stg + (g >> 1) * 512 + (g & 1) * 8;
          float a0 = 0.f, a1 = 0.f, a2 = 0.f, a3 = 0.f;
#pragma unroll 1
          for (int b = 0; b < 3; b++) {
            uint32_t v[6];
#pragma unroll
            for (int s = 0; s < 3; s++) lds2(a + (3 * b + s) * 2048, v + 2 * s);
#pragma unroll
            for (int s = 0; s < 3; s++) { a0 += bf_lo(v[2 * s]); a1 += bf_hi(v[2 * s]); a2 += bf_lo(v[2 * s + 1]); a3 += bf_hi(v[2 * s + 1]); }
          }
          sts1(a + 18432, pack_bf16(a0, a1)); sts1(a + 18436, pack_bf16(a2, a3));
          s0 += a0 + a1; s1 += a2 + a3;
        }
        __syncwarp();
        if (lane == 0) mbar_arrive(c8_done);
        s0 = quad_sum(s0); s1 = quad_sum(s1);
        float q0 = 0.f, q1 = 0.f;
        const uint32_t ln = lane_id();
#pragma unroll 1
        for (uint32_t i = 0; i < 4; i++) {
          uint32_t x[4];
          lds4(stg + 18432 + i * 512, x);
          stg4(xb + i * 32 + ln, 0u, 0u, 0u, 0u);
          if (layer == 0) {
            stg4(xb - 3 * 8 * SLAB + i * 32 + ln, nz(x[0]), x[1], x[2], x[3]);
#pragma unroll
            for (int e = 0; e < 4; e++) {
              const float m = (e & 1) ? s1 : s0, c = fmaf(m, -1.f / 64, bf_lo(x[e])), d = fmaf(m, -1.f / 64, bf_hi(x[e]));
              if (e & 1) q1 = fmaf(c, c, fmaf(d, d, q1)); else q0 = fmaf(c, c, fmaf(d, d, q0));
            }
          } else {
            uint32_t* o = (uint32_t*)(out + (128 * t + 32 * (j >> 1) + 2 * (ln >> 2) + (j & 1)) * 576 + 512 + 16 * i + 2 * (ln & 3));
            o[0] = x[0]; o[8 * 576] = x[1]; o[4] = x[2]; o[8 * 576 + 4] = x[3];
          }
        }
        if (layer == 0) {
          q0 = quad_sum(q0); q1 = quad_sum(q1);
          if ((ln & 3) == 0) stg4(scr + OFF_S + j * 96 + 64 + (ln >> 2), __float_as_uint(s0) | 1u, __float_as_uint(q0), __float_as_uint(s1), __float_as_uint(q1));
        }
      }
    } else {
      auto mark = [&](uint32_t k0, uint32_t v) {
        const uint32_t lane = lane_id();
#pragma unroll 1
        for (uint32_t k = k0; k < 6; k++) stg4(scr + OFF_S + (k * 4 + (lane >> 3)) * 96 + j * 8 + (lane & 7), k < 2 ? 0u : v, 0u, 0u, 0u);
      };
      if (w == 11) mark(2, 0u);
      auto phase2_duties = [&](uint32_t layer) {
        const uint32_t lane = lane_id();
        asm volatile("bar.sync 7, 96;" ::: "memory");
        if (w == 11) {
          if (layer == 0) mark(0, 1u);
          __syncwarp();
          if (lane == 0) mbar_arrive(c8_done);
        }
        mbar_wait_sleep(res_full, layer);
#pragma unroll 1
        for (uint32_t i = 0; i < 4; i++) {
          uint4* z = scr + OFF_X + ((4 + layer) * 8 + (w - 10) * 4 + i) * SLAB + 4 * j * 32 + lane;
#pragma unroll
          for (int k = 0; k < 4; k++) stg4(z + k * 32, 0u, 0u, 0u, 0u);
          __nanosleep(300);
        }
      };
      if (w == 10) {
        const uint32_t lane = lane_id();
        uint32_t* fl = (uint32_t*)(scratch + OFF_F + (t * 8 + j) * 8) + (lane & 15);
        uint32_t v;
        asm volatile("ld.relaxed.gpu.global.b32 %0, [%1];" : "=r"(v) : "l"(fl) : "memory");
        mbar_wait(piece_full, 0);
        asm volatile("{\n.reg .pred e;\nelect.sync _|e, 0xffffffff;\n@e cp.async.bulk.global.shared::cta.bulk_group [%0], [%1], 2304;\n}\n"
                     "cp.async.bulk.commit_group;\ncp.async.bulk.wait_group 0;\nfence.proxy.async;"
                     :: "l"(scratch + OFF_R + j * 2304 + t * 144), "r"(sb + PIECE) : "memory");
        __syncwarp();
        if (lane < 16) asm volatile("st.release.gpu.global.b32 [%0], 1;" :: "l"((uint32_t*)(scratch + OFF_F + (lane_id() * 8 + j) * 8) + t) : "memory");
        int n = 0;
        while (!__all_sync(~0u, v != 0u)) {
          __nanosleep(100);
          SPIN_GUARD(n);
          asm volatile("ld.relaxed.gpu.global.b32 %0, [%1];" : "=r"(v) : "l"(fl) : "memory");
        }
        asm volatile("st.relaxed.gpu.global.b32 [%0], 0;" :: "l"(fl) : "memory");
        mbar_wait(x_done, 0);
      }
#pragma unroll 1
      for (uint32_t layer = 0; layer < 2; layer++) {
        if (w == 10) {
          if (layer) mbar_wait_sleep(park_free, 0);
          bulk_load(sb + REM, scratch + OFF_R + j * 2304, 36864, rem_full, true);
          if (layer == 0) { fetch_x(sb + PARK, j, xbar0); fetch_x(sb + PARK + STAGE, j + 1, xbar0 + 8); }
        }
        mbar_wait_sleep(rem_full, layer);
#pragma unroll 1
        for (uint32_t b = 0; b < 5; b++) {
          const uint32_t blk = sb + REM + 27648 + b * 2048, k = (w - 10) * 32 + lane_id(), rr = k & 7;
          const uint32_t dst = blk + ((k >> 3) & 1) * 1024 + rr * 128 + (((k >> 4) ^ rr) << 4);
          uint32_t v[8];
          lds4(blk + k * 16, v); lds4(blk + 1024 + k * 16, v + 4);
          asm volatile("bar.sync 3, 64;" ::: "memory");
          sts4(dst, v); sts4(dst ^ 64, v + 4);
        }
        asm volatile("fence.proxy.async.shared::cta;" ::: "memory");
        mbar_arrive(remo_full);
        if (layer) { phase2_duties(0); mbar_wait_sleep(kv_free, 0); }
        if (t > 0) {
          const uint32_t lane = lane_id(), r = lane >> 2, q = lane & 3;
#pragma unroll 1
          for (uint32_t pc = 0; pc < 3; pc++) {
            uint4* hp = scr + OFF_H + ((layer * 8 + j) * 2 + (w - 10)) * 192 + pc * 64 + lane;
            uint32_t hl[8];
            int n = 0;
            hl[4] = 1u;
            while (true) {
              ldg4(hl, hp);
              if (pc < 2) ldg4(hl + 4, hp + 32);
              if (__all_sync(~0u, hl[0] != 0u && hl[4] != 0u)) break;
              __nanosleep(100);
              SPIN_GUARD(n);
            }
            const uint32_t dst = sb + KVS + (w - 10) * 10368 + r * 144 + q * 4;
            if (pc < 2) {
#pragma unroll
              for (int g = 0; g < 8; g++) sts1(dst + pc * 20736 + odd * 16 + g * 16, hl[g]);
              stg4(hp + 32, 0u, 0u, 0u, 0u);
            } else {
              sts1(dst + (odd ? 0 : 128), hl[0]); sts1(dst + 20736 + (odd ? 0 : 128), hl[1]);
            }
            stg4(hp, 0u, 0u, 0u, 0u);
          }
        }
        asm volatile("bar.arrive 1, 192;" ::: "memory");
        mbar_wait_sleep(xb_done, layer);
        if (w == 10 && layer == 1) {
          const uint32_t lane = lane_id();
          stg4(scr + OFF_S + (lane >> 3) * 96 + j * 8 + (lane & 7), 0u, 0u, 0u, 0u);
          stg4(scr + OFF_S + (4 + (lane >> 3)) * 96 + j * 8 + (lane & 7), 0u, 0u, 0u, 0u);
          if (lane < 8) stg4(scr + OFF_S + j * 96 + 64 + lane, 0u, 0u, 0u, 0u);
        }
#pragma unroll 1
        for (uint32_t i = 0; i < 8 && (w == 11 || layer == 1); i++) {
          zero_share(scr + OFF_X + ((w - 10) * 16 + layer * 8 + i) * SLAB, j, lane_id());
          __nanosleep(500);
        }
      }
      phase2_duties(1);
    }
  } else {
    asm volatile("setmaxnreg.inc.sync.aligned.u32 240;");
    const bool lead = lane_id() == 0;
    Ring rg{0, 0};
    uint32_t prev = 0;
    uint32_t X[144];
    float rs0, rs1;
    const bool lead2 = lane_id() < 2;
    uint32_t empty_at;
    asm volatile("mapa.shared::cluster.u32 %0, %1, %2;" : "=r"(empty_at) : "r"(empty0), "r"(lane_id() & 1));
    auto release = [&](uint32_t st) { if (lead2) asm volatile("mbarrier.arrive.shared::cluster.b64 _, [%0];" :: "r"(empty_at + st * 8) : "memory"); };
    auto load_kb = [&](int kb, const uint4* src, const char* lo, uint32_t hoff) {
#pragma unroll
      for (int k = 4 * kb; k < 4 * kb + 4; k++) {
        if (k % 9 == 4) { ldg2(X + 4 * k, lo + k * 512); ldg2(X + 4 * k + 2, lo + hoff + k * 512); }
        else ldg4(X + 4 * k, src + k * 32);
      }
    };
    auto check_kb = [&](bool skip, int kb, const uint4* src, const char* lo, uint32_t hoff) {
      int n = 0;
      while (true) {
        uint32_t m = umin2(umin2(X[16 * kb], X[16 * kb + 4]), umin2(X[16 * kb + 8], X[16 * kb + 12]));
        if (kb & 1) m = umin2(m, X[16 * kb + 4 * (kb >> 1) + 2]);
        if (__all_sync(~0u, m != 0u || skip)) break;
        SPIN_GUARD(n);
        load_kb(kb, src, lo, hoff);
      }
    };
#pragma unroll 1
    for (uint32_t hf = 0; hf < 4; hf++) {
      const uint32_t layer = hf >> 1;
      const bool ffn = hf & 1;
      const uint32_t tag = 1 - layer;
      uint4* const xbase = scr + OFF_X + (layer * 8 + w) * SLAB;
      float aA[32], aB[32];
      {
        const uint32_t lane = lane_id(), r = lane >> 2, q = lane & 3;
        const uint4* src = xbase + (ffn ? 32 * SLAB : 0) + lane;
        const char* lo = (const char*)src - (ffn ? lane * 8 : 0);
        const uint32_t hoff = ffn ? 256 : 8;
        const uint32_t xoff = (w & 1) * 8192 + (16 * (w >> 1) + (lane & 15)) * 128 + (((lane >> 4) ^ (lane & 7)) << 4);
        auto load_x = [&](uint32_t b, uint32_t* d) {
#pragma unroll
          for (int i = 0; i < 4; i++) ldsm4(xs + b * STAGE + (xoff ^ (32 * i)), d[4 * i], d[4 * i + 1], d[4 * i + 2], d[4 * i + 3]);
        };
        auto load_any = [&](int kb) { if (hf == 0) load_x(kb, X + 16 * kb); else load_kb(kb, src, lo, hoff); };
        float m0, m1, v0, v1;
        STAMP(ffn * 16 + 0);
        if (hf == 0) {
          float sum[2][4] = {}, sq0[4][4] = {}, sq1[4][4] = {};
          uint32_t p0, p1;
          mbar_wait(xbar0, 0);
          ldsm4(xs + xoff, p0, p1, X[0], X[1]);
          p0 = __byte_perm(__shfl_sync(~0u, p0, lane & 28), 0, 0x1010); p1 = __byte_perm(__shfl_sync(~0u, p1, lane & 28), 0, 0x1010);
#pragma unroll 3
          for (uint32_t b = 0; b < 9; b++) {
            uint32_t d[16];
            mbar_wait(xbar0 + 8 * b, 0);
            load_x(b, d);
#pragma unroll
            for (int i = 0; i < 16; i++) d[i] = sub_bf16x2(d[i], (i & 1) ? p1 : p0);
#pragma unroll
            for (int g = 0; g < 8; g++) {
              if (!(g & 1)) mma16(sum[(g >> 1) & 1], d[2 * g], d[2 * g + 1], d[2 * g + 2], d[2 * g + 3], 0x3f803f80u, 0x3f803f80u);
              mma8(sq0[g & 3], d[2 * g], d[2 * g + 1], d[2 * g]); mma8(sq1[g & 3], d[2 * g], d[2 * g + 1], d[2 * g + 1]);
            }
          }
          STAMP(1);
          GSTAMP(14);
#pragma unroll
          for (int kb = 0; kb < GD; kb++) load_x(kb, X + 16 * kb);
          release((x_ring - empty0) / 8);
          auto tot = [](float (&c)[4][4], int e) { return (c[0][e] + c[1][e]) + (c[2][e] + c[3][e]); };
          const float a0 = (sum[0][0] + sum[1][0]) * (1.f / 576), a1 = (sum[0][2] + sum[1][2]) * (1.f / 576);
          const uint32_t dg = (lane & 28) + (r >> 1);
          v0 = fmaxf(fmaf(__shfl_sync(~0u, (r & 1) ? tot(sq0, 1) : tot(sq0, 0), dg), 1.f / 576, -a0 * a0), 0.f);
          v1 = fmaxf(fmaf(__shfl_sync(~0u, (r & 1) ? tot(sq1, 3) : tot(sq1, 2), dg), 1.f / 576, -a1 * a1), 0.f);
          m0 = bf_lo(p0) + a0; m1 = bf_lo(p1) + a1;
        } else {
          uint32_t s[3][4];
          const uint4* p = scr + OFF_S + ((ffn ? 16 : 0) + w) * 96 + q * 8 + r;
          const bool third = !ffn && q == 0;
          const uint32_t rdy = ffn ? tag : 1u;
          int n = 0;
          s[2][0] = rdy; s[2][1] = s[2][2] = s[2][3] = 0u;
          while (true) {
            ldg4(s[0], p); ldg4(s[1], p + 32);
            if (third) ldg4(s[2], p + 64);
            if (__all_sync(~0u, ((diff2(s[0][0], s[1][0], rdy) | diff2(s[1][0], s[2][0], rdy)) & 1u) == 0u)) break;
            SPIN_GUARD(n);
          }
          STAMP(ffn * 16 + 1);
          ZSTAMP(1 + ffn, 0);
          GSTAMP(14 + ffn);
#pragma unroll
          for (int kb = 0; kb < GD; kb++) load_kb(kb, src, lo, hoff);
          float t0 = 0.f, t1 = 0.f;
#pragma unroll
          for (int i = 0; i < 3; i++) { t0 += __uint_as_float(s[i][0]); t1 += __uint_as_float(s[i][2]); }
          m0 = quad_sum(t0) * (1.f / 576); m1 = quad_sum(t1) * (1.f / 576);
          const float cnt = ffn ? 72.f : 64.f, inv = ffn ? 1.f / 72 : 1.f / 64;
          v0 = 0.f; v1 = 0.f;
#pragma unroll
          for (int i = 0; i < 3; i++) {
            const float c = (i < 2 || third) ? cnt : 0.f;
            const float d0 = fmaf(__uint_as_float(s[i][0]), inv, -m0), d1 = fmaf(__uint_as_float(s[i][2]), inv, -m1);
            v0 += fmaf(d0 * d0, c, __uint_as_float(s[i][1])); v1 += fmaf(d1 * d1, c, __uint_as_float(s[i][3]));
          }
          v0 = quad_sum(v0) * (1.f / 576); v1 = quad_sum(v1) * (1.f / 576);
        }
        rs0 = rsqrtf(v0 + 1e-5f); rs1 = rsqrtf(v1 + 1e-5f);
        const uint32_t mean0 = pack_bf16(m0, m0), mean1 = pack_bf16(m1, m1);
#pragma unroll
        for (int kb = 0; kb < 9; kb++) {
          check_kb(hf == 0, kb, src, lo, hoff);
          if (kb + GD < 9) load_any(kb + GD);
          if (kb + GD == 8 && hf == 0 && lead) mbar_arrive(x_done);
#pragma unroll
          for (int i = 16 * kb; i < 16 * kb + 16; i++) X[i] = sub_bf16x2(X[i], (i & 1) ? mean1 : mean0);
          ZSTAMP(1 + ffn, 1 + 3 * kb);
          mbar_wait(full0 + rg.st * 8, rg.ph);
          ZSTAMP(1 + ffn, 2 + 3 * kb);
          const uint64_t desc = DESC_HI | ((sd + rg.st * STAGE) >> 4);
          wg_fence();
#pragma unroll
          for (int i = 0; i < 4; i++) wgmma_rs_n64(aA, X + 4 * (4 * kb + i), desc + i * 128, kb + i != 0);
          if (kb == 8) { wg_commit(); wg_wait<1>(); wg_fence(); }
#pragma unroll
          for (int i = 0; i < 4; i++) wgmma_rs_n64(aB, X + 4 * (4 * kb + i), desc + 512 + i * 128, kb + i != 0);
          wg_commit();
          wg_wait<1>();
          ZSTAMP(1 + ffn, 3 + 3 * kb);
          if (kb > 0) release(prev);
          prev = rg.st; rg.next();
        }
        ZSTAMP(1 + ffn, 28);
        ZSTAMP(4, 0);
        STAMP(ffn * 16 + 2);
      }
      if (!ffn) {
      const uint32_t lane = lane_id(), r = lane >> 2, q = lane & 3;
      const uint32_t kvrow = sb + KVS + (w & 1) * 10368 + (16 * (w >> 1)) * 144;
      uint32_t Q[18], Km[3][8], Ke[3][4];
      const bool edge = (t == 0 && w < 2);
      const uint32_t row0 = edge ? sb + KVS + 8 * 144 : kvrow + (lane & 7) * 144, row1 = kvrow + (8 + (lane & 7)) * 144;
      {
        const uint32_t dst = kvrow + (8 + r) * 144 + q * 4 + odd * 16, dstr = dst + (odd ? -16 : 128);
        const bool edge_out = w >= 6 && t < 15;
        uint4* const hp = scr + TILE + OFF_H + ((layer * 8 + j) * 2 + (w & 1)) * 192 + lane;
        auto put_kv = [&](float (&a)[32], int part, int half) {
          uint32_t hl[4];
#pragma unroll
          for (int i = 0; i < 16; i++) asm volatile("" : "+f"(a[16 * half + i]) :: "memory");
#pragma unroll
          for (int i = 0; i < 4; i++) {
            const int g = 4 * half + i;
            hl[i] = pack_bf16(a[4 * g + 2] * rs1, a[4 * g + 3] * rs1);
            sts1(dst + part * 20736 + g * 16, pack_bf16(a[4 * g] * rs0, a[4 * g + 1] * rs0)); sts1(dst + part * 20736 + 8 * 144 + g * 16, hl[i]);
          }
          if (edge_out) stg4(hp + part * 64 + half * 32, nz(hl[0]), hl[1], hl[2], hl[3]);
        };
        put_kv(aA, 0, 0); put_kv(aA, 0, 1);
        wg_wait<0>();
        release(prev);
        float aR[12];
        mbar_wait(rem_full, layer);
        const uint64_t dr = DESC_REM | ((sd + REM) >> 4);
        wg_fence();
#pragma unroll
        for (int s = 0; s < 36; s++) {
          wgmma_rs_n24(aR, X + 4 * s, dr + s * 16, s != 0);
          if (s == 4) put_kv(aB, 1, 0);
          if (s == 16) put_kv(aB, 1, 1);
        }
        wg_commit();
#pragma unroll
        for (int kb = 0; kb < 9; kb++) {
          if (!(kb & 1)) mbar_wait(full0 + rg.st * 8, rg.ph);
          const uint64_t desc = DESC_HI | ((sd + rg.st * STAGE + (kb & 1) * 8192) >> 4);
          wg_fence();
#pragma unroll
          for (int i = 0; i < 4; i++) wgmma_rs_n64(aB, X + 4 * (4 * kb + i), desc + i * 128, kb + i != 0);
          wg_commit();
          wg_wait<1>();
          if (kb > 0 && !(kb & 1)) release(prev);
          if ((kb & 1) || kb == 8) { prev = rg.st; rg.next(); }
          if (kb == 0) {
            pin(aR);
            const uint32_t k1 = pack_bf16(aR[2] * rs1, aR[3] * rs1), v1 = pack_bf16(aR[6] * rs1, aR[7] * rs1);
            if (edge_out) stg4(hp + 128, nz(k1), v1, 0u, 0u);
            sts1(dstr, pack_bf16(aR[0] * rs0, aR[1] * rs0)); sts1(dstr + 8 * 144, k1);
            sts1(dstr + 20736, pack_bf16(aR[4] * rs0, aR[5] * rs0)); sts1(dstr + 20736 + 8 * 144, v1);
            Q[16] = pack_bf16(aR[8], aR[9]); Q[17] = pack_bf16(aR[10], aR[11]);
            if (w < 4) asm volatile("bar.arrive 2, 256;" ::: "memory");
          }
          if (kb == 6) mbar_wait(remo_full, layer);
          if (kb == 8) {
            if (w < 4) asm volatile("bar.sync 1, 192;" ::: "memory");
            else asm volatile("bar.sync 2, 256;" ::: "memory");
#pragma unroll
            for (int nt = 0; nt < 3; nt++) {
              const uint32_t ra = (nt == 0 ? row0 : row1 + (nt - 1) * 8 * 144);
              ldsm4(ra + odd * 16 + (lane >> 3) * 16, Km[nt][0], Km[nt][1], Km[nt][2], Km[nt][3]);
              ldsm4(ra + odd * 16 + 64 + (lane >> 3) * 16, Km[nt][4], Km[nt][5], Km[nt][6], Km[nt][7]);
              ldsm4(ra + (odd ? 0 : 32) + (lane >> 3) * 32, Ke[nt][0], Ke[nt][1], Ke[nt][2], Ke[nt][3]);
            }
            const uint32_t ge = (2u << q) - 1, le = 0xfu << q, on = edge ? 0u : ~0u;
            const uint32_t bits = odd ? 0xfu | ((le & 0xfu) << 4) | (ge << 8) : ge | 0xf0u | (le << 8);
#pragma unroll
            for (int h = 0; h < 4; h++) {
              const uint32_t ma = bitmask(bits, h), mb = bitmask(bits, 4 + h), mc = bitmask(bits, 8 + h);
              Km[0][2 * h] &= ma & on; Km[0][2 * h + 1] &= mb & on; Ke[0][h] &= mc & on;
#pragma unroll
              for (int nt = 1; nt < 3; nt++) { Km[nt][2 * h] &= ma; Km[nt][2 * h + 1] &= mb; Ke[nt][h] &= mc; }
            }
          }
        }
        wg_wait<0>();
        release(prev);
        pin(aB);
        STAMP(3);
#pragma unroll
        for (int i = 0; i < 16; i++) Q[i] = pack_bf16(aB[2 * i], aB[2 * i + 1]);
      }
      uint32_t res[18] = {};
      if (layer) {
        const uint4* p = xbase + ((9 * j + 1) >> 1) * 32 + lane;
#pragma unroll
        for (int i = 0; i < 4; i++) ldg4(res + 4 * i, p + i * 32);
        ldg2(res + 16, odd ? (const char*)(p - 32) + 8 : (const char*)(p + 4 * 32));
      }
      {
        uint32_t V01[12][2], V2[12];
        const uint32_t rv = ((lane & 8) ? row1 : row0) + 20736, rw = row1 + 8 * 144 + 20736;
#pragma unroll
        for (int i = 0; i < 4; i++) ldsm4t(rv + odd * 16 + i * 32 + (lane >> 4) * 16, V01[2 * i][0], V01[2 * i][1], V01[2 * i + 1][0], V01[2 * i + 1][1]);
#pragma unroll
        for (int i = 0; i < 2; i++) ldsm4t(rv + (odd ? 0 : 32) + i * 64 + (lane >> 4) * 32, V01[8 + 2 * i][0], V01[8 + 2 * i][1], V01[9 + 2 * i][0], V01[9 + 2 * i][1]);
        ldsm4t(rw + odd * 16 + (lane >> 3) * 16, V2[0], V2[1], V2[2], V2[3]);
        ldsm4t(rw + odd * 16 + 64 + (lane >> 3) * 16, V2[4], V2[5], V2[6], V2[7]);
        ldsm4t(rw + (odd ? 0 : 32) + (lane >> 3) * 32, V2[8], V2[9], V2[10], V2[11]);
        const bool up0 = 2 * q > r, up1 = 2 * q + 1 > r;
        const uint32_t upm = (up0 ? 0xffffu : 0u) | (up1 ? 0xffff0000u : 0u);
        const float c0 = 0.23570226039551584f * 1.4426950408889634f * rs0, c1 = 0.23570226039551584f * 1.4426950408889634f * rs1;
        const float masked = edge ? -1e9f * 1.4426950408889634f * rcp(c0) : 0.f;
        uint32_t Om[16], Oe[8];
        uint4* const po = xbase + 16 * SLAB + ((9 * j + 1) >> 1) * 32 + lane;
#pragma unroll
        for (int h = 0; h < 4; h++) {
          const uint32_t e0 = odd ? Q[(4 * h + 16) % 18] : Q[4 * h + 4], e1 = odd ? Q[(4 * h + 17) % 18] : Q[4 * h + 5];
          float S[3][4];
#pragma unroll
          for (int nt = 0; nt < 3; nt++) {
            mma16c(S[nt], Q + 4 * h, Km[nt][2 * h], Km[nt][2 * h + 1], nt == 0 ? masked : 0.f);
            mma8(S[nt], e0, e1, Ke[nt][h]);
          }
          const float s00 = up0 ? S[0][0] : S[1][0], s01 = up1 ? S[0][1] : S[1][1];
          const float s10 = up0 ? S[1][2] : S[2][2], s11 = up1 ? S[1][3] : S[2][3];
          const float m0 = quad_max(fmaxf(s00, s01)) * c0, m1 = quad_max(fmaxf(s10, s11)) * c1;
          const float p00 = ex2(fmaf(s00, c0, -m0)), p01 = ex2(fmaf(s01, c0, -m0)), p10 = ex2(fmaf(s10, c1, -m1)), p11 = ex2(fmaf(s11, c1, -m1));
          const float i0 = rcp(quad_sum(p00 + p01)), i1 = rcp(quad_sum(p10 + p11));
          const uint32_t p0 = pack_bf16(p00 * i0, p01 * i0), p1 = pack_bf16(p10 * i1, p11 * i1);
          const uint32_t pf[4] = {p0 & upm, 0u, p0 & ~upm, p1 & upm};
#pragma unroll
          for (int gi = 0; gi < 3; gi++) {
            const int g = gi < 2 ? 2 * h + gi : 8 + h;
            float o[4];
            mma16c(o, pf, V01[g][0], V01[g][1], 0.f);
            mma8(o, 0u, p1 & ~upm, V2[g]);
            uint32_t* d = gi < 2 ? Om + 2 * g : Oe + 2 * h;
            d[0] = pack_bf16(o[0], o[1]); d[1] = pack_bf16(o[2], o[3]);
          }
          if (h > 0) {
#pragma unroll
            for (int e = 0; e < 2; e++) {
              if (!odd && q < h) Om[4 * h + e] = Oe[2 * h - 2 + e];
              if (odd && q >= h) Om[4 * h - 2 + e] = Oe[2 * h + e];
            }
            stg4(po + (h - 1) * 32, nz(Om[4 * h - 4]), Om[4 * h - 3], Om[4 * h - 2], Om[4 * h - 1]);
          }
        }
        STAMP(4);
        stg4(po + 96, nz(Om[12]), Om[13], Om[14], Om[15]);
        stg2((char*)(odd ? po - 16 : po + 128) - lane * 8, nz(odd ? Oe[0] : Oe[6]), odd ? Oe[1] : Oe[7]);
      }
      if (lane == 0) asm volatile("st.relaxed.gpu.global.b32 [%0], %1;" :: "l"(scr + OFF_S + (8 + w) * 96 + j * 8), "r"(tag) : "memory");
      {
        if (layer == 0) {
          const uint32_t xrow = (w & 1) * 8192 + (16 * (w >> 1) + (lane & 15)) * 128;
          uint32_t u0, u1;
          mbar_wait(xbar0, 1); mbar_wait(xbar0 + 8, 1);
#pragma unroll
          for (int i = 0; i < 5; i++) {
            const uint32_t g = i < 4 ? j + odd + 2 * i : j + (odd ? 0 : 8);
            const uint32_t a = sb + PARK + (g >> 3) * STAGE + xrow;
            if (i < 4) ldsm4(a + ((((g & 7) + (lane >> 4)) ^ (lane & 7)) << 4), res[4 * i], res[4 * i + 1], res[4 * i + 2], res[4 * i + 3]);
            else ldsm4(a + (((g & 7) ^ (lane & 7)) << 4), res[16], res[17], u0, u1);
          }
        }
        const uint4* src = xbase + 16 * SLAB + lane;
        {
          const uint4* fp = scr + OFF_S + (8 + w) * 96 + (lane & 7) * 8;
          int n = 0;
          STAMP(8);
          while (true) {
            uint32_t f;
            asm volatile("ld.relaxed.gpu.global.b32 %0, [%1];" : "=r"(f) : "l"(fp) : "memory");
            if (__all_sync(~0u, f == tag)) break;
            SPIN_GUARD(n);
          }
          STAMP(9);
        }
#pragma unroll
        for (int kb = 0; kb < GD; kb++) load_kb(kb, src, (const char*)src - lane * 8, 256);
        float acc[36];
#pragma unroll
        for (int i = 0; i < 18; i++) { acc[2 * i] = bf_lo(res[i]); acc[2 * i + 1] = bf_hi(res[i]); }
#pragma unroll
        for (int kb = 0; kb < 9; kb++) {
          check_kb(false, kb, src, (const char*)src - lane * 8, 256);
          if (kb + GD < 9) load_kb(kb + GD, src, (const char*)src - lane * 8, 256);
          if (!(kb & 1)) mbar_wait(full0 + rg.st * 8, rg.ph);
          const uint32_t base = sd + rg.st * STAGE + (kb & 1) * 8192;
          const uint64_t d0 = DESC_HI | ((base >> 4) + (((sd + REM + 27648 + (kb >> 1) * 2048 + (kb & 1) * 64 - base) >> 4) << 16));
          wg_fence();
#pragma unroll
          for (int i = 0; i < 4; i++) wgmma_rs_n72(acc, X + 4 * (4 * kb + i), d0 - (uint64_t)(i * ((127u << 16) - 128u)), 1);
          wg_commit();
          wg_wait<1>();
          if (kb > 0 && !(kb & 1)) release(prev);
          if ((kb & 1) || kb == 8) { prev = rg.st; rg.next(); }
        }
        wg_wait<0>();
        release(prev);
        pin(acc);
        STAMP(10);
#pragma unroll
        for (int i = 0; i < 18; i++) res[i] = pack_bf16(acc[2 * i], acc[2 * i + 1]);
        if (j < PRI) put72(xbase + 32 * SLAB, j, lane, res, res[16], res[17]);
        publish_stats<9>(scr + OFF_S + (16 + w) * 96 + j * 8, acc, tag, lane);
        if (j >= PRI) put72(xbase + 32 * SLAB, j, lane, res, res[16], res[17]);
      }
      continue;
      }
      const uint32_t hp = sb + PARK + w * 512 + lane_id() * 16;
      auto pack8 = [&](float (&a)[32], int p, uint32_t* o) {
#pragma unroll
        for (int e = 0; e < 8; e++) asm volatile("" : "+f"(a[8 * p + e]) :: "memory");
#pragma unroll
        for (int e = 0; e < 4; e++) o[e] = pack_bf16(a[8 * p + 2 * e], a[8 * p + 2 * e + 1]);
      };
      const float ka0 = 0.7978845608028654f * rs0, kb0 = 0.044715f * ka0 * rs0 * rs0, ku0 = 0.5f * rs0 * rs0;
      const float ka1 = 0.7978845608028654f * rs1, kb1 = 0.044715f * ka1 * rs1 * rs1, ku1 = 0.5f * rs1 * rs1;
      auto packu8 = [&](int p, uint32_t* o) {
#pragma unroll
        for (int e = 0; e < 8; e++) asm volatile("" : "+f"(aA[8 * p + e]) :: "memory");
#pragma unroll
        for (int e = 0; e < 4; e++) o[e] = pack_bf16(aA[8 * p + 2 * e] * ((e & 1) ? ku1 : ku0), aA[8 * p + 2 * e + 1] * ((e & 1) ? ku1 : ku0));
      };
      auto geglu8 = [&](int p, uint32_t* u) {
#pragma unroll
        for (int e = 0; e < 8; e++) asm volatile("" : "+f"(aB[8 * p + e]) :: "memory");
        float h[8];
#pragma unroll
        for (int e = 0; e < 8; e++) {
          const float g = aB[8 * p + e];
          h[e] = fmaf(g, tanh_ap(g * fmaf(g * g, (e & 2) ? kb1 : kb0, (e & 2) ? ka1 : ka0)), g);
        }
#pragma unroll
        for (int e = 0; e < 4; e++) u[e] = mul_bf16x2(pack_bf16(h[2 * e], h[2 * e + 1]), u[e]);
      };
      auto box = [&](int b, auto&& filler) {
        const int kb = b < 9 ? b : b - 9;
        if (!(b & 1)) { if (b == 0) mbar_wait_trap(full0 + rg.st * 8, rg.ph); else mbar_wait(full0 + rg.st * 8, rg.ph); }
        const uint64_t desc = DESC_HI | ((sd + rg.st * STAGE + (b & 1) * 8192) >> 4);
        wg_fence();
#pragma unroll
        for (int i = 0; i < 4; i++) {
          if (b < 9) wgmma_rs_n64(aA, X + 4 * (4 * kb + i), desc + i * 128, kb + i != 0);
          else wgmma_rs_n64(aB, X + 4 * (4 * kb + i), desc + i * 128, kb + i != 0);
          if (i == 2) filler();
        }
        wg_commit();
        if (b & 1) { prev = rg.st; rg.next(); } else { wg_wait<1>(); release(prev); }
      };
      auto nop = [] {};
      auto step = [&](int st, auto&& filler) { box(2 * st, nop); box(2 * st + 1, filler); };
#pragma unroll
      for (int p = 0; p < 4; p++) { uint32_t o[4]; packu8(p, o); sts4(hp + p * 4096, o); }
      box(0, nop);
      if (lead) mbar_arrive(xb_done);
#pragma unroll 1
      for (int c = 1;; c++) {
        const uint32_t hc = hp + c * 4 * 4096;
#pragma unroll
        for (int b = 1; b < 18; b++) box(b, [&] {
          if ((b & 1) && b < 8) { uint32_t o[4]; const uint32_t a = hc - (4 - (b >> 1)) * 4096; lds4(a, o); geglu8(b >> 1, o); sts4(a, o); }
          if ((b & 1) && b > 10) { uint32_t o[4]; packu8((b - 11) >> 1, o); if (c < 8) sts4(hc + ((b - 11) >> 1) * 4096, o); } });
        ZSTAMP(4, c);
        if (c == 8) break;
        box(0, nop);
      }
      wg_wait<0>();
      STAMP(21);
      GSTAMP(19);
      auto unpark = [&](int kb) {
#pragma unroll
        for (int s = 4 * kb; s < 4 * kb + 4; s++) lds4(hp + s * 4096, X + 4 * s);
      };
      unpark(0);
      uint32_t U[16];
#pragma unroll
      for (int p = 0; p < 4; p++) packu8(p, U + 4 * p);
#pragma unroll
      for (int b = 0; b < 8; b++) box(b, [&] {
        if (b < 7) unpark(b + 1);
        if (b & 1) {
          geglu8(b >> 1, U + 2 * (b - 1));
          if (rg.ph > 1) sts4(hp, U + 2 * (b - 1));
#pragma unroll
          for (int i = 0; i < 4; i++) X[128 + 2 * (b - 1) + i] = U[2 * (b - 1) + i];
        } });
      STAMP(24);
      if (layer == 0 && lead) mbar_arrive(park_free);
      const uint32_t lane2 = lane_id();
      uint4* const pw = scr + OFF_P + (j * 8 + w) * SLAB + lane2;
      const uint4* const pr = scr + OFF_P + w * SLAB + 4 * j * 32 + lane2;
      auto put_part = [&](float (&a)[32], int p, uint32_t chunk) {
        uint32_t o[4];
        pack8(a, p, o);
        stg4(pw + (chunk * 4 + p) * 32, (o[0] & ~1u) | tag, o[1], o[2], o[3]);
      };
      uint4* const xb = xbase + 32 * SLAB + 4 * j * 32;
      auto slot = [&](int p) { return sb + w * 2048 + (p < 3 ? PARK + p * 16384 : KVS + (p - 3) * 16384); };
      auto fetch = [&](int p) {
        bulk_load(slot(p), p ? scr + OFF_P + (((j - p) & 7) * 8 + w) * SLAB + 4 * j * 32 : xb, 2048, p ? pbar0 + w * 8 : res_full, true);
      };
#pragma unroll 1
      for (int sp = 0;; sp++) {
        const uint32_t ca = sp == 0 ? 8 : ((j + 2 * sp) & 7), cb = (j + 2 * sp + 1) & 7;
        if (sp == 1 && lead) mbar_arrive(c8_go);
#pragma unroll
        for (int st = 4; st < 9; st++) step(st, [&] {
          if (st == 5 || st == 6) { put_part(aA, 2 * (st - 5), ca); put_part(aA, 2 * (st - 5) + 1, ca); }
          if (st == 8 && sp > 0) { if (sp == 3) mbar_wait(c8_done, layer); fetch(2 * sp - 2); } });
        STAMP(25 + sp);
        if (sp == 3) break;
#pragma unroll
        for (int st = 0; st < 4; st++) step(st, [&] {
          if (st < 2) { put_part(aB, 2 * st, cb); put_part(aB, 2 * st + 1, cb); }
          if (st == 3 && sp > 0) fetch(2 * sp - 1); });
      }
      auto load_p = [&](int p, uint32_t* d) {
#pragma unroll
        for (int i = 0; i < 4; i++) ldg4(d + 4 * i, pr + ((j - p) & 7) * 8 * SLAB + i * 32);
      };
#pragma unroll
      for (int b = 0; b < 9; b++) {
        box(b, [&] {
          if (b == 1) {
#pragma unroll
            for (int p = 0; p < 4; p++) put_part(aB, p, (j + 7) & 7);
          }
          if (b == 3) { load_p(5, X); load_p(6, X + 16); }
          if (b == 7) load_p(7, X + 32); });
      }
      mbar_wait(res_full, layer);
      mbar_wait(pbar0 + w * 8, layer);
#pragma unroll
      for (int p = 1; p < 5; p++)
#pragma unroll
        for (int i = 0; i < 4; i++) lds4(slot(p) + lane2 * 16 + i * 512, X + 48 + 16 * p + 4 * i);
#pragma unroll
      for (int i = 0; i < 4; i++) {
        const bool split = j == 2 * i + 1;
        const uint32_t a = slot(0) + i * 512 + (split ? lane2 * 8 : lane2 * 16);
        lds2(a, X + 48 + 4 * i); lds2(a + (split ? 256 : 8), X + 50 + 4 * i);
      }
      wg_wait<0>();
      release(rg.st); rg.next();
      pin(aA);
      STAMP(22);
      GSTAMP(20);
      {
        const uint32_t lane = lane2, r = lane >> 2, q = lane & 3;
        const uint32_t eye = r == 2 * q ? 0x3f80u : r == 2 * q + 1 ? 0x3f800000u : 0u;
        auto bad = [&](const uint32_t* d) { return diff2(d[0], d[4], tag) | diff2(d[8], d[12], tag); };
        auto add = [&](const uint32_t* d) {
#pragma unroll
          for (int g = 0; g < 8; g++) mma8(aA + 4 * g, d[2 * g], d[2 * g + 1], eye);
        };
        int n = 0;
        while (!__all_sync(~0u, ((or3(bad(X), bad(X + 16), bad(X + 64)) | or3(bad(X + 80), bad(X + 96), bad(X + 112))) & 1u) == 0u)) {
          SPIN_GUARD(n);
          load_p(5, X); load_p(6, X + 16);
#pragma unroll
          for (int p = 1; p < 5; p++) load_p(p, X + 48 + 16 * p);
        }
        add(X); add(X + 16);
#pragma unroll
        for (int p = 4; p >= 0; p--) add(X + 48 + 16 * ((p + 1) % 5));
        STAMP(11);
        while (!__all_sync(~0u, (bad(X + 32) & 1u) == 0u)) { SPIN_GUARD(n); load_p(7, X + 32); }
        add(X + 32);
        STAMP(12);
        uint32_t res[16];
#pragma unroll
        for (int i = 0; i < 16; i++) res[i] = pack_bf16(aA[2 * i], aA[2 * i + 1]);
        if (layer == 0) {
          uint4* p = xbase + 8 * SLAB + 4 * j * 32 + lane;
          auto put = [&] {
#pragma unroll
            for (int i = 0; i < 4; i++) stg4(p + i * 32, nz(res[4 * i]), res[4 * i + 1], nz(res[4 * i + 2]), res[4 * i + 3]);
          };
          if (j < PRI) put();
          publish_stats<8>(scr + OFF_S + w * 96 + j * 8, aA, 1u, lane);
          if (j >= PRI) put();
          if (lane == 0) mbar_arrive(kv_free);
        } else {
          const uint32_t tb = slot(0);
          __syncwarp();
#pragma unroll
          for (int i = 0; i < 4; i++) {
            const uint32_t row = (lane2 & 7) + (lane2 & 8), g = 2 * i + (lane2 >> 4);
            asm volatile("stmatrix.sync.aligned.m8n8.x4.shared.b16 [%0], {%1,%2,%3,%4};"
                         :: "r"(tb + row * 128 + ((g ^ (row & 7)) << 4)), "r"(res[4 * i]), "r"(res[4 * i + 1]), "r"(res[4 * i + 2]), "r"(res[4 * i + 3]) : "memory");
          }
          __syncwarp();
#pragma unroll
          for (int i = 0; i < 4; i++) {
            const uint32_t row = 4 * i + (lane2 >> 3), g = lane2 & 7;
            uint32_t v[4];
            lds4(tb + row * 128 + ((g ^ (row & 7)) << 4), v);
            *(uint4*)(out + (128 * t + 32 * (w >> 1) + 2 * row + (w & 1)) * 576 + 64 * j + 8 * g) = make_uint4(v[0], v[1], v[2], v[3]);
          }
        }
      }
      STAMP(23);
    }
  }
}

typedef CUresult (*EncodeFn)(CUtensorMap*, CUtensorMapDataType, cuuint32_t, void*, const cuuint64_t*, const cuuint64_t*,
                             const cuuint32_t*, const cuuint32_t*, CUtensorMapInterleave, CUtensorMapSwizzle,
                             CUtensorMapL2promotion, CUtensorMapFloatOOBfill);

CUtensorMap make_map(EncodeFn f, const void* p, uint64_t cols, uint64_t rows, bool rem = false) {
  CUtensorMap m;
  cuuint64_t dims[2] = {cols, rows};
  cuuint64_t str[1] = {cols * 2};
  cuuint32_t box[2] = {rem ? 8u : 64u, rem ? 144u : 64u};
  cuuint32_t es[2] = {1, 1};
  f(&m, CU_TENSOR_MAP_DATA_TYPE_BFLOAT16, 2, const_cast<void*>(p), dims, str, box, es, CU_TENSOR_MAP_INTERLEAVE_NONE,
    rem ? CU_TENSOR_MAP_SWIZZLE_NONE : CU_TENSOR_MAP_SWIZZLE_128B, CU_TENSOR_MAP_L2_PROMOTION_NONE, CU_TENSOR_MAP_FLOAT_OOB_FILL_NONE);
  return m;
}

}

extern "C" void kernel_launch(void* const* d_in, const int* in_sizes, int n_in, void* d_out, int out_size) {
  void* fn = nullptr;
  cudaDriverEntryPointQueryResult qr;
  cudaGetDriverEntryPoint("cuTensorMapEncodeTiled", &fn, cudaEnableDefault, &qr);
  EncodeFn enc = (EncodeFn)fn;
  Maps maps;
  maps.m[0] = make_map(enc, d_in[1], 1728, 576); maps.m[1] = make_map(enc, d_in[2], 576, 576);
  maps.m[2] = make_map(enc, d_in[4], 4608, 576); maps.m[3] = make_map(enc, d_in[5], 4608, 576); maps.m[4] = make_map(enc, d_in[6], 576, 4608);
  maps.m[5] = make_map(enc, d_in[1], 1728, 576, true); maps.m[6] = make_map(enc, d_in[2], 576, 576, true);
  {
    cuuint64_t dims[3] = {576, 1024, 2}, str[2] = {2304, 1152};
    cuuint32_t box[3] = {64, 64, 2}, es[3] = {1, 1, 1};
    enc(&maps.m[7], CU_TENSOR_MAP_DATA_TYPE_BFLOAT16, 3, d_in[0], dims, str, box, es, CU_TENSOR_MAP_INTERLEAVE_NONE,
        CU_TENSOR_MAP_SWIZZLE_128B, CU_TENSOR_MAP_L2_PROMOTION_NONE, CU_TENSOR_MAP_FLOAT_OOB_FILL_NONE);
  }
  void* scr = nullptr;
  cudaGetSymbolAddress(&scr, g_scratch);
  cudaFuncSetAttribute(mega_kernel, cudaFuncAttributeMaxDynamicSharedMemorySize, SMEM_BYTES);
  cudaLaunchConfig_t cfg = {};
  cfg.gridDim = dim3(128); cfg.blockDim = dim3(384); cfg.dynamicSmemBytes = SMEM_BYTES; cfg.stream = cudaStreamPerThread;
  cudaLaunchAttribute at[1];
  at[0].id = cudaLaunchAttributeClusterDimension; at[0].val.clusterDim.x = 2; at[0].val.clusterDim.y = 1; at[0].val.clusterDim.z = 1;
  cfg.attrs = at; cfg.numAttrs = 1;
  int dev = 0, sms = 0, clusters = 0;
  cudaGetDevice(&dev);
  cudaDeviceGetAttribute(&sms, cudaDevAttrMultiProcessorCount, dev);
  cudaOccupancyMaxActiveClusters(&clusters, mega_kernel, &cfg);
  if (sms == 132 && clusters == 66) cfg.gridDim = dim3(132);
  cudaLaunchKernelEx(&cfg, mega_kernel, maps, (uint4*)scr, (__nv_bfloat16*)d_out);
}
```

```cpp
#include <cuda_runtime.h>
#include <cuda.h>
#include <cuda_bf16.h>
#include <stdint.h>

#define TRACE 0
#define GUARD 0
#define ZT 0

namespace {

constexpr int NST = 6;
constexpr int STAGE = 16384;
constexpr int PARK = NST * STAGE;
constexpr int REM = PARK + 49152;
constexpr int KVS = REM + 40960;
constexpr int PIECE = PARK + 7 * STAGE;
constexpr int HSTG = KVS + 16384;
constexpr int BARS = KVS + 41472;
constexpr int TRC = BARS + 512;
constexpr int SMEM_BYTES = TRC + (TRACE ? 512 : 0);
static_assert(NST == 6, "the producer addresses empty barriers as full + 48");
static_assert(BARS >= PARK + 131072, "barriers overlap park");
static_assert(SMEM_BYTES <= 232448, "smem");

constexpr int SLAB = 36 * 32;
constexpr int SPIN_MAX = 1 << 17;
constexpr uint32_t PRI = 4;
constexpr int GD = 3;
constexpr int OFF_S = 0;
constexpr int OFF_H = OFF_S + 3 * 8 * 96;
constexpr int OFF_X = OFF_H + 2 * 8 * 384;
constexpr int OFF_P = OFF_X + 6 * 8 * SLAB;
constexpr int TILE = OFF_P + 8 * 8 * SLAB;
constexpr int OFF_R = 16 * TILE;
constexpr int OFF_F = OFF_R + 8 * 2304;
constexpr int SCRATCH = OFF_F + 128 * 8;

}

__device__ uint4 g_scratch[SCRATCH];

namespace {

constexpr uint64_t DESC_HI = 0x4000004000000000ull;
constexpr uint64_t DESC_REM = (576ull << 32) | (8u << 16);
__device__ __forceinline__ void wgmma_rs_n64(float (&d)[32], const uint32_t* a, uint64_t desc, int scale_d) {
  asm volatile("{\n.reg .pred p;\nsetp.ne.b32 p, %37, 0;\n"
    "wgmma.mma_async.sync.aligned.m64n64k16.f32.bf16.bf16 "
    "{%0, %1, %2, %3, %4, %5, %6, %7, %8, %9, %10, %11, %12, %13, %14, %15, %16, %17, %18, %19, %20, %21, %22, %23, %24, %25, %26, %27, %28, %29, %30, %31}, "
    "{%32, %33, %34, %35}, %36, p, 1, 1, 1;\n}\n"
    : "+f"(d[0]), "+f"(d[1]), "+f"(d[2]), "+f"(d[3]), "+f"(d[4]), "+f"(d[5]), "+f"(d[6]), "+f"(d[7]), "+f"(d[8]), "+f"(d[9]), "+f"(d[10]), "+f"(d[11]), "+f"(d[12]), "+f"(d[13]), "+f"(d[14]), "+f"(d[15]), "+f"(d[16]), "+f"(d[17]), "+f"(d[18]), "+f"(d[19]), "+f"(d[20]), "+f"(d[21]), "+f"(d[22]), "+f"(d[23]), "+f"(d[24]), "+f"(d[25]), "+f"(d[26]), "+f"(d[27]), "+f"(d[28]), "+f"(d[29]), "+f"(d[30]), "+f"(d[31])
    : "r"(a[0]), "r"(a[1]), "r"(a[2]), "r"(a[3]), "l"(desc), "r"(scale_d));
}
__device__ __forceinline__ void wgmma_rs_n72(float (&d)[36], const uint32_t* a, uint64_t desc, int scale_d) {
  asm volatile("{\n.reg .pred p;\nsetp.ne.b32 p, %41, 0;\n"
    "wgmma.mma_async.sync.aligned.m64n72k16.f32.bf16.bf16 "
    "{%0, %1, %2, %3, %4, %5, %6, %7, %8, %9, %10, %11, %12, %13, %14, %15, %16, %17, %18, %19, %20, %21, %22, %23, %24, %25, %26, %27, %28, %29, %30, %31, %32, %33, %34, %35}, "
    "{%36, %37, %38, %39}, %40, p, 1, 1, 1;\n}\n"
    : "+f"(d[0]), "+f"(d[1]), "+f"(d[2]), "+f"(d[3]), "+f"(d[4]), "+f"(d[5]), "+f"(d[6]), "+f"(d[7]), "+f"(d[8]), "+f"(d[9]), "+f"(d[10]), "+f"(d[11]), "+f"(d[12]), "+f"(d[13]), "+f"(d[14]), "+f"(d[15]), "+f"(d[16]), "+f"(d[17]), "+f"(d[18]), "+f"(d[19]), "+f"(d[20]), "+f"(d[21]), "+f"(d[22]), "+f"(d[23]), "+f"(d[24]), "+f"(d[25]), "+f"(d[26]), "+f"(d[27]), "+f"(d[28]), "+f"(d[29]), "+f"(d[30]), "+f"(d[31]), "+f"(d[32]), "+f"(d[33]), "+f"(d[34]), "+f"(d[35])
    : "r"(a[0]), "r"(a[1]), "r"(a[2]), "r"(a[3]), "l"(desc), "r"(scale_d));
}
__device__ __forceinline__ void wgmma_rs_n24(float (&d)[12], const uint32_t* a, uint64_t desc, int scale_d) {
  asm volatile("{\n.reg .pred p;\nsetp.ne.b32 p, %17, 0;\n"
    "wgmma.mma_async.sync.aligned.m64n24k16.f32.bf16.bf16 "
    "{%0, %1, %2, %3, %4, %5, %6, %7, %8, %9, %10, %11}, "
    "{%12, %13, %14, %15}, %16, p, 1, 1, 1;\n}\n"
    : "+f"(d[0]), "+f"(d[1]), "+f"(d[2]), "+f"(d[3]), "+f"(d[4]), "+f"(d[5]), "+f"(d[6]), "+f"(d[7]), "+f"(d[8]), "+f"(d[9]), "+f"(d[10]), "+f"(d[11])
    : "r"(a[0]), "r"(a[1]), "r"(a[2]), "r"(a[3]), "l"(desc), "r"(scale_d));
}

__device__ __forceinline__ void mbar_init(uint32_t a, uint32_t c) { asm volatile("mbarrier.init.shared::cta.b64 [%0], %1;" :: "r"(a), "r"(c)); }
__device__ __forceinline__ void mbar_arrive(uint32_t a) { asm volatile("mbarrier.arrive.shared::cta.b64 _, [%0];" :: "r"(a) : "memory"); }
__device__ __forceinline__ void mbar_wait_trap(uint32_t a, uint32_t ph) {
  asm volatile("{\n.reg .pred p;\n.reg .u32 n;\nmov.u32 n, 0;\n"
               "W: mbarrier.try_wait.parity.shared::cta.b64 p, [%0], %1;\n@p bra D;\n"
               "add.u32 n, n, 1;\nsetp.lt.u32 p, n, 4194304;\n@p bra W;\ntrap;\nD:\n}" :: "r"(a), "r"(ph) : "memory");
}
__device__ __forceinline__ void mbar_wait(uint32_t a, uint32_t ph) {
  asm volatile("{\n.reg .pred p;\nW: mbarrier.try_wait.parity.shared::cta.b64 p, [%0], %1;\n@!p bra W;\n}" :: "r"(a), "r"(ph) : "memory");
}
__device__ __forceinline__ void mbar_wait_sleep(uint32_t a, uint32_t ph) {
  asm volatile("{\n.reg .pred p;\nW: mbarrier.test_wait.parity.shared::cta.b64 p, [%0], %1;\n@p bra D;\nnanosleep.u32 500;\nbra W;\nD:\n}" :: "r"(a), "r"(ph) : "memory");
}
__device__ __forceinline__ void wg_fence() { asm volatile("wgmma.fence.sync.aligned;" ::: "memory"); }
__device__ __forceinline__ void wg_commit() { asm volatile("wgmma.commit_group.sync.aligned;" ::: "memory"); }
template <int N> __device__ __forceinline__ void wg_wait() { asm volatile("wgmma.wait_group.sync.aligned %0;" :: "n"(N) : "memory"); }
__device__ __forceinline__ float tanh_ap(float x) { float y; asm("tanh.approx.f32 %0, %1;" : "=f"(y) : "f"(x)); return y; }
__device__ __forceinline__ float ex2(float x) { float y; asm("ex2.approx.ftz.f32 %0, %1;" : "=f"(y) : "f"(x)); return y; }
__device__ __forceinline__ uint32_t pack_bf16(float lo, float hi) { uint32_t r; asm("cvt.rn.bf16x2.f32 %0, %1, %2;" : "=r"(r) : "f"(hi), "f"(lo)); return r; }
__device__ __forceinline__ float bf_lo(uint32_t v) { return __uint_as_float(v << 16); }
__device__ __forceinline__ float bf_hi(uint32_t v) { return __uint_as_float(v & 0xffff0000u); }
__device__ __forceinline__ uint32_t sub_bf16x2(uint32_t a, uint32_t b) { uint32_t r; asm("sub.rn.bf16x2 %0, %1, %2;" : "=r"(r) : "r"(a), "r"(b)); return r; }
__device__ __forceinline__ uint32_t mul_bf16x2(uint32_t a, uint32_t b) { uint32_t r; asm("mul.rn.bf16x2 %0, %1, %2;" : "=r"(r) : "r"(a), "r"(b)); return r; }
__device__ __forceinline__ uint32_t diff2(uint32_t a, uint32_t b, uint32_t t) { uint32_t r; asm("lop3.b32 %0, %1, %2, %3, 0x7e;" : "=r"(r) : "r"(a), "r"(b), "r"(t)); return r; }
__device__ __forceinline__ uint32_t or3(uint32_t a, uint32_t b, uint32_t c) { uint32_t r; asm("lop3.b32 %0, %1, %2, %3, 0xfe;" : "=r"(r) : "r"(a), "r"(b), "r"(c)); return r; }
__device__ __forceinline__ uint32_t umin2(uint32_t a, uint32_t b) { uint32_t r; asm("min.u32 %0, %1, %2;" : "=r"(r) : "r"(a), "r"(b)); return r; }
__device__ __forceinline__ uint32_t bitmask(uint32_t v, int bit) { uint32_t r; asm("bfe.s32 %0, %1, %2, 1;" : "=r"(r) : "r"(v), "r"(bit)); return r; }
__device__ __forceinline__ uint32_t nz(uint32_t w) { return w == 0u ? 0x8000u : w; }

__device__ __forceinline__ void ldg4(uint32_t* d, const uint4* p) {
  asm volatile("ld.relaxed.gpu.global.v4.b32 {%0,%1,%2,%3}, [%4];" : "=r"(d[0]), "=r"(d[1]), "=r"(d[2]), "=r"(d[3]) : "l"(p) : "memory");
}
__device__ __forceinline__ void ldg2(uint32_t* d, const void* p) {
  asm volatile("ld.relaxed.gpu.global.v2.b32 {%0,%1}, [%2];" : "=r"(d[0]), "=r"(d[1]) : "l"(p) : "memory");
}
__device__ __forceinline__ void stg4(uint4* p, uint32_t a, uint32_t b, uint32_t c, uint32_t d) {
  asm volatile("st.relaxed.gpu.global.v4.b32 [%0], {%1,%2,%3,%4};" :: "l"(p), "r"(a), "r"(b), "r"(c), "r"(d) : "memory");
}
__device__ __forceinline__ void stg2(void* p, uint32_t a, uint32_t b) {
  asm volatile("st.relaxed.gpu.global.v2.b32 [%0], {%1,%2};" :: "l"(p), "r"(a), "r"(b) : "memory");
}
__device__ __forceinline__ void sts4(uint32_t a, const uint32_t* o) { asm volatile("st.shared.v4.b32 [%0], {%1,%2,%3,%4};" :: "r"(a), "r"(o[0]), "r"(o[1]), "r"(o[2]), "r"(o[3]) : "memory"); }
__device__ __forceinline__ void lds4(uint32_t a, uint32_t* o) { asm volatile("ld.shared.v4.b32 {%0,%1,%2,%3}, [%4];" : "=r"(o[0]), "=r"(o[1]), "=r"(o[2]), "=r"(o[3]) : "r"(a) : "memory"); }
__device__ __forceinline__ void lds2(uint32_t a, uint32_t* o) { asm volatile("ld.shared.v2.b32 {%0,%1}, [%2];" : "=r"(o[0]), "=r"(o[1]) : "r"(a) : "memory"); }
__device__ __forceinline__ float rcp(float x) { float y; asm("rcp.approx.ftz.f32 %0, %1;" : "=f"(y) : "f"(x)); return y; }
__device__ __forceinline__ void sts1(uint32_t a, uint32_t v) { asm volatile("st.shared.b32 [%0], %1;" :: "r"(a), "r"(v) : "memory"); }
__device__ __forceinline__ void ldsm4(uint32_t a, uint32_t& r0, uint32_t& r1, uint32_t& r2, uint32_t& r3) {
  asm volatile("ldmatrix.sync.aligned.m8n8.x4.shared.b16 {%0,%1,%2,%3}, [%4];" : "=r"(r0), "=r"(r1), "=r"(r2), "=r"(r3) : "r"(a) : "memory");
}
__device__ __forceinline__ void ldsm4t(uint32_t a, uint32_t& r0, uint32_t& r1, uint32_t& r2, uint32_t& r3) {
  asm volatile("ldmatrix.sync.aligned.m8n8.x4.trans.shared.b16 {%0,%1,%2,%3}, [%4];" : "=r"(r0), "=r"(r1), "=r"(r2), "=r"(r3) : "r"(a) : "memory");
}
__device__ __forceinline__ void mma16(float* c, uint32_t a0, uint32_t a1, uint32_t a2, uint32_t a3, uint32_t b0, uint32_t b1) {
  asm("mma.sync.aligned.m16n8k16.row.col.f32.bf16.bf16.f32 {%0,%1,%2,%3}, {%4,%5,%6,%7}, {%8,%9}, {%0,%1,%2,%3};"
    : "+f"(c[0]), "+f"(c[1]), "+f"(c[2]), "+f"(c[3]) : "r"(a0), "r"(a1), "r"(a2), "r"(a3), "r"(b0), "r"(b1));
}
__device__ __forceinline__ void mma16c(float* d, const uint32_t* a, uint32_t b0, uint32_t b1, float c01) {
  asm("mma.sync.aligned.m16n8k16.row.col.f32.bf16.bf16.f32 {%0,%1,%2,%3}, {%4,%5,%6,%7}, {%8,%9}, {%10,%10,%10,%10};"
    : "=f"(d[0]), "=f"(d[1]), "=f"(d[2]), "=f"(d[3]) : "r"(a[0]), "r"(a[1]), "r"(a[2]), "r"(a[3]), "r"(b0), "r"(b1), "f"(c01));
}
__device__ __forceinline__ void mma8(float* c, uint32_t a0, uint32_t a1, uint32_t b0) {
  asm("mma.sync.aligned.m16n8k8.row.col.f32.bf16.bf16.f32 {%0,%1,%2,%3}, {%4,%5}, {%6}, {%0,%1,%2,%3};"
    : "+f"(c[0]), "+f"(c[1]), "+f"(c[2]), "+f"(c[3]) : "r"(a0), "r"(a1), "r"(b0));
}
__device__ __forceinline__ uint32_t lane_id() { uint32_t l; asm volatile("mov.u32 %0, %%laneid;" : "=r"(l)); return l; }
__device__ __forceinline__ float quad_sum(float v) { v += __shfl_xor_sync(~0u, v, 1); v += __shfl_xor_sync(~0u, v, 2); return v; }
__device__ __forceinline__ float quad_max(float v) { v = fmaxf(v, __shfl_xor_sync(~0u, v, 1)); v = fmaxf(v, __shfl_xor_sync(~0u, v, 2)); return v; }
template <int N> __device__ __forceinline__ void pin(float (&d)[N]) {
#pragma unroll
  for (int i = 0; i < N; i++) asm volatile("" : "+f"(d[i]) :: "memory");
}
#define SPIN_GUARD(n) if (++(n) > SPIN_MAX) break

template <int NG> __device__ __forceinline__ void publish_stats(uint4* dst, const float* y, uint32_t tag, uint32_t lane) {
  float s0 = 0.f, s1 = 0.f;
#pragma unroll
  for (int g = 0; g < NG; g++) { s0 += y[4 * g] + y[4 * g + 1]; s1 += y[4 * g + 2] + y[4 * g + 3]; }
  s0 = quad_sum(s0); s1 = quad_sum(s1);
  const float m0 = s0 * (1.f / (8 * NG)), m1 = s1 * (1.f / (8 * NG));
  float q0 = 0.f, q1 = 0.f, q2 = 0.f, q3 = 0.f;
#pragma unroll
  for (int g = 0; g < NG; g++) {
    const float a = y[4 * g] - m0, b = y[4 * g + 1] - m0, c = y[4 * g + 2] - m1, d = y[4 * g + 3] - m1;
    q0 = fmaf(a, a, q0); q1 = fmaf(b, b, q1); q2 = fmaf(c, c, q2); q3 = fmaf(d, d, q3);
  }
  q0 = quad_sum(q0 + q1); q2 = quad_sum(q2 + q3);
  if ((lane & 3) == 0)
    stg4(dst + (lane >> 2), (__float_as_uint(s0) & ~1u) | tag, __float_as_uint(q0), __float_as_uint(s1), __float_as_uint(q2));
}

__device__ __forceinline__ void put72(uint4* slab, uint32_t j, uint32_t lane, const uint32_t* v) {
#pragma unroll
  for (int i = 0; i < 4; i++) stg4(slab + (4 * j + i) * 32 + lane, nz(v[4 * i]), v[4 * i + 1], v[4 * i + 2], v[4 * i + 3]);
  stg2((char*)(slab + 1024 + j * 16) + lane * 8, nz(v[16]), v[17]);
}
__device__ __forceinline__ uint32_t row72(uint32_t k) { return k % 9 == 4 ? 32 + k / 9 : k - (k + 4) / 9; }
__device__ __forceinline__ void zero_share(uint4* slab, uint32_t j, uint32_t lane) {
  uint4* p = slab + j * 144 + lane;
#pragma unroll
  for (int i = 0; i < 4; i++) stg4(p + i * 32, 0u, 0u, 0u, 0u);
  if (lane < 16) stg4(p + 128, 0u, 0u, 0u, 0u);
}

struct Maps { CUtensorMap m[11]; };

struct Ring {
  uint32_t st, ph;
  __device__ __forceinline__ void next() { if (++st == NST) { st = 0; ph ^= 1; } }
};

#define GSTAMP(i) do {} while (0)
#define STAMP(i) do {} while (0)
#define ZSTAMP(m, i) do {} while (0)

__device__ __forceinline__ void tma_box(uint32_t dst, const CUtensorMap* m, int col, int row, uint32_t bar, uint32_t expect) {
  asm volatile("{\n.reg .pred e, h;\nelect.sync _|e, 0xffffffff;\nsetp.ne.and.u32 h, %5, 0, e;\n"
               "@h mbarrier.arrive.expect_tx.shared::cta.b64 _, [%2], %5;\n"
               "@e cp.async.bulk.tensor.2d.shared::cluster.global.mbarrier::complete_tx::bytes [%0], [%1, {%3, %4}], [%2];\n}"
               :: "r"(dst), "l"(m), "r"(bar), "r"(col), "r"(row), "r"(expect) : "memory");
}

__device__ __forceinline__ void bulk_load(uint32_t dst, const void* src, uint32_t bytes, uint32_t bar, bool arm) {
  asm volatile("{\n.reg .pred e, h;\nelect.sync _|e, 0xffffffff;\nsetp.ne.and.u32 h, %4, 0, e;\n"
               "@h mbarrier.arrive.expect_tx.shared::cta.b64 _, [%3], %2;\n"
               "@e cp.async.bulk.shared::cluster.global.mbarrier::complete_tx::bytes [%0], [%1], %2, [%3];\n}"
               :: "r"(dst), "l"(src), "r"(bytes), "r"(bar), "r"((uint32_t)arm) : "memory");
}

__global__ void __launch_bounds__(384, 1) mega_kernel(
    const __grid_constant__ Maps maps, uint4* __restrict__ scratch,
    __nv_bfloat16* __restrict__ out) {
  extern __shared__ __align__(1024) uint8_t smem[];
  const uint32_t sb = (uint32_t)__cvta_generic_to_shared(smem);
  const uint32_t full0 = sb + BARS, empty0 = full0 + 8 * NST, rem_full = empty0 + 8 * NST, park_free = rem_full + 8, kv_free = park_free + 8;
  const uint32_t c8_go = kv_free + 8, c8_done = c8_go + 8, c8_full = c8_done + 8, remo_full = c8_full + 8, piece_full = remo_full + 8, xb_done = piece_full + 8, res_full = xb_done + 8, pbar0 = res_full + 8;
  const uint32_t x_done = pbar0 + 64, x_ring = x_done + 8, xbar0 = x_ring + 8;
  const uint32_t w = __shfl_sync(~0u, threadIdx.x >> 5, 0);
  uint32_t pair = blockIdx.x >> 1;
  if (gridDim.x == 132) {
    uint32_t smid;
    asm("mov.u32 %0, %%smid;" : "=r"(smid));
    const uint32_t tpc = smid >> 1;
    if (tpc == 60 || tpc == 61) { if (threadIdx.x == 0) { __nanosleep(20000); } return; }
    pair = tpc < 32 ? tpc : tpc >= 62 ? (tpc - 58) * 8 : 33 + (tpc - 32) / 7 * 8 + (tpc - 32) % 7;
  }
  const uint32_t rank = blockIdx.x & 1, t = (pair & 7) * 2 + rank, j = pair >> 3;
  const uint32_t sd = sb & 0x3ffff;
  const uint32_t odd = j & 1;
  uint4* const scr = scratch + t * TILE;
  auto blk = [&](uint32_t kb) { return kb == 0 ? j : kb - (kb <= j); };
  const uint32_t xs = sb + (NST - 2) * STAGE;
  auto fetch_x = [&](uint32_t dst, uint32_t b, uint32_t bar) {
    asm volatile("{\n.reg .pred e;\nelect.sync _|e, 0xffffffff;\n@e mbarrier.arrive.expect_tx.shared::cta.b64 _, [%2], 16384;\n"
                 "@e cp.async.bulk.tensor.3d.shared::cluster.global.mbarrier::complete_tx::bytes [%0], [%1, {%3, %4, 0}], [%2];\n}"
                 :: "r"(dst), "l"(&maps.m[7]), "r"(bar), "r"(64 * b), "r"(64 * t) : "memory");
  };
  if (threadIdx.x == 256) {
    for (int i = 0; i < 9; i++) mbar_init(xbar0 + 8 * i, 1);
    mbar_init(piece_full, 1);
    asm volatile("fence.mbarrier_init.release.cluster;" ::: "memory");
  }
  if (threadIdx.x == 288) {
    for (int i = 0; i < NST; i++) { mbar_init(full0 + 8 * i, 1); mbar_init(empty0 + 8 * i, 16); }
    mbar_init(x_done, 8); mbar_init(x_ring, 16);
    asm volatile("fence.mbarrier_init.release.cluster;" ::: "memory");
  }
  if (threadIdx.x == 320) {
    mbar_init(rem_full, 1); mbar_init(park_free, 8); mbar_init(kv_free, 8); mbar_init(c8_go, 8); mbar_init(c8_done, 2); mbar_init(c8_full, 1);
    mbar_init(remo_full, 64); mbar_init(xb_done, 8); mbar_init(res_full, 32);
    for (int i = 0; i < 8; i++) mbar_init(pbar0 + 8 * i, 4);
    asm volatile("fence.mbarrier_init.release.cluster;" ::: "memory");
  }
  if (threadIdx.x == 352) {
    asm volatile("prefetch.tensormap [%0];" :: "l"(&maps.m[7]) : "memory");
    asm volatile("prefetch.tensormap [%0];" :: "l"(&maps.m[0]) : "memory");
  }
  __syncwarp();
  asm volatile("barrier.cluster.arrive.relaxed.aligned;" ::: "memory");
  if (w != 8) asm volatile("barrier.cluster.wait.aligned;" ::: "memory");

  if (w >= 8) {
    asm volatile("setmaxnreg.dec.sync.aligned.u32 24;");
    if (w == 8) {
#pragma unroll 1
      for (uint32_t b = 0; b < 9; b++) fetch_x(xs + b * STAGE, b, xbar0 + 8 * b);
      tma_box(sb + PIECE, &maps.m[t >= 12 ? 6 : 5], 72 * j + (odd ? 0 : 64) + (t < 8 ? 576 * ((t >> 2) + 1) : 0), 144 * (t & 3), piece_full, 2304);
      asm volatile("barrier.cluster.wait.aligned;" ::: "memory");
      uint32_t dst = sb, bar = full0, ph = 1;
#pragma unroll 1
      for (int seg = 0; seg < 34; seg++) {
        const int n = seg >= 17 ? seg - 17 : seg;
        int ma, mb, ca, cb;
        if (n < 3) { ma = mb = n == 2; ca = 72 * j + 8 * odd + (n == 0 ? 576 : 0); cb = ca + 576; }
        else if (n < 12) { ma = 3; mb = 2; ca = cb = 576 * j + 64 * (n - 3); }
        else { ma = mb = 4; ca = n == 12 ? 512 : ((j + 2 * n) & 7) * 64; cb = ((j + 2 * n + 1) & 7) * 64; }
        const bool zip = n == 0 || n == 3, solo = n == 1 || n == 2 || n == 16;
#pragma unroll 1
        for (uint32_t st = 0; st < (solo ? 5 : 9); st++) {
          if (seg == 0 && st == NST - 2) mbar_wait(x_ring, 0);
          const uint32_t b = 2 * st + rank, kb = zip ? st : b >= 9 ? b - 9 : b;
          const bool second = zip ? rank : b >= 9, shared = kb == 8 && n >= 2 && n < 12;
          const uint32_t ks = n >= 12 ? 36 * j + 4 * kb : n < 2 ? 4 * blk(kb) : shared ? 0 : (9 * blk(kb) + 1) >> 1;
          asm volatile("{\n.reg .pred p, e, f;\n.reg .u32 n;\nelect.sync _|e, 0xffffffff;\nsetp.ne.and.u32 f, %8, 0, e;\nmov.u32 n, 0;\n"
                       "W: mbarrier.try_wait.parity.shared::cta.b64 p, [%1+48], %2;\n@p bra D;\n"
                       "add.u32 n, n, 1;\nsetp.lt.u32 p, n, 4194304;\n@p bra W;\ntrap;\n"
                       "D: @e mbarrier.arrive.expect_tx.shared::cta.b64 _, [%1], %7;\n"
                       "@f cp.async.bulk.tensor.3d.shared::cluster.global.mbarrier::complete_tx::bytes.multicast::cluster [%0], [%3, {%4, %5, %6}], [%1], 3;\n}"
                       :: "r"(dst + rank * 8192), "r"(bar), "r"(ph), "l"(&maps.m[(second ? mb : ma) + (shared ? 7 : 0)]), "r"(second ? cb : ca),
                          "r"(shared ? 64 : 0), "r"(ks), "r"(solo && st == 4 ? STAGE / 2 : STAGE), "r"((uint32_t)!(solo && b == 9)) : "memory");
          dst += STAGE; bar += 8;
          if (bar == full0 + 8 * NST) { dst = sb; bar = full0; ph ^= 1; }
        }
      }
      {
#pragma unroll 1
        for (int i = 0; i < NST; i++) {
          mbar_wait_trap(bar + 48, ph);
          bar += 8;
          if (bar == full0 + 8 * NST) { bar = full0; ph ^= 1; }
        }
      }
    } else if (w == 9) {
      const uint32_t lane = lane_id();
      const uint32_t stg = sb + HSTG + lane * 16;
      uint32_t fph = 0;
#pragma unroll 1
      for (uint32_t layer = 0; layer < 2; layer++) {
        uint4* xb = scr + OFF_X + ((4 + layer) * 8 + j) * SLAB + 28 * 32;
        mbar_wait_sleep(c8_go, layer);
        int n = 0;
        while (true) {
          if (lane == 0) asm volatile("mbarrier.arrive.expect_tx.shared::cta.b64 _, [%0], 18432;" :: "r"(c8_full) : "memory");
          __syncwarp();
#pragma unroll 1
          for (uint32_t s = 0; s < 9; s++)
            bulk_load(sb + HSTG + s * 2048, s < 8 ? scr + OFF_P + (j + s * 8) * SLAB + 32 * 32 : xb, 2048, c8_full, false);
          mbar_wait(c8_full, fph); fph ^= 1;
          uint32_t bad = 0;
#pragma unroll 8
          for (int s = 0; s < 32; s++) { uint32_t v; asm volatile("ld.shared.b32 %0, [%1];" : "=r"(v) : "r"(stg + s * 512) : "memory"); bad |= v ^ (1 - layer); }
          if (__all_sync(~0u, (bad & 1u) == 0u)) break;
          __nanosleep(300);
          SPIN_GUARD(n);
        }
        asm volatile("bar.arrive 7, 96;" ::: "memory");
        float s0 = 0.f, s1 = 0.f;
#pragma unroll 1
        for (int g = 0; g < 8; g++) {
          const uint32_t a = stg + (g >> 1) * 512 + (g & 1) * 8;
          float a0 = 0.f, a1 = 0.f, a2 = 0.f, a3 = 0.f;
#pragma unroll 1
          for (int b = 0; b < 3; b++) {
            uint32_t v[6];
#pragma unroll
            for (int s = 0; s < 3; s++) lds2(a + (3 * b + s) * 2048, v + 2 * s);
#pragma unroll
            for (int s = 0; s < 3; s++) { a0 += bf_lo(v[2 * s]); a1 += bf_hi(v[2 * s]); a2 += bf_lo(v[2 * s + 1]); a3 += bf_hi(v[2 * s + 1]); }
          }
          sts1(a + 18432, pack_bf16(a0, a1)); sts1(a + 18436, pack_bf16(a2, a3));
          s0 += a0 + a1; s1 += a2 + a3;
        }
        __syncwarp();
        if (lane == 0) mbar_arrive(c8_done);
        s0 = quad_sum(s0); s1 = quad_sum(s1);
        float q0 = 0.f, q1 = 0.f;
        const uint32_t ln = lane_id();
#pragma unroll 1
        for (uint32_t i = 0; i < 4; i++) {
          uint32_t x[4];
          lds4(stg + 18432 + i * 512, x);
          stg4(xb + i * 32 + ln, 0u, 0u, 0u, 0u);
          if (layer == 0) {
            stg4(xb - 3 * 8 * SLAB + (4 + i) * 32 + ln, nz(x[0]), x[1], nz(x[2]), x[3]);
#pragma unroll
            for (int e = 0; e < 4; e++) {
              const float m = (e & 1) ? s1 : s0, c = fmaf(m, -1.f / 64, bf_lo(x[e])), d = fmaf(m, -1.f / 64, bf_hi(x[e]));
              if (e & 1) q1 = fmaf(c, c, fmaf(d, d, q1)); else q0 = fmaf(c, c, fmaf(d, d, q0));
            }
          } else {
            uint32_t* o = (uint32_t*)(out + (128 * t + 32 * (j >> 1) + 2 * (ln >> 2) + (j & 1)) * 576 + 512 + 16 * i + 2 * (ln & 3));
            o[0] = x[0]; o[8 * 576] = x[1]; o[4] = x[2]; o[8 * 576 + 4] = x[3];
          }
        }
        if (layer == 0) {
          q0 = quad_sum(q0); q1 = quad_sum(q1);
          if ((ln & 3) == 0) stg4(scr + OFF_S + j * 96 + 64 + (ln >> 2), __float_as_uint(s0) | 1u, __float_as_uint(q0), __float_as_uint(s1), __float_as_uint(q1));
        }
      }
    } else {
      auto mark = [&](uint32_t k0, uint32_t v) {
        const uint32_t lane = lane_id();
#pragma unroll 1
        for (uint32_t k = k0; k < 6; k++) stg4(scr + OFF_S + (k * 4 + (lane >> 3)) * 96 + j * 8 + (lane & 7), k < 2 ? 0u : v, 0u, 0u, 0u);
      };
      if (w == 11) mark(2, 0u);
      auto phase2_duties = [&](uint32_t layer) {
        const uint32_t lane = lane_id();
        asm volatile("bar.sync 7, 96;" ::: "memory");
        if (w == 11) {
          if (layer == 0) mark(0, 1u);
          __syncwarp();
          if (lane == 0) mbar_arrive(c8_done);
        }
#pragma unroll 1
        for (uint32_t i = 0; i < 16; i++) {
          const uint32_t sl = (w - 10) * 4 + (i >> 2);
          bulk_load(sb + PARK + sl * 2048 + (i & 3) * 512, scr + OFF_X + ((4 + layer) * 8 + sl) * SLAB + row72(4 * j + (i & 3)) * 32, 512, res_full, true);
        }
        mbar_wait_sleep(res_full, layer);
#pragma unroll 1
        for (uint32_t i = 0; i < 16; i++) {
          stg4(scr + OFF_X + ((4 + layer) * 8 + (w - 10) * 4 + (i >> 2)) * SLAB + row72(4 * j + (i & 3)) * 32 + lane, 0u, 0u, 0u, 0u);
          __nanosleep(100);
        }
      };
      if (w == 10) {
        const uint32_t lane = lane_id();
        uint32_t* fl = (uint32_t*)(scratch + OFF_F + (t * 8 + j) * 8) + (lane & 15);
        uint32_t v;
        asm volatile("ld.relaxed.gpu.global.b32 %0, [%1];" : "=r"(v) : "l"(fl) : "memory");
        mbar_wait(piece_full, 0);
        asm volatile("{\n.reg .pred e;\nelect.sync _|e, 0xffffffff;\n@e cp.async.bulk.global.shared::cta.bulk_group [%0], [%1], 2304;\n}\n"
                     "cp.async.bulk.commit_group;\ncp.async.bulk.wait_group 0;\nfence.proxy.async;"
                     :: "l"(scratch + OFF_R + j * 2304 + t * 144), "r"(sb + PIECE) : "memory");
        __syncwarp();
        if (lane < 16) asm volatile("st.release.gpu.global.b32 [%0], 1;" :: "l"((uint32_t*)(scratch + OFF_F + (lane_id() * 8 + j) * 8) + t) : "memory");
        int n = 0;
        while (!__all_sync(~0u, v != 0u)) {
          __nanosleep(100);
          SPIN_GUARD(n);
          asm volatile("ld.relaxed.gpu.global.b32 %0, [%1];" : "=r"(v) : "l"(fl) : "memory");
        }
        asm volatile("st.relaxed.gpu.global.b32 [%0], 0;" :: "l"(fl) : "memory");
        mbar_wait(x_done, 0);
      }
#pragma unroll 1
      for (uint32_t layer = 0; layer < 2; layer++) {
        if (w == 10) {
          if (layer) mbar_wait_sleep(park_free, 0);
          const uint4* img = scratch + OFF_R + j * 2304;
          if (lane_id() == 0) asm volatile("mbarrier.arrive.expect_tx.shared::cta.b64 _, [%0], 27648;\nmbarrier.arrive.expect_tx.shared::cta.b64 _, [%1], 9216;"
                                           :: "r"(rem_full), "r"(piece_full) : "memory");
          __syncwarp();
#pragma unroll 1
          for (uint32_t p = 0; p < 3; p++) {
            bulk_load(sb + REM + p * 9216, img + p * 576 + j * 64, 1024, rem_full, false);
            if (j) bulk_load(sb + REM + p * 9216 + 1024, img + p * 576, j * 1024, rem_full, false);
            bulk_load(sb + REM + p * 9216 + (j + 1) * 1024, img + p * 576 + (j + 1) * 64, (8 - j) * 1024, rem_full, false);
          }
#pragma unroll 1
          for (uint32_t i = 0; i < 12; i++)
            bulk_load(sb + REM + 27648 + (i < 8 ? i * 1024 : 6144 + i * 256), img + 1728 + (i < 8 ? (9 * blk(i) + 1) >> 1 : 9 * i - 68) * 16,
                      i < 8 ? 1024 : 256, piece_full, false);
          if (layer == 0) { fetch_x(sb + PARK, j, xbar0); fetch_x(sb + PARK + STAGE, j + 1, xbar0 + 8); }
        }
        mbar_wait_sleep(rem_full, layer);
        mbar_wait(piece_full, 1 - layer);
#pragma unroll 1
        for (uint32_t b = 0; b < 5; b++) {
          const uint32_t blk = sb + REM + 27648 + b * 2048, k = (w - 10) * 32 + lane_id(), rr = k & 7;
          const uint32_t dst = blk + ((k >> 3) & 1) * 1024 + rr * 128 + (((k >> 4) ^ rr) << 4);
          uint32_t v[8];
          lds4(blk + k * 16, v); lds4(blk + 1024 + k * 16, v + 4);
          asm volatile("bar.sync 3, 64;" ::: "memory");
          sts4(dst, v); sts4(dst ^ 64, v + 4);
        }
        asm volatile("fence.proxy.async.shared::cta;" ::: "memory");
        mbar_arrive(remo_full);
        if (layer) { phase2_duties(0); mbar_wait_sleep(kv_free, 0); }
        if (t > 0) {
          const uint32_t lane = lane_id(), r = lane >> 2, q = lane & 3;
#pragma unroll 1
          for (uint32_t pc = 0; pc < 3; pc++) {
            uint4* hp = scr + OFF_H + ((layer * 8 + j) * 2 + (w - 10)) * 192 + pc * 64 + lane;
            uint32_t hl[8];
            int n = 0;
            hl[4] = 1u;
            while (true) {
              ldg4(hl, hp);
              if (pc < 2) ldg4(hl + 4, hp + 32);
              if (__all_sync(~0u, hl[0] != 0u && hl[4] != 0u)) break;
              __nanosleep(100);
              SPIN_GUARD(n);
            }
            const uint32_t dst = sb + KVS + (w - 10) * 10368 + r * 144 + q * 4;
            if (pc < 2) {
#pragma unroll
              for (int g = 0; g < 8; g++) sts1(dst + pc * 20736 + odd * 16 + g * 16, hl[g]);
              stg4(hp + 32, 0u, 0u, 0u, 0u);
            } else {
              sts1(dst + (odd ? 0 : 128), hl[0]); sts1(dst + 20736 + (odd ? 0 : 128), hl[1]);
            }
            stg4(hp, 0u, 0u, 0u, 0u);
          }
        }
        asm volatile("bar.arrive 1, 192;" ::: "memory");
        mbar_wait_sleep(xb_done, layer);
        if (w == 10 && layer == 1) {
          const uint32_t lane = lane_id();
          stg4(scr + OFF_S + (lane >> 3) * 96 + j * 8 + (lane & 7), 0u, 0u, 0u, 0u);
          stg4(scr + OFF_S + (4 + (lane >> 3)) * 96 + j * 8 + (lane & 7), 0u, 0u, 0u, 0u);
          if (lane < 8) stg4(scr + OFF_S + j * 96 + 64 + lane, 0u, 0u, 0u, 0u);
        }
#pragma unroll 1
        for (uint32_t i = 0; i < 8 && (w == 11 || layer == 1); i++) {
          zero_share(scr + OFF_X + ((w - 10) * 16 + layer * 8 + i) * SLAB, j, lane_id());
          __nanosleep(500);
        }
      }
      phase2_duties(1);
    }
  } else {
    asm volatile("setmaxnreg.inc.sync.aligned.u32 240;");
    const bool lead = lane_id() == 0;
    Ring rg{0, 0};
    uint32_t prev = 0;
    uint32_t X[144];
    float rs0, rs1;
    const bool lead2 = lane_id() < 2;
    uint32_t empty_at;
    asm volatile("mapa.shared::cluster.u32 %0, %1, %2;" : "=r"(empty_at) : "r"(empty0), "r"(lane_id() & 1));
    auto release = [&](uint32_t st) { if (lead2) asm volatile("mbarrier.arrive.shared::cluster.b64 _, [%0];" :: "r"(empty_at + st * 8) : "memory"); };
    auto load_kb = [&](int kb, const uint4* src, const char* lo, uint32_t hoff) {
#pragma unroll
      for (int i = 0; i < 4; i++) {
        if (kb == 8) { ldg2(X + 128 + 4 * i, lo + (32 + i) * 512); ldg2(X + 130 + 4 * i, lo + hoff + (32 + i) * 512); }
        else ldg4(X + 16 * kb + 4 * i, src + blk(kb) * 128 + i * 32);
      }
    };
    auto check_kb = [&](bool skip, int kb, const uint4* src, const char* lo, uint32_t hoff) {
      int n = 0;
      while (true) {
        uint32_t m = umin2(umin2(X[16 * kb], X[16 * kb + 4]), umin2(X[16 * kb + 8], X[16 * kb + 12]));
        if (kb == 8) m = umin2(m, umin2(umin2(X[130], X[134]), umin2(X[138], X[142])));
        if (__all_sync(~0u, m != 0u || skip)) break;
        SPIN_GUARD(n);
        load_kb(kb, src, lo, hoff);
      }
    };
#pragma unroll
    for (int i = 0; i < 16; i++) X[i] = 0u;
#pragma unroll 1
    for (uint32_t hf = 0; hf < 4; hf++) {
      const uint32_t layer = hf >> 1;
      const bool ffn = hf & 1;
      const uint32_t tag = 1 - layer;
      uint4* const xbase = scr + OFF_X + (layer * 8 + w) * SLAB;
      float aA[32], aB[32];
      {
        const uint32_t lane = lane_id(), r = lane >> 2, q = lane & 3;
        const uint4* src = xbase + (ffn ? 32 * SLAB : 0) + lane;
        const char* lo = (const char*)src - (ffn ? lane * 8 : 0);
        const uint32_t hoff = ffn ? 256 : 8;
        const uint32_t xoff = (w & 1) * 8192 + (16 * (w >> 1) + (lane & 15)) * 128 + (((lane >> 4) ^ (lane & 7)) << 4);
        auto load_x = [&](uint32_t b, uint32_t* d) {
#pragma unroll
          for (int i = 0; i < 4; i++) ldsm4(xs + b * STAGE + (xoff ^ (32 * i)), d[4 * i], d[4 * i + 1], d[4 * i + 2], d[4 * i + 3]);
        };
        auto load_any = [&](int kb) { if (hf == 0) load_x(blk(kb), X + 16 * kb); else load_kb(kb, src, lo, hoff); };
        float m0, m1, v0, v1;
        STAMP(ffn * 16 + 0);
        if (hf == 0) {
          float sum[2][4] = {}, sq0[4][4] = {}, sq1[4][4] = {};
          uint32_t p0, p1;
          mbar_wait(xbar0, 0);
          ldsm4(xs + xoff, p0, p1, X[0], X[1]);
          p0 = __byte_perm(__shfl_sync(~0u, p0, lane & 28), 0, 0x1010); p1 = __byte_perm(__shfl_sync(~0u, p1, lane & 28), 0, 0x1010);
#pragma unroll 3
          for (uint32_t b = 0; b < 9; b++) {
            uint32_t d[16];
            mbar_wait(xbar0 + 8 * b, 0);
            load_x(b, d);
#pragma unroll
            for (int i = 0; i < 16; i++) d[i] = sub_bf16x2(d[i], (i & 1) ? p1 : p0);
#pragma unroll
            for (int g = 0; g < 8; g++) {
              if (!(g & 1)) mma16(sum[(g >> 1) & 1], d[2 * g], d[2 * g + 1], d[2 * g + 2], d[2 * g + 3], 0x3f803f80u, 0x3f803f80u);
              mma8(sq0[g & 3], d[2 * g], d[2 * g + 1], d[2 * g]); mma8(sq1[g & 3], d[2 * g], d[2 * g + 1], d[2 * g + 1]);
            }
          }
          STAMP(1);
          GSTAMP(14);
#pragma unroll
          for (int kb = 0; kb < GD; kb++) load_x(blk(kb), X + 16 * kb);
          release((x_ring - empty0) / 8);
          auto tot = [](float (&c)[4][4], int e) { return (c[0][e] + c[1][e]) + (c[2][e] + c[3][e]); };
          const float a0 = (sum[0][0] + sum[1][0]) * (1.f / 576), a1 = (sum[0][2] + sum[1][2]) * (1.f / 576);
          const uint32_t dg = (lane & 28) + (r >> 1);
          v0 = fmaxf(fmaf(__shfl_sync(~0u, (r & 1) ? tot(sq0, 1) : tot(sq0, 0), dg), 1.f / 576, -a0 * a0), 0.f);
          v1 = fmaxf(fmaf(__shfl_sync(~0u, (r & 1) ? tot(sq1, 3) : tot(sq1, 2), dg), 1.f / 576, -a1 * a1), 0.f);
          m0 = bf_lo(p0) + a0; m1 = bf_lo(p1) + a1;
        } else {
          uint32_t s[3][4];
          const uint4* p = scr + OFF_S + ((ffn ? 16 : 0) + w) * 96 + q * 8 + r;
          const bool third = !ffn && q == 0;
          const uint32_t rdy = ffn ? tag : 1u;
          int n = 0;
          s[2][0] = rdy; s[2][1] = s[2][2] = s[2][3] = 0u;
          while (true) {
            ldg4(s[0], p); ldg4(s[1], p + 32);
            if (third) ldg4(s[2], p + 64);
            if (__all_sync(~0u, ((diff2(s[0][0], s[1][0], rdy) | diff2(s[1][0], s[2][0], rdy)) & 1u) == 0u)) break;
            SPIN_GUARD(n);
          }
          STAMP(ffn * 16 + 1);
          ZSTAMP(1 + ffn, 0);
          GSTAMP(14 + ffn);
#pragma unroll
          for (int kb = 1; kb < GD; kb++) load_kb(kb, src, lo, hoff);
          float t0 = 0.f, t1 = 0.f;
#pragma unroll
          for (int i = 0; i < 3; i++) { t0 += __uint_as_float(s[i][0]); t1 += __uint_as_float(s[i][2]); }
          m0 = quad_sum(t0) * (1.f / 576); m1 = quad_sum(t1) * (1.f / 576);
          const float cnt = ffn ? 72.f : 64.f, inv = ffn ? 1.f / 72 : 1.f / 64;
          v0 = 0.f; v1 = 0.f;
#pragma unroll
          for (int i = 0; i < 3; i++) {
            const float c = (i < 2 || third) ? cnt : 0.f;
            const float d0 = fmaf(__uint_as_float(s[i][0]), inv, -m0), d1 = fmaf(__uint_as_float(s[i][2]), inv, -m1);
            v0 += fmaf(d0 * d0, c, __uint_as_float(s[i][1])); v1 += fmaf(d1 * d1, c, __uint_as_float(s[i][3]));
          }
          v0 = quad_sum(v0) * (1.f / 576); v1 = quad_sum(v1) * (1.f / 576);
        }
        rs0 = rsqrtf(v0 + 1e-5f); rs1 = rsqrtf(v1 + 1e-5f);
        const uint32_t mean0 = pack_bf16(m0, m0), mean1 = pack_bf16(m1, m1);
#pragma unroll
        for (int kb = 0; kb < 9; kb++) {
          if (kb > 0) check_kb(hf == 0, kb, src, lo, hoff);
          if (kb + GD < 9) load_any(kb + GD);
          if (kb + GD == 8 && hf == 0 && lead) mbar_arrive(x_done);
#pragma unroll
          for (int i = 16 * kb; i < 16 * kb + 16; i++) X[i] = sub_bf16x2(X[i], (i & 1) ? mean1 : mean0);
          ZSTAMP(1 + ffn, 1 + 3 * kb);
          mbar_wait(full0 + rg.st * 8, rg.ph);
          ZSTAMP(1 + ffn, 2 + 3 * kb);
          const uint64_t desc = DESC_HI | ((sd + rg.st * STAGE) >> 4);
          wg_fence();
#pragma unroll
          for (int i = 0; i < 4; i++) wgmma_rs_n64(aA, X + 4 * (4 * kb + i), desc + i * 128, kb + i != 0);
          if (kb == 8) { wg_commit(); wg_wait<1>(); wg_fence(); }
#pragma unroll
          for (int i = 0; i < 4; i++) wgmma_rs_n64(aB, X + 4 * (4 * kb + i), desc + 512 + i * 128, kb + i != 0);
          wg_commit();
          wg_wait<1>();
          ZSTAMP(1 + ffn, 3 + 3 * kb);
          if (kb > 0) release(prev);
          prev = rg.st; rg.next();
        }
        ZSTAMP(1 + ffn, 28);
        ZSTAMP(4, 0);
        STAMP(ffn * 16 + 2);
      }
      if (!ffn) {
      const uint32_t lane = lane_id(), r = lane >> 2, q = lane & 3;
      const uint32_t kvrow = sb + KVS + (w & 1) * 10368 + (16 * (w >> 1)) * 144;
      uint32_t Q[18], Km[3][8], Ke[3][4];
      const bool edge = (t == 0 && w < 2);
      const uint32_t row0 = edge ? sb + KVS + 8 * 144 : kvrow + (lane & 7) * 144, row1 = kvrow + (8 + (lane & 7)) * 144;
      {
        const uint32_t dst = kvrow + (8 + r) * 144 + q * 4 + odd * 16, dstr = dst + (odd ? -16 : 128);
        const bool edge_out = w >= 6 && t < 15;
        uint4* const hp = scr + TILE + OFF_H + ((layer * 8 + j) * 2 + (w & 1)) * 192 + lane;
        auto put_kv = [&](float (&a)[32], int part, int half) {
          uint32_t hl[4];
#pragma unroll
          for (int i = 0; i < 16; i++) asm volatile("" : "+f"(a[16 * half + i]) :: "memory");
#pragma unroll
          for (int i = 0; i < 4; i++) {
            const int g = 4 * half + i;
            hl[i] = pack_bf16(a[4 * g + 2] * rs1, a[4 * g + 3] * rs1);
            sts1(dst + part * 20736 + g * 16, pack_bf16(a[4 * g] * rs0, a[4 * g + 1] * rs0)); sts1(dst + part * 20736 + 8 * 144 + g * 16, hl[i]);
          }
          if (edge_out) stg4(hp + part * 64 + half * 32, nz(hl[0]), hl[1], hl[2], hl[3]);
        };
        put_kv(aA, 0, 0); put_kv(aA, 0, 1);
        wg_wait<0>();
        release(prev);
        float aR[12];
        mbar_wait(rem_full, layer);
        const uint64_t dr = DESC_REM | ((sd + REM) >> 4);
        wg_fence();
#pragma unroll
        for (int s = 0; s < 36; s++) {
          wgmma_rs_n24(aR, X + 4 * s, dr + s * 16, s != 0);
          if (s == 4) put_kv(aB, 1, 0);
          if (s == 16) put_kv(aB, 1, 1);
        }
        wg_commit();
#pragma unroll
        for (int kb = 0; kb < 9; kb++) {
          if (!(kb & 1)) mbar_wait(full0 + rg.st * 8, rg.ph);
          const uint64_t desc = DESC_HI | ((sd + rg.st * STAGE + (kb & 1) * 8192) >> 4);
          wg_fence();
#pragma unroll
          for (int i = 0; i < 4; i++) wgmma_rs_n64(aB, X + 4 * (4 * kb + i), desc + i * 128, kb + i != 0);
          wg_commit();
          wg_wait<1>();
          if (kb > 0 && !(kb & 1)) release(prev);
          if ((kb & 1) || kb == 8) { prev = rg.st; rg.next(); }
          if (kb == 0) {
            pin(aR);
            const uint32_t k1 = pack_bf16(aR[2] * rs1, aR[3] * rs1), v1 = pack_bf16(aR[6] * rs1, aR[7] * rs1);
            if (edge_out) stg4(hp + 128, nz(k1), v1, 0u, 0u);
            sts1(dstr, pack_bf16(aR[0] * rs0, aR[1] * rs0)); sts1(dstr + 8 * 144, k1);
            sts1(dstr + 20736, pack_bf16(aR[4] * rs0, aR[5] * rs0)); sts1(dstr + 20736 + 8 * 144, v1);
            Q[16] = pack_bf16(aR[8], aR[9]); Q[17] = pack_bf16(aR[10], aR[11]);
            if (w < 4) asm volatile("bar.arrive 2, 256;" ::: "memory");
          }
          if (kb == 6) mbar_wait(remo_full, layer);
          if (kb == 8) {
            if (w < 4) asm volatile("bar.sync 1, 192;" ::: "memory");
            else asm volatile("bar.sync 2, 256;" ::: "memory");
#pragma unroll
            for (int nt = 0; nt < 3; nt++) {
              const uint32_t ra = (nt == 0 ? row0 : row1 + (nt - 1) * 8 * 144);
              ldsm4(ra + odd * 16 + (lane >> 3) * 16, Km[nt][0], Km[nt][1], Km[nt][2], Km[nt][3]);
              ldsm4(ra + odd * 16 + 64 + (lane >> 3) * 16, Km[nt][4], Km[nt][5], Km[nt][6], Km[nt][7]);
              ldsm4(ra + (odd ? 0 : 32) + (lane >> 3) * 32, Ke[nt][0], Ke[nt][1], Ke[nt][2], Ke[nt][3]);
            }
            const uint32_t ge = (2u << q) - 1, le = 0xfu << q, on = edge ? 0u : ~0u;
            const uint32_t bits = odd ? 0xfu | ((le & 0xfu) << 4) | (ge << 8) : ge | 0xf0u | (le << 8);
#pragma unroll
            for (int h = 0; h < 4; h++) {
              const uint32_t ma = bitmask(bits, h), mb = bitmask(bits, 4 + h), mc = bitmask(bits, 8 + h);
              Km[0][2 * h] &= ma & on; Km[0][2 * h + 1] &= mb & on; Ke[0][h] &= mc & on;
#pragma unroll
              for (int nt = 1; nt < 3; nt++) { Km[nt][2 * h] &= ma; Km[nt][2 * h + 1] &= mb; Ke[nt][h] &= mc; }
            }
          }
        }
        wg_wait<0>();
        release(prev);
        pin(aB);
        STAMP(3);
#pragma unroll
        for (int i = 0; i < 16; i++) Q[i] = pack_bf16(aB[2 * i], aB[2 * i + 1]);
      }
      uint32_t res[18] = {};
      if (layer) {
        const uint4* p = xbase + ((9 * j + 1) >> 1) * 32 + lane;
#pragma unroll
        for (int i = 0; i < 4; i++) ldg4(res + 4 * i, p + i * 32);
        ldg2(res + 16, odd ? (const char*)(p - 32) + 8 : (const char*)(p + 4 * 32));
      }
      {
        uint32_t V01[12][2], V2[12];
        const uint32_t rv = ((lane & 8) ? row1 : row0) + 20736, rw = row1 + 8 * 144 + 20736;
#pragma unroll
        for (int i = 0; i < 4; i++) ldsm4t(rv + odd * 16 + i * 32 + (lane >> 4) * 16, V01[2 * i][0], V01[2 * i][1], V01[2 * i + 1][0], V01[2 * i + 1][1]);
#pragma unroll
        for (int i = 0; i < 2; i++) ldsm4t(rv + (odd ? 0 : 32) + i * 64 + (lane >> 4) * 32, V01[8 + 2 * i][0], V01[8 + 2 * i][1], V01[9 + 2 * i][0], V01[9 + 2 * i][1]);
        ldsm4t(rw + odd * 16 + (lane >> 3) * 16, V2[0], V2[1], V2[2], V2[3]);
        ldsm4t(rw + odd * 16 + 64 + (lane >> 3) * 16, V2[4], V2[5], V2[6], V2[7]);
        ldsm4t(rw + (odd ? 0 : 32) + (lane >> 3) * 32, V2[8], V2[9], V2[10], V2[11]);
        const bool up0 = 2 * q > r, up1 = 2 * q + 1 > r;
        const uint32_t upm = (up0 ? 0xffffu : 0u) | (up1 ? 0xffff0000u : 0u);
        const float c0 = 0.23570226039551584f * 1.4426950408889634f * rs0, c1 = 0.23570226039551584f * 1.4426950408889634f * rs1;
        const float masked = edge ? -1e9f * 1.4426950408889634f * rcp(c0) : 0.f;
        uint32_t Om[16], Oe[8];
        uint4* const po = xbase + 16 * SLAB + 4 * j * 32 + lane;
#pragma unroll
        for (int h = 0; h < 4; h++) {
          const uint32_t e0 = odd ? Q[(4 * h + 16) % 18] : Q[4 * h + 4], e1 = odd ? Q[(4 * h + 17) % 18] : Q[4 * h + 5];
          float S[3][4];
#pragma unroll
          for (int nt = 0; nt < 3; nt++) {
            mma16c(S[nt], Q + 4 * h, Km[nt][2 * h], Km[nt][2 * h + 1], nt == 0 ? masked : 0.f);
            mma8(S[nt], e0, e1, Ke[nt][h]);
          }
          const float s00 = up0 ? S[0][0] : S[1][0], s01 = up1 ? S[0][1] : S[1][1];
          const float s10 = up0 ? S[1][2] : S[2][2], s11 = up1 ? S[1][3] : S[2][3];
          const float m0 = quad_max(fmaxf(s00, s01)) * c0, m1 = quad_max(fmaxf(s10, s11)) * c1;
          const float p00 = ex2(fmaf(s00, c0, -m0)), p01 = ex2(fmaf(s01, c0, -m0)), p10 = ex2(fmaf(s10, c1, -m1)), p11 = ex2(fmaf(s11, c1, -m1));
          const float i0 = rcp(quad_sum(p00 + p01)), i1 = rcp(quad_sum(p10 + p11));
          const uint32_t p0 = pack_bf16(p00 * i0, p01 * i0), p1 = pack_bf16(p10 * i1, p11 * i1);
          const uint32_t pf[4] = {p0 & upm, 0u, p0 & ~upm, p1 & upm};
#pragma unroll
          for (int gi = 0; gi < 3; gi++) {
            const int g = gi < 2 ? 2 * h + gi : 8 + h;
            float o[4];
            mma16c(o, pf, V01[g][0], V01[g][1], 0.f);
            mma8(o, 0u, p1 & ~upm, V2[g]);
            uint32_t* d = gi < 2 ? Om + 2 * g : Oe + 2 * h;
            d[0] = pack_bf16(o[0], o[1]); d[1] = pack_bf16(o[2], o[3]);
          }
          if (h > 0) {
#pragma unroll
            for (int e = 0; e < 2; e++) {
              if (!odd && q < h) Om[4 * h + e] = Oe[2 * h - 2 + e];
              if (odd && q >= h) Om[4 * h - 2 + e] = Oe[2 * h + e];
            }
            stg4(po + (h - 1) * 32, nz(Om[4 * h - 4]), Om[4 * h - 3], Om[4 * h - 2], Om[4 * h - 1]);
          }
        }
        STAMP(4);
        stg4(po + 96, nz(Om[12]), Om[13], Om[14], Om[15]);
        stg2((char*)(xbase + 16 * SLAB + 1024 + j * 16) + lane * 8, nz(odd ? Oe[0] : Oe[6]), odd ? Oe[1] : Oe[7]);
#pragma unroll
        for (int i = 0; i < 16; i++) X[i] = Om[i];
      }
      if (lane == 0) asm volatile("st.relaxed.gpu.global.b32 [%0], %1;" :: "l"(scr + OFF_S + (8 + w) * 96 + j * 8), "r"(tag) : "memory");
      {
        if (layer == 0) {
          const uint32_t xrow = (w & 1) * 8192 + (16 * (w >> 1) + (lane & 15)) * 128;
          uint32_t u0, u1;
          mbar_wait(xbar0, 1); mbar_wait(xbar0 + 8, 1);
#pragma unroll
          for (int i = 0; i < 5; i++) {
            const uint32_t g = i < 4 ? j + odd + 2 * i : j + (odd ? 0 : 8);
            const uint32_t a = sb + PARK + (g >> 3) * STAGE + xrow;
            if (i < 4) ldsm4(a + ((((g & 7) + (lane >> 4)) ^ (lane & 7)) << 4), res[4 * i], res[4 * i + 1], res[4 * i + 2], res[4 * i + 3]);
            else ldsm4(a + (((g & 7) ^ (lane & 7)) << 4), res[16], res[17], u0, u1);
          }
        }
        const uint4* src = xbase + 16 * SLAB + lane;
        {
          const uint4* fp = scr + OFF_S + (8 + w) * 96 + (lane & 7) * 8;
          int n = 0;
          STAMP(8);
          while (true) {
            uint32_t f;
            asm volatile("ld.relaxed.gpu.global.b32 %0, [%1];" : "=r"(f) : "l"(fp) : "memory");
            if (__all_sync(~0u, f == tag)) break;
            SPIN_GUARD(n);
          }
          STAMP(9);
        }
#pragma unroll
        for (int kb = 1; kb < GD; kb++) load_kb(kb, src, (const char*)src - lane * 8, 256);
        float acc[36];
#pragma unroll
        for (int i = 0; i < 18; i++) { acc[2 * i] = bf_lo(res[i]); acc[2 * i + 1] = bf_hi(res[i]); }
#pragma unroll
        for (int kb = 0; kb < 9; kb++) {
          if (kb > 0) check_kb(false, kb, src, (const char*)src - lane * 8, 256);
          if (kb + GD < 9) load_kb(kb + GD, src, (const char*)src - lane * 8, 256);
          if (!(kb & 1)) mbar_wait(full0 + rg.st * 8, rg.ph);
          const uint32_t base = sd + rg.st * STAGE + (kb & 1) * 8192;
          const uint64_t d0 = DESC_HI | ((base >> 4) + (((sd + REM + 27648 + (kb >> 1) * 2048 + (kb & 1) * 64 - base) >> 4) << 16));
          wg_fence();
#pragma unroll
          for (int i = 0; i < 4; i++) wgmma_rs_n72(acc, X + 4 * (4 * kb + i), d0 - (uint64_t)(i * ((127u << 16) - 128u)), 1);
          wg_commit();
          wg_wait<1>();
          if (kb > 0 && !(kb & 1)) release(prev);
          if ((kb & 1) || kb == 8) { prev = rg.st; rg.next(); }
        }
        wg_wait<0>();
        release(prev);
        pin(acc);
        STAMP(10);
#pragma unroll
        for (int i = 0; i < 18; i++) res[i] = pack_bf16(acc[2 * i], acc[2 * i + 1]);
        if (j < PRI) put72(xbase + 32 * SLAB, j, lane, res);
        publish_stats<9>(scr + OFF_S + (16 + w) * 96 + j * 8, acc, tag, lane);
        if (j >= PRI) put72(xbase + 32 * SLAB, j, lane, res);
#pragma unroll
        for (int i = 0; i < 16; i++) X[i] = res[i];
      }
      continue;
      }
      const uint32_t hp = sb + PARK + w * 512 + lane_id() * 16;
      auto pack8 = [&](float (&a)[32], int p, uint32_t* o) {
#pragma unroll
        for (int e = 0; e < 8; e++) asm volatile("" : "+f"(a[8 * p + e]) :: "memory");
#pragma unroll
        for (int e = 0; e < 4; e++) o[e] = pack_bf16(a[8 * p + 2 * e], a[8 * p + 2 * e + 1]);
      };
      const float ka0 = 0.7978845608028654f * rs0, kb0 = 0.044715f * ka0 * rs0 * rs0, ku0 = 0.5f * rs0 * rs0;
      const float ka1 = 0.7978845608028654f * rs1, kb1 = 0.044715f * ka1 * rs1 * rs1, ku1 = 0.5f * rs1 * rs1;
      auto packu8 = [&](int p, uint32_t* o) {
#pragma unroll
        for (int e = 0; e < 8; e++) asm volatile("" : "+f"(aA[8 * p + e]) :: "memory");
#pragma unroll
        for (int e = 0; e < 4; e++) o[e] = pack_bf16(aA[8 * p + 2 * e] * ((e & 1) ? ku1 : ku0), aA[8 * p + 2 * e + 1] * ((e & 1) ? ku1 : ku0));
      };
      auto geglu8 = [&](int p, uint32_t* u) {
#pragma unroll
        for (int e = 0; e < 8; e++) asm volatile("" : "+f"(aB[8 * p + e]) :: "memory");
        float h[8];
#pragma unroll
        for (int e = 0; e < 8; e++) {
          const float g = aB[8 * p + e];
          h[e] = fmaf(g, tanh_ap(g * fmaf(g * g, (e & 2) ? kb1 : kb0, (e & 2) ? ka1 : ka0)), g);
        }
#pragma unroll
        for (int e = 0; e < 4; e++) u[e] = mul_bf16x2(pack_bf16(h[2 * e], h[2 * e + 1]), u[e]);
      };
      auto box = [&](int b, auto&& filler) {
        const int kb = b < 9 ? b : b - 9;
        if (!(b & 1)) { if (b == 0) mbar_wait_trap(full0 + rg.st * 8, rg.ph); else mbar_wait(full0 + rg.st * 8, rg.ph); }
        const uint64_t desc = DESC_HI | ((sd + rg.st * STAGE + (b & 1) * 8192) >> 4);
        wg_fence();
#pragma unroll
        for (int i = 0; i < 4; i++) {
          if (b < 9) wgmma_rs_n64(aA, X + 4 * (4 * kb + i), desc + i * 128, kb + i != 0);
          else wgmma_rs_n64(aB, X + 4 * (4 * kb + i), desc + i * 128, kb + i != 0);
          if (i == 2) filler();
        }
        wg_commit();
        if (b & 1) { prev = rg.st; rg.next(); } else { wg_wait<1>(); release(prev); }
      };
      auto nop = [] {};
      auto step = [&](int st, auto&& filler) { box(2 * st, nop); box(2 * st + 1, filler); };
#pragma unroll
      for (int p = 0; p < 4; p++) { uint32_t o[4]; packu8(p, o); sts4(hp + p * 4096, o); }
      box(0, nop);
      if (lead) mbar_arrive(xb_done);
#pragma unroll 1
      for (int c = 1;; c++) {
        const uint32_t hc = hp + c * 4 * 4096;
#pragma unroll
        for (int b = 1; b < 18; b++) box(b, [&] {
          if ((b & 1) && b < 8) { uint32_t o[4]; const uint32_t a = hc - (4 - (b >> 1)) * 4096; lds4(a, o); geglu8(b >> 1, o); sts4(a, o); }
          if ((b & 1) && b > 10) { uint32_t o[4]; packu8((b - 11) >> 1, o); if (c < 8) sts4(hc + ((b - 11) >> 1) * 4096, o); } });
        ZSTAMP(4, c);
        if (c == 8) break;
        box(0, nop);
      }
      wg_wait<0>();
      STAMP(21);
      GSTAMP(19);
      auto unpark = [&](int kb) {
#pragma unroll
        for (int s = 4 * kb; s < 4 * kb + 4; s++) lds4(hp + s * 4096, X + 4 * s);
      };
      unpark(0);
      uint32_t U[16];
#pragma unroll
      for (int p = 0; p < 4; p++) packu8(p, U + 4 * p);
#pragma unroll
      for (int b = 0; b < 8; b++) box(b, [&] {
        if (b < 7) unpark(b + 1);
        if (b & 1) {
          geglu8(b >> 1, U + 2 * (b - 1));
          if (rg.ph > 1) sts4(hp, U + 2 * (b - 1));
#pragma unroll
          for (int i = 0; i < 4; i++) X[128 + 2 * (b - 1) + i] = U[2 * (b - 1) + i];
        } });
      STAMP(24);
      if (layer == 0 && lead) mbar_arrive(park_free);
      const uint32_t lane2 = lane_id();
      uint4* const pw = scr + OFF_P + (j * 8 + w) * SLAB + lane2;
      const uint4* const pr = scr + OFF_P + w * SLAB + 4 * j * 32 + lane2;
      auto put_part = [&](float (&a)[32], int p, uint32_t chunk) {
        uint32_t o[4];
        pack8(a, p, o);
        stg4(pw + (chunk * 4 + p) * 32, (o[0] & ~1u) | tag, o[1], o[2], o[3]);
      };
      auto slot = [&](int p) { return sb + w * 2048 + (p < 3 ? PARK + p * 16384 : KVS + (p - 3) * 16384); };
      auto fetch = [&](int p) {
        bulk_load(slot(p), scr + OFF_P + (((j - p) & 7) * 8 + w) * SLAB + 4 * j * 32, 2048, pbar0 + w * 8, true);
      };
#pragma unroll 1
      for (int sp = 0;; sp++) {
        const uint32_t ca = sp == 0 ? 8 : ((j + 2 * sp) & 7), cb = (j + 2 * sp + 1) & 7;
        if (sp == 1 && lead) mbar_arrive(c8_go);
#pragma unroll
        for (int st = 4; st < 9; st++) step(st, [&] {
          if (st == 5 || st == 6) { put_part(aA, 2 * (st - 5), ca); put_part(aA, 2 * (st - 5) + 1, ca); }
          if (st == 8 && sp > 1) { if (sp == 3) mbar_wait(c8_done, layer); fetch(2 * sp - 2); } });
        STAMP(25 + sp);
        if (sp == 3) break;
#pragma unroll
        for (int st = 0; st < 4; st++) step(st, [&] {
          if (st < 2) { put_part(aB, 2 * st, cb); put_part(aB, 2 * st + 1, cb); }
          if (st == 3 && sp > 0) fetch(2 * sp - 1); });
      }
      auto load_p = [&](int p, uint32_t* d) {
#pragma unroll
        for (int i = 0; i < 4; i++) ldg4(d + 4 * i, pr + ((j - p) & 7) * 8 * SLAB + i * 32);
      };
#pragma unroll
      for (int b = 0; b < 9; b++) {
        box(b, [&] {
          if (b == 1) {
#pragma unroll
            for (int p = 0; p < 4; p++) put_part(aB, p, (j + 7) & 7);
          }
          if (b == 3) { load_p(5, X); load_p(6, X + 16); }
          if (b == 7) load_p(7, X + 32); });
      }
      mbar_wait(res_full, layer);
      mbar_wait(pbar0 + w * 8, layer);
#pragma unroll
      for (int p = 1; p < 5; p++)
#pragma unroll
        for (int i = 0; i < 4; i++) lds4(slot(p) + lane2 * 16 + i * 512, X + 48 + 16 * p + 4 * i);
#pragma unroll
      for (int i = 0; i < 4; i++) {
        const bool split = j == 2 * i + 1;
        const uint32_t a = slot(0) + i * 512 + (split ? lane2 * 8 : lane2 * 16);
        lds2(a, X + 48 + 4 * i); lds2(a + (split ? 256 : 8), X + 50 + 4 * i);
      }
      wg_wait<0>();
      release(rg.st); rg.next();
      pin(aA);
      STAMP(22);
      GSTAMP(20);
      {
        const uint32_t lane = lane2, r = lane >> 2, q = lane & 3;
        const uint32_t eye = r == 2 * q ? 0x3f80u : r == 2 * q + 1 ? 0x3f800000u : 0u;
        auto bad = [&](const uint32_t* d) { return diff2(d[0], d[4], tag) | diff2(d[8], d[12], tag); };
        auto add = [&](const uint32_t* d) {
#pragma unroll
          for (int g = 0; g < 8; g++) mma8(aA + 4 * g, d[2 * g], d[2 * g + 1], eye);
        };
        int n = 0;
        while (!__all_sync(~0u, ((or3(bad(X), bad(X + 16), bad(X + 64)) | or3(bad(X + 80), bad(X + 96), bad(X + 112))) & 1u) == 0u)) {
          SPIN_GUARD(n);
          load_p(5, X); load_p(6, X + 16);
#pragma unroll
          for (int p = 1; p < 5; p++) load_p(p, X + 48 + 16 * p);
        }
        add(X); add(X + 16);
#pragma unroll
        for (int p = 4; p >= 0; p--) add(X + 48 + 16 * ((p + 1) % 5));
        STAMP(11);
        while (!__all_sync(~0u, (bad(X + 32) & 1u) == 0u)) { SPIN_GUARD(n); load_p(7, X + 32); }
        add(X + 32);
        STAMP(12);
        uint32_t res[16];
#pragma unroll
        for (int i = 0; i < 16; i++) X[i] = res[i] = pack_bf16(aA[2 * i], aA[2 * i + 1]);
        if (layer == 0) {
          uint4* p = xbase + 8 * SLAB + 4 * j * 32 + lane;
          auto put = [&] {
#pragma unroll
            for (int i = 0; i < 4; i++) stg4(p + i * 32, nz(res[4 * i]), res[4 * i + 1], res[4 * i + 2], res[4 * i + 3]);
          };
          if (j < PRI) put();
          publish_stats<8>(scr + OFF_S + w * 96 + j * 8, aA, 1u, lane);
          if (j >= PRI) put();
          if (lane == 0) mbar_arrive(kv_free);
        } else {
          const uint32_t tb = slot(0);
          __syncwarp();
#pragma unroll
          for (int i = 0; i < 4; i++) {
            const uint32_t row = (lane2 & 7) + (lane2 & 8), g = 2 * i + (lane2 >> 4);
            asm volatile("stmatrix.sync.aligned.m8n8.x4.shared.b16 [%0], {%1,%2,%3,%4};"
                         :: "r"(tb + row * 128 + ((g ^ (row & 7)) << 4)), "r"(res[4 * i]), "r"(res[4 * i + 1]), "r"(res[4 * i + 2]), "r"(res[4 * i + 3]) : "memory");
          }
          __syncwarp();
#pragma unroll
          for (int i = 0; i < 4; i++) {
            const uint32_t row = 4 * i + (lane2 >> 3), g = lane2 & 7;
            uint32_t v[4];
            lds4(tb + row * 128 + ((g ^ (row & 7)) << 4), v);
            *(uint4*)(out + (128 * t + 32 * (w >> 1) + 2 * row + (w & 1)) * 576 + 64 * j + 8 * g) = make_uint4(v[0], v[1], v[2], v[3]);
          }
        }
      }
      STAMP(23);
    }
  }
}

typedef CUresult (*EncodeFn)(CUtensorMap*, CUtensorMapDataType, cuuint32_t, void*, const cuuint64_t*, const cuuint64_t*,
                             const cuuint32_t*, const cuuint32_t*, CUtensorMapInterleave, CUtensorMapSwizzle,
                             CUtensorMapL2promotion, CUtensorMapFloatOOBfill);

CUtensorMap make_map(EncodeFn f, const void* p, uint64_t cols, uint64_t rows, uint64_t grp) {
  CUtensorMap m;
  cuuint64_t dims[3] = {cols, grp, rows / grp}, str[2] = {cols * 2, cols * 2 * grp};
  cuuint32_t box[3] = {64, 16, 4}, es[3] = {1, 1, 1};
  f(&m, CU_TENSOR_MAP_DATA_TYPE_BFLOAT16, 3, const_cast<void*>(p), dims, str, box, es, CU_TENSOR_MAP_INTERLEAVE_NONE,
    CU_TENSOR_MAP_SWIZZLE_128B, CU_TENSOR_MAP_L2_PROMOTION_NONE, CU_TENSOR_MAP_FLOAT_OOB_FILL_NONE);
  return m;
}
CUtensorMap make_rem_map(EncodeFn f, const void* p, uint64_t cols) {
  CUtensorMap m;
  cuuint64_t dims[2] = {cols, 576}, str[1] = {cols * 2};
  cuuint32_t box[2] = {8, 144}, es[2] = {1, 1};
  f(&m, CU_TENSOR_MAP_DATA_TYPE_BFLOAT16, 2, const_cast<void*>(p), dims, str, box, es, CU_TENSOR_MAP_INTERLEAVE_NONE,
    CU_TENSOR_MAP_SWIZZLE_NONE, CU_TENSOR_MAP_L2_PROMOTION_NONE, CU_TENSOR_MAP_FLOAT_OOB_FILL_NONE);
  return m;
}

}

extern "C" void kernel_launch(void* const* d_in, const int* in_sizes, int n_in, void* d_out, int out_size) {
  void* fn = nullptr;
  cudaDriverEntryPointQueryResult qr;
  cudaGetDriverEntryPoint("cuTensorMapEncodeTiled", &fn, cudaEnableDefault, &qr);
  EncodeFn enc = (EncodeFn)fn;
  Maps maps;
  maps.m[0] = make_map(enc, d_in[1], 1728, 576, 16); maps.m[1] = make_map(enc, d_in[2], 576, 576, 16);
  maps.m[2] = make_map(enc, d_in[4], 4608, 576, 16); maps.m[3] = make_map(enc, d_in[5], 4608, 576, 16);
  maps.m[4] = make_map(enc, d_in[6], 576, 4608, 16);
  maps.m[5] = make_rem_map(enc, d_in[1], 1728); maps.m[6] = make_rem_map(enc, d_in[2], 576);
  maps.m[8] = make_map(enc, d_in[2], 576, 576, 144); maps.m[9] = make_map(enc, d_in[4], 4608, 576, 144);
  maps.m[10] = make_map(enc, d_in[5], 4608, 576, 144);
  {
    cuuint64_t dims[3] = {576, 1024, 2}, str[2] = {2304, 1152};
    cuuint32_t box[3] = {64, 64, 2}, es[3] = {1, 1, 1};
    enc(&maps.m[7], CU_TENSOR_MAP_DATA_TYPE_BFLOAT16, 3, d_in[0], dims, str, box, es, CU_TENSOR_MAP_INTERLEAVE_NONE,
        CU_TENSOR_MAP_SWIZZLE_128B, CU_TENSOR_MAP_L2_PROMOTION_NONE, CU_TENSOR_MAP_FLOAT_OOB_FILL_NONE);
  }
  void* scr = nullptr;
  cudaGetSymbolAddress(&scr, g_scratch);
  cudaFuncSetAttribute(mega_kernel, cudaFuncAttributeMaxDynamicSharedMemorySize, SMEM_BYTES);
  cudaLaunchConfig_t cfg = {};
  cfg.gridDim = dim3(128); cfg.blockDim = dim3(384); cfg.dynamicSmemBytes = SMEM_BYTES; cfg.stream = cudaStreamPerThread;
  cudaLaunchAttribute at[1];
  at[0].id = cudaLaunchAttributeClusterDimension; at[0].val.clusterDim.x = 2; at[0].val.clusterDim.y = 1; at[0].val.clusterDim.z = 1;
  cfg.attrs = at; cfg.numAttrs = 1;
  int dev = 0, sms = 0, clusters = 0;
  cudaGetDevice(&dev);
  cudaDeviceGetAttribute(&sms, cudaDevAttrMultiProcessorCount, dev);
  cudaOccupancyMaxActiveClusters(&clusters, mega_kernel, &cfg);
  if (sms == 132 && clusters == 66) cfg.gridDim = dim3(132);
  cudaLaunchKernelEx(&cfg, mega_kernel, maps, (uint4*)scr, (__nv_bfloat16*)d_out);
}
```

```cpp
#include <cuda_runtime.h>
#include <cuda.h>
#include <cuda_bf16.h>
#include <stdint.h>

#define TRACE 0
#define GUARD 0
#define DLY 0
#define HQ 9
#define GO 5
#define FORCE_REDO 0
#define ZT 0

namespace {

constexpr int NST = 6;
constexpr int STAGE = 16384;
constexpr int PARK = NST * STAGE;
constexpr int REM = PARK + 49152;
constexpr int KVS = REM + 40960;
constexpr int PIECE = PARK + 7 * STAGE;
constexpr int HSTG = KVS + 16384;
constexpr int BARS = KVS + 41472;
constexpr int TRC = BARS + 512;
constexpr int SMEM_BYTES = TRC + (TRACE ? 512 : 0);
static_assert(NST == 6, "the producer addresses empty barriers as full + 48");
static_assert(BARS >= PARK + 131072, "barriers overlap park");
static_assert(SMEM_BYTES <= 232448, "smem");

constexpr int SLAB = 36 * 32;
constexpr int SPIN_MAX = 1 << 17;
constexpr uint32_t PRI = 4;
constexpr int GD = 3;
constexpr int OFF_S = 0;
constexpr int OFF_H = OFF_S + 3 * 8 * 96;
constexpr int OFF_X = OFF_H + 2 * 8 * 384;
constexpr int OFF_P = OFF_X + 6 * 8 * SLAB;
constexpr int TILE = OFF_P + 8 * 8 * SLAB;
constexpr int OFF_R = 16 * TILE;
constexpr int OFF_F = OFF_R + 8 * 2304;
constexpr int SCRATCH = OFF_F + 128 * 8;

}

__device__ uint4 g_scratch[SCRATCH];

namespace {

constexpr uint64_t DESC_HI = 0x4000004000000000ull;
constexpr uint64_t DESC_REM = (576ull << 32) | (8u << 16);
__device__ __forceinline__ void wgmma_rs_n64(float (&d)[32], const uint32_t* a, uint64_t desc, int scale_d) {
  asm volatile("{\n.reg .pred p;\nsetp.ne.b32 p, %37, 0;\n"
    "wgmma.mma_async.sync.aligned.m64n64k16.f32.bf16.bf16 "
    "{%0, %1, %2, %3, %4, %5, %6, %7, %8, %9, %10, %11, %12, %13, %14, %15, %16, %17, %18, %19, %20, %21, %22, %23, %24, %25, %26, %27, %28, %29, %30, %31}, "
    "{%32, %33, %34, %35}, %36, p, 1, 1, 1;\n}\n"
    : "+f"(d[0]), "+f"(d[1]), "+f"(d[2]), "+f"(d[3]), "+f"(d[4]), "+f"(d[5]), "+f"(d[6]), "+f"(d[7]), "+f"(d[8]), "+f"(d[9]), "+f"(d[10]), "+f"(d[11]), "+f"(d[12]), "+f"(d[13]), "+f"(d[14]), "+f"(d[15]), "+f"(d[16]), "+f"(d[17]), "+f"(d[18]), "+f"(d[19]), "+f"(d[20]), "+f"(d[21]), "+f"(d[22]), "+f"(d[23]), "+f"(d[24]), "+f"(d[25]), "+f"(d[26]), "+f"(d[27]), "+f"(d[28]), "+f"(d[29]), "+f"(d[30]), "+f"(d[31])
    : "r"(a[0]), "r"(a[1]), "r"(a[2]), "r"(a[3]), "l"(desc), "r"(scale_d));
}
__device__ __forceinline__ void wgmma_rs_n72(float (&d)[36], const uint32_t* a, uint64_t desc, int scale_d) {
  asm volatile("{\n.reg .pred p;\nsetp.ne.b32 p, %41, 0;\n"
    "wgmma.mma_async.sync.aligned.m64n72k16.f32.bf16.bf16 "
    "{%0, %1, %2, %3, %4, %5, %6, %7, %8, %9, %10, %11, %12, %13, %14, %15, %16, %17, %18, %19, %20, %21, %22, %23, %24, %25, %26, %27, %28, %29, %30, %31, %32, %33, %34, %35}, "
    "{%36, %37, %38, %39}, %40, p, 1, 1, 1;\n}\n"
    : "+f"(d[0]), "+f"(d[1]), "+f"(d[2]), "+f"(d[3]), "+f"(d[4]), "+f"(d[5]), "+f"(d[6]), "+f"(d[7]), "+f"(d[8]), "+f"(d[9]), "+f"(d[10]), "+f"(d[11]), "+f"(d[12]), "+f"(d[13]), "+f"(d[14]), "+f"(d[15]), "+f"(d[16]), "+f"(d[17]), "+f"(d[18]), "+f"(d[19]), "+f"(d[20]), "+f"(d[21]), "+f"(d[22]), "+f"(d[23]), "+f"(d[24]), "+f"(d[25]), "+f"(d[26]), "+f"(d[27]), "+f"(d[28]), "+f"(d[29]), "+f"(d[30]), "+f"(d[31]), "+f"(d[32]), "+f"(d[33]), "+f"(d[34]), "+f"(d[35])
    : "r"(a[0]), "r"(a[1]), "r"(a[2]), "r"(a[3]), "l"(desc), "r"(scale_d));
}
__device__ __forceinline__ void wgmma_rs_n24(float (&d)[12], const uint32_t* a, uint64_t desc, int scale_d) {
  asm volatile("{\n.reg .pred p;\nsetp.ne.b32 p, %17, 0;\n"
    "wgmma.mma_async.sync.aligned.m64n24k16.f32.bf16.bf16 "
    "{%0, %1, %2, %3, %4, %5, %6, %7, %8, %9, %10, %11}, "
    "{%12, %13, %14, %15}, %16, p, 1, 1, 1;\n}\n"
    : "+f"(d[0]), "+f"(d[1]), "+f"(d[2]), "+f"(d[3]), "+f"(d[4]), "+f"(d[5]), "+f"(d[6]), "+f"(d[7]), "+f"(d[8]), "+f"(d[9]), "+f"(d[10]), "+f"(d[11])
    : "r"(a[0]), "r"(a[1]), "r"(a[2]), "r"(a[3]), "l"(desc), "r"(scale_d));
}

__device__ __forceinline__ void mbar_init(uint32_t a, uint32_t c) { asm volatile("mbarrier.init.shared::cta.b64 [%0], %1;" :: "r"(a), "r"(c)); }
__device__ __forceinline__ void mbar_arrive(uint32_t a) { asm volatile("mbarrier.arrive.shared::cta.b64 _, [%0];" :: "r"(a) : "memory"); }
__device__ __forceinline__ void mbar_wait_trap(uint32_t a, uint32_t ph) {
  asm volatile("{\n.reg .pred p;\n.reg .u32 n;\nmov.u32 n, 0;\n"
               "W: mbarrier.try_wait.parity.shared::cta.b64 p, [%0], %1;\n@p bra D;\n"
               "add.u32 n, n, 1;\nsetp.lt.u32 p, n, 4194304;\n@p bra W;\ntrap;\nD:\n}" :: "r"(a), "r"(ph) : "memory");
}
__device__ __forceinline__ void mbar_wait(uint32_t a, uint32_t ph) {
  asm volatile("{\n.reg .pred p;\nW: mbarrier.try_wait.parity.shared::cta.b64 p, [%0], %1;\n@!p bra W;\n}" :: "r"(a), "r"(ph) : "memory");
}
__device__ __forceinline__ void mbar_wait_sleep(uint32_t a, uint32_t ph) {
  asm volatile("{\n.reg .pred p;\nW: mbarrier.test_wait.parity.shared::cta.b64 p, [%0], %1;\n@p bra D;\nnanosleep.u32 500;\nbra W;\nD:\n}" :: "r"(a), "r"(ph) : "memory");
}
__device__ __forceinline__ void wg_fence() { asm volatile("wgmma.fence.sync.aligned;" ::: "memory"); }
__device__ __forceinline__ void wg_commit() { asm volatile("wgmma.commit_group.sync.aligned;" ::: "memory"); }
template <int N> __device__ __forceinline__ void wg_wait() { asm volatile("wgmma.wait_group.sync.aligned %0;" :: "n"(N) : "memory"); }
__device__ __forceinline__ float tanh_ap(float x) { float y; asm("tanh.approx.f32 %0, %1;" : "=f"(y) : "f"(x)); return y; }
__device__ __forceinline__ float ex2(float x) { float y; asm("ex2.approx.ftz.f32 %0, %1;" : "=f"(y) : "f"(x)); return y; }
__device__ __forceinline__ uint32_t pack_bf16(float lo, float hi) { uint32_t r; asm("cvt.rn.bf16x2.f32 %0, %1, %2;" : "=r"(r) : "f"(hi), "f"(lo)); return r; }
__device__ __forceinline__ float bf_lo(uint32_t v) { return __uint_as_float(v << 16); }
__device__ __forceinline__ float bf_hi(uint32_t v) { return __uint_as_float(v & 0xffff0000u); }
__device__ __forceinline__ uint32_t sub_bf16x2(uint32_t a, uint32_t b) { uint32_t r; asm("sub.rn.bf16x2 %0, %1, %2;" : "=r"(r) : "r"(a), "r"(b)); return r; }
__device__ __forceinline__ uint32_t mul_bf16x2(uint32_t a, uint32_t b) { uint32_t r; asm("mul.rn.bf16x2 %0, %1, %2;" : "=r"(r) : "r"(a), "r"(b)); return r; }
__device__ __forceinline__ uint32_t diff2(uint32_t a, uint32_t b, uint32_t t) { uint32_t r; asm("lop3.b32 %0, %1, %2, %3, 0x7e;" : "=r"(r) : "r"(a), "r"(b), "r"(t)); return r; }
__device__ __forceinline__ uint32_t or3(uint32_t a, uint32_t b, uint32_t c) { uint32_t r; asm("lop3.b32 %0, %1, %2, %3, 0xfe;" : "=r"(r) : "r"(a), "r"(b), "r"(c)); return r; }
__device__ __forceinline__ uint32_t umin2(uint32_t a, uint32_t b) { uint32_t r; asm("min.u32 %0, %1, %2;" : "=r"(r) : "r"(a), "r"(b)); return r; }
__device__ __forceinline__ uint32_t bitmask(uint32_t v, int bit) { uint32_t r; asm("bfe.s32 %0, %1, %2, 1;" : "=r"(r) : "r"(v), "r"(bit)); return r; }
__device__ __forceinline__ uint32_t nz(uint32_t w) { return w == 0u ? 0x8000u : w; }

__device__ __forceinline__ void ldg4(uint32_t* d, const uint4* p) {
  asm volatile("ld.relaxed.gpu.global.v4.b32 {%0,%1,%2,%3}, [%4];" : "=r"(d[0]), "=r"(d[1]), "=r"(d[2]), "=r"(d[3]) : "l"(p) : "memory");
}
__device__ __forceinline__ void ldg2(uint32_t* d, const void* p) {
  asm volatile("ld.relaxed.gpu.global.v2.b32 {%0,%1}, [%2];" : "=r"(d[0]), "=r"(d[1]) : "l"(p) : "memory");
}
__device__ __forceinline__ void stg4(uint4* p, uint32_t a, uint32_t b, uint32_t c, uint32_t d) {
  asm volatile("st.relaxed.gpu.global.v4.b32 [%0], {%1,%2,%3,%4};" :: "l"(p), "r"(a), "r"(b), "r"(c), "r"(d) : "memory");
}
__device__ __forceinline__ void stg2(void* p, uint32_t a, uint32_t b) {
  asm volatile("st.relaxed.gpu.global.v2.b32 [%0], {%1,%2};" :: "l"(p), "r"(a), "r"(b) : "memory");
}
__device__ __forceinline__ void sts4(uint32_t a, const uint32_t* o) { asm volatile("st.shared.v4.b32 [%0], {%1,%2,%3,%4};" :: "r"(a), "r"(o[0]), "r"(o[1]), "r"(o[2]), "r"(o[3]) : "memory"); }
__device__ __forceinline__ void lds4(uint32_t a, uint32_t* o) { asm volatile("ld.shared.v4.b32 {%0,%1,%2,%3}, [%4];" : "=r"(o[0]), "=r"(o[1]), "=r"(o[2]), "=r"(o[3]) : "r"(a) : "memory"); }
__device__ __forceinline__ void lds2(uint32_t a, uint32_t* o) { asm volatile("ld.shared.v2.b32 {%0,%1}, [%2];" : "=r"(o[0]), "=r"(o[1]) : "r"(a) : "memory"); }
__device__ __forceinline__ float rcp(float x) { float y; asm("rcp.approx.ftz.f32 %0, %1;" : "=f"(y) : "f"(x)); return y; }
__device__ __forceinline__ void sts1(uint32_t a, uint32_t v) { asm volatile("st.shared.b32 [%0], %1;" :: "r"(a), "r"(v) : "memory"); }
__device__ __forceinline__ void ldsm4(uint32_t a, uint32_t& r0, uint32_t& r1, uint32_t& r2, uint32_t& r3) {
  asm volatile("ldmatrix.sync.aligned.m8n8.x4.shared.b16 {%0,%1,%2,%3}, [%4];" : "=r"(r0), "=r"(r1), "=r"(r2), "=r"(r3) : "r"(a) : "memory");
}
__device__ __forceinline__ void ldsm4t(uint32_t a, uint32_t& r0, uint32_t& r1, uint32_t& r2, uint32_t& r3) {
  asm volatile("ldmatrix.sync.aligned.m8n8.x4.trans.shared.b16 {%0,%1,%2,%3}, [%4];" : "=r"(r0), "=r"(r1), "=r"(r2), "=r"(r3) : "r"(a) : "memory");
}
__device__ __forceinline__ void mma16(float* c, uint32_t a0, uint32_t a1, uint32_t a2, uint32_t a3, uint32_t b0, uint32_t b1) {
  asm("mma.sync.aligned.m16n8k16.row.col.f32.bf16.bf16.f32 {%0,%1,%2,%3}, {%4,%5,%6,%7}, {%8,%9}, {%0,%1,%2,%3};"
    : "+f"(c[0]), "+f"(c[1]), "+f"(c[2]), "+f"(c[3]) : "r"(a0), "r"(a1), "r"(a2), "r"(a3), "r"(b0), "r"(b1));
}
__device__ __forceinline__ void mma16c(float* d, const uint32_t* a, uint32_t b0, uint32_t b1, float c01) {
  asm("mma.sync.aligned.m16n8k16.row.col.f32.bf16.bf16.f32 {%0,%1,%2,%3}, {%4,%5,%6,%7}, {%8,%9}, {%10,%10,%10,%10};"
    : "=f"(d[0]), "=f"(d[1]), "=f"(d[2]), "=f"(d[3]) : "r"(a[0]), "r"(a[1]), "r"(a[2]), "r"(a[3]), "r"(b0), "r"(b1), "f"(c01));
}
__device__ __forceinline__ void mma8(float* c, uint32_t a0, uint32_t a1, uint32_t b0) {
  asm("mma.sync.aligned.m16n8k8.row.col.f32.bf16.bf16.f32 {%0,%1,%2,%3}, {%4,%5}, {%6}, {%0,%1,%2,%3};"
    : "+f"(c[0]), "+f"(c[1]), "+f"(c[2]), "+f"(c[3]) : "r"(a0), "r"(a1), "r"(b0));
}
__device__ __forceinline__ uint32_t lane_id() { uint32_t l; asm volatile("mov.u32 %0, %%laneid;" : "=r"(l)); return l; }
__device__ __forceinline__ float quad_sum(float v) { v += __shfl_xor_sync(~0u, v, 1); v += __shfl_xor_sync(~0u, v, 2); return v; }
__device__ __forceinline__ float quad_max(float v) { v = fmaxf(v, __shfl_xor_sync(~0u, v, 1)); v = fmaxf(v, __shfl_xor_sync(~0u, v, 2)); return v; }
template <int N> __device__ __forceinline__ void pin(float (&d)[N]) {
#pragma unroll
  for (int i = 0; i < N; i++) asm volatile("" : "+f"(d[i]) :: "memory");
}
#define SPIN_GUARD(n) if (++(n) > SPIN_MAX) break

template <int NG> __device__ __forceinline__ void publish_stats(uint4* dst, const float* y, uint32_t tag, uint32_t lane) {
  float s0 = 0.f, s1 = 0.f;
#pragma unroll
  for (int g = 0; g < NG; g++) { s0 += y[4 * g] + y[4 * g + 1]; s1 += y[4 * g + 2] + y[4 * g + 3]; }
  s0 = quad_sum(s0); s1 = quad_sum(s1);
  const float m0 = s0 * (1.f / (8 * NG)), m1 = s1 * (1.f / (8 * NG));
  float q0 = 0.f, q1 = 0.f, q2 = 0.f, q3 = 0.f;
#pragma unroll
  for (int g = 0; g < NG; g++) {
    const float a = y[4 * g] - m0, b = y[4 * g + 1] - m0, c = y[4 * g + 2] - m1, d = y[4 * g + 3] - m1;
    q0 = fmaf(a, a, q0); q1 = fmaf(b, b, q1); q2 = fmaf(c, c, q2); q3 = fmaf(d, d, q3);
  }
  q0 = quad_sum(q0 + q1); q2 = quad_sum(q2 + q3);
  if ((lane & 3) == 0)
    stg4(dst + (lane >> 2), (__float_as_uint(s0) & ~1u) | tag, __float_as_uint(q0), __float_as_uint(s1), __float_as_uint(q2));
}

__device__ __forceinline__ void put72(uint4* slab, uint32_t j, uint32_t lane, const uint32_t* v) {
#pragma unroll
  for (int i = 0; i < 4; i++) stg4(slab + (4 * j + i) * 32 + lane, nz(v[4 * i]), v[4 * i + 1], v[4 * i + 2], v[4 * i + 3]);
  stg2((char*)(slab + 1024 + j * 16) + lane * 8, nz(v[16]), v[17]);
}
__device__ __forceinline__ uint32_t row72(uint32_t k) { return k % 9 == 4 ? 32 + k / 9 : k - (k + 4) / 9; }
__device__ __forceinline__ void zero_share(uint4* slab, uint32_t j, uint32_t lane) {
  uint4* p = slab + j * 144 + lane;
#pragma unroll
  for (int i = 0; i < 4; i++) stg4(p + i * 32, 0u, 0u, 0u, 0u);
  if (lane < 16) stg4(p + 128, 0u, 0u, 0u, 0u);
}

struct Maps { CUtensorMap m[11]; };

struct Ring {
  uint32_t st, ph;
  __device__ __forceinline__ void next() { if (++st == NST) { st = 0; ph ^= 1; } }
};

#define GSTAMP(i) do {} while (0)
#define STAMP(i) do {} while (0)
#define ZSTAMP(m, i) do {} while (0)

__device__ __forceinline__ void tma_box(uint32_t dst, const CUtensorMap* m, int col, int row, uint32_t bar, uint32_t expect) {
  asm volatile("{\n.reg .pred e, h;\nelect.sync _|e, 0xffffffff;\nsetp.ne.and.u32 h, %5, 0, e;\n"
               "@h mbarrier.arrive.expect_tx.shared::cta.b64 _, [%2], %5;\n"
               "@e cp.async.bulk.tensor.2d.shared::cluster.global.mbarrier::complete_tx::bytes [%0], [%1, {%3, %4}], [%2];\n}"
               :: "r"(dst), "l"(m), "r"(bar), "r"(col), "r"(row), "r"(expect) : "memory");
}

__device__ __forceinline__ void bulk_load(uint32_t dst, const void* src, uint32_t bytes, uint32_t bar, bool arm) {
  asm volatile("{\n.reg .pred e, h;\nelect.sync _|e, 0xffffffff;\nsetp.ne.and.u32 h, %4, 0, e;\n"
               "@h mbarrier.arrive.expect_tx.shared::cta.b64 _, [%3], %2;\n"
               "@e cp.async.bulk.shared::cluster.global.mbarrier::complete_tx::bytes [%0], [%1], %2, [%3];\n}"
               :: "r"(dst), "l"(src), "r"(bytes), "r"(bar), "r"((uint32_t)arm) : "memory");
}

__global__ void __launch_bounds__(384, 1) mega_kernel(
    const __grid_constant__ Maps maps, uint4* __restrict__ scratch,
    __nv_bfloat16* __restrict__ out) {
  extern __shared__ __align__(1024) uint8_t smem[];
  const uint32_t sb = (uint32_t)__cvta_generic_to_shared(smem);
  const uint32_t full0 = sb + BARS, empty0 = full0 + 8 * NST, rem_full = empty0 + 8 * NST, park_free = rem_full + 8, kv_free = park_free + 8;
  const uint32_t c8_go = kv_free + 8, c8_done = c8_go + 8, c8_full = c8_done + 8, remo_full = c8_full + 8, piece_full = remo_full + 8, xb_done = piece_full + 8, res_full = xb_done + 8, pbar0 = res_full + 8;
  const uint32_t x_done = pbar0 + 64, x_ring = x_done + 8, xbar0 = x_ring + 8, redo_full = xbar0 + 72;
  const uint32_t w = __shfl_sync(~0u, threadIdx.x >> 5, 0);
  uint32_t pair = blockIdx.x >> 1;
  if (gridDim.x == 132) {
    uint32_t smid;
    asm("mov.u32 %0, %%smid;" : "=r"(smid));
    const uint32_t tpc = smid >> 1;
    if (tpc == 60 || tpc == 61) { if (threadIdx.x == 0) { __nanosleep(20000); } return; }
    pair = tpc < 32 ? tpc : tpc >= 62 ? (tpc - 58) * 8 : 33 + (tpc - 32) / 7 * 8 + (tpc - 32) % 7;
  }
  const uint32_t rank = blockIdx.x & 1, t = (pair & 7) * 2 + rank, j = pair >> 3;
  const uint32_t sd = sb & 0x3ffff;
  const uint32_t odd = j & 1;
  uint4* const scr = scratch + t * TILE;
  auto blk = [&](uint32_t kb) { return kb == 0 ? j : kb - (kb <= j); };
  const uint32_t xs = sb + (NST - 2) * STAGE;
  auto fetch_x = [&](uint32_t dst, uint32_t b, uint32_t bar) {
    asm volatile("{\n.reg .pred e;\nelect.sync _|e, 0xffffffff;\n@e mbarrier.arrive.expect_tx.shared::cta.b64 _, [%2], 16384;\n"
                 "@e cp.async.bulk.tensor.3d.shared::cluster.global.mbarrier::complete_tx::bytes [%0], [%1, {%3, %4, 0}], [%2];\n}"
                 :: "r"(dst), "l"(&maps.m[7]), "r"(bar), "r"(64 * b), "r"(64 * t) : "memory");
  };
  if (threadIdx.x == 256) {
    for (int i = 0; i < 9; i++) mbar_init(xbar0 + 8 * i, 1);
    mbar_init(piece_full, 1);
    asm volatile("fence.mbarrier_init.release.cluster;" ::: "memory");
  }
  if (threadIdx.x == 288) {
    for (int i = 0; i < NST; i++) { mbar_init(full0 + 8 * i, 1); mbar_init(empty0 + 8 * i, 16); }
    mbar_init(x_done, 8); mbar_init(x_ring, 16); mbar_init(redo_full, 1); mbar_init(redo_full + 8, 1);
    asm volatile("fence.mbarrier_init.release.cluster;" ::: "memory");
  }
  if (threadIdx.x == 320) {
    mbar_init(rem_full, 2); mbar_init(park_free, 8); mbar_init(kv_free, 8); mbar_init(c8_go, 8); mbar_init(c8_done, 2); mbar_init(c8_full, 1);
    mbar_init(remo_full, 64); mbar_init(xb_done, 8); mbar_init(res_full, 32);
    for (int i = 0; i < 8; i++) mbar_init(pbar0 + 8 * i, 4);
    asm volatile("fence.mbarrier_init.release.cluster;" ::: "memory");
  }
  if (threadIdx.x == 352) {
    asm volatile("prefetch.tensormap [%0];" :: "l"(&maps.m[7]) : "memory");
    asm volatile("prefetch.tensormap [%0];" :: "l"(&maps.m[0]) : "memory");
  }
  __syncwarp();
  asm volatile("barrier.cluster.arrive.relaxed.aligned;" ::: "memory");
  if (w != 8) asm volatile("barrier.cluster.wait.aligned;" ::: "memory");

  if (w >= 8) {
    asm volatile("setmaxnreg.dec.sync.aligned.u32 24;");
    if (w == 8) {
#pragma unroll 1
      for (uint32_t b = 0; b < 9; b++) fetch_x(xs + b * STAGE, b, xbar0 + 8 * b);
      tma_box(sb + PIECE, &maps.m[t >= 12 ? 6 : 5], 72 * j + (odd ? 0 : 64) + (t < 8 ? 576 * ((t >> 2) + 1) : 0), 144 * (t & 3), piece_full, 2304);
      asm volatile("barrier.cluster.wait.aligned;" ::: "memory");
      uint32_t dst = sb, bar = full0, ph = 1;
#pragma unroll 1
      for (int seg = 0; seg < 34; seg++) {
        const int n = seg >= 17 ? seg - 17 : seg;
        int ma, mb, ca, cb;
        if (n < 3) { ma = mb = n == 2; ca = 72 * j + 8 * odd + (n == 0 ? 576 : 0); cb = ca + 576; }
        else if (n < 12) { ma = 3; mb = 2; ca = cb = 576 * j + 64 * (n - 3); }
        else { ma = mb = 4; ca = n == 12 ? 512 : ((j + 2 * n) & 7) * 64; cb = ((j + 2 * n + 1) & 7) * 64; }
        const bool zip = n == 0 || n == 3, solo = n == 1 || n == 2 || n == 16;
#pragma unroll 1
        for (uint32_t st = 0; st < (solo ? 5 : 9); st++) {
          if (seg == 0 && st == NST - 2) mbar_wait(x_ring, 0);
          const uint32_t b = 2 * st + rank, kb = zip ? st : b >= 9 ? b - 9 : b;
          const bool second = zip ? rank : b >= 9, shared = kb == 8 && n >= 2 && n < 12;
          const uint32_t ks = n >= 12 ? 36 * j + 4 * kb : n < 2 ? 4 * blk(kb) : shared ? 0 : (9 * blk(kb) + 1) >> 1;
          asm volatile("{\n.reg .pred p, e, f;\n.reg .u32 n;\nelect.sync _|e, 0xffffffff;\nsetp.ne.and.u32 f, %8, 0, e;\nmov.u32 n, 0;\n"
                       "W: mbarrier.try_wait.parity.shared::cta.b64 p, [%1+48], %2;\n@p bra D;\n"
                       "add.u32 n, n, 1;\nsetp.lt.u32 p, n, 4194304;\n@p bra W;\ntrap;\n"
                       "D: @e mbarrier.arrive.expect_tx.shared::cta.b64 _, [%1], %7;\n"
                       "@f cp.async.bulk.tensor.3d.shared::cluster.global.mbarrier::complete_tx::bytes.multicast::cluster [%0], [%3, {%4, %5, %6}], [%1], 3;\n}"
                       :: "r"(dst + rank * 8192), "r"(bar), "r"(ph), "l"(&maps.m[(second ? mb : ma) + (shared ? 7 : 0)]), "r"(second ? cb : ca),
                          "r"(shared ? 64 : 0), "r"(ks), "r"(solo && st == 4 ? STAGE / 2 : STAGE), "r"((uint32_t)!(solo && b == 9)) : "memory");
          dst += STAGE; bar += 8;
          if (bar == full0 + 8 * NST) { dst = sb; bar = full0; ph ^= 1; }
        }
      }
      {
#pragma unroll 1
        for (int i = 0; i < NST; i++) {
          mbar_wait_trap(bar + 48, ph);
          bar += 8;
          if (bar == full0 + 8 * NST) { bar = full0; ph ^= 1; }
        }
      }
    } else if (w == 9) {
      const uint32_t lane = lane_id();
      const uint32_t stg = sb + HSTG + lane * 16;
      uint32_t fph = 0;
#pragma unroll 1
      for (uint32_t layer = 0; layer < 2; layer++) {
        uint4* xb = scr + OFF_X + ((4 + layer) * 8 + j) * SLAB + 28 * 32;
        mbar_wait_sleep(c8_go, layer);
        int n = 0;
#pragma unroll 1
        while (true) {
          if (lane == 0) asm volatile("mbarrier.arrive.expect_tx.shared::cta.b64 _, [%0], 18432;" :: "r"(c8_full) : "memory");
          __syncwarp();
#pragma unroll 1
          for (uint32_t s = 0; s < 9; s++)
            bulk_load(sb + HSTG + s * 2048, s < 8 ? scr + OFF_P + (j + s * 8) * SLAB + 32 * 32 : xb, 2048, c8_full, false);
          mbar_wait(c8_full, fph); fph ^= 1;
          uint32_t bad = 0;
#pragma unroll 8
          for (int s = 0; s < 32; s++) { uint32_t v; asm volatile("ld.shared.b32 %0, [%1];" : "=r"(v) : "r"(stg + s * 512) : "memory"); bad |= v ^ (1 - layer); }
          if (__all_sync(~0u, (bad & 1u) == 0u)) break;
          __nanosleep(300);
          SPIN_GUARD(n);
        }
        asm volatile("bar.arrive 7, 96;" ::: "memory");
        float s0 = 0.f, s1 = 0.f;
#pragma unroll 1
        for (int g = 0; g < 8; g++) {
          const uint32_t a = stg + (g >> 1) * 512 + (g & 1) * 8;
          float a0 = 0.f, a1 = 0.f, a2 = 0.f, a3 = 0.f;
#pragma unroll 1
          for (int b = 0; b < 3; b++) {
            uint32_t v[6];
#pragma unroll
            for (int s = 0; s < 3; s++) lds2(a + (3 * b + s) * 2048, v + 2 * s);
#pragma unroll
            for (int s = 0; s < 3; s++) { a0 += bf_lo(v[2 * s]); a1 += bf_hi(v[2 * s]); a2 += bf_lo(v[2 * s + 1]); a3 += bf_hi(v[2 * s + 1]); }
          }
          sts1(a + 18432, pack_bf16(a0, a1)); sts1(a + 18436, pack_bf16(a2, a3));
          s0 += a0 + a1; s1 += a2 + a3;
        }
        __syncwarp();
        if (lane == 0) mbar_arrive(c8_done);
        s0 = quad_sum(s0); s1 = quad_sum(s1);
        float q0 = 0.f, q1 = 0.f;
        const uint32_t ln = lane_id();
#pragma unroll 1
        for (uint32_t i = 0; i < 4; i++) {
          uint32_t x[4];
          lds4(stg + 18432 + i * 512, x);
          uint4* z = xb + i * 32 + ln;
          asm volatile("" : "+l"(z));
          stg4(z, 0u, 0u, 0u, 0u);
          if (layer == 0) {
            stg4(z - (3 * 8 * SLAB - 128), nz(x[0]), x[1], nz(x[2]), x[3]);
#pragma unroll
            for (int e = 0; e < 4; e++) {
              const float m = (e & 1) ? s1 : s0, c = fmaf(m, -1.f / 64, bf_lo(x[e])), d = fmaf(m, -1.f / 64, bf_hi(x[e]));
              if (e & 1) q1 = fmaf(c, c, fmaf(d, d, q1)); else q0 = fmaf(c, c, fmaf(d, d, q0));
            }
          } else {
            uint32_t* o = (uint32_t*)(out + (128 * t + 32 * (j >> 1) + 2 * (ln >> 2) + (j & 1)) * 576 + 512 + 16 * i + 2 * (ln & 3));
            o[0] = x[0]; o[8 * 576] = x[1]; o[4] = x[2]; o[8 * 576 + 4] = x[3];
          }
        }
        if (layer == 0) {
          q0 = quad_sum(q0); q1 = quad_sum(q1);
          if ((ln & 3) == 0) stg4(scr + OFF_S + j * 96 + 64 + (ln >> 2), __float_as_uint(s0) | 1u, __float_as_uint(q0), __float_as_uint(s1), __float_as_uint(q1));
        }
      }
    } else {
      auto mark = [&](uint32_t k0, uint32_t v) {
        const uint32_t lane = lane_id();
#pragma unroll 1
        for (uint32_t k = k0; k < 6; k++) stg4(scr + OFF_S + (k * 4 + (lane >> 3)) * 96 + j * 8 + (lane & 7), k < 2 ? 0u : v, 0u, 0u, 0u);
      };
      if (w == 11) mark(2, 0u);
      auto phase2_duties = [&](uint32_t layer) {
        const uint32_t lane = lane_id();
        asm volatile("bar.sync 7, 96;" ::: "memory");
        if (w == 11) {
          if (layer == 0) mark(0, 1u);
          __syncwarp();
          if (lane == 0) mbar_arrive(c8_done);
        }
#pragma unroll 1
        for (uint32_t i = 0; i < 16; i++) {
          const uint32_t sl = (w - 10) * 4 + (i >> 2);
          bulk_load(sb + PARK + sl * 2048 + (i & 3) * 512, scr + OFF_X + ((4 + layer) * 8 + sl) * SLAB + row72(4 * j + (i & 3)) * 32, 512, res_full, true);
        }
        mbar_wait_sleep(res_full, layer);
#pragma unroll 1
        for (uint32_t i = 0; i < 16; i++) {
          stg4(scr + OFF_X + ((4 + layer) * 8 + (w - 10) * 4 + (i >> 2)) * SLAB + row72(4 * j + (i & 3)) * 32 + lane, 0u, 0u, 0u, 0u);
          if ((i & 3) == 3) __nanosleep(200);
        }
      };
      if (w == 10) {
        const uint32_t lane = lane_id();
        uint32_t* fl = (uint32_t*)(scratch + OFF_F + (t * 8 + j) * 8) + (lane & 15);
        uint32_t v;
        asm volatile("ld.relaxed.gpu.global.b32 %0, [%1];" : "=r"(v) : "l"(fl) : "memory");
        mbar_wait(piece_full, 0);
        asm volatile("{\n.reg .pred e;\nelect.sync _|e, 0xffffffff;\n@e cp.async.bulk.global.shared::cta.bulk_group [%0], [%1], 2304;\n}\n"
                     "cp.async.bulk.commit_group;\ncp.async.bulk.wait_group 0;\nfence.proxy.async;"
                     :: "l"(scratch + OFF_R + j * 2304 + t * 144), "r"(sb + PIECE) : "memory");
        __syncwarp();
        if (lane < 16) asm volatile("st.release.gpu.global.b32 [%0], 1;" :: "l"((uint32_t*)(scratch + OFF_F + (lane_id() * 8 + j) * 8) + t) : "memory");
        int n = 0;
#pragma unroll 1
        while (!__all_sync(~0u, v != 0u)) {
          __nanosleep(100);
          SPIN_GUARD(n);
          asm volatile("ld.relaxed.gpu.global.b32 %0, [%1];" : "=r"(v) : "l"(fl) : "memory");
        }
        asm volatile("st.relaxed.gpu.global.b32 [%0], 0;" :: "l"(fl) : "memory");
        mbar_wait(x_done, 0);
      }
#pragma unroll 1
      for (uint32_t layer = 0; layer < 3; layer++) {
        if (w == 10 && layer < 2) {
          if (layer) mbar_wait_sleep(park_free, 0);
          const uint4* img = scratch + OFF_R + j * 2304;
          if (lane_id() == 0) asm volatile("mbarrier.arrive.expect_tx.shared::cta.b64 _, [%0], 27648;\nmbarrier.arrive.expect_tx.shared::cta.b64 _, [%1], 9216;"
                                           :: "r"(rem_full), "r"(piece_full) : "memory");
          __syncwarp();
#pragma unroll 1
          for (uint32_t p = 0; p < 3; p++) {
            bulk_load(sb + REM + p * 9216, img + p * 576 + j * 64, 1024, rem_full, false);
            if (j) bulk_load(sb + REM + p * 9216 + 1024, img + p * 576, j * 1024, rem_full, false);
            bulk_load(sb + REM + p * 9216 + (j + 1) * 1024, img + p * 576 + (j + 1) * 64, (8 - j) * 1024, rem_full, false);
          }
#pragma unroll 1
          for (uint32_t i = 0; i < 12; i++)
            bulk_load(sb + REM + 27648 + (i < 8 ? i * 1024 : 6144 + i * 256), img + 1728 + (i < 8 ? (9 * blk(i) + 1) >> 1 : 9 * i - 68) * 16,
                      i < 8 ? 1024 : 256, piece_full, false);
          if (layer == 0) { fetch_x(sb + PARK, j, xbar0); fetch_x(sb + PARK + STAGE, j + 1, xbar0 + 8); }
        }
        if (w == 11 && layer < 2) {
          if (layer) mbar_wait_sleep(park_free, 0);
          __syncwarp();
          if (lane_id() == 0) mbar_arrive(rem_full);
        }
        if (layer) phase2_duties(layer - 1);
        if (layer == 2) break;
        mbar_wait_sleep(layer ? kv_free : x_done, 0);
        if (t > 0) {
          const uint32_t lane = lane_id(), r = lane >> 2, q = lane & 3;
#pragma unroll 1
          for (uint32_t pc = 0; pc < 3; pc++) {
            uint4* hp = scr + OFF_H + ((layer * 8 + j) * 2 + (w - 10)) * 192 + pc * 64 + lane;
            uint32_t hl[8];
            int n = 0;
            hl[4] = 1u;
#pragma unroll 1
            while (true) {
              ldg4(hl, hp);
              if (pc < 2) ldg4(hl + 4, hp + 32);
              if (__all_sync(~0u, hl[0] != 0u && hl[4] != 0u)) break;
              __nanosleep(100);
              SPIN_GUARD(n);
            }
            const uint32_t dst = sb + KVS + (w - 10) * 10368 + r * 144 + q * 4;
            if (pc < 2) {
#pragma unroll
              for (int g = 0; g < 8; g++) sts1(dst + pc * 20736 + odd * 16 + g * 16, hl[g]);
              stg4(hp + 32, 0u, 0u, 0u, 0u);
            } else {
              sts1(dst + (odd ? 0 : 128), hl[0]); sts1(dst + 20736 + (odd ? 0 : 128), hl[1]);
            }
            stg4(hp, 0u, 0u, 0u, 0u);
          }
        }
        asm volatile("bar.arrive 1, 192;" ::: "memory");
        mbar_wait(rem_full, layer);
        mbar_wait(piece_full, 1 - layer);
#pragma unroll 1
        for (uint32_t b = 0; b < 5; b++) {
          const uint32_t blk = sb + REM + 27648 + b * 2048, k = (w - 10) * 32 + lane_id(), rr = k & 7;
          const uint32_t dst = blk + ((k >> 3) & 1) * 1024 + rr * 128 + (((k >> 4) ^ rr) << 4);
          uint32_t v[8];
          lds4(blk + k * 16, v); lds4(blk + 1024 + k * 16, v + 4);
          asm volatile("bar.sync 3, 64;" ::: "memory");
          sts4(dst, v); sts4(dst ^ 64, v + 4);
        }
        asm volatile("fence.proxy.async.shared::cta;" ::: "memory");
        mbar_arrive(remo_full);
        mbar_wait_sleep(xb_done, layer);
        if (w == 10 && layer == 1) {
          const uint32_t lane = lane_id();
          stg4(scr + OFF_S + (lane >> 3) * 96 + j * 8 + (lane & 7), 0u, 0u, 0u, 0u);
          stg4(scr + OFF_S + (4 + (lane >> 3)) * 96 + j * 8 + (lane & 7), 0u, 0u, 0u, 0u);
          if (lane < 8) stg4(scr + OFF_S + j * 96 + 64 + lane, 0u, 0u, 0u, 0u);
        }
#pragma unroll 1
        for (uint32_t i = 0; i < 8 && (w == 11 || layer == 1); i++) {
          zero_share(scr + OFF_X + ((w - 10) * 16 + layer * 8 + i) * SLAB, j, lane_id());
          __nanosleep(500);
        }
      }
    }
  } else {
    asm volatile("setmaxnreg.inc.sync.aligned.u32 240;");
    const bool lead = lane_id() == 0;
    Ring rg{0, 0};
    uint32_t prev = 0;
    uint32_t X[144];
    float rs0, rs1;
    const bool lead2 = lane_id() < 2;
    uint32_t empty_at;
    asm volatile("mapa.shared::cluster.u32 %0, %1, %2;" : "=r"(empty_at) : "r"(empty0), "r"(lane_id() & 1));
    auto release = [&](uint32_t st) { if (lead2) asm volatile("mbarrier.arrive.shared::cluster.b64 _, [%0];" :: "r"(empty_at + st * 8) : "memory"); };
    auto load_kb = [&](int kb, const uint4* src, const char* lo, uint32_t hoff) {
      const uint4* p;
      asm("{\n.reg .pred p;\n.reg .u64 t;\nsetp.ge.u32 p, %2, %3;\nadd.u64 t, %1, -2048;\nselp.b64 %0, t, %1, p;\n}" : "=l"(p) : "l"(src), "r"(j), "r"(kb));
#pragma unroll
      for (int i = 0; i < 4; i++) {
        if (kb == 8) { ldg2(X + 128 + 4 * i, lo + (32 + i) * 512); ldg2(X + 130 + 4 * i, lo + hoff + (32 + i) * 512); }
        else ldg4(X + 16 * kb + 4 * i, p + kb * 128 + i * 32);
      }
    };
    auto check_kb = [&](bool skip, int kb, const uint4* src, const char* lo, uint32_t hoff) {
      int n = 0;
#pragma unroll 1
      while (true) {
        uint32_t m = umin2(umin2(X[16 * kb], X[16 * kb + 4]), umin2(X[16 * kb + 8], X[16 * kb + 12]));
        if (kb == 8) m = umin2(m, umin2(umin2(X[130], X[134]), umin2(X[138], X[142])));
        if (__all_sync(~0u, m != 0u || skip)) break;
        SPIN_GUARD(n);
        load_kb(kb, src, lo, hoff);
      }
    };
#pragma unroll
    for (int i = 0; i < 16; i++) X[i] = 0u;
#pragma unroll 1
    for (uint32_t hf = 0; hf < 4; hf++) {
      const uint32_t layer = hf >> 1;
      const bool ffn = hf & 1;
      const uint32_t tag = 1 - layer;
      uint4* const xbase = scr + OFF_X + (layer * 8 + w) * SLAB;
      float aA[32], aB[32];
      {
        const uint32_t lane = lane_id(), r = lane >> 2, q = lane & 3;
        const uint4* src = xbase + (ffn ? 32 * SLAB : 0) + lane;
        const char* lo = (const char*)src - (ffn ? lane * 8 : 0);
        const uint32_t hoff = ffn ? 256 : 8;
        const uint32_t xoff = (w & 1) * 8192 + (16 * (w >> 1) + (lane & 15)) * 128 + (((lane >> 4) ^ (lane & 7)) << 4);
        auto load_x = [&](uint32_t b, uint32_t* d) {
#pragma unroll
          for (int i = 0; i < 4; i++) ldsm4(xs + b * STAGE + (xoff ^ (32 * i)), d[4 * i], d[4 * i + 1], d[4 * i + 2], d[4 * i + 3]);
        };
        auto load_any = [&](int kb) { if (hf == 0) load_x(blk(kb), X + 16 * kb); else load_kb(kb, src, lo, hoff); };
        float m0, m1, v0, v1;
        STAMP(ffn * 16 + 0);
        if (hf == 0) {
          float sum[2][4] = {}, sq0[4][4] = {}, sq1[4][4] = {};
          uint32_t p0, p1;
          mbar_wait(xbar0, 0);
          ldsm4(xs + xoff, p0, p1, X[0], X[1]);
          p0 = __byte_perm(__shfl_sync(~0u, p0, lane & 28), 0, 0x1010); p1 = __byte_perm(__shfl_sync(~0u, p1, lane & 28), 0, 0x1010);
#pragma unroll 3
          for (uint32_t b = 0; b < 9; b++) {
            uint32_t d[16];
            mbar_wait(xbar0 + 8 * b, 0);
            load_x(b, d);
#pragma unroll
            for (int i = 0; i < 16; i++) d[i] = sub_bf16x2(d[i], (i & 1) ? p1 : p0);
#pragma unroll
            for (int g = 0; g < 8; g++) {
              if (!(g & 1)) mma16(sum[(g >> 1) & 1], d[2 * g], d[2 * g + 1], d[2 * g + 2], d[2 * g + 3], 0x3f803f80u, 0x3f803f80u);
              mma8(sq0[g & 3], d[2 * g], d[2 * g + 1], d[2 * g]); mma8(sq1[g & 3], d[2 * g], d[2 * g + 1], d[2 * g + 1]);
            }
          }
          STAMP(1);
          GSTAMP(14);
#pragma unroll
          for (int kb = 0; kb < GD; kb++) load_x(blk(kb), X + 16 * kb);
          release((x_ring - empty0) / 8);
          auto tot = [](float (&c)[4][4], int e) { return (c[0][e] + c[1][e]) + (c[2][e] + c[3][e]); };
          const float a0 = (sum[0][0] + sum[1][0]) * (1.f / 576), a1 = (sum[0][2] + sum[1][2]) * (1.f / 576);
          const uint32_t dg = (lane & 28) + (r >> 1);
          v0 = fmaxf(fmaf(__shfl_sync(~0u, (r & 1) ? tot(sq0, 1) : tot(sq0, 0), dg), 1.f / 576, -a0 * a0), 0.f);
          v1 = fmaxf(fmaf(__shfl_sync(~0u, (r & 1) ? tot(sq1, 3) : tot(sq1, 2), dg), 1.f / 576, -a1 * a1), 0.f);
          m0 = bf_lo(p0) + a0; m1 = bf_lo(p1) + a1;
        } else {
          uint32_t s[3][4];
          const uint4* p = scr + OFF_S + ((ffn ? 16 : 0) + w) * 96 + q * 8 + r;
          const bool third = !ffn && q == 0;
          const uint32_t rdy = ffn ? tag : 1u;
          int n = 0;
          s[2][0] = rdy; s[2][1] = s[2][2] = s[2][3] = 0u;
#pragma unroll 1
          while (true) {
            ldg4(s[0], p); ldg4(s[1], p + 32);
            if (third) ldg4(s[2], p + 64);
            if (__all_sync(~0u, ((diff2(s[0][0], s[1][0], rdy) | diff2(s[1][0], s[2][0], rdy)) & 1u) == 0u)) break;
            SPIN_GUARD(n);
          }
          STAMP(ffn * 16 + 1);
          ZSTAMP(1 + ffn, 0);
          GSTAMP(14 + ffn);
#pragma unroll
          for (int kb = 1; kb < GD; kb++) load_kb(kb, src, lo, hoff);
          float t0 = 0.f, t1 = 0.f;
#pragma unroll
          for (int i = 0; i < 3; i++) { t0 += __uint_as_float(s[i][0]); t1 += __uint_as_float(s[i][2]); }
          m0 = quad_sum(t0) * (1.f / 576); m1 = quad_sum(t1) * (1.f / 576);
          const float cnt = ffn ? 72.f : 64.f, inv = ffn ? 1.f / 72 : 1.f / 64;
          v0 = 0.f; v1 = 0.f;
#pragma unroll
          for (int i = 0; i < 3; i++) {
            const float c = (i < 2 || third) ? cnt : 0.f;
            const float d0 = fmaf(__uint_as_float(s[i][0]), inv, -m0), d1 = fmaf(__uint_as_float(s[i][2]), inv, -m1);
            v0 += fmaf(d0 * d0, c, __uint_as_float(s[i][1])); v1 += fmaf(d1 * d1, c, __uint_as_float(s[i][3]));
          }
          v0 = quad_sum(v0) * (1.f / 576); v1 = quad_sum(v1) * (1.f / 576);
        }
        rs0 = rsqrtf(v0 + 1e-5f); rs1 = rsqrtf(v1 + 1e-5f);
        const uint32_t mean0 = pack_bf16(m0, m0), mean1 = pack_bf16(m1, m1);
#pragma unroll
        for (int kb = 0; kb < 9; kb++) {
          if (kb > 0) check_kb(hf == 0, kb, src, lo, hoff);
          if (kb + GD < 9) load_any(kb + GD);
          if (kb + GD == 8 && hf == 0 && lead) mbar_arrive(x_done);
#pragma unroll
          for (int i = 16 * kb; i < 16 * kb + 16; i++) X[i] = sub_bf16x2(X[i], (i & 1) ? mean1 : mean0);
          ZSTAMP(1 + ffn, 1 + 3 * kb);
          mbar_wait(full0 + rg.st * 8, rg.ph);
          ZSTAMP(1 + ffn, 2 + 3 * kb);
          const uint64_t desc = DESC_HI | ((sd + rg.st * STAGE) >> 4);
          wg_fence();
#pragma unroll
          for (int i = 0; i < 4; i++) wgmma_rs_n64(aA, X + 4 * (4 * kb + i), desc + i * 128, kb + i != 0);
          if (kb == 8) { wg_commit(); wg_wait<1>(); wg_fence(); }
#pragma unroll
          for (int i = 0; i < 4; i++) wgmma_rs_n64(aB, X + 4 * (4 * kb + i), desc + 512 + i * 128, kb + i != 0);
          wg_commit();
          wg_wait<1>();
          ZSTAMP(1 + ffn, 3 + 3 * kb);
          if (kb > 0) release(prev);
          prev = rg.st; rg.next();
        }
        ZSTAMP(1 + ffn, 28);
        ZSTAMP(4, 0);
        STAMP(ffn * 16 + 2);
      }
      if (!ffn) {
      const uint32_t lane = lane_id(), r = lane >> 2, q = lane & 3;
      const uint32_t kvrow = sb + KVS + (w & 1) * 10368 + (16 * (w >> 1)) * 144;
      uint32_t Q[18], Km[3][8], Ke[3][4];
      const bool edge = (t == 0 && w < 2);
      const uint32_t row0 = edge ? sb + KVS + 8 * 144 : kvrow + (lane & 7) * 144, row1 = kvrow + (8 + (lane & 7)) * 144;
      {
        const uint32_t dst = kvrow + (8 + r) * 144 + q * 4 + odd * 16, dstr = dst + (odd ? -16 : 128);
        const bool edge_out = w >= 6 && t < 15;
        uint4* const hp = scr + TILE + OFF_H + ((layer * 8 + j) * 2 + (w & 1)) * 192 + lane;
        auto put_kv = [&](float (&a)[32], int part, int half) {
          uint32_t hl[4];
#pragma unroll
          for (int i = 0; i < 16; i++) asm volatile("" : "+f"(a[16 * half + i]) :: "memory");
#pragma unroll
          for (int i = 0; i < 4; i++) {
            const int g = 4 * half + i;
            hl[i] = pack_bf16(a[4 * g + 2] * rs1, a[4 * g + 3] * rs1);
            sts1(dst + part * 20736 + g * 16, pack_bf16(a[4 * g] * rs0, a[4 * g + 1] * rs0)); sts1(dst + part * 20736 + 8 * 144 + g * 16, hl[i]);
          }
          if (edge_out) stg4(hp + part * 64 + half * 32, nz(hl[0]), hl[1], hl[2], hl[3]);
        };
        put_kv(aA, 0, 0); put_kv(aA, 0, 1);
        wg_wait<0>();
        release(prev);
        float aR[12];
        mbar_wait(rem_full, layer);
        const uint64_t dr = DESC_REM | ((sd + REM) >> 4);
        wg_fence();
#pragma unroll
        for (int s = 0; s < 36; s++) {
          wgmma_rs_n24(aR, X + 4 * s, dr + s * 16, s != 0);
          if (s == 4) put_kv(aB, 1, 0);
          if (s == 16) put_kv(aB, 1, 1);
        }
        wg_commit();
#pragma unroll
        for (int kb = 0; kb < 9; kb++) {
          if (kb == HQ && w < 4) asm volatile("bar.sync 4, 256;" ::: "memory");
          if (!(kb & 1)) mbar_wait(full0 + rg.st * 8, rg.ph);
          const uint64_t desc = DESC_HI | ((sd + rg.st * STAGE + (kb & 1) * 8192) >> 4);
          wg_fence();
#pragma unroll
          for (int i = 0; i < 4; i++) wgmma_rs_n64(aB, X + 4 * (4 * kb + i), desc + i * 128, kb + i != 0);
          wg_commit();
          wg_wait<1>();
          if (kb > 0 && !(kb & 1)) release(prev);
          if ((kb & 1) || kb == 8) { prev = rg.st; rg.next(); }
          if (kb == 0) {
            pin(aR);
            const uint32_t k1 = pack_bf16(aR[2] * rs1, aR[3] * rs1), v1 = pack_bf16(aR[6] * rs1, aR[7] * rs1);
            if (edge_out) stg4(hp + 128, nz(k1), v1, 0u, 0u);
            sts1(dstr, pack_bf16(aR[0] * rs0, aR[1] * rs0)); sts1(dstr + 8 * 144, k1);
            sts1(dstr + 20736, pack_bf16(aR[4] * rs0, aR[5] * rs0)); sts1(dstr + 20736 + 8 * 144, v1);
            Q[16] = pack_bf16(aR[8], aR[9]); Q[17] = pack_bf16(aR[10], aR[11]);
            if (w < 4) asm volatile("bar.arrive 2, 256;" ::: "memory");
          }
          if (kb == 8) {
            if (w < 4) asm volatile("bar.sync 1, 192;" ::: "memory");
            else asm volatile("bar.sync 2, 256;" ::: "memory");
#pragma unroll
            for (int nt = 0; nt < 3; nt++) {
              const uint32_t ra = (nt == 0 ? row0 : row1 + (nt - 1) * 8 * 144);
              ldsm4(ra + odd * 16 + (lane >> 3) * 16, Km[nt][0], Km[nt][1], Km[nt][2], Km[nt][3]);
              ldsm4(ra + odd * 16 + 64 + (lane >> 3) * 16, Km[nt][4], Km[nt][5], Km[nt][6], Km[nt][7]);
              ldsm4(ra + (odd ? 0 : 32) + (lane >> 3) * 32, Ke[nt][0], Ke[nt][1], Ke[nt][2], Ke[nt][3]);
            }
            const uint32_t ge = (2u << q) - 1, le = 0xfu << q, on = edge ? 0u : ~0u;
            const uint32_t bits = odd ? 0xfu | ((le & 0xfu) << 4) | (ge << 8) : ge | 0xf0u | (le << 8);
#pragma unroll
            for (int h = 0; h < 4; h++) {
              const uint32_t ma = bitmask(bits, h), mb = bitmask(bits, 4 + h), mc = bitmask(bits, 8 + h);
              Km[0][2 * h] &= ma & on; Km[0][2 * h + 1] &= mb & on; Ke[0][h] &= mc & on;
#pragma unroll
              for (int nt = 1; nt < 3; nt++) { Km[nt][2 * h] &= ma; Km[nt][2 * h + 1] &= mb; Ke[nt][h] &= mc; }
            }
          }
        }
        wg_wait<0>();
        release(prev);
        pin(aB);
        if (HQ == 9 && w < 4) asm volatile("bar.sync 4, 256;" ::: "memory");
        if (DLY && w < 4) asm volatile("{\n.reg .pred p;\n.reg .u32 a, b;\nmov.u32 a, %%clock;\nW: nanosleep.u32 20;\nmov.u32 b, %%clock;\nsub.u32 b, b, a;\nsetp.lt.u32 p, b, %0;\n@p bra.uni W;\n}" :: "n"(DLY) : "memory");
        STAMP(3);
#pragma unroll
        for (int i = 0; i < 16; i++) Q[i] = pack_bf16(aB[2 * i], aB[2 * i + 1]);
      }
      uint32_t res[18] = {};
      if (layer) {
        const uint4* p = xbase + ((9 * j + 1) >> 1) * 32 + lane;
#pragma unroll
        for (int i = 0; i < 4; i++) ldg4(res + 4 * i, p + i * 32);
        ldg2(res + 16, odd ? (const char*)(p - 32) + 8 : (const char*)(p + 4 * 32));
      }
      {
        uint32_t V01[12][2], V2[12];
        const uint32_t rv = ((lane & 8) ? row1 : row0) + 20736, rw = row1 + 8 * 144 + 20736;
#pragma unroll
        for (int i = 0; i < 4; i++) ldsm4t(rv + odd * 16 + i * 32 + (lane >> 4) * 16, V01[2 * i][0], V01[2 * i][1], V01[2 * i + 1][0], V01[2 * i + 1][1]);
#pragma unroll
        for (int i = 0; i < 2; i++) ldsm4t(rv + (odd ? 0 : 32) + i * 64 + (lane >> 4) * 32, V01[8 + 2 * i][0], V01[8 + 2 * i][1], V01[9 + 2 * i][0], V01[9 + 2 * i][1]);
        ldsm4t(rw + odd * 16 + (lane >> 3) * 16, V2[0], V2[1], V2[2], V2[3]);
        ldsm4t(rw + odd * 16 + 64 + (lane >> 3) * 16, V2[4], V2[5], V2[6], V2[7]);
        ldsm4t(rw + (odd ? 0 : 32) + (lane >> 3) * 32, V2[8], V2[9], V2[10], V2[11]);
        const bool up0 = 2 * q > r, up1 = 2 * q + 1 > r;
        const uint32_t upm = (up0 ? 0xffffu : 0u) | (up1 ? 0xffff0000u : 0u);
        const float c0 = 0.23570226039551584f * 1.4426950408889634f * rs0, c1 = 0.23570226039551584f * 1.4426950408889634f * rs1;
        const float masked = edge ? -1e9f * 1.4426950408889634f * rcp(c0) : 0.f;
        uint32_t Om[16], Oe[8];
        uint4* const po = xbase + 16 * SLAB + 4 * j * 32 + lane;
#pragma unroll
        for (int h = 0; h < 4; h++) {
          const uint32_t e0 = odd ? Q[(4 * h + 16) % 18] : Q[4 * h + 4], e1 = odd ? Q[(4 * h + 17) % 18] : Q[4 * h + 5];
          float S[3][4];
#pragma unroll
          for (int nt = 0; nt < 3; nt++) {
            mma16c(S[nt], Q + 4 * h, Km[nt][2 * h], Km[nt][2 * h + 1], nt == 0 ? masked : 0.f);
            mma8(S[nt], e0, e1, Ke[nt][h]);
          }
          const float s00 = up0 ? S[0][0] : S[1][0], s01 = up1 ? S[0][1] : S[1][1];
          const float s10 = up0 ? S[1][2] : S[2][2], s11 = up1 ? S[1][3] : S[2][3];
          const float m0 = quad_max(fmaxf(s00, s01)) * c0, m1 = quad_max(fmaxf(s10, s11)) * c1;
          const float p00 = ex2(fmaf(s00, c0, -m0)), p01 = ex2(fmaf(s01, c0, -m0)), p10 = ex2(fmaf(s10, c1, -m1)), p11 = ex2(fmaf(s11, c1, -m1));
          const float i0 = rcp(quad_sum(p00 + p01)), i1 = rcp(quad_sum(p10 + p11));
          const uint32_t p0 = pack_bf16(p00 * i0, p01 * i0), p1 = pack_bf16(p10 * i1, p11 * i1);
          const uint32_t pf[4] = {p0 & upm, 0u, p0 & ~upm, p1 & upm};
#pragma unroll
          for (int gi = 0; gi < 3; gi++) {
            const int g = gi < 2 ? 2 * h + gi : 8 + h;
            float o[4];
            mma16c(o, pf, V01[g][0], V01[g][1], 0.f);
            mma8(o, 0u, p1 & ~upm, V2[g]);
            uint32_t* d = gi < 2 ? Om + 2 * g : Oe + 2 * h;
            d[0] = pack_bf16(o[0], o[1]); d[1] = pack_bf16(o[2], o[3]);
          }
          if (h > 0) {
#pragma unroll
            for (int e = 0; e < 2; e++) {
              if (!odd && q < h) Om[4 * h + e] = Oe[2 * h - 2 + e];
              if (odd && q >= h) Om[4 * h - 2 + e] = Oe[2 * h + e];
            }
            stg4(po + (h - 1) * 32, nz(Om[4 * h - 4]), Om[4 * h - 3], Om[4 * h - 2], Om[4 * h - 1]);
            if (HQ <= 9 && h == 1 && w >= 4) asm volatile("bar.arrive 4, 256;" ::: "memory");
          }
        }
        STAMP(4);
        stg4(po + 96, nz(Om[12]), Om[13], Om[14], Om[15]);
        stg2((char*)(xbase + 16 * SLAB + 1024 + j * 16) + lane * 8, nz(odd ? Oe[0] : Oe[6]), odd ? Oe[1] : Oe[7]);
#pragma unroll
        for (int i = 0; i < 16; i++) X[i] = Om[i];
      }
      if (lane == 0) asm volatile("st.relaxed.gpu.global.b32 [%0], %1;" :: "l"(scr + OFF_S + (8 + w) * 96 + j * 8), "r"(tag) : "memory");
      {
        if (layer == 0) {
          const uint32_t xrow = (w & 1) * 8192 + (16 * (w >> 1) + (lane & 15)) * 128;
          uint32_t u0, u1;
          mbar_wait(xbar0, 1); mbar_wait(xbar0 + 8, 1);
#pragma unroll
          for (int i = 0; i < 5; i++) {
            const uint32_t g = i < 4 ? j + odd + 2 * i : j + (odd ? 0 : 8);
            const uint32_t a = sb + PARK + (g >> 3) * STAGE + xrow;
            if (i < 4) ldsm4(a + ((((g & 7) + (lane >> 4)) ^ (lane & 7)) << 4), res[4 * i], res[4 * i + 1], res[4 * i + 2], res[4 * i + 3]);
            else ldsm4(a + (((g & 7) ^ (lane & 7)) << 4), res[16], res[17], u0, u1);
          }
        }
        const uint4* src = xbase + 16 * SLAB + lane;
        const uint32_t st0 = rg.st;
        auto stage_of = [&](uint32_t i) { const uint32_t x = st0 + i; return x >= NST ? x - NST : x; };
        {
          const uint32_t x = st0 + lane, wrap = x >= NST;
          mbar_wait(lane < 5 ? full0 + (x - wrap * NST) * 8 : remo_full, lane < 5 ? rg.ph ^ wrap : layer);
          __syncwarp();
          if (st0) { rg.st = st0 - 1; rg.ph ^= 1; } else rg.st = 5;
        }
        float acc[36];
        auto block72 = [&](uint32_t kb, uint32_t base, const uint32_t* a) {
          const uint64_t d0 = DESC_HI | ((base >> 4) + (((sd + REM + 27648 + (kb >> 1) * 2048 + (kb & 1) * 64 - base) >> 4) << 16));
          wg_fence();
#pragma unroll
          for (int i = 0; i < 4; i++) wgmma_rs_n72(acc, a + 4 * i, d0 - (uint64_t)(i * ((127u << 16) - 128u)), 1);
          wg_commit();
        };
#pragma unroll
        for (int i = 0; i < 18; i++) { acc[2 * i] = bf_lo(res[i]); acc[2 * i + 1] = bf_hi(res[i]); }
        block72(0, sd + st0 * STAGE, X);
        {
          const uint4* fp = scr + OFF_S + (8 + w) * 96 + (lane & 7) * 8;
          int n = 0;
          STAMP(8);
#pragma unroll 1
          while (true) {
            uint32_t f;
            asm volatile("ld.relaxed.gpu.global.b32 %0, [%1];" : "=r"(f) : "l"(fp) : "memory");
            if (__all_sync(~0u, f == tag)) break;
            SPIN_GUARD(n);
          }
          STAMP(9);
        }
#pragma unroll
        for (int kb = 1; kb < GO; kb++) load_kb(kb, src, (const char*)src - lane * 8, 256);
        uint32_t m = ~0u;
#pragma unroll
        for (int kb = 1; kb < 9; kb++) {
          m = umin2(m, umin2(umin2(X[16 * kb], X[16 * kb + 4]), umin2(X[16 * kb + 8], X[16 * kb + 12])));
          if (kb == 8) m = umin2(m, umin2(umin2(X[130], X[134]), umin2(X[138], X[142])));
          if (kb + GO - 1 < 9) {
            const uint4* s2 = src + (m == 0u);
            load_kb(kb + GO - 1, s2, (const char*)s2 - lane * 8, 256);
          }
          block72(kb, sd + stage_of(kb >> 1) * STAGE + (kb & 1) * 8192, X + 16 * kb);
          if (!(kb & 1)) { wg_wait<1>(); release(stage_of((kb >> 1) - 1)); }
        }
        uint32_t redo;
        asm volatile("{\n.reg .pred p;\nsetp.eq.u32 p, %1, 0;\nbar.red.or.pred p, %2, 128, p;\nselp.u32 %0, 1, 0, p;\n}" : "=r"(redo) : "r"(m), "r"(5 + (w >> 2)) : "memory");
        wg_wait<0>();
        release(stage_of(4));
        pin(acc);
        if (__any_sync(~0u, redo || FORCE_REDO)) {
#pragma unroll
          for (int i = 0; i < 18; i++) { res[i] = __shfl_sync(~0u, res[i], lane); acc[2 * i] = bf_lo(res[i]); acc[2 * i + 1] = bf_hi(res[i]); }
          const uint32_t box = PARK + 2 * STAGE + (w >> 2) * 8192, bar = redo_full + (w >> 2) * 8;
#pragma unroll 1
          for (uint32_t kb = 0; kb < 10; kb++) {
            asm volatile("bar.sync %0, 128;" :: "r"(5 + (w >> 2)) : "memory");
            if ((w & 3) == 0)
              asm volatile("{\n.reg .pred e;\nelect.sync _|e, 0xffffffff;\n@e mbarrier.arrive.expect_tx.shared::cta.b64 _, [%2], 8192;\n"
                           "@e cp.async.bulk.tensor.3d.shared::cluster.global.mbarrier::complete_tx::bytes [%0], [%1, {%3, %4, %5}], [%2];\n}"
                           :: "r"(sb + box), "l"(&maps.m[kb >= 8 ? 8 : 1]), "r"(bar), "r"(72 * j + 8 * odd), "r"(kb >= 8 ? 64 : 0),
                              "r"(kb >= 8 ? 0 : (9 * blk(kb) + 1) >> 1) : "memory");
            mbar_wait(bar, kb & 1);
            if (kb == 9) break;
            int n = 0;
#pragma unroll 1
            while (true) {
              const char* l = (const char*)(src + blk(kb) * 128) - (kb == 8 ? lane * 8 : 0);
#pragma unroll
              for (int i = 0; i < 4; i++) ldg2(X + 4 * i, l + i * 512);
              uint32_t mm = umin2(umin2(X[0], X[4]), umin2(X[8], X[12]));
              l += (kb == 8 ? 256 : 8) + (mm == 0u ? 16 : 0);
#pragma unroll
              for (int i = 0; i < 4; i++) ldg2(X + 4 * i + 2, l + i * 512);
              if (kb == 8) mm = umin2(mm, umin2(umin2(X[2], X[6]), umin2(X[10], X[14])));
              if (__all_sync(~0u, mm != 0u)) break;
              SPIN_GUARD(n);
            }
            block72(kb, sd + box, X);
            wg_wait<0>();
            pin(acc);
          }
        }
        STAMP(10);
#pragma unroll
        for (int i = 0; i < 18; i++) res[i] = pack_bf16(acc[2 * i], acc[2 * i + 1]);
        if (j < PRI) put72(xbase + 32 * SLAB, j, lane, res);
        publish_stats<9>(scr + OFF_S + (16 + w) * 96 + j * 8, acc, tag, lane);
        if (j >= PRI) put72(xbase + 32 * SLAB, j, lane, res);
#pragma unroll
        for (int i = 0; i < 16; i++) X[i] = res[i];
      }
      continue;
      }
      const uint32_t hp = sb + PARK + w * 512 + lane_id() * 16;
      auto pack8 = [&](float (&a)[32], int p, uint32_t* o) {
#pragma unroll
        for (int e = 0; e < 8; e++) asm volatile("" : "+f"(a[8 * p + e]) :: "memory");
#pragma unroll
        for (int e = 0; e < 4; e++) o[e] = pack_bf16(a[8 * p + 2 * e], a[8 * p + 2 * e + 1]);
      };
      const float ka0 = 0.7978845608028654f * rs0, kb0 = 0.044715f * ka0 * rs0 * rs0, ku0 = 0.5f * rs0 * rs0;
      const float ka1 = 0.7978845608028654f * rs1, kb1 = 0.044715f * ka1 * rs1 * rs1, ku1 = 0.5f * rs1 * rs1;
      auto packu8 = [&](int p, uint32_t* o) {
#pragma unroll
        for (int e = 0; e < 8; e++) asm volatile("" : "+f"(aA[8 * p + e]) :: "memory");
#pragma unroll
        for (int e = 0; e < 4; e++) o[e] = pack_bf16(aA[8 * p + 2 * e] * ((e & 1) ? ku1 : ku0), aA[8 * p + 2 * e + 1] * ((e & 1) ? ku1 : ku0));
      };
      auto geglu8 = [&](int p, uint32_t* u) {
#pragma unroll
        for (int e = 0; e < 8; e++) asm volatile("" : "+f"(aB[8 * p + e]) :: "memory");
        float h[8];
#pragma unroll
        for (int e = 0; e < 8; e++) {
          const float g = aB[8 * p + e];
          h[e] = fmaf(g, tanh_ap(g * fmaf(g * g, (e & 2) ? kb1 : kb0, (e & 2) ? ka1 : ka0)), g);
        }
#pragma unroll
        for (int e = 0; e < 4; e++) u[e] = mul_bf16x2(pack_bf16(h[2 * e], h[2 * e + 1]), u[e]);
      };
      auto box = [&](int b, auto&& filler) {
        const int kb = b < 9 ? b : b - 9;
        if (!(b & 1)) { if (b == 0) mbar_wait_trap(full0 + rg.st * 8, rg.ph); else mbar_wait(full0 + rg.st * 8, rg.ph); }
        const uint64_t desc = DESC_HI | ((sd + rg.st * STAGE + (b & 1) * 8192) >> 4);
        wg_fence();
#pragma unroll
        for (int i = 0; i < 4; i++) {
          if (b < 9) wgmma_rs_n64(aA, X + 4 * (4 * kb + i), desc + i * 128, kb + i != 0);
          else wgmma_rs_n64(aB, X + 4 * (4 * kb + i), desc + i * 128, kb + i != 0);
          if (i == 2) filler();
        }
        wg_commit();
        if (b & 1) { prev = rg.st; rg.next(); } else { wg_wait<1>(); release(prev); }
      };
      auto nop = [] {};
      auto step = [&](int st, auto&& filler) { box(2 * st, nop); box(2 * st + 1, filler); };
#pragma unroll
      for (int p = 0; p < 4; p++) { uint32_t o[4]; packu8(p, o); sts4(hp + p * 4096, o); }
      box(0, nop);
      if (lead) mbar_arrive(xb_done);
#pragma unroll 1
      for (int c = 1;; c++) {
        const uint32_t hc = hp + c * 4 * 4096;
#pragma unroll
        for (int b = 1; b < 18; b++) box(b, [&] {
          if ((b & 1) && b < 8) { uint32_t o[4]; const uint32_t a = hc - (4 - (b >> 1)) * 4096; lds4(a, o); geglu8(b >> 1, o); sts4(a, o); }
          if ((b & 1) && b > 10) { uint32_t o[4]; packu8((b - 11) >> 1, o); if (c < 8) sts4(hc + ((b - 11) >> 1) * 4096, o); } });
        ZSTAMP(4, c);
        if (c == 8) break;
        box(0, nop);
      }
      wg_wait<0>();
      STAMP(21);
      GSTAMP(19);
      auto unpark = [&](int kb) {
#pragma unroll
        for (int s = 4 * kb; s < 4 * kb + 4; s++) lds4(hp + s * 4096, X + 4 * s);
      };
      unpark(0);
      uint32_t U[16];
#pragma unroll
      for (int p = 0; p < 4; p++) packu8(p, U + 4 * p);
#pragma unroll
      for (int b = 0; b < 8; b++) box(b, [&] {
        if (b < 7) unpark(b + 1);
        if (b & 1) {
          geglu8(b >> 1, U + 2 * (b - 1));
          if (rg.ph > 1) sts4(hp, U + 2 * (b - 1));
#pragma unroll
          for (int i = 0; i < 4; i++) X[128 + 2 * (b - 1) + i] = U[2 * (b - 1) + i];
        } });
      STAMP(24);
      if (layer == 0 && lead) mbar_arrive(park_free);
      const uint32_t lane2 = lane_id();
      uint4* const pw = scr + OFF_P + (j * 8 + w) * SLAB + lane2;
      const uint4* const pr = scr + OFF_P + w * SLAB + 4 * j * 32 + lane2;
      auto put_part = [&](float (&a)[32], int p, uint32_t chunk) {
        uint32_t o[4];
        pack8(a, p, o);
        stg4(pw + (chunk * 4 + p) * 32, (o[0] & ~1u) | tag, o[1], o[2], o[3]);
      };
      auto slot = [&](int p) { return sb + w * 2048 + (p < 3 ? PARK + p * 16384 : KVS + (p - 3) * 16384); };
      auto fetch = [&](int p) {
        bulk_load(slot(p), scr + OFF_P + (((j - p) & 7) * 8 + w) * SLAB + 4 * j * 32, 2048, pbar0 + w * 8, true);
      };
#pragma unroll 1
      for (int sp = 0;; sp++) {
        const uint32_t ca = sp == 0 ? 8 : ((j + 2 * sp) & 7), cb = (j + 2 * sp + 1) & 7;
        if (sp == 1 && lead) mbar_arrive(c8_go);
#pragma unroll
        for (int st = 4; st < 9; st++) step(st, [&] {
          if (st == 5 || st == 6) { put_part(aA, 2 * (st - 5), ca); put_part(aA, 2 * (st - 5) + 1, ca); }
          if (st == 8 && sp > 1) { if (sp == 3) mbar_wait(c8_done, layer); fetch(2 * sp - 2); } });
        STAMP(25 + sp);
        if (sp == 3) break;
#pragma unroll
        for (int st = 0; st < 4; st++) step(st, [&] {
          if (st < 2) { put_part(aB, 2 * st, cb); put_part(aB, 2 * st + 1, cb); }
          if (st == 3 && sp > 0) fetch(2 * sp - 1); });
      }
      auto load_p = [&](int p, uint32_t* d) {
#pragma unroll
        for (int i = 0; i < 4; i++) ldg4(d + 4 * i, pr + ((j - p) & 7) * 8 * SLAB + i * 32);
      };
#pragma unroll
      for (int b = 0; b < 9; b++) {
        box(b, [&] {
          if (b == 1) {
#pragma unroll
            for (int p = 0; p < 4; p++) put_part(aB, p, (j + 7) & 7);
          }
          if (b == 3) { load_p(5, X); load_p(6, X + 16); }
          if (b == 7) load_p(7, X + 32); });
      }
      mbar_wait(res_full, layer);
      mbar_wait(pbar0 + w * 8, layer);
#pragma unroll
      for (int p = 1; p < 5; p++)
#pragma unroll
        for (int i = 0; i < 4; i++) lds4(slot(p) + lane2 * 16 + i * 512, X + 48 + 16 * p + 4 * i);
#pragma unroll
      for (int i = 0; i < 4; i++) {
        const bool split = j == 2 * i + 1;
        const uint32_t a = slot(0) + i * 512 + (split ? lane2 * 8 : lane2 * 16);
        lds2(a, X + 48 + 4 * i); lds2(a + (split ? 256 : 8), X + 50 + 4 * i);
      }
      wg_wait<0>();
      release(rg.st); rg.next();
      pin(aA);
      STAMP(22);
      GSTAMP(20);
      {
        const uint32_t lane = lane2, r = lane >> 2, q = lane & 3;
        const uint32_t eye = r == 2 * q ? 0x3f80u : r == 2 * q + 1 ? 0x3f800000u : 0u;
        auto bad = [&](const uint32_t* d) { return diff2(d[0], d[4], tag) | diff2(d[8], d[12], tag); };
        auto add = [&](const uint32_t* d) {
#pragma unroll
          for (int g = 0; g < 8; g++) mma8(aA + 4 * g, d[2 * g], d[2 * g + 1], eye);
        };
        int n = 0;
#pragma unroll 1
        while (!__all_sync(~0u, ((or3(bad(X), bad(X + 16), bad(X + 64)) | or3(bad(X + 80), bad(X + 96), bad(X + 112))) & 1u) == 0u)) {
          SPIN_GUARD(n);
          load_p(5, X); load_p(6, X + 16);
#pragma unroll
          for (int p = 1; p < 5; p++) load_p(p, X + 48 + 16 * p);
        }
        add(X); add(X + 16);
#pragma unroll
        for (int p = 4; p >= 0; p--) add(X + 48 + 16 * ((p + 1) % 5));
        STAMP(11);
#pragma unroll 1
        while (!__all_sync(~0u, (bad(X + 32) & 1u) == 0u)) { SPIN_GUARD(n); load_p(7, X + 32); }
        add(X + 32);
        STAMP(12);
        uint32_t res[16];
#pragma unroll
        for (int i = 0; i < 16; i++) X[i] = res[i] = pack_bf16(aA[2 * i], aA[2 * i + 1]);
        if (layer == 0) {
          uint4* p = xbase + 8 * SLAB + 4 * j * 32 + lane;
          auto put = [&] {
#pragma unroll
            for (int i = 0; i < 4; i++) stg4(p + i * 32, nz(res[4 * i]), res[4 * i + 1], res[4 * i + 2], res[4 * i + 3]);
          };
          if (j < PRI) put();
          publish_stats<8>(scr + OFF_S + w * 96 + j * 8, aA, 1u, lane);
          if (j >= PRI) put();
          if (lane == 0) mbar_arrive(kv_free);
        } else {
          const uint32_t tb = slot(0);
          __syncwarp();
#pragma unroll
          for (int i = 0; i < 4; i++) {
            const uint32_t row = (lane2 & 7) + (lane2 & 8), g = 2 * i + (lane2 >> 4);
            asm volatile("stmatrix.sync.aligned.m8n8.x4.shared.b16 [%0], {%1,%2,%3,%4};"
                         :: "r"(tb + row * 128 + ((g ^ (row & 7)) << 4)), "r"(res[4 * i]), "r"(res[4 * i + 1]), "r"(res[4 * i + 2]), "r"(res[4 * i + 3]) : "memory");
          }
          __syncwarp();
#pragma unroll
          for (int i = 0; i < 4; i++) {
            const uint32_t row = 4 * i + (lane2 >> 3), g = lane2 & 7;
            uint32_t v[4];
            lds4(tb + row * 128 + ((g ^ (row & 7)) << 4), v);
            *(uint4*)(out + (128 * t + 32 * (w >> 1) + 2 * row + (w & 1)) * 576 + 64 * j + 8 * g) = make_uint4(v[0], v[1], v[2], v[3]);
          }
        }
      }
      STAMP(23);
    }
  }
}

typedef CUresult (*EncodeFn)(CUtensorMap*, CUtensorMapDataType, cuuint32_t, void*, const cuuint64_t*, const cuuint64_t*,
                             const cuuint32_t*, const cuuint32_t*, CUtensorMapInterleave, CUtensorMapSwizzle,
                             CUtensorMapL2promotion, CUtensorMapFloatOOBfill);

CUtensorMap make_map(EncodeFn f, const void* p, uint64_t cols, uint64_t rows, uint64_t grp) {
  CUtensorMap m;
  cuuint64_t dims[3] = {cols, grp, rows / grp}, str[2] = {cols * 2, cols * 2 * grp};
  cuuint32_t box[3] = {64, 16, 4}, es[3] = {1, 1, 1};
  f(&m, CU_TENSOR_MAP_DATA_TYPE_BFLOAT16, 3, const_cast<void*>(p), dims, str, box, es, CU_TENSOR_MAP_INTERLEAVE_NONE,
    CU_TENSOR_MAP_SWIZZLE_128B, CU_TENSOR_MAP_L2_PROMOTION_NONE, CU_TENSOR_MAP_FLOAT_OOB_FILL_NONE);
  return m;
}
CUtensorMap make_rem_map(EncodeFn f, const void* p, uint64_t cols) {
  CUtensorMap m;
  cuuint64_t dims[2] = {cols, 576}, str[1] = {cols * 2};
  cuuint32_t box[2] = {8, 144}, es[2] = {1, 1};
  f(&m, CU_TENSOR_MAP_DATA_TYPE_BFLOAT16, 2, const_cast<void*>(p), dims, str, box, es, CU_TENSOR_MAP_INTERLEAVE_NONE,
    CU_TENSOR_MAP_SWIZZLE_NONE, CU_TENSOR_MAP_L2_PROMOTION_NONE, CU_TENSOR_MAP_FLOAT_OOB_FILL_NONE);
  return m;
}

}

extern "C" void kernel_launch(void* const* d_in, const int* in_sizes, int n_in, void* d_out, int out_size) {
  void* fn = nullptr;
  cudaDriverEntryPointQueryResult qr;
  cudaGetDriverEntryPoint("cuTensorMapEncodeTiled", &fn, cudaEnableDefault, &qr);
  EncodeFn enc = (EncodeFn)fn;
  Maps maps;
  maps.m[0] = make_map(enc, d_in[1], 1728, 576, 16); maps.m[1] = make_map(enc, d_in[2], 576, 576, 16);
  maps.m[2] = make_map(enc, d_in[4], 4608, 576, 16); maps.m[3] = make_map(enc, d_in[5], 4608, 576, 16);
  maps.m[4] = make_map(enc, d_in[6], 576, 4608, 16);
  maps.m[5] = make_rem_map(enc, d_in[1], 1728); maps.m[6] = make_rem_map(enc, d_in[2], 576);
  maps.m[8] = make_map(enc, d_in[2], 576, 576, 144); maps.m[9] = make_map(enc, d_in[4], 4608, 576, 144);
  maps.m[10] = make_map(enc, d_in[5], 4608, 576, 144);
  {
    cuuint64_t dims[3] = {576, 1024, 2}, str[2] = {2304, 1152};
    cuuint32_t box[3] = {64, 64, 2}, es[3] = {1, 1, 1};
    enc(&maps.m[7], CU_TENSOR_MAP_DATA_TYPE_BFLOAT16, 3, d_in[0], dims, str, box, es, CU_TENSOR_MAP_INTERLEAVE_NONE,
        CU_TENSOR_MAP_SWIZZLE_128B, CU_TENSOR_MAP_L2_PROMOTION_NONE, CU_TENSOR_MAP_FLOAT_OOB_FILL_NONE);
  }
  void* scr = nullptr;
  cudaGetSymbolAddress(&scr, g_scratch);
  cudaFuncSetAttribute(mega_kernel, cudaFuncAttributeMaxDynamicSharedMemorySize, SMEM_BYTES);
  cudaLaunchConfig_t cfg = {};
  cfg.gridDim = dim3(128); cfg.blockDim = dim3(384); cfg.dynamicSmemBytes = SMEM_BYTES; cfg.stream = cudaStreamPerThread;
  cudaLaunchAttribute at[1];
  at[0].id = cudaLaunchAttributeClusterDimension; at[0].val.clusterDim.x = 2; at[0].val.clusterDim.y = 1; at[0].val.clusterDim.z = 1;
  cfg.attrs = at; cfg.numAttrs = 1;
  int dev = 0, sms = 0, clusters = 0;
  cudaGetDevice(&dev);
  cudaDeviceGetAttribute(&sms, cudaDevAttrMultiProcessorCount, dev);
  cudaOccupancyMaxActiveClusters(&clusters, mega_kernel, &cfg);
  if (sms == 132 && clusters == 66) cfg.gridDim = dim3(132);
  cudaLaunchKernelEx(&cfg, mega_kernel, maps, (uint4*)scr, (__nv_bfloat16*)d_out);
}
```

```cpp
#include <cuda_runtime.h>
#include <cuda.h>
#include <cuda_bf16.h>
#include <stdint.h>

#define TRACE 0
#define GUARD 0
#define FORCE_REDO 0
#define ZT 0

namespace {

constexpr int NST = 6;
constexpr int STAGE = 16384;
constexpr int PARK = NST * STAGE;
constexpr int REM = PARK + 49152;
constexpr int KVS = REM + 40960;
constexpr int PIECE = PARK + 7 * STAGE;
constexpr int HSTG = KVS + 16384;
constexpr int BARS = KVS + 41472;
constexpr int TRC = BARS + 512;
constexpr int SMEM_BYTES = TRC + (TRACE ? 512 : 0);
static_assert(NST == 6, "the producer addresses empty barriers as full + 48");
static_assert(BARS >= PARK + 131072, "barriers overlap park");
static_assert(SMEM_BYTES <= 232448, "smem");

constexpr int SLAB = 36 * 32;
constexpr int SPIN_MAX = 1 << 17;
constexpr uint32_t PRI = 4;
constexpr int GD = 3, GO = 5;
constexpr int OFF_S = 0;
constexpr int OFF_H = OFF_S + 3 * 8 * 96;
constexpr int OFF_X = OFF_H + 2 * 8 * 384;
constexpr int OFF_P = OFF_X + 6 * 8 * SLAB;
constexpr int TILE = OFF_P + 8 * 8 * SLAB;
constexpr int OFF_R = 16 * TILE;
constexpr int OFF_F = OFF_R + 8 * 2304;
constexpr int SCRATCH = OFF_F + 128 * 8;

}

__device__ uint4 g_scratch[SCRATCH];

namespace {

constexpr uint64_t DESC_HI = 0x4000004000000000ull;
constexpr uint64_t DESC_REM = (576ull << 32) | (8u << 16);
__device__ __forceinline__ void wgmma_rs_n64(float (&d)[32], const uint32_t* a, uint64_t desc, int scale_d) {
  asm volatile("{\n.reg .pred p;\nsetp.ne.b32 p, %37, 0;\n"
    "wgmma.mma_async.sync.aligned.m64n64k16.f32.bf16.bf16 "
    "{%0, %1, %2, %3, %4, %5, %6, %7, %8, %9, %10, %11, %12, %13, %14, %15, %16, %17, %18, %19, %20, %21, %22, %23, %24, %25, %26, %27, %28, %29, %30, %31}, "
    "{%32, %33, %34, %35}, %36, p, 1, 1, 1;\n}\n"
    : "+f"(d[0]), "+f"(d[1]), "+f"(d[2]), "+f"(d[3]), "+f"(d[4]), "+f"(d[5]), "+f"(d[6]), "+f"(d[7]), "+f"(d[8]), "+f"(d[9]), "+f"(d[10]), "+f"(d[11]), "+f"(d[12]), "+f"(d[13]), "+f"(d[14]), "+f"(d[15]), "+f"(d[16]), "+f"(d[17]), "+f"(d[18]), "+f"(d[19]), "+f"(d[20]), "+f"(d[21]), "+f"(d[22]), "+f"(d[23]), "+f"(d[24]), "+f"(d[25]), "+f"(d[26]), "+f"(d[27]), "+f"(d[28]), "+f"(d[29]), "+f"(d[30]), "+f"(d[31])
    : "r"(a[0]), "r"(a[1]), "r"(a[2]), "r"(a[3]), "l"(desc), "r"(scale_d));
}
__device__ __forceinline__ void wgmma_rs_n72(float (&d)[36], const uint32_t* a, uint64_t desc, int scale_d) {
  asm volatile("{\n.reg .pred p;\nsetp.ne.b32 p, %41, 0;\n"
    "wgmma.mma_async.sync.aligned.m64n72k16.f32.bf16.bf16 "
    "{%0, %1, %2, %3, %4, %5, %6, %7, %8, %9, %10, %11, %12, %13, %14, %15, %16, %17, %18, %19, %20, %21, %22, %23, %24, %25, %26, %27, %28, %29, %30, %31, %32, %33, %34, %35}, "
    "{%36, %37, %38, %39}, %40, p, 1, 1, 1;\n}\n"
    : "+f"(d[0]), "+f"(d[1]), "+f"(d[2]), "+f"(d[3]), "+f"(d[4]), "+f"(d[5]), "+f"(d[6]), "+f"(d[7]), "+f"(d[8]), "+f"(d[9]), "+f"(d[10]), "+f"(d[11]), "+f"(d[12]), "+f"(d[13]), "+f"(d[14]), "+f"(d[15]), "+f"(d[16]), "+f"(d[17]), "+f"(d[18]), "+f"(d[19]), "+f"(d[20]), "+f"(d[21]), "+f"(d[22]), "+f"(d[23]), "+f"(d[24]), "+f"(d[25]), "+f"(d[26]), "+f"(d[27]), "+f"(d[28]), "+f"(d[29]), "+f"(d[30]), "+f"(d[31]), "+f"(d[32]), "+f"(d[33]), "+f"(d[34]), "+f"(d[35])
    : "r"(a[0]), "r"(a[1]), "r"(a[2]), "r"(a[3]), "l"(desc), "r"(scale_d));
}
__device__ __forceinline__ void wgmma_rs_n24(float (&d)[12], const uint32_t* a, uint64_t desc, int scale_d) {
  asm volatile("{\n.reg .pred p;\nsetp.ne.b32 p, %17, 0;\n"
    "wgmma.mma_async.sync.aligned.m64n24k16.f32.bf16.bf16 "
    "{%0, %1, %2, %3, %4, %5, %6, %7, %8, %9, %10, %11}, "
    "{%12, %13, %14, %15}, %16, p, 1, 1, 1;\n}\n"
    : "+f"(d[0]), "+f"(d[1]), "+f"(d[2]), "+f"(d[3]), "+f"(d[4]), "+f"(d[5]), "+f"(d[6]), "+f"(d[7]), "+f"(d[8]), "+f"(d[9]), "+f"(d[10]), "+f"(d[11])
    : "r"(a[0]), "r"(a[1]), "r"(a[2]), "r"(a[3]), "l"(desc), "r"(scale_d));
}

__device__ __forceinline__ void mbar_init(uint32_t a, uint32_t c) { asm volatile("mbarrier.init.shared::cta.b64 [%0], %1;" :: "r"(a), "r"(c)); }
__device__ __forceinline__ void mbar_arrive(uint32_t a) { asm volatile("mbarrier.arrive.shared::cta.b64 _, [%0];" :: "r"(a) : "memory"); }
__device__ __forceinline__ void mbar_wait_trap(uint32_t a, uint32_t ph) {
  asm volatile("{\n.reg .pred p;\n.reg .u32 n;\nmov.u32 n, 0;\n"
               "W: mbarrier.try_wait.parity.shared::cta.b64 p, [%0], %1;\n@p bra D;\n"
               "add.u32 n, n, 1;\nsetp.lt.u32 p, n, 4194304;\n@p bra W;\ntrap;\nD:\n}" :: "r"(a), "r"(ph) : "memory");
}
__device__ __forceinline__ void mbar_wait(uint32_t a, uint32_t ph) {
  asm volatile("{\n.reg .pred p;\nW: mbarrier.try_wait.parity.shared::cta.b64 p, [%0], %1;\n@!p bra W;\n}" :: "r"(a), "r"(ph) : "memory");
}
__device__ __forceinline__ void mbar_wait_sleep(uint32_t a, uint32_t ph) {
  asm volatile("{\n.reg .pred p;\nW: mbarrier.test_wait.parity.shared::cta.b64 p, [%0], %1;\n@p bra D;\nnanosleep.u32 500;\nbra W;\nD:\n}" :: "r"(a), "r"(ph) : "memory");
}
__device__ __forceinline__ void wg_fence() { asm volatile("wgmma.fence.sync.aligned;" ::: "memory"); }
__device__ __forceinline__ void wg_commit() { asm volatile("wgmma.commit_group.sync.aligned;" ::: "memory"); }
template <int N> __device__ __forceinline__ void wg_wait() { asm volatile("wgmma.wait_group.sync.aligned %0;" :: "n"(N) : "memory"); }
__device__ __forceinline__ float tanh_ap(float x) { float y; asm("tanh.approx.f32 %0, %1;" : "=f"(y) : "f"(x)); return y; }
__device__ __forceinline__ float ex2(float x) { float y; asm("ex2.approx.ftz.f32 %0, %1;" : "=f"(y) : "f"(x)); return y; }
__device__ __forceinline__ uint32_t pack_bf16(float lo, float hi) { uint32_t r; asm("cvt.rn.bf16x2.f32 %0, %1, %2;" : "=r"(r) : "f"(hi), "f"(lo)); return r; }
__device__ __forceinline__ float bf_lo(uint32_t v) { return __uint_as_float(v << 16); }
__device__ __forceinline__ float bf_hi(uint32_t v) { return __uint_as_float(v & 0xffff0000u); }
__device__ __forceinline__ uint32_t sub_bf16x2(uint32_t a, uint32_t b) { uint32_t r; asm("sub.rn.bf16x2 %0, %1, %2;" : "=r"(r) : "r"(a), "r"(b)); return r; }
__device__ __forceinline__ uint32_t mul_bf16x2(uint32_t a, uint32_t b) { uint32_t r; asm("mul.rn.bf16x2 %0, %1, %2;" : "=r"(r) : "r"(a), "r"(b)); return r; }
__device__ __forceinline__ uint32_t diff2(uint32_t a, uint32_t b, uint32_t t) { uint32_t r; asm("lop3.b32 %0, %1, %2, %3, 0x7e;" : "=r"(r) : "r"(a), "r"(b), "r"(t)); return r; }
__device__ __forceinline__ uint32_t or3(uint32_t a, uint32_t b, uint32_t c) { uint32_t r; asm("lop3.b32 %0, %1, %2, %3, 0xfe;" : "=r"(r) : "r"(a), "r"(b), "r"(c)); return r; }
__device__ __forceinline__ uint32_t umin2(uint32_t a, uint32_t b) { uint32_t r; asm("min.u32 %0, %1, %2;" : "=r"(r) : "r"(a), "r"(b)); return r; }
__device__ __forceinline__ uint32_t bitmask(uint32_t v, int bit) { uint32_t r; asm("bfe.s32 %0, %1, %2, 1;" : "=r"(r) : "r"(v), "r"(bit)); return r; }
__device__ __forceinline__ uint32_t nz(uint32_t w) { return w == 0u ? 0x8000u : w; }

__device__ __forceinline__ void ldg4(uint32_t* d, const uint4* p) {
  asm volatile("ld.relaxed.gpu.global.v4.b32 {%0,%1,%2,%3}, [%4];" : "=r"(d[0]), "=r"(d[1]), "=r"(d[2]), "=r"(d[3]) : "l"(p) : "memory");
}
__device__ __forceinline__ void ldg2(uint32_t* d, const void* p) {
  asm volatile("ld.relaxed.gpu.global.v2.b32 {%0,%1}, [%2];" : "=r"(d[0]), "=r"(d[1]) : "l"(p) : "memory");
}
__device__ __forceinline__ void stg4(uint4* p, uint32_t a, uint32_t b, uint32_t c, uint32_t d) {
  asm volatile("st.relaxed.gpu.global.v4.b32 [%0], {%1,%2,%3,%4};" :: "l"(p), "r"(a), "r"(b), "r"(c), "r"(d) : "memory");
}
__device__ __forceinline__ void stg2(void* p, uint32_t a, uint32_t b) {
  asm volatile("st.relaxed.gpu.global.v2.b32 [%0], {%1,%2};" :: "l"(p), "r"(a), "r"(b) : "memory");
}
__device__ __forceinline__ void sts4(uint32_t a, const uint32_t* o) { asm volatile("st.shared.v4.b32 [%0], {%1,%2,%3,%4};" :: "r"(a), "r"(o[0]), "r"(o[1]), "r"(o[2]), "r"(o[3]) : "memory"); }
__device__ __forceinline__ void lds4(uint32_t a, uint32_t* o) { asm volatile("ld.shared.v4.b32 {%0,%1,%2,%3}, [%4];" : "=r"(o[0]), "=r"(o[1]), "=r"(o[2]), "=r"(o[3]) : "r"(a) : "memory"); }
__device__ __forceinline__ void lds2(uint32_t a, uint32_t* o) { asm volatile("ld.shared.v2.b32 {%0,%1}, [%2];" : "=r"(o[0]), "=r"(o[1]) : "r"(a) : "memory"); }
__device__ __forceinline__ float rcp(float x) { float y; asm("rcp.approx.ftz.f32 %0, %1;" : "=f"(y) : "f"(x)); return y; }
__device__ __forceinline__ void sts1(uint32_t a, uint32_t v) { asm volatile("st.shared.b32 [%0], %1;" :: "r"(a), "r"(v) : "memory"); }
__device__ __forceinline__ void ldsm4(uint32_t a, uint32_t& r0, uint32_t& r1, uint32_t& r2, uint32_t& r3) {
  asm volatile("ldmatrix.sync.aligned.m8n8.x4.shared.b16 {%0,%1,%2,%3}, [%4];" : "=r"(r0), "=r"(r1), "=r"(r2), "=r"(r3) : "r"(a) : "memory");
}
__device__ __forceinline__ void ldsm4t(uint32_t a, uint32_t& r0, uint32_t& r1, uint32_t& r2, uint32_t& r3) {
  asm volatile("ldmatrix.sync.aligned.m8n8.x4.trans.shared.b16 {%0,%1,%2,%3}, [%4];" : "=r"(r0), "=r"(r1), "=r"(r2), "=r"(r3) : "r"(a) : "memory");
}
__device__ __forceinline__ void mma16(float* c, uint32_t a0, uint32_t a1, uint32_t a2, uint32_t a3, uint32_t b0, uint32_t b1) {
  asm("mma.sync.aligned.m16n8k16.row.col.f32.bf16.bf16.f32 {%0,%1,%2,%3}, {%4,%5,%6,%7}, {%8,%9}, {%0,%1,%2,%3};"
    : "+f"(c[0]), "+f"(c[1]), "+f"(c[2]), "+f"(c[3]) : "r"(a0), "r"(a1), "r"(a2), "r"(a3), "r"(b0), "r"(b1));
}
__device__ __forceinline__ void mma16c(float* d, const uint32_t* a, uint32_t b0, uint32_t b1, float c01) {
  asm("mma.sync.aligned.m16n8k16.row.col.f32.bf16.bf16.f32 {%0,%1,%2,%3}, {%4,%5,%6,%7}, {%8,%9}, {%10,%10,%10,%10};"
    : "=f"(d[0]), "=f"(d[1]), "=f"(d[2]), "=f"(d[3]) : "r"(a[0]), "r"(a[1]), "r"(a[2]), "r"(a[3]), "r"(b0), "r"(b1), "f"(c01));
}
__device__ __forceinline__ void mma8(float* c, uint32_t a0, uint32_t a1, uint32_t b0) {
  asm("mma.sync.aligned.m16n8k8.row.col.f32.bf16.bf16.f32 {%0,%1,%2,%3}, {%4,%5}, {%6}, {%0,%1,%2,%3};"
    : "+f"(c[0]), "+f"(c[1]), "+f"(c[2]), "+f"(c[3]) : "r"(a0), "r"(a1), "r"(b0));
}
__device__ __forceinline__ uint32_t lane_id() { uint32_t l; asm volatile("mov.u32 %0, %%laneid;" : "=r"(l)); return l; }
__device__ __forceinline__ float quad_sum(float v) { v += __shfl_xor_sync(~0u, v, 1); v += __shfl_xor_sync(~0u, v, 2); return v; }
__device__ __forceinline__ float quad_max(float v) { v = fmaxf(v, __shfl_xor_sync(~0u, v, 1)); v = fmaxf(v, __shfl_xor_sync(~0u, v, 2)); return v; }
template <int N> __device__ __forceinline__ void pin(float (&d)[N]) {
#pragma unroll
  for (int i = 0; i < N; i++) asm volatile("" : "+f"(d[i]) :: "memory");
}
#define SPIN_GUARD(n) if (++(n) > SPIN_MAX) break

template <int NG> __device__ __forceinline__ void publish_stats(uint4* dst, const float* y, uint32_t tag, uint32_t lane) {
  float s0 = 0.f, s1 = 0.f;
#pragma unroll
  for (int g = 0; g < NG; g++) { s0 += y[4 * g] + y[4 * g + 1]; s1 += y[4 * g + 2] + y[4 * g + 3]; }
  s0 = quad_sum(s0); s1 = quad_sum(s1);
  const float m0 = s0 * (1.f / (8 * NG)), m1 = s1 * (1.f / (8 * NG));
  float q0 = 0.f, q1 = 0.f, q2 = 0.f, q3 = 0.f;
#pragma unroll
  for (int g = 0; g < NG; g++) {
    const float a = y[4 * g] - m0, b = y[4 * g + 1] - m0, c = y[4 * g + 2] - m1, d = y[4 * g + 3] - m1;
    q0 = fmaf(a, a, q0); q1 = fmaf(b, b, q1); q2 = fmaf(c, c, q2); q3 = fmaf(d, d, q3);
  }
  q0 = quad_sum(q0 + q1); q2 = quad_sum(q2 + q3);
  if ((lane & 3) == 0)
    stg4(dst + (lane >> 2), (__float_as_uint(s0) & ~1u) | tag, __float_as_uint(q0), __float_as_uint(s1), __float_as_uint(q2));
}

__device__ __forceinline__ void put72(uint4* slab, uint32_t j, uint32_t lane, const uint32_t* v) {
#pragma unroll
  for (int i = 0; i < 4; i++) stg4(slab + (4 * j + i) * 32 + lane, nz(v[4 * i]), v[4 * i + 1], v[4 * i + 2], v[4 * i + 3]);
  stg2((char*)(slab + 1024 + j * 16) + lane * 8, nz(v[16]), v[17]);
}
__device__ __forceinline__ uint32_t row72(uint32_t k) { return k % 9 == 4 ? 32 + k / 9 : k - (k + 4) / 9; }
__device__ __forceinline__ void zero_share(uint4* slab, uint32_t j, uint32_t lane) {
  uint4* p = slab + j * 144 + lane;
#pragma unroll
  for (int i = 0; i < 4; i++) stg4(p + i * 32, 0u, 0u, 0u, 0u);
  if (lane < 16) stg4(p + 128, 0u, 0u, 0u, 0u);
}

struct Maps { CUtensorMap m[11]; };

struct Ring {
  uint32_t st, ph;
  __device__ __forceinline__ void next() { if (++st == NST) { st = 0; ph ^= 1; } }
};

#define GSTAMP(i) do {} while (0)
#define STAMP(i) do {} while (0)
#define ZSTAMP(m, i) do {} while (0)

__device__ __forceinline__ void tma_box(uint32_t dst, const CUtensorMap* m, int col, int row, uint32_t bar, uint32_t expect) {
  asm volatile("{\n.reg .pred e, h;\nelect.sync _|e, 0xffffffff;\nsetp.ne.and.u32 h, %5, 0, e;\n"
               "@h mbarrier.arrive.expect_tx.shared::cta.b64 _, [%2], %5;\n"
               "@e cp.async.bulk.tensor.2d.shared::cluster.global.mbarrier::complete_tx::bytes [%0], [%1, {%3, %4}], [%2];\n}"
               :: "r"(dst), "l"(m), "r"(bar), "r"(col), "r"(row), "r"(expect) : "memory");
}

__device__ __forceinline__ void bulk_load(uint32_t dst, const void* src, uint32_t bytes, uint32_t bar, bool arm) {
  asm volatile("{\n.reg .pred e, h;\nelect.sync _|e, 0xffffffff;\nsetp.ne.and.u32 h, %4, 0, e;\n"
               "@h mbarrier.arrive.expect_tx.shared::cta.b64 _, [%3], %2;\n"
               "@e cp.async.bulk.shared::cluster.global.mbarrier::complete_tx::bytes [%0], [%1], %2, [%3];\n}"
               :: "r"(dst), "l"(src), "r"(bytes), "r"(bar), "r"((uint32_t)arm) : "memory");
}

__global__ void __launch_bounds__(384, 1) mega_kernel(
    const __grid_constant__ Maps maps, uint4* __restrict__ scratch,
    __nv_bfloat16* __restrict__ out) {
  extern __shared__ __align__(1024) uint8_t smem[];
  const uint32_t sb = (uint32_t)__cvta_generic_to_shared(smem);
  const uint32_t full0 = sb + BARS, empty0 = full0 + 8 * NST, rem_full = empty0 + 8 * NST, park_free = rem_full + 8, kv_free = park_free + 8;
  const uint32_t c8_go = kv_free + 8, c8_done = c8_go + 8, c8_full = c8_done + 8, remo_full = c8_full + 8, piece_full = remo_full + 8, xb_done = piece_full + 8, res_full = xb_done + 8, pbar0 = res_full + 8;
  const uint32_t x_done = pbar0 + 64, x_ring = x_done + 8, xbar0 = x_ring + 8, redo_full = xbar0 + 72;
  const uint32_t w = __shfl_sync(~0u, threadIdx.x >> 5, 0);
  uint32_t pair = blockIdx.x >> 1;
  if (gridDim.x == 132) {
    uint32_t smid;
    asm("mov.u32 %0, %%smid;" : "=r"(smid));
    const uint32_t tpc = smid >> 1;
    if (tpc == 60 || tpc == 61) { if (threadIdx.x == 0) { __nanosleep(20000); } return; }
    pair = tpc < 32 ? tpc : tpc >= 62 ? (tpc - 58) * 8 : 33 + (tpc - 32) / 7 * 8 + (tpc - 32) % 7;
  }
  const uint32_t rank = blockIdx.x & 1, t = (pair & 7) * 2 + rank, j = pair >> 3;
  const uint32_t sd = sb & 0x3ffff;
  const uint32_t odd = j & 1;
  uint4* const scr = scratch + t * TILE;
  auto blk = [&](uint32_t kb) { return kb == 0 ? j : kb - (kb <= j); };
  const uint32_t xs = sb + (NST - 2) * STAGE;
  auto fetch_x = [&](uint32_t dst, uint32_t b, uint32_t bar) {
    asm volatile("{\n.reg .pred e;\nelect.sync _|e, 0xffffffff;\n@e mbarrier.arrive.expect_tx.shared::cta.b64 _, [%2], 16384;\n"
                 "@e cp.async.bulk.tensor.3d.shared::cluster.global.mbarrier::complete_tx::bytes [%0], [%1, {%3, %4, 0}], [%2];\n}"
                 :: "r"(dst), "l"(&maps.m[7]), "r"(bar), "r"(64 * b), "r"(64 * t) : "memory");
  };
  if (threadIdx.x == 256) {
    for (int i = 0; i < 9; i++) mbar_init(xbar0 + 8 * i, 1);
    mbar_init(piece_full, 1);
    asm volatile("fence.mbarrier_init.release.cluster;" ::: "memory");
  }
  if (threadIdx.x == 288) {
    for (int i = 0; i < NST; i++) { mbar_init(full0 + 8 * i, 1); mbar_init(empty0 + 8 * i, 16); }
    mbar_init(x_done, 8); mbar_init(x_ring, 16); mbar_init(redo_full, 1); mbar_init(redo_full + 8, 1);
    asm volatile("fence.mbarrier_init.release.cluster;" ::: "memory");
  }
  if (threadIdx.x == 320) {
    mbar_init(rem_full, 2); mbar_init(park_free, 8); mbar_init(kv_free, 8); mbar_init(c8_go, 8); mbar_init(c8_done, 2); mbar_init(c8_full, 1);
    mbar_init(remo_full, 64); mbar_init(xb_done, 8); mbar_init(res_full, 32);
    for (int i = 0; i < 8; i++) mbar_init(pbar0 + 8 * i, 4);
    asm volatile("fence.mbarrier_init.release.cluster;" ::: "memory");
  }
  if (threadIdx.x == 352) {
    asm volatile("prefetch.tensormap [%0];" :: "l"(&maps.m[7]) : "memory");
    asm volatile("prefetch.tensormap [%0];" :: "l"(&maps.m[0]) : "memory");
  }
  __syncwarp();
  asm volatile("barrier.cluster.arrive.relaxed.aligned;" ::: "memory");
  if (w != 8) asm volatile("barrier.cluster.wait.aligned;" ::: "memory");

  if (w >= 8) {
    asm volatile("setmaxnreg.dec.sync.aligned.u32 24;");
    if (w == 8) {
#pragma unroll 1
      for (uint32_t b = 0; b < 9; b++) fetch_x(xs + b * STAGE, b, xbar0 + 8 * b);
      tma_box(sb + PIECE, &maps.m[t >= 12 ? 6 : 5], 72 * j + (odd ? 0 : 64) + (t < 8 ? 576 * ((t >> 2) + 1) : 0), 144 * (t & 3), piece_full, 2304);
      asm volatile("barrier.cluster.wait.aligned;" ::: "memory");
      uint32_t dst = sb, bar = full0, ph = 1;
#pragma unroll 1
      for (int seg = 0; seg < 34; seg++) {
        const int n = seg >= 17 ? seg - 17 : seg;
        int ma, mb, ca, cb;
        if (n < 3) { ma = mb = n == 2; ca = 72 * j + 8 * odd + (n == 0 ? 576 : 0); cb = ca + 576; }
        else if (n < 12) { ma = 3; mb = 2; ca = cb = 576 * j + 64 * (n - 3); }
        else { ma = mb = 4; ca = n == 12 ? 512 : ((j + 2 * n) & 7) * 64; cb = ((j + 2 * n + 1) & 7) * 64; }
        const bool zip = n == 0 || n == 3, solo = n == 1 || n == 2 || n == 16;
#pragma unroll 1
        for (uint32_t st = 0; st < (solo ? 5 : 9); st++) {
          if (seg == 0 && st == NST - 2) mbar_wait(x_ring, 0);
          const uint32_t b = 2 * st + rank, kb = zip ? st : b >= 9 ? b - 9 : b;
          const bool second = zip ? rank : b >= 9, shared = kb == 8 && n >= 2 && n < 12;
          const uint32_t ks = n >= 12 ? 36 * j + 4 * kb : n < 2 ? 4 * blk(kb) : shared ? 0 : (9 * blk(kb) + 1) >> 1;
          asm volatile("{\n.reg .pred p, e, f;\n.reg .u32 n;\nelect.sync _|e, 0xffffffff;\nsetp.ne.and.u32 f, %8, 0, e;\nmov.u32 n, 0;\n"
                       "W: mbarrier.try_wait.parity.shared::cta.b64 p, [%1+48], %2;\n@p bra D;\n"
                       "add.u32 n, n, 1;\nsetp.lt.u32 p, n, 4194304;\n@p bra W;\ntrap;\n"
                       "D: @e mbarrier.arrive.expect_tx.shared::cta.b64 _, [%1], %7;\n"
                       "@f cp.async.bulk.tensor.3d.shared::cluster.global.mbarrier::complete_tx::bytes.multicast::cluster [%0], [%3, {%4, %5, %6}], [%1], 3;\n}"
                       :: "r"(dst + rank * 8192), "r"(bar), "r"(ph), "l"(&maps.m[(second ? mb : ma) + (shared ? 7 : 0)]), "r"(second ? cb : ca),
                          "r"(shared ? 64 : 0), "r"(ks), "r"(solo && st == 4 ? STAGE / 2 : STAGE), "r"((uint32_t)!(solo && b == 9)) : "memory");
          dst += STAGE; bar += 8;
          if (bar == full0 + 8 * NST) { dst = sb; bar = full0; ph ^= 1; }
        }
      }
      {
#pragma unroll 1
        for (int i = 0; i < NST; i++) {
          mbar_wait_trap(bar + 48, ph);
          bar += 8;
          if (bar == full0 + 8 * NST) { bar = full0; ph ^= 1; }
        }
      }
    } else if (w == 9) {
      const uint32_t lane = lane_id();
      const uint32_t stg = sb + HSTG + lane * 16;
      uint32_t fph = 0;
#pragma unroll 1
      for (uint32_t layer = 0; layer < 2; layer++) {
        uint4* xb = scr + OFF_X + ((4 + layer) * 8 + j) * SLAB + 28 * 32;
        mbar_wait_sleep(c8_go, layer);
        int n = 0;
#pragma unroll 1
        while (true) {
          if (lane == 0) asm volatile("mbarrier.arrive.expect_tx.shared::cta.b64 _, [%0], 18432;" :: "r"(c8_full) : "memory");
          __syncwarp();
#pragma unroll 1
          for (uint32_t s = 0; s < 9; s++)
            bulk_load(sb + HSTG + s * 2048, s < 8 ? scr + OFF_P + (j + s * 8) * SLAB + 32 * 32 : xb, 2048, c8_full, false);
          mbar_wait(c8_full, fph); fph ^= 1;
          uint32_t bad = 0;
#pragma unroll 8
          for (int s = 0; s < 32; s++) { uint32_t v; asm volatile("ld.shared.b32 %0, [%1];" : "=r"(v) : "r"(stg + s * 512) : "memory"); bad |= v ^ (1 - layer); }
          if (__all_sync(~0u, (bad & 1u) == 0u)) break;
          __nanosleep(300);
          SPIN_GUARD(n);
        }
        asm volatile("bar.arrive 7, 96;" ::: "memory");
        float s0 = 0.f, s1 = 0.f;
#pragma unroll 1
        for (int g = 0; g < 8; g++) {
          const uint32_t a = stg + (g >> 1) * 512 + (g & 1) * 8;
          float a0 = 0.f, a1 = 0.f, a2 = 0.f, a3 = 0.f;
#pragma unroll 1
          for (int b = 0; b < 3; b++) {
            uint32_t v[6];
#pragma unroll
            for (int s = 0; s < 3; s++) lds2(a + (3 * b + s) * 2048, v + 2 * s);
#pragma unroll
            for (int s = 0; s < 3; s++) { a0 += bf_lo(v[2 * s]); a1 += bf_hi(v[2 * s]); a2 += bf_lo(v[2 * s + 1]); a3 += bf_hi(v[2 * s + 1]); }
          }
          sts1(a + 18432, pack_bf16(a0, a1)); sts1(a + 18436, pack_bf16(a2, a3));
          s0 += a0 + a1; s1 += a2 + a3;
        }
        __syncwarp();
        if (lane == 0) mbar_arrive(c8_done);
        s0 = quad_sum(s0); s1 = quad_sum(s1);
        float q0 = 0.f, q1 = 0.f;
        const uint32_t ln = lane_id();
#pragma unroll 1
        for (uint32_t i = 0; i < 4; i++) {
          uint32_t x[4];
          lds4(stg + 18432 + i * 512, x);
          uint4* z = xb + i * 32 + ln;
          asm volatile("" : "+l"(z));
          stg4(z, 0u, 0u, 0u, 0u);
          if (layer == 0) {
            stg4(z - (3 * 8 * SLAB - 128), nz(x[0]), x[1], nz(x[2]), x[3]);
#pragma unroll
            for (int e = 0; e < 4; e++) {
              const float m = (e & 1) ? s1 : s0, c = fmaf(m, -1.f / 64, bf_lo(x[e])), d = fmaf(m, -1.f / 64, bf_hi(x[e]));
              if (e & 1) q1 = fmaf(c, c, fmaf(d, d, q1)); else q0 = fmaf(c, c, fmaf(d, d, q0));
            }
          } else {
            uint32_t* o = (uint32_t*)(out + (128 * t + 32 * (j >> 1) + 2 * (ln >> 2) + (j & 1)) * 576 + 512 + 16 * i + 2 * (ln & 3));
            o[0] = x[0]; o[8 * 576] = x[1]; o[4] = x[2]; o[8 * 576 + 4] = x[3];
          }
        }
        if (layer == 0) {
          q0 = quad_sum(q0); q1 = quad_sum(q1);
          if ((ln & 3) == 0) stg4(scr + OFF_S + j * 96 + 64 + (ln >> 2), __float_as_uint(s0) | 1u, __float_as_uint(q0), __float_as_uint(s1), __float_as_uint(q1));
        }
      }
    } else {
      auto mark = [&](uint32_t k0, uint32_t v) {
        const uint32_t lane = lane_id();
#pragma unroll 1
        for (uint32_t k = k0; k < 6; k++) stg4(scr + OFF_S + (k * 4 + (lane >> 3)) * 96 + j * 8 + (lane & 7), k < 2 ? 0u : v, 0u, 0u, 0u);
      };
      if (w == 11) mark(2, 0u);
      auto phase2_duties = [&](uint32_t layer) {
        const uint32_t lane = lane_id();
        asm volatile("bar.sync 7, 96;" ::: "memory");
        if (w == 11) {
          if (layer == 0) mark(0, 1u);
          __syncwarp();
          if (lane == 0) mbar_arrive(c8_done);
        }
#pragma unroll 1
        for (uint32_t i = 0; i < 16; i++) {
          const uint32_t sl = (w - 10) * 4 + (i >> 2);
          bulk_load(sb + PARK + sl * 2048 + (i & 3) * 512, scr + OFF_X + ((4 + layer) * 8 + sl) * SLAB + row72(4 * j + (i & 3)) * 32, 512, res_full, true);
        }
        mbar_wait_sleep(res_full, layer);
#pragma unroll 1
        for (uint32_t i = 0; i < 16; i++) {
          stg4(scr + OFF_X + ((4 + layer) * 8 + (w - 10) * 4 + (i >> 2)) * SLAB + row72(4 * j + (i & 3)) * 32 + lane, 0u, 0u, 0u, 0u);
          if ((i & 3) == 3) __nanosleep(200);
        }
      };
      if (w == 10) {
        const uint32_t lane = lane_id();
        uint32_t* fl = (uint32_t*)(scratch + OFF_F + (t * 8 + j) * 8) + (lane & 15);
        uint32_t v;
        asm volatile("ld.relaxed.gpu.global.b32 %0, [%1];" : "=r"(v) : "l"(fl) : "memory");
        mbar_wait(piece_full, 0);
        asm volatile("{\n.reg .pred e;\nelect.sync _|e, 0xffffffff;\n@e cp.async.bulk.global.shared::cta.bulk_group [%0], [%1], 2304;\n}\n"
                     "cp.async.bulk.commit_group;\ncp.async.bulk.wait_group 0;\nfence.proxy.async;"
                     :: "l"(scratch + OFF_R + j * 2304 + t * 144), "r"(sb + PIECE) : "memory");
        __syncwarp();
        if (lane < 16) asm volatile("st.release.gpu.global.b32 [%0], 1;" :: "l"((uint32_t*)(scratch + OFF_F + (lane_id() * 8 + j) * 8) + t) : "memory");
        int n = 0;
#pragma unroll 1
        while (!__all_sync(~0u, v != 0u)) {
          __nanosleep(100);
          SPIN_GUARD(n);
          asm volatile("ld.relaxed.gpu.global.b32 %0, [%1];" : "=r"(v) : "l"(fl) : "memory");
        }
        asm volatile("st.relaxed.gpu.global.b32 [%0], 0;" :: "l"(fl) : "memory");
        mbar_wait(x_done, 0);
      }
#pragma unroll 1
      for (uint32_t layer = 0; layer < 3; layer++) {
        if (w == 10 && layer < 2) {
          if (layer) mbar_wait_sleep(park_free, 0);
          const uint4* img = scratch + OFF_R + j * 2304;
          if (lane_id() == 0) asm volatile("mbarrier.arrive.expect_tx.shared::cta.b64 _, [%0], 27648;\nmbarrier.arrive.expect_tx.shared::cta.b64 _, [%1], 9216;"
                                           :: "r"(rem_full), "r"(piece_full) : "memory");
          __syncwarp();
#pragma unroll 1
          for (uint32_t p = 0; p < 3; p++) {
            bulk_load(sb + REM + p * 9216, img + p * 576 + j * 64, 1024, rem_full, false);
            if (j) bulk_load(sb + REM + p * 9216 + 1024, img + p * 576, j * 1024, rem_full, false);
            bulk_load(sb + REM + p * 9216 + (j + 1) * 1024, img + p * 576 + (j + 1) * 64, (8 - j) * 1024, rem_full, false);
          }
#pragma unroll 1
          for (uint32_t i = 0; i < 12; i++)
            bulk_load(sb + REM + 27648 + (i < 8 ? i * 1024 : 6144 + i * 256), img + 1728 + (i < 8 ? (9 * blk(i) + 1) >> 1 : 9 * i - 68) * 16,
                      i < 8 ? 1024 : 256, piece_full, false);
          if (layer == 0) { fetch_x(sb + PARK, j, xbar0); fetch_x(sb + PARK + STAGE, j + 1, xbar0 + 8); }
        }
        if (w == 11 && layer < 2) {
          if (layer) mbar_wait_sleep(park_free, 0);
          __syncwarp();
          if (lane_id() == 0) mbar_arrive(rem_full);
        }
        if (layer) phase2_duties(layer - 1);
        if (layer == 2) break;
        mbar_wait_sleep(layer ? kv_free : x_done, 0);
        if (t > 0) {
          const uint32_t lane = lane_id(), r = lane >> 2, q = lane & 3;
#pragma unroll 1
          for (uint32_t pc = 0; pc < 3; pc++) {
            uint4* hp = scr + OFF_H + ((layer * 8 + j) * 2 + (w - 10)) * 192 + pc * 64 + lane;
            uint32_t hl[8];
            int n = 0;
            hl[4] = 1u;
#pragma unroll 1
            while (true) {
              ldg4(hl, hp);
              if (pc < 2) ldg4(hl + 4, hp + 32);
              if (__all_sync(~0u, hl[0] != 0u && hl[4] != 0u)) break;
              __nanosleep(100);
              SPIN_GUARD(n);
            }
            const uint32_t dst = sb + KVS + (w - 10) * 10368 + r * 144 + q * 4;
            if (pc < 2) {
#pragma unroll
              for (int g = 0; g < 8; g++) sts1(dst + pc * 20736 + odd * 16 + g * 16, hl[g]);
              stg4(hp + 32, 0u, 0u, 0u, 0u);
            } else {
              sts1(dst + (odd ? 0 : 128), hl[0]); sts1(dst + 20736 + (odd ? 0 : 128), hl[1]);
            }
            stg4(hp, 0u, 0u, 0u, 0u);
          }
        }
        asm volatile("bar.arrive 1, 192;" ::: "memory");
        mbar_wait(rem_full, layer);
        mbar_wait(piece_full, 1 - layer);
#pragma unroll 1
        for (uint32_t b = 0; b < 5; b++) {
          const uint32_t blk = sb + REM + 27648 + b * 2048, k = (w - 10) * 32 + lane_id(), rr = k & 7;
          const uint32_t dst = blk + ((k >> 3) & 1) * 1024 + rr * 128 + (((k >> 4) ^ rr) << 4);
          uint32_t v[8];
          lds4(blk + k * 16, v); lds4(blk + 1024 + k * 16, v + 4);
          asm volatile("bar.sync 3, 64;" ::: "memory");
          sts4(dst, v); sts4(dst ^ 64, v + 4);
        }
        asm volatile("fence.proxy.async.shared::cta;" ::: "memory");
        mbar_arrive(remo_full);
        mbar_wait_sleep(xb_done, layer);
        if (w == 10 && layer == 1) {
          const uint32_t lane = lane_id();
          stg4(scr + OFF_S + (lane >> 3) * 96 + j * 8 + (lane & 7), 0u, 0u, 0u, 0u);
          stg4(scr + OFF_S + (4 + (lane >> 3)) * 96 + j * 8 + (lane & 7), 0u, 0u, 0u, 0u);
          if (lane < 8) stg4(scr + OFF_S + j * 96 + 64 + lane, 0u, 0u, 0u, 0u);
        }
#pragma unroll 1
        for (uint32_t i = 0; i < 8 && (w == 11 || layer == 1); i++) {
          zero_share(scr + OFF_X + ((w - 10) * 16 + layer * 8 + i) * SLAB, j, lane_id());
          __nanosleep(500);
        }
      }
    }
  } else {
    asm volatile("setmaxnreg.inc.sync.aligned.u32 240;");
    const bool lead = lane_id() == 0;
    Ring rg{0, 0};
    uint32_t prev = 0;
    uint32_t X[144];
    float rs0, rs1;
    const bool lead2 = lane_id() < 2;
    uint32_t empty_at;
    asm volatile("mapa.shared::cluster.u32 %0, %1, %2;" : "=r"(empty_at) : "r"(empty0), "r"(lane_id() & 1));
    auto release = [&](uint32_t st) { if (lead2) asm volatile("mbarrier.arrive.shared::cluster.b64 _, [%0];" :: "r"(empty_at + st * 8) : "memory"); };
    auto load_kb = [&](int kb, const uint4* src, const char* lo, uint32_t hoff) {
      const uint4* p;
      asm("{\n.reg .pred p;\n.reg .u64 t;\nsetp.ge.u32 p, %2, %3;\nadd.u64 t, %1, -2048;\nselp.b64 %0, t, %1, p;\n}" : "=l"(p) : "l"(src), "r"(j), "r"(kb));
#pragma unroll
      for (int i = 0; i < 4; i++) {
        if (kb == 8) { ldg2(X + 128 + 4 * i, lo + (32 + i) * 512); ldg2(X + 130 + 4 * i, lo + hoff + (32 + i) * 512); }
        else ldg4(X + 16 * kb + 4 * i, p + kb * 128 + i * 32);
      }
    };
    auto check_kb = [&](bool skip, int kb, const uint4* src, const char* lo, uint32_t hoff) {
      int n = 0;
#pragma unroll 1
      while (true) {
        uint32_t m = umin2(umin2(X[16 * kb], X[16 * kb + 4]), umin2(X[16 * kb + 8], X[16 * kb + 12]));
        if (kb == 8) m = umin2(m, umin2(umin2(X[130], X[134]), umin2(X[138], X[142])));
        if (__all_sync(~0u, m != 0u || skip)) break;
        SPIN_GUARD(n);
        load_kb(kb, src, lo, hoff);
      }
    };
#pragma unroll
    for (int i = 0; i < 16; i++) X[i] = 0u;
#pragma unroll 1
    for (uint32_t hf = 0; hf < 4; hf++) {
      const uint32_t layer = hf >> 1;
      const bool ffn = hf & 1;
      const uint32_t tag = 1 - layer;
      uint4* const xbase = scr + OFF_X + (layer * 8 + w) * SLAB;
      float aA[32], aB[32];
      {
        const uint32_t lane = lane_id(), r = lane >> 2, q = lane & 3;
        const uint4* src = xbase + (ffn ? 32 * SLAB : 0) + lane;
        const char* lo = (const char*)src - (ffn ? lane * 8 : 0);
        const uint32_t hoff = ffn ? 256 : 8;
        const uint32_t xoff = (w & 1) * 8192 + (16 * (w >> 1) + (lane & 15)) * 128 + (((lane >> 4) ^ (lane & 7)) << 4);
        auto load_x = [&](uint32_t b, uint32_t* d) {
#pragma unroll
          for (int i = 0; i < 4; i++) ldsm4(xs + b * STAGE + (xoff ^ (32 * i)), d[4 * i], d[4 * i + 1], d[4 * i + 2], d[4 * i + 3]);
        };
        auto load_any = [&](int kb) { if (hf == 0) load_x(blk(kb), X + 16 * kb); else load_kb(kb, src, lo, hoff); };
        float m0, m1, v0, v1;
        STAMP(ffn * 16 + 0);
        if (hf == 0) {
          float sum[2][4] = {}, sq0[4][4] = {}, sq1[4][4] = {};
          uint32_t p0, p1;
          mbar_wait(xbar0, 0);
          ldsm4(xs + xoff, p0, p1, X[0], X[1]);
          p0 = __byte_perm(__shfl_sync(~0u, p0, lane & 28), 0, 0x1010); p1 = __byte_perm(__shfl_sync(~0u, p1, lane & 28), 0, 0x1010);
#pragma unroll 3
          for (uint32_t b = 0; b < 9; b++) {
            uint32_t d[16];
            mbar_wait(xbar0 + 8 * b, 0);
            load_x(b, d);
#pragma unroll
            for (int i = 0; i < 16; i++) d[i] = sub_bf16x2(d[i], (i & 1) ? p1 : p0);
#pragma unroll
            for (int g = 0; g < 8; g++) {
              if (!(g & 1)) mma16(sum[(g >> 1) & 1], d[2 * g], d[2 * g + 1], d[2 * g + 2], d[2 * g + 3], 0x3f803f80u, 0x3f803f80u);
              mma8(sq0[g & 3], d[2 * g], d[2 * g + 1], d[2 * g]); mma8(sq1[g & 3], d[2 * g], d[2 * g + 1], d[2 * g + 1]);
            }
          }
          STAMP(1);
          GSTAMP(14);
#pragma unroll
          for (int kb = 0; kb < GD; kb++) load_x(blk(kb), X + 16 * kb);
          release((x_ring - empty0) / 8);
          auto tot = [](float (&c)[4][4], int e) { return (c[0][e] + c[1][e]) + (c[2][e] + c[3][e]); };
          const float a0 = (sum[0][0] + sum[1][0]) * (1.f / 576), a1 = (sum[0][2] + sum[1][2]) * (1.f / 576);
          const uint32_t dg = (lane & 28) + (r >> 1);
          v0 = fmaxf(fmaf(__shfl_sync(~0u, (r & 1) ? tot(sq0, 1) : tot(sq0, 0), dg), 1.f / 576, -a0 * a0), 0.f);
          v1 = fmaxf(fmaf(__shfl_sync(~0u, (r & 1) ? tot(sq1, 3) : tot(sq1, 2), dg), 1.f / 576, -a1 * a1), 0.f);
          m0 = bf_lo(p0) + a0; m1 = bf_lo(p1) + a1;
        } else {
          uint32_t s[3][4];
          const uint4* p = scr + OFF_S + ((ffn ? 16 : 0) + w) * 96 + q * 8 + r;
          const bool third = !ffn && q == 0;
          const uint32_t rdy = ffn ? tag : 1u;
          int n = 0;
          s[2][0] = rdy; s[2][1] = s[2][2] = s[2][3] = 0u;
#pragma unroll 1
          while (true) {
            ldg4(s[0], p); ldg4(s[1], p + 32);
            if (third) ldg4(s[2], p + 64);
            if (__all_sync(~0u, ((diff2(s[0][0], s[1][0], rdy) | diff2(s[1][0], s[2][0], rdy)) & 1u) == 0u)) break;
            SPIN_GUARD(n);
          }
          STAMP(ffn * 16 + 1);
          ZSTAMP(1 + ffn, 0);
          GSTAMP(14 + ffn);
#pragma unroll
          for (int kb = 1; kb < GD; kb++) load_kb(kb, src, lo, hoff);
          float t0 = 0.f, t1 = 0.f;
#pragma unroll
          for (int i = 0; i < 3; i++) { t0 += __uint_as_float(s[i][0]); t1 += __uint_as_float(s[i][2]); }
          m0 = quad_sum(t0) * (1.f / 576); m1 = quad_sum(t1) * (1.f / 576);
          const float cnt = ffn ? 72.f : 64.f, inv = ffn ? 1.f / 72 : 1.f / 64;
          v0 = 0.f; v1 = 0.f;
#pragma unroll
          for (int i = 0; i < 3; i++) {
            const float c = (i < 2 || third) ? cnt : 0.f;
            const float d0 = fmaf(__uint_as_float(s[i][0]), inv, -m0), d1 = fmaf(__uint_as_float(s[i][2]), inv, -m1);
            v0 += fmaf(d0 * d0, c, __uint_as_float(s[i][1])); v1 += fmaf(d1 * d1, c, __uint_as_float(s[i][3]));
          }
          v0 = quad_sum(v0) * (1.f / 576); v1 = quad_sum(v1) * (1.f / 576);
        }
        rs0 = rsqrtf(v0 + 1e-5f); rs1 = rsqrtf(v1 + 1e-5f);
        const uint32_t mean0 = pack_bf16(m0, m0), mean1 = pack_bf16(m1, m1);
#pragma unroll
        for (int kb = 0; kb < 9; kb++) {
          if (kb > 0) check_kb(hf == 0, kb, src, lo, hoff);
          if (kb + GD < 9) load_any(kb + GD);
          if (kb + GD == 8 && hf == 0 && lead) mbar_arrive(x_done);
#pragma unroll
          for (int i = 16 * kb; i < 16 * kb + 16; i++) X[i] = sub_bf16x2(X[i], (i & 1) ? mean1 : mean0);
          ZSTAMP(1 + ffn, 1 + 3 * kb);
          mbar_wait(full0 + rg.st * 8, rg.ph);
          ZSTAMP(1 + ffn, 2 + 3 * kb);
          const uint64_t desc = DESC_HI | ((sd + rg.st * STAGE) >> 4);
          wg_fence();
#pragma unroll
          for (int i = 0; i < 4; i++) wgmma_rs_n64(aA, X + 4 * (4 * kb + i), desc + i * 128, kb + i != 0);
          if (kb == 8) { wg_commit(); wg_wait<1>(); wg_fence(); }
#pragma unroll
          for (int i = 0; i < 4; i++) wgmma_rs_n64(aB, X + 4 * (4 * kb + i), desc + 512 + i * 128, kb + i != 0);
          wg_commit();
          wg_wait<1>();
          ZSTAMP(1 + ffn, 3 + 3 * kb);
          if (kb > 0) release(prev);
          prev = rg.st; rg.next();
        }
        ZSTAMP(1 + ffn, 28);
        ZSTAMP(4, 0);
        STAMP(ffn * 16 + 2);
      }
      if (!ffn) {
      const uint32_t lane = lane_id(), r = lane >> 2, q = lane & 3;
      const uint32_t kvrow = sb + KVS + (w & 1) * 10368 + (16 * (w >> 1)) * 144;
      uint32_t Q[18], Km[3][8], Ke[3][4];
      const bool edge = (t == 0 && w < 2);
      const uint32_t row0 = edge ? sb + KVS + 8 * 144 : kvrow + (lane & 7) * 144, row1 = kvrow + (8 + (lane & 7)) * 144;
      {
        const uint32_t dst = kvrow + (8 + r) * 144 + q * 4 + odd * 16, dstr = dst + (odd ? -16 : 128);
        const bool edge_out = w >= 6 && t < 15;
        uint4* const hp = scr + TILE + OFF_H + ((layer * 8 + j) * 2 + (w & 1)) * 192 + lane;
        auto put_kv = [&](float (&a)[32], int part, int half) {
          uint32_t hl[4];
#pragma unroll
          for (int i = 0; i < 16; i++) asm volatile("" : "+f"(a[16 * half + i]) :: "memory");
#pragma unroll
          for (int i = 0; i < 4; i++) {
            const int g = 4 * half + i;
            hl[i] = pack_bf16(a[4 * g + 2] * rs1, a[4 * g + 3] * rs1);
            sts1(dst + part * 20736 + g * 16, pack_bf16(a[4 * g] * rs0, a[4 * g + 1] * rs0)); sts1(dst + part * 20736 + 8 * 144 + g * 16, hl[i]);
          }
          if (edge_out) stg4(hp + part * 64 + half * 32, nz(hl[0]), hl[1], hl[2], hl[3]);
        };
        put_kv(aA, 0, 0); put_kv(aA, 0, 1);
        wg_wait<0>();
        release(prev);
        float aR[12];
        mbar_wait(rem_full, layer);
        const uint64_t dr = DESC_REM | ((sd + REM) >> 4);
        wg_fence();
#pragma unroll
        for (int s = 0; s < 36; s++) {
          wgmma_rs_n24(aR, X + 4 * s, dr + s * 16, s != 0);
          if (s == 4) put_kv(aB, 1, 0);
          if (s == 16) put_kv(aB, 1, 1);
        }
        wg_commit();
#pragma unroll
        for (int kb = 0; kb < 9; kb++) {
          if (!(kb & 1)) mbar_wait(full0 + rg.st * 8, rg.ph);
          const uint64_t desc = DESC_HI | ((sd + rg.st * STAGE + (kb & 1) * 8192) >> 4);
          wg_fence();
#pragma unroll
          for (int i = 0; i < 4; i++) wgmma_rs_n64(aB, X + 4 * (4 * kb + i), desc + i * 128, kb + i != 0);
          wg_commit();
          wg_wait<1>();
          if (kb > 0 && !(kb & 1)) release(prev);
          if ((kb & 1) || kb == 8) { prev = rg.st; rg.next(); }
          if (kb == 0) {
            pin(aR);
            const uint32_t k1 = pack_bf16(aR[2] * rs1, aR[3] * rs1), v1 = pack_bf16(aR[6] * rs1, aR[7] * rs1);
            if (edge_out) stg4(hp + 128, nz(k1), v1, 0u, 0u);
            sts1(dstr, pack_bf16(aR[0] * rs0, aR[1] * rs0)); sts1(dstr + 8 * 144, k1);
            sts1(dstr + 20736, pack_bf16(aR[4] * rs0, aR[5] * rs0)); sts1(dstr + 20736 + 8 * 144, v1);
            Q[16] = pack_bf16(aR[8], aR[9]); Q[17] = pack_bf16(aR[10], aR[11]);
            if (w < 4) asm volatile("bar.arrive 2, 256;" ::: "memory");
          }
          if (kb == 8) {
            if (w < 4) asm volatile("bar.sync 1, 192;" ::: "memory");
            else asm volatile("bar.sync 2, 256;" ::: "memory");
#pragma unroll
            for (int nt = 0; nt < 3; nt++) {
              const uint32_t ra = (nt == 0 ? row0 : row1 + (nt - 1) * 8 * 144);
              ldsm4(ra + odd * 16 + (lane >> 3) * 16, Km[nt][0], Km[nt][1], Km[nt][2], Km[nt][3]);
              ldsm4(ra + odd * 16 + 64 + (lane >> 3) * 16, Km[nt][4], Km[nt][5], Km[nt][6], Km[nt][7]);
              ldsm4(ra + (odd ? 0 : 32) + (lane >> 3) * 32, Ke[nt][0], Ke[nt][1], Ke[nt][2], Ke[nt][3]);
            }
            const uint32_t ge = (2u << q) - 1, le = 0xfu << q, on = edge ? 0u : ~0u;
            const uint32_t bits = odd ? 0xfu | ((le & 0xfu) << 4) | (ge << 8) : ge | 0xf0u | (le << 8);
#pragma unroll
            for (int h = 0; h < 4; h++) {
              const uint32_t ma = bitmask(bits, h), mb = bitmask(bits, 4 + h), mc = bitmask(bits, 8 + h);
              Km[0][2 * h] &= ma & on; Km[0][2 * h + 1] &= mb & on; Ke[0][h] &= mc & on;
#pragma unroll
              for (int nt = 1; nt < 3; nt++) { Km[nt][2 * h] &= ma; Km[nt][2 * h + 1] &= mb; Ke[nt][h] &= mc; }
            }
          }
        }
        wg_wait<0>();
        release(prev);
        pin(aB);
        if (w < 4) asm volatile("bar.sync 4, 256;" ::: "memory");
        STAMP(3);
#pragma unroll
        for (int i = 0; i < 16; i++) Q[i] = pack_bf16(aB[2 * i], aB[2 * i + 1]);
      }
      uint32_t res[18] = {};
      if (layer) {
        const uint4* p = xbase + ((9 * j + 1) >> 1) * 32 + lane;
#pragma unroll
        for (int i = 0; i < 4; i++) ldg4(res + 4 * i, p + i * 32);
        ldg2(res + 16, odd ? (const char*)(p - 32) + 8 : (const char*)(p + 4 * 32));
      }
      {
        uint32_t V01[12][2], V2[12];
        const uint32_t rv = ((lane & 8) ? row1 : row0) + 20736, rw = row1 + 8 * 144 + 20736;
#pragma unroll
        for (int i = 0; i < 4; i++) ldsm4t(rv + odd * 16 + i * 32 + (lane >> 4) * 16, V01[2 * i][0], V01[2 * i][1], V01[2 * i + 1][0], V01[2 * i + 1][1]);
#pragma unroll
        for (int i = 0; i < 2; i++) ldsm4t(rv + (odd ? 0 : 32) + i * 64 + (lane >> 4) * 32, V01[8 + 2 * i][0], V01[8 + 2 * i][1], V01[9 + 2 * i][0], V01[9 + 2 * i][1]);
        ldsm4t(rw + odd * 16 + (lane >> 3) * 16, V2[0], V2[1], V2[2], V2[3]);
        ldsm4t(rw + odd * 16 + 64 + (lane >> 3) * 16, V2[4], V2[5], V2[6], V2[7]);
        ldsm4t(rw + (odd ? 0 : 32) + (lane >> 3) * 32, V2[8], V2[9], V2[10], V2[11]);
        const bool up0 = 2 * q > r, up1 = 2 * q + 1 > r;
        const uint32_t upm = (up0 ? 0xffffu : 0u) | (up1 ? 0xffff0000u : 0u);
        const float c0 = 0.23570226039551584f * 1.4426950408889634f * rs0, c1 = 0.23570226039551584f * 1.4426950408889634f * rs1;
        const float masked = edge ? -1e9f * 1.4426950408889634f * rcp(c0) : 0.f;
        uint32_t Om[16], Oe[8];
        uint4* const po = xbase + 16 * SLAB + 4 * j * 32 + lane;
#pragma unroll
        for (int h = 0; h < 4; h++) {
          const uint32_t e0 = odd ? Q[(4 * h + 16) % 18] : Q[4 * h + 4], e1 = odd ? Q[(4 * h + 17) % 18] : Q[4 * h + 5];
          float S[3][4];
#pragma unroll
          for (int nt = 0; nt < 3; nt++) {
            mma16c(S[nt], Q + 4 * h, Km[nt][2 * h], Km[nt][2 * h + 1], nt == 0 ? masked : 0.f);
            mma8(S[nt], e0, e1, Ke[nt][h]);
          }
          const float s00 = up0 ? S[0][0] : S[1][0], s01 = up1 ? S[0][1] : S[1][1];
          const float s10 = up0 ? S[1][2] : S[2][2], s11 = up1 ? S[1][3] : S[2][3];
          const float m0 = quad_max(fmaxf(s00, s01)) * c0, m1 = quad_max(fmaxf(s10, s11)) * c1;
          const float p00 = ex2(fmaf(s00, c0, -m0)), p01 = ex2(fmaf(s01, c0, -m0)), p10 = ex2(fmaf(s10, c1, -m1)), p11 = ex2(fmaf(s11, c1, -m1));
          const float i0 = rcp(quad_sum(p00 + p01)), i1 = rcp(quad_sum(p10 + p11));
          const uint32_t p0 = pack_bf16(p00 * i0, p01 * i0), p1 = pack_bf16(p10 * i1, p11 * i1);
          const uint32_t pf[4] = {p0 & upm, 0u, p0 & ~upm, p1 & upm};
#pragma unroll
          for (int gi = 0; gi < 3; gi++) {
            const int g = gi < 2 ? 2 * h + gi : 8 + h;
            float o[4];
            mma16c(o, pf, V01[g][0], V01[g][1], 0.f);
            mma8(o, 0u, p1 & ~upm, V2[g]);
            uint32_t* d = gi < 2 ? Om + 2 * g : Oe + 2 * h;
            d[0] = pack_bf16(o[0], o[1]); d[1] = pack_bf16(o[2], o[3]);
          }
          if (h > 0) {
#pragma unroll
            for (int e = 0; e < 2; e++) {
              if (!odd && q < h) Om[4 * h + e] = Oe[2 * h - 2 + e];
              if (odd && q >= h) Om[4 * h - 2 + e] = Oe[2 * h + e];
            }
            stg4(po + (h - 1) * 32, nz(Om[4 * h - 4]), Om[4 * h - 3], Om[4 * h - 2], Om[4 * h - 1]);
            if (h == 1 && w >= 4) asm volatile("bar.arrive 4, 256;" ::: "memory");
          }
        }
        STAMP(4);
        stg4(po + 96, nz(Om[12]), Om[13], Om[14], Om[15]);
        stg2((char*)(xbase + 16 * SLAB + 1024 + j * 16) + lane * 8, nz(odd ? Oe[0] : Oe[6]), odd ? Oe[1] : Oe[7]);
#pragma unroll
        for (int i = 0; i < 16; i++) X[i] = Om[i];
      }
      if (lane == 0) asm volatile("st.relaxed.gpu.global.b32 [%0], %1;" :: "l"(scr + OFF_S + (8 + w) * 96 + j * 8), "r"(tag) : "memory");
      {
        if (layer == 0) {
          const uint32_t xrow = (w & 1) * 8192 + (16 * (w >> 1) + (lane & 15)) * 128;
          uint32_t u0, u1;
          mbar_wait(xbar0, 1); mbar_wait(xbar0 + 8, 1);
#pragma unroll
          for (int i = 0; i < 5; i++) {
            const uint32_t g = i < 4 ? j + odd + 2 * i : j + (odd ? 0 : 8);
            const uint32_t a = sb + PARK + (g >> 3) * STAGE + xrow;
            if (i < 4) ldsm4(a + ((((g & 7) + (lane >> 4)) ^ (lane & 7)) << 4), res[4 * i], res[4 * i + 1], res[4 * i + 2], res[4 * i + 3]);
            else ldsm4(a + (((g & 7) ^ (lane & 7)) << 4), res[16], res[17], u0, u1);
          }
        }
        const uint4* src = xbase + 16 * SLAB + lane;
        const uint32_t st0 = rg.st;
        auto stage_of = [&](uint32_t i) { const uint32_t x = st0 + i; return x >= NST ? x - NST : x; };
        {
          const uint32_t x = st0 + lane, wrap = x >= NST;
          mbar_wait(lane < 5 ? full0 + (x - wrap * NST) * 8 : remo_full, lane < 5 ? rg.ph ^ wrap : layer);
          __syncwarp();
          if (st0) { rg.st = st0 - 1; rg.ph ^= 1; } else rg.st = 5;
        }
        float acc[36];
        auto block72 = [&](uint32_t kb, uint32_t base, const uint32_t* a) {
          const uint64_t d0 = DESC_HI | ((base >> 4) + (((sd + REM + 27648 + (kb >> 1) * 2048 + (kb & 1) * 64 - base) >> 4) << 16));
          wg_fence();
#pragma unroll
          for (int i = 0; i < 4; i++) wgmma_rs_n72(acc, a + 4 * i, d0 - (uint64_t)(i * ((127u << 16) - 128u)), 1);
          wg_commit();
        };
#pragma unroll
        for (int i = 0; i < 18; i++) { acc[2 * i] = bf_lo(res[i]); acc[2 * i + 1] = bf_hi(res[i]); }
        block72(0, sd + st0 * STAGE, X);
        {
          const uint4* fp = scr + OFF_S + (8 + w) * 96 + (lane & 7) * 8;
          int n = 0;
          STAMP(8);
#pragma unroll 1
          while (true) {
            uint32_t f;
            asm volatile("ld.relaxed.gpu.global.b32 %0, [%1];" : "=r"(f) : "l"(fp) : "memory");
            if (__all_sync(~0u, f == tag)) break;
            SPIN_GUARD(n);
          }
          STAMP(9);
        }
#pragma unroll
        for (int kb = 1; kb < GO; kb++) load_kb(kb, src, (const char*)src - lane * 8, 256);
        __syncwarp();
        uint32_t m = ~0u;
#pragma unroll
        for (int kb = 1; kb < 9; kb++) {
          m = umin2(m, umin2(umin2(X[16 * kb], X[16 * kb + 4]), umin2(X[16 * kb + 8], X[16 * kb + 12])));
          if (kb == 8) m = umin2(m, umin2(umin2(X[130], X[134]), umin2(X[138], X[142])));
          if (kb + GO - 1 < 9) {
            const uint4* s2 = src + (m == 0u);
            load_kb(kb + GO - 1, s2, (const char*)s2 - lane * 8, 256);
            __syncwarp();
          }
          block72(kb, sd + stage_of(kb >> 1) * STAGE + (kb & 1) * 8192, X + 16 * kb);
          if (!(kb & 1)) { wg_wait<1>(); release(stage_of((kb >> 1) - 1)); }
        }
        uint32_t redo;
        asm volatile("{\n.reg .pred p;\nsetp.eq.u32 p, %1, 0;\nbar.red.or.pred p, %2, 128, p;\nselp.u32 %0, 1, 0, p;\n}" : "=r"(redo) : "r"(m), "r"(5 + (w >> 2)) : "memory");
        wg_wait<0>();
        release(stage_of(4));
        pin(acc);
        if (__any_sync(~0u, redo || FORCE_REDO)) {
#pragma unroll
          for (int i = 0; i < 18; i++) { res[i] = __shfl_sync(~0u, res[i], lane); acc[2 * i] = bf_lo(res[i]); acc[2 * i + 1] = bf_hi(res[i]); }
          const uint32_t box = PARK + 2 * STAGE + (w >> 2) * 8192, bar = redo_full + (w >> 2) * 8;
#pragma unroll 1
          for (uint32_t kb = 0; kb < 10; kb++) {
            asm volatile("bar.sync %0, 128;" :: "r"(5 + (w >> 2)) : "memory");
            if ((w & 3) == 0)
              asm volatile("{\n.reg .pred e;\nelect.sync _|e, 0xffffffff;\n@e mbarrier.arrive.expect_tx.shared::cta.b64 _, [%2], 8192;\n"
                           "@e cp.async.bulk.tensor.3d.shared::cluster.global.mbarrier::complete_tx::bytes [%0], [%1, {%3, %4, %5}], [%2];\n}"
                           :: "r"(sb + box), "l"(&maps.m[kb >= 8 ? 8 : 1]), "r"(bar), "r"(72 * j + 8 * odd), "r"(kb >= 8 ? 64 : 0),
                              "r"(kb >= 8 ? 0 : (9 * blk(kb) + 1) >> 1) : "memory");
            mbar_wait(bar, kb & 1);
            if (kb == 9) break;
            int n = 0;
#pragma unroll 1
            while (true) {
              const char* l = (const char*)(src + blk(kb) * 128) - (kb == 8 ? lane * 8 : 0);
#pragma unroll
              for (int i = 0; i < 4; i++) ldg2(X + 4 * i, l + i * 512);
              uint32_t mm = umin2(umin2(X[0], X[4]), umin2(X[8], X[12]));
              l += (kb == 8 ? 256 : 8) + (mm == 0u ? 16 : 0);
#pragma unroll
              for (int i = 0; i < 4; i++) ldg2(X + 4 * i + 2, l + i * 512);
              if (kb == 8) mm = umin2(mm, umin2(umin2(X[2], X[6]), umin2(X[10], X[14])));
              if (__all_sync(~0u, mm != 0u)) break;
              SPIN_GUARD(n);
            }
            block72(kb, sd + box, X);
            wg_wait<0>();
            pin(acc);
          }
        }
        STAMP(10);
#pragma unroll
        for (int i = 0; i < 18; i++) res[i] = pack_bf16(acc[2 * i], acc[2 * i + 1]);
        if (j < PRI) put72(xbase + 32 * SLAB, j, lane, res);
        publish_stats<9>(scr + OFF_S + (16 + w) * 96 + j * 8, acc, tag, lane);
        if (j >= PRI) put72(xbase + 32 * SLAB, j, lane, res);
#pragma unroll
        for (int i = 0; i < 16; i++) X[i] = res[i];
      }
      continue;
      }
      const uint32_t hp = sb + PARK + w * 512 + lane_id() * 16;
      auto pack8 = [&](float (&a)[32], int p, uint32_t* o) {
#pragma unroll
        for (int e = 0; e < 8; e++) asm volatile("" : "+f"(a[8 * p + e]) :: "memory");
#pragma unroll
        for (int e = 0; e < 4; e++) o[e] = pack_bf16(a[8 * p + 2 * e], a[8 * p + 2 * e + 1]);
      };
      const float ka0 = 0.7978845608028654f * rs0, kb0 = 0.044715f * ka0 * rs0 * rs0, ku0 = 0.5f * rs0 * rs0;
      const float ka1 = 0.7978845608028654f * rs1, kb1 = 0.044715f * ka1 * rs1 * rs1, ku1 = 0.5f * rs1 * rs1;
      auto packu8 = [&](int p, uint32_t* o) {
#pragma unroll
        for (int e = 0; e < 8; e++) asm volatile("" : "+f"(aA[8 * p + e]) :: "memory");
#pragma unroll
        for (int e = 0; e < 4; e++) o[e] = pack_bf16(aA[8 * p + 2 * e] * ((e & 1) ? ku1 : ku0), aA[8 * p + 2 * e + 1] * ((e & 1) ? ku1 : ku0));
      };
      auto geglu8 = [&](int p, uint32_t* u) {
#pragma unroll
        for (int e = 0; e < 8; e++) asm volatile("" : "+f"(aB[8 * p + e]) :: "memory");
        float h[8];
#pragma unroll
        for (int e = 0; e < 8; e++) {
          const float g = aB[8 * p + e];
          h[e] = fmaf(g, tanh_ap(g * fmaf(g * g, (e & 2) ? kb1 : kb0, (e & 2) ? ka1 : ka0)), g);
        }
#pragma unroll
        for (int e = 0; e < 4; e++) u[e] = mul_bf16x2(pack_bf16(h[2 * e], h[2 * e + 1]), u[e]);
      };
      auto box = [&](int b, auto&& filler) {
        const int kb = b < 9 ? b : b - 9;
        if (!(b & 1)) { if (b == 0) mbar_wait_trap(full0 + rg.st * 8, rg.ph); else mbar_wait(full0 + rg.st * 8, rg.ph); }
        const uint64_t desc = DESC_HI | ((sd + rg.st * STAGE + (b & 1) * 8192) >> 4);
        wg_fence();
#pragma unroll
        for (int i = 0; i < 4; i++) {
          if (b < 9) wgmma_rs_n64(aA, X + 4 * (4 * kb + i), desc + i * 128, kb + i != 0);
          else wgmma_rs_n64(aB, X + 4 * (4 * kb + i), desc + i * 128, kb + i != 0);
          if (i == 2) filler();
        }
        wg_commit();
        if (b & 1) { prev = rg.st; rg.next(); } else { wg_wait<1>(); release(prev); }
      };
      auto nop = [] {};
      auto step = [&](int st, auto&& filler) { box(2 * st, nop); box(2 * st + 1, filler); };
#pragma unroll
      for (int p = 0; p < 4; p++) { uint32_t o[4]; packu8(p, o); sts4(hp + p * 4096, o); }
      box(0, nop);
      if (lead) mbar_arrive(xb_done);
#pragma unroll 1
      for (int c = 1;; c++) {
        const uint32_t hc = hp + c * 4 * 4096;
#pragma unroll
        for (int b = 1; b < 18; b++) box(b, [&] {
          if ((b & 1) && b < 8) { uint32_t o[4]; const uint32_t a = hc - (4 - (b >> 1)) * 4096; lds4(a, o); geglu8(b >> 1, o); sts4(a, o); }
          if ((b & 1) && b > 10) { uint32_t o[4]; packu8((b - 11) >> 1, o); if (c < 8) sts4(hc + ((b - 11) >> 1) * 4096, o); } });
        ZSTAMP(4, c);
        if (c == 8) break;
        box(0, nop);
      }
      wg_wait<0>();
      STAMP(21);
      GSTAMP(19);
      auto unpark = [&](int kb) {
#pragma unroll
        for (int s = 4 * kb; s < 4 * kb + 4; s++) lds4(hp + s * 4096, X + 4 * s);
      };
      unpark(0);
      uint32_t U[16];
#pragma unroll
      for (int p = 0; p < 4; p++) packu8(p, U + 4 * p);
#pragma unroll
      for (int b = 0; b < 8; b++) box(b, [&] {
        if (b < 7) unpark(b + 1);
        if (b & 1) {
          geglu8(b >> 1, U + 2 * (b - 1));
          if (rg.ph > 1) sts4(hp, U + 2 * (b - 1));
#pragma unroll
          for (int i = 0; i < 4; i++) X[128 + 2 * (b - 1) + i] = U[2 * (b - 1) + i];
        } });
      STAMP(24);
      if (layer == 0 && lead) mbar_arrive(park_free);
      const uint32_t lane2 = lane_id();
      uint4* const pw = scr + OFF_P + (j * 8 + w) * SLAB + lane2;
      const uint4* const pr = scr + OFF_P + w * SLAB + 4 * j * 32 + lane2;
      auto put_part = [&](float (&a)[32], int p, uint32_t chunk) {
        uint32_t o[4];
        pack8(a, p, o);
        stg4(pw + (chunk * 4 + p) * 32, (o[0] & ~1u) | tag, o[1], o[2], o[3]);
      };
      auto slot = [&](int p) { return sb + w * 2048 + (p < 3 ? PARK + p * 16384 : KVS + (p - 3) * 16384); };
      auto fetch = [&](int p) {
        bulk_load(slot(p), scr + OFF_P + (((j - p) & 7) * 8 + w) * SLAB + 4 * j * 32, 2048, pbar0 + w * 8, true);
      };
#pragma unroll 1
      for (int sp = 0;; sp++) {
        const uint32_t ca = sp == 0 ? 8 : ((j + 2 * sp) & 7), cb = (j + 2 * sp + 1) & 7;
        if (sp == 1 && lead) mbar_arrive(c8_go);
#pragma unroll
        for (int st = 4; st < 9; st++) step(st, [&] {
          if (st == 5 || st == 6) { put_part(aA, 2 * (st - 5), ca); put_part(aA, 2 * (st - 5) + 1, ca); }
          if (st == 8 && sp > 1) { if (sp == 3) mbar_wait(c8_done, layer); fetch(2 * sp - 2); } });
        STAMP(25 + sp);
        if (sp == 3) break;
#pragma unroll
        for (int st = 0; st < 4; st++) step(st, [&] {
          if (st < 2) { put_part(aB, 2 * st, cb); put_part(aB, 2 * st + 1, cb); }
          if (st == 3 && sp > 0) fetch(2 * sp - 1); });
      }
      auto load_p = [&](int p, uint32_t* d) {
#pragma unroll
        for (int i = 0; i < 4; i++) ldg4(d + 4 * i, pr + ((j - p) & 7) * 8 * SLAB + i * 32);
      };
#pragma unroll
      for (int b = 0; b < 9; b++) {
        box(b, [&] {
          if (b == 1) {
#pragma unroll
            for (int p = 0; p < 4; p++) put_part(aB, p, (j + 7) & 7);
          }
          if (b == 3) { load_p(5, X); load_p(6, X + 16); }
          if (b == 7) load_p(7, X + 32); });
      }
      mbar_wait(res_full, layer);
      mbar_wait(pbar0 + w * 8, layer);
#pragma unroll
      for (int p = 1; p < 5; p++)
#pragma unroll
        for (int i = 0; i < 4; i++) lds4(slot(p) + lane2 * 16 + i * 512, X + 48 + 16 * p + 4 * i);
#pragma unroll
      for (int i = 0; i < 4; i++) {
        const bool split = j == 2 * i + 1;
        const uint32_t a = slot(0) + i * 512 + (split ? lane2 * 8 : lane2 * 16);
        lds2(a, X + 48 + 4 * i); lds2(a + (split ? 256 : 8), X + 50 + 4 * i);
      }
      wg_wait<0>();
      release(rg.st); rg.next();
      pin(aA);
      STAMP(22);
      GSTAMP(20);
      {
        const uint32_t lane = lane2, r = lane >> 2, q = lane & 3;
        const uint32_t eye = r == 2 * q ? 0x3f80u : r == 2 * q + 1 ? 0x3f800000u : 0u;
        auto bad = [&](const uint32_t* d) { return diff2(d[0], d[4], tag) | diff2(d[8], d[12], tag); };
        auto add = [&](const uint32_t* d) {
#pragma unroll
          for (int g = 0; g < 8; g++) mma8(aA + 4 * g, d[2 * g], d[2 * g + 1], eye);
        };
        int n = 0;
#pragma unroll 1
        while (!__all_sync(~0u, ((or3(bad(X), bad(X + 16), bad(X + 64)) | or3(bad(X + 80), bad(X + 96), bad(X + 112))) & 1u) == 0u)) {
          SPIN_GUARD(n);
          load_p(5, X); load_p(6, X + 16);
#pragma unroll
          for (int p = 1; p < 5; p++) load_p(p, X + 48 + 16 * p);
        }
        add(X); add(X + 16);
#pragma unroll
        for (int p = 4; p >= 0; p--) add(X + 48 + 16 * ((p + 1) % 5));
        STAMP(11);
#pragma unroll 1
        while (!__all_sync(~0u, (bad(X + 32) & 1u) == 0u)) { SPIN_GUARD(n); load_p(7, X + 32); }
        add(X + 32);
        STAMP(12);
        uint32_t res[16];
#pragma unroll
        for (int i = 0; i < 16; i++) X[i] = res[i] = pack_bf16(aA[2 * i], aA[2 * i + 1]);
        if (layer == 0) {
          uint4* p = xbase + 8 * SLAB + 4 * j * 32 + lane;
          auto put = [&] {
#pragma unroll
            for (int i = 0; i < 4; i++) stg4(p + i * 32, nz(res[4 * i]), res[4 * i + 1], res[4 * i + 2], res[4 * i + 3]);
          };
          if (j < PRI) put();
          publish_stats<8>(scr + OFF_S + w * 96 + j * 8, aA, 1u, lane);
          if (j >= PRI) put();
          if (lane == 0) mbar_arrive(kv_free);
        } else {
          const uint32_t tb = slot(0);
          __syncwarp();
#pragma unroll
          for (int i = 0; i < 4; i++) {
            const uint32_t row = (lane2 & 7) + (lane2 & 8), g = 2 * i + (lane2 >> 4);
            asm volatile("stmatrix.sync.aligned.m8n8.x4.shared.b16 [%0], {%1,%2,%3,%4};"
                         :: "r"(tb + row * 128 + ((g ^ (row & 7)) << 4)), "r"(res[4 * i]), "r"(res[4 * i + 1]), "r"(res[4 * i + 2]), "r"(res[4 * i + 3]) : "memory");
          }
          __syncwarp();
#pragma unroll
          for (int i = 0; i < 4; i++) {
            const uint32_t row = 4 * i + (lane2 >> 3), g = lane2 & 7;
            uint32_t v[4];
            lds4(tb + row * 128 + ((g ^ (row & 7)) << 4), v);
            *(uint4*)(out + (128 * t + 32 * (w >> 1) + 2 * row + (w & 1)) * 576 + 64 * j + 8 * g) = make_uint4(v[0], v[1], v[2], v[3]);
          }
        }
      }
      STAMP(23);
    }
  }
}

typedef CUresult (*EncodeFn)(CUtensorMap*, CUtensorMapDataType, cuuint32_t, void*, const cuuint64_t*, const cuuint64_t*,
                             const cuuint32_t*, const cuuint32_t*, CUtensorMapInterleave, CUtensorMapSwizzle,
                             CUtensorMapL2promotion, CUtensorMapFloatOOBfill);

CUtensorMap make_map(EncodeFn f, const void* p, uint64_t cols, uint64_t rows, uint64_t grp) {
  CUtensorMap m;
  cuuint64_t dims[3] = {cols, grp, rows / grp}, str[2] = {cols * 2, cols * 2 * grp};
  cuuint32_t box[3] = {64, 16, 4}, es[3] = {1, 1, 1};
  f(&m, CU_TENSOR_MAP_DATA_TYPE_BFLOAT16, 3, const_cast<void*>(p), dims, str, box, es, CU_TENSOR_MAP_INTERLEAVE_NONE,
    CU_TENSOR_MAP_SWIZZLE_128B, CU_TENSOR_MAP_L2_PROMOTION_NONE, CU_TENSOR_MAP_FLOAT_OOB_FILL_NONE);
  return m;
}
CUtensorMap make_rem_map(EncodeFn f, const void* p, uint64_t cols) {
  CUtensorMap m;
  cuuint64_t dims[2] = {cols, 576}, str[1] = {cols * 2};
  cuuint32_t box[2] = {8, 144}, es[2] = {1, 1};
  f(&m, CU_TENSOR_MAP_DATA_TYPE_BFLOAT16, 2, const_cast<void*>(p), dims, str, box, es, CU_TENSOR_MAP_INTERLEAVE_NONE,
    CU_TENSOR_MAP_SWIZZLE_NONE, CU_TENSOR_MAP_L2_PROMOTION_NONE, CU_TENSOR_MAP_FLOAT_OOB_FILL_NONE);
  return m;
}

}

extern "C" void kernel_launch(void* const* d_in, const int* in_sizes, int n_in, void* d_out, int out_size) {
  void* fn = nullptr;
  cudaDriverEntryPointQueryResult qr;
  cudaGetDriverEntryPoint("cuTensorMapEncodeTiled", &fn, cudaEnableDefault, &qr);
  EncodeFn enc = (EncodeFn)fn;
  Maps maps;
  maps.m[0] = make_map(enc, d_in[1], 1728, 576, 16); maps.m[1] = make_map(enc, d_in[2], 576, 576, 16);
  maps.m[2] = make_map(enc, d_in[4], 4608, 576, 16); maps.m[3] = make_map(enc, d_in[5], 4608, 576, 16);
  maps.m[4] = make_map(enc, d_in[6], 576, 4608, 16);
  maps.m[5] = make_rem_map(enc, d_in[1], 1728); maps.m[6] = make_rem_map(enc, d_in[2], 576);
  maps.m[8] = make_map(enc, d_in[2], 576, 576, 144); maps.m[9] = make_map(enc, d_in[4], 4608, 576, 144);
  maps.m[10] = make_map(enc, d_in[5], 4608, 576, 144);
  {
    cuuint64_t dims[3] = {576, 1024, 2}, str[2] = {2304, 1152};
    cuuint32_t box[3] = {64, 64, 2}, es[3] = {1, 1, 1};
    enc(&maps.m[7], CU_TENSOR_MAP_DATA_TYPE_BFLOAT16, 3, d_in[0], dims, str, box, es, CU_TENSOR_MAP_INTERLEAVE_NONE,
        CU_TENSOR_MAP_SWIZZLE_128B, CU_TENSOR_MAP_L2_PROMOTION_NONE, CU_TENSOR_MAP_FLOAT_OOB_FILL_NONE);
  }
  void* scr = nullptr;
  cudaGetSymbolAddress(&scr, g_scratch);
  cudaFuncSetAttribute(mega_kernel, cudaFuncAttributeMaxDynamicSharedMemorySize, SMEM_BYTES);
  cudaLaunchConfig_t cfg = {};
  cfg.gridDim = dim3(128); cfg.blockDim = dim3(384); cfg.dynamicSmemBytes = SMEM_BYTES; cfg.stream = cudaStreamPerThread;
  cudaLaunchAttribute at[1];
  at[0].id = cudaLaunchAttributeClusterDimension; at[0].val.clusterDim.x = 2; at[0].val.clusterDim.y = 1; at[0].val.clusterDim.z = 1;
  cfg.attrs = at; cfg.numAttrs = 1;
  int dev = 0, sms = 0, clusters = 0;
  cudaGetDevice(&dev);
  cudaDeviceGetAttribute(&sms, cudaDevAttrMultiProcessorCount, dev);
  cudaOccupancyMaxActiveClusters(&clusters, mega_kernel, &cfg);
  if (sms == 132 && clusters == 66) cfg.gridDim = dim3(132);
  cudaLaunchKernelEx(&cfg, mega_kernel, maps, (uint4*)scr, (__nv_bfloat16*)d_out);
}
```

```cpp
#include <cuda_runtime.h>
#include <cuda.h>
#include <cuda_bf16.h>
#include <stdint.h>

#define TRACE 0
#define GUARD 0
#define FORCE_REDO 0
#define XPRI 4
#define XGD 3
#define XGO 5
#define VAR 0
#define ZT 0

namespace {

constexpr int NST = 6;
constexpr int STAGE = 16384;
constexpr int PARK = NST * STAGE;
constexpr int REM = PARK + 49152;
constexpr int KVS = REM + 40960;
constexpr int PIECE = PARK + 7 * STAGE;
constexpr int HSTG = KVS + 16384;
constexpr int BARS = KVS + 41472;
constexpr int TRC = BARS + 512;
constexpr int SMEM_BYTES = TRC + (TRACE ? 512 : 0);
static_assert(NST == 6, "the producer addresses empty barriers as full + 48");
static_assert(BARS >= PARK + 131072, "barriers overlap park");
static_assert(SMEM_BYTES <= 232448, "smem");

constexpr int SLAB = 36 * 32;
constexpr int SPIN_MAX = 1 << 17;
constexpr uint32_t PRI = XPRI;
constexpr int GD = XGD, GO = XGO;
constexpr int OFF_S = 0;
constexpr int OFF_H = OFF_S + 3 * 8 * 96;
constexpr int OFF_X = OFF_H + 2 * 8 * 384;
constexpr int OFF_P = OFF_X + 6 * 8 * SLAB;
constexpr int TILE = OFF_P + 8 * 8 * SLAB;
constexpr int OFF_R = 16 * TILE;
constexpr int OFF_F = OFF_R + 8 * 2304;
constexpr int SCRATCH = OFF_F + 128 * 8;

}

__device__ uint4 g_scratch[SCRATCH];

namespace {

constexpr uint64_t DESC_HI = 0x4000004000000000ull;
constexpr uint64_t DESC_REM = (576ull << 32) | (8u << 16);
__device__ __forceinline__ void wgmma_rs_n64(float (&d)[32], const uint32_t* a, uint64_t desc, int scale_d) {
  asm volatile("{\n.reg .pred p;\nsetp.ne.b32 p, %37, 0;\n"
    "wgmma.mma_async.sync.aligned.m64n64k16.f32.bf16.bf16 "
    "{%0, %1, %2, %3, %4, %5, %6, %7, %8, %9, %10, %11, %12, %13, %14, %15, %16, %17, %18, %19, %20, %21, %22, %23, %24, %25, %26, %27, %28, %29, %30, %31}, "
    "{%32, %33, %34, %35}, %36, p, 1, 1, 1;\n}\n"
    : "+f"(d[0]), "+f"(d[1]), "+f"(d[2]), "+f"(d[3]), "+f"(d[4]), "+f"(d[5]), "+f"(d[6]), "+f"(d[7]), "+f"(d[8]), "+f"(d[9]), "+f"(d[10]), "+f"(d[11]), "+f"(d[12]), "+f"(d[13]), "+f"(d[14]), "+f"(d[15]), "+f"(d[16]), "+f"(d[17]), "+f"(d[18]), "+f"(d[19]), "+f"(d[20]), "+f"(d[21]), "+f"(d[22]), "+f"(d[23]), "+f"(d[24]), "+f"(d[25]), "+f"(d[26]), "+f"(d[27]), "+f"(d[28]), "+f"(d[29]), "+f"(d[30]), "+f"(d[31])
    : "r"(a[0]), "r"(a[1]), "r"(a[2]), "r"(a[3]), "l"(desc), "r"(scale_d));
}
__device__ __forceinline__ void wgmma_rs_n72(float (&d)[36], const uint32_t* a, uint64_t desc, int scale_d) {
  asm volatile("{\n.reg .pred p;\nsetp.ne.b32 p, %41, 0;\n"
    "wgmma.mma_async.sync.aligned.m64n72k16.f32.bf16.bf16 "
    "{%0, %1, %2, %3, %4, %5, %6, %7, %8, %9, %10, %11, %12, %13, %14, %15, %16, %17, %18, %19, %20, %21, %22, %23, %24, %25, %26, %27, %28, %29, %30, %31, %32, %33, %34, %35}, "
    "{%36, %37, %38, %39}, %40, p, 1, 1, 1;\n}\n"
    : "+f"(d[0]), "+f"(d[1]), "+f"(d[2]), "+f"(d[3]), "+f"(d[4]), "+f"(d[5]), "+f"(d[6]), "+f"(d[7]), "+f"(d[8]), "+f"(d[9]), "+f"(d[10]), "+f"(d[11]), "+f"(d[12]), "+f"(d[13]), "+f"(d[14]), "+f"(d[15]), "+f"(d[16]), "+f"(d[17]), "+f"(d[18]), "+f"(d[19]), "+f"(d[20]), "+f"(d[21]), "+f"(d[22]), "+f"(d[23]), "+f"(d[24]), "+f"(d[25]), "+f"(d[26]), "+f"(d[27]), "+f"(d[28]), "+f"(d[29]), "+f"(d[30]), "+f"(d[31]), "+f"(d[32]), "+f"(d[33]), "+f"(d[34]), "+f"(d[35])
    : "r"(a[0]), "r"(a[1]), "r"(a[2]), "r"(a[3]), "l"(desc), "r"(scale_d));
}
__device__ __forceinline__ void wgmma_rs_n24(float (&d)[12], const uint32_t* a, uint64_t desc, int scale_d) {
  asm volatile("{\n.reg .pred p;\nsetp.ne.b32 p, %17, 0;\n"
    "wgmma.mma_async.sync.aligned.m64n24k16.f32.bf16.bf16 "
    "{%0, %1, %2, %3, %4, %5, %6, %7, %8, %9, %10, %11}, "
    "{%12, %13, %14, %15}, %16, p, 1, 1, 1;\n}\n"
    : "+f"(d[0]), "+f"(d[1]), "+f"(d[2]), "+f"(d[3]), "+f"(d[4]), "+f"(d[5]), "+f"(d[6]), "+f"(d[7]), "+f"(d[8]), "+f"(d[9]), "+f"(d[10]), "+f"(d[11])
    : "r"(a[0]), "r"(a[1]), "r"(a[2]), "r"(a[3]), "l"(desc), "r"(scale_d));
}

__device__ __forceinline__ void mbar_init(uint32_t a, uint32_t c) { asm volatile("mbarrier.init.shared::cta.b64 [%0], %1;" :: "r"(a), "r"(c)); }
__device__ __forceinline__ void mbar_arrive(uint32_t a) { asm volatile("mbarrier.arrive.shared::cta.b64 _, [%0];" :: "r"(a) : "memory"); }
__device__ __forceinline__ void mbar_wait_trap(uint32_t a, uint32_t ph) {
  asm volatile("{\n.reg .pred p;\n.reg .u32 n;\nmov.u32 n, 0;\n"
               "W: mbarrier.try_wait.parity.shared::cta.b64 p, [%0], %1;\n@p bra D;\n"
               "add.u32 n, n, 1;\nsetp.lt.u32 p, n, 4194304;\n@p bra W;\ntrap;\nD:\n}" :: "r"(a), "r"(ph) : "memory");
}
__device__ __forceinline__ void mbar_wait(uint32_t a, uint32_t ph) {
  asm volatile("{\n.reg .pred p;\nW: mbarrier.try_wait.parity.shared::cta.b64 p, [%0], %1;\n@!p bra W;\n}" :: "r"(a), "r"(ph) : "memory");
}
__device__ __forceinline__ uint32_t mbar_peek(uint32_t a, uint32_t ph) {
  uint32_t r;
  asm volatile("{\n.reg .pred p;\nmbarrier.test_wait.parity.shared::cta.b64 p, [%1], %2;\nselp.u32 %0, 1, 0, p;\n}" : "=r"(r) : "r"(a), "r"(ph) : "memory");
  return r;
}
__device__ __forceinline__ void mbar_wait_unless(uint32_t ready, uint32_t a, uint32_t ph) {
  asm volatile("{\n.reg .pred p;\nsetp.ne.u32 p, %2, 0;\n@p bra D;\nW: mbarrier.try_wait.parity.shared::cta.b64 p, [%0], %1;\n@!p bra W;\nD:\n}"
               :: "r"(a), "r"(ph), "r"(ready) : "memory");
}
__device__ __forceinline__ void mbar_wait_sleep(uint32_t a, uint32_t ph) {
  asm volatile("{\n.reg .pred p;\nW: mbarrier.test_wait.parity.shared::cta.b64 p, [%0], %1;\n@p bra D;\nnanosleep.u32 500;\nbra W;\nD:\n}" :: "r"(a), "r"(ph) : "memory");
}
__device__ __forceinline__ void wg_fence() { asm volatile("wgmma.fence.sync.aligned;" ::: "memory"); }
__device__ __forceinline__ void wg_commit() { asm volatile("wgmma.commit_group.sync.aligned;" ::: "memory"); }
template <int N> __device__ __forceinline__ void wg_wait() { asm volatile("wgmma.wait_group.sync.aligned %0;" :: "n"(N) : "memory"); }
__device__ __forceinline__ float tanh_ap(float x) { float y; asm("tanh.approx.f32 %0, %1;" : "=f"(y) : "f"(x)); return y; }
__device__ __forceinline__ float ex2(float x) { float y; asm("ex2.approx.ftz.f32 %0, %1;" : "=f"(y) : "f"(x)); return y; }
__device__ __forceinline__ uint32_t pack_bf16(float lo, float hi) { uint32_t r; asm("cvt.rn.bf16x2.f32 %0, %1, %2;" : "=r"(r) : "f"(hi), "f"(lo)); return r; }
__device__ __forceinline__ float bf_lo(uint32_t v) { return __uint_as_float(v << 16); }
__device__ __forceinline__ float bf_hi(uint32_t v) { return __uint_as_float(v & 0xffff0000u); }
__device__ __forceinline__ uint32_t sub_bf16x2(uint32_t a, uint32_t b) { uint32_t r; asm("sub.rn.bf16x2 %0, %1, %2;" : "=r"(r) : "r"(a), "r"(b)); return r; }
__device__ __forceinline__ uint32_t mul_bf16x2(uint32_t a, uint32_t b) { uint32_t r; asm("mul.rn.bf16x2 %0, %1, %2;" : "=r"(r) : "r"(a), "r"(b)); return r; }
__device__ __forceinline__ uint32_t diff2(uint32_t a, uint32_t b, uint32_t t) { uint32_t r; asm("lop3.b32 %0, %1, %2, %3, 0x7e;" : "=r"(r) : "r"(a), "r"(b), "r"(t)); return r; }
__device__ __forceinline__ uint32_t or3(uint32_t a, uint32_t b, uint32_t c) { uint32_t r; asm("lop3.b32 %0, %1, %2, %3, 0xfe;" : "=r"(r) : "r"(a), "r"(b), "r"(c)); return r; }
__device__ __forceinline__ uint32_t umin2(uint32_t a, uint32_t b) { uint32_t r; asm("min.u32 %0, %1, %2;" : "=r"(r) : "r"(a), "r"(b)); return r; }
__device__ __forceinline__ uint32_t bitmask(uint32_t v, int bit) { uint32_t r; asm("bfe.s32 %0, %1, %2, 1;" : "=r"(r) : "r"(v), "r"(bit)); return r; }
__device__ __forceinline__ uint32_t nz(uint32_t w) { return w == 0u ? 0x8000u : w; }

__device__ __forceinline__ void ldg4(uint32_t* d, const uint4* p) {
  asm volatile("ld.relaxed.gpu.global.v4.b32 {%0,%1,%2,%3}, [%4];" : "=r"(d[0]), "=r"(d[1]), "=r"(d[2]), "=r"(d[3]) : "l"(p) : "memory");
}
__device__ __forceinline__ void ldg2(uint32_t* d, const void* p) {
  asm volatile("ld.relaxed.gpu.global.v2.b32 {%0,%1}, [%2];" : "=r"(d[0]), "=r"(d[1]) : "l"(p) : "memory");
}
__device__ __forceinline__ void stg4(uint4* p, uint32_t a, uint32_t b, uint32_t c, uint32_t d) {
  asm volatile("st.relaxed.gpu.global.v4.b32 [%0], {%1,%2,%3,%4};" :: "l"(p), "r"(a), "r"(b), "r"(c), "r"(d) : "memory");
}
__device__ __forceinline__ void stg2(void* p, uint32_t a, uint32_t b) {
  asm volatile("st.relaxed.gpu.global.v2.b32 [%0], {%1,%2};" :: "l"(p), "r"(a), "r"(b) : "memory");
}
__device__ __forceinline__ void sts4(uint32_t a, const uint32_t* o) { asm volatile("st.shared.v4.b32 [%0], {%1,%2,%3,%4};" :: "r"(a), "r"(o[0]), "r"(o[1]), "r"(o[2]), "r"(o[3]) : "memory"); }
__device__ __forceinline__ void lds4(uint32_t a, uint32_t* o) { asm volatile("ld.shared.v4.b32 {%0,%1,%2,%3}, [%4];" : "=r"(o[0]), "=r"(o[1]), "=r"(o[2]), "=r"(o[3]) : "r"(a) : "memory"); }
__device__ __forceinline__ void lds2(uint32_t a, uint32_t* o) { asm volatile("ld.shared.v2.b32 {%0,%1}, [%2];" : "=r"(o[0]), "=r"(o[1]) : "r"(a) : "memory"); }
__device__ __forceinline__ float rcp(float x) { float y; asm("rcp.approx.ftz.f32 %0, %1;" : "=f"(y) : "f"(x)); return y; }
__device__ __forceinline__ void sts1(uint32_t a, uint32_t v) { asm volatile("st.shared.b32 [%0], %1;" :: "r"(a), "r"(v) : "memory"); }
__device__ __forceinline__ void ldsm4(uint32_t a, uint32_t& r0, uint32_t& r1, uint32_t& r2, uint32_t& r3) {
  asm volatile("ldmatrix.sync.aligned.m8n8.x4.shared.b16 {%0,%1,%2,%3}, [%4];" : "=r"(r0), "=r"(r1), "=r"(r2), "=r"(r3) : "r"(a) : "memory");
}
__device__ __forceinline__ void ldsm4t(uint32_t a, uint32_t& r0, uint32_t& r1, uint32_t& r2, uint32_t& r3) {
  asm volatile("ldmatrix.sync.aligned.m8n8.x4.trans.shared.b16 {%0,%1,%2,%3}, [%4];" : "=r"(r0), "=r"(r1), "=r"(r2), "=r"(r3) : "r"(a) : "memory");
}
__device__ __forceinline__ void mma16(float* c, uint32_t a0, uint32_t a1, uint32_t a2, uint32_t a3, uint32_t b0, uint32_t b1) {
  asm("mma.sync.aligned.m16n8k16.row.col.f32.bf16.bf16.f32 {%0,%1,%2,%3}, {%4,%5,%6,%7}, {%8,%9}, {%0,%1,%2,%3};"
    : "+f"(c[0]), "+f"(c[1]), "+f"(c[2]), "+f"(c[3]) : "r"(a0), "r"(a1), "r"(a2), "r"(a3), "r"(b0), "r"(b1));
}
__device__ __forceinline__ void mma16c(float* d, const uint32_t* a, uint32_t b0, uint32_t b1, float c01) {
  asm("mma.sync.aligned.m16n8k16.row.col.f32.bf16.bf16.f32 {%0,%1,%2,%3}, {%4,%5,%6,%7}, {%8,%9}, {%10,%10,%10,%10};"
    : "=f"(d[0]), "=f"(d[1]), "=f"(d[2]), "=f"(d[3]) : "r"(a[0]), "r"(a[1]), "r"(a[2]), "r"(a[3]), "r"(b0), "r"(b1), "f"(c01));
}
__device__ __forceinline__ void mma8(float* c, uint32_t a0, uint32_t a1, uint32_t b0) {
  asm("mma.sync.aligned.m16n8k8.row.col.f32.bf16.bf16.f32 {%0,%1,%2,%3}, {%4,%5}, {%6}, {%0,%1,%2,%3};"
    : "+f"(c[0]), "+f"(c[1]), "+f"(c[2]), "+f"(c[3]) : "r"(a0), "r"(a1), "r"(b0));
}
__device__ __forceinline__ uint32_t lane_id() { uint32_t l; asm volatile("mov.u32 %0, %%laneid;" : "=r"(l)); return l; }
__device__ __forceinline__ float quad_sum(float v) { v += __shfl_xor_sync(~0u, v, 1); v += __shfl_xor_sync(~0u, v, 2); return v; }
__device__ __forceinline__ float quad_max(float v) { v = fmaxf(v, __shfl_xor_sync(~0u, v, 1)); v = fmaxf(v, __shfl_xor_sync(~0u, v, 2)); return v; }
template <int N> __device__ __forceinline__ void pin(float (&d)[N]) {
#pragma unroll
  for (int i = 0; i < N; i++) asm volatile("" : "+f"(d[i]) :: "memory");
}
#define SPIN_GUARD(n) if (++(n) > SPIN_MAX) break

template <int NG> __device__ __forceinline__ void publish_stats(uint4* dst, const float* y, uint32_t tag, uint32_t lane) {
  float s0 = 0.f, s1 = 0.f;
#pragma unroll
  for (int g = 0; g < NG; g++) { s0 += y[4 * g] + y[4 * g + 1]; s1 += y[4 * g + 2] + y[4 * g + 3]; }
  s0 = quad_sum(s0); s1 = quad_sum(s1);
  const float m0 = s0 * (1.f / (8 * NG)), m1 = s1 * (1.f / (8 * NG));
  float q0 = 0.f, q1 = 0.f, q2 = 0.f, q3 = 0.f;
#pragma unroll
  for (int g = 0; g < NG; g++) {
    const float a = y[4 * g] - m0, b = y[4 * g + 1] - m0, c = y[4 * g + 2] - m1, d = y[4 * g + 3] - m1;
    q0 = fmaf(a, a, q0); q1 = fmaf(b, b, q1); q2 = fmaf(c, c, q2); q3 = fmaf(d, d, q3);
  }
  q0 = quad_sum(q0 + q1); q2 = quad_sum(q2 + q3);
  if ((lane & 3) == 0)
    stg4(dst + (lane >> 2), (__float_as_uint(s0) & ~1u) | tag, __float_as_uint(q0), __float_as_uint(s1), __float_as_uint(q2));
}

__device__ __forceinline__ void put72(uint4* slab, uint32_t j, uint32_t lane, const uint32_t* v) {
#pragma unroll
  for (int i = 0; i < 4; i++) stg4(slab + (4 * j + i) * 32 + lane, nz(v[4 * i]), v[4 * i + 1], v[4 * i + 2], v[4 * i + 3]);
  stg2((char*)(slab + 1024 + j * 16) + lane * 8, nz(v[16]), v[17]);
}
__device__ __forceinline__ uint32_t row72(uint32_t k) { return k % 9 == 4 ? 32 + k / 9 : k - (k + 4) / 9; }
__device__ __forceinline__ void zero_share(uint4* slab, uint32_t j, uint32_t lane) {
  uint4* p = slab + j * 144 + lane;
#pragma unroll
  for (int i = 0; i < 4; i++) stg4(p + i * 32, 0u, 0u, 0u, 0u);
  if (lane < 16) stg4(p + 128, 0u, 0u, 0u, 0u);
}

struct Maps { CUtensorMap m[11]; };

struct Ring {
  uint32_t st, ph;
  __device__ __forceinline__ void next() { if (++st == NST) { st = 0; ph ^= 1; } }
};

#define GSTAMP(i) do {} while (0)
#define STAMP(i) do {} while (0)
#define ZSTAMP(m, i) do {} while (0)

__device__ __forceinline__ void tma_box(uint32_t dst, const CUtensorMap* m, int col, int row, uint32_t bar, uint32_t expect) {
  asm volatile("{\n.reg .pred e, h;\nelect.sync _|e, 0xffffffff;\nsetp.ne.and.u32 h, %5, 0, e;\n"
               "@h mbarrier.arrive.expect_tx.shared::cta.b64 _, [%2], %5;\n"
               "@e cp.async.bulk.tensor.2d.shared::cluster.global.mbarrier::complete_tx::bytes [%0], [%1, {%3, %4}], [%2];\n}"
               :: "r"(dst), "l"(m), "r"(bar), "r"(col), "r"(row), "r"(expect) : "memory");
}

__device__ __forceinline__ void bulk_load(uint32_t dst, const void* src, uint32_t bytes, uint32_t bar, bool arm) {
  asm volatile("{\n.reg .pred e, h;\nelect.sync _|e, 0xffffffff;\nsetp.ne.and.u32 h, %4, 0, e;\n"
               "@h mbarrier.arrive.expect_tx.shared::cta.b64 _, [%3], %2;\n"
               "@e cp.async.bulk.shared::cluster.global.mbarrier::complete_tx::bytes [%0], [%1], %2, [%3];\n}"
               :: "r"(dst), "l"(src), "r"(bytes), "r"(bar), "r"((uint32_t)arm) : "memory");
}

__global__ void __launch_bounds__(384, 1) mega_kernel(
    const __grid_constant__ Maps maps, uint4* __restrict__ scratch,
    __nv_bfloat16* __restrict__ out) {
  extern __shared__ __align__(1024) uint8_t smem[];
  const uint32_t sb = (uint32_t)__cvta_generic_to_shared(smem);
  const uint32_t full0 = sb + BARS, empty0 = full0 + 8 * NST, rem_full = empty0 + 8 * NST, park_free = rem_full + 8, kv_free = park_free + 8;
  const uint32_t c8_go = kv_free + 8, c8_done = c8_go + 8, c8_full = c8_done + 8, remo_full = c8_full + 8, piece_full = remo_full + 8, xb_done = piece_full + 8, res_full = xb_done + 8, pbar0 = res_full + 8;
  const uint32_t x_done = pbar0 + 64, x_ring = x_done + 8, xbar0 = x_ring + 8, redo_full = xbar0 + 72;
  const uint32_t w = __shfl_sync(~0u, threadIdx.x >> 5, 0);
  uint32_t pair = blockIdx.x >> 1;
  if (gridDim.x == 132) {
    uint32_t smid;
    asm("mov.u32 %0, %%smid;" : "=r"(smid));
    const uint32_t tpc = smid >> 1;
    if (tpc == 60 || tpc == 61) { if (threadIdx.x == 0) { __nanosleep(20000); } return; }
    pair = tpc < 32 ? tpc : tpc >= 62 ? (tpc - 58) * 8 : 33 + (tpc - 32) / 7 * 8 + (tpc - 32) % 7;
  }
  const uint32_t rank = blockIdx.x & 1, t = (pair & 7) * 2 + rank, j = pair >> 3;
  const uint32_t sd = sb & 0x3ffff;
  const uint32_t odd = j & 1;
  uint4* const scr = scratch + t * TILE;
  auto blk = [&](uint32_t kb) { return kb == 0 ? j : kb - (kb <= j); };
  const uint32_t xs = sb + (NST - 2) * STAGE;
  auto fetch_x = [&](uint32_t dst, uint32_t b, uint32_t bar) {
    asm volatile("{\n.reg .pred e;\nelect.sync _|e, 0xffffffff;\n@e mbarrier.arrive.expect_tx.shared::cta.b64 _, [%2], 16384;\n"
                 "@e cp.async.bulk.tensor.3d.shared::cluster.global.mbarrier::complete_tx::bytes [%0], [%1, {%3, %4, 0}], [%2];\n}"
                 :: "r"(dst), "l"(&maps.m[7]), "r"(bar), "r"(64 * b), "r"(64 * t) : "memory");
  };
  if (threadIdx.x == 256) {
    for (int i = 0; i < 9; i++) mbar_init(xbar0 + 8 * i, 1);
    mbar_init(piece_full, 1);
    asm volatile("fence.mbarrier_init.release.cluster;" ::: "memory");
  }
  if (threadIdx.x == 288) {
    for (int i = 0; i < NST; i++) { mbar_init(full0 + 8 * i, 1); mbar_init(empty0 + 8 * i, 16); }
    mbar_init(x_done, 8); mbar_init(x_ring, 16); mbar_init(redo_full, 1); mbar_init(redo_full + 8, 1);
    asm volatile("fence.mbarrier_init.release.cluster;" ::: "memory");
  }
  if (threadIdx.x == 320) {
    mbar_init(rem_full, 2); mbar_init(park_free, 8); mbar_init(kv_free, 8); mbar_init(c8_go, 8); mbar_init(c8_done, 2); mbar_init(c8_full, 1);
    mbar_init(remo_full, 64); mbar_init(xb_done, 8); mbar_init(res_full, 32);
    for (int i = 0; i < 8; i++) mbar_init(pbar0 + 8 * i, 4);
    asm volatile("fence.mbarrier_init.release.cluster;" ::: "memory");
  }
  if (threadIdx.x == 352) {
    asm volatile("prefetch.tensormap [%0];" :: "l"(&maps.m[7]) : "memory");
    asm volatile("prefetch.tensormap [%0];" :: "l"(&maps.m[0]) : "memory");
  }
  __syncwarp();
  asm volatile("barrier.cluster.arrive.relaxed.aligned;" ::: "memory");
  if (w != 8) asm volatile("barrier.cluster.wait.aligned;" ::: "memory");

  if (w >= 8) {
    asm volatile("setmaxnreg.dec.sync.aligned.u32 24;");
    if (w == 8) {
#pragma unroll 1
      for (uint32_t b = 0; b < 9; b++) fetch_x(xs + b * STAGE, b, xbar0 + 8 * b);
      tma_box(sb + PIECE, &maps.m[t >= 12 ? 6 : 5], 72 * j + (odd ? 0 : 64) + (t < 8 ? 576 * ((t >> 2) + 1) : 0), 144 * (t & 3), piece_full, 2304);
      asm volatile("barrier.cluster.wait.aligned;" ::: "memory");
      uint32_t dst = sb, bar = full0, ph = 1;
#pragma unroll 1
      for (int seg = 0; seg < 34; seg++) {
        const int n = seg >= 17 ? seg - 17 : seg;
        int ma, mb, ca, cb;
        if (n < 3) { ma = mb = n == 2; ca = 72 * j + 8 * odd + (n == 0 ? 576 : 0); cb = ca + 576; }
        else if (n < 12) { ma = 3; mb = 2; ca = cb = 576 * j + 64 * (n - 3); }
        else { ma = mb = 4; ca = n == 12 ? 512 : ((j + 2 * n) & 7) * 64; cb = ((j + 2 * n + 1) & 7) * 64; }
        const bool zip = n == 0 || n == 3, solo = n == 1 || n == 2 || n == 16;
#pragma unroll 1
        for (uint32_t st = 0; st < (solo ? 5 : 9); st++) {
          if (seg == 0 && st == NST - 2) mbar_wait(x_ring, 0);
          const uint32_t b = 2 * st + rank, kb = zip ? st : b >= 9 ? b - 9 : b;
          const bool second = zip ? rank : b >= 9, shared = kb == 8 && n >= 2 && n < 12;
          const uint32_t ks = n >= 12 ? 36 * j + 4 * kb : n < 2 ? 4 * blk(kb) : shared ? 0 : (9 * blk(kb) + 1) >> 1;
          asm volatile("{\n.reg .pred p, e, f;\n.reg .u32 n;\nelect.sync _|e, 0xffffffff;\nsetp.ne.and.u32 f, %8, 0, e;\nmov.u32 n, 0;\n"
                       "W: mbarrier.try_wait.parity.shared::cta.b64 p, [%1+48], %2;\n@p bra D;\n"
                       "add.u32 n, n, 1;\nsetp.lt.u32 p, n, 4194304;\n@p bra W;\ntrap;\n"
                       "D: @e mbarrier.arrive.expect_tx.shared::cta.b64 _, [%1], %7;\n"
                       "@f cp.async.bulk.tensor.3d.shared::cluster.global.mbarrier::complete_tx::bytes.multicast::cluster [%0], [%3, {%4, %5, %6}], [%1], 3;\n}"
                       :: "r"(dst + rank * 8192), "r"(bar), "r"(ph), "l"(&maps.m[(second ? mb : ma) + (shared ? 7 : 0)]), "r"(second ? cb : ca),
                          "r"(shared ? 64 : 0), "r"(ks), "r"(solo && st == 4 ? STAGE / 2 : STAGE), "r"((uint32_t)!(solo && b == 9)) : "memory");
          dst += STAGE; bar += 8;
          if (bar == full0 + 8 * NST) { dst = sb; bar = full0; ph ^= 1; }
        }
      }
      {
#pragma unroll 1
        for (int i = 0; i < NST; i++) {
          mbar_wait_trap(bar + 48, ph);
          bar += 8;
          if (bar == full0 + 8 * NST) { bar = full0; ph ^= 1; }
        }
      }
    } else if (w == 9) {
      const uint32_t lane = lane_id();
      const uint32_t stg = sb + HSTG + lane * 16;
      uint32_t fph = 0;
#pragma unroll 1
      for (uint32_t layer = 0; layer < 2; layer++) {
        uint4* xb = scr + OFF_X + ((4 + layer) * 8 + j) * SLAB + 28 * 32;
        mbar_wait_sleep(c8_go, layer);
        int n = 0;
#pragma unroll 1
        while (true) {
          if (lane == 0) asm volatile("mbarrier.arrive.expect_tx.shared::cta.b64 _, [%0], 18432;" :: "r"(c8_full) : "memory");
          __syncwarp();
#pragma unroll 1
          for (uint32_t s = 0; s < 9; s++)
            bulk_load(sb + HSTG + s * 2048, s < 8 ? scr + OFF_P + (j + s * 8) * SLAB + 32 * 32 : xb, 2048, c8_full, false);
          mbar_wait(c8_full, fph); fph ^= 1;
          uint32_t bad = 0;
#pragma unroll 8
          for (int s = 0; s < 32; s++) { uint32_t v; asm volatile("ld.shared.b32 %0, [%1];" : "=r"(v) : "r"(stg + s * 512) : "memory"); bad |= v ^ (1 - layer); }
          if (__all_sync(~0u, (bad & 1u) == 0u)) break;
          __nanosleep(300);
          SPIN_GUARD(n);
        }
        asm volatile("bar.arrive 7, 96;" ::: "memory");
        float s0 = 0.f, s1 = 0.f;
#pragma unroll 1
        for (int g = 0; g < 8; g++) {
          const uint32_t a = stg + (g >> 1) * 512 + (g & 1) * 8;
          float a0 = 0.f, a1 = 0.f, a2 = 0.f, a3 = 0.f;
#pragma unroll 1
          for (int b = 0; b < 3; b++) {
            uint32_t v[6];
#pragma unroll
            for (int s = 0; s < 3; s++) lds2(a + (3 * b + s) * 2048, v + 2 * s);
#pragma unroll
            for (int s = 0; s < 3; s++) { a0 += bf_lo(v[2 * s]); a1 += bf_hi(v[2 * s]); a2 += bf_lo(v[2 * s + 1]); a3 += bf_hi(v[2 * s + 1]); }
          }
          sts1(a + 18432, pack_bf16(a0, a1)); sts1(a + 18436, pack_bf16(a2, a3));
          s0 += a0 + a1; s1 += a2 + a3;
        }
        __syncwarp();
        if (lane == 0) mbar_arrive(c8_done);
        s0 = quad_sum(s0); s1 = quad_sum(s1);
        float q0 = 0.f, q1 = 0.f;
        const uint32_t ln = lane_id();
#pragma unroll 1
        for (uint32_t i = 0; i < 4; i++) {
          uint32_t x[4];
          lds4(stg + 18432 + i * 512, x);
          uint4* z = xb + i * 32 + ln;
          asm volatile("" : "+l"(z));
          stg4(z, 0u, 0u, 0u, 0u);
          if (layer == 0) {
            stg4(z - (3 * 8 * SLAB - 128), nz(x[0]), x[1], nz(x[2]), x[3]);
#pragma unroll
            for (int e = 0; e < 4; e++) {
              const float m = (e & 1) ? s1 : s0, c = fmaf(m, -1.f / 64, bf_lo(x[e])), d = fmaf(m, -1.f / 64, bf_hi(x[e]));
              if (e & 1) q1 = fmaf(c, c, fmaf(d, d, q1)); else q0 = fmaf(c, c, fmaf(d, d, q0));
            }
          } else {
            uint32_t* o = (uint32_t*)(out + (128 * t + 32 * (j >> 1) + 2 * (ln >> 2) + (j & 1)) * 576 + 512 + 16 * i + 2 * (ln & 3));
            o[0] = x[0]; o[8 * 576] = x[1]; o[4] = x[2]; o[8 * 576 + 4] = x[3];
          }
        }
        if (layer == 0) {
          q0 = quad_sum(q0); q1 = quad_sum(q1);
          if ((ln & 3) == 0) stg4(scr + OFF_S + j * 96 + 64 + (ln >> 2), __float_as_uint(s0) | 1u, __float_as_uint(q0), __float_as_uint(s1), __float_as_uint(q1));
        }
      }
    } else {
      auto mark = [&](uint32_t k0, uint32_t v) {
        const uint32_t lane = lane_id();
#pragma unroll 1
        for (uint32_t k = k0; k < 6; k++) stg4(scr + OFF_S + (k * 4 + (lane >> 3)) * 96 + j * 8 + (lane & 7), k < 2 ? 0u : v, 0u, 0u, 0u);
      };
      if (w == 11) mark(2, 0u);
      auto phase2_duties = [&](uint32_t layer) {
        const uint32_t lane = lane_id();
        asm volatile("bar.sync 7, 96;" ::: "memory");
        if (w == 11) {
          if (layer == 0) mark(0, 1u);
          __syncwarp();
          if (lane == 0) mbar_arrive(c8_done);
        }
#pragma unroll 1
        for (uint32_t i = 0; i < 16; i++) {
          const uint32_t sl = (w - 10) * 4 + (i >> 2);
          bulk_load(sb + PARK + sl * 2048 + (i & 3) * 512, scr + OFF_X + ((4 + layer) * 8 + sl) * SLAB + row72(4 * j + (i & 3)) * 32, 512, res_full, true);
        }
        mbar_wait_sleep(res_full, layer);
#pragma unroll 1
        for (uint32_t i = 0; i < 16; i++) {
          stg4(scr + OFF_X + ((4 + layer) * 8 + (w - 10) * 4 + (i >> 2)) * SLAB + row72(4 * j + (i & 3)) * 32 + lane, 0u, 0u, 0u, 0u);
          if ((i & 3) == 3) __nanosleep(200);
        }
      };
      if (w == 10) {
        const uint32_t lane = lane_id();
        uint32_t* fl = (uint32_t*)(scratch + OFF_F + (t * 8 + j) * 8) + (lane & 15);
        uint32_t v;
        asm volatile("ld.relaxed.gpu.global.b32 %0, [%1];" : "=r"(v) : "l"(fl) : "memory");
        mbar_wait(piece_full, 0);
        asm volatile("{\n.reg .pred e;\nelect.sync _|e, 0xffffffff;\n@e cp.async.bulk.global.shared::cta.bulk_group [%0], [%1], 2304;\n}\n"
                     "cp.async.bulk.commit_group;\ncp.async.bulk.wait_group 0;\nfence.proxy.async;"
                     :: "l"(scratch + OFF_R + j * 2304 + t * 144), "r"(sb + PIECE) : "memory");
        __syncwarp();
        if (lane < 16) asm volatile("st.release.gpu.global.b32 [%0], 1;" :: "l"((uint32_t*)(scratch + OFF_F + (lane_id() * 8 + j) * 8) + t) : "memory");
        int n = 0;
#pragma unroll 1
        while (!__all_sync(~0u, v != 0u)) {
          __nanosleep(100);
          SPIN_GUARD(n);
          asm volatile("ld.relaxed.gpu.global.b32 %0, [%1];" : "=r"(v) : "l"(fl) : "memory");
        }
        asm volatile("st.relaxed.gpu.global.b32 [%0], 0;" :: "l"(fl) : "memory");
        mbar_wait(x_done, 0);
      }
#pragma unroll 1
      for (uint32_t layer = 0; layer < 3; layer++) {
        if (w == 10 && layer < 2) {
          if (layer) mbar_wait_sleep(park_free, 0);
          const uint4* img = scratch + OFF_R + j * 2304;
          if (lane_id() == 0) asm volatile("mbarrier.arrive.expect_tx.shared::cta.b64 _, [%0], 27648;\nmbarrier.arrive.expect_tx.shared::cta.b64 _, [%1], 9216;"
                                           :: "r"(rem_full), "r"(piece_full) : "memory");
          __syncwarp();
#pragma unroll 1
          for (uint32_t p = 0; p < 3; p++) {
            bulk_load(sb + REM + p * 9216, img + p * 576 + j * 64, 1024, rem_full, false);
            if (j) bulk_load(sb + REM + p * 9216 + 1024, img + p * 576, j * 1024, rem_full, false);
            bulk_load(sb + REM + p * 9216 + (j + 1) * 1024, img + p * 576 + (j + 1) * 64, (8 - j) * 1024, rem_full, false);
          }
#pragma unroll 1
          for (uint32_t i = 0; i < 12; i++)
            bulk_load(sb + REM + 27648 + (i < 8 ? i * 1024 : 6144 + i * 256), img + 1728 + (i < 8 ? (9 * blk(i) + 1) >> 1 : 9 * i - 68) * 16,
                      i < 8 ? 1024 : 256, piece_full, false);
          if (layer == 0) { fetch_x(sb + PARK, j, xbar0); fetch_x(sb + PARK + STAGE, j + 1, xbar0 + 8); }
        }
        if (w == 11 && layer < 2) {
          if (layer) mbar_wait_sleep(park_free, 0);
          __syncwarp();
          if (lane_id() == 0) mbar_arrive(rem_full);
        }
        if (layer) phase2_duties(layer - 1);
        if (layer == 2) break;
        mbar_wait_sleep(layer ? kv_free : x_done, 0);
        if (t > 0) {
          const uint32_t lane = lane_id(), r = lane >> 2, q = lane & 3;
#pragma unroll 1
          for (uint32_t pc = 0; pc < 3; pc++) {
            uint4* hp = scr + OFF_H + ((layer * 8 + j) * 2 + (w - 10)) * 192 + pc * 64 + lane;
            uint32_t hl[8];
            int n = 0;
            hl[4] = 1u;
#pragma unroll 1
            while (true) {
              ldg4(hl, hp);
              if (pc < 2) ldg4(hl + 4, hp + 32);
              if (__all_sync(~0u, hl[0] != 0u && hl[4] != 0u)) break;
              __nanosleep(100);
              SPIN_GUARD(n);
            }
            const uint32_t dst = sb + KVS + (w - 10) * 10368 + r * 144 + q * 4;
            if (pc < 2) {
#pragma unroll
              for (int g = 0; g < 8; g++) sts1(dst + pc * 20736 + odd * 16 + g * 16, hl[g]);
              stg4(hp + 32, 0u, 0u, 0u, 0u);
            } else {
              sts1(dst + (odd ? 0 : 128), hl[0]); sts1(dst + 20736 + (odd ? 0 : 128), hl[1]);
            }
            stg4(hp, 0u, 0u, 0u, 0u);
          }
        }
        asm volatile("bar.arrive 1, 192;" ::: "memory");
        mbar_wait(rem_full, layer);
        mbar_wait(piece_full, 1 - layer);
#pragma unroll 1
        for (uint32_t b = 0; b < 5; b++) {
          const uint32_t blk = sb + REM + 27648 + b * 2048, k = (w - 10) * 32 + lane_id(), rr = k & 7;
          const uint32_t dst = blk + ((k >> 3) & 1) * 1024 + rr * 128 + (((k >> 4) ^ rr) << 4);
          uint32_t v[8];
          lds4(blk + k * 16, v); lds4(blk + 1024 + k * 16, v + 4);
          asm volatile("bar.sync 3, 64;" ::: "memory");
          sts4(dst, v); sts4(dst ^ 64, v + 4);
        }
        asm volatile("fence.proxy.async.shared::cta;" ::: "memory");
        mbar_arrive(remo_full);
        mbar_wait_sleep(xb_done, layer);
        if (w == 10 && layer == 1) {
          const uint32_t lane = lane_id();
          stg4(scr + OFF_S + (lane >> 3) * 96 + j * 8 + (lane & 7), 0u, 0u, 0u, 0u);
          stg4(scr + OFF_S + (4 + (lane >> 3)) * 96 + j * 8 + (lane & 7), 0u, 0u, 0u, 0u);
          if (lane < 8) stg4(scr + OFF_S + j * 96 + 64 + lane, 0u, 0u, 0u, 0u);
        }
#pragma unroll 1
        for (uint32_t i = 0; i < 8 && (w == 11 || layer == 1); i++) {
          zero_share(scr + OFF_X + ((w - 10) * 16 + layer * 8 + i) * SLAB, j, lane_id());
          __nanosleep(500);
        }
      }
    }
  } else {
    asm volatile("setmaxnreg.inc.sync.aligned.u32 240;");
    const bool lead = lane_id() == 0;
    Ring rg{0, 0};
    uint32_t prev = 0;
    uint32_t X[144];
    float rs0, rs1;
    const bool lead2 = lane_id() < 2;
    uint32_t empty_at;
    asm volatile("mapa.shared::cluster.u32 %0, %1, %2;" : "=r"(empty_at) : "r"(empty0), "r"(lane_id() & 1));
    auto release = [&](uint32_t st) { if (lead2) asm volatile("mbarrier.arrive.shared::cluster.b64 _, [%0];" :: "r"(empty_at + st * 8) : "memory"); };
    auto load_kb = [&](int kb, const uint4* src, const char* lo, uint32_t hoff) {
      const uint4* p;
      asm("{\n.reg .pred p;\n.reg .u64 t;\nsetp.ge.u32 p, %2, %3;\nadd.u64 t, %1, -2048;\nselp.b64 %0, t, %1, p;\n}" : "=l"(p) : "l"(src), "r"(j), "r"(kb));
#pragma unroll
      for (int i = 0; i < 4; i++) {
        if (kb == 8) { ldg2(X + 128 + 4 * i, lo + (32 + i) * 512); ldg2(X + 130 + 4 * i, lo + hoff + (32 + i) * 512); }
        else ldg4(X + 16 * kb + 4 * i, p + kb * 128 + i * 32);
      }
    };
    auto check_kb = [&](bool skip, int kb, const uint4* src, const char* lo, uint32_t hoff) {
      int n = 0;
#pragma unroll 1
      while (true) {
        uint32_t m = umin2(umin2(X[16 * kb], X[16 * kb + 4]), umin2(X[16 * kb + 8], X[16 * kb + 12]));
        if (kb == 8) m = umin2(m, umin2(umin2(X[130], X[134]), umin2(X[138], X[142])));
        if (__all_sync(~0u, m != 0u || skip)) break;
        SPIN_GUARD(n);
        load_kb(kb, src, lo, hoff);
      }
    };
#pragma unroll
    for (int i = 0; i < 16; i++) X[i] = 0u;
#pragma unroll 1
    for (uint32_t hf = 0; hf < 4; hf++) {
      const uint32_t layer = hf >> 1;
      const bool ffn = hf & 1;
      const uint32_t tag = 1 - layer;
      uint4* const xbase = scr + OFF_X + (layer * 8 + w) * SLAB;
      float aA[32], aB[32];
      {
        const uint32_t lane = lane_id(), r = lane >> 2, q = lane & 3;
        const uint4* src = xbase + (ffn ? 32 * SLAB : 0) + lane;
        const char* lo = (const char*)src - (ffn ? lane * 8 : 0);
        const uint32_t hoff = ffn ? 256 : 8;
        const uint32_t xoff = (w & 1) * 8192 + (16 * (w >> 1) + (lane & 15)) * 128 + (((lane >> 4) ^ (lane & 7)) << 4);
        auto load_x = [&](uint32_t b, uint32_t* d) {
#pragma unroll
          for (int i = 0; i < 4; i++) ldsm4(xs + b * STAGE + (xoff ^ (32 * i)), d[4 * i], d[4 * i + 1], d[4 * i + 2], d[4 * i + 3]);
        };
        auto load_any = [&](int kb) { if (hf == 0) load_x(blk(kb), X + 16 * kb); else load_kb(kb, src, lo, hoff); };
        float m0, m1, v0, v1;
        STAMP(ffn * 16 + 0);
        if (hf == 0) {
          float sum[2][4] = {}, sq0[4][4] = {}, sq1[4][4] = {};
          uint32_t p0, p1;
          mbar_wait(xbar0, 0);
          ldsm4(xs + xoff, p0, p1, X[0], X[1]);
          p0 = __byte_perm(__shfl_sync(~0u, p0, lane & 28), 0, 0x1010); p1 = __byte_perm(__shfl_sync(~0u, p1, lane & 28), 0, 0x1010);
#pragma unroll 3
          for (uint32_t b = 0; b < 9; b++) {
            uint32_t d[16];
            mbar_wait(xbar0 + 8 * b, 0);
            load_x(b, d);
#pragma unroll
            for (int i = 0; i < 16; i++) d[i] = sub_bf16x2(d[i], (i & 1) ? p1 : p0);
#pragma unroll
            for (int g = 0; g < 8; g++) {
              if (!(g & 1)) mma16(sum[(g >> 1) & 1], d[2 * g], d[2 * g + 1], d[2 * g + 2], d[2 * g + 3], 0x3f803f80u, 0x3f803f80u);
              mma8(sq0[g & 3], d[2 * g], d[2 * g + 1], d[2 * g]); mma8(sq1[g & 3], d[2 * g], d[2 * g + 1], d[2 * g + 1]);
            }
          }
          STAMP(1);
          GSTAMP(14);
#pragma unroll
          for (int kb = 0; kb < GD; kb++) load_x(blk(kb), X + 16 * kb);
          release((x_ring - empty0) / 8);
          auto tot = [](float (&c)[4][4], int e) { return (c[0][e] + c[1][e]) + (c[2][e] + c[3][e]); };
          const float a0 = (sum[0][0] + sum[1][0]) * (1.f / 576), a1 = (sum[0][2] + sum[1][2]) * (1.f / 576);
          const uint32_t dg = (lane & 28) + (r >> 1);
          v0 = fmaxf(fmaf(__shfl_sync(~0u, (r & 1) ? tot(sq0, 1) : tot(sq0, 0), dg), 1.f / 576, -a0 * a0), 0.f);
          v1 = fmaxf(fmaf(__shfl_sync(~0u, (r & 1) ? tot(sq1, 3) : tot(sq1, 2), dg), 1.f / 576, -a1 * a1), 0.f);
          m0 = bf_lo(p0) + a0; m1 = bf_lo(p1) + a1;
        } else {
          uint32_t s[3][4];
          const uint4* p = scr + OFF_S + ((ffn ? 16 : 0) + w) * 96 + q * 8 + r;
          const bool third = !ffn && q == 0;
          const uint32_t rdy = ffn ? tag : 1u;
          int n = 0;
          s[2][0] = rdy; s[2][1] = s[2][2] = s[2][3] = 0u;
#pragma unroll 1
          while (true) {
            ldg4(s[0], p); ldg4(s[1], p + 32);
            if (third) ldg4(s[2], p + 64);
            if (__all_sync(~0u, ((diff2(s[0][0], s[1][0], rdy) | diff2(s[1][0], s[2][0], rdy)) & 1u) == 0u)) break;
            SPIN_GUARD(n);
          }
          STAMP(ffn * 16 + 1);
          ZSTAMP(1 + ffn, 0);
          GSTAMP(14 + ffn);
#pragma unroll
          for (int kb = 1; kb < GD; kb++) load_kb(kb, src, lo, hoff);
          float t0 = 0.f, t1 = 0.f;
#pragma unroll
          for (int i = 0; i < 3; i++) { t0 += __uint_as_float(s[i][0]); t1 += __uint_as_float(s[i][2]); }
          m0 = quad_sum(t0) * (1.f / 576); m1 = quad_sum(t1) * (1.f / 576);
          const float cnt = ffn ? 72.f : 64.f, inv = ffn ? 1.f / 72 : 1.f / 64;
          v0 = 0.f; v1 = 0.f;
#pragma unroll
          for (int i = 0; i < 3; i++) {
            const float c = (i < 2 || third) ? cnt : 0.f;
            const float d0 = fmaf(__uint_as_float(s[i][0]), inv, -m0), d1 = fmaf(__uint_as_float(s[i][2]), inv, -m1);
            v0 += fmaf(d0 * d0, c, __uint_as_float(s[i][1])); v1 += fmaf(d1 * d1, c, __uint_as_float(s[i][3]));
          }
          v0 = quad_sum(v0) * (1.f / 576); v1 = quad_sum(v1) * (1.f / 576);
        }
        rs0 = rsqrtf(v0 + 1e-5f); rs1 = rsqrtf(v1 + 1e-5f);
        const uint32_t mean0 = pack_bf16(m0, m0), mean1 = pack_bf16(m1, m1);
#pragma unroll
        for (int kb = 0; kb < 9; kb++) {
          if (kb > 0) check_kb(hf == 0, kb, src, lo, hoff);
          if (kb + GD < 9) load_any(kb + GD);
          if (kb + GD == 8 && hf == 0 && lead) mbar_arrive(x_done);
#pragma unroll
          for (int i = 16 * kb; i < 16 * kb + 16; i++) X[i] = sub_bf16x2(X[i], (i & 1) ? mean1 : mean0);
          ZSTAMP(1 + ffn, 1 + 3 * kb);
          mbar_wait(full0 + rg.st * 8, rg.ph);
          ZSTAMP(1 + ffn, 2 + 3 * kb);
          const uint64_t desc = DESC_HI | ((sd + rg.st * STAGE) >> 4);
          wg_fence();
#pragma unroll
          for (int i = 0; i < 4; i++) wgmma_rs_n64(aA, X + 4 * (4 * kb + i), desc + i * 128, kb + i != 0);
          if (kb == 8) { wg_commit(); wg_wait<1>(); wg_fence(); }
#pragma unroll
          for (int i = 0; i < 4; i++) wgmma_rs_n64(aB, X + 4 * (4 * kb + i), desc + 512 + i * 128, kb + i != 0);
          wg_commit();
          wg_wait<1>();
          ZSTAMP(1 + ffn, 3 + 3 * kb);
          if (kb > 0) release(prev);
          prev = rg.st; rg.next();
        }
        ZSTAMP(1 + ffn, 28);
        ZSTAMP(4, 0);
        STAMP(ffn * 16 + 2);
      }
      if (!ffn) {
      const uint32_t lane = lane_id(), r = lane >> 2, q = lane & 3;
      const uint32_t kvrow = sb + KVS + (w & 1) * 10368 + (16 * (w >> 1)) * 144;
      uint32_t Q[18], Km[3][8], Ke[3][4];
      const bool edge = (t == 0 && w < 2);
      const uint32_t row0 = edge ? sb + KVS + 8 * 144 : kvrow + (lane & 7) * 144, row1 = kvrow + (8 + (lane & 7)) * 144;
      {
        const uint32_t dst = kvrow + (8 + r) * 144 + q * 4 + odd * 16, dstr = dst + (odd ? -16 : 128);
        const bool edge_out = w >= 6 && t < 15;
        uint4* const hp = scr + TILE + OFF_H + ((layer * 8 + j) * 2 + (w & 1)) * 192 + lane;
        auto put_kv = [&](float (&a)[32], int part, int half) {
          uint32_t hl[4];
#pragma unroll
          for (int i = 0; i < 16; i++) asm volatile("" : "+f"(a[16 * half + i]) :: "memory");
#pragma unroll
          for (int i = 0; i < 4; i++) {
            const int g = 4 * half + i;
            hl[i] = pack_bf16(a[4 * g + 2] * rs1, a[4 * g + 3] * rs1);
            sts1(dst + part * 20736 + g * 16, pack_bf16(a[4 * g] * rs0, a[4 * g + 1] * rs0)); sts1(dst + part * 20736 + 8 * 144 + g * 16, hl[i]);
          }
          if (edge_out) stg4(hp + part * 64 + half * 32, nz(hl[0]), hl[1], hl[2], hl[3]);
        };
        put_kv(aA, 0, 0); put_kv(aA, 0, 1);
        wg_wait<0>();
        release(prev);
        float aR[12];
        mbar_wait(rem_full, layer);
        const uint64_t dr = DESC_REM | ((sd + REM) >> 4);
        wg_fence();
#pragma unroll
        for (int s = 0; s < 36; s++) {
          wgmma_rs_n24(aR, X + 4 * s, dr + s * 16, s != 0);
          if (s == 4) put_kv(aB, 1, 0);
          if (s == 16) put_kv(aB, 1, 1);
        }
        wg_commit();
#pragma unroll
        for (int kb = 0; kb < 9; kb++) {
          if (!(kb & 1)) mbar_wait(full0 + rg.st * 8, rg.ph);
          const uint64_t desc = DESC_HI | ((sd + rg.st * STAGE + (kb & 1) * 8192) >> 4);
          wg_fence();
#pragma unroll
          for (int i = 0; i < 4; i++) wgmma_rs_n64(aB, X + 4 * (4 * kb + i), desc + i * 128, kb + i != 0);
          wg_commit();
          wg_wait<1>();
          if (kb > 0 && !(kb & 1)) release(prev);
          if ((kb & 1) || kb == 8) { prev = rg.st; rg.next(); }
          if (kb == 0) {
            pin(aR);
            const uint32_t k1 = pack_bf16(aR[2] * rs1, aR[3] * rs1), v1 = pack_bf16(aR[6] * rs1, aR[7] * rs1);
            if (edge_out) stg4(hp + 128, nz(k1), v1, 0u, 0u);
            sts1(dstr, pack_bf16(aR[0] * rs0, aR[1] * rs0)); sts1(dstr + 8 * 144, k1);
            sts1(dstr + 20736, pack_bf16(aR[4] * rs0, aR[5] * rs0)); sts1(dstr + 20736 + 8 * 144, v1);
            Q[16] = pack_bf16(aR[8], aR[9]); Q[17] = pack_bf16(aR[10], aR[11]);
            if (w < 4) asm volatile("bar.arrive 2, 256;" ::: "memory");
          }
          if (kb == 8) {
            if (w < 4) asm volatile("bar.sync 1, 192;" ::: "memory");
            else asm volatile("bar.sync 2, 256;" ::: "memory");
#pragma unroll
            for (int nt = 0; nt < 3; nt++) {
              const uint32_t ra = (nt == 0 ? row0 : row1 + (nt - 1) * 8 * 144);
              ldsm4(ra + odd * 16 + (lane >> 3) * 16, Km[nt][0], Km[nt][1], Km[nt][2], Km[nt][3]);
              ldsm4(ra + odd * 16 + 64 + (lane >> 3) * 16, Km[nt][4], Km[nt][5], Km[nt][6], Km[nt][7]);
              ldsm4(ra + (odd ? 0 : 32) + (lane >> 3) * 32, Ke[nt][0], Ke[nt][1], Ke[nt][2], Ke[nt][3]);
            }
            const uint32_t ge = (2u << q) - 1, le = 0xfu << q, on = edge ? 0u : ~0u;
            const uint32_t bits = odd ? 0xfu | ((le & 0xfu) << 4) | (ge << 8) : ge | 0xf0u | (le << 8);
#pragma unroll
            for (int h = 0; h < 4; h++) {
              const uint32_t ma = bitmask(bits, h), mb = bitmask(bits, 4 + h), mc = bitmask(bits, 8 + h);
              Km[0][2 * h] &= ma & on; Km[0][2 * h + 1] &= mb & on; Ke[0][h] &= mc & on;
#pragma unroll
              for (int nt = 1; nt < 3; nt++) { Km[nt][2 * h] &= ma; Km[nt][2 * h + 1] &= mb; Ke[nt][h] &= mc; }
            }
          }
        }
        wg_wait<0>();
        release(prev);
        pin(aB);
        if (VAR == 2 ? w >= 4 : w < 4) asm volatile("bar.sync 4, 256;" ::: "memory");
        STAMP(3);
#pragma unroll
        for (int i = 0; i < 16; i++) Q[i] = pack_bf16(aB[2 * i], aB[2 * i + 1]);
      }
      uint32_t res[18] = {};
      if (layer) {
        const uint4* p = xbase + ((9 * j + 1) >> 1) * 32 + lane;
#pragma unroll
        for (int i = 0; i < 4; i++) ldg4(res + 4 * i, p + i * 32);
        ldg2(res + 16, odd ? (const char*)(p - 32) + 8 : (const char*)(p + 4 * 32));
      }
      {
        uint32_t V01[12][2], V2[12];
        const uint32_t rv = ((lane & 8) ? row1 : row0) + 20736, rw = row1 + 8 * 144 + 20736;
#pragma unroll
        for (int i = 0; i < 4; i++) ldsm4t(rv + odd * 16 + i * 32 + (lane >> 4) * 16, V01[2 * i][0], V01[2 * i][1], V01[2 * i + 1][0], V01[2 * i + 1][1]);
#pragma unroll
        for (int i = 0; i < 2; i++) ldsm4t(rv + (odd ? 0 : 32) + i * 64 + (lane >> 4) * 32, V01[8 + 2 * i][0], V01[8 + 2 * i][1], V01[9 + 2 * i][0], V01[9 + 2 * i][1]);
        ldsm4t(rw + odd * 16 + (lane >> 3) * 16, V2[0], V2[1], V2[2], V2[3]);
        ldsm4t(rw + odd * 16 + 64 + (lane >> 3) * 16, V2[4], V2[5], V2[6], V2[7]);
        ldsm4t(rw + (odd ? 0 : 32) + (lane >> 3) * 32, V2[8], V2[9], V2[10], V2[11]);
        const bool up0 = 2 * q > r, up1 = 2 * q + 1 > r;
        const uint32_t upm = (up0 ? 0xffffu : 0u) | (up1 ? 0xffff0000u : 0u);
        const float c0 = 0.23570226039551584f * 1.4426950408889634f * rs0, c1 = 0.23570226039551584f * 1.4426950408889634f * rs1;
        const float masked = edge ? -1e9f * 1.4426950408889634f * rcp(c0) : 0.f;
        uint32_t Om[16], Oe[8];
        uint4* const po = xbase + 16 * SLAB + 4 * j * 32 + lane;
#pragma unroll
        for (int h = 0; h < 4; h++) {
          const uint32_t e0 = odd ? Q[(4 * h + 16) % 18] : Q[4 * h + 4], e1 = odd ? Q[(4 * h + 17) % 18] : Q[4 * h + 5];
          float S[3][4];
#pragma unroll
          for (int nt = 0; nt < 3; nt++) {
            mma16c(S[nt], Q + 4 * h, Km[nt][2 * h], Km[nt][2 * h + 1], nt == 0 ? masked : 0.f);
            mma8(S[nt], e0, e1, Ke[nt][h]);
          }
          const float s00 = up0 ? S[0][0] : S[1][0], s01 = up1 ? S[0][1] : S[1][1];
          const float s10 = up0 ? S[1][2] : S[2][2], s11 = up1 ? S[1][3] : S[2][3];
          const float m0 = quad_max(fmaxf(s00, s01)) * c0, m1 = quad_max(fmaxf(s10, s11)) * c1;
          const float p00 = ex2(fmaf(s00, c0, -m0)), p01 = ex2(fmaf(s01, c0, -m0)), p10 = ex2(fmaf(s10, c1, -m1)), p11 = ex2(fmaf(s11, c1, -m1));
          const float i0 = rcp(quad_sum(p00 + p01)), i1 = rcp(quad_sum(p10 + p11));
          const uint32_t p0 = pack_bf16(p00 * i0, p01 * i0), p1 = pack_bf16(p10 * i1, p11 * i1);
          const uint32_t pf[4] = {p0 & upm, 0u, p0 & ~upm, p1 & upm};
#pragma unroll
          for (int gi = 0; gi < 3; gi++) {
            const int g = gi < 2 ? 2 * h + gi : 8 + h;
            float o[4];
            mma16c(o, pf, V01[g][0], V01[g][1], 0.f);
            mma8(o, 0u, p1 & ~upm, V2[g]);
            uint32_t* d = gi < 2 ? Om + 2 * g : Oe + 2 * h;
            d[0] = pack_bf16(o[0], o[1]); d[1] = pack_bf16(o[2], o[3]);
          }
          if (h > 0) {
#pragma unroll
            for (int e = 0; e < 2; e++) {
              if (!odd && q < h) Om[4 * h + e] = Oe[2 * h - 2 + e];
              if (odd && q >= h) Om[4 * h - 2 + e] = Oe[2 * h + e];
            }
            stg4(po + (h - 1) * 32, nz(Om[4 * h - 4]), Om[4 * h - 3], Om[4 * h - 2], Om[4 * h - 1]);
            if (h == (VAR == 3 ? 3 : 1) && (VAR == 2 ? w < 4 : w >= 4)) asm volatile("bar.arrive 4, 256;" ::: "memory");
          }
        }
        STAMP(4);
        stg4(po + 96, nz(Om[12]), Om[13], Om[14], Om[15]);
        stg2((char*)(xbase + 16 * SLAB + 1024 + j * 16) + lane * 8, nz(odd ? Oe[0] : Oe[6]), odd ? Oe[1] : Oe[7]);
#pragma unroll
        for (int i = 0; i < 16; i++) X[i] = Om[i];
      }
      if (lane == 0) asm volatile("st.relaxed.gpu.global.b32 [%0], %1;" :: "l"(scr + OFF_S + (8 + w) * 96 + j * 8), "r"(tag) : "memory");
      {
        if (layer == 0) {
          const uint32_t xrow = (w & 1) * 8192 + (16 * (w >> 1) + (lane & 15)) * 128;
          uint32_t u0, u1;
          mbar_wait(xbar0, 1); mbar_wait(xbar0 + 8, 1);
#pragma unroll
          for (int i = 0; i < 5; i++) {
            const uint32_t g = i < 4 ? j + odd + 2 * i : j + (odd ? 0 : 8);
            const uint32_t a = sb + PARK + (g >> 3) * STAGE + xrow;
            if (i < 4) ldsm4(a + ((((g & 7) + (lane >> 4)) ^ (lane & 7)) << 4), res[4 * i], res[4 * i + 1], res[4 * i + 2], res[4 * i + 3]);
            else ldsm4(a + (((g & 7) ^ (lane & 7)) << 4), res[16], res[17], u0, u1);
          }
        }
        const uint4* src = xbase + 16 * SLAB + lane;
        const uint32_t st0 = rg.st;
        auto stage_of = [&](uint32_t i) { const uint32_t x = st0 + i; return x >= NST ? x - NST : x; };
        {
          const uint32_t x = st0 + lane, wrap = x >= NST;
          mbar_wait(lane < 5 ? full0 + (x - wrap * NST) * 8 : remo_full, lane < 5 ? rg.ph ^ wrap : layer);
          __syncwarp();
          if (st0) { rg.st = st0 - 1; rg.ph ^= 1; } else rg.st = 5;
        }
        float acc[36];
        auto block72 = [&](uint32_t kb, uint32_t base, const uint32_t* a) {
          const uint64_t d0 = DESC_HI | ((base >> 4) + (((sd + REM + 27648 + (kb >> 1) * 2048 + (kb & 1) * 64 - base) >> 4) << 16));
          wg_fence();
#pragma unroll
          for (int i = 0; i < 4; i++) wgmma_rs_n72(acc, a + 4 * i, d0 - (uint64_t)(i * ((127u << 16) - 128u)), 1);
          wg_commit();
        };
#pragma unroll
        for (int i = 0; i < 18; i++) { acc[2 * i] = bf_lo(res[i]); acc[2 * i + 1] = bf_hi(res[i]); }
        block72(0, sd + st0 * STAGE, X);
        {
          const uint4* fp = scr + OFF_S + (8 + w) * 96 + (lane & 7) * 8;
          int n = 0;
          STAMP(8);
#pragma unroll 1
          while (true) {
            uint32_t f;
            asm volatile("ld.relaxed.gpu.global.b32 %0, [%1];" : "=r"(f) : "l"(fp) : "memory");
            if (__all_sync(~0u, f == tag)) break;
            SPIN_GUARD(n);
          }
          STAMP(9);
        }
#pragma unroll
        for (int kb = 1; kb < GO; kb++) load_kb(kb, src, (const char*)src - lane * 8, 256);
        __syncwarp();
        uint32_t m = ~0u;
#pragma unroll
        for (int kb = 1; kb < 9; kb++) {
          m = umin2(m, umin2(umin2(X[16 * kb], X[16 * kb + 4]), umin2(X[16 * kb + 8], X[16 * kb + 12])));
          if (kb == 8) m = umin2(m, umin2(umin2(X[130], X[134]), umin2(X[138], X[142])));
          if (kb + GO - 1 < 9) {
            const uint4* s2 = src + (m == 0u);
            load_kb(kb + GO - 1, s2, (const char*)s2 - lane * 8, 256);
            __syncwarp();
          }
          block72(kb, sd + stage_of(kb >> 1) * STAGE + (kb & 1) * 8192, X + 16 * kb);
          if (!(kb & 1)) { wg_wait<1>(); release(stage_of((kb >> 1) - 1)); }
        }
        uint32_t redo;
        asm volatile("{\n.reg .pred p;\nsetp.eq.u32 p, %1, 0;\nbar.red.or.pred p, %2, 128, p;\nselp.u32 %0, 1, 0, p;\n}" : "=r"(redo) : "r"(m), "r"(5 + (w >> 2)) : "memory");
        wg_wait<0>();
        release(stage_of(4));
        pin(acc);
        if (__any_sync(~0u, redo || FORCE_REDO)) {
#pragma unroll
          for (int i = 0; i < 18; i++) { res[i] = __shfl_sync(~0u, res[i], lane); acc[2 * i] = bf_lo(res[i]); acc[2 * i + 1] = bf_hi(res[i]); }
          const uint32_t box = PARK + 2 * STAGE + (w >> 2) * 8192, bar = redo_full + (w >> 2) * 8;
#pragma unroll 1
          for (uint32_t kb = 0; kb < 10; kb++) {
            asm volatile("bar.sync %0, 128;" :: "r"(5 + (w >> 2)) : "memory");
            if ((w & 3) == 0)
              asm volatile("{\n.reg .pred e;\nelect.sync _|e, 0xffffffff;\n@e mbarrier.arrive.expect_tx.shared::cta.b64 _, [%2], 8192;\n"
                           "@e cp.async.bulk.tensor.3d.shared::cluster.global.mbarrier::complete_tx::bytes [%0], [%1, {%3, %4, %5}], [%2];\n}"
                           :: "r"(sb + box), "l"(&maps.m[kb >= 8 ? 8 : 1]), "r"(bar), "r"(72 * j + 8 * odd), "r"(kb >= 8 ? 64 : 0),
                              "r"(kb >= 8 ? 0 : (9 * blk(kb) + 1) >> 1) : "memory");
            mbar_wait(bar, kb & 1);
            if (kb == 9) break;
            int n = 0;
#pragma unroll 1
            while (true) {
              const char* l = (const char*)(src + blk(kb) * 128) - (kb == 8 ? lane * 8 : 0);
#pragma unroll
              for (int i = 0; i < 4; i++) ldg2(X + 4 * i, l + i * 512);
              uint32_t mm = umin2(umin2(X[0], X[4]), umin2(X[8], X[12]));
              l += (kb == 8 ? 256 : 8) + (mm == 0u ? 16 : 0);
#pragma unroll
              for (int i = 0; i < 4; i++) ldg2(X + 4 * i + 2, l + i * 512);
              if (kb == 8) mm = umin2(mm, umin2(umin2(X[2], X[6]), umin2(X[10], X[14])));
              if (__all_sync(~0u, mm != 0u)) break;
              SPIN_GUARD(n);
            }
            block72(kb, sd + box, X);
            wg_wait<0>();
            pin(acc);
          }
        }
        STAMP(10);
#pragma unroll
        for (int i = 0; i < 18; i++) res[i] = pack_bf16(acc[2 * i], acc[2 * i + 1]);
        if (j < PRI) put72(xbase + 32 * SLAB, j, lane, res);
        publish_stats<9>(scr + OFF_S + (16 + w) * 96 + j * 8, acc, tag, lane);
        if (j >= PRI) put72(xbase + 32 * SLAB, j, lane, res);
#pragma unroll
        for (int i = 0; i < 16; i++) X[i] = res[i];
      }
      continue;
      }
      const uint32_t hp = sb + PARK + w * 512 + lane_id() * 16;
      auto pack8 = [&](float (&a)[32], int p, uint32_t* o) {
#pragma unroll
        for (int e = 0; e < 8; e++) asm volatile("" : "+f"(a[8 * p + e]) :: "memory");
#pragma unroll
        for (int e = 0; e < 4; e++) o[e] = pack_bf16(a[8 * p + 2 * e], a[8 * p + 2 * e + 1]);
      };
      const float ka0 = 0.7978845608028654f * rs0, kb0 = 0.044715f * ka0 * rs0 * rs0, ku0 = 0.5f * rs0 * rs0;
      const float ka1 = 0.7978845608028654f * rs1, kb1 = 0.044715f * ka1 * rs1 * rs1, ku1 = 0.5f * rs1 * rs1;
      auto packu8 = [&](int p, uint32_t* o) {
#pragma unroll
        for (int e = 0; e < 8; e++) asm volatile("" : "+f"(aA[8 * p + e]) :: "memory");
#pragma unroll
        for (int e = 0; e < 4; e++) o[e] = pack_bf16(aA[8 * p + 2 * e] * ((e & 1) ? ku1 : ku0), aA[8 * p + 2 * e + 1] * ((e & 1) ? ku1 : ku0));
      };
      auto geglu8 = [&](int p, uint32_t* u) {
#pragma unroll
        for (int e = 0; e < 8; e++) asm volatile("" : "+f"(aB[8 * p + e]) :: "memory");
        float h[8];
#pragma unroll
        for (int e = 0; e < 8; e++) {
          const float g = aB[8 * p + e];
          h[e] = fmaf(g, tanh_ap(g * fmaf(g * g, (e & 2) ? kb1 : kb0, (e & 2) ? ka1 : ka0)), g);
        }
#pragma unroll
        for (int e = 0; e < 4; e++) u[e] = mul_bf16x2(pack_bf16(h[2 * e], h[2 * e + 1]), u[e]);
      };
      uint32_t ready = 0;
      auto box = [&](int b, auto&& filler) {
        const int kb = b < 9 ? b : b - 9;
        if (b == 0) mbar_wait_trap(full0 + rg.st * 8, rg.ph);
        else if (!(b & 1)) mbar_wait_unless(ready, full0 + rg.st * 8, rg.ph);
        const uint64_t desc = DESC_HI | ((sd + rg.st * STAGE + (b & 1) * 8192) >> 4);
        if (b & 1) { prev = rg.st; rg.next(); }
        wg_fence();
#pragma unroll
        for (int i = 0; i < 4; i++) {
          if (b < 9) wgmma_rs_n64(aA, X + 4 * (4 * kb + i), desc + i * 128, kb + i != 0);
          else wgmma_rs_n64(aB, X + 4 * (4 * kb + i), desc + i * 128, kb + i != 0);
          if ((b & 1) && b < 17 && i == 0) ready = mbar_peek(full0 + rg.st * 8, rg.ph);
          if (i == 1) filler();
        }
        wg_commit();
        if (!(b & 1)) { wg_wait<1>(); release(prev); }
      };
      auto nop = [] {};
      auto step = [&](int st, auto&& filler) { box(2 * st, nop); box(2 * st + 1, filler); };
#pragma unroll
      for (int p = 0; p < 4; p++) { uint32_t o[4]; packu8(p, o); sts4(hp + p * 4096, o); }
      box(0, nop);
      if (lead) mbar_arrive(xb_done);
#pragma unroll 1
      for (int c = 1;; c++) {
        const uint32_t hc = hp + c * 4 * 4096;
#pragma unroll
        for (int b = 1; b < 18; b++) box(b, [&] {
          if ((b & 1) && b < 8) { uint32_t o[4]; const uint32_t a = hc - (4 - (b >> 1)) * 4096; lds4(a, o); geglu8(b >> 1, o); sts4(a, o); }
          if ((b & 1) && b > 10) { uint32_t o[4]; packu8((b - 11) >> 1, o); if (c < 8) sts4(hc + ((b - 11) >> 1) * 4096, o); } });
        ZSTAMP(4, c);
        if (c == 8) break;
        box(0, nop);
      }
      wg_wait<0>();
      STAMP(21);
      GSTAMP(19);
      auto unpark = [&](int kb) {
#pragma unroll
        for (int s = 4 * kb; s < 4 * kb + 4; s++) lds4(hp + s * 4096, X + 4 * s);
      };
      unpark(0);
      uint32_t U[16];
#pragma unroll
      for (int p = 0; p < 4; p++) packu8(p, U + 4 * p);
#pragma unroll
      for (int b = 0; b < 8; b++) box(b, [&] {
        if (b < 7) unpark(b + 1);
        if (b & 1) {
          geglu8(b >> 1, U + 2 * (b - 1));
          if (rg.ph > 1) sts4(hp, U + 2 * (b - 1));
#pragma unroll
          for (int i = 0; i < 4; i++) X[128 + 2 * (b - 1) + i] = U[2 * (b - 1) + i];
        } });
      STAMP(24);
      if (layer == 0 && lead) mbar_arrive(park_free);
      const uint32_t lane2 = lane_id();
      uint4* const pw = scr + OFF_P + (j * 8 + w) * SLAB + lane2;
      const uint4* const pr = scr + OFF_P + w * SLAB + 4 * j * 32 + lane2;
      auto put_part = [&](float (&a)[32], int p, uint32_t chunk) {
        uint32_t o[4];
        pack8(a, p, o);
        stg4(pw + (chunk * 4 + p) * 32, (o[0] & ~1u) | tag, o[1], o[2], o[3]);
      };
      auto slot = [&](int p) { return sb + w * 2048 + (p < 3 ? PARK + p * 16384 : KVS + (p - 3) * 16384); };
      auto fetch = [&](int p) {
        bulk_load(slot(p), scr + OFF_P + (((j - p) & 7) * 8 + w) * SLAB + 4 * j * 32, 2048, pbar0 + w * 8, true);
      };
#pragma unroll 1
      for (int sp = 0;; sp++) {
        const uint32_t ca = sp == 0 ? 8 : ((j + 2 * sp) & 7), cb = (j + 2 * sp + 1) & 7;
        if (sp == 1 && lead) mbar_arrive(c8_go);
#pragma unroll
        for (int st = 4; st < 9; st++) step(st, [&] {
          if (st == 5 || st == 6) { put_part(aA, 2 * (st - 5), ca); put_part(aA, 2 * (st - 5) + 1, ca); }
          if (st == 8 && sp > 1) { if (sp == 3) mbar_wait(c8_done, layer); fetch(2 * sp - 2); } });
        STAMP(25 + sp);
        if (sp == 3) break;
#pragma unroll
        for (int st = 0; st < 4; st++) step(st, [&] {
          if (st < 2) { put_part(aB, 2 * st, cb); put_part(aB, 2 * st + 1, cb); }
          if (st == 3 && sp > 0) fetch(2 * sp - 1); });
      }
      auto load_p = [&](int p, uint32_t* d) {
#pragma unroll
        for (int i = 0; i < 4; i++) ldg4(d + 4 * i, pr + ((j - p) & 7) * 8 * SLAB + i * 32);
      };
#pragma unroll
      for (int b = 0; b < 9; b++) {
        box(b, [&] {
          if (b == 1) {
#pragma unroll
            for (int p = 0; p < 4; p++) put_part(aB, p, (j + 7) & 7);
          }
          if (b == 3) { load_p(5, X); load_p(6, X + 16); }
          if (b == 7) load_p(7, X + 32); });
      }
      mbar_wait(res_full, layer);
      mbar_wait(pbar0 + w * 8, layer);
#pragma unroll
      for (int p = 1; p < 5; p++)
#pragma unroll
        for (int i = 0; i < 4; i++) lds4(slot(p) + lane2 * 16 + i * 512, X + 48 + 16 * p + 4 * i);
#pragma unroll
      for (int i = 0; i < 4; i++) {
        const bool split = j == 2 * i + 1;
        const uint32_t a = slot(0) + i * 512 + (split ? lane2 * 8 : lane2 * 16);
        lds2(a, X + 48 + 4 * i); lds2(a + (split ? 256 : 8), X + 50 + 4 * i);
      }
      wg_wait<0>();
      release(rg.st); rg.next();
      pin(aA);
      STAMP(22);
      GSTAMP(20);
      {
        const uint32_t lane = lane2, r = lane >> 2, q = lane & 3;
        const uint32_t eye = r == 2 * q ? 0x3f80u : r == 2 * q + 1 ? 0x3f800000u : 0u;
        auto bad = [&](const uint32_t* d) { return diff2(d[0], d[4], tag) | diff2(d[8], d[12], tag); };
        auto add = [&](const uint32_t* d) {
#pragma unroll
          for (int g = 0; g < 8; g++) mma8(aA + 4 * g, d[2 * g], d[2 * g + 1], eye);
        };
        int n = 0;
#pragma unroll 1
        while (!__all_sync(~0u, ((or3(bad(X), bad(X + 16), bad(X + 64)) | or3(bad(X + 80), bad(X + 96), bad(X + 112))) & 1u) == 0u)) {
          SPIN_GUARD(n);
          load_p(5, X); load_p(6, X + 16);
#pragma unroll
          for (int p = 1; p < 5; p++) load_p(p, X + 48 + 16 * p);
        }
        add(X); add(X + 16);
#pragma unroll
        for (int p = 4; p >= 0; p--) add(X + 48 + 16 * ((p + 1) % 5));
        STAMP(11);
#pragma unroll 1
        while (!__all_sync(~0u, (bad(X + 32) & 1u) == 0u)) { SPIN_GUARD(n); load_p(7, X + 32); }
        add(X + 32);
        STAMP(12);
        uint32_t res[16];
#pragma unroll
        for (int i = 0; i < 16; i++) X[i] = res[i] = pack_bf16(aA[2 * i], aA[2 * i + 1]);
        if (layer == 0) {
          uint4* p = xbase + 8 * SLAB + 4 * j * 32 + lane;
          auto put = [&] {
#pragma unroll
            for (int i = 0; i < 4; i++) stg4(p + i * 32, nz(res[4 * i]), res[4 * i + 1], res[4 * i + 2], res[4 * i + 3]);
          };
          if (j < PRI) put();
          publish_stats<8>(scr + OFF_S + w * 96 + j * 8, aA, 1u, lane);
          if (j >= PRI) put();
          if (lane == 0) mbar_arrive(kv_free);
        } else {
          const uint32_t tb = slot(0);
          __syncwarp();
#pragma unroll
          for (int i = 0; i < 4; i++) {
            const uint32_t row = (lane2 & 7) + (lane2 & 8), g = 2 * i + (lane2 >> 4);
            asm volatile("stmatrix.sync.aligned.m8n8.x4.shared.b16 [%0], {%1,%2,%3,%4};"
                         :: "r"(tb + row * 128 + ((g ^ (row & 7)) << 4)), "r"(res[4 * i]), "r"(res[4 * i + 1]), "r"(res[4 * i + 2]), "r"(res[4 * i + 3]) : "memory");
          }
          __syncwarp();
#pragma unroll
          for (int i = 0; i < 4; i++) {
            const uint32_t row = 4 * i + (lane2 >> 3), g = lane2 & 7;
            uint32_t v[4];
            lds4(tb + row * 128 + ((g ^ (row & 7)) << 4), v);
            *(uint4*)(out + (128 * t + 32 * (w >> 1) + 2 * row + (w & 1)) * 576 + 64 * j + 8 * g) = make_uint4(v[0], v[1], v[2], v[3]);
          }
        }
      }
      STAMP(23);
    }
  }
}

typedef CUresult (*EncodeFn)(CUtensorMap*, CUtensorMapDataType, cuuint32_t, void*, const cuuint64_t*, const cuuint64_t*,
                             const cuuint32_t*, const cuuint32_t*, CUtensorMapInterleave, CUtensorMapSwizzle,
                             CUtensorMapL2promotion, CUtensorMapFloatOOBfill);

CUtensorMap make_map(EncodeFn f, const void* p, uint64_t cols, uint64_t rows, uint64_t grp) {
  CUtensorMap m;
  cuuint64_t dims[3] = {cols, grp, rows / grp}, str[2] = {cols * 2, cols * 2 * grp};
  cuuint32_t box[3] = {64, 16, 4}, es[3] = {1, 1, 1};
  f(&m, CU_TENSOR_MAP_DATA_TYPE_BFLOAT16, 3, const_cast<void*>(p), dims, str, box, es, CU_TENSOR_MAP_INTERLEAVE_NONE,
    CU_TENSOR_MAP_SWIZZLE_128B, CU_TENSOR_MAP_L2_PROMOTION_NONE, CU_TENSOR_MAP_FLOAT_OOB_FILL_NONE);
  return m;
}
CUtensorMap make_rem_map(EncodeFn f, const void* p, uint64_t cols) {
  CUtensorMap m;
  cuuint64_t dims[2] = {cols, 576}, str[1] = {cols * 2};
  cuuint32_t box[2] = {8, 144}, es[2] = {1, 1};
  f(&m, CU_TENSOR_MAP_DATA_TYPE_BFLOAT16, 2, const_cast<void*>(p), dims, str, box, es, CU_TENSOR_MAP_INTERLEAVE_NONE,
    CU_TENSOR_MAP_SWIZZLE_NONE, CU_TENSOR_MAP_L2_PROMOTION_NONE, CU_TENSOR_MAP_FLOAT_OOB_FILL_NONE);
  return m;
}

}

extern "C" void kernel_launch(void* const* d_in, const int* in_sizes, int n_in, void* d_out, int out_size) {
  void* fn = nullptr;
  cudaDriverEntryPointQueryResult qr;
  cudaGetDriverEntryPoint("cuTensorMapEncodeTiled", &fn, cudaEnableDefault, &qr);
  EncodeFn enc = (EncodeFn)fn;
  Maps maps;
  maps.m[0] = make_map(enc, d_in[1], 1728, 576, 16); maps.m[1] = make_map(enc, d_in[2], 576, 576, 16);
  maps.m[2] = make_map(enc, d_in[4], 4608, 576, 16); maps.m[3] = make_map(enc, d_in[5], 4608, 576, 16);
  maps.m[4] = make_map(enc, d_in[6], 576, 4608, 16);
  maps.m[5] = make_rem_map(enc, d_in[1], 1728); maps.m[6] = make_rem_map(enc, d_in[2], 576);
  maps.m[8] = make_map(enc, d_in[2], 576, 576, 144); maps.m[9] = make_map(enc, d_in[4], 4608, 576, 144);
  maps.m[10] = make_map(enc, d_in[5], 4608, 576, 144);
  {
    cuuint64_t dims[3] = {576, 1024, 2}, str[2] = {2304, 1152};
    cuuint32_t box[3] = {64, 64, 2}, es[3] = {1, 1, 1};
    enc(&maps.m[7], CU_TENSOR_MAP_DATA_TYPE_BFLOAT16, 3, d_in[0], dims, str, box, es, CU_TENSOR_MAP_INTERLEAVE_NONE,
        CU_TENSOR_MAP_SWIZZLE_128B, CU_TENSOR_MAP_L2_PROMOTION_NONE, CU_TENSOR_MAP_FLOAT_OOB_FILL_NONE);
  }
  void* scr = nullptr;
  cudaGetSymbolAddress(&scr, g_scratch);
  cudaFuncSetAttribute(mega_kernel, cudaFuncAttributeMaxDynamicSharedMemorySize, SMEM_BYTES);
  cudaLaunchConfig_t cfg = {};
  cfg.gridDim = dim3(128); cfg.blockDim = dim3(384); cfg.dynamicSmemBytes = SMEM_BYTES; cfg.stream = cudaStreamPerThread;
  cudaLaunchAttribute at[1];
  at[0].id = cudaLaunchAttributeClusterDimension; at[0].val.clusterDim.x = 2; at[0].val.clusterDim.y = 1; at[0].val.clusterDim.z = 1;
  cfg.attrs = at; cfg.numAttrs = 1;
  int dev = 0, sms = 0, clusters = 0;
  cudaGetDevice(&dev);
  cudaDeviceGetAttribute(&sms, cudaDevAttrMultiProcessorCount, dev);
  cudaOccupancyMaxActiveClusters(&clusters, mega_kernel, &cfg);
  if (sms == 132 && clusters == 66) cfg.gridDim = dim3(132);
  cudaLaunchKernelEx(&cfg, mega_kernel, maps, (uint4*)scr, (__nv_bfloat16*)d_out);
}
```

```cpp
#include <cuda_runtime.h>
#include <cuda.h>
#include <cuda_bf16.h>
#include <stdint.h>

#define TRACE 0
#define GUARD 0
#define FORCE_REDO 0
#define ZT 0

namespace {

constexpr int NST = 6;
constexpr int STAGE = 16384;
constexpr int PARK = NST * STAGE;
constexpr int REM = PARK + 49152;
constexpr int KVS = REM + 40960;
constexpr int PIECE = PARK + 7 * STAGE;
constexpr int HSTG = KVS + 16384;
constexpr int BARS = KVS + 41472;
constexpr int TRC = BARS + 512;
constexpr int SMEM_BYTES = TRC + (TRACE ? 512 : 0);
static_assert(NST == 6, "the producer addresses empty barriers as full + 48");
static_assert(BARS >= PARK + 131072, "barriers overlap park");
static_assert(SMEM_BYTES <= 232448, "smem");

constexpr int SLAB = 36 * 32;
constexpr int SPIN_MAX = 1 << 17;
constexpr uint32_t PRI = 4;
constexpr int GD = 3, GO = 5;
constexpr int OFF_S = 0;
constexpr int OFF_H = OFF_S + 3 * 8 * 96;
constexpr int OFF_X = OFF_H + 2 * 8 * 384;
constexpr int OFF_P = OFF_X + 6 * 8 * SLAB;
constexpr int TILE = OFF_P + 8 * 8 * SLAB;
constexpr int OFF_R = 16 * TILE;
constexpr int OFF_F = OFF_R + 8 * 2304;
constexpr int SCRATCH = OFF_F + 128 * 8;

}

__device__ uint4 g_scratch[SCRATCH];

namespace {

constexpr uint64_t DESC_HI = 0x4000004000000000ull;
constexpr uint64_t DESC_REM = (576ull << 32) | (8u << 16);
__device__ __forceinline__ void wgmma_rs_n64(float (&d)[32], const uint32_t* a, uint64_t desc, int scale_d) {
  asm volatile("{\n.reg .pred p;\nsetp.ne.b32 p, %37, 0;\n"
    "wgmma.mma_async.sync.aligned.m64n64k16.f32.bf16.bf16 "
    "{%0, %1, %2, %3, %4, %5, %6, %7, %8, %9, %10, %11, %12, %13, %14, %15, %16, %17, %18, %19, %20, %21, %22, %23, %24, %25, %26, %27, %28, %29, %30, %31}, "
    "{%32, %33, %34, %35}, %36, p, 1, 1, 1;\n}\n"
    : "+f"(d[0]), "+f"(d[1]), "+f"(d[2]), "+f"(d[3]), "+f"(d[4]), "+f"(d[5]), "+f"(d[6]), "+f"(d[7]), "+f"(d[8]), "+f"(d[9]), "+f"(d[10]), "+f"(d[11]), "+f"(d[12]), "+f"(d[13]), "+f"(d[14]), "+f"(d[15]), "+f"(d[16]), "+f"(d[17]), "+f"(d[18]), "+f"(d[19]), "+f"(d[20]), "+f"(d[21]), "+f"(d[22]), "+f"(d[23]), "+f"(d[24]), "+f"(d[25]), "+f"(d[26]), "+f"(d[27]), "+f"(d[28]), "+f"(d[29]), "+f"(d[30]), "+f"(d[31])
    : "r"(a[0]), "r"(a[1]), "r"(a[2]), "r"(a[3]), "l"(desc), "r"(scale_d));
}
__device__ __forceinline__ void wgmma_rs_n72(float (&d)[36], const uint32_t* a, uint64_t desc, int scale_d) {
  asm volatile("{\n.reg .pred p;\nsetp.ne.b32 p, %41, 0;\n"
    "wgmma.mma_async.sync.aligned.m64n72k16.f32.bf16.bf16 "
    "{%0, %1, %2, %3, %4, %5, %6, %7, %8, %9, %10, %11, %12, %13, %14, %15, %16, %17, %18, %19, %20, %21, %22, %23, %24, %25, %26, %27, %28, %29, %30, %31, %32, %33, %34, %35}, "
    "{%36, %37, %38, %39}, %40, p, 1, 1, 1;\n}\n"
    : "+f"(d[0]), "+f"(d[1]), "+f"(d[2]), "+f"(d[3]), "+f"(d[4]), "+f"(d[5]), "+f"(d[6]), "+f"(d[7]), "+f"(d[8]), "+f"(d[9]), "+f"(d[10]), "+f"(d[11]), "+f"(d[12]), "+f"(d[13]), "+f"(d[14]), "+f"(d[15]), "+f"(d[16]), "+f"(d[17]), "+f"(d[18]), "+f"(d[19]), "+f"(d[20]), "+f"(d[21]), "+f"(d[22]), "+f"(d[23]), "+f"(d[24]), "+f"(d[25]), "+f"(d[26]), "+f"(d[27]), "+f"(d[28]), "+f"(d[29]), "+f"(d[30]), "+f"(d[31]), "+f"(d[32]), "+f"(d[33]), "+f"(d[34]), "+f"(d[35])
    : "r"(a[0]), "r"(a[1]), "r"(a[2]), "r"(a[3]), "l"(desc), "r"(scale_d));
}
__device__ __forceinline__ void wgmma_rs_n24(float (&d)[12], const uint32_t* a, uint64_t desc, int scale_d) {
  asm volatile("{\n.reg .pred p;\nsetp.ne.b32 p, %17, 0;\n"
    "wgmma.mma_async.sync.aligned.m64n24k16.f32.bf16.bf16 "
    "{%0, %1, %2, %3, %4, %5, %6, %7, %8, %9, %10, %11}, "
    "{%12, %13, %14, %15}, %16, p, 1, 1, 1;\n}\n"
    : "+f"(d[0]), "+f"(d[1]), "+f"(d[2]), "+f"(d[3]), "+f"(d[4]), "+f"(d[5]), "+f"(d[6]), "+f"(d[7]), "+f"(d[8]), "+f"(d[9]), "+f"(d[10]), "+f"(d[11])
    : "r"(a[0]), "r"(a[1]), "r"(a[2]), "r"(a[3]), "l"(desc), "r"(scale_d));
}

__device__ __forceinline__ void mbar_init(uint32_t a, uint32_t c) { asm volatile("mbarrier.init.shared::cta.b64 [%0], %1;" :: "r"(a), "r"(c)); }
__device__ __forceinline__ void mbar_arrive(uint32_t a) { asm volatile("mbarrier.arrive.shared::cta.b64 _, [%0];" :: "r"(a) : "memory"); }
__device__ __forceinline__ void mbar_wait_trap(uint32_t a, uint32_t ph) {
  asm volatile("{\n.reg .pred p;\n.reg .u32 n;\nmov.u32 n, 0;\n"
               "W: mbarrier.try_wait.parity.shared::cta.b64 p, [%0], %1;\n@p bra D;\n"
               "add.u32 n, n, 1;\nsetp.lt.u32 p, n, 4194304;\n@p bra W;\ntrap;\nD:\n}" :: "r"(a), "r"(ph) : "memory");
}
__device__ __forceinline__ void mbar_wait(uint32_t a, uint32_t ph) {
  asm volatile("{\n.reg .pred p;\nW: mbarrier.try_wait.parity.shared::cta.b64 p, [%0], %1;\n@!p bra W;\n}" :: "r"(a), "r"(ph) : "memory");
}
__device__ __forceinline__ uint32_t mbar_peek(uint32_t a, uint32_t ph) {
  uint32_t r;
  asm volatile("{\n.reg .pred p;\nmbarrier.test_wait.parity.shared::cta.b64 p, [%1], %2;\nselp.u32 %0, 1, 0, p;\n}" : "=r"(r) : "r"(a), "r"(ph) : "memory");
  return r;
}
__device__ __forceinline__ void mbar_wait_unless(uint32_t ready, uint32_t a, uint32_t ph) {
  asm volatile("{\n.reg .pred p;\nsetp.ne.u32 p, %2, 0;\n@p bra D;\nW: mbarrier.try_wait.parity.shared::cta.b64 p, [%0], %1;\n@!p bra W;\nD:\n}"
               :: "r"(a), "r"(ph), "r"(ready) : "memory");
}
__device__ __forceinline__ void mbar_wait_sleep(uint32_t a, uint32_t ph) {
  asm volatile("{\n.reg .pred p;\nW: mbarrier.test_wait.parity.shared::cta.b64 p, [%0], %1;\n@p bra D;\nnanosleep.u32 500;\nbra W;\nD:\n}" :: "r"(a), "r"(ph) : "memory");
}
__device__ __forceinline__ void wg_fence() { asm volatile("wgmma.fence.sync.aligned;" ::: "memory"); }
__device__ __forceinline__ void wg_commit() { asm volatile("wgmma.commit_group.sync.aligned;" ::: "memory"); }
template <int N> __device__ __forceinline__ void wg_wait() { asm volatile("wgmma.wait_group.sync.aligned %0;" :: "n"(N) : "memory"); }
__device__ __forceinline__ float tanh_ap(float x) { float y; asm("tanh.approx.f32 %0, %1;" : "=f"(y) : "f"(x)); return y; }
__device__ __forceinline__ float ex2(float x) { float y; asm("ex2.approx.ftz.f32 %0, %1;" : "=f"(y) : "f"(x)); return y; }
__device__ __forceinline__ uint32_t pack_bf16(float lo, float hi) { uint32_t r; asm("cvt.rn.bf16x2.f32 %0, %1, %2;" : "=r"(r) : "f"(hi), "f"(lo)); return r; }
__device__ __forceinline__ float bf_lo(uint32_t v) { return __uint_as_float(v << 16); }
__device__ __forceinline__ float bf_hi(uint32_t v) { return __uint_as_float(v & 0xffff0000u); }
__device__ __forceinline__ uint32_t sub_bf16x2(uint32_t a, uint32_t b) { uint32_t r; asm("sub.rn.bf16x2 %0, %1, %2;" : "=r"(r) : "r"(a), "r"(b)); return r; }
__device__ __forceinline__ uint32_t mul_bf16x2(uint32_t a, uint32_t b) { uint32_t r; asm("mul.rn.bf16x2 %0, %1, %2;" : "=r"(r) : "r"(a), "r"(b)); return r; }
__device__ __forceinline__ uint32_t diff2(uint32_t a, uint32_t b, uint32_t t) { uint32_t r; asm("lop3.b32 %0, %1, %2, %3, 0x7e;" : "=r"(r) : "r"(a), "r"(b), "r"(t)); return r; }
__device__ __forceinline__ uint32_t or3(uint32_t a, uint32_t b, uint32_t c) { uint32_t r; asm("lop3.b32 %0, %1, %2, %3, 0xfe;" : "=r"(r) : "r"(a), "r"(b), "r"(c)); return r; }
__device__ __forceinline__ uint32_t umin2(uint32_t a, uint32_t b) { uint32_t r; asm("min.u32 %0, %1, %2;" : "=r"(r) : "r"(a), "r"(b)); return r; }
__device__ __forceinline__ uint32_t bitmask(uint32_t v, int bit) { uint32_t r; asm("bfe.s32 %0, %1, %2, 1;" : "=r"(r) : "r"(v), "r"(bit)); return r; }
__device__ __forceinline__ uint32_t nz(uint32_t w) { return w == 0u ? 0x8000u : w; }

__device__ __forceinline__ void ldg4(uint32_t* d, const uint4* p) {
  asm volatile("ld.relaxed.gpu.global.v4.b32 {%0,%1,%2,%3}, [%4];" : "=r"(d[0]), "=r"(d[1]), "=r"(d[2]), "=r"(d[3]) : "l"(p) : "memory");
}
__device__ __forceinline__ void ldg2(uint32_t* d, const void* p) {
  asm volatile("ld.relaxed.gpu.global.v2.b32 {%0,%1}, [%2];" : "=r"(d[0]), "=r"(d[1]) : "l"(p) : "memory");
}
__device__ __forceinline__ void stg4(uint4* p, uint32_t a, uint32_t b, uint32_t c, uint32_t d) {
  asm volatile("st.relaxed.gpu.global.v4.b32 [%0], {%1,%2,%3,%4};" :: "l"(p), "r"(a), "r"(b), "r"(c), "r"(d) : "memory");
}
__device__ __forceinline__ void stg2(void* p, uint32_t a, uint32_t b) {
  asm volatile("st.relaxed.gpu.global.v2.b32 [%0], {%1,%2};" :: "l"(p), "r"(a), "r"(b) : "memory");
}
__device__ __forceinline__ void sts4(uint32_t a, const uint32_t* o) { asm volatile("st.shared.v4.b32 [%0], {%1,%2,%3,%4};" :: "r"(a), "r"(o[0]), "r"(o[1]), "r"(o[2]), "r"(o[3]) : "memory"); }
__device__ __forceinline__ void lds4(uint32_t a, uint32_t* o) { asm volatile("ld.shared.v4.b32 {%0,%1,%2,%3}, [%4];" : "=r"(o[0]), "=r"(o[1]), "=r"(o[2]), "=r"(o[3]) : "r"(a) : "memory"); }
__device__ __forceinline__ void lds2(uint32_t a, uint32_t* o) { asm volatile("ld.shared.v2.b32 {%0,%1}, [%2];" : "=r"(o[0]), "=r"(o[1]) : "r"(a) : "memory"); }
__device__ __forceinline__ float rcp(float x) { float y; asm("rcp.approx.ftz.f32 %0, %1;" : "=f"(y) : "f"(x)); return y; }
__device__ __forceinline__ void sts1(uint32_t a, uint32_t v) { asm volatile("st.shared.b32 [%0], %1;" :: "r"(a), "r"(v) : "memory"); }
__device__ __forceinline__ void ldsm4(uint32_t a, uint32_t& r0, uint32_t& r1, uint32_t& r2, uint32_t& r3) {
  asm volatile("ldmatrix.sync.aligned.m8n8.x4.shared.b16 {%0,%1,%2,%3}, [%4];" : "=r"(r0), "=r"(r1), "=r"(r2), "=r"(r3) : "r"(a) : "memory");
}
__device__ __forceinline__ void ldsm4t(uint32_t a, uint32_t& r0, uint32_t& r1, uint32_t& r2, uint32_t& r3) {
  asm volatile("ldmatrix.sync.aligned.m8n8.x4.trans.shared.b16 {%0,%1,%2,%3}, [%4];" : "=r"(r0), "=r"(r1), "=r"(r2), "=r"(r3) : "r"(a) : "memory");
}
__device__ __forceinline__ void mma16(float* c, uint32_t a0, uint32_t a1, uint32_t a2, uint32_t a3, uint32_t b0, uint32_t b1) {
  asm("mma.sync.aligned.m16n8k16.row.col.f32.bf16.bf16.f32 {%0,%1,%2,%3}, {%4,%5,%6,%7}, {%8,%9}, {%0,%1,%2,%3};"
    : "+f"(c[0]), "+f"(c[1]), "+f"(c[2]), "+f"(c[3]) : "r"(a0), "r"(a1), "r"(a2), "r"(a3), "r"(b0), "r"(b1));
}
__device__ __forceinline__ void mma16c(float* d, const uint32_t* a, uint32_t b0, uint32_t b1, float c01) {
  asm("mma.sync.aligned.m16n8k16.row.col.f32.bf16.bf16.f32 {%0,%1,%2,%3}, {%4,%5,%6,%7}, {%8,%9}, {%10,%10,%10,%10};"
    : "=f"(d[0]), "=f"(d[1]), "=f"(d[2]), "=f"(d[3]) : "r"(a[0]), "r"(a[1]), "r"(a[2]), "r"(a[3]), "r"(b0), "r"(b1), "f"(c01));
}
__device__ __forceinline__ void mma8(float* c, uint32_t a0, uint32_t a1, uint32_t b0) {
  asm("mma.sync.aligned.m16n8k8.row.col.f32.bf16.bf16.f32 {%0,%1,%2,%3}, {%4,%5}, {%6}, {%0,%1,%2,%3};"
    : "+f"(c[0]), "+f"(c[1]), "+f"(c[2]), "+f"(c[3]) : "r"(a0), "r"(a1), "r"(b0));
}
__device__ __forceinline__ uint32_t lane_id() { uint32_t l; asm volatile("mov.u32 %0, %%laneid;" : "=r"(l)); return l; }
__device__ __forceinline__ float quad_sum(float v) { v += __shfl_xor_sync(~0u, v, 1); v += __shfl_xor_sync(~0u, v, 2); return v; }
__device__ __forceinline__ float quad_max(float v) { v = fmaxf(v, __shfl_xor_sync(~0u, v, 1)); v = fmaxf(v, __shfl_xor_sync(~0u, v, 2)); return v; }
template <int N> __device__ __forceinline__ void pin(float (&d)[N]) {
#pragma unroll
  for (int i = 0; i < N; i++) asm volatile("" : "+f"(d[i]) :: "memory");
}
#define SPIN_GUARD(n) if (++(n) > SPIN_MAX) break

template <int NG> __device__ __forceinline__ void publish_stats(uint4* dst, const float* y, uint32_t tag, uint32_t lane) {
  float s0 = 0.f, s1 = 0.f;
#pragma unroll
  for (int g = 0; g < NG; g++) { s0 += y[4 * g] + y[4 * g + 1]; s1 += y[4 * g + 2] + y[4 * g + 3]; }
  s0 = quad_sum(s0); s1 = quad_sum(s1);
  const float m0 = s0 * (1.f / (8 * NG)), m1 = s1 * (1.f / (8 * NG));
  float q0 = 0.f, q1 = 0.f, q2 = 0.f, q3 = 0.f;
#pragma unroll
  for (int g = 0; g < NG; g++) {
    const float a = y[4 * g] - m0, b = y[4 * g + 1] - m0, c = y[4 * g + 2] - m1, d = y[4 * g + 3] - m1;
    q0 = fmaf(a, a, q0); q1 = fmaf(b, b, q1); q2 = fmaf(c, c, q2); q3 = fmaf(d, d, q3);
  }
  q0 = quad_sum(q0 + q1); q2 = quad_sum(q2 + q3);
  if ((lane & 3) == 0)
    stg4(dst + (lane >> 2), (__float_as_uint(s0) & ~1u) | tag, __float_as_uint(q0), __float_as_uint(s1), __float_as_uint(q2));
}

__device__ __forceinline__ void put72(uint4* slab, uint32_t j, uint32_t lane, const uint32_t* v) {
#pragma unroll
  for (int i = 0; i < 4; i++) stg4(slab + (4 * j + i) * 32 + lane, nz(v[4 * i]), v[4 * i + 1], v[4 * i + 2], v[4 * i + 3]);
  stg2((char*)(slab + 1024 + j * 16) + lane * 8, nz(v[16]), v[17]);
}
__device__ __forceinline__ uint32_t row72(uint32_t k) { return k % 9 == 4 ? 32 + k / 9 : k - (k + 4) / 9; }
__device__ __forceinline__ void zero_share(uint4* slab, uint32_t j, uint32_t lane) {
  uint4* p = slab + j * 144 + lane;
#pragma unroll
  for (int i = 0; i < 4; i++) stg4(p + i * 32, 0u, 0u, 0u, 0u);
  if (lane < 16) stg4(p + 128, 0u, 0u, 0u, 0u);
}

struct Maps { CUtensorMap m[11]; };

struct Ring {
  uint32_t st, ph;
  __device__ __forceinline__ void next() { if (++st == NST) { st = 0; ph ^= 1; } }
};

#define GSTAMP(i) do {} while (0)
#define STAMP(i) do {} while (0)
#define ZSTAMP(m, i) do {} while (0)

__device__ __forceinline__ void tma_box(uint32_t dst, const CUtensorMap* m, int col, int row, uint32_t bar, uint32_t expect) {
  asm volatile("{\n.reg .pred e, h;\nelect.sync _|e, 0xffffffff;\nsetp.ne.and.u32 h, %5, 0, e;\n"
               "@h mbarrier.arrive.expect_tx.shared::cta.b64 _, [%2], %5;\n"
               "@e cp.async.bulk.tensor.2d.shared::cluster.global.mbarrier::complete_tx::bytes [%0], [%1, {%3, %4}], [%2];\n}"
               :: "r"(dst), "l"(m), "r"(bar), "r"(col), "r"(row), "r"(expect) : "memory");
}

__device__ __forceinline__ void bulk_load(uint32_t dst, const void* src, uint32_t bytes, uint32_t bar, bool arm) {
  asm volatile("{\n.reg .pred e, h;\nelect.sync _|e, 0xffffffff;\nsetp.ne.and.u32 h, %4, 0, e;\n"
               "@h mbarrier.arrive.expect_tx.shared::cta.b64 _, [%3], %2;\n"
               "@e cp.async.bulk.shared::cluster.global.mbarrier::complete_tx::bytes [%0], [%1], %2, [%3];\n}"
               :: "r"(dst), "l"(src), "r"(bytes), "r"(bar), "r"((uint32_t)arm) : "memory");
}

__global__ void __launch_bounds__(384, 1) mega_kernel(
    const __grid_constant__ Maps maps, uint4* __restrict__ scratch,
    __nv_bfloat16* __restrict__ out) {
  extern __shared__ __align__(1024) uint8_t smem[];
  const uint32_t sb = (uint32_t)__cvta_generic_to_shared(smem);
  const uint32_t full0 = sb + BARS, empty0 = full0 + 8 * NST, rem_full = empty0 + 8 * NST, park_free = rem_full + 8, kv_free = park_free + 8;
  const uint32_t c8_go = kv_free + 8, c8_done = c8_go + 8, c8_full = c8_done + 8, remo_full = c8_full + 8, piece_full = remo_full + 8, xb_done = piece_full + 8, res_full = xb_done + 8, pbar0 = res_full + 8;
  const uint32_t x_done = pbar0 + 64, x_ring = x_done + 8, xbar0 = x_ring + 8, redo_full = xbar0 + 72;
  const uint32_t w = __shfl_sync(~0u, threadIdx.x >> 5, 0);
  uint32_t pair = blockIdx.x >> 1;
  if (gridDim.x == 132) {
    uint32_t smid;
    asm("mov.u32 %0, %%smid;" : "=r"(smid));
    const uint32_t tpc = smid >> 1;
    if (tpc == 60 || tpc == 61) { if (threadIdx.x == 0) { __nanosleep(20000); } return; }
    pair = tpc < 32 ? tpc : tpc >= 62 ? (tpc - 58) * 8 : 33 + (tpc - 32) / 7 * 8 + (tpc - 32) % 7;
  }
  const uint32_t rank = blockIdx.x & 1, t = (pair & 7) * 2 + rank, j = pair >> 3;
  const uint32_t sd = sb & 0x3ffff;
  const uint32_t odd = j & 1;
  uint4* const scr = scratch + t * TILE;
  auto blk = [&](uint32_t kb) { return kb == 0 ? j : kb - (kb <= j); };
  const uint32_t xs = sb + (NST - 2) * STAGE;
  auto fetch_x = [&](uint32_t dst, uint32_t b, uint32_t bar) {
    asm volatile("{\n.reg .pred e;\nelect.sync _|e, 0xffffffff;\n@e mbarrier.arrive.expect_tx.shared::cta.b64 _, [%2], 16384;\n"
                 "@e cp.async.bulk.tensor.3d.shared::cluster.global.mbarrier::complete_tx::bytes [%0], [%1, {%3, %4, 0}], [%2];\n}"
                 :: "r"(dst), "l"(&maps.m[7]), "r"(bar), "r"(64 * b), "r"(64 * t) : "memory");
  };
  if (threadIdx.x == 256) {
    for (int i = 0; i < 9; i++) mbar_init(xbar0 + 8 * i, 1);
    mbar_init(piece_full, 1);
    asm volatile("fence.mbarrier_init.release.cluster;" ::: "memory");
  }
  if (threadIdx.x == 288) {
    for (int i = 0; i < NST; i++) { mbar_init(full0 + 8 * i, 1); mbar_init(empty0 + 8 * i, 16); }
    mbar_init(x_done, 8); mbar_init(x_ring, 16); mbar_init(redo_full, 1); mbar_init(redo_full + 8, 1);
    asm volatile("fence.mbarrier_init.release.cluster;" ::: "memory");
  }
  if (threadIdx.x == 320) {
    mbar_init(rem_full, 2); mbar_init(park_free, 8); mbar_init(kv_free, 8); mbar_init(c8_go, 8); mbar_init(c8_done, 2); mbar_init(c8_full, 1);
    mbar_init(remo_full, 64); mbar_init(xb_done, 8); mbar_init(res_full, 32);
    for (int i = 0; i < 8; i++) mbar_init(pbar0 + 8 * i, 4);
    asm volatile("fence.mbarrier_init.release.cluster;" ::: "memory");
  }
  if (threadIdx.x == 352) {
    asm volatile("prefetch.tensormap [%0];" :: "l"(&maps.m[7]) : "memory");
    asm volatile("prefetch.tensormap [%0];" :: "l"(&maps.m[0]) : "memory");
  }
  __syncwarp();
  asm volatile("barrier.cluster.arrive.relaxed.aligned;" ::: "memory");
  if (w != 8) asm volatile("barrier.cluster.wait.aligned;" ::: "memory");

  if (w >= 8) {
    asm volatile("setmaxnreg.dec.sync.aligned.u32 24;");
    if (w == 8) {
#pragma unroll 1
      for (uint32_t b = 0; b < 9; b++) fetch_x(xs + b * STAGE, b, xbar0 + 8 * b);
      tma_box(sb + PIECE, &maps.m[t >= 12 ? 6 : 5], 72 * j + (odd ? 0 : 64) + (t < 8 ? 576 * ((t >> 2) + 1) : 0), 144 * (t & 3), piece_full, 2304);
      asm volatile("barrier.cluster.wait.aligned;" ::: "memory");
      uint32_t dst = sb, bar = full0, ph = 1;
#pragma unroll 1
      for (int seg = 0; seg < 34; seg++) {
        const int n = seg >= 17 ? seg - 17 : seg;
        int ma, mb, ca, cb;
        if (n < 3) { ma = mb = n == 2; ca = 72 * j + 8 * odd + (n == 0 ? 576 : 0); cb = ca + 576; }
        else if (n < 12) { ma = 3; mb = 2; ca = cb = 576 * j + 64 * (n - 3); }
        else { ma = mb = 4; ca = n == 12 ? 512 : ((j + 2 * n) & 7) * 64; cb = ((j + 2 * n + 1) & 7) * 64; }
        const bool zip = n == 0 || n == 3, solo = n == 1 || n == 2 || n == 16;
#pragma unroll 1
        for (uint32_t st = 0; st < (solo ? 5 : 9); st++) {
          if (seg == 0 && st == NST - 2) mbar_wait(x_ring, 0);
          const uint32_t b = 2 * st + rank, kb = zip ? st : b >= 9 ? b - 9 : b;
          const bool second = zip ? rank : b >= 9, shared = kb == 8 && n >= 2 && n < 12;
          const uint32_t ks = n >= 12 ? 36 * j + 4 * kb : n < 2 ? 4 * blk(kb) : shared ? 0 : (9 * blk(kb) + 1) >> 1;
          asm volatile("{\n.reg .pred p, e, f;\n.reg .u32 n;\nelect.sync _|e, 0xffffffff;\nsetp.ne.and.u32 f, %8, 0, e;\nmov.u32 n, 0;\n"
                       "W: mbarrier.try_wait.parity.shared::cta.b64 p, [%1+48], %2;\n@p bra D;\n"
                       "add.u32 n, n, 1;\nsetp.lt.u32 p, n, 4194304;\n@p bra W;\ntrap;\n"
                       "D: @e mbarrier.arrive.expect_tx.shared::cta.b64 _, [%1], %7;\n"
                       "@f cp.async.bulk.tensor.3d.shared::cluster.global.mbarrier::complete_tx::bytes.multicast::cluster [%0], [%3, {%4, %5, %6}], [%1], 3;\n}"
                       :: "r"(dst + rank * 8192), "r"(bar), "r"(ph), "l"(&maps.m[(second ? mb : ma) + (shared ? 7 : 0)]), "r"(second ? cb : ca),
                          "r"(shared ? 64 : 0), "r"(ks), "r"(solo && st == 4 ? STAGE / 2 : STAGE), "r"((uint32_t)!(solo && b == 9)) : "memory");
          dst += STAGE; bar += 8;
          if (bar == full0 + 8 * NST) { dst = sb; bar = full0; ph ^= 1; }
        }
      }
      {
#pragma unroll 1
        for (int i = 0; i < NST; i++) {
          mbar_wait_trap(bar + 48, ph);
          bar += 8;
          if (bar == full0 + 8 * NST) { bar = full0; ph ^= 1; }
        }
      }
    } else if (w == 9) {
      const uint32_t lane = lane_id();
      const uint32_t stg = sb + HSTG + lane * 16;
      uint32_t fph = 0;
#pragma unroll 1
      for (uint32_t layer = 0; layer < 2; layer++) {
        uint4* xb = scr + OFF_X + ((4 + layer) * 8 + j) * SLAB + 28 * 32;
        mbar_wait_sleep(c8_go, layer);
        int n = 0;
#pragma unroll 1
        while (true) {
          if (lane == 0) asm volatile("mbarrier.arrive.expect_tx.shared::cta.b64 _, [%0], 18432;" :: "r"(c8_full) : "memory");
          __syncwarp();
#pragma unroll 1
          for (uint32_t s = 0; s < 9; s++)
            bulk_load(sb + HSTG + s * 2048, s < 8 ? scr + OFF_P + (j + s * 8) * SLAB + 32 * 32 : xb, 2048, c8_full, false);
          mbar_wait(c8_full, fph); fph ^= 1;
          uint32_t bad = 0;
#pragma unroll 8
          for (int s = 0; s < 32; s++) { uint32_t v; asm volatile("ld.shared.b32 %0, [%1];" : "=r"(v) : "r"(stg + s * 512) : "memory"); bad |= v ^ (1 - layer); }
          if (__all_sync(~0u, (bad & 1u) == 0u)) break;
          __nanosleep(300);
          SPIN_GUARD(n);
        }
        asm volatile("bar.arrive 7, 96;" ::: "memory");
        float s0 = 0.f, s1 = 0.f;
#pragma unroll 1
        for (int g = 0; g < 8; g++) {
          const uint32_t a = stg + (g >> 1) * 512 + (g & 1) * 8;
          float a0 = 0.f, a1 = 0.f, a2 = 0.f, a3 = 0.f;
#pragma unroll 1
          for (int b = 0; b < 3; b++) {
            uint32_t v[6];
#pragma unroll
            for (int s = 0; s < 3; s++) lds2(a + (3 * b + s) * 2048, v + 2 * s);
#pragma unroll
            for (int s = 0; s < 3; s++) { a0 += bf_lo(v[2 * s]); a1 += bf_hi(v[2 * s]); a2 += bf_lo(v[2 * s + 1]); a3 += bf_hi(v[2 * s + 1]); }
          }
          sts1(a + 18432, pack_bf16(a0, a1)); sts1(a + 18436, pack_bf16(a2, a3));
          s0 += a0 + a1; s1 += a2 + a3;
        }
        __syncwarp();
        if (lane == 0) mbar_arrive(c8_done);
        s0 = quad_sum(s0); s1 = quad_sum(s1);
        float q0 = 0.f, q1 = 0.f;
        const uint32_t ln = lane_id();
#pragma unroll 1
        for (uint32_t i = 0; i < 4; i++) {
          uint32_t x[4];
          lds4(stg + 18432 + i * 512, x);
          uint4* z = xb + i * 32 + ln;
          asm volatile("" : "+l"(z));
          stg4(z, 0u, 0u, 0u, 0u);
          if (layer == 0) {
            stg4(z - (3 * 8 * SLAB - 128), nz(x[0]), x[1], nz(x[2]), x[3]);
#pragma unroll
            for (int e = 0; e < 4; e++) {
              const float m = (e & 1) ? s1 : s0, c = fmaf(m, -1.f / 64, bf_lo(x[e])), d = fmaf(m, -1.f / 64, bf_hi(x[e]));
              if (e & 1) q1 = fmaf(c, c, fmaf(d, d, q1)); else q0 = fmaf(c, c, fmaf(d, d, q0));
            }
          } else {
            uint32_t* o = (uint32_t*)(out + (128 * t + 32 * (j >> 1) + 2 * (ln >> 2) + (j & 1)) * 576 + 512 + 16 * i + 2 * (ln & 3));
            o[0] = x[0]; o[8 * 576] = x[1]; o[4] = x[2]; o[8 * 576 + 4] = x[3];
          }
        }
        if (layer == 0) {
          q0 = quad_sum(q0); q1 = quad_sum(q1);
          if ((ln & 3) == 0) stg4(scr + OFF_S + j * 96 + 64 + (ln >> 2), __float_as_uint(s0) | 1u, __float_as_uint(q0), __float_as_uint(s1), __float_as_uint(q1));
        }
      }
    } else {
      auto mark = [&](uint32_t k0, uint32_t v) {
        const uint32_t lane = lane_id();
#pragma unroll 1
        for (uint32_t k = k0; k < 6; k++) stg4(scr + OFF_S + (k * 4 + (lane >> 3)) * 96 + j * 8 + (lane & 7), k < 2 ? 0u : v, 0u, 0u, 0u);
      };
      if (w == 11) mark(2, 0u);
      auto phase2_duties = [&](uint32_t layer) {
        const uint32_t lane = lane_id();
        asm volatile("bar.sync 7, 96;" ::: "memory");
        if (w == 11) {
          if (layer == 0) mark(0, 1u);
          __syncwarp();
          if (lane == 0) mbar_arrive(c8_done);
        }
#pragma unroll 1
        for (uint32_t i = 0; i < 16; i++) {
          const uint32_t sl = (w - 10) * 4 + (i >> 2);
          bulk_load(sb + PARK + sl * 2048 + (i & 3) * 512, scr + OFF_X + ((4 + layer) * 8 + sl) * SLAB + row72(4 * j + (i & 3)) * 32, 512, res_full, true);
        }
        mbar_wait_sleep(res_full, layer);
#pragma unroll 1
        for (uint32_t i = 0; i < 16; i++) {
          stg4(scr + OFF_X + ((4 + layer) * 8 + (w - 10) * 4 + (i >> 2)) * SLAB + row72(4 * j + (i & 3)) * 32 + lane, 0u, 0u, 0u, 0u);
          if ((i & 3) == 3) __nanosleep(200);
        }
      };
      if (w == 10) {
        const uint32_t lane = lane_id();
        uint32_t* fl = (uint32_t*)(scratch + OFF_F + (t * 8 + j) * 8) + (lane & 15);
        uint32_t v;
        asm volatile("ld.relaxed.gpu.global.b32 %0, [%1];" : "=r"(v) : "l"(fl) : "memory");
        mbar_wait(piece_full, 0);
        asm volatile("{\n.reg .pred e;\nelect.sync _|e, 0xffffffff;\n@e cp.async.bulk.global.shared::cta.bulk_group [%0], [%1], 2304;\n}\n"
                     "cp.async.bulk.commit_group;\ncp.async.bulk.wait_group 0;\nfence.proxy.async;"
                     :: "l"(scratch + OFF_R + j * 2304 + t * 144), "r"(sb + PIECE) : "memory");
        __syncwarp();
        if (lane < 16) asm volatile("st.release.gpu.global.b32 [%0], 1;" :: "l"((uint32_t*)(scratch + OFF_F + (lane_id() * 8 + j) * 8) + t) : "memory");
        int n = 0;
#pragma unroll 1
        while (!__all_sync(~0u, v != 0u)) {
          __nanosleep(100);
          SPIN_GUARD(n);
          asm volatile("ld.relaxed.gpu.global.b32 %0, [%1];" : "=r"(v) : "l"(fl) : "memory");
        }
        asm volatile("st.relaxed.gpu.global.b32 [%0], 0;" :: "l"(fl) : "memory");
        mbar_wait(x_done, 0);
      }
#pragma unroll 1
      for (uint32_t layer = 0; layer < 3; layer++) {
        if (w == 10 && layer < 2) {
          if (layer) mbar_wait_sleep(park_free, 0);
          const uint4* img = scratch + OFF_R + j * 2304;
          if (lane_id() == 0) asm volatile("mbarrier.arrive.expect_tx.shared::cta.b64 _, [%0], 27648;\nmbarrier.arrive.expect_tx.shared::cta.b64 _, [%1], 9216;"
                                           :: "r"(rem_full), "r"(piece_full) : "memory");
          __syncwarp();
#pragma unroll 1
          for (uint32_t p = 0; p < 3; p++) {
            bulk_load(sb + REM + p * 9216, img + p * 576 + j * 64, 1024, rem_full, false);
            if (j) bulk_load(sb + REM + p * 9216 + 1024, img + p * 576, j * 1024, rem_full, false);
            bulk_load(sb + REM + p * 9216 + (j + 1) * 1024, img + p * 576 + (j + 1) * 64, (8 - j) * 1024, rem_full, false);
          }
#pragma unroll 1
          for (uint32_t i = 0; i < 12; i++)
            bulk_load(sb + REM + 27648 + (i < 8 ? i * 1024 : 6144 + i * 256), img + 1728 + (i < 8 ? (9 * blk(i) + 1) >> 1 : 9 * i - 68) * 16,
                      i < 8 ? 1024 : 256, piece_full, false);
          if (layer == 0) { fetch_x(sb + PARK, j, xbar0); fetch_x(sb + PARK + STAGE, j + 1, xbar0 + 8); }
        }
        if (w == 11 && layer < 2) {
          if (layer) mbar_wait_sleep(park_free, 0);
          __syncwarp();
          if (lane_id() == 0) mbar_arrive(rem_full);
        }
        if (layer) phase2_duties(layer - 1);
        if (layer == 2) break;
        mbar_wait_sleep(layer ? kv_free : x_done, 0);
        if (t > 0) {
          const uint32_t lane = lane_id(), r = lane >> 2, q = lane & 3;
#pragma unroll 1
          for (uint32_t pc = 0; pc < 3; pc++) {
            uint4* hp = scr + OFF_H + ((layer * 8 + j) * 2 + (w - 10)) * 192 + pc * 64 + lane;
            uint32_t hl[8];
            int n = 0;
            hl[4] = 1u;
#pragma unroll 1
            while (true) {
              ldg4(hl, hp);
              if (pc < 2) ldg4(hl + 4, hp + 32);
              if (__all_sync(~0u, hl[0] != 0u && hl[4] != 0u)) break;
              __nanosleep(100);
              SPIN_GUARD(n);
            }
            const uint32_t dst = sb + KVS + (w - 10) * 10368 + r * 144 + q * 4;
            if (pc < 2) {
#pragma unroll
              for (int g = 0; g < 8; g++) sts1(dst + pc * 20736 + odd * 16 + g * 16, hl[g]);
              stg4(hp + 32, 0u, 0u, 0u, 0u);
            } else {
              sts1(dst + (odd ? 0 : 128), hl[0]); sts1(dst + 20736 + (odd ? 0 : 128), hl[1]);
            }
            stg4(hp, 0u, 0u, 0u, 0u);
          }
        }
        asm volatile("bar.arrive 1, 192;" ::: "memory");
        mbar_wait(rem_full, layer);
        mbar_wait(piece_full, 1 - layer);
#pragma unroll 1
        for (uint32_t b = 0; b < 5; b++) {
          const uint32_t blk = sb + REM + 27648 + b * 2048, k = (w - 10) * 32 + lane_id(), rr = k & 7;
          const uint32_t dst = blk + ((k >> 3) & 1) * 1024 + rr * 128 + (((k >> 4) ^ rr) << 4);
          uint32_t v[8];
          lds4(blk + k * 16, v); lds4(blk + 1024 + k * 16, v + 4);
          asm volatile("bar.sync 3, 64;" ::: "memory");
          sts4(dst, v); sts4(dst ^ 64, v + 4);
        }
        asm volatile("fence.proxy.async.shared::cta;" ::: "memory");
        mbar_arrive(remo_full);
        mbar_wait_sleep(xb_done, layer);
        if (w == 10 && layer == 1) {
          const uint32_t lane = lane_id();
          stg4(scr + OFF_S + (lane >> 3) * 96 + j * 8 + (lane & 7), 0u, 0u, 0u, 0u);
          stg4(scr + OFF_S + (4 + (lane >> 3)) * 96 + j * 8 + (lane & 7), 0u, 0u, 0u, 0u);
          if (lane < 8) stg4(scr + OFF_S + j * 96 + 64 + lane, 0u, 0u, 0u, 0u);
        }
#pragma unroll 1
        for (uint32_t i = 0; i < 8 && (w == 11 || layer == 1); i++) {
          zero_share(scr + OFF_X + ((w - 10) * 16 + layer * 8 + i) * SLAB, j, lane_id());
          __nanosleep(500);
        }
      }
    }
  } else {
    asm volatile("setmaxnreg.inc.sync.aligned.u32 240;");
    const bool lead = lane_id() == 0;
    Ring rg{0, 0};
    uint32_t prev = 0;
    uint32_t X[144];
    float rs0, rs1;
    const bool lead2 = lane_id() < 2;
    uint32_t empty_at;
    asm volatile("mapa.shared::cluster.u32 %0, %1, %2;" : "=r"(empty_at) : "r"(empty0), "r"(lane_id() & 1));
    auto release = [&](uint32_t st) { if (lead2) asm volatile("mbarrier.arrive.shared::cluster.b64 _, [%0];" :: "r"(empty_at + st * 8) : "memory"); };
    auto load_kb = [&](int kb, const uint4* src, const char* lo, uint32_t hoff) {
      const uint4* p;
      asm("{\n.reg .pred p;\n.reg .u64 t;\nsetp.ge.u32 p, %2, %3;\nadd.u64 t, %1, -2048;\nselp.b64 %0, t, %1, p;\n}" : "=l"(p) : "l"(src), "r"(j), "r"(kb));
#pragma unroll
      for (int i = 0; i < 4; i++) {
        if (kb == 8) { ldg2(X + 128 + 4 * i, lo + (32 + i) * 512); ldg2(X + 130 + 4 * i, lo + hoff + (32 + i) * 512); }
        else ldg4(X + 16 * kb + 4 * i, p + kb * 128 + i * 32);
      }
    };
    auto check_kb = [&](bool skip, int kb, const uint4* src, const char* lo, uint32_t hoff) {
      int n = 0;
#pragma unroll 1
      while (true) {
        uint32_t m = umin2(umin2(X[16 * kb], X[16 * kb + 4]), umin2(X[16 * kb + 8], X[16 * kb + 12]));
        if (kb == 8) m = umin2(m, umin2(umin2(X[130], X[134]), umin2(X[138], X[142])));
        if (__all_sync(~0u, m != 0u || skip)) break;
        SPIN_GUARD(n);
        load_kb(kb, src, lo, hoff);
      }
    };
#pragma unroll
    for (int i = 0; i < 16; i++) X[i] = 0u;
#pragma unroll 1
    for (uint32_t hf = 0; hf < 4; hf++) {
      const uint32_t layer = hf >> 1;
      const bool ffn = hf & 1;
      const uint32_t tag = 1 - layer;
      uint4* const xbase = scr + OFF_X + (layer * 8 + w) * SLAB;
      float aA[32], aB[32];
      {
        const uint32_t lane = lane_id(), r = lane >> 2, q = lane & 3;
        const uint4* src = xbase + (ffn ? 32 * SLAB : 0) + lane;
        const char* lo = (const char*)src - (ffn ? lane * 8 : 0);
        const uint32_t hoff = ffn ? 256 : 8;
        const uint32_t xoff = (w & 1) * 8192 + (16 * (w >> 1) + (lane & 15)) * 128 + (((lane >> 4) ^ (lane & 7)) << 4);
        auto load_x = [&](uint32_t b, uint32_t* d) {
#pragma unroll
          for (int i = 0; i < 4; i++) ldsm4(xs + b * STAGE + (xoff ^ (32 * i)), d[4 * i], d[4 * i + 1], d[4 * i + 2], d[4 * i + 3]);
        };
        auto load_any = [&](int kb) { if (hf == 0) load_x(blk(kb), X + 16 * kb); else load_kb(kb, src, lo, hoff); };
        float m0, m1, v0, v1;
        STAMP(ffn * 16 + 0);
        if (hf == 0) {
          float sum[2][4] = {}, sq0[4][4] = {}, sq1[4][4] = {};
          uint32_t p0, p1;
          mbar_wait(xbar0, 0);
          ldsm4(xs + xoff, p0, p1, X[0], X[1]);
          p0 = __byte_perm(__shfl_sync(~0u, p0, lane & 28), 0, 0x1010); p1 = __byte_perm(__shfl_sync(~0u, p1, lane & 28), 0, 0x1010);
#pragma unroll 3
          for (uint32_t b = 0; b < 9; b++) {
            uint32_t d[16];
            mbar_wait(xbar0 + 8 * b, 0);
            load_x(b, d);
#pragma unroll
            for (int i = 0; i < 16; i++) d[i] = sub_bf16x2(d[i], (i & 1) ? p1 : p0);
#pragma unroll
            for (int g = 0; g < 8; g++) {
              if (!(g & 1)) mma16(sum[(g >> 1) & 1], d[2 * g], d[2 * g + 1], d[2 * g + 2], d[2 * g + 3], 0x3f803f80u, 0x3f803f80u);
              mma8(sq0[g & 3], d[2 * g], d[2 * g + 1], d[2 * g]); mma8(sq1[g & 3], d[2 * g], d[2 * g + 1], d[2 * g + 1]);
            }
          }
          STAMP(1);
          GSTAMP(14);
#pragma unroll
          for (int kb = 0; kb < GD; kb++) load_x(blk(kb), X + 16 * kb);
          release((x_ring - empty0) / 8);
          auto tot = [](float (&c)[4][4], int e) { return (c[0][e] + c[1][e]) + (c[2][e] + c[3][e]); };
          const float a0 = (sum[0][0] + sum[1][0]) * (1.f / 576), a1 = (sum[0][2] + sum[1][2]) * (1.f / 576);
          const uint32_t dg = (lane & 28) + (r >> 1);
          v0 = fmaxf(fmaf(__shfl_sync(~0u, (r & 1) ? tot(sq0, 1) : tot(sq0, 0), dg), 1.f / 576, -a0 * a0), 0.f);
          v1 = fmaxf(fmaf(__shfl_sync(~0u, (r & 1) ? tot(sq1, 3) : tot(sq1, 2), dg), 1.f / 576, -a1 * a1), 0.f);
          m0 = bf_lo(p0) + a0; m1 = bf_lo(p1) + a1;
        } else {
          uint32_t s[3][4];
          const uint4* p = scr + OFF_S + ((ffn ? 16 : 0) + w) * 96 + q * 8 + r;
          const bool third = !ffn && q == 0;
          const uint32_t rdy = ffn ? tag : 1u;
          int n = 0;
          s[2][0] = rdy; s[2][1] = s[2][2] = s[2][3] = 0u;
#pragma unroll 1
          while (true) {
            ldg4(s[0], p); ldg4(s[1], p + 32);
            if (third) ldg4(s[2], p + 64);
            if (__all_sync(~0u, ((diff2(s[0][0], s[1][0], rdy) | diff2(s[1][0], s[2][0], rdy)) & 1u) == 0u)) break;
            SPIN_GUARD(n);
          }
          STAMP(ffn * 16 + 1);
          ZSTAMP(1 + ffn, 0);
          GSTAMP(14 + ffn);
#pragma unroll
          for (int kb = 1; kb < GD; kb++) load_kb(kb, src, lo, hoff);
          float t0 = 0.f, t1 = 0.f;
#pragma unroll
          for (int i = 0; i < 3; i++) { t0 += __uint_as_float(s[i][0]); t1 += __uint_as_float(s[i][2]); }
          m0 = quad_sum(t0) * (1.f / 576); m1 = quad_sum(t1) * (1.f / 576);
          const float cnt = ffn ? 72.f : 64.f, inv = ffn ? 1.f / 72 : 1.f / 64;
          v0 = 0.f; v1 = 0.f;
#pragma unroll
          for (int i = 0; i < 3; i++) {
            const float c = (i < 2 || third) ? cnt : 0.f;
            const float d0 = fmaf(__uint_as_float(s[i][0]), inv, -m0), d1 = fmaf(__uint_as_float(s[i][2]), inv, -m1);
            v0 += fmaf(d0 * d0, c, __uint_as_float(s[i][1])); v1 += fmaf(d1 * d1, c, __uint_as_float(s[i][3]));
          }
          v0 = quad_sum(v0) * (1.f / 576); v1 = quad_sum(v1) * (1.f / 576);
        }
        rs0 = rsqrtf(v0 + 1e-5f); rs1 = rsqrtf(v1 + 1e-5f);
        const uint32_t mean0 = pack_bf16(m0, m0), mean1 = pack_bf16(m1, m1);
#pragma unroll
        for (int kb = 0; kb < 9; kb++) {
          if (kb > 0) check_kb(hf == 0, kb, src, lo, hoff);
          if (kb + GD < 9) load_any(kb + GD);
          if (kb + GD == 8 && hf == 0 && lead) mbar_arrive(x_done);
#pragma unroll
          for (int i = 16 * kb; i < 16 * kb + 16; i++) X[i] = sub_bf16x2(X[i], (i & 1) ? mean1 : mean0);
          ZSTAMP(1 + ffn, 1 + 3 * kb);
          mbar_wait(full0 + rg.st * 8, rg.ph);
          ZSTAMP(1 + ffn, 2 + 3 * kb);
          const uint64_t desc = DESC_HI | ((sd + rg.st * STAGE) >> 4);
          wg_fence();
#pragma unroll
          for (int i = 0; i < 4; i++) wgmma_rs_n64(aA, X + 4 * (4 * kb + i), desc + i * 128, kb + i != 0);
          if (kb == 8) { wg_commit(); wg_wait<1>(); wg_fence(); }
#pragma unroll
          for (int i = 0; i < 4; i++) wgmma_rs_n64(aB, X + 4 * (4 * kb + i), desc + 512 + i * 128, kb + i != 0);
          wg_commit();
          wg_wait<1>();
          ZSTAMP(1 + ffn, 3 + 3 * kb);
          if (kb > 0) release(prev);
          prev = rg.st; rg.next();
        }
        ZSTAMP(1 + ffn, 28);
        ZSTAMP(4, 0);
        STAMP(ffn * 16 + 2);
      }
      if (!ffn) {
      const uint32_t lane = lane_id(), r = lane >> 2, q = lane & 3;
      const uint32_t kvrow = sb + KVS + (w & 1) * 10368 + (16 * (w >> 1)) * 144;
      uint32_t Q[18], Km[3][8], Ke[3][4];
      const bool edge = (t == 0 && w < 2);
      const uint32_t row0 = edge ? sb + KVS + 8 * 144 : kvrow + (lane & 7) * 144, row1 = kvrow + (8 + (lane & 7)) * 144;
      {
        const uint32_t dst = kvrow + (8 + r) * 144 + q * 4 + odd * 16, dstr = dst + (odd ? -16 : 128);
        const bool edge_out = w >= 6 && t < 15;
        uint4* const hp = scr + TILE + OFF_H + ((layer * 8 + j) * 2 + (w & 1)) * 192 + lane;
        auto put_kv = [&](float (&a)[32], int part, int half) {
          uint32_t hl[4];
#pragma unroll
          for (int i = 0; i < 16; i++) asm volatile("" : "+f"(a[16 * half + i]) :: "memory");
#pragma unroll
          for (int i = 0; i < 4; i++) {
            const int g = 4 * half + i;
            hl[i] = pack_bf16(a[4 * g + 2] * rs1, a[4 * g + 3] * rs1);
            sts1(dst + part * 20736 + g * 16, pack_bf16(a[4 * g] * rs0, a[4 * g + 1] * rs0)); sts1(dst + part * 20736 + 8 * 144 + g * 16, hl[i]);
          }
          if (edge_out) stg4(hp + part * 64 + half * 32, nz(hl[0]), hl[1], hl[2], hl[3]);
        };
        put_kv(aA, 0, 0); put_kv(aA, 0, 1);
        wg_wait<0>();
        release(prev);
        float aR[12];
        mbar_wait(rem_full, layer);
        const uint64_t dr = DESC_REM | ((sd + REM) >> 4);
        wg_fence();
#pragma unroll
        for (int s = 0; s < 36; s++) {
          wgmma_rs_n24(aR, X + 4 * s, dr + s * 16, s != 0);
          if (s == 4) put_kv(aB, 1, 0);
          if (s == 16) put_kv(aB, 1, 1);
        }
        wg_commit();
#pragma unroll
        for (int kb = 0; kb < 9; kb++) {
          if (!(kb & 1)) mbar_wait(full0 + rg.st * 8, rg.ph);
          const uint64_t desc = DESC_HI | ((sd + rg.st * STAGE + (kb & 1) * 8192) >> 4);
          wg_fence();
#pragma unroll
          for (int i = 0; i < 4; i++) wgmma_rs_n64(aB, X + 4 * (4 * kb + i), desc + i * 128, kb + i != 0);
          wg_commit();
          wg_wait<1>();
          if (kb > 0 && !(kb & 1)) release(prev);
          if ((kb & 1) || kb == 8) { prev = rg.st; rg.next(); }
          if (kb == 0) {
            pin(aR);
            const uint32_t k1 = pack_bf16(aR[2] * rs1, aR[3] * rs1), v1 = pack_bf16(aR[6] * rs1, aR[7] * rs1);
            if (edge_out) stg4(hp + 128, nz(k1), v1, 0u, 0u);
            sts1(dstr, pack_bf16(aR[0] * rs0, aR[1] * rs0)); sts1(dstr + 8 * 144, k1);
            sts1(dstr + 20736, pack_bf16(aR[4] * rs0, aR[5] * rs0)); sts1(dstr + 20736 + 8 * 144, v1);
            Q[16] = pack_bf16(aR[8], aR[9]); Q[17] = pack_bf16(aR[10], aR[11]);
            if (w < 4) asm volatile("bar.arrive 2, 256;" ::: "memory");
          }
          if (kb == 8) {
            if (w < 4) asm volatile("bar.sync 1, 192;" ::: "memory");
            else asm volatile("bar.sync 2, 256;" ::: "memory");
#pragma unroll
            for (int nt = 0; nt < 3; nt++) {
              const uint32_t ra = (nt == 0 ? row0 : row1 + (nt - 1) * 8 * 144);
              ldsm4(ra + odd * 16 + (lane >> 3) * 16, Km[nt][0], Km[nt][1], Km[nt][2], Km[nt][3]);
              ldsm4(ra + odd * 16 + 64 + (lane >> 3) * 16, Km[nt][4], Km[nt][5], Km[nt][6], Km[nt][7]);
              ldsm4(ra + (odd ? 0 : 32) + (lane >> 3) * 32, Ke[nt][0], Ke[nt][1], Ke[nt][2], Ke[nt][3]);
            }
            const uint32_t ge = (2u << q) - 1, le = 0xfu << q, on = edge ? 0u : ~0u;
            const uint32_t bits = odd ? 0xfu | ((le & 0xfu) << 4) | (ge << 8) : ge | 0xf0u | (le << 8);
#pragma unroll
            for (int h = 0; h < 4; h++) {
              const uint32_t ma = bitmask(bits, h), mb = bitmask(bits, 4 + h), mc = bitmask(bits, 8 + h);
              Km[0][2 * h] &= ma & on; Km[0][2 * h + 1] &= mb & on; Ke[0][h] &= mc & on;
#pragma unroll
              for (int nt = 1; nt < 3; nt++) { Km[nt][2 * h] &= ma; Km[nt][2 * h + 1] &= mb; Ke[nt][h] &= mc; }
            }
          }
        }
        wg_wait<0>();
        release(prev);
        pin(aB);
        if (w < 4) asm volatile("bar.sync 4, 256;" ::: "memory");
        STAMP(3);
#pragma unroll
        for (int i = 0; i < 16; i++) Q[i] = pack_bf16(aB[2 * i], aB[2 * i + 1]);
      }
      uint32_t res[18] = {};
      if (layer) {
        const uint4* p = xbase + ((9 * j + 1) >> 1) * 32 + lane;
#pragma unroll
        for (int i = 0; i < 4; i++) ldg4(res + 4 * i, p + i * 32);
        ldg2(res + 16, odd ? (const char*)(p - 32) + 8 : (const char*)(p + 4 * 32));
      }
      {
        uint32_t V01[12][2], V2[12];
        const uint32_t rv = ((lane & 8) ? row1 : row0) + 20736, rw = row1 + 8 * 144 + 20736;
#pragma unroll
        for (int i = 0; i < 4; i++) ldsm4t(rv + odd * 16 + i * 32 + (lane >> 4) * 16, V01[2 * i][0], V01[2 * i][1], V01[2 * i + 1][0], V01[2 * i + 1][1]);
#pragma unroll
        for (int i = 0; i < 2; i++) ldsm4t(rv + (odd ? 0 : 32) + i * 64 + (lane >> 4) * 32, V01[8 + 2 * i][0], V01[8 + 2 * i][1], V01[9 + 2 * i][0], V01[9 + 2 * i][1]);
        ldsm4t(rw + odd * 16 + (lane >> 3) * 16, V2[0], V2[1], V2[2], V2[3]);
        ldsm4t(rw + odd * 16 + 64 + (lane >> 3) * 16, V2[4], V2[5], V2[6], V2[7]);
        ldsm4t(rw + (odd ? 0 : 32) + (lane >> 3) * 32, V2[8], V2[9], V2[10], V2[11]);
        const bool up0 = 2 * q > r, up1 = 2 * q + 1 > r;
        const uint32_t upm = (up0 ? 0xffffu : 0u) | (up1 ? 0xffff0000u : 0u);
        const float c0 = 0.23570226039551584f * 1.4426950408889634f * rs0, c1 = 0.23570226039551584f * 1.4426950408889634f * rs1;
        const float masked = edge ? -1e9f * 1.4426950408889634f * rcp(c0) : 0.f;
        uint32_t Om[16], Oe[8];
        uint4* const po = xbase + 16 * SLAB + 4 * j * 32 + lane;
#pragma unroll
        for (int h = 0; h < 4; h++) {
          const uint32_t e0 = odd ? Q[(4 * h + 16) % 18] : Q[4 * h + 4], e1 = odd ? Q[(4 * h + 17) % 18] : Q[4 * h + 5];
          float S[3][4];
#pragma unroll
          for (int nt = 0; nt < 3; nt++) {
            mma16c(S[nt], Q + 4 * h, Km[nt][2 * h], Km[nt][2 * h + 1], nt == 0 ? masked : 0.f);
            mma8(S[nt], e0, e1, Ke[nt][h]);
          }
          const float s00 = up0 ? S[0][0] : S[1][0], s01 = up1 ? S[0][1] : S[1][1];
          const float s10 = up0 ? S[1][2] : S[2][2], s11 = up1 ? S[1][3] : S[2][3];
          const float m0 = quad_max(fmaxf(s00, s01)) * c0, m1 = quad_max(fmaxf(s10, s11)) * c1;
          const float p00 = ex2(fmaf(s00, c0, -m0)), p01 = ex2(fmaf(s01, c0, -m0)), p10 = ex2(fmaf(s10, c1, -m1)), p11 = ex2(fmaf(s11, c1, -m1));
          const float i0 = rcp(quad_sum(p00 + p01)), i1 = rcp(quad_sum(p10 + p11));
          const uint32_t p0 = pack_bf16(p00 * i0, p01 * i0), p1 = pack_bf16(p10 * i1, p11 * i1);
          const uint32_t pf[4] = {p0 & upm, 0u, p0 & ~upm, p1 & upm};
#pragma unroll
          for (int gi = 0; gi < 3; gi++) {
            const int g = gi < 2 ? 2 * h + gi : 8 + h;
            float o[4];
            mma16c(o, pf, V01[g][0], V01[g][1], 0.f);
            mma8(o, 0u, p1 & ~upm, V2[g]);
            uint32_t* d = gi < 2 ? Om + 2 * g : Oe + 2 * h;
            d[0] = pack_bf16(o[0], o[1]); d[1] = pack_bf16(o[2], o[3]);
          }
          if (h > 0) {
#pragma unroll
            for (int e = 0; e < 2; e++) {
              if (!odd && q < h) Om[4 * h + e] = Oe[2 * h - 2 + e];
              if (odd && q >= h) Om[4 * h - 2 + e] = Oe[2 * h + e];
            }
            stg4(po + (h - 1) * 32, nz(Om[4 * h - 4]), Om[4 * h - 3], Om[4 * h - 2], Om[4 * h - 1]);
            if (h == 1 && w >= 4) asm volatile("bar.arrive 4, 256;" ::: "memory");
          }
        }
        STAMP(4);
        stg4(po + 96, nz(Om[12]), Om[13], Om[14], Om[15]);
        stg2((char*)(xbase + 16 * SLAB + 1024 + j * 16) + lane * 8, nz(odd ? Oe[0] : Oe[6]), odd ? Oe[1] : Oe[7]);
#pragma unroll
        for (int i = 0; i < 16; i++) X[i] = Om[i];
      }
      if (lane == 0) asm volatile("st.relaxed.gpu.global.b32 [%0], %1;" :: "l"(scr + OFF_S + (8 + w) * 96 + j * 8), "r"(tag) : "memory");
      {
        if (layer == 0) {
          const uint32_t xrow = (w & 1) * 8192 + (16 * (w >> 1) + (lane & 15)) * 128;
          uint32_t u0, u1;
          mbar_wait(xbar0, 1); mbar_wait(xbar0 + 8, 1);
#pragma unroll
          for (int i = 0; i < 5; i++) {
            const uint32_t g = i < 4 ? j + odd + 2 * i : j + (odd ? 0 : 8);
            const uint32_t a = sb + PARK + (g >> 3) * STAGE + xrow;
            if (i < 4) ldsm4(a + ((((g & 7) + (lane >> 4)) ^ (lane & 7)) << 4), res[4 * i], res[4 * i + 1], res[4 * i + 2], res[4 * i + 3]);
            else ldsm4(a + (((g & 7) ^ (lane & 7)) << 4), res[16], res[17], u0, u1);
          }
        }
        const uint4* src = xbase + 16 * SLAB + lane;
        const uint32_t st0 = rg.st;
        auto stage_of = [&](uint32_t i) { const uint32_t x = st0 + i; return x >= NST ? x - NST : x; };
        {
          const uint32_t x = st0 + lane, wrap = x >= NST;
          mbar_wait(lane < 5 ? full0 + (x - wrap * NST) * 8 : remo_full, lane < 5 ? rg.ph ^ wrap : layer);
          __syncwarp();
          if (st0) { rg.st = st0 - 1; rg.ph ^= 1; } else rg.st = 5;
        }
        float acc[36];
        auto block72 = [&](uint32_t kb, uint32_t base, const uint32_t* a) {
          const uint64_t d0 = DESC_HI | ((base >> 4) + (((sd + REM + 27648 + (kb >> 1) * 2048 + (kb & 1) * 64 - base) >> 4) << 16));
          wg_fence();
#pragma unroll
          for (int i = 0; i < 4; i++) wgmma_rs_n72(acc, a + 4 * i, d0 - (uint64_t)(i * ((127u << 16) - 128u)), 1);
          wg_commit();
        };
#pragma unroll
        for (int i = 0; i < 18; i++) { acc[2 * i] = bf_lo(res[i]); acc[2 * i + 1] = bf_hi(res[i]); }
        block72(0, sd + st0 * STAGE, X);
        {
          const uint4* fp = scr + OFF_S + (8 + w) * 96 + (lane & 7) * 8;
          int n = 0;
          STAMP(8);
#pragma unroll 1
          while (true) {
            uint32_t f;
            asm volatile("ld.relaxed.gpu.global.b32 %0, [%1];" : "=r"(f) : "l"(fp) : "memory");
            if (__all_sync(~0u, f == tag)) break;
            SPIN_GUARD(n);
          }
          STAMP(9);
        }
#pragma unroll
        for (int kb = 1; kb < GO; kb++) load_kb(kb, src, (const char*)src - lane * 8, 256);
        __syncwarp();
        uint32_t m = ~0u;
#pragma unroll
        for (int kb = 1; kb < 9; kb++) {
          m = umin2(m, umin2(umin2(X[16 * kb], X[16 * kb + 4]), umin2(X[16 * kb + 8], X[16 * kb + 12])));
          if (kb == 8) m = umin2(m, umin2(umin2(X[130], X[134]), umin2(X[138], X[142])));
          if (kb + GO - 1 < 9) {
            const uint4* s2 = src + (m == 0u);
            load_kb(kb + GO - 1, s2, (const char*)s2 - lane * 8, 256);
            __syncwarp();
          }
          block72(kb, sd + stage_of(kb >> 1) * STAGE + (kb & 1) * 8192, X + 16 * kb);
          if (!(kb & 1)) { wg_wait<1>(); release(stage_of((kb >> 1) - 1)); }
        }
        uint32_t redo;
        asm volatile("{\n.reg .pred p;\nsetp.eq.u32 p, %1, 0;\nbar.red.or.pred p, %2, 128, p;\nselp.u32 %0, 1, 0, p;\n}" : "=r"(redo) : "r"(m), "r"(5 + (w >> 2)) : "memory");
        wg_wait<0>();
        release(stage_of(4));
        pin(acc);
        if (__any_sync(~0u, redo || FORCE_REDO)) {
#pragma unroll
          for (int i = 0; i < 18; i++) { res[i] = __shfl_sync(~0u, res[i], lane); acc[2 * i] = bf_lo(res[i]); acc[2 * i + 1] = bf_hi(res[i]); }
          const uint32_t box = PARK + 2 * STAGE + (w >> 2) * 8192, bar = redo_full + (w >> 2) * 8;
#pragma unroll 1
          for (uint32_t kb = 0; kb < 10; kb++) {
            asm volatile("bar.sync %0, 128;" :: "r"(5 + (w >> 2)) : "memory");
            if ((w & 3) == 0)
              asm volatile("{\n.reg .pred e;\nelect.sync _|e, 0xffffffff;\n@e mbarrier.arrive.expect_tx.shared::cta.b64 _, [%2], 8192;\n"
                           "@e cp.async.bulk.tensor.3d.shared::cluster.global.mbarrier::complete_tx::bytes [%0], [%1, {%3, %4, %5}], [%2];\n}"
                           :: "r"(sb + box), "l"(&maps.m[kb >= 8 ? 8 : 1]), "r"(bar), "r"(72 * j + 8 * odd), "r"(kb >= 8 ? 64 : 0),
                              "r"(kb >= 8 ? 0 : (9 * blk(kb) + 1) >> 1) : "memory");
            mbar_wait(bar, kb & 1);
            if (kb == 9) break;
            int n = 0;
#pragma unroll 1
            while (true) {
              const char* l = (const char*)(src + blk(kb) * 128) - (kb == 8 ? lane * 8 : 0);
#pragma unroll
              for (int i = 0; i < 4; i++) ldg2(X + 4 * i, l + i * 512);
              uint32_t mm = umin2(umin2(X[0], X[4]), umin2(X[8], X[12]));
              l += (kb == 8 ? 256 : 8) + (mm == 0u ? 16 : 0);
#pragma unroll
              for (int i = 0; i < 4; i++) ldg2(X + 4 * i + 2, l + i * 512);
              if (kb == 8) mm = umin2(mm, umin2(umin2(X[2], X[6]), umin2(X[10], X[14])));
              if (__all_sync(~0u, mm != 0u)) break;
              SPIN_GUARD(n);
            }
            block72(kb, sd + box, X);
            wg_wait<0>();
            pin(acc);
          }
        }
        STAMP(10);
#pragma unroll
        for (int i = 0; i < 18; i++) res[i] = pack_bf16(acc[2 * i], acc[2 * i + 1]);
        if (j < PRI) put72(xbase + 32 * SLAB, j, lane, res);
        publish_stats<9>(scr + OFF_S + (16 + w) * 96 + j * 8, acc, tag, lane);
        if (j >= PRI) put72(xbase + 32 * SLAB, j, lane, res);
#pragma unroll
        for (int i = 0; i < 16; i++) X[i] = res[i];
      }
      continue;
      }
      const uint32_t hp = sb + PARK + w * 512 + lane_id() * 16;
      auto pack8 = [&](float (&a)[32], int p, uint32_t* o) {
#pragma unroll
        for (int e = 0; e < 8; e++) asm volatile("" : "+f"(a[8 * p + e]) :: "memory");
#pragma unroll
        for (int e = 0; e < 4; e++) o[e] = pack_bf16(a[8 * p + 2 * e], a[8 * p + 2 * e + 1]);
      };
      const float ka0 = 0.7978845608028654f * rs0, kb0 = 0.044715f * ka0 * rs0 * rs0, ku0 = 0.5f * rs0 * rs0;
      const float ka1 = 0.7978845608028654f * rs1, kb1 = 0.044715f * ka1 * rs1 * rs1, ku1 = 0.5f * rs1 * rs1;
      auto packu8 = [&](int p, uint32_t* o) {
#pragma unroll
        for (int e = 0; e < 8; e++) asm volatile("" : "+f"(aA[8 * p + e]) :: "memory");
#pragma unroll
        for (int e = 0; e < 4; e++) o[e] = pack_bf16(aA[8 * p + 2 * e] * ((e & 1) ? ku1 : ku0), aA[8 * p + 2 * e + 1] * ((e & 1) ? ku1 : ku0));
      };
      auto geglu8 = [&](int p, uint32_t* u) {
#pragma unroll
        for (int e = 0; e < 8; e++) asm volatile("" : "+f"(aB[8 * p + e]) :: "memory");
        float h[8];
#pragma unroll
        for (int e = 0; e < 8; e++) {
          const float g = aB[8 * p + e];
          h[e] = fmaf(g, tanh_ap(g * fmaf(g * g, (e & 2) ? kb1 : kb0, (e & 2) ? ka1 : ka0)), g);
        }
#pragma unroll
        for (int e = 0; e < 4; e++) u[e] = mul_bf16x2(pack_bf16(h[2 * e], h[2 * e + 1]), u[e]);
      };
      uint32_t ready = 0;
      auto box = [&](int b, auto&& filler) {
        const int kb = b < 9 ? b : b - 9;
        if (b == 0) mbar_wait_trap(full0 + rg.st * 8, rg.ph);
        else if (!(b & 1)) mbar_wait_unless(ready, full0 + rg.st * 8, rg.ph);
        const uint64_t desc = DESC_HI | ((sd + rg.st * STAGE + (b & 1) * 8192) >> 4);
        if (b & 1) { prev = rg.st; rg.next(); }
        wg_fence();
#pragma unroll
        for (int i = 0; i < 4; i++) {
          if (b < 9) wgmma_rs_n64(aA, X + 4 * (4 * kb + i), desc + i * 128, kb + i != 0);
          else wgmma_rs_n64(aB, X + 4 * (4 * kb + i), desc + i * 128, kb + i != 0);
          if ((b & 1) && b < 17 && i == 0) ready = mbar_peek(full0 + rg.st * 8, rg.ph);
          if (i == 1) filler();
        }
        wg_commit();
        if (!(b & 1)) { wg_wait<1>(); release(prev); }
      };
      auto nop = [] {};
      auto step = [&](int st, auto&& filler) { box(2 * st, nop); box(2 * st + 1, filler); };
#pragma unroll
      for (int p = 0; p < 4; p++) { uint32_t o[4]; packu8(p, o); sts4(hp + p * 4096, o); }
      box(0, nop);
      if (lead) mbar_arrive(xb_done);
#pragma unroll 1
      for (int c = 1;; c++) {
        const uint32_t hc = hp + c * 4 * 4096;
#pragma unroll
        for (int b = 1; b < 18; b++) box(b, [&] {
          if ((b & 1) && b < 8) { uint32_t o[4]; const uint32_t a = hc - (4 - (b >> 1)) * 4096; lds4(a, o); geglu8(b >> 1, o); sts4(a, o); }
          if ((b & 1) && b > 10) { uint32_t o[4]; packu8((b - 11) >> 1, o); if (c < 8) sts4(hc + ((b - 11) >> 1) * 4096, o); } });
        ZSTAMP(4, c);
        if (c == 8) break;
        box(0, nop);
      }
      wg_wait<0>();
      STAMP(21);
      GSTAMP(19);
      auto unpark = [&](int kb) {
#pragma unroll
        for (int s = 4 * kb; s < 4 * kb + 4; s++) lds4(hp + s * 4096, X + 4 * s);
      };
      unpark(0);
      uint32_t U[16];
#pragma unroll
      for (int p = 0; p < 4; p++) packu8(p, U + 4 * p);
#pragma unroll
      for (int b = 0; b < 8; b++) box(b, [&] {
        if (b < 7) unpark(b + 1);
        if (b & 1) {
          geglu8(b >> 1, U + 2 * (b - 1));
          if (rg.ph > 1) sts4(hp, U + 2 * (b - 1));
#pragma unroll
          for (int i = 0; i < 4; i++) X[128 + 2 * (b - 1) + i] = U[2 * (b - 1) + i];
        } });
      STAMP(24);
      if (layer == 0 && lead) mbar_arrive(park_free);
      const uint32_t lane2 = lane_id();
      uint4* const pw = scr + OFF_P + (j * 8 + w) * SLAB + lane2;
      const uint4* const pr = scr + OFF_P + w * SLAB + 4 * j * 32 + lane2;
      auto put_part = [&](float (&a)[32], int p, uint32_t chunk) {
        uint32_t o[4];
        pack8(a, p, o);
        stg4(pw + (chunk * 4 + p) * 32, (o[0] & ~1u) | tag, o[1], o[2], o[3]);
      };
      auto slot = [&](int p) { return sb + w * 2048 + (p < 3 ? PARK + p * 16384 : KVS + (p - 3) * 16384); };
      auto fetch = [&](int p) {
        bulk_load(slot(p), scr + OFF_P + (((j - p) & 7) * 8 + w) * SLAB + 4 * j * 32, 2048, pbar0 + w * 8, true);
      };
#pragma unroll 1
      for (int sp = 0;; sp++) {
        const uint32_t ca = sp == 0 ? 8 : ((j + 2 * sp) & 7), cb = (j + 2 * sp + 1) & 7;
        if (sp == 1 && lead) mbar_arrive(c8_go);
#pragma unroll
        for (int st = 4; st < 9; st++) step(st, [&] {
          if (st == 5 || st == 6) { put_part(aA, 2 * (st - 5), ca); put_part(aA, 2 * (st - 5) + 1, ca); }
          if (st == 8 && sp > 1) { if (sp == 3) mbar_wait(c8_done, layer); fetch(2 * sp - 2); } });
        STAMP(25 + sp);
        if (sp == 3) break;
#pragma unroll
        for (int st = 0; st < 4; st++) step(st, [&] {
          if (st < 2) { put_part(aB, 2 * st, cb); put_part(aB, 2 * st + 1, cb); }
          if (st == 3 && sp > 0) fetch(2 * sp - 1); });
      }
      auto load_p = [&](int p, uint32_t* d) {
#pragma unroll
        for (int i = 0; i < 4; i++) ldg4(d + 4 * i, pr + ((j - p) & 7) * 8 * SLAB + i * 32);
      };
#pragma unroll
      for (int b = 0; b < 9; b++) {
        box(b, [&] {
          if (b == 1) {
#pragma unroll
            for (int p = 0; p < 4; p++) put_part(aB, p, (j + 7) & 7);
          }
          if (b == 3) { load_p(5, X); load_p(6, X + 16); }
          if (b == 7) load_p(7, X + 32); });
      }
      mbar_wait(res_full, layer);
      mbar_wait(pbar0 + w * 8, layer);
#pragma unroll
      for (int p = 1; p < 5; p++)
#pragma unroll
        for (int i = 0; i < 4; i++) lds4(slot(p) + lane2 * 16 + i * 512, X + 48 + 16 * p + 4 * i);
#pragma unroll
      for (int i = 0; i < 4; i++) {
        const bool split = j == 2 * i + 1;
        const uint32_t a = slot(0) + i * 512 + (split ? lane2 * 8 : lane2 * 16);
        lds2(a, X + 48 + 4 * i); lds2(a + (split ? 256 : 8), X + 50 + 4 * i);
      }
      wg_wait<0>();
      release(rg.st); rg.next();
      pin(aA);
      STAMP(22);
      GSTAMP(20);
      {
        const uint32_t lane = lane2, r = lane >> 2, q = lane & 3;
        const uint32_t eye = r == 2 * q ? 0x3f80u : r == 2 * q + 1 ? 0x3f800000u : 0u;
        auto bad = [&](const uint32_t* d) { return diff2(d[0], d[4], tag) | diff2(d[8], d[12], tag); };
        auto add = [&](const uint32_t* d) {
#pragma unroll
          for (int g = 0; g < 8; g++) mma8(aA + 4 * g, d[2 * g], d[2 * g + 1], eye);
        };
        int n = 0;
#pragma unroll 1
        while (!__all_sync(~0u, ((or3(bad(X), bad(X + 16), bad(X + 64)) | or3(bad(X + 80), bad(X + 96), bad(X + 112))) & 1u) == 0u)) {
          SPIN_GUARD(n);
          load_p(5, X); load_p(6, X + 16);
#pragma unroll
          for (int p = 1; p < 5; p++) load_p(p, X + 48 + 16 * p);
        }
        add(X); add(X + 16);
#pragma unroll
        for (int p = 4; p >= 0; p--) add(X + 48 + 16 * ((p + 1) % 5));
        STAMP(11);
#pragma unroll 1
        while (!__all_sync(~0u, (bad(X + 32) & 1u) == 0u)) { SPIN_GUARD(n); load_p(7, X + 32); }
        add(X + 32);
        STAMP(12);
        uint32_t res[16];
#pragma unroll
        for (int i = 0; i < 16; i++) X[i] = res[i] = pack_bf16(aA[2 * i], aA[2 * i + 1]);
        if (layer == 0) {
          uint4* p = xbase + 8 * SLAB + 4 * j * 32 + lane;
          auto put = [&] {
#pragma unroll
            for (int i = 0; i < 4; i++) stg4(p + i * 32, nz(res[4 * i]), res[4 * i + 1], res[4 * i + 2], res[4 * i + 3]);
          };
          if (j < PRI) put();
          publish_stats<8>(scr + OFF_S + w * 96 + j * 8, aA, 1u, lane);
          if (j >= PRI) put();
          if (lane == 0) mbar_arrive(kv_free);
        } else {
          const uint32_t tb = slot(0);
          __syncwarp();
#pragma unroll
          for (int i = 0; i < 4; i++) {
            const uint32_t row = (lane2 & 7) + (lane2 & 8), g = 2 * i + (lane2 >> 4);
            asm volatile("stmatrix.sync.aligned.m8n8.x4.shared.b16 [%0], {%1,%2,%3,%4};"
                         :: "r"(tb + row * 128 + ((g ^ (row & 7)) << 4)), "r"(res[4 * i]), "r"(res[4 * i + 1]), "r"(res[4 * i + 2]), "r"(res[4 * i + 3]) : "memory");
          }
          __syncwarp();
#pragma unroll
          for (int i = 0; i < 4; i++) {
            const uint32_t row = 4 * i + (lane2 >> 3), g = lane2 & 7;
            uint32_t v[4];
            lds4(tb + row * 128 + ((g ^ (row & 7)) << 4), v);
            *(uint4*)(out + (128 * t + 32 * (w >> 1) + 2 * row + (w & 1)) * 576 + 64 * j + 8 * g) = make_uint4(v[0], v[1], v[2], v[3]);
          }
        }
      }
      STAMP(23);
    }
  }
}

typedef CUresult (*EncodeFn)(CUtensorMap*, CUtensorMapDataType, cuuint32_t, void*, const cuuint64_t*, const cuuint64_t*,
                             const cuuint32_t*, const cuuint32_t*, CUtensorMapInterleave, CUtensorMapSwizzle,
                             CUtensorMapL2promotion, CUtensorMapFloatOOBfill);

CUtensorMap make_map(EncodeFn f, const void* p, uint64_t cols, uint64_t rows, uint64_t grp) {
  CUtensorMap m;
  cuuint64_t dims[3] = {cols, grp, rows / grp}, str[2] = {cols * 2, cols * 2 * grp};
  cuuint32_t box[3] = {64, 16, 4}, es[3] = {1, 1, 1};
  f(&m, CU_TENSOR_MAP_DATA_TYPE_BFLOAT16, 3, const_cast<void*>(p), dims, str, box, es, CU_TENSOR_MAP_INTERLEAVE_NONE,
    CU_TENSOR_MAP_SWIZZLE_128B, CU_TENSOR_MAP_L2_PROMOTION_NONE, CU_TENSOR_MAP_FLOAT_OOB_FILL_NONE);
  return m;
}
CUtensorMap make_rem_map(EncodeFn f, const void* p, uint64_t cols) {
  CUtensorMap m;
  cuuint64_t dims[2] = {cols, 576}, str[1] = {cols * 2};
  cuuint32_t box[2] = {8, 144}, es[2] = {1, 1};
  f(&m, CU_TENSOR_MAP_DATA_TYPE_BFLOAT16, 2, const_cast<void*>(p), dims, str, box, es, CU_TENSOR_MAP_INTERLEAVE_NONE,
    CU_TENSOR_MAP_SWIZZLE_NONE, CU_TENSOR_MAP_L2_PROMOTION_NONE, CU_TENSOR_MAP_FLOAT_OOB_FILL_NONE);
  return m;
}

}

extern "C" void kernel_launch(void* const* d_in, const int* in_sizes, int n_in, void* d_out, int out_size) {
  void* fn = nullptr;
  cudaDriverEntryPointQueryResult qr;
  cudaGetDriverEntryPoint("cuTensorMapEncodeTiled", &fn, cudaEnableDefault, &qr);
  EncodeFn enc = (EncodeFn)fn;
  Maps maps;
  maps.m[0] = make_map(enc, d_in[1], 1728, 576, 16); maps.m[1] = make_map(enc, d_in[2], 576, 576, 16);
  maps.m[2] = make_map(enc, d_in[4], 4608, 576, 16); maps.m[3] = make_map(enc, d_in[5], 4608, 576, 16);
  maps.m[4] = make_map(enc, d_in[6], 576, 4608, 16);
  maps.m[5] = make_rem_map(enc, d_in[1], 1728); maps.m[6] = make_rem_map(enc, d_in[2], 576);
  maps.m[8] = make_map(enc, d_in[2], 576, 576, 144); maps.m[9] = make_map(enc, d_in[4], 4608, 576, 144);
  maps.m[10] = make_map(enc, d_in[5], 4608, 576, 144);
  {
    cuuint64_t dims[3] = {576, 1024, 2}, str[2] = {2304, 1152};
    cuuint32_t box[3] = {64, 64, 2}, es[3] = {1, 1, 1};
    enc(&maps.m[7], CU_TENSOR_MAP_DATA_TYPE_BFLOAT16, 3, d_in[0], dims, str, box, es, CU_TENSOR_MAP_INTERLEAVE_NONE,
        CU_TENSOR_MAP_SWIZZLE_128B, CU_TENSOR_MAP_L2_PROMOTION_NONE, CU_TENSOR_MAP_FLOAT_OOB_FILL_NONE);
  }
  void* scr = nullptr;
  cudaGetSymbolAddress(&scr, g_scratch);
  cudaFuncSetAttribute(mega_kernel, cudaFuncAttributeMaxDynamicSharedMemorySize, SMEM_BYTES);
  cudaLaunchConfig_t cfg = {};
  cfg.gridDim = dim3(128); cfg.blockDim = dim3(384); cfg.dynamicSmemBytes = SMEM_BYTES; cfg.stream = cudaStreamPerThread;
  cudaLaunchAttribute at[1];
  at[0].id = cudaLaunchAttributeClusterDimension; at[0].val.clusterDim.x = 2; at[0].val.clusterDim.y = 1; at[0].val.clusterDim.z = 1;
  cfg.attrs = at; cfg.numAttrs = 1;
  int dev = 0, sms = 0, clusters = 0;
  cudaGetDevice(&dev);
  cudaDeviceGetAttribute(&sms, cudaDevAttrMultiProcessorCount, dev);
  cudaOccupancyMaxActiveClusters(&clusters, mega_kernel, &cfg);
  if (sms == 132 && clusters == 66) cfg.gridDim = dim3(132);
  cudaLaunchKernelEx(&cfg, mega_kernel, maps, (uint4*)scr, (__nv_bfloat16*)d_out);
}
```

```cpp
#include <cuda_runtime.h>
#include <cuda.h>
#include <cuda_bf16.h>
#include <stdint.h>

#define TRACE 0
#define GUARD 0
#define FORCE_REDO 0
#define ZT 0

namespace {

constexpr int NST = 6;
constexpr int STAGE = 16384;
constexpr int PARK = NST * STAGE;
constexpr int REM = PARK + 49152;
constexpr int KVS = REM + 40960;
constexpr int PIECE = PARK + 7 * STAGE;
constexpr int HSTG = KVS + 16384;
constexpr int BARS = KVS + 41472;
constexpr int TRC = BARS + 512;
constexpr int SMEM_BYTES = TRC + (TRACE ? 512 : 0);
static_assert(NST == 6, "the producer addresses empty barriers as full + 48");
static_assert(BARS >= PARK + 131072, "barriers overlap park");
static_assert(SMEM_BYTES <= 232448, "smem");

constexpr int SLAB = 36 * 32;
constexpr int SPIN_MAX = 1 << 17;
constexpr uint32_t PRI = 4;
constexpr int GD = 3, GO = 5;
constexpr int OFF_S = 0;
constexpr int OFF_H = OFF_S + 3 * 8 * 96;
constexpr int OFF_X = OFF_H + 2 * 8 * 384;
constexpr int OFF_P = OFF_X + 6 * 8 * SLAB;
constexpr int TILE = OFF_P + 8 * 8 * SLAB;
constexpr int OFF_R = 16 * TILE;
constexpr int OFF_F = OFF_R + 8 * 2304;
constexpr int SCRATCH = OFF_F + 128 * 8;

}

__device__ uint4 g_scratch[SCRATCH];

namespace {

constexpr uint64_t DESC_HI = 0x4000004000000000ull;
constexpr uint64_t DESC_REM = (576ull << 32) | (8u << 16);
__device__ __forceinline__ void wgmma_rs_n64(float (&d)[32], const uint32_t* a, uint64_t desc, int scale_d) {
  asm volatile("{\n.reg .pred p;\nsetp.ne.b32 p, %37, 0;\n"
    "wgmma.mma_async.sync.aligned.m64n64k16.f32.bf16.bf16 "
    "{%0, %1, %2, %3, %4, %5, %6, %7, %8, %9, %10, %11, %12, %13, %14, %15, %16, %17, %18, %19, %20, %21, %22, %23, %24, %25, %26, %27, %28, %29, %30, %31}, "
    "{%32, %33, %34, %35}, %36, p, 1, 1, 1;\n}\n"
    : "+f"(d[0]), "+f"(d[1]), "+f"(d[2]), "+f"(d[3]), "+f"(d[4]), "+f"(d[5]), "+f"(d[6]), "+f"(d[7]), "+f"(d[8]), "+f"(d[9]), "+f"(d[10]), "+f"(d[11]), "+f"(d[12]), "+f"(d[13]), "+f"(d[14]), "+f"(d[15]), "+f"(d[16]), "+f"(d[17]), "+f"(d[18]), "+f"(d[19]), "+f"(d[20]), "+f"(d[21]), "+f"(d[22]), "+f"(d[23]), "+f"(d[24]), "+f"(d[25]), "+f"(d[26]), "+f"(d[27]), "+f"(d[28]), "+f"(d[29]), "+f"(d[30]), "+f"(d[31])
    : "r"(a[0]), "r"(a[1]), "r"(a[2]), "r"(a[3]), "l"(desc), "r"(scale_d));
}
__device__ __forceinline__ void wgmma_rs_n72(float (&d)[36], const uint32_t* a, uint64_t desc, int scale_d) {
  asm volatile("{\n.reg .pred p;\nsetp.ne.b32 p, %41, 0;\n"
    "wgmma.mma_async.sync.aligned.m64n72k16.f32.bf16.bf16 "
    "{%0, %1, %2, %3, %4, %5, %6, %7, %8, %9, %10, %11, %12, %13, %14, %15, %16, %17, %18, %19, %20, %21, %22, %23, %24, %25, %26, %27, %28, %29, %30, %31, %32, %33, %34, %35}, "
    "{%36, %37, %38, %39}, %40, p, 1, 1, 1;\n}\n"
    : "+f"(d[0]), "+f"(d[1]), "+f"(d[2]), "+f"(d[3]), "+f"(d[4]), "+f"(d[5]), "+f"(d[6]), "+f"(d[7]), "+f"(d[8]), "+f"(d[9]), "+f"(d[10]), "+f"(d[11]), "+f"(d[12]), "+f"(d[13]), "+f"(d[14]), "+f"(d[15]), "+f"(d[16]), "+f"(d[17]), "+f"(d[18]), "+f"(d[19]), "+f"(d[20]), "+f"(d[21]), "+f"(d[22]), "+f"(d[23]), "+f"(d[24]), "+f"(d[25]), "+f"(d[26]), "+f"(d[27]), "+f"(d[28]), "+f"(d[29]), "+f"(d[30]), "+f"(d[31]), "+f"(d[32]), "+f"(d[33]), "+f"(d[34]), "+f"(d[35])
    : "r"(a[0]), "r"(a[1]), "r"(a[2]), "r"(a[3]), "l"(desc), "r"(scale_d));
}
__device__ __forceinline__ void wgmma_rs_n24(float (&d)[12], const uint32_t* a, uint64_t desc, int scale_d) {
  asm volatile("{\n.reg .pred p;\nsetp.ne.b32 p, %17, 0;\n"
    "wgmma.mma_async.sync.aligned.m64n24k16.f32.bf16.bf16 "
    "{%0, %1, %2, %3, %4, %5, %6, %7, %8, %9, %10, %11}, "
    "{%12, %13, %14, %15}, %16, p, 1, 1, 1;\n}\n"
    : "+f"(d[0]), "+f"(d[1]), "+f"(d[2]), "+f"(d[3]), "+f"(d[4]), "+f"(d[5]), "+f"(d[6]), "+f"(d[7]), "+f"(d[8]), "+f"(d[9]), "+f"(d[10]), "+f"(d[11])
    : "r"(a[0]), "r"(a[1]), "r"(a[2]), "r"(a[3]), "l"(desc), "r"(scale_d));
}

__device__ __forceinline__ void mbar_init(uint32_t a, uint32_t c) { asm volatile("mbarrier.init.shared::cta.b64 [%0], %1;" :: "r"(a), "r"(c)); }
__device__ __forceinline__ void mbar_arrive(uint32_t a) { asm volatile("mbarrier.arrive.shared::cta.b64 _, [%0];" :: "r"(a) : "memory"); }
__device__ __forceinline__ void mbar_wait_trap(uint32_t a, uint32_t ph) {
  asm volatile("{\n.reg .pred p;\n.reg .u32 n;\nmov.u32 n, 0;\n"
               "W: mbarrier.try_wait.parity.shared::cta.b64 p, [%0], %1;\n@p bra D;\n"
               "add.u32 n, n, 1;\nsetp.lt.u32 p, n, 4194304;\n@p bra W;\ntrap;\nD:\n}" :: "r"(a), "r"(ph) : "memory");
}
__device__ __forceinline__ void mbar_wait(uint32_t a, uint32_t ph) {
  asm volatile("{\n.reg .pred p;\nW: mbarrier.try_wait.parity.shared::cta.b64 p, [%0], %1;\n@!p bra W;\n}" :: "r"(a), "r"(ph) : "memory");
}
__device__ __forceinline__ uint32_t mbar_peek(uint32_t a, uint32_t ph) {
  uint32_t r;
  asm volatile("{\n.reg .pred p;\nmbarrier.test_wait.parity.shared::cta.b64 p, [%1], %2;\nselp.u32 %0, 1, 0, p;\n}" : "=r"(r) : "r"(a), "r"(ph) : "memory");
  return r;
}
__device__ __forceinline__ void mbar_wait_unless(uint32_t ready, uint32_t a, uint32_t ph) {
  asm volatile("{\n.reg .pred p;\nsetp.ne.u32 p, %2, 0;\n@p bra D;\nW: mbarrier.try_wait.parity.shared::cta.b64 p, [%0], %1;\n@!p bra W;\nD:\n}"
               :: "r"(a), "r"(ph), "r"(ready) : "memory");
}
__device__ __forceinline__ void mbar_wait_sleep(uint32_t a, uint32_t ph) {
  asm volatile("{\n.reg .pred p;\nW: mbarrier.test_wait.parity.shared::cta.b64 p, [%0], %1;\n@p bra D;\nnanosleep.u32 500;\nbra W;\nD:\n}" :: "r"(a), "r"(ph) : "memory");
}
__device__ __forceinline__ void wg_fence() { asm volatile("wgmma.fence.sync.aligned;" ::: "memory"); }
__device__ __forceinline__ void wg_commit() { asm volatile("wgmma.commit_group.sync.aligned;" ::: "memory"); }
template <int N> __device__ __forceinline__ void wg_wait() { asm volatile("wgmma.wait_group.sync.aligned %0;" :: "n"(N) : "memory"); }
__device__ __forceinline__ float tanh_ap(float x) { float y; asm("tanh.approx.f32 %0, %1;" : "=f"(y) : "f"(x)); return y; }
__device__ __forceinline__ float ex2(float x) { float y; asm("ex2.approx.ftz.f32 %0, %1;" : "=f"(y) : "f"(x)); return y; }
__device__ __forceinline__ uint32_t pack_bf16(float lo, float hi) { uint32_t r; asm("cvt.rn.bf16x2.f32 %0, %1, %2;" : "=r"(r) : "f"(hi), "f"(lo)); return r; }
__device__ __forceinline__ float bf_lo(uint32_t v) { return __uint_as_float(v << 16); }
__device__ __forceinline__ float bf_hi(uint32_t v) { return __uint_as_float(v & 0xffff0000u); }
__device__ __forceinline__ uint32_t sub_bf16x2(uint32_t a, uint32_t b) { uint32_t r; asm("sub.rn.bf16x2 %0, %1, %2;" : "=r"(r) : "r"(a), "r"(b)); return r; }
__device__ __forceinline__ uint32_t mul_bf16x2(uint32_t a, uint32_t b) { uint32_t r; asm("mul.rn.bf16x2 %0, %1, %2;" : "=r"(r) : "r"(a), "r"(b)); return r; }
__device__ __forceinline__ uint32_t diff2(uint32_t a, uint32_t b, uint32_t t) { uint32_t r; asm("lop3.b32 %0, %1, %2, %3, 0x7e;" : "=r"(r) : "r"(a), "r"(b), "r"(t)); return r; }
__device__ __forceinline__ uint32_t or3(uint32_t a, uint32_t b, uint32_t c) { uint32_t r; asm("lop3.b32 %0, %1, %2, %3, 0xfe;" : "=r"(r) : "r"(a), "r"(b), "r"(c)); return r; }
__device__ __forceinline__ uint32_t umin2(uint32_t a, uint32_t b) { uint32_t r; asm("min.u32 %0, %1, %2;" : "=r"(r) : "r"(a), "r"(b)); return r; }
__device__ __forceinline__ uint32_t bitmask(uint32_t v, int bit) { uint32_t r; asm("bfe.s32 %0, %1, %2, 1;" : "=r"(r) : "r"(v), "r"(bit)); return r; }
__device__ __forceinline__ uint32_t nz(uint32_t w) { return w == 0u ? 0x8000u : w; }

__device__ __forceinline__ void ldg4(uint32_t* d, const uint4* p) {
  asm volatile("ld.relaxed.gpu.global.v4.b32 {%0,%1,%2,%3}, [%4];" : "=r"(d[0]), "=r"(d[1]), "=r"(d[2]), "=r"(d[3]) : "l"(p) : "memory");
}
__device__ __forceinline__ void ldg2(uint32_t* d, const void* p) {
  asm volatile("ld.relaxed.gpu.global.v2.b32 {%0,%1}, [%2];" : "=r"(d[0]), "=r"(d[1]) : "l"(p) : "memory");
}
__device__ __forceinline__ void stg4(uint4* p, uint32_t a, uint32_t b, uint32_t c, uint32_t d) {
  asm volatile("st.relaxed.gpu.global.v4.b32 [%0], {%1,%2,%3,%4};" :: "l"(p), "r"(a), "r"(b), "r"(c), "r"(d) : "memory");
}
__device__ __forceinline__ void stg2(void* p, uint32_t a, uint32_t b) {
  asm volatile("st.relaxed.gpu.global.v2.b32 [%0], {%1,%2};" :: "l"(p), "r"(a), "r"(b) : "memory");
}
__device__ __forceinline__ void sts4(uint32_t a, const uint32_t* o) { asm volatile("st.shared.v4.b32 [%0], {%1,%2,%3,%4};" :: "r"(a), "r"(o[0]), "r"(o[1]), "r"(o[2]), "r"(o[3]) : "memory"); }
__device__ __forceinline__ void lds4(uint32_t a, uint32_t* o) { asm volatile("ld.shared.v4.b32 {%0,%1,%2,%3}, [%4];" : "=r"(o[0]), "=r"(o[1]), "=r"(o[2]), "=r"(o[3]) : "r"(a) : "memory"); }
__device__ __forceinline__ void lds2(uint32_t a, uint32_t* o) { asm volatile("ld.shared.v2.b32 {%0,%1}, [%2];" : "=r"(o[0]), "=r"(o[1]) : "r"(a) : "memory"); }
__device__ __forceinline__ float rcp(float x) { float y; asm("rcp.approx.ftz.f32 %0, %1;" : "=f"(y) : "f"(x)); return y; }
__device__ __forceinline__ void sts1(uint32_t a, uint32_t v) { asm volatile("st.shared.b32 [%0], %1;" :: "r"(a), "r"(v) : "memory"); }
__device__ __forceinline__ void ldsm4(uint32_t a, uint32_t& r0, uint32_t& r1, uint32_t& r2, uint32_t& r3) {
  asm volatile("ldmatrix.sync.aligned.m8n8.x4.shared.b16 {%0,%1,%2,%3}, [%4];" : "=r"(r0), "=r"(r1), "=r"(r2), "=r"(r3) : "r"(a) : "memory");
}
__device__ __forceinline__ void ldsm4t(uint32_t a, uint32_t& r0, uint32_t& r1, uint32_t& r2, uint32_t& r3) {
  asm volatile("ldmatrix.sync.aligned.m8n8.x4.trans.shared.b16 {%0,%1,%2,%3}, [%4];" : "=r"(r0), "=r"(r1), "=r"(r2), "=r"(r3) : "r"(a) : "memory");
}
__device__ __forceinline__ void mma16(float* c, uint32_t a0, uint32_t a1, uint32_t a2, uint32_t a3, uint32_t b0, uint32_t b1) {
  asm("mma.sync.aligned.m16n8k16.row.col.f32.bf16.bf16.f32 {%0,%1,%2,%3}, {%4,%5,%6,%7}, {%8,%9}, {%0,%1,%2,%3};"
    : "+f"(c[0]), "+f"(c[1]), "+f"(c[2]), "+f"(c[3]) : "r"(a0), "r"(a1), "r"(a2), "r"(a3), "r"(b0), "r"(b1));
}
__device__ __forceinline__ void mma16c(float* d, const uint32_t* a, uint32_t b0, uint32_t b1, float c01) {
  asm("mma.sync.aligned.m16n8k16.row.col.f32.bf16.bf16.f32 {%0,%1,%2,%3}, {%4,%5,%6,%7}, {%8,%9}, {%10,%10,%10,%10};"
    : "=f"(d[0]), "=f"(d[1]), "=f"(d[2]), "=f"(d[3]) : "r"(a[0]), "r"(a[1]), "r"(a[2]), "r"(a[3]), "r"(b0), "r"(b1), "f"(c01));
}
__device__ __forceinline__ void mma8(float* c, uint32_t a0, uint32_t a1, uint32_t b0) {
  asm("mma.sync.aligned.m16n8k8.row.col.f32.bf16.bf16.f32 {%0,%1,%2,%3}, {%4,%5}, {%6}, {%0,%1,%2,%3};"
    : "+f"(c[0]), "+f"(c[1]), "+f"(c[2]), "+f"(c[3]) : "r"(a0), "r"(a1), "r"(b0));
}
__device__ __forceinline__ uint32_t lane_id() { uint32_t l; asm volatile("mov.u32 %0, %%laneid;" : "=r"(l)); return l; }
__device__ __forceinline__ float quad_sum(float v) { v += __shfl_xor_sync(~0u, v, 1); v += __shfl_xor_sync(~0u, v, 2); return v; }
__device__ __forceinline__ float quad_max(float v) { v = fmaxf(v, __shfl_xor_sync(~0u, v, 1)); v = fmaxf(v, __shfl_xor_sync(~0u, v, 2)); return v; }
template <int N> __device__ __forceinline__ void pin(float (&d)[N]) {
#pragma unroll
  for (int i = 0; i < N; i++) asm volatile("" : "+f"(d[i]) :: "memory");
}
#define SPIN_GUARD(n) if (++(n) > SPIN_MAX) break

template <int NG> __device__ __forceinline__ void publish_stats(uint4* dst, const float* y, uint32_t tag, uint32_t lane) {
  float s0 = 0.f, s1 = 0.f;
#pragma unroll
  for (int g = 0; g < NG; g++) { s0 += y[4 * g] + y[4 * g + 1]; s1 += y[4 * g + 2] + y[4 * g + 3]; }
  s0 = quad_sum(s0); s1 = quad_sum(s1);
  const float m0 = s0 * (1.f / (8 * NG)), m1 = s1 * (1.f / (8 * NG));
  float q0 = 0.f, q1 = 0.f, q2 = 0.f, q3 = 0.f;
#pragma unroll
  for (int g = 0; g < NG; g++) {
    const float a = y[4 * g] - m0, b = y[4 * g + 1] - m0, c = y[4 * g + 2] - m1, d = y[4 * g + 3] - m1;
    q0 = fmaf(a, a, q0); q1 = fmaf(b, b, q1); q2 = fmaf(c, c, q2); q3 = fmaf(d, d, q3);
  }
  q0 = quad_sum(q0 + q1); q2 = quad_sum(q2 + q3);
  if ((lane & 3) == 0)
    stg4(dst + (lane >> 2), (__float_as_uint(s0) & ~1u) | tag, __float_as_uint(q0), __float_as_uint(s1), __float_as_uint(q2));
}

__device__ __forceinline__ void put72(uint4* slab, uint32_t j, uint32_t lane, const uint32_t* v) {
#pragma unroll
  for (int i = 0; i < 4; i++) stg4(slab + (4 * j + i) * 32 + lane, nz(v[4 * i]), v[4 * i + 1], v[4 * i + 2], v[4 * i + 3]);
  stg2((char*)(slab + 1024 + j * 16) + lane * 8, nz(v[16]), v[17]);
}
__device__ __forceinline__ uint32_t row72(uint32_t k) { return k % 9 == 4 ? 32 + k / 9 : k - (k + 4) / 9; }
__device__ __forceinline__ void zero_share(uint4* slab, uint32_t j, uint32_t lane) {
  uint4* p = slab + j * 144 + lane;
#pragma unroll
  for (int i = 0; i < 4; i++) stg4(p + i * 32, 0u, 0u, 0u, 0u);
  if (lane < 16) stg4(p + 128, 0u, 0u, 0u, 0u);
}

struct Maps { CUtensorMap m[11]; };

struct Ring {
  uint32_t st, ph;
  __device__ __forceinline__ void next() { if (++st == NST) { st = 0; ph ^= 1; } }
};

#define GSTAMP(i) do {} while (0)
#define STAMP(i) do {} while (0)
#define ZSTAMP(m, i) do {} while (0)

__device__ __forceinline__ void tma_box(uint32_t dst, const CUtensorMap* m, int col, int row, uint32_t bar, uint32_t expect) {
  asm volatile("{\n.reg .pred e, h;\nelect.sync _|e, 0xffffffff;\nsetp.ne.and.u32 h, %5, 0, e;\n"
               "@h mbarrier.arrive.expect_tx.shared::cta.b64 _, [%2], %5;\n"
               "@e cp.async.bulk.tensor.2d.shared::cluster.global.mbarrier::complete_tx::bytes [%0], [%1, {%3, %4}], [%2];\n}"
               :: "r"(dst), "l"(m), "r"(bar), "r"(col), "r"(row), "r"(expect) : "memory");
}

__device__ __forceinline__ void bulk_load(uint32_t dst, const void* src, uint32_t bytes, uint32_t bar, bool arm) {
  asm volatile("{\n.reg .pred e, h;\nelect.sync _|e, 0xffffffff;\nsetp.ne.and.u32 h, %4, 0, e;\n"
               "@h mbarrier.arrive.expect_tx.shared::cta.b64 _, [%3], %2;\n"
               "@e cp.async.bulk.shared::cluster.global.mbarrier::complete_tx::bytes [%0], [%1], %2, [%3];\n}"
               :: "r"(dst), "l"(src), "r"(bytes), "r"(bar), "r"((uint32_t)arm) : "memory");
}

__global__ void __launch_bounds__(384, 1) mega_kernel(
    const __grid_constant__ Maps maps, uint4* __restrict__ scratch,
    __nv_bfloat16* __restrict__ out) {
  extern __shared__ __align__(1024) uint8_t smem[];
  const uint32_t sb = (uint32_t)__cvta_generic_to_shared(smem);
  const uint32_t full0 = sb + BARS, empty0 = full0 + 8 * NST, rem_full = empty0 + 8 * NST, park_free = rem_full + 8, kv_free = park_free + 8;
  const uint32_t c8_go = kv_free + 8, c8_done = c8_go + 8, c8_full = c8_done + 8, remo_full = c8_full + 8, piece_full = remo_full + 8, xb_done = piece_full + 8, res_full = xb_done + 8, pbar0 = res_full + 8;
  const uint32_t x_done = pbar0 + 64, x_ring = x_done + 8, xbar0 = x_ring + 8, redo_full = xbar0 + 72;
  const uint32_t w = __shfl_sync(~0u, threadIdx.x >> 5, 0);
  uint32_t pair = blockIdx.x >> 1;
  if (gridDim.x == 132) {
    uint32_t smid;
    asm("mov.u32 %0, %%smid;" : "=r"(smid));
    const uint32_t tpc = smid >> 1;
    if (tpc == 60 || tpc == 61) { if (threadIdx.x == 0) { __nanosleep(20000); } return; }
    pair = tpc < 32 ? tpc : tpc >= 62 ? (tpc - 58) * 8 : 33 + (tpc - 32) / 7 * 8 + (tpc - 32) % 7;
  }
  const uint32_t rank = blockIdx.x & 1, t = (pair & 7) * 2 + rank, j = pair >> 3;
  const uint32_t sd = sb & 0x3ffff;
  const uint32_t odd = j & 1;
  uint4* const scr = scratch + t * TILE;
  auto blk = [&](uint32_t kb) { return kb == 0 ? j : kb - (kb <= j); };
  const uint32_t xs = sb + (NST - 2) * STAGE;
  auto fetch_x = [&](uint32_t dst, uint32_t b, uint32_t bar) {
    asm volatile("{\n.reg .pred e;\nelect.sync _|e, 0xffffffff;\n@e mbarrier.arrive.expect_tx.shared::cta.b64 _, [%2], 16384;\n"
                 "@e cp.async.bulk.tensor.3d.shared::cluster.global.mbarrier::complete_tx::bytes [%0], [%1, {%3, %4, 0}], [%2];\n}"
                 :: "r"(dst), "l"(&maps.m[7]), "r"(bar), "r"(64 * b), "r"(64 * t) : "memory");
  };
  if (threadIdx.x == 256) {
    for (int i = 0; i < 9; i++) mbar_init(xbar0 + 8 * i, 1);
    mbar_init(piece_full, 1);
    asm volatile("fence.mbarrier_init.release.cluster;" ::: "memory");
  }
  if (threadIdx.x == 288) {
    for (int i = 0; i < NST; i++) { mbar_init(full0 + 8 * i, 1); mbar_init(empty0 + 8 * i, 16); }
    mbar_init(x_done, 8); mbar_init(x_ring, 16); mbar_init(redo_full, 1); mbar_init(redo_full + 8, 1);
    asm volatile("fence.mbarrier_init.release.cluster;" ::: "memory");
  }
  if (threadIdx.x == 320) {
    mbar_init(rem_full, 2); mbar_init(park_free, 8); mbar_init(kv_free, 8); mbar_init(c8_go, 8); mbar_init(c8_done, 2); mbar_init(c8_full, 1);
    mbar_init(remo_full, 64); mbar_init(xb_done, 8); mbar_init(res_full, 32);
    for (int i = 0; i < 8; i++) mbar_init(pbar0 + 8 * i, 4);
    asm volatile("fence.mbarrier_init.release.cluster;" ::: "memory");
  }
  if (threadIdx.x == 352) {
    asm volatile("prefetch.tensormap [%0];" :: "l"(&maps.m[7]) : "memory");
    asm volatile("prefetch.tensormap [%0];" :: "l"(&maps.m[0]) : "memory");
  }
  __syncwarp();
  asm volatile("barrier.cluster.arrive.relaxed.aligned;" ::: "memory");
  if (w != 8) asm volatile("barrier.cluster.wait.aligned;" ::: "memory");

  if (w >= 8) {
    asm volatile("setmaxnreg.dec.sync.aligned.u32 24;");
    if (w == 8) {
#pragma unroll 1
      for (uint32_t b = 0; b < 9; b++) fetch_x(xs + b * STAGE, b, xbar0 + 8 * b);
      tma_box(sb + PIECE, &maps.m[t >= 12 ? 6 : 5], 72 * j + (odd ? 0 : 64) + (t < 8 ? 576 * ((t >> 2) + 1) : 0), 144 * (t & 3), piece_full, 2304);
      asm volatile("barrier.cluster.wait.aligned;" ::: "memory");
      uint32_t dst = sb, bar = full0, ph = 1;
#pragma unroll 1
      for (int seg = 0; seg < 34; seg++) {
        const int n = seg >= 17 ? seg - 17 : seg;
        int ma, mb, ca, cb;
        if (n == 2) continue;
        if (n < 2) { ma = 0; mb = n; ca = 72 * j + 8 * odd + (n ? 0 : 576); cb = ca + (n ? 0 : 576); }
        else if (n < 12) { ma = 3; mb = 2; ca = cb = 576 * j + 64 * (n - 3); }
        else { ma = mb = 4; ca = n == 12 ? 512 : ((j + 2 * n) & 7) * 64; cb = ((j + 2 * n + 1) & 7) * 64; }
        const bool zip = n == 0 || n == 3, solo = n == 16;
#pragma unroll 1
        for (uint32_t st = 0; st < (solo ? 5 : 9); st++) {
          if (seg == 0 && st == NST - 2) mbar_wait(x_ring, 0);
          const uint32_t b = 2 * st + rank, kb = zip ? st : b >= 9 ? b - 9 : b;
          const bool second = zip ? rank : b >= 9;
          const int m = second ? mb : ma;
          const bool shared = kb == 8 && m > 0 && m < 4;
          const uint32_t ks = m == 4 ? 36 * j + 4 * kb : m == 0 ? 4 * blk(kb) : shared ? 0 : (9 * blk(kb) + 1) >> 1;
          asm volatile("{\n.reg .pred p, e, f;\n.reg .u32 n;\nelect.sync _|e, 0xffffffff;\nsetp.ne.and.u32 f, %8, 0, e;\nmov.u32 n, 0;\n"
                       "W: mbarrier.try_wait.parity.shared::cta.b64 p, [%1+48], %2;\n@p bra D;\n"
                       "add.u32 n, n, 1;\nsetp.lt.u32 p, n, 4194304;\n@p bra W;\ntrap;\n"
                       "D: @e mbarrier.arrive.expect_tx.shared::cta.b64 _, [%1], %7;\n"
                       "@f cp.async.bulk.tensor.3d.shared::cluster.global.mbarrier::complete_tx::bytes.multicast::cluster [%0], [%3, {%4, %5, %6}], [%1], 3;\n}"
                       :: "r"(dst + rank * 8192), "r"(bar), "r"(ph), "l"(&maps.m[m + (shared ? 7 : 0)]), "r"(second ? cb : ca),
                          "r"(shared ? 64 : 0), "r"(ks), "r"(solo && st == 4 ? STAGE / 2 : STAGE), "r"((uint32_t)!(solo && b == 9)) : "memory");
          dst += STAGE; bar += 8;
          if (bar == full0 + 8 * NST) { dst = sb; bar = full0; ph ^= 1; }
        }
      }
      {
#pragma unroll 1
        for (int i = 0; i < NST; i++) {
          mbar_wait_trap(bar + 48, ph);
          bar += 8;
          if (bar == full0 + 8 * NST) { bar = full0; ph ^= 1; }
        }
      }
    } else if (w == 9) {
      const uint32_t lane = lane_id();
      const uint32_t stg = sb + HSTG + lane * 16;
      uint32_t fph = 0;
#pragma unroll 1
      for (uint32_t layer = 0; layer < 2; layer++) {
        uint4* xb = scr + OFF_X + ((4 + layer) * 8 + j) * SLAB + 28 * 32;
        mbar_wait_sleep(c8_go, layer);
        int n = 0;
#pragma unroll 1
        while (true) {
          if (lane == 0) asm volatile("mbarrier.arrive.expect_tx.shared::cta.b64 _, [%0], 18432;" :: "r"(c8_full) : "memory");
          __syncwarp();
#pragma unroll 1
          for (uint32_t s = 0; s < 9; s++)
            bulk_load(sb + HSTG + s * 2048, s < 8 ? scr + OFF_P + (j + s * 8) * SLAB + 32 * 32 : xb, 2048, c8_full, false);
          mbar_wait(c8_full, fph); fph ^= 1;
          uint32_t bad = 0;
#pragma unroll 8
          for (int s = 0; s < 32; s++) { uint32_t v; asm volatile("ld.shared.b32 %0, [%1];" : "=r"(v) : "r"(stg + s * 512) : "memory"); bad |= v ^ (1 - layer); }
          if (__all_sync(~0u, (bad & 1u) == 0u)) break;
          __nanosleep(300);
          SPIN_GUARD(n);
        }
        asm volatile("bar.arrive 7, 96;" ::: "memory");
        float s0 = 0.f, s1 = 0.f;
#pragma unroll 1
        for (int g = 0; g < 8; g++) {
          const uint32_t a = stg + (g >> 1) * 512 + (g & 1) * 8;
          float a0 = 0.f, a1 = 0.f, a2 = 0.f, a3 = 0.f;
#pragma unroll 1
          for (int b = 0; b < 3; b++) {
            uint32_t v[6];
#pragma unroll
            for (int s = 0; s < 3; s++) lds2(a + (3 * b + s) * 2048, v + 2 * s);
#pragma unroll
            for (int s = 0; s < 3; s++) { a0 += bf_lo(v[2 * s]); a1 += bf_hi(v[2 * s]); a2 += bf_lo(v[2 * s + 1]); a3 += bf_hi(v[2 * s + 1]); }
          }
          sts1(a + 18432, pack_bf16(a0, a1)); sts1(a + 18436, pack_bf16(a2, a3));
          s0 += a0 + a1; s1 += a2 + a3;
        }
        __syncwarp();
        if (lane == 0) mbar_arrive(c8_done);
        s0 = quad_sum(s0); s1 = quad_sum(s1);
        float q0 = 0.f, q1 = 0.f;
        const uint32_t ln = lane_id();
#pragma unroll 1
        for (uint32_t i = 0; i < 4; i++) {
          uint32_t x[4];
          lds4(stg + 18432 + i * 512, x);
          uint4* z = xb + i * 32 + ln;
          asm volatile("" : "+l"(z));
          stg4(z, 0u, 0u, 0u, 0u);
          if (layer == 0) {
            stg4(z - (3 * 8 * SLAB - 128), nz(x[0]), x[1], nz(x[2]), x[3]);
#pragma unroll
            for (int e = 0; e < 4; e++) {
              const float m = (e & 1) ? s1 : s0, c = fmaf(m, -1.f / 64, bf_lo(x[e])), d = fmaf(m, -1.f / 64, bf_hi(x[e]));
              if (e & 1) q1 = fmaf(c, c, fmaf(d, d, q1)); else q0 = fmaf(c, c, fmaf(d, d, q0));
            }
          } else {
            uint32_t* o = (uint32_t*)(out + (128 * t + 32 * (j >> 1) + 2 * (ln >> 2) + (j & 1)) * 576 + 512 + 16 * i + 2 * (ln & 3));
            o[0] = x[0]; o[8 * 576] = x[1]; o[4] = x[2]; o[8 * 576 + 4] = x[3];
          }
        }
        if (layer == 0) {
          q0 = quad_sum(q0); q1 = quad_sum(q1);
          if ((ln & 3) == 0) stg4(scr + OFF_S + j * 96 + 64 + (ln >> 2), __float_as_uint(s0) | 1u, __float_as_uint(q0), __float_as_uint(s1), __float_as_uint(q1));
        }
      }
    } else {
      auto mark = [&](uint32_t k0, uint32_t v) {
        const uint32_t lane = lane_id();
#pragma unroll 1
        for (uint32_t k = k0; k < 6; k++) stg4(scr + OFF_S + (k * 4 + (lane >> 3)) * 96 + j * 8 + (lane & 7), k < 2 ? 0u : v, 0u, 0u, 0u);
      };
      if (w == 11) mark(2, 0u);
      auto phase2_duties = [&](uint32_t layer) {
        const uint32_t lane = lane_id();
        asm volatile("bar.sync 7, 96;" ::: "memory");
        if (w == 11) {
          if (layer == 0) mark(0, 1u);
          __syncwarp();
          if (lane == 0) mbar_arrive(c8_done);
        }
#pragma unroll 1
        for (uint32_t i = 0; i < 16; i++) {
          const uint32_t sl = (w - 10) * 4 + (i >> 2);
          bulk_load(sb + PARK + sl * 2048 + (i & 3) * 512, scr + OFF_X + ((4 + layer) * 8 + sl) * SLAB + row72(4 * j + (i & 3)) * 32, 512, res_full, true);
        }
        mbar_wait_sleep(res_full, layer);
#pragma unroll 1
        for (uint32_t i = 0; i < 16; i++) {
          stg4(scr + OFF_X + ((4 + layer) * 8 + (w - 10) * 4 + (i >> 2)) * SLAB + row72(4 * j + (i & 3)) * 32 + lane, 0u, 0u, 0u, 0u);
          if ((i & 3) == 3) __nanosleep(200);
        }
      };
      if (w == 10) {
        const uint32_t lane = lane_id();
        uint32_t* fl = (uint32_t*)(scratch + OFF_F + (t * 8 + j) * 8) + (lane & 15);
        uint32_t v;
        asm volatile("ld.relaxed.gpu.global.b32 %0, [%1];" : "=r"(v) : "l"(fl) : "memory");
        mbar_wait(piece_full, 0);
        asm volatile("{\n.reg .pred e;\nelect.sync _|e, 0xffffffff;\n@e cp.async.bulk.global.shared::cta.bulk_group [%0], [%1], 2304;\n}\n"
                     "cp.async.bulk.commit_group;\ncp.async.bulk.wait_group 0;\nfence.proxy.async;"
                     :: "l"(scratch + OFF_R + j * 2304 + t * 144), "r"(sb + PIECE) : "memory");
        __syncwarp();
        if (lane < 16) asm volatile("st.release.gpu.global.b32 [%0], 1;" :: "l"((uint32_t*)(scratch + OFF_F + (lane_id() * 8 + j) * 8) + t) : "memory");
        int n = 0;
#pragma unroll 1
        while (!__all_sync(~0u, v != 0u)) {
          __nanosleep(100);
          SPIN_GUARD(n);
          asm volatile("ld.relaxed.gpu.global.b32 %0, [%1];" : "=r"(v) : "l"(fl) : "memory");
        }
        asm volatile("st.relaxed.gpu.global.b32 [%0], 0;" :: "l"(fl) : "memory");
        mbar_wait(x_done, 0);
      }
#pragma unroll 1
      for (uint32_t layer = 0; layer < 3; layer++) {
        if (w == 10 && layer < 2) {
          if (layer) mbar_wait_sleep(park_free, 0);
          const uint4* img = scratch + OFF_R + j * 2304;
          if (lane_id() == 0) asm volatile("mbarrier.arrive.expect_tx.shared::cta.b64 _, [%0], 27648;\nmbarrier.arrive.expect_tx.shared::cta.b64 _, [%1], 9216;"
                                           :: "r"(rem_full), "r"(piece_full) : "memory");
          __syncwarp();
#pragma unroll 1
          for (uint32_t p = 0; p < 3; p++) {
            bulk_load(sb + REM + p * 9216, img + p * 576 + j * 64, 1024, rem_full, false);
            if (j) bulk_load(sb + REM + p * 9216 + 1024, img + p * 576, j * 1024, rem_full, false);
            bulk_load(sb + REM + p * 9216 + (j + 1) * 1024, img + p * 576 + (j + 1) * 64, (8 - j) * 1024, rem_full, false);
          }
#pragma unroll 1
          for (uint32_t i = 0; i < 12; i++)
            bulk_load(sb + REM + 27648 + (i < 8 ? i * 1024 : 6144 + i * 256), img + 1728 + (i < 8 ? (9 * blk(i) + 1) >> 1 : 9 * i - 68) * 16,
                      i < 8 ? 1024 : 256, piece_full, false);
          if (layer == 0) { fetch_x(sb + PARK, j, xbar0); fetch_x(sb + PARK + STAGE, j + 1, xbar0 + 8); }
        }
        if (w == 11 && layer < 2) {
          if (layer) mbar_wait_sleep(park_free, 0);
          __syncwarp();
          if (lane_id() == 0) mbar_arrive(rem_full);
        }
        if (layer) phase2_duties(layer - 1);
        if (layer == 2) break;
        mbar_wait_sleep(layer ? kv_free : x_done, 0);
        if (t > 0) {
          const uint32_t lane = lane_id(), r = lane >> 2, q = lane & 3;
#pragma unroll 1
          for (uint32_t pc = 0; pc < 3; pc++) {
            uint4* hp = scr + OFF_H + ((layer * 8 + j) * 2 + (w - 10)) * 192 + pc * 64 + lane;
            uint32_t hl[8];
            int n = 0;
            hl[4] = 1u;
#pragma unroll 1
            while (true) {
              ldg4(hl, hp);
              if (pc < 2) ldg4(hl + 4, hp + 32);
              if (__all_sync(~0u, hl[0] != 0u && hl[4] != 0u)) break;
              __nanosleep(100);
              SPIN_GUARD(n);
            }
            const uint32_t dst = sb + KVS + (w - 10) * 10368 + r * 144 + q * 4;
            if (pc < 2) {
#pragma unroll
              for (int g = 0; g < 8; g++) sts1(dst + pc * 20736 + odd * 16 + g * 16, hl[g]);
              stg4(hp + 32, 0u, 0u, 0u, 0u);
            } else {
              sts1(dst + (odd ? 0 : 128), hl[0]); sts1(dst + 20736 + (odd ? 0 : 128), hl[1]);
            }
            stg4(hp, 0u, 0u, 0u, 0u);
          }
        }
        asm volatile("bar.arrive 1, 192;" ::: "memory");
        mbar_wait(rem_full, layer);
        mbar_wait(piece_full, 1 - layer);
#pragma unroll 1
        for (uint32_t b = 0; b < 5; b++) {
          const uint32_t blk = sb + REM + 27648 + b * 2048, k = (w - 10) * 32 + lane_id(), rr = k & 7;
          const uint32_t dst = blk + ((k >> 3) & 1) * 1024 + rr * 128 + (((k >> 4) ^ rr) << 4);
          uint32_t v[8];
          lds4(blk + k * 16, v); lds4(blk + 1024 + k * 16, v + 4);
          asm volatile("bar.sync 3, 64;" ::: "memory");
          sts4(dst, v); sts4(dst ^ 64, v + 4);
        }
        asm volatile("fence.proxy.async.shared::cta;" ::: "memory");
        mbar_arrive(remo_full);
        mbar_wait_sleep(xb_done, layer);
        if (w == 10 && layer == 1) {
          const uint32_t lane = lane_id();
          stg4(scr + OFF_S + (lane >> 3) * 96 + j * 8 + (lane & 7), 0u, 0u, 0u, 0u);
          stg4(scr + OFF_S + (4 + (lane >> 3)) * 96 + j * 8 + (lane & 7), 0u, 0u, 0u, 0u);
          if (lane < 8) stg4(scr + OFF_S + j * 96 + 64 + lane, 0u, 0u, 0u, 0u);
        }
#pragma unroll 1
        for (uint32_t i = 0; i < 8 && (w == 11 || layer == 1); i++) {
          zero_share(scr + OFF_X + ((w - 10) * 16 + layer * 8 + i) * SLAB, j, lane_id());
          __nanosleep(500);
        }
      }
    }
  } else {
    asm volatile("setmaxnreg.inc.sync.aligned.u32 240;");
    const bool lead = lane_id() == 0;
    Ring rg{0, 0};
    uint32_t prev = 0;
    uint32_t X[144];
    float rs0, rs1;
    const bool lead2 = lane_id() < 2;
    uint32_t empty_at;
    asm volatile("mapa.shared::cluster.u32 %0, %1, %2;" : "=r"(empty_at) : "r"(empty0), "r"(lane_id() & 1));
    auto release = [&](uint32_t st) { if (lead2) asm volatile("mbarrier.arrive.shared::cluster.b64 _, [%0];" :: "r"(empty_at + st * 8) : "memory"); };
    auto load_kb = [&](int kb, const uint4* src, const char* lo, uint32_t hoff) {
      const uint4* p;
      asm("{\n.reg .pred p;\n.reg .u64 t;\nsetp.ge.u32 p, %2, %3;\nadd.u64 t, %1, -2048;\nselp.b64 %0, t, %1, p;\n}" : "=l"(p) : "l"(src), "r"(j), "r"(kb));
#pragma unroll
      for (int i = 0; i < 4; i++) {
        if (kb == 8) { ldg2(X + 128 + 4 * i, lo + (32 + i) * 512); ldg2(X + 130 + 4 * i, lo + hoff + (32 + i) * 512); }
        else ldg4(X + 16 * kb + 4 * i, p + kb * 128 + i * 32);
      }
    };
    auto check_kb = [&](bool skip, int kb, const uint4* src, const char* lo, uint32_t hoff) {
      int n = 0;
#pragma unroll 1
      while (true) {
        uint32_t m = umin2(umin2(X[16 * kb], X[16 * kb + 4]), umin2(X[16 * kb + 8], X[16 * kb + 12]));
        if (kb == 8) m = umin2(m, umin2(umin2(X[130], X[134]), umin2(X[138], X[142])));
        if (__all_sync(~0u, m != 0u || skip)) break;
        SPIN_GUARD(n);
        load_kb(kb, src, lo, hoff);
      }
    };
#pragma unroll
    for (int i = 0; i < 16; i++) X[i] = 0u;
#pragma unroll 1
    for (uint32_t hf = 0; hf < 4; hf++) {
      const uint32_t layer = hf >> 1;
      const bool ffn = hf & 1;
      const uint32_t tag = 1 - layer;
      uint4* const xbase = scr + OFF_X + (layer * 8 + w) * SLAB;
      float aA[32], aB[32];
      {
        const uint32_t lane = lane_id(), r = lane >> 2, q = lane & 3;
        const uint4* src = xbase + (ffn ? 32 * SLAB : 0) + lane;
        const char* lo = (const char*)src - (ffn ? lane * 8 : 0);
        const uint32_t hoff = ffn ? 256 : 8;
        const uint32_t xoff = (w & 1) * 8192 + (16 * (w >> 1) + (lane & 15)) * 128 + (((lane >> 4) ^ (lane & 7)) << 4);
        auto load_x = [&](uint32_t b, uint32_t* d) {
#pragma unroll
          for (int i = 0; i < 4; i++) ldsm4(xs + b * STAGE + (xoff ^ (32 * i)), d[4 * i], d[4 * i + 1], d[4 * i + 2], d[4 * i + 3]);
        };
        auto load_any = [&](int kb) { if (hf == 0) load_x(blk(kb), X + 16 * kb); else load_kb(kb, src, lo, hoff); };
        float m0, m1, v0, v1;
        STAMP(ffn * 16 + 0);
        if (hf == 0) {
          float sum[2][4] = {}, sq0[4][4] = {}, sq1[4][4] = {};
          uint32_t p0, p1;
          mbar_wait(xbar0, 0);
          ldsm4(xs + xoff, p0, p1, X[0], X[1]);
          p0 = __byte_perm(__shfl_sync(~0u, p0, lane & 28), 0, 0x1010); p1 = __byte_perm(__shfl_sync(~0u, p1, lane & 28), 0, 0x1010);
#pragma unroll 3
          for (uint32_t b = 0; b < 9; b++) {
            uint32_t d[16];
            mbar_wait(xbar0 + 8 * b, 0);
            load_x(b, d);
#pragma unroll
            for (int i = 0; i < 16; i++) d[i] = sub_bf16x2(d[i], (i & 1) ? p1 : p0);
#pragma unroll
            for (int g = 0; g < 8; g++) {
              if (!(g & 1)) mma16(sum[(g >> 1) & 1], d[2 * g], d[2 * g + 1], d[2 * g + 2], d[2 * g + 3], 0x3f803f80u, 0x3f803f80u);
              mma8(sq0[g & 3], d[2 * g], d[2 * g + 1], d[2 * g]); mma8(sq1[g & 3], d[2 * g], d[2 * g + 1], d[2 * g + 1]);
            }
          }
          STAMP(1);
          GSTAMP(14);
#pragma unroll
          for (int kb = 0; kb < GD; kb++) load_x(blk(kb), X + 16 * kb);
          release((x_ring - empty0) / 8);
          auto tot = [](float (&c)[4][4], int e) { return (c[0][e] + c[1][e]) + (c[2][e] + c[3][e]); };
          const float a0 = (sum[0][0] + sum[1][0]) * (1.f / 576), a1 = (sum[0][2] + sum[1][2]) * (1.f / 576);
          const uint32_t dg = (lane & 28) + (r >> 1);
          v0 = fmaxf(fmaf(__shfl_sync(~0u, (r & 1) ? tot(sq0, 1) : tot(sq0, 0), dg), 1.f / 576, -a0 * a0), 0.f);
          v1 = fmaxf(fmaf(__shfl_sync(~0u, (r & 1) ? tot(sq1, 3) : tot(sq1, 2), dg), 1.f / 576, -a1 * a1), 0.f);
          m0 = bf_lo(p0) + a0; m1 = bf_lo(p1) + a1;
        } else {
          uint32_t s[3][4];
          const uint4* p = scr + OFF_S + ((ffn ? 16 : 0) + w) * 96 + q * 8 + r;
          const bool third = !ffn && q == 0;
          const uint32_t rdy = ffn ? tag : 1u;
          int n = 0;
          s[2][0] = rdy; s[2][1] = s[2][2] = s[2][3] = 0u;
#pragma unroll 1
          while (true) {
            ldg4(s[0], p); ldg4(s[1], p + 32);
            if (third) ldg4(s[2], p + 64);
            if (__all_sync(~0u, ((diff2(s[0][0], s[1][0], rdy) | diff2(s[1][0], s[2][0], rdy)) & 1u) == 0u)) break;
            SPIN_GUARD(n);
          }
          STAMP(ffn * 16 + 1);
          ZSTAMP(1 + ffn, 0);
          GSTAMP(14 + ffn);
#pragma unroll
          for (int kb = 1; kb < GD; kb++) load_kb(kb, src, lo, hoff);
          float t0 = 0.f, t1 = 0.f;
#pragma unroll
          for (int i = 0; i < 3; i++) { t0 += __uint_as_float(s[i][0]); t1 += __uint_as_float(s[i][2]); }
          m0 = quad_sum(t0) * (1.f / 576); m1 = quad_sum(t1) * (1.f / 576);
          const float cnt = ffn ? 72.f : 64.f, inv = ffn ? 1.f / 72 : 1.f / 64;
          v0 = 0.f; v1 = 0.f;
#pragma unroll
          for (int i = 0; i < 3; i++) {
            const float c = (i < 2 || third) ? cnt : 0.f;
            const float d0 = fmaf(__uint_as_float(s[i][0]), inv, -m0), d1 = fmaf(__uint_as_float(s[i][2]), inv, -m1);
            v0 += fmaf(d0 * d0, c, __uint_as_float(s[i][1])); v1 += fmaf(d1 * d1, c, __uint_as_float(s[i][3]));
          }
          v0 = quad_sum(v0) * (1.f / 576); v1 = quad_sum(v1) * (1.f / 576);
        }
        rs0 = rsqrtf(v0 + 1e-5f); rs1 = rsqrtf(v1 + 1e-5f);
        const uint32_t mean0 = pack_bf16(m0, m0), mean1 = pack_bf16(m1, m1);
#pragma unroll
        for (int kb = 0; kb < 9; kb++) {
          if (kb > 0) check_kb(hf == 0, kb, src, lo, hoff);
          if (kb + GD < 9) load_any(kb + GD);
          if (kb + GD == 8 && hf == 0 && lead) mbar_arrive(x_done);
#pragma unroll
          for (int i = 16 * kb; i < 16 * kb + 16; i++) X[i] = sub_bf16x2(X[i], (i & 1) ? mean1 : mean0);
          ZSTAMP(1 + ffn, 1 + 3 * kb);
          mbar_wait(full0 + rg.st * 8, rg.ph);
          ZSTAMP(1 + ffn, 2 + 3 * kb);
          const uint64_t desc = DESC_HI | ((sd + rg.st * STAGE) >> 4);
          wg_fence();
#pragma unroll
          for (int i = 0; i < 4; i++) wgmma_rs_n64(aA, X + 4 * (4 * kb + i), desc + i * 128, kb + i != 0);
          if (kb == 8) { wg_commit(); wg_wait<1>(); wg_fence(); }
#pragma unroll
          for (int i = 0; i < 4; i++) wgmma_rs_n64(aB, X + 4 * (4 * kb + i), desc + 512 + i * 128, kb + i != 0);
          wg_commit();
          wg_wait<1>();
          ZSTAMP(1 + ffn, 3 + 3 * kb);
          if (kb > 0) release(prev);
          prev = rg.st; rg.next();
        }
        ZSTAMP(1 + ffn, 28);
        ZSTAMP(4, 0);
        STAMP(ffn * 16 + 2);
      }
      if (!ffn) {
      const uint32_t lane = lane_id(), r = lane >> 2, q = lane & 3;
      const uint32_t kvrow = sb + KVS + (w & 1) * 10368 + (16 * (w >> 1)) * 144;
      uint32_t Q[18], Km[3][8], Ke[3][4];
      const bool edge = (t == 0 && w < 2);
      const uint32_t row0 = edge ? sb + KVS + 8 * 144 : kvrow + (lane & 7) * 144, row1 = kvrow + (8 + (lane & 7)) * 144;
      {
        const uint32_t dst = kvrow + (8 + r) * 144 + q * 4 + odd * 16, dstr = dst + (odd ? -16 : 128);
        const bool edge_out = w >= 6 && t < 15;
        uint4* const hp = scr + TILE + OFF_H + ((layer * 8 + j) * 2 + (w & 1)) * 192 + lane;
        auto put_kv = [&](float (&a)[32], int part, int half) {
          uint32_t hl[4];
#pragma unroll
          for (int i = 0; i < 16; i++) asm volatile("" : "+f"(a[16 * half + i]) :: "memory");
#pragma unroll
          for (int i = 0; i < 4; i++) {
            const int g = 4 * half + i;
            hl[i] = pack_bf16(a[4 * g + 2] * rs1, a[4 * g + 3] * rs1);
            sts1(dst + part * 20736 + g * 16, pack_bf16(a[4 * g] * rs0, a[4 * g + 1] * rs0)); sts1(dst + part * 20736 + 8 * 144 + g * 16, hl[i]);
          }
          if (edge_out) stg4(hp + part * 64 + half * 32, nz(hl[0]), hl[1], hl[2], hl[3]);
        };
        put_kv(aA, 0, 0); put_kv(aA, 0, 1);
        wg_wait<0>();
        release(prev);
        float aR[12];
        mbar_wait(rem_full, layer);
        const uint64_t dr = DESC_REM | ((sd + REM) >> 4);
        wg_fence();
#pragma unroll
        for (int s = 0; s < 36; s++) {
          wgmma_rs_n24(aR, X + 4 * s, dr + s * 16, s != 0);
          if (s == 4) put_kv(aB, 1, 0);
          if (s == 16) put_kv(aB, 1, 1);
        }
        wg_commit();
#pragma unroll
        for (int kb = 0; kb < 9; kb++) {
          if (!(kb & 1)) mbar_wait(full0 + rg.st * 8, rg.ph);
          const uint64_t desc = DESC_HI | ((sd + rg.st * STAGE + (kb & 1) * 8192) >> 4);
          wg_fence();
#pragma unroll
          for (int i = 0; i < 4; i++) wgmma_rs_n64(aB, X + 4 * (4 * kb + i), desc + i * 128, kb + i != 0);
          wg_commit();
          wg_wait<1>();
          if (kb > 0 && !(kb & 1)) release(prev);
          if (kb & 1) { prev = rg.st; rg.next(); }
          if (kb == 0) {
            pin(aR);
            const uint32_t k1 = pack_bf16(aR[2] * rs1, aR[3] * rs1), v1 = pack_bf16(aR[6] * rs1, aR[7] * rs1);
            if (edge_out) stg4(hp + 128, nz(k1), v1, 0u, 0u);
            sts1(dstr, pack_bf16(aR[0] * rs0, aR[1] * rs0)); sts1(dstr + 8 * 144, k1);
            sts1(dstr + 20736, pack_bf16(aR[4] * rs0, aR[5] * rs0)); sts1(dstr + 20736 + 8 * 144, v1);
            Q[16] = pack_bf16(aR[8], aR[9]); Q[17] = pack_bf16(aR[10], aR[11]);
            if (w < 4) asm volatile("bar.arrive 2, 256;" ::: "memory");
          }
          if (kb == 8) {
            if (w < 4) asm volatile("bar.sync 1, 192;" ::: "memory");
            else asm volatile("bar.sync 2, 256;" ::: "memory");
#pragma unroll
            for (int nt = 0; nt < 3; nt++) {
              const uint32_t ra = (nt == 0 ? row0 : row1 + (nt - 1) * 8 * 144);
              ldsm4(ra + odd * 16 + (lane >> 3) * 16, Km[nt][0], Km[nt][1], Km[nt][2], Km[nt][3]);
              ldsm4(ra + odd * 16 + 64 + (lane >> 3) * 16, Km[nt][4], Km[nt][5], Km[nt][6], Km[nt][7]);
              ldsm4(ra + (odd ? 0 : 32) + (lane >> 3) * 32, Ke[nt][0], Ke[nt][1], Ke[nt][2], Ke[nt][3]);
            }
            const uint32_t ge = (2u << q) - 1, le = 0xfu << q, on = edge ? 0u : ~0u;
            const uint32_t bits = odd ? 0xfu | ((le & 0xfu) << 4) | (ge << 8) : ge | 0xf0u | (le << 8);
#pragma unroll
            for (int h = 0; h < 4; h++) {
              const uint32_t ma = bitmask(bits, h), mb = bitmask(bits, 4 + h), mc = bitmask(bits, 8 + h);
              Km[0][2 * h] &= ma & on; Km[0][2 * h + 1] &= mb & on; Ke[0][h] &= mc & on;
#pragma unroll
              for (int nt = 1; nt < 3; nt++) { Km[nt][2 * h] &= ma; Km[nt][2 * h + 1] &= mb; Ke[nt][h] &= mc; }
            }
          }
        }
        wg_wait<0>();
        pin(aB);
        if (w < 4) asm volatile("bar.sync 4, 256;" ::: "memory");
        STAMP(3);
#pragma unroll
        for (int i = 0; i < 16; i++) Q[i] = pack_bf16(aB[2 * i], aB[2 * i + 1]);
      }
      uint32_t res[18] = {};
      if (layer) {
        const uint4* p = xbase + ((9 * j + 1) >> 1) * 32 + lane;
#pragma unroll
        for (int i = 0; i < 4; i++) ldg4(res + 4 * i, p + i * 32);
        ldg2(res + 16, odd ? (const char*)(p - 32) + 8 : (const char*)(p + 4 * 32));
      }
      {
        uint32_t V01[12][2], V2[12];
        const uint32_t rv = ((lane & 8) ? row1 : row0) + 20736, rw = row1 + 8 * 144 + 20736;
#pragma unroll
        for (int i = 0; i < 4; i++) ldsm4t(rv + odd * 16 + i * 32 + (lane >> 4) * 16, V01[2 * i][0], V01[2 * i][1], V01[2 * i + 1][0], V01[2 * i + 1][1]);
#pragma unroll
        for (int i = 0; i < 2; i++) ldsm4t(rv + (odd ? 0 : 32) + i * 64 + (lane >> 4) * 32, V01[8 + 2 * i][0], V01[8 + 2 * i][1], V01[9 + 2 * i][0], V01[9 + 2 * i][1]);
        ldsm4t(rw + odd * 16 + (lane >> 3) * 16, V2[0], V2[1], V2[2], V2[3]);
        ldsm4t(rw + odd * 16 + 64 + (lane >> 3) * 16, V2[4], V2[5], V2[6], V2[7]);
        ldsm4t(rw + (odd ? 0 : 32) + (lane >> 3) * 32, V2[8], V2[9], V2[10], V2[11]);
        const bool up0 = 2 * q > r, up1 = 2 * q + 1 > r;
        const uint32_t upm = (up0 ? 0xffffu : 0u) | (up1 ? 0xffff0000u : 0u);
        const float c0 = 0.23570226039551584f * 1.4426950408889634f * rs0, c1 = 0.23570226039551584f * 1.4426950408889634f * rs1;
        const float masked = edge ? -1e9f * 1.4426950408889634f * rcp(c0) : 0.f;
        uint32_t Om[16], Oe[8];
        uint4* const po = xbase + 16 * SLAB + 4 * j * 32 + lane;
#pragma unroll
        for (int h = 0; h < 4; h++) {
          const uint32_t e0 = odd ? Q[(4 * h + 16) % 18] : Q[4 * h + 4], e1 = odd ? Q[(4 * h + 17) % 18] : Q[4 * h + 5];
          float S[3][4];
#pragma unroll
          for (int nt = 0; nt < 3; nt++) {
            mma16c(S[nt], Q + 4 * h, Km[nt][2 * h], Km[nt][2 * h + 1], nt == 0 ? masked : 0.f);
            mma8(S[nt], e0, e1, Ke[nt][h]);
          }
          const float s00 = up0 ? S[0][0] : S[1][0], s01 = up1 ? S[0][1] : S[1][1];
          const float s10 = up0 ? S[1][2] : S[2][2], s11 = up1 ? S[1][3] : S[2][3];
          const float m0 = quad_max(fmaxf(s00, s01)) * c0, m1 = quad_max(fmaxf(s10, s11)) * c1;
          const float p00 = ex2(fmaf(s00, c0, -m0)), p01 = ex2(fmaf(s01, c0, -m0)), p10 = ex2(fmaf(s10, c1, -m1)), p11 = ex2(fmaf(s11, c1, -m1));
          const float i0 = rcp(quad_sum(p00 + p01)), i1 = rcp(quad_sum(p10 + p11));
          const uint32_t p0 = pack_bf16(p00 * i0, p01 * i0), p1 = pack_bf16(p10 * i1, p11 * i1);
          const uint32_t pf[4] = {p0 & upm, 0u, p0 & ~upm, p1 & upm};
#pragma unroll
          for (int gi = 0; gi < 3; gi++) {
            const int g = gi < 2 ? 2 * h + gi : 8 + h;
            float o[4];
            mma16c(o, pf, V01[g][0], V01[g][1], 0.f);
            mma8(o, 0u, p1 & ~upm, V2[g]);
            uint32_t* d = gi < 2 ? Om + 2 * g : Oe + 2 * h;
            d[0] = pack_bf16(o[0], o[1]); d[1] = pack_bf16(o[2], o[3]);
          }
          if (h > 0) {
#pragma unroll
            for (int e = 0; e < 2; e++) {
              if (!odd && q < h) Om[4 * h + e] = Oe[2 * h - 2 + e];
              if (odd && q >= h) Om[4 * h - 2 + e] = Oe[2 * h + e];
            }
            stg4(po + (h - 1) * 32, nz(Om[4 * h - 4]), Om[4 * h - 3], Om[4 * h - 2], Om[4 * h - 1]);
            if (h == 1 && w >= 4) asm volatile("bar.arrive 4, 256;" ::: "memory");
          }
        }
        STAMP(4);
        stg4(po + 96, nz(Om[12]), Om[13], Om[14], Om[15]);
        stg2((char*)(xbase + 16 * SLAB + 1024 + j * 16) + lane * 8, nz(odd ? Oe[0] : Oe[6]), odd ? Oe[1] : Oe[7]);
#pragma unroll
        for (int i = 0; i < 16; i++) X[i] = Om[i];
      }
      if (lane == 0) asm volatile("st.relaxed.gpu.global.b32 [%0], %1;" :: "l"(scr + OFF_S + (8 + w) * 96 + j * 8), "r"(tag) : "memory");
      {
        if (layer == 0) {
          const uint32_t xrow = (w & 1) * 8192 + (16 * (w >> 1) + (lane & 15)) * 128;
          uint32_t u0, u1;
          mbar_wait(xbar0, 1); mbar_wait(xbar0 + 8, 1);
#pragma unroll
          for (int i = 0; i < 5; i++) {
            const uint32_t g = i < 4 ? j + odd + 2 * i : j + (odd ? 0 : 8);
            const uint32_t a = sb + PARK + (g >> 3) * STAGE + xrow;
            if (i < 4) ldsm4(a + ((((g & 7) + (lane >> 4)) ^ (lane & 7)) << 4), res[4 * i], res[4 * i + 1], res[4 * i + 2], res[4 * i + 3]);
            else ldsm4(a + (((g & 7) ^ (lane & 7)) << 4), res[16], res[17], u0, u1);
          }
        }
        const uint4* src = xbase + 16 * SLAB + lane;
        const uint32_t st0 = rg.st;
        auto stage_of = [&](uint32_t i) { const uint32_t x = st0 + i; return x >= NST ? x - NST : x; };
        {
          const uint32_t x = st0 + lane, wrap = x >= NST;
          mbar_wait(lane < 5 ? full0 + (x - wrap * NST) * 8 : remo_full, lane < 5 ? rg.ph ^ wrap : layer);
          __syncwarp();
          if (st0) { rg.st = st0 - 1; rg.ph ^= 1; } else rg.st = 5;
        }
        float acc[36];
        auto block72 = [&](uint32_t kb, uint32_t base, const uint32_t* a) {
          const uint64_t d0 = DESC_HI | ((base >> 4) + (((sd + REM + 27648 + (kb >> 1) * 2048 + (kb & 1) * 64 - base) >> 4) << 16));
          wg_fence();
#pragma unroll
          for (int i = 0; i < 4; i++) wgmma_rs_n72(acc, a + 4 * i, d0 - (uint64_t)(i * ((127u << 16) - 128u)), 1);
          wg_commit();
        };
#pragma unroll
        for (int i = 0; i < 18; i++) { acc[2 * i] = bf_lo(res[i]); acc[2 * i + 1] = bf_hi(res[i]); }
        block72(0, sd + st0 * STAGE + 8192, X);
        {
          const uint4* fp = scr + OFF_S + (8 + w) * 96 + (lane & 7) * 8;
          int n = 0;
          STAMP(8);
#pragma unroll 1
          while (true) {
            uint32_t f;
            asm volatile("ld.relaxed.gpu.global.b32 %0, [%1];" : "=r"(f) : "l"(fp) : "memory");
            if (__all_sync(~0u, f == tag)) break;
            SPIN_GUARD(n);
          }
          wg_wait<0>(); release(st0);
          STAMP(9);
        }
#pragma unroll
        for (int kb = 1; kb < GO; kb++) load_kb(kb, src, (const char*)src - lane * 8, 256);
        __syncwarp();
        uint32_t m = ~0u;
#pragma unroll
        for (int kb = 1; kb < 9; kb++) {
          m = umin2(m, umin2(umin2(X[16 * kb], X[16 * kb + 4]), umin2(X[16 * kb + 8], X[16 * kb + 12])));
          if (kb == 8) m = umin2(m, umin2(umin2(X[130], X[134]), umin2(X[138], X[142])));
          if (kb + GO - 1 < 9) {
            const uint4* s2 = src + (m == 0u);
            load_kb(kb + GO - 1, s2, (const char*)s2 - lane * 8, 256);
            __syncwarp();
          }
          block72(kb, sd + stage_of((kb + 1) >> 1) * STAGE + (~kb & 1) * 8192, X + 16 * kb);
          if ((kb & 1) && kb > 1) { wg_wait<1>(); release(stage_of(kb >> 1)); }
        }
        uint32_t redo;
        asm volatile("{\n.reg .pred p;\nsetp.eq.u32 p, %1, 0;\nbar.red.or.pred p, %2, 128, p;\nselp.u32 %0, 1, 0, p;\n}" : "=r"(redo) : "r"(m), "r"(5 + (w >> 2)) : "memory");
        wg_wait<0>();
        release(stage_of(4));
        pin(acc);
        if (__any_sync(~0u, redo || FORCE_REDO)) {
#pragma unroll
          for (int i = 0; i < 18; i++) { res[i] = __shfl_sync(~0u, res[i], lane); acc[2 * i] = bf_lo(res[i]); acc[2 * i + 1] = bf_hi(res[i]); }
          const uint32_t box = PARK + 2 * STAGE + (w >> 2) * 8192, bar = redo_full + (w >> 2) * 8;
#pragma unroll 1
          for (uint32_t kb = 0; kb < 10; kb++) {
            asm volatile("bar.sync %0, 128;" :: "r"(5 + (w >> 2)) : "memory");
            if ((w & 3) == 0)
              asm volatile("{\n.reg .pred e;\nelect.sync _|e, 0xffffffff;\n@e mbarrier.arrive.expect_tx.shared::cta.b64 _, [%2], 8192;\n"
                           "@e cp.async.bulk.tensor.3d.shared::cluster.global.mbarrier::complete_tx::bytes [%0], [%1, {%3, %4, %5}], [%2];\n}"
                           :: "r"(sb + box), "l"(&maps.m[kb >= 8 ? 8 : 1]), "r"(bar), "r"(72 * j + 8 * odd), "r"(kb >= 8 ? 64 : 0),
                              "r"(kb >= 8 ? 0 : (9 * blk(kb) + 1) >> 1) : "memory");
            mbar_wait(bar, kb & 1);
            if (kb == 9) break;
            int n = 0;
#pragma unroll 1
            while (true) {
              const char* l = (const char*)(src + blk(kb) * 128) - (kb == 8 ? lane * 8 : 0);
#pragma unroll
              for (int i = 0; i < 4; i++) ldg2(X + 4 * i, l + i * 512);
              uint32_t mm = umin2(umin2(X[0], X[4]), umin2(X[8], X[12]));
              l += (kb == 8 ? 256 : 8) + (mm == 0u ? 16 : 0);
#pragma unroll
              for (int i = 0; i < 4; i++) ldg2(X + 4 * i + 2, l + i * 512);
              if (kb == 8) mm = umin2(mm, umin2(umin2(X[2], X[6]), umin2(X[10], X[14])));
              if (__all_sync(~0u, mm != 0u)) break;
              SPIN_GUARD(n);
            }
            block72(kb, sd + box, X);
            wg_wait<0>();
            pin(acc);
          }
        }
        STAMP(10);
#pragma unroll
        for (int i = 0; i < 18; i++) res[i] = pack_bf16(acc[2 * i], acc[2 * i + 1]);
        if (j < PRI) put72(xbase + 32 * SLAB, j, lane, res);
        publish_stats<9>(scr + OFF_S + (16 + w) * 96 + j * 8, acc, tag, lane);
        if (j >= PRI) put72(xbase + 32 * SLAB, j, lane, res);
#pragma unroll
        for (int i = 0; i < 16; i++) X[i] = res[i];
      }
      continue;
      }
      const uint32_t hp = sb + PARK + w * 512 + lane_id() * 16;
      auto pack8 = [&](float (&a)[32], int p, uint32_t* o) {
#pragma unroll
        for (int e = 0; e < 8; e++) asm volatile("" : "+f"(a[8 * p + e]) :: "memory");
#pragma unroll
        for (int e = 0; e < 4; e++) o[e] = pack_bf16(a[8 * p + 2 * e], a[8 * p + 2 * e + 1]);
      };
      const float ka0 = 0.7978845608028654f * rs0, kb0 = 0.044715f * ka0 * rs0 * rs0, ku0 = 0.5f * rs0 * rs0;
      const float ka1 = 0.7978845608028654f * rs1, kb1 = 0.044715f * ka1 * rs1 * rs1, ku1 = 0.5f * rs1 * rs1;
      auto packu8 = [&](int p, uint32_t* o) {
#pragma unroll
        for (int e = 0; e < 8; e++) asm volatile("" : "+f"(aA[8 * p + e]) :: "memory");
#pragma unroll
        for (int e = 0; e < 4; e++) o[e] = pack_bf16(aA[8 * p + 2 * e] * ((e & 1) ? ku1 : ku0), aA[8 * p + 2 * e + 1] * ((e & 1) ? ku1 : ku0));
      };
      auto geglu8 = [&](int p, uint32_t* u) {
#pragma unroll
        for (int e = 0; e < 8; e++) asm volatile("" : "+f"(aB[8 * p + e]) :: "memory");
        float h[8];
#pragma unroll
        for (int e = 0; e < 8; e++) {
          const float g = aB[8 * p + e];
          h[e] = fmaf(g, tanh_ap(g * fmaf(g * g, (e & 2) ? kb1 : kb0, (e & 2) ? ka1 : ka0)), g);
        }
#pragma unroll
        for (int e = 0; e < 4; e++) u[e] = mul_bf16x2(pack_bf16(h[2 * e], h[2 * e + 1]), u[e]);
      };
      uint32_t ready = 0;
      auto box = [&](int b, auto&& filler) {
        const int kb = b < 9 ? b : b - 9;
        if (b == 0) mbar_wait_trap(full0 + rg.st * 8, rg.ph);
        else if (!(b & 1)) mbar_wait_unless(ready, full0 + rg.st * 8, rg.ph);
        const uint64_t desc = DESC_HI | ((sd + rg.st * STAGE + (b & 1) * 8192) >> 4);
        if (b & 1) { prev = rg.st; rg.next(); }
        wg_fence();
#pragma unroll
        for (int i = 0; i < 4; i++) {
          if (b < 9) wgmma_rs_n64(aA, X + 4 * (4 * kb + i), desc + i * 128, kb + i != 0);
          else wgmma_rs_n64(aB, X + 4 * (4 * kb + i), desc + i * 128, kb + i != 0);
          if ((b & 1) && b < 17 && i == 0) ready = mbar_peek(full0 + rg.st * 8, rg.ph);
          if (i == 1) filler();
        }
        wg_commit();
        if (!(b & 1)) { wg_wait<1>(); release(prev); }
      };
      auto nop = [] {};
      auto step = [&](int st, auto&& filler) { box(2 * st, nop); box(2 * st + 1, filler); };
#pragma unroll
      for (int p = 0; p < 4; p++) { uint32_t o[4]; packu8(p, o); sts4(hp + p * 4096, o); }
      box(0, nop);
      if (lead) mbar_arrive(xb_done);
#pragma unroll 1
      for (int c = 1;; c++) {
        const uint32_t hc = hp + c * 4 * 4096;
#pragma unroll
        for (int b = 1; b < 18; b++) box(b, [&] {
          if ((b & 1) && b < 8) { uint32_t o[4]; const uint32_t a = hc - (4 - (b >> 1)) * 4096; lds4(a, o); geglu8(b >> 1, o); sts4(a, o); }
          if ((b & 1) && b > 10) { uint32_t o[4]; packu8((b - 11) >> 1, o); if (c < 8) sts4(hc + ((b - 11) >> 1) * 4096, o); } });
        ZSTAMP(4, c);
        if (c == 8) break;
        box(0, nop);
      }
      wg_wait<0>();
      STAMP(21);
      GSTAMP(19);
      auto unpark = [&](int kb) {
#pragma unroll
        for (int s = 4 * kb; s < 4 * kb + 4; s++) lds4(hp + s * 4096, X + 4 * s);
      };
      unpark(0);
      uint32_t U[16];
#pragma unroll
      for (int p = 0; p < 4; p++) packu8(p, U + 4 * p);
#pragma unroll
      for (int b = 0; b < 8; b++) box(b, [&] {
        if (b < 7) unpark(b + 1);
        if (b & 1) {
          geglu8(b >> 1, U + 2 * (b - 1));
          if (rg.ph > 1) sts4(hp, U + 2 * (b - 1));
#pragma unroll
          for (int i = 0; i < 4; i++) X[128 + 2 * (b - 1) + i] = U[2 * (b - 1) + i];
        } });
      STAMP(24);
      if (layer == 0 && lead) mbar_arrive(park_free);
      const uint32_t lane2 = lane_id();
      uint4* const pw = scr + OFF_P + (j * 8 + w) * SLAB + lane2;
      const uint4* const pr = scr + OFF_P + w * SLAB + 4 * j * 32 + lane2;
      auto put_part = [&](float (&a)[32], int p, uint32_t chunk) {
        uint32_t o[4];
        pack8(a, p, o);
        stg4(pw + (chunk * 4 + p) * 32, (o[0] & ~1u) | tag, o[1], o[2], o[3]);
      };
      auto slot = [&](int p) { return sb + w * 2048 + (p < 3 ? PARK + p * 16384 : KVS + (p - 3) * 16384); };
      auto fetch = [&](int p) {
        bulk_load(slot(p), scr + OFF_P + (((j - p) & 7) * 8 + w) * SLAB + 4 * j * 32, 2048, pbar0 + w * 8, true);
      };
#pragma unroll 1
      for (int sp = 0;; sp++) {
        const uint32_t ca = sp == 0 ? 8 : ((j + 2 * sp) & 7), cb = (j + 2 * sp + 1) & 7;
        if (sp == 1 && lead) mbar_arrive(c8_go);
#pragma unroll
        for (int st = 4; st < 9; st++) step(st, [&] {
          if (st == 5 || st == 6) { put_part(aA, 2 * (st - 5), ca); put_part(aA, 2 * (st - 5) + 1, ca); }
          if (st == 8 && sp > 1) { if (sp == 3) mbar_wait(c8_done, layer); fetch(2 * sp - 2); } });
        STAMP(25 + sp);
        if (sp == 3) break;
#pragma unroll
        for (int st = 0; st < 4; st++) step(st, [&] {
          if (st < 2) { put_part(aB, 2 * st, cb); put_part(aB, 2 * st + 1, cb); }
          if (st == 3 && sp > 0) fetch(2 * sp - 1); });
      }
      auto load_p = [&](int p, uint32_t* d) {
#pragma unroll
        for (int i = 0; i < 4; i++) ldg4(d + 4 * i, pr + ((j - p) & 7) * 8 * SLAB + i * 32);
      };
#pragma unroll
      for (int b = 0; b < 9; b++) {
        box(b, [&] {
          if (b == 1) {
#pragma unroll
            for (int p = 0; p < 4; p++) put_part(aB, p, (j + 7) & 7);
          }
          if (b == 3) { load_p(5, X); load_p(6, X + 16); }
          if (b == 7) load_p(7, X + 32); });
      }
      mbar_wait(res_full, layer);
      mbar_wait(pbar0 + w * 8, layer);
#pragma unroll
      for (int p = 1; p < 5; p++)
#pragma unroll
        for (int i = 0; i < 4; i++) lds4(slot(p) + lane2 * 16 + i * 512, X + 48 + 16 * p + 4 * i);
#pragma unroll
      for (int i = 0; i < 4; i++) {
        const bool split = j == 2 * i + 1;
        const uint32_t a = slot(0) + i * 512 + (split ? lane2 * 8 : lane2 * 16);
        lds2(a, X + 48 + 4 * i); lds2(a + (split ? 256 : 8), X + 50 + 4 * i);
      }
      wg_wait<0>();
      release(rg.st); rg.next();
      pin(aA);
      STAMP(22);
      GSTAMP(20);
      {
        const uint32_t lane = lane2, r = lane >> 2, q = lane & 3;
        const uint32_t eye = r == 2 * q ? 0x3f80u : r == 2 * q + 1 ? 0x3f800000u : 0u;
        auto bad = [&](const uint32_t* d) { return diff2(d[0], d[4], tag) | diff2(d[8], d[12], tag); };
        auto add = [&](const uint32_t* d) {
#pragma unroll
          for (int g = 0; g < 8; g++) mma8(aA + 4 * g, d[2 * g], d[2 * g + 1], eye);
        };
        int n = 0;
#pragma unroll 1
        while (!__all_sync(~0u, ((or3(bad(X), bad(X + 16), bad(X + 64)) | or3(bad(X + 80), bad(X + 96), bad(X + 112))) & 1u) == 0u)) {
          SPIN_GUARD(n);
          load_p(5, X); load_p(6, X + 16);
#pragma unroll
          for (int p = 1; p < 5; p++) load_p(p, X + 48 + 16 * p);
        }
        add(X); add(X + 16);
#pragma unroll
        for (int p = 4; p >= 0; p--) add(X + 48 + 16 * ((p + 1) % 5));
        STAMP(11);
#pragma unroll 1
        while (!__all_sync(~0u, (bad(X + 32) & 1u) == 0u)) { SPIN_GUARD(n); load_p(7, X + 32); }
        add(X + 32);
        STAMP(12);
        uint32_t res[16];
#pragma unroll
        for (int i = 0; i < 16; i++) X[i] = res[i] = pack_bf16(aA[2 * i], aA[2 * i + 1]);
        if (layer == 0) {
          uint4* p = xbase + 8 * SLAB + 4 * j * 32 + lane;
          auto put = [&] {
#pragma unroll
            for (int i = 0; i < 4; i++) stg4(p + i * 32, nz(res[4 * i]), res[4 * i + 1], res[4 * i + 2], res[4 * i + 3]);
          };
          if (j < PRI) put();
          publish_stats<8>(scr + OFF_S + w * 96 + j * 8, aA, 1u, lane);
          if (j >= PRI) put();
          if (lane == 0) mbar_arrive(kv_free);
        } else {
          const uint32_t tb = slot(0);
          __syncwarp();
#pragma unroll
          for (int i = 0; i < 4; i++) {
            const uint32_t row = (lane2 & 7) + (lane2 & 8), g = 2 * i + (lane2 >> 4);
            asm volatile("stmatrix.sync.aligned.m8n8.x4.shared.b16 [%0], {%1,%2,%3,%4};"
                         :: "r"(tb + row * 128 + ((g ^ (row & 7)) << 4)), "r"(res[4 * i]), "r"(res[4 * i + 1]), "r"(res[4 * i + 2]), "r"(res[4 * i + 3]) : "memory");
          }
          __syncwarp();
#pragma unroll
          for (int i = 0; i < 4; i++) {
            const uint32_t row = 4 * i + (lane2 >> 3), g = lane2 & 7;
            uint32_t v[4];
            lds4(tb + row * 128 + ((g ^ (row & 7)) << 4), v);
            *(uint4*)(out + (128 * t + 32 * (w >> 1) + 2 * row + (w & 1)) * 576 + 64 * j + 8 * g) = make_uint4(v[0], v[1], v[2], v[3]);
          }
        }
      }
      STAMP(23);
    }
  }
}

typedef CUresult (*EncodeFn)(CUtensorMap*, CUtensorMapDataType, cuuint32_t, void*, const cuuint64_t*, const cuuint64_t*,
                             const cuuint32_t*, const cuuint32_t*, CUtensorMapInterleave, CUtensorMapSwizzle,
                             CUtensorMapL2promotion, CUtensorMapFloatOOBfill);

CUtensorMap make_map(EncodeFn f, const void* p, uint64_t cols, uint64_t rows, uint64_t grp) {
  CUtensorMap m;
  cuuint64_t dims[3] = {cols, grp, rows / grp}, str[2] = {cols * 2, cols * 2 * grp};
  cuuint32_t box[3] = {64, 16, 4}, es[3] = {1, 1, 1};
  f(&m, CU_TENSOR_MAP_DATA_TYPE_BFLOAT16, 3, const_cast<void*>(p), dims, str, box, es, CU_TENSOR_MAP_INTERLEAVE_NONE,
    CU_TENSOR_MAP_SWIZZLE_128B, CU_TENSOR_MAP_L2_PROMOTION_NONE, CU_TENSOR_MAP_FLOAT_OOB_FILL_NONE);
  return m;
}
CUtensorMap make_rem_map(EncodeFn f, const void* p, uint64_t cols) {
  CUtensorMap m;
  cuuint64_t dims[2] = {cols, 576}, str[1] = {cols * 2};
  cuuint32_t box[2] = {8, 144}, es[2] = {1, 1};
  f(&m, CU_TENSOR_MAP_DATA_TYPE_BFLOAT16, 2, const_cast<void*>(p), dims, str, box, es, CU_TENSOR_MAP_INTERLEAVE_NONE,
    CU_TENSOR_MAP_SWIZZLE_NONE, CU_TENSOR_MAP_L2_PROMOTION_NONE, CU_TENSOR_MAP_FLOAT_OOB_FILL_NONE);
  return m;
}

}

extern "C" void kernel_launch(void* const* d_in, const int* in_sizes, int n_in, void* d_out, int out_size) {
  void* fn = nullptr;
  cudaDriverEntryPointQueryResult qr;
  cudaGetDriverEntryPoint("cuTensorMapEncodeTiled", &fn, cudaEnableDefault, &qr);
  EncodeFn enc = (EncodeFn)fn;
  Maps maps;
  maps.m[0] = make_map(enc, d_in[1], 1728, 576, 16); maps.m[1] = make_map(enc, d_in[2], 576, 576, 16);
  maps.m[2] = make_map(enc, d_in[4], 4608, 576, 16); maps.m[3] = make_map(enc, d_in[5], 4608, 576, 16);
  maps.m[4] = make_map(enc, d_in[6], 576, 4608, 16);
  maps.m[5] = make_rem_map(enc, d_in[1], 1728); maps.m[6] = make_rem_map(enc, d_in[2], 576);
  maps.m[8] = make_map(enc, d_in[2], 576, 576, 144); maps.m[9] = make_map(enc, d_in[4], 4608, 576, 144);
  maps.m[10] = make_map(enc, d_in[5], 4608, 576, 144);
  {
    cuuint64_t dims[3] = {576, 1024, 2}, str[2] = {2304, 1152};
    cuuint32_t box[3] = {64, 64, 2}, es[3] = {1, 1, 1};
    enc(&maps.m[7], CU_TENSOR_MAP_DATA_TYPE_BFLOAT16, 3, d_in[0], dims, str, box, es, CU_TENSOR_MAP_INTERLEAVE_NONE,
        CU_TENSOR_MAP_SWIZZLE_128B, CU_TENSOR_MAP_L2_PROMOTION_NONE, CU_TENSOR_MAP_FLOAT_OOB_FILL_NONE);
  }
  void* scr = nullptr;
  cudaGetSymbolAddress(&scr, g_scratch);
  cudaFuncSetAttribute(mega_kernel, cudaFuncAttributeMaxDynamicSharedMemorySize, SMEM_BYTES);
  cudaLaunchConfig_t cfg = {};
  cfg.gridDim = dim3(128); cfg.blockDim = dim3(384); cfg.dynamicSmemBytes = SMEM_BYTES; cfg.stream = cudaStreamPerThread;
  cudaLaunchAttribute at[1];
  at[0].id = cudaLaunchAttributeClusterDimension; at[0].val.clusterDim.x = 2; at[0].val.clusterDim.y = 1; at[0].val.clusterDim.z = 1;
  cfg.attrs = at; cfg.numAttrs = 1;
  int dev = 0, sms = 0, clusters = 0;
  cudaGetDevice(&dev);
  cudaDeviceGetAttribute(&sms, cudaDevAttrMultiProcessorCount, dev);
  cudaOccupancyMaxActiveClusters(&clusters, mega_kernel, &cfg);
  if (sms == 132 && clusters == 66) cfg.gridDim = dim3(132);
  cudaLaunchKernelEx(&cfg, mega_kernel, maps, (uint4*)scr, (__nv_bfloat16*)d_out);
}
```

```cpp
#include <cuda_runtime.h>
#include <cuda.h>
#include <cuda_bf16.h>
#include <stdint.h>

#define TRACE 0
#define GUARD 0
#define FORCE_REDO 0
#define ZT 0

namespace {

constexpr int NST = 6;
constexpr int STAGE = 16384;
constexpr int PARK = NST * STAGE;
constexpr int REM = PARK + 49152;
constexpr int KVS = REM + 40960;
constexpr int PIECE = PARK + 7 * STAGE;
constexpr int HSTG = KVS + 16384;
constexpr int BARS = KVS + 41472;
constexpr int TRC = BARS + 512;
constexpr int SMEM_BYTES = TRC + (TRACE ? 512 : 0);
static_assert(NST == 6, "the producer addresses empty barriers as full + 48");
static_assert(BARS >= PARK + 131072, "barriers overlap park");
static_assert(SMEM_BYTES <= 232448, "smem");

constexpr int SLAB = 36 * 32;
constexpr int SPIN_MAX = 1 << 17;
constexpr uint32_t PRI = 4;
constexpr int GD = 3, GO = 5;
constexpr int OFF_S = 0;
constexpr int OFF_H = OFF_S + 3 * 8 * 96;
constexpr int OFF_X = OFF_H + 2 * 8 * 384;
constexpr int OFF_P = OFF_X + 6 * 8 * SLAB;
constexpr int TILE = OFF_P + 8 * 8 * SLAB;
constexpr int OFF_R = 16 * TILE;
constexpr int OFF_F = OFF_R + 8 * 2304;
constexpr int SCRATCH = OFF_F + 128 * 8;

}

__device__ uint4 g_scratch[SCRATCH];

namespace {

constexpr uint64_t DESC_HI = 0x4000004000000000ull;
constexpr uint64_t DESC_REM = (576ull << 32) | (8u << 16);
__device__ __forceinline__ void wgmma_rs_n64(float (&d)[32], const uint32_t* a, uint64_t desc, int scale_d) {
  asm volatile("{\n.reg .pred p;\nsetp.ne.b32 p, %37, 0;\n"
    "wgmma.mma_async.sync.aligned.m64n64k16.f32.bf16.bf16 "
    "{%0, %1, %2, %3, %4, %5, %6, %7, %8, %9, %10, %11, %12, %13, %14, %15, %16, %17, %18, %19, %20, %21, %22, %23, %24, %25, %26, %27, %28, %29, %30, %31}, "
    "{%32, %33, %34, %35}, %36, p, 1, 1, 1;\n}\n"
    : "+f"(d[0]), "+f"(d[1]), "+f"(d[2]), "+f"(d[3]), "+f"(d[4]), "+f"(d[5]), "+f"(d[6]), "+f"(d[7]), "+f"(d[8]), "+f"(d[9]), "+f"(d[10]), "+f"(d[11]), "+f"(d[12]), "+f"(d[13]), "+f"(d[14]), "+f"(d[15]), "+f"(d[16]), "+f"(d[17]), "+f"(d[18]), "+f"(d[19]), "+f"(d[20]), "+f"(d[21]), "+f"(d[22]), "+f"(d[23]), "+f"(d[24]), "+f"(d[25]), "+f"(d[26]), "+f"(d[27]), "+f"(d[28]), "+f"(d[29]), "+f"(d[30]), "+f"(d[31])
    : "r"(a[0]), "r"(a[1]), "r"(a[2]), "r"(a[3]), "l"(desc), "r"(scale_d));
}
__device__ __forceinline__ void wgmma_rs_n72(float (&d)[36], const uint32_t* a, uint64_t desc, int scale_d) {
  asm volatile("{\n.reg .pred p;\nsetp.ne.b32 p, %41, 0;\n"
    "wgmma.mma_async.sync.aligned.m64n72k16.f32.bf16.bf16 "
    "{%0, %1, %2, %3, %4, %5, %6, %7, %8, %9, %10, %11, %12, %13, %14, %15, %16, %17, %18, %19, %20, %21, %22, %23, %24, %25, %26, %27, %28, %29, %30, %31, %32, %33, %34, %35}, "
    "{%36, %37, %38, %39}, %40, p, 1, 1, 1;\n}\n"
    : "+f"(d[0]), "+f"(d[1]), "+f"(d[2]), "+f"(d[3]), "+f"(d[4]), "+f"(d[5]), "+f"(d[6]), "+f"(d[7]), "+f"(d[8]), "+f"(d[9]), "+f"(d[10]), "+f"(d[11]), "+f"(d[12]), "+f"(d[13]), "+f"(d[14]), "+f"(d[15]), "+f"(d[16]), "+f"(d[17]), "+f"(d[18]), "+f"(d[19]), "+f"(d[20]), "+f"(d[21]), "+f"(d[22]), "+f"(d[23]), "+f"(d[24]), "+f"(d[25]), "+f"(d[26]), "+f"(d[27]), "+f"(d[28]), "+f"(d[29]), "+f"(d[30]), "+f"(d[31]), "+f"(d[32]), "+f"(d[33]), "+f"(d[34]), "+f"(d[35])
    : "r"(a[0]), "r"(a[1]), "r"(a[2]), "r"(a[3]), "l"(desc), "r"(scale_d));
}
__device__ __forceinline__ void wgmma_rs_n24(float (&d)[12], const uint32_t* a, uint64_t desc, int scale_d) {
  asm volatile("{\n.reg .pred p;\nsetp.ne.b32 p, %17, 0;\n"
    "wgmma.mma_async.sync.aligned.m64n24k16.f32.bf16.bf16 "
    "{%0, %1, %2, %3, %4, %5, %6, %7, %8, %9, %10, %11}, "
    "{%12, %13, %14, %15}, %16, p, 1, 1, 1;\n}\n"
    : "+f"(d[0]), "+f"(d[1]), "+f"(d[2]), "+f"(d[3]), "+f"(d[4]), "+f"(d[5]), "+f"(d[6]), "+f"(d[7]), "+f"(d[8]), "+f"(d[9]), "+f"(d[10]), "+f"(d[11])
    : "r"(a[0]), "r"(a[1]), "r"(a[2]), "r"(a[3]), "l"(desc), "r"(scale_d));
}

__device__ __forceinline__ void mbar_init(uint32_t a, uint32_t c) { asm volatile("mbarrier.init.shared::cta.b64 [%0], %1;" :: "r"(a), "r"(c)); }
__device__ __forceinline__ void mbar_arrive(uint32_t a) { asm volatile("mbarrier.arrive.shared::cta.b64 _, [%0];" :: "r"(a) : "memory"); }
__device__ __forceinline__ void mbar_wait_trap(uint32_t a, uint32_t ph) {
  asm volatile("{\n.reg .pred p;\n.reg .u32 n;\nmov.u32 n, 0;\n"
               "W: mbarrier.try_wait.parity.shared::cta.b64 p, [%0], %1;\n@p bra D;\n"
               "add.u32 n, n, 1;\nsetp.lt.u32 p, n, 4194304;\n@p bra W;\ntrap;\nD:\n}" :: "r"(a), "r"(ph) : "memory");
}
__device__ __forceinline__ void mbar_wait(uint32_t a, uint32_t ph) {
  asm volatile("{\n.reg .pred p;\nW: mbarrier.try_wait.parity.shared::cta.b64 p, [%0], %1;\n@!p bra W;\n}" :: "r"(a), "r"(ph) : "memory");
}
__device__ __forceinline__ uint32_t mbar_peek(uint32_t a, uint32_t ph) {
  uint32_t r;
  asm volatile("{\n.reg .pred p;\nmbarrier.test_wait.parity.shared::cta.b64 p, [%1], %2;\nselp.u32 %0, 1, 0, p;\n}" : "=r"(r) : "r"(a), "r"(ph) : "memory");
  return r;
}
__device__ __forceinline__ void mbar_wait_unless(uint32_t ready, uint32_t a, uint32_t ph) {
  asm volatile("{\n.reg .pred p;\nsetp.ne.u32 p, %2, 0;\n@p bra D;\nW: mbarrier.try_wait.parity.shared::cta.b64 p, [%0], %1;\n@!p bra W;\nD:\n}"
               :: "r"(a), "r"(ph), "r"(ready) : "memory");
}
__device__ __forceinline__ void mbar_wait_sleep(uint32_t a, uint32_t ph) {
  asm volatile("{\n.reg .pred p;\nW: mbarrier.test_wait.parity.shared::cta.b64 p, [%0], %1;\n@p bra D;\nnanosleep.u32 500;\nbra W;\nD:\n}" :: "r"(a), "r"(ph) : "memory");
}
__device__ __forceinline__ void wg_fence() { asm volatile("wgmma.fence.sync.aligned;" ::: "memory"); }
__device__ __forceinline__ void wg_commit() { asm volatile("wgmma.commit_group.sync.aligned;" ::: "memory"); }
template <int N> __device__ __forceinline__ void wg_wait() { asm volatile("wgmma.wait_group.sync.aligned %0;" :: "n"(N) : "memory"); }
__device__ __forceinline__ float tanh_ap(float x) { float y; asm("tanh.approx.f32 %0, %1;" : "=f"(y) : "f"(x)); return y; }
__device__ __forceinline__ float ex2(float x) { float y; asm("ex2.approx.ftz.f32 %0, %1;" : "=f"(y) : "f"(x)); return y; }
__device__ __forceinline__ uint32_t pack_bf16(float lo, float hi) { uint32_t r; asm("cvt.rn.bf16x2.f32 %0, %1, %2;" : "=r"(r) : "f"(hi), "f"(lo)); return r; }
__device__ __forceinline__ float bf_lo(uint32_t v) { return __uint_as_float(v << 16); }
__device__ __forceinline__ float bf_hi(uint32_t v) { return __uint_as_float(v & 0xffff0000u); }
__device__ __forceinline__ uint32_t sub_bf16x2(uint32_t a, uint32_t b) { uint32_t r; asm("sub.rn.bf16x2 %0, %1, %2;" : "=r"(r) : "r"(a), "r"(b)); return r; }
__device__ __forceinline__ uint32_t mul_bf16x2(uint32_t a, uint32_t b) { uint32_t r; asm("mul.rn.bf16x2 %0, %1, %2;" : "=r"(r) : "r"(a), "r"(b)); return r; }
__device__ __forceinline__ uint32_t diff2(uint32_t a, uint32_t b, uint32_t t) { uint32_t r; asm("lop3.b32 %0, %1, %2, %3, 0x7e;" : "=r"(r) : "r"(a), "r"(b), "r"(t)); return r; }
__device__ __forceinline__ uint32_t or3(uint32_t a, uint32_t b, uint32_t c) { uint32_t r; asm("lop3.b32 %0, %1, %2, %3, 0xfe;" : "=r"(r) : "r"(a), "r"(b), "r"(c)); return r; }
__device__ __forceinline__ uint32_t umin2(uint32_t a, uint32_t b) { uint32_t r; asm("min.u32 %0, %1, %2;" : "=r"(r) : "r"(a), "r"(b)); return r; }
__device__ __forceinline__ uint32_t bitmask(uint32_t v, int bit) { uint32_t r; asm("bfe.s32 %0, %1, %2, 1;" : "=r"(r) : "r"(v), "r"(bit)); return r; }
__device__ __forceinline__ uint32_t nz(uint32_t w) { return w == 0u ? 0x8000u : w; }

__device__ __forceinline__ void ldg4(uint32_t* d, const uint4* p) {
  asm volatile("ld.relaxed.gpu.global.v4.b32 {%0,%1,%2,%3}, [%4];" : "=r"(d[0]), "=r"(d[1]), "=r"(d[2]), "=r"(d[3]) : "l"(p) : "memory");
}
__device__ __forceinline__ void ldg2(uint32_t* d, const void* p) {
  asm volatile("ld.relaxed.gpu.global.v2.b32 {%0,%1}, [%2];" : "=r"(d[0]), "=r"(d[1]) : "l"(p) : "memory");
}
__device__ __forceinline__ void stg4(uint4* p, uint32_t a, uint32_t b, uint32_t c, uint32_t d) {
  asm volatile("st.relaxed.gpu.global.v4.b32 [%0], {%1,%2,%3,%4};" :: "l"(p), "r"(a), "r"(b), "r"(c), "r"(d) : "memory");
}
__device__ __forceinline__ void stg2(void* p, uint32_t a, uint32_t b) {
  asm volatile("st.relaxed.gpu.global.v2.b32 [%0], {%1,%2};" :: "l"(p), "r"(a), "r"(b) : "memory");
}
__device__ __forceinline__ void sts4(uint32_t a, const uint32_t* o) { asm volatile("st.shared.v4.b32 [%0], {%1,%2,%3,%4};" :: "r"(a), "r"(o[0]), "r"(o[1]), "r"(o[2]), "r"(o[3]) : "memory"); }
__device__ __forceinline__ void lds4(uint32_t a, uint32_t* o) { asm volatile("ld.shared.v4.b32 {%0,%1,%2,%3}, [%4];" : "=r"(o[0]), "=r"(o[1]), "=r"(o[2]), "=r"(o[3]) : "r"(a) : "memory"); }
__device__ __forceinline__ void lds2(uint32_t a, uint32_t* o) { asm volatile("ld.shared.v2.b32 {%0,%1}, [%2];" : "=r"(o[0]), "=r"(o[1]) : "r"(a) : "memory"); }
__device__ __forceinline__ float rcp(float x) { float y; asm("rcp.approx.ftz.f32 %0, %1;" : "=f"(y) : "f"(x)); return y; }
__device__ __forceinline__ void sts1(uint32_t a, uint32_t v) { asm volatile("st.shared.b32 [%0], %1;" :: "r"(a), "r"(v) : "memory"); }
__device__ __forceinline__ void ldsm4(uint32_t a, uint32_t& r0, uint32_t& r1, uint32_t& r2, uint32_t& r3) {
  asm volatile("ldmatrix.sync.aligned.m8n8.x4.shared.b16 {%0,%1,%2,%3}, [%4];" : "=r"(r0), "=r"(r1), "=r"(r2), "=r"(r3) : "r"(a) : "memory");
}
__device__ __forceinline__ void ldsm4t(uint32_t a, uint32_t& r0, uint32_t& r1, uint32_t& r2, uint32_t& r3) {
  asm volatile("ldmatrix.sync.aligned.m8n8.x4.trans.shared.b16 {%0,%1,%2,%3}, [%4];" : "=r"(r0), "=r"(r1), "=r"(r2), "=r"(r3) : "r"(a) : "memory");
}
__device__ __forceinline__ void mma16(float* c, uint32_t a0, uint32_t a1, uint32_t a2, uint32_t a3, uint32_t b0, uint32_t b1) {
  asm("mma.sync.aligned.m16n8k16.row.col.f32.bf16.bf16.f32 {%0,%1,%2,%3}, {%4,%5,%6,%7}, {%8,%9}, {%0,%1,%2,%3};"
    : "+f"(c[0]), "+f"(c[1]), "+f"(c[2]), "+f"(c[3]) : "r"(a0), "r"(a1), "r"(a2), "r"(a3), "r"(b0), "r"(b1));
}
__device__ __forceinline__ void mma16c(float* d, const uint32_t* a, uint32_t b0, uint32_t b1, float c01) {
  asm("mma.sync.aligned.m16n8k16.row.col.f32.bf16.bf16.f32 {%0,%1,%2,%3}, {%4,%5,%6,%7}, {%8,%9}, {%10,%10,%10,%10};"
    : "=f"(d[0]), "=f"(d[1]), "=f"(d[2]), "=f"(d[3]) : "r"(a[0]), "r"(a[1]), "r"(a[2]), "r"(a[3]), "r"(b0), "r"(b1), "f"(c01));
}
__device__ __forceinline__ void mma8(float* c, uint32_t a0, uint32_t a1, uint32_t b0) {
  asm("mma.sync.aligned.m16n8k8.row.col.f32.bf16.bf16.f32 {%0,%1,%2,%3}, {%4,%5}, {%6}, {%0,%1,%2,%3};"
    : "+f"(c[0]), "+f"(c[1]), "+f"(c[2]), "+f"(c[3]) : "r"(a0), "r"(a1), "r"(b0));
}
__device__ __forceinline__ uint32_t lane_id() { uint32_t l; asm volatile("mov.u32 %0, %%laneid;" : "=r"(l)); return l; }
__device__ __forceinline__ float quad_sum(float v) { v += __shfl_xor_sync(~0u, v, 1); v += __shfl_xor_sync(~0u, v, 2); return v; }
__device__ __forceinline__ float quad_max(float v) { v = fmaxf(v, __shfl_xor_sync(~0u, v, 1)); v = fmaxf(v, __shfl_xor_sync(~0u, v, 2)); return v; }
template <int N> __device__ __forceinline__ void pin(float (&d)[N]) {
#pragma unroll
  for (int i = 0; i < N; i++) asm volatile("" : "+f"(d[i]) :: "memory");
}
#define SPIN_GUARD(n) if (++(n) > SPIN_MAX) break

template <int NG> __device__ __forceinline__ void publish_stats(uint4* dst, const float* y, uint32_t tag, uint32_t lane) {
  float s0 = 0.f, s1 = 0.f;
#pragma unroll
  for (int g = 0; g < NG; g++) { s0 += y[4 * g] + y[4 * g + 1]; s1 += y[4 * g + 2] + y[4 * g + 3]; }
  s0 = quad_sum(s0); s1 = quad_sum(s1);
  const float m0 = s0 * (1.f / (8 * NG)), m1 = s1 * (1.f / (8 * NG));
  float q0 = 0.f, q1 = 0.f, q2 = 0.f, q3 = 0.f;
#pragma unroll
  for (int g = 0; g < NG; g++) {
    const float a = y[4 * g] - m0, b = y[4 * g + 1] - m0, c = y[4 * g + 2] - m1, d = y[4 * g + 3] - m1;
    q0 = fmaf(a, a, q0); q1 = fmaf(b, b, q1); q2 = fmaf(c, c, q2); q3 = fmaf(d, d, q3);
  }
  q0 = quad_sum(q0 + q1); q2 = quad_sum(q2 + q3);
  if ((lane & 3) == 0)
    stg4(dst + (lane >> 2), (__float_as_uint(s0) & ~1u) | tag, __float_as_uint(q0), __float_as_uint(s1), __float_as_uint(q2));
}

__device__ __forceinline__ void put72(uint4* slab, uint32_t j, uint32_t lane, const uint32_t* v) {
#pragma unroll
  for (int i = 0; i < 4; i++) stg4(slab + (4 * j + i) * 32 + lane, nz(v[4 * i]), v[4 * i + 1], v[4 * i + 2], v[4 * i + 3]);
  stg2((char*)(slab + 1024 + j * 16) + lane * 8, nz(v[16]), v[17]);
}
__device__ __forceinline__ uint32_t row72(uint32_t k) { return k % 9 == 4 ? 32 + k / 9 : k - (k + 4) / 9; }
__device__ __forceinline__ void zero_share(uint4* slab, uint32_t j, uint32_t lane) {
  uint4* p = slab + j * 144 + lane;
#pragma unroll
  for (int i = 0; i < 4; i++) stg4(p + i * 32, 0u, 0u, 0u, 0u);
  if (lane < 16) stg4(p + 128, 0u, 0u, 0u, 0u);
}

struct Maps { CUtensorMap m[12]; };

struct Ring {
  uint32_t st, ph;
  __device__ __forceinline__ void next() { if (++st == NST) { st = 0; ph ^= 1; } }
};

#define GSTAMP(i) do {} while (0)
#define STAMP(i) do {} while (0)
#define ZSTAMP(m, i) do {} while (0)

__device__ __forceinline__ void tma_box(uint32_t dst, const CUtensorMap* m, int col, int row, uint32_t bar, uint32_t expect) {
  asm volatile("{\n.reg .pred e, h;\nelect.sync _|e, 0xffffffff;\nsetp.ne.and.u32 h, %5, 0, e;\n"
               "@h mbarrier.arrive.expect_tx.shared::cta.b64 _, [%2], %5;\n"
               "@e cp.async.bulk.tensor.2d.shared::cluster.global.mbarrier::complete_tx::bytes [%0], [%1, {%3, %4}], [%2];\n}"
               :: "r"(dst), "l"(m), "r"(bar), "r"(col), "r"(row), "r"(expect) : "memory");
}

__device__ __forceinline__ void bulk_load(uint32_t dst, const void* src, uint32_t bytes, uint32_t bar, bool arm) {
  asm volatile("{\n.reg .pred e, h;\nelect.sync _|e, 0xffffffff;\nsetp.ne.and.u32 h, %4, 0, e;\n"
               "@h mbarrier.arrive.expect_tx.shared::cta.b64 _, [%3], %2;\n"
               "@e cp.async.bulk.shared::cluster.global.mbarrier::complete_tx::bytes [%0], [%1], %2, [%3];\n}"
               :: "r"(dst), "l"(src), "r"(bytes), "r"(bar), "r"((uint32_t)arm) : "memory");
}

__global__ void __launch_bounds__(384, 1) mega_kernel(
    const __grid_constant__ Maps maps, uint4* __restrict__ scratch,
    __nv_bfloat16* __restrict__ out) {
  extern __shared__ __align__(1024) uint8_t smem[];
  const uint32_t sb = (uint32_t)__cvta_generic_to_shared(smem);
  const uint32_t full0 = sb + BARS, empty0 = full0 + 8 * NST, rem_full = empty0 + 8 * NST, park_free = rem_full + 8, kv_free = park_free + 8;
  const uint32_t c8_go = kv_free + 8, c8_done = c8_go + 8, c8_full = c8_done + 8, remo_full = c8_full + 8, piece_full = remo_full + 8, xb_done = piece_full + 8, res_full = xb_done + 8, pbar0 = res_full + 8;
  const uint32_t x_done = pbar0 + 64, x_ring = x_done + 8, xbar0 = x_ring + 8, redo_full = xbar0 + 72;
  const uint32_t side_full = redo_full + 16;
  const uint32_t w = __shfl_sync(~0u, threadIdx.x >> 5, 0);
  uint32_t pair = blockIdx.x >> 1;
  if (gridDim.x == 132) {
    uint32_t smid;
    asm("mov.u32 %0, %%smid;" : "=r"(smid));
    const uint32_t tpc = smid >> 1;
    if (tpc == 60 || tpc == 61) { if (threadIdx.x == 0) { __nanosleep(20000); } return; }
    pair = tpc < 32 ? tpc : tpc >= 62 ? (tpc - 58) * 8 : 33 + (tpc - 32) / 7 * 8 + (tpc - 32) % 7;
  }
  const uint32_t rank = blockIdx.x & 1, t = (pair & 7) * 2 + rank, j = pair >> 3;
  const uint32_t sd = sb & 0x3ffff;
  const uint32_t odd = j & 1;
  uint4* const scr = scratch + t * TILE;
  auto blk = [&](uint32_t kb) { return kb == 0 ? j : kb - (kb <= j); };
  const uint32_t xs = sb + (NST - 2) * STAGE;
  auto fetch_x = [&](uint32_t dst, uint32_t col, uint32_t bar, bool narrow) {
    asm volatile("{\n.reg .pred e;\nelect.sync _|e, 0xffffffff;\n@e mbarrier.arrive.expect_tx.shared::cta.b64 _, [%2], %5;\n"
                 "@e cp.async.bulk.tensor.3d.shared::cluster.global.mbarrier::complete_tx::bytes [%0], [%1, {%3, %4, 0}], [%2];\n}"
                 :: "r"(dst), "l"(&maps.m[narrow ? 11 : 7]), "r"(bar), "r"(col), "r"(64 * t), "r"(narrow ? 2048 : 16384) : "memory");
  };
  if (threadIdx.x == 256) {
    for (int i = 0; i < 9; i++) mbar_init(xbar0 + 8 * i, 1);
    mbar_init(piece_full, 1);
    asm volatile("fence.mbarrier_init.release.cluster;" ::: "memory");
  }
  if (threadIdx.x == 288) {
    for (int i = 0; i < NST; i++) { mbar_init(full0 + 8 * i, 1); mbar_init(empty0 + 8 * i, 16); }
    mbar_init(x_done, 8); mbar_init(x_ring, 16); mbar_init(redo_full, 1); mbar_init(redo_full + 8, 1);
    mbar_init(side_full, 1); mbar_init(side_full + 8, 1); mbar_init(side_full + 48, 16); mbar_init(side_full + 56, 16);
    asm volatile("fence.mbarrier_init.release.cluster;" ::: "memory");
  }
  if (threadIdx.x == 320) {
    mbar_init(rem_full, 2); mbar_init(park_free, 8); mbar_init(kv_free, 8); mbar_init(c8_go, 8); mbar_init(c8_done, 2); mbar_init(c8_full, 1);
    mbar_init(remo_full, 64); mbar_init(xb_done, 8); mbar_init(res_full, 32);
    for (int i = 0; i < 8; i++) mbar_init(pbar0 + 8 * i, 4);
    asm volatile("fence.mbarrier_init.release.cluster;" ::: "memory");
  }
  if (threadIdx.x == 352) {
    asm volatile("prefetch.tensormap [%0];" :: "l"(&maps.m[7]) : "memory");
    asm volatile("prefetch.tensormap [%0];" :: "l"(&maps.m[0]) : "memory");
  }
  __syncwarp();
  asm volatile("barrier.cluster.arrive.relaxed.aligned;" ::: "memory");
  if (w != 8) asm volatile("barrier.cluster.wait.aligned;" ::: "memory");

  if (w >= 8) {
    asm volatile("setmaxnreg.dec.sync.aligned.u32 24;");
    if (w == 8) {
#pragma unroll 1
      for (uint32_t b = 0; b < 9; b++) fetch_x(xs + b * STAGE, 64 * b, xbar0 + 8 * b, false);
      tma_box(sb + PIECE, &maps.m[t >= 12 ? 6 : 5], 72 * j + (odd ? 0 : 64) + (t < 8 ? 576 * ((t >> 2) + 1) : 0), 144 * (t & 3), piece_full, 2304);
      asm volatile("barrier.cluster.wait.aligned;" ::: "memory");
      uint32_t dst = sb, bar = full0, ph = 1;
#pragma unroll 1
      for (int seg = 0; seg < 34; seg++) {
        const int n = seg >= 17 ? seg - 17 : seg;
        int ma, mb, ca, cb;
        if (n == 2) continue;
        if (n < 2) { ma = 0; mb = n; ca = 72 * j + 8 * odd + (n ? 0 : 576); cb = ca + (n ? 0 : 576); }
        else if (n < 12) { ma = 3; mb = 2; ca = cb = 576 * j + 64 * (n - 3); }
        else { ma = mb = 4; ca = n == 12 ? 512 : ((j + 2 * n) & 7) * 64; cb = ((j + 2 * n + 1) & 7) * 64; }
        const bool zip = n == 0 || n == 3, solo = n == 16;
#pragma unroll 1
        for (uint32_t st = 0; st < (solo ? 5 : 9); st++) {
          if (seg == 0 && st == NST - 2) mbar_wait(x_ring, 0);
          const uint32_t b = 2 * st + rank, kb = zip ? st : b >= 9 ? b - 9 : b;
          const bool second = zip ? rank : b >= 9;
          const int m = second ? mb : ma;
          const bool shared = kb == 8 && m > 0 && m < 4;
          const uint32_t ks = m == 4 ? 36 * j + 4 * kb : m == 0 ? 4 * blk(kb) : shared ? 0 : (9 * blk(kb) + 1) >> 1;
          const bool side = n == 1 && st >= 7;
          asm volatile("{\n.reg .pred p, e, f;\n.reg .u32 n;\nelect.sync _|e, 0xffffffff;\nsetp.ne.and.u32 f, %8, 0, e;\nmov.u32 n, 0;\n"
                       "W: mbarrier.try_wait.parity.shared::cta.b64 p, [%1+48], %2;\n@p bra D;\n"
                       "add.u32 n, n, 1;\nsetp.lt.u32 p, n, 4194304;\n@p bra W;\ntrap;\n"
                       "D: @e mbarrier.arrive.expect_tx.shared::cta.b64 _, [%1], %7;\n"
                       "@f cp.async.bulk.tensor.3d.shared::cluster.global.mbarrier::complete_tx::bytes.multicast::cluster [%0], [%3, {%4, %5, %6}], [%1], 3;\n}"
                       :: "r"((side ? sb + (st - 1) * STAGE : dst) + rank * 8192), "r"(side ? side_full + (st - 7) * 8 : bar), "r"(side ? seg >= 17 : ph), "l"(&maps.m[m + (shared ? 7 : 0)]), "r"(second ? cb : ca),
                          "r"(shared ? 64 : 0), "r"(ks), "r"(solo && st == 4 ? STAGE / 2 : STAGE), "r"((uint32_t)!(solo && b == 9)) : "memory");
          if (!side) { dst += STAGE; bar += 8; }
          if (bar == full0 + 8 * NST) { dst = sb; bar = full0; ph ^= 1; }
        }
      }
      {
#pragma unroll 1
        for (int i = 0; i < NST; i++) {
          mbar_wait_trap(bar + 48, ph);
          bar += 8;
          if (bar == full0 + 8 * NST) { bar = full0; ph ^= 1; }
        }
      }
    } else if (w == 9) {
      const uint32_t lane = lane_id();
      const uint32_t stg = sb + HSTG + lane * 16;
      uint32_t fph = 0;
#pragma unroll 1
      for (uint32_t layer = 0; layer < 2; layer++) {
        uint4* xb = scr + OFF_X + ((4 + layer) * 8 + j) * SLAB + 28 * 32;
        mbar_wait_sleep(c8_go, layer);
        int n = 0;
#pragma unroll 1
        while (true) {
          if (lane == 0) asm volatile("mbarrier.arrive.expect_tx.shared::cta.b64 _, [%0], 18432;" :: "r"(c8_full) : "memory");
          __syncwarp();
#pragma unroll 1
          for (uint32_t s = 0; s < 9; s++)
            bulk_load(sb + HSTG + s * 2048, s < 8 ? scr + OFF_P + (j + s * 8) * SLAB + 32 * 32 : xb, 2048, c8_full, false);
          mbar_wait(c8_full, fph); fph ^= 1;
          uint32_t bad = 0;
#pragma unroll 8
          for (int s = 0; s < 32; s++) { uint32_t v; asm volatile("ld.shared.b32 %0, [%1];" : "=r"(v) : "r"(stg + s * 512) : "memory"); bad |= v ^ (1 - layer); }
          if (__all_sync(~0u, (bad & 1u) == 0u)) break;
          __nanosleep(300);
          SPIN_GUARD(n);
        }
        asm volatile("bar.arrive 7, 96;" ::: "memory");
        float s0 = 0.f, s1 = 0.f;
#pragma unroll 1
        for (int g = 0; g < 8; g++) {
          const uint32_t a = stg + (g >> 1) * 512 + (g & 1) * 8;
          float a0 = 0.f, a1 = 0.f, a2 = 0.f, a3 = 0.f;
#pragma unroll 1
          for (int b = 0; b < 3; b++) {
            uint32_t v[6];
#pragma unroll
            for (int s = 0; s < 3; s++) lds2(a + (3 * b + s) * 2048, v + 2 * s);
#pragma unroll
            for (int s = 0; s < 3; s++) { a0 += bf_lo(v[2 * s]); a1 += bf_hi(v[2 * s]); a2 += bf_lo(v[2 * s + 1]); a3 += bf_hi(v[2 * s + 1]); }
          }
          sts1(a + 18432, pack_bf16(a0, a1)); sts1(a + 18436, pack_bf16(a2, a3));
          s0 += a0 + a1; s1 += a2 + a3;
        }
        __syncwarp();
        if (lane == 0) mbar_arrive(c8_done);
        s0 = quad_sum(s0); s1 = quad_sum(s1);
        float q0 = 0.f, q1 = 0.f;
        const uint32_t ln = lane_id();
#pragma unroll 1
        for (uint32_t i = 0; i < 4; i++) {
          uint32_t x[4];
          lds4(stg + 18432 + i * 512, x);
          uint4* z = xb + i * 32 + ln;
          asm volatile("" : "+l"(z));
          stg4(z, 0u, 0u, 0u, 0u);
          if (layer == 0) {
            stg4(z - (3 * 8 * SLAB - 128), nz(x[0]), x[1], nz(x[2]), x[3]);
#pragma unroll
            for (int e = 0; e < 4; e++) {
              const float m = (e & 1) ? s1 : s0, c = fmaf(m, -1.f / 64, bf_lo(x[e])), d = fmaf(m, -1.f / 64, bf_hi(x[e]));
              if (e & 1) q1 = fmaf(c, c, fmaf(d, d, q1)); else q0 = fmaf(c, c, fmaf(d, d, q0));
            }
          } else {
            uint32_t* o = (uint32_t*)(out + (128 * t + 32 * (j >> 1) + 2 * (ln >> 2) + (j & 1)) * 576 + 512 + 16 * i + 2 * (ln & 3));
            o[0] = x[0]; o[8 * 576] = x[1]; o[4] = x[2]; o[8 * 576 + 4] = x[3];
          }
        }
        if (layer == 0) {
          q0 = quad_sum(q0); q1 = quad_sum(q1);
          if ((ln & 3) == 0) stg4(scr + OFF_S + j * 96 + 64 + (ln >> 2), __float_as_uint(s0) | 1u, __float_as_uint(q0), __float_as_uint(s1), __float_as_uint(q1));
        }
      }
    } else {
      auto mark = [&](uint32_t k0, uint32_t v) {
        const uint32_t lane = lane_id();
#pragma unroll 1
        for (uint32_t k = k0; k < 6; k++) stg4(scr + OFF_S + (k * 4 + (lane >> 3)) * 96 + j * 8 + (lane & 7), k < 2 ? 0u : v, 0u, 0u, 0u);
      };
      if (w == 11) mark(2, 0u);
      auto phase2_duties = [&](uint32_t layer) {
        const uint32_t lane = lane_id();
        asm volatile("bar.sync 7, 96;" ::: "memory");
        if (w == 11) {
          if (layer == 0) mark(0, 1u);
          __syncwarp();
          if (lane == 0) mbar_arrive(c8_done);
        }
#pragma unroll 1
        for (uint32_t i = 0; i < 16; i++) {
          const uint32_t sl = (w - 10) * 4 + (i >> 2);
          bulk_load(sb + PARK + sl * 2048 + (i & 3) * 512, scr + OFF_X + ((4 + layer) * 8 + sl) * SLAB + row72(4 * j + (i & 3)) * 32, 512, res_full, true);
        }
        mbar_wait_sleep(res_full, layer);
#pragma unroll 1
        for (uint32_t i = 0; i < 16; i++) {
          stg4(scr + OFF_X + ((4 + layer) * 8 + (w - 10) * 4 + (i >> 2)) * SLAB + row72(4 * j + (i & 3)) * 32 + lane, 0u, 0u, 0u, 0u);
          if ((i & 3) == 3) __nanosleep(200);
        }
      };
      if (w == 10) {
        const uint32_t lane = lane_id();
        uint32_t* fl = (uint32_t*)(scratch + OFF_F + (t * 8 + j) * 8) + (lane & 15);
        uint32_t v;
        asm volatile("ld.relaxed.gpu.global.b32 %0, [%1];" : "=r"(v) : "l"(fl) : "memory");
        mbar_wait(piece_full, 0);
        asm volatile("{\n.reg .pred e;\nelect.sync _|e, 0xffffffff;\n@e cp.async.bulk.global.shared::cta.bulk_group [%0], [%1], 2304;\n}\n"
                     "cp.async.bulk.commit_group;\ncp.async.bulk.wait_group 0;\nfence.proxy.async;"
                     :: "l"(scratch + OFF_R + j * 2304 + t * 144), "r"(sb + PIECE) : "memory");
        __syncwarp();
        if (lane < 16) asm volatile("st.release.gpu.global.b32 [%0], 1;" :: "l"((uint32_t*)(scratch + OFF_F + (lane_id() * 8 + j) * 8) + t) : "memory");
        int n = 0;
#pragma unroll 1
        while (!__all_sync(~0u, v != 0u)) {
          __nanosleep(100);
          SPIN_GUARD(n);
          asm volatile("ld.relaxed.gpu.global.b32 %0, [%1];" : "=r"(v) : "l"(fl) : "memory");
        }
        asm volatile("st.relaxed.gpu.global.b32 [%0], 0;" :: "l"(fl) : "memory");
        mbar_wait(x_done, 0);
      }
#pragma unroll 1
      for (uint32_t layer = 0; layer < 3; layer++) {
        if (w == 10 && layer < 2) {
          if (layer) mbar_wait_sleep(park_free, 0);
          const uint4* img = scratch + OFF_R + j * 2304;
          if (lane_id() == 0) asm volatile("mbarrier.arrive.expect_tx.shared::cta.b64 _, [%0], 27648;\nmbarrier.arrive.expect_tx.shared::cta.b64 _, [%1], 9216;"
                                           :: "r"(rem_full), "r"(piece_full) : "memory");
          __syncwarp();
#pragma unroll 1
          for (uint32_t p = 0; p < 3; p++) {
            bulk_load(sb + REM + p * 9216, img + p * 576 + j * 64, 1024, rem_full, false);
            if (j) bulk_load(sb + REM + p * 9216 + 1024, img + p * 576, j * 1024, rem_full, false);
            bulk_load(sb + REM + p * 9216 + (j + 1) * 1024, img + p * 576 + (j + 1) * 64, (8 - j) * 1024, rem_full, false);
          }
#pragma unroll 1
          for (uint32_t i = 0; i < 12; i++)
            bulk_load(sb + REM + 27648 + (i < 8 ? i * 1024 : 6144 + i * 256), img + 1728 + (i < 8 ? (9 * blk(i) + 1) >> 1 : 9 * i - 68) * 16,
                      i < 8 ? 1024 : 256, piece_full, false);
          if (layer == 0) { fetch_x(sb + PARK + 2 * STAGE, 72 * j + 8 * odd, xbar0, false); fetch_x(sb + REM + 37888, 72 * j + (odd ? 0 : 64), xbar0 + 8, true); }
        }
        if (w == 11 && layer < 2) {
          if (layer) mbar_wait_sleep(park_free, 0);
          __syncwarp();
          if (lane_id() == 0) mbar_arrive(rem_full);
        }
        if (layer) phase2_duties(layer - 1);
        if (layer == 2) break;
        mbar_wait_sleep(layer ? kv_free : x_done, 0);
        if (t > 0) {
          const uint32_t lane = lane_id(), r = lane >> 2, q = lane & 3;
#pragma unroll 1
          for (uint32_t pc = 0; pc < 3; pc++) {
            uint4* hp = scr + OFF_H + ((layer * 8 + j) * 2 + (w - 10)) * 192 + pc * 64 + lane;
            uint32_t hl[8];
            int n = 0;
            hl[4] = 1u;
#pragma unroll 1
            while (true) {
              ldg4(hl, hp);
              if (pc < 2) ldg4(hl + 4, hp + 32);
              if (__all_sync(~0u, hl[0] != 0u && hl[4] != 0u)) break;
              __nanosleep(100);
              SPIN_GUARD(n);
            }
            const uint32_t dst = sb + KVS + (w - 10) * 10368 + r * 144 + q * 4;
            if (pc < 2) {
#pragma unroll
              for (int g = 0; g < 8; g++) sts1(dst + pc * 20736 + odd * 16 + g * 16, hl[g]);
              stg4(hp + 32, 0u, 0u, 0u, 0u);
            } else {
              sts1(dst + (odd ? 0 : 128), hl[0]); sts1(dst + 20736 + (odd ? 0 : 128), hl[1]);
            }
            stg4(hp, 0u, 0u, 0u, 0u);
          }
        }
        asm volatile("bar.arrive 1, 192;" ::: "memory");
        mbar_wait(rem_full, layer);
        mbar_wait(piece_full, 1 - layer);
#pragma unroll 1
        for (uint32_t b = 0; b < 5; b++) {
          const uint32_t blk = sb + REM + 27648 + b * 2048, k = (w - 10) * 32 + lane_id(), rr = k & 7;
          const uint32_t dst = blk + ((k >> 3) & 1) * 1024 + rr * 128 + (((k >> 4) ^ rr) << 4);
          uint32_t v[8];
          lds4(blk + k * 16, v); lds4(blk + 1024 + k * 16, v + 4);
          asm volatile("bar.sync 3, 64;" ::: "memory");
          sts4(dst, v); sts4(dst ^ 64, v + 4);
        }
        asm volatile("fence.proxy.async.shared::cta;" ::: "memory");
        mbar_arrive(remo_full);
        mbar_wait_sleep(xb_done, layer);
        if (w == 10 && layer == 1) {
          const uint32_t lane = lane_id();
          stg4(scr + OFF_S + (lane >> 3) * 96 + j * 8 + (lane & 7), 0u, 0u, 0u, 0u);
          stg4(scr + OFF_S + (4 + (lane >> 3)) * 96 + j * 8 + (lane & 7), 0u, 0u, 0u, 0u);
          if (lane < 8) stg4(scr + OFF_S + j * 96 + 64 + lane, 0u, 0u, 0u, 0u);
        }
#pragma unroll 1
        for (uint32_t i = 0; i < 8 && (w == 11 || layer == 1); i++) {
          zero_share(scr + OFF_X + ((w - 10) * 16 + layer * 8 + i) * SLAB, j, lane_id());
          __nanosleep(500);
        }
      }
    }
  } else {
    asm volatile("setmaxnreg.inc.sync.aligned.u32 240;");
    const bool lead = lane_id() == 0;
    Ring rg{0, 0};
    uint32_t prev = 0;
    uint32_t X[144];
    float rs0, rs1;
    const bool lead2 = lane_id() < 2;
    uint32_t empty_at;
    asm volatile("mapa.shared::cluster.u32 %0, %1, %2;" : "=r"(empty_at) : "r"(empty0), "r"(lane_id() & 1));
    auto release = [&](uint32_t st) { if (lead2) asm volatile("mbarrier.arrive.shared::cluster.b64 _, [%0];" :: "r"(empty_at + st * 8) : "memory"); };
    auto load_kb = [&](int kb, const uint4* src, const char* lo, uint32_t hoff) {
      const uint4* p;
      asm("{\n.reg .pred p;\n.reg .u64 t;\nsetp.ge.u32 p, %2, %3;\nadd.u64 t, %1, -2048;\nselp.b64 %0, t, %1, p;\n}" : "=l"(p) : "l"(src), "r"(j), "r"(kb));
#pragma unroll
      for (int i = 0; i < 4; i++) {
        if (kb == 8) { ldg2(X + 128 + 4 * i, lo + (32 + i) * 512); ldg2(X + 130 + 4 * i, lo + hoff + (32 + i) * 512); }
        else ldg4(X + 16 * kb + 4 * i, p + kb * 128 + i * 32);
      }
    };
    auto check_kb = [&](bool skip, int kb, const uint4* src, const char* lo, uint32_t hoff) {
      int n = 0;
#pragma unroll 1
      while (true) {
        uint32_t m = umin2(umin2(X[16 * kb], X[16 * kb + 4]), umin2(X[16 * kb + 8], X[16 * kb + 12]));
        if (kb == 8) m = umin2(m, umin2(umin2(X[130], X[134]), umin2(X[138], X[142])));
        if (__all_sync(~0u, m != 0u || skip)) break;
        SPIN_GUARD(n);
        load_kb(kb, src, lo, hoff);
      }
    };
#pragma unroll
    for (int i = 0; i < 16; i++) X[i] = 0u;
#pragma unroll 1
    for (uint32_t hf = 0; hf < 4; hf++) {
      const uint32_t layer = hf >> 1;
      const bool ffn = hf & 1;
      const uint32_t tag = 1 - layer;
      uint4* const xbase = scr + OFF_X + (layer * 8 + w) * SLAB;
      float aA[32], aB[32];
      {
        const uint32_t lane = lane_id(), r = lane >> 2, q = lane & 3;
        const uint4* src = xbase + (ffn ? 32 * SLAB : 0) + lane;
        const char* lo = (const char*)src - (ffn ? lane * 8 : 0);
        const uint32_t hoff = ffn ? 256 : 8;
        const uint32_t xoff = (w & 1) * 8192 + (16 * (w >> 1) + (lane & 15)) * 128 + (((lane >> 4) ^ (lane & 7)) << 4);
        auto load_x = [&](uint32_t b, uint32_t* d) {
#pragma unroll
          for (int i = 0; i < 4; i++) ldsm4(xs + b * STAGE + (xoff ^ (32 * i)), d[4 * i], d[4 * i + 1], d[4 * i + 2], d[4 * i + 3]);
        };
        auto load_any = [&](int kb) { if (hf == 0) load_x(blk(kb), X + 16 * kb); else load_kb(kb, src, lo, hoff); };
        float m0, m1, v0, v1;
        STAMP(ffn * 16 + 0);
        if (hf == 0) {
          float sum[2][4] = {}, sq0[4][4] = {}, sq1[4][4] = {};
          uint32_t p0, p1;
          mbar_wait(xbar0, 0);
          ldsm4(xs + xoff, p0, p1, X[0], X[1]);
          p0 = __byte_perm(__shfl_sync(~0u, p0, lane & 28), 0, 0x1010); p1 = __byte_perm(__shfl_sync(~0u, p1, lane & 28), 0, 0x1010);
#pragma unroll 3
          for (uint32_t b = 0; b < 9; b++) {
            uint32_t d[16];
            mbar_wait(xbar0 + 8 * b, 0);
            load_x(b, d);
#pragma unroll
            for (int i = 0; i < 16; i++) d[i] = sub_bf16x2(d[i], (i & 1) ? p1 : p0);
#pragma unroll
            for (int g = 0; g < 8; g++) {
              if (!(g & 1)) mma16(sum[(g >> 1) & 1], d[2 * g], d[2 * g + 1], d[2 * g + 2], d[2 * g + 3], 0x3f803f80u, 0x3f803f80u);
              mma8(sq0[g & 3], d[2 * g], d[2 * g + 1], d[2 * g]); mma8(sq1[g & 3], d[2 * g], d[2 * g + 1], d[2 * g + 1]);
            }
          }
          STAMP(1);
          GSTAMP(14);
#pragma unroll
          for (int kb = 0; kb < GD; kb++) load_x(blk(kb), X + 16 * kb);
          release((x_ring - empty0) / 8);
          auto tot = [](float (&c)[4][4], int e) { return (c[0][e] + c[1][e]) + (c[2][e] + c[3][e]); };
          const float a0 = (sum[0][0] + sum[1][0]) * (1.f / 576), a1 = (sum[0][2] + sum[1][2]) * (1.f / 576);
          const uint32_t dg = (lane & 28) + (r >> 1);
          v0 = fmaxf(fmaf(__shfl_sync(~0u, (r & 1) ? tot(sq0, 1) : tot(sq0, 0), dg), 1.f / 576, -a0 * a0), 0.f);
          v1 = fmaxf(fmaf(__shfl_sync(~0u, (r & 1) ? tot(sq1, 3) : tot(sq1, 2), dg), 1.f / 576, -a1 * a1), 0.f);
          m0 = bf_lo(p0) + a0; m1 = bf_lo(p1) + a1;
        } else {
          uint32_t s[3][4];
          const uint4* p = scr + OFF_S + ((ffn ? 16 : 0) + w) * 96 + q * 8 + r;
          const bool third = !ffn && q == 0;
          const uint32_t rdy = ffn ? tag : 1u;
          int n = 0;
          s[2][0] = rdy; s[2][1] = s[2][2] = s[2][3] = 0u;
#pragma unroll 1
          while (true) {
            ldg4(s[0], p); ldg4(s[1], p + 32);
            if (third) ldg4(s[2], p + 64);
            if (__all_sync(~0u, ((diff2(s[0][0], s[1][0], rdy) | diff2(s[1][0], s[2][0], rdy)) & 1u) == 0u)) break;
            SPIN_GUARD(n);
          }
          STAMP(ffn * 16 + 1);
          ZSTAMP(1 + ffn, 0);
          GSTAMP(14 + ffn);
#pragma unroll
          for (int kb = 1; kb < GD; kb++) load_kb(kb, src, lo, hoff);
          float t0 = 0.f, t1 = 0.f;
#pragma unroll
          for (int i = 0; i < 3; i++) { t0 += __uint_as_float(s[i][0]); t1 += __uint_as_float(s[i][2]); }
          m0 = quad_sum(t0) * (1.f / 576); m1 = quad_sum(t1) * (1.f / 576);
          const float cnt = ffn ? 72.f : 64.f, inv = ffn ? 1.f / 72 : 1.f / 64;
          v0 = 0.f; v1 = 0.f;
#pragma unroll
          for (int i = 0; i < 3; i++) {
            const float c = (i < 2 || third) ? cnt : 0.f;
            const float d0 = fmaf(__uint_as_float(s[i][0]), inv, -m0), d1 = fmaf(__uint_as_float(s[i][2]), inv, -m1);
            v0 += fmaf(d0 * d0, c, __uint_as_float(s[i][1])); v1 += fmaf(d1 * d1, c, __uint_as_float(s[i][3]));
          }
          v0 = quad_sum(v0) * (1.f / 576); v1 = quad_sum(v1) * (1.f / 576);
        }
        rs0 = rsqrtf(v0 + 1e-5f); rs1 = rsqrtf(v1 + 1e-5f);
        const uint32_t mean0 = pack_bf16(m0, m0), mean1 = pack_bf16(m1, m1);
#pragma unroll
        for (int kb = 0; kb < 9; kb++) {
          if (kb > 0) check_kb(hf == 0, kb, src, lo, hoff);
          if (kb + GD < 9) load_any(kb + GD);
          if (kb + GD == 8 && hf == 0 && lead) mbar_arrive(x_done);
#pragma unroll
          for (int i = 16 * kb; i < 16 * kb + 16; i++) X[i] = sub_bf16x2(X[i], (i & 1) ? mean1 : mean0);
          ZSTAMP(1 + ffn, 1 + 3 * kb);
          mbar_wait(full0 + rg.st * 8, rg.ph);
          ZSTAMP(1 + ffn, 2 + 3 * kb);
          const uint64_t desc = DESC_HI | ((sd + rg.st * STAGE) >> 4);
          wg_fence();
#pragma unroll
          for (int i = 0; i < 4; i++) wgmma_rs_n64(aA, X + 4 * (4 * kb + i), desc + i * 128, kb + i != 0);
          if (kb == 8) { wg_commit(); wg_wait<1>(); wg_fence(); }
#pragma unroll
          for (int i = 0; i < 4; i++) wgmma_rs_n64(aB, X + 4 * (4 * kb + i), desc + 512 + i * 128, kb + i != 0);
          wg_commit();
          wg_wait<1>();
          ZSTAMP(1 + ffn, 3 + 3 * kb);
          if (kb > 0) release(prev);
          prev = rg.st; rg.next();
        }
        ZSTAMP(1 + ffn, 28);
        ZSTAMP(4, 0);
        STAMP(ffn * 16 + 2);
      }
      if (!ffn) {
      const uint32_t lane = lane_id(), r = lane >> 2, q = lane & 3;
      const uint32_t kvrow = sb + KVS + (w & 1) * 10368 + (16 * (w >> 1)) * 144;
      uint32_t Q[18], Km[3][8], Ke[3][4];
      const bool edge = (t == 0 && w < 2);
      const uint32_t row0 = edge ? sb + KVS + 8 * 144 : kvrow + (lane & 7) * 144, row1 = kvrow + (8 + (lane & 7)) * 144;
      {
        const uint32_t dst = kvrow + (8 + r) * 144 + q * 4 + odd * 16, dstr = dst + (odd ? -16 : 128);
        const bool edge_out = w >= 6 && t < 15;
        uint4* const hp = scr + TILE + OFF_H + ((layer * 8 + j) * 2 + (w & 1)) * 192 + lane;
        auto put_kv = [&](float (&a)[32], int part, int half) {
          uint32_t hl[4];
#pragma unroll
          for (int i = 0; i < 16; i++) asm volatile("" : "+f"(a[16 * half + i]) :: "memory");
#pragma unroll
          for (int i = 0; i < 4; i++) {
            const int g = 4 * half + i;
            hl[i] = pack_bf16(a[4 * g + 2] * rs1, a[4 * g + 3] * rs1);
            sts1(dst + part * 20736 + g * 16, pack_bf16(a[4 * g] * rs0, a[4 * g + 1] * rs0)); sts1(dst + part * 20736 + 8 * 144 + g * 16, hl[i]);
          }
          if (edge_out) stg4(hp + part * 64 + half * 32, nz(hl[0]), hl[1], hl[2], hl[3]);
        };
        put_kv(aA, 0, 0); put_kv(aA, 0, 1);
        wg_wait<0>();
        release(prev);
        release((side_full + 48 - empty0) / 8); release((side_full + 56 - empty0) / 8);
        float aR[12];
        mbar_wait(rem_full, layer);
        const uint64_t dr = DESC_REM | ((sd + REM) >> 4);
        wg_fence();
#pragma unroll
        for (int s = 0; s < 36; s++) {
          wgmma_rs_n24(aR, X + 4 * s, dr + s * 16, s != 0);
          if (s == 4) put_kv(aB, 1, 0);
          if (s == 16) put_kv(aB, 1, 1);
        }
        wg_commit();
#pragma unroll
        for (int kb = 0; kb < 9; kb++) {
          if (!(kb & 1)) mbar_wait(full0 + rg.st * 8, rg.ph);
          const uint64_t desc = DESC_HI | ((sd + rg.st * STAGE + (kb & 1) * 8192) >> 4);
          wg_fence();
#pragma unroll
          for (int i = 0; i < 4; i++) wgmma_rs_n64(aB, X + 4 * (4 * kb + i), desc + i * 128, kb + i != 0);
          wg_commit();
          wg_wait<1>();
          if (kb > 0 && !(kb & 1)) release(prev);
          if (kb & 1) { prev = rg.st; rg.next(); }
          if (kb == 0) {
            pin(aR);
            const uint32_t k1 = pack_bf16(aR[2] * rs1, aR[3] * rs1), v1 = pack_bf16(aR[6] * rs1, aR[7] * rs1);
            if (edge_out) stg4(hp + 128, nz(k1), v1, 0u, 0u);
            sts1(dstr, pack_bf16(aR[0] * rs0, aR[1] * rs0)); sts1(dstr + 8 * 144, k1);
            sts1(dstr + 20736, pack_bf16(aR[4] * rs0, aR[5] * rs0)); sts1(dstr + 20736 + 8 * 144, v1);
            Q[16] = pack_bf16(aR[8], aR[9]); Q[17] = pack_bf16(aR[10], aR[11]);
            if (w < 4) asm volatile("bar.arrive 2, 256;" ::: "memory");
          }
          if (kb == 8) {
            if (w < 4) asm volatile("bar.sync 1, 192;" ::: "memory");
            else asm volatile("bar.sync 2, 256;" ::: "memory");
#pragma unroll
            for (int nt = 0; nt < 3; nt++) {
              const uint32_t ra = (nt == 0 ? row0 : row1 + (nt - 1) * 8 * 144);
              ldsm4(ra + odd * 16 + (lane >> 3) * 16, Km[nt][0], Km[nt][1], Km[nt][2], Km[nt][3]);
              ldsm4(ra + odd * 16 + 64 + (lane >> 3) * 16, Km[nt][4], Km[nt][5], Km[nt][6], Km[nt][7]);
              ldsm4(ra + (odd ? 0 : 32) + (lane >> 3) * 32, Ke[nt][0], Ke[nt][1], Ke[nt][2], Ke[nt][3]);
            }
            const uint32_t ge = (2u << q) - 1, le = 0xfu << q, on = edge ? 0u : ~0u;
            const uint32_t bits = odd ? 0xfu | ((le & 0xfu) << 4) | (ge << 8) : ge | 0xf0u | (le << 8);
#pragma unroll
            for (int h = 0; h < 4; h++) {
              const uint32_t ma = bitmask(bits, h), mb = bitmask(bits, 4 + h), mc = bitmask(bits, 8 + h);
              Km[0][2 * h] &= ma & on; Km[0][2 * h + 1] &= mb & on; Ke[0][h] &= mc & on;
#pragma unroll
              for (int nt = 1; nt < 3; nt++) { Km[nt][2 * h] &= ma; Km[nt][2 * h + 1] &= mb; Ke[nt][h] &= mc; }
            }
          }
        }
        wg_wait<0>();
        pin(aB);
        if (w < 4) asm volatile("bar.sync 4, 256;" ::: "memory");
        STAMP(3);
#pragma unroll
        for (int i = 0; i < 16; i++) Q[i] = pack_bf16(aB[2 * i], aB[2 * i + 1]);
      }
      uint32_t res[18] = {};
      if (layer) {
        const uint4* p = xbase + ((9 * j + 1) >> 1) * 32 + lane;
#pragma unroll
        for (int i = 0; i < 4; i++) ldg4(res + 4 * i, p + i * 32);
        ldg2(res + 16, odd ? (const char*)(p - 32) + 8 : (const char*)(p + 4 * 32));
      }
      {
        uint32_t V01[12][2], V2[12];
        const uint32_t rv = ((lane & 8) ? row1 : row0) + 20736, rw = row1 + 8 * 144 + 20736;
#pragma unroll
        for (int i = 0; i < 4; i++) ldsm4t(rv + odd * 16 + i * 32 + (lane >> 4) * 16, V01[2 * i][0], V01[2 * i][1], V01[2 * i + 1][0], V01[2 * i + 1][1]);
#pragma unroll
        for (int i = 0; i < 2; i++) ldsm4t(rv + (odd ? 0 : 32) + i * 64 + (lane >> 4) * 32, V01[8 + 2 * i][0], V01[8 + 2 * i][1], V01[9 + 2 * i][0], V01[9 + 2 * i][1]);
        ldsm4t(rw + odd * 16 + (lane >> 3) * 16, V2[0], V2[1], V2[2], V2[3]);
        ldsm4t(rw + odd * 16 + 64 + (lane >> 3) * 16, V2[4], V2[5], V2[6], V2[7]);
        ldsm4t(rw + (odd ? 0 : 32) + (lane >> 3) * 32, V2[8], V2[9], V2[10], V2[11]);
        const bool up0 = 2 * q > r, up1 = 2 * q + 1 > r;
        const uint32_t upm = (up0 ? 0xffffu : 0u) | (up1 ? 0xffff0000u : 0u);
        const float c0 = 0.23570226039551584f * 1.4426950408889634f * rs0, c1 = 0.23570226039551584f * 1.4426950408889634f * rs1;
        const float masked = edge ? -1e9f * 1.4426950408889634f * rcp(c0) : 0.f;
        uint32_t Om[16], Oe[8];
        uint4* const po = xbase + 16 * SLAB + 4 * j * 32 + lane;
#pragma unroll
        for (int h = 0; h < 4; h++) {
          const uint32_t e0 = odd ? Q[(4 * h + 16) % 18] : Q[4 * h + 4], e1 = odd ? Q[(4 * h + 17) % 18] : Q[4 * h + 5];
          float S[3][4];
#pragma unroll
          for (int nt = 0; nt < 3; nt++) {
            mma16c(S[nt], Q + 4 * h, Km[nt][2 * h], Km[nt][2 * h + 1], nt == 0 ? masked : 0.f);
            mma8(S[nt], e0, e1, Ke[nt][h]);
          }
          const float s00 = up0 ? S[0][0] : S[1][0], s01 = up1 ? S[0][1] : S[1][1];
          const float s10 = up0 ? S[1][2] : S[2][2], s11 = up1 ? S[1][3] : S[2][3];
          const float m0 = quad_max(fmaxf(s00, s01)) * c0, m1 = quad_max(fmaxf(s10, s11)) * c1;
          const float p00 = ex2(fmaf(s00, c0, -m0)), p01 = ex2(fmaf(s01, c0, -m0)), p10 = ex2(fmaf(s10, c1, -m1)), p11 = ex2(fmaf(s11, c1, -m1));
          const float i0 = rcp(quad_sum(p00 + p01)), i1 = rcp(quad_sum(p10 + p11));
          const uint32_t p0 = pack_bf16(p00 * i0, p01 * i0), p1 = pack_bf16(p10 * i1, p11 * i1);
          const uint32_t pf[4] = {p0 & upm, 0u, p0 & ~upm, p1 & upm};
#pragma unroll
          for (int gi = 0; gi < 3; gi++) {
            const int g = gi < 2 ? 2 * h + gi : 8 + h;
            float o[4];
            mma16c(o, pf, V01[g][0], V01[g][1], 0.f);
            mma8(o, 0u, p1 & ~upm, V2[g]);
            uint32_t* d = gi < 2 ? Om + 2 * g : Oe + 2 * h;
            d[0] = pack_bf16(o[0], o[1]); d[1] = pack_bf16(o[2], o[3]);
          }
          if (h > 0) {
#pragma unroll
            for (int e = 0; e < 2; e++) {
              if (!odd && q < h) Om[4 * h + e] = Oe[2 * h - 2 + e];
              if (odd && q >= h) Om[4 * h - 2 + e] = Oe[2 * h + e];
            }
            stg4(po + (h - 1) * 32, nz(Om[4 * h - 4]), Om[4 * h - 3], Om[4 * h - 2], Om[4 * h - 1]);
            if (h == 1 && w >= 4) asm volatile("bar.arrive 4, 256;" ::: "memory");
          }
        }
        STAMP(4);
        stg4(po + 96, nz(Om[12]), Om[13], Om[14], Om[15]);
        stg2((char*)(xbase + 16 * SLAB + 1024 + j * 16) + lane * 8, nz(odd ? Oe[0] : Oe[6]), odd ? Oe[1] : Oe[7]);
#pragma unroll
        for (int i = 0; i < 16; i++) X[i] = Om[i];
      }
      if (lane == 0) asm volatile("st.relaxed.gpu.global.b32 [%0], %1;" :: "l"(scr + OFF_S + (8 + w) * 96 + j * 8), "r"(tag) : "memory");
      {
        if (layer == 0) {
          const uint32_t xrow = (w & 1) * 8192 + (16 * (w >> 1) + (lane & 15)) * 128;
          uint32_t u0, u1;
          mbar_wait(xbar0, 1); mbar_wait(xbar0 + 8, 1);
#pragma unroll
          for (int i = 0; i < 4; i++)
            ldsm4(sb + PARK + 2 * STAGE + xrow + (((2 * i + (lane >> 4)) ^ (lane & 7)) << 4), res[4 * i], res[4 * i + 1], res[4 * i + 2], res[4 * i + 3]);
          ldsm4(sb + REM + 37888 + (xrow >> 3), res[16], res[17], u0, u1);
        }
        const uint4* src = xbase + 16 * SLAB + lane;
        const uint32_t st0 = rg.st;
        auto stage_of = [&](uint32_t i) { const uint32_t x = st0 + i; return i >= 3 ? NST - 3 + i : x >= NST ? x - NST : x; };
        {
          const uint32_t x = st0 + lane, wrap = x >= NST;
          mbar_wait(lane < 3 ? full0 + (x - wrap * NST) * 8 : lane < 5 ? side_full - 24 + lane * 8 : remo_full, lane < 3 ? rg.ph ^ wrap : layer);
          __syncwarp();
          if (st0 >= 3) { rg.st = st0 - 3; rg.ph ^= 1; } else rg.st = st0 + 3;
        }
        float acc[36];
        auto block72 = [&](uint32_t kb, uint32_t base, const uint32_t* a) {
          const uint64_t d0 = DESC_HI | ((base >> 4) + (((sd + REM + 27648 + (kb >> 1) * 2048 + (kb & 1) * 64 - base) >> 4) << 16));
          wg_fence();
#pragma unroll
          for (int i = 0; i < 4; i++) wgmma_rs_n72(acc, a + 4 * i, d0 - (uint64_t)(i * ((127u << 16) - 128u)), 1);
          wg_commit();
        };
#pragma unroll
        for (int i = 0; i < 18; i++) { acc[2 * i] = bf_lo(res[i]); acc[2 * i + 1] = bf_hi(res[i]); }
        block72(0, sd + st0 * STAGE + 8192, X);
        {
          const uint4* fp = scr + OFF_S + (8 + w) * 96 + (lane & 7) * 8;
          int n = 0;
          STAMP(8);
#pragma unroll 1
          while (true) {
            uint32_t f;
            asm volatile("ld.relaxed.gpu.global.b32 %0, [%1];" : "=r"(f) : "l"(fp) : "memory");
            if (__all_sync(~0u, f == tag)) break;
            SPIN_GUARD(n);
          }
          wg_wait<0>(); release(st0);
          STAMP(9);
        }
#pragma unroll
        for (int kb = 1; kb < GO; kb++) load_kb(kb, src, (const char*)src - lane * 8, 256);
        __syncwarp();
        uint32_t m = ~0u;
#pragma unroll
        for (int kb = 1; kb < 9; kb++) {
          m = umin2(m, umin2(umin2(X[16 * kb], X[16 * kb + 4]), umin2(X[16 * kb + 8], X[16 * kb + 12])));
          if (kb == 8) m = umin2(m, umin2(umin2(X[130], X[134]), umin2(X[138], X[142])));
          if (kb + GO - 1 < 9) {
            const uint4* s2 = src + (m == 0u);
            load_kb(kb + GO - 1, s2, (const char*)s2 - lane * 8, 256);
            __syncwarp();
          }
          block72(kb, sd + stage_of((kb + 1) >> 1) * STAGE + (~kb & 1) * 8192, X + 16 * kb);
          if (kb == 3 || kb == 5) { wg_wait<1>(); release(stage_of(kb >> 1)); }
        }
        uint32_t redo;
        asm volatile("{\n.reg .pred p;\nsetp.eq.u32 p, %1, 0;\nbar.red.or.pred p, %2, 128, p;\nselp.u32 %0, 1, 0, p;\n}" : "=r"(redo) : "r"(m), "r"(5 + (w >> 2)) : "memory");
        wg_wait<0>();
        pin(acc);
        if (__any_sync(~0u, redo || FORCE_REDO)) {
#pragma unroll
          for (int i = 0; i < 18; i++) { res[i] = __shfl_sync(~0u, res[i], lane); acc[2 * i] = bf_lo(res[i]); acc[2 * i + 1] = bf_hi(res[i]); }
          const uint32_t box = REM + (w >> 2) * 8192, bar = redo_full + (w >> 2) * 8;
#pragma unroll 1
          for (uint32_t kb = 0; kb < 10; kb++) {
            asm volatile("bar.sync %0, 128;" :: "r"(5 + (w >> 2)) : "memory");
            if ((w & 3) == 0)
              asm volatile("{\n.reg .pred e;\nelect.sync _|e, 0xffffffff;\n@e mbarrier.arrive.expect_tx.shared::cta.b64 _, [%2], 8192;\n"
                           "@e cp.async.bulk.tensor.3d.shared::cluster.global.mbarrier::complete_tx::bytes [%0], [%1, {%3, %4, %5}], [%2];\n}"
                           :: "r"(sb + box), "l"(&maps.m[kb >= 8 ? 8 : 1]), "r"(bar), "r"(72 * j + 8 * odd), "r"(kb >= 8 ? 64 : 0),
                              "r"(kb >= 8 ? 0 : (9 * blk(kb) + 1) >> 1) : "memory");
            mbar_wait(bar, kb & 1);
            if (kb == 9) break;
            int n = 0;
#pragma unroll 1
            while (true) {
              const char* l = (const char*)(src + blk(kb) * 128) - (kb == 8 ? lane * 8 : 0);
#pragma unroll
              for (int i = 0; i < 4; i++) ldg2(X + 4 * i, l + i * 512);
              uint32_t mm = umin2(umin2(X[0], X[4]), umin2(X[8], X[12]));
              l += (kb == 8 ? 256 : 8) + (mm == 0u ? 16 : 0);
#pragma unroll
              for (int i = 0; i < 4; i++) ldg2(X + 4 * i + 2, l + i * 512);
              if (kb == 8) mm = umin2(mm, umin2(umin2(X[2], X[6]), umin2(X[10], X[14])));
              if (__all_sync(~0u, mm != 0u)) break;
              SPIN_GUARD(n);
            }
            block72(kb, sd + box, X);
            wg_wait<0>();
            pin(acc);
          }
        }
        STAMP(10);
#pragma unroll
        for (int i = 0; i < 18; i++) res[i] = pack_bf16(acc[2 * i], acc[2 * i + 1]);
        if (j < PRI) put72(xbase + 32 * SLAB, j, lane, res);
        publish_stats<9>(scr + OFF_S + (16 + w) * 96 + j * 8, acc, tag, lane);
        if (j >= PRI) put72(xbase + 32 * SLAB, j, lane, res);
#pragma unroll
        for (int i = 0; i < 16; i++) X[i] = res[i];
      }
      continue;
      }
      const uint32_t hp = sb + PARK + w * 512 + lane_id() * 16;
      auto pack8 = [&](float (&a)[32], int p, uint32_t* o) {
#pragma unroll
        for (int e = 0; e < 8; e++) asm volatile("" : "+f"(a[8 * p + e]) :: "memory");
#pragma unroll
        for (int e = 0; e < 4; e++) o[e] = pack_bf16(a[8 * p + 2 * e], a[8 * p + 2 * e + 1]);
      };
      const float ka0 = 0.7978845608028654f * rs0, kb0 = 0.044715f * ka0 * rs0 * rs0, ku0 = 0.5f * rs0 * rs0;
      const float ka1 = 0.7978845608028654f * rs1, kb1 = 0.044715f * ka1 * rs1 * rs1, ku1 = 0.5f * rs1 * rs1;
      auto packu8 = [&](int p, uint32_t* o) {
#pragma unroll
        for (int e = 0; e < 8; e++) asm volatile("" : "+f"(aA[8 * p + e]) :: "memory");
#pragma unroll
        for (int e = 0; e < 4; e++) o[e] = pack_bf16(aA[8 * p + 2 * e] * ((e & 1) ? ku1 : ku0), aA[8 * p + 2 * e + 1] * ((e & 1) ? ku1 : ku0));
      };
      auto geglu8 = [&](int p, uint32_t* u) {
#pragma unroll
        for (int e = 0; e < 8; e++) asm volatile("" : "+f"(aB[8 * p + e]) :: "memory");
        float h[8];
#pragma unroll
        for (int e = 0; e < 8; e++) {
          const float g = aB[8 * p + e];
          h[e] = fmaf(g, tanh_ap(g * fmaf(g * g, (e & 2) ? kb1 : kb0, (e & 2) ? ka1 : ka0)), g);
        }
#pragma unroll
        for (int e = 0; e < 4; e++) u[e] = mul_bf16x2(pack_bf16(h[2 * e], h[2 * e + 1]), u[e]);
      };
      uint32_t ready = 0;
      auto box = [&](int b, auto&& filler) {
        const int kb = b < 9 ? b : b - 9;
        if (b == 0) mbar_wait_trap(full0 + rg.st * 8, rg.ph);
        else if (!(b & 1)) mbar_wait_unless(ready, full0 + rg.st * 8, rg.ph);
        const uint64_t desc = DESC_HI | ((sd + rg.st * STAGE + (b & 1) * 8192) >> 4);
        if (b & 1) { prev = rg.st; rg.next(); }
        wg_fence();
#pragma unroll
        for (int i = 0; i < 4; i++) {
          if (b < 9) wgmma_rs_n64(aA, X + 4 * (4 * kb + i), desc + i * 128, kb + i != 0);
          else wgmma_rs_n64(aB, X + 4 * (4 * kb + i), desc + i * 128, kb + i != 0);
          if ((b & 1) && b < 17 && i == 0) ready = mbar_peek(full0 + rg.st * 8, rg.ph);
          if (i == 1) filler();
        }
        wg_commit();
        if (!(b & 1)) { wg_wait<1>(); release(prev); }
      };
      auto nop = [] {};
      auto step = [&](int st, auto&& filler) { box(2 * st, nop); box(2 * st + 1, filler); };
#pragma unroll
      for (int p = 0; p < 4; p++) { uint32_t o[4]; packu8(p, o); sts4(hp + p * 4096, o); }
      box(0, nop);
      if (lead) mbar_arrive(xb_done);
#pragma unroll 1
      for (int c = 1;; c++) {
        const uint32_t hc = hp + c * 4 * 4096;
#pragma unroll
        for (int b = 1; b < 18; b++) box(b, [&] {
          if ((b & 1) && b < 8) { uint32_t o[4]; const uint32_t a = hc - (4 - (b >> 1)) * 4096; lds4(a, o); geglu8(b >> 1, o); sts4(a, o); }
          if ((b & 1) && b > 10) { uint32_t o[4]; packu8((b - 11) >> 1, o); if (c < 8) sts4(hc + ((b - 11) >> 1) * 4096, o); } });
        ZSTAMP(4, c);
        if (c == 8) break;
        box(0, nop);
      }
      wg_wait<0>();
      STAMP(21);
      GSTAMP(19);
      auto unpark = [&](int kb) {
#pragma unroll
        for (int s = 4 * kb; s < 4 * kb + 4; s++) lds4(hp + s * 4096, X + 4 * s);
      };
      unpark(0);
      uint32_t U[16];
#pragma unroll
      for (int p = 0; p < 4; p++) packu8(p, U + 4 * p);
#pragma unroll
      for (int b = 0; b < 8; b++) box(b, [&] {
        if (b < 7) unpark(b + 1);
        if (b & 1) {
          geglu8(b >> 1, U + 2 * (b - 1));
          if (rg.ph > 1) sts4(hp, U + 2 * (b - 1));
#pragma unroll
          for (int i = 0; i < 4; i++) X[128 + 2 * (b - 1) + i] = U[2 * (b - 1) + i];
        } });
      STAMP(24);
      if (layer == 0 && lead) mbar_arrive(park_free);
      const uint32_t lane2 = lane_id();
      uint4* const pw = scr + OFF_P + (j * 8 + w) * SLAB + lane2;
      const uint4* const pr = scr + OFF_P + w * SLAB + 4 * j * 32 + lane2;
      auto put_part = [&](float (&a)[32], int p, uint32_t chunk) {
        uint32_t o[4];
        pack8(a, p, o);
        stg4(pw + (chunk * 4 + p) * 32, (o[0] & ~1u) | tag, o[1], o[2], o[3]);
      };
      auto slot = [&](int p) { return sb + w * 2048 + (p < 3 ? PARK + p * 16384 : KVS + (p - 3) * 16384); };
      auto fetch = [&](int p) {
        bulk_load(slot(p), scr + OFF_P + (((j - p) & 7) * 8 + w) * SLAB + 4 * j * 32, 2048, pbar0 + w * 8, true);
      };
#pragma unroll 1
      for (int sp = 0;; sp++) {
        const uint32_t ca = sp == 0 ? 8 : ((j + 2 * sp) & 7), cb = (j + 2 * sp + 1) & 7;
        if (sp == 1 && lead) mbar_arrive(c8_go);
#pragma unroll
        for (int st = 4; st < 9; st++) step(st, [&] {
          if (st == 5 || st == 6) { put_part(aA, 2 * (st - 5), ca); put_part(aA, 2 * (st - 5) + 1, ca); }
          if (st == 8 && sp > 1) { if (sp == 3) mbar_wait(c8_done, layer); fetch(2 * sp - 2); } });
        STAMP(25 + sp);
        if (sp == 3) break;
#pragma unroll
        for (int st = 0; st < 4; st++) step(st, [&] {
          if (st < 2) { put_part(aB, 2 * st, cb); put_part(aB, 2 * st + 1, cb); }
          if (st == 3 && sp > 0) fetch(2 * sp - 1); });
      }
      auto load_p = [&](int p, uint32_t* d) {
#pragma unroll
        for (int i = 0; i < 4; i++) ldg4(d + 4 * i, pr + ((j - p) & 7) * 8 * SLAB + i * 32);
      };
#pragma unroll
      for (int b = 0; b < 9; b++) {
        box(b, [&] {
          if (b == 1) {
#pragma unroll
            for (int p = 0; p < 4; p++) put_part(aB, p, (j + 7) & 7);
          }
          if (b == 3) { load_p(5, X); load_p(6, X + 16); }
          if (b == 7) load_p(7, X + 32); });
      }
      mbar_wait(res_full, layer);
      mbar_wait(pbar0 + w * 8, layer);
#pragma unroll
      for (int p = 1; p < 5; p++)
#pragma unroll
        for (int i = 0; i < 4; i++) lds4(slot(p) + lane2 * 16 + i * 512, X + 48 + 16 * p + 4 * i);
#pragma unroll
      for (int i = 0; i < 4; i++) {
        const bool split = j == 2 * i + 1;
        const uint32_t a = slot(0) + i * 512 + (split ? lane2 * 8 : lane2 * 16);
        lds2(a, X + 48 + 4 * i); lds2(a + (split ? 256 : 8), X + 50 + 4 * i);
      }
      wg_wait<0>();
      release(rg.st); rg.next();
      pin(aA);
      STAMP(22);
      GSTAMP(20);
      {
        const uint32_t lane = lane2, r = lane >> 2, q = lane & 3;
        const uint32_t eye = r == 2 * q ? 0x3f80u : r == 2 * q + 1 ? 0x3f800000u : 0u;
        auto bad = [&](const uint32_t* d) { return diff2(d[0], d[4], tag) | diff2(d[8], d[12], tag); };
        auto add = [&](const uint32_t* d) {
#pragma unroll
          for (int g = 0; g < 8; g++) mma8(aA + 4 * g, d[2 * g], d[2 * g + 1], eye);
        };
        int n = 0;
#pragma unroll 1
        while (!__all_sync(~0u, ((or3(bad(X), bad(X + 16), bad(X + 64)) | or3(bad(X + 80), bad(X + 96), bad(X + 112))) & 1u) == 0u)) {
          SPIN_GUARD(n);
          load_p(5, X); load_p(6, X + 16);
#pragma unroll
          for (int p = 1; p < 5; p++) load_p(p, X + 48 + 16 * p);
        }
        add(X); add(X + 16);
#pragma unroll
        for (int p = 4; p >= 0; p--) add(X + 48 + 16 * ((p + 1) % 5));
        STAMP(11);
#pragma unroll 1
        while (!__all_sync(~0u, (bad(X + 32) & 1u) == 0u)) { SPIN_GUARD(n); load_p(7, X + 32); }
        add(X + 32);
        STAMP(12);
        uint32_t res[16];
#pragma unroll
        for (int i = 0; i < 16; i++) X[i] = res[i] = pack_bf16(aA[2 * i], aA[2 * i + 1]);
        if (layer == 0) {
          uint4* p = xbase + 8 * SLAB + 4 * j * 32 + lane;
          auto put = [&] {
#pragma unroll
            for (int i = 0; i < 4; i++) stg4(p + i * 32, nz(res[4 * i]), res[4 * i + 1], res[4 * i + 2], res[4 * i + 3]);
          };
          if (j < PRI) put();
          publish_stats<8>(scr + OFF_S + w * 96 + j * 8, aA, 1u, lane);
          if (j >= PRI) put();
          if (lane == 0) mbar_arrive(kv_free);
        } else {
          const uint32_t tb = slot(0);
          __syncwarp();
#pragma unroll
          for (int i = 0; i < 4; i++) {
            const uint32_t row = (lane2 & 7) + (lane2 & 8), g = 2 * i + (lane2 >> 4);
            asm volatile("stmatrix.sync.aligned.m8n8.x4.shared.b16 [%0], {%1,%2,%3,%4};"
                         :: "r"(tb + row * 128 + ((g ^ (row & 7)) << 4)), "r"(res[4 * i]), "r"(res[4 * i + 1]), "r"(res[4 * i + 2]), "r"(res[4 * i + 3]) : "memory");
          }
          __syncwarp();
#pragma unroll
          for (int i = 0; i < 4; i++) {
            const uint32_t row = 4 * i + (lane2 >> 3), g = lane2 & 7;
            uint32_t v[4];
            lds4(tb + row * 128 + ((g ^ (row & 7)) << 4), v);
            *(uint4*)(out + (128 * t + 32 * (w >> 1) + 2 * row + (w & 1)) * 576 + 64 * j + 8 * g) = make_uint4(v[0], v[1], v[2], v[3]);
          }
        }
      }
      STAMP(23);
    }
  }
}

typedef CUresult (*EncodeFn)(CUtensorMap*, CUtensorMapDataType, cuuint32_t, void*, const cuuint64_t*, const cuuint64_t*,
                             const cuuint32_t*, const cuuint32_t*, CUtensorMapInterleave, CUtensorMapSwizzle,
                             CUtensorMapL2promotion, CUtensorMapFloatOOBfill);

CUtensorMap make_map(EncodeFn f, const void* p, uint64_t cols, uint64_t rows, uint64_t grp) {
  CUtensorMap m;
  cuuint64_t dims[3] = {cols, grp, rows / grp}, str[2] = {cols * 2, cols * 2 * grp};
  cuuint32_t box[3] = {64, 16, 4}, es[3] = {1, 1, 1};
  f(&m, CU_TENSOR_MAP_DATA_TYPE_BFLOAT16, 3, const_cast<void*>(p), dims, str, box, es, CU_TENSOR_MAP_INTERLEAVE_NONE,
    CU_TENSOR_MAP_SWIZZLE_128B, CU_TENSOR_MAP_L2_PROMOTION_NONE, CU_TENSOR_MAP_FLOAT_OOB_FILL_NONE);
  return m;
}
CUtensorMap make_rem_map(EncodeFn f, const void* p, uint64_t cols) {
  CUtensorMap m;
  cuuint64_t dims[2] = {cols, 576}, str[1] = {cols * 2};
  cuuint32_t box[2] = {8, 144}, es[2] = {1, 1};
  f(&m, CU_TENSOR_MAP_DATA_TYPE_BFLOAT16, 2, const_cast<void*>(p), dims, str, box, es, CU_TENSOR_MAP_INTERLEAVE_NONE,
    CU_TENSOR_MAP_SWIZZLE_NONE, CU_TENSOR_MAP_L2_PROMOTION_NONE, CU_TENSOR_MAP_FLOAT_OOB_FILL_NONE);
  return m;
}

}

extern "C" void kernel_launch(void* const* d_in, const int* in_sizes, int n_in, void* d_out, int out_size) {
  void* fn = nullptr;
  cudaDriverEntryPointQueryResult qr;
  cudaGetDriverEntryPoint("cuTensorMapEncodeTiled", &fn, cudaEnableDefault, &qr);
  EncodeFn enc = (EncodeFn)fn;
  Maps maps;
  maps.m[0] = make_map(enc, d_in[1], 1728, 576, 16); maps.m[1] = make_map(enc, d_in[2], 576, 576, 16);
  maps.m[2] = make_map(enc, d_in[4], 4608, 576, 16); maps.m[3] = make_map(enc, d_in[5], 4608, 576, 16);
  maps.m[4] = make_map(enc, d_in[6], 576, 4608, 16);
  maps.m[5] = make_rem_map(enc, d_in[1], 1728); maps.m[6] = make_rem_map(enc, d_in[2], 576);
  maps.m[8] = make_map(enc, d_in[2], 576, 576, 144); maps.m[9] = make_map(enc, d_in[4], 4608, 576, 144);
  maps.m[10] = make_map(enc, d_in[5], 4608, 576, 144);
  {
    cuuint64_t dims[3] = {576, 1024, 2}, str[2] = {2304, 1152};
    cuuint32_t box[3] = {64, 64, 2}, es[3] = {1, 1, 1};
    enc(&maps.m[7], CU_TENSOR_MAP_DATA_TYPE_BFLOAT16, 3, d_in[0], dims, str, box, es, CU_TENSOR_MAP_INTERLEAVE_NONE,
        CU_TENSOR_MAP_SWIZZLE_128B, CU_TENSOR_MAP_L2_PROMOTION_NONE, CU_TENSOR_MAP_FLOAT_OOB_FILL_NONE);
    box[0] = 8;
    enc(&maps.m[11], CU_TENSOR_MAP_DATA_TYPE_BFLOAT16, 3, d_in[0], dims, str, box, es, CU_TENSOR_MAP_INTERLEAVE_NONE,
        CU_TENSOR_MAP_SWIZZLE_NONE, CU_TENSOR_MAP_L2_PROMOTION_NONE, CU_TENSOR_MAP_FLOAT_OOB_FILL_NONE);
  }
  void* scr = nullptr;
  cudaGetSymbolAddress(&scr, g_scratch);
  cudaFuncSetAttribute(mega_kernel, cudaFuncAttributeMaxDynamicSharedMemorySize, SMEM_BYTES);
  cudaLaunchConfig_t cfg = {};
  cfg.gridDim = dim3(128); cfg.blockDim = dim3(384); cfg.dynamicSmemBytes = SMEM_BYTES; cfg.stream = cudaStreamPerThread;
  cudaLaunchAttribute at[1];
  at[0].id = cudaLaunchAttributeClusterDimension; at[0].val.clusterDim.x = 2; at[0].val.clusterDim.y = 1; at[0].val.clusterDim.z = 1;
  cfg.attrs = at; cfg.numAttrs = 1;
  int dev = 0, sms = 0, clusters = 0;
  cudaGetDevice(&dev);
  cudaDeviceGetAttribute(&sms, cudaDevAttrMultiProcessorCount, dev);
  cudaOccupancyMaxActiveClusters(&clusters, mega_kernel, &cfg);
  if (sms == 132 && clusters == 66) cfg.gridDim = dim3(132);
  cudaLaunchKernelEx(&cfg, mega_kernel, maps, (uint4*)scr, (__nv_bfloat16*)d_out);
}
```

```cpp
#include <cuda_runtime.h>
#include <cuda.h>
#include <cuda_bf16.h>
#include <stdint.h>

#define TRACE 0
#define GUARD 0
#define FORCE_REDO 0
#define ZT 0

namespace {

constexpr int NST = 6;
constexpr int STAGE = 16384;
constexpr int PARK = NST * STAGE;
constexpr int REM = PARK + 49152;
constexpr int KVS = REM + 40960;
constexpr int PIECE = PARK + 7 * STAGE;
constexpr int HSTG = KVS + 16384;
constexpr int BARS = KVS + 41472;
constexpr int TRC = BARS + 512;
constexpr int SMEM_BYTES = TRC + (TRACE ? 512 : 0);
static_assert(NST == 6, "the producer addresses empty barriers as full + 48");
static_assert(BARS >= PARK + 131072, "barriers overlap park");
static_assert(SMEM_BYTES <= 232448, "smem");

constexpr int SLAB = 36 * 32;
constexpr int SPIN_MAX = 1 << 17;
constexpr uint32_t PRI = 4;
constexpr int GD = 3, GO = 5;
constexpr int OFF_S = 0;
constexpr int OFF_H = OFF_S + 3 * 8 * 96;
constexpr int OFF_X = OFF_H + 2 * 8 * 384;
constexpr int OFF_P = OFF_X + 6 * 8 * SLAB;
constexpr int TILE = OFF_P + 8 * 8 * SLAB;
constexpr int OFF_R = 16 * TILE;
constexpr int OFF_F = OFF_R + 8 * 2304;
constexpr int SCRATCH = OFF_F + 128 * 8;

}

__device__ uint4 g_scratch[SCRATCH];

namespace {

constexpr uint64_t DESC_HI = 0x4000004000000000ull;
constexpr uint64_t DESC_REM = (576ull << 32) | (8u << 16);
__device__ __forceinline__ void wgmma_rs_n64(float (&d)[32], const uint32_t* a, uint64_t desc, int scale_d) {
  asm volatile("{\n.reg .pred p;\nsetp.ne.b32 p, %37, 0;\n"
    "wgmma.mma_async.sync.aligned.m64n64k16.f32.bf16.bf16 "
    "{%0, %1, %2, %3, %4, %5, %6, %7, %8, %9, %10, %11, %12, %13, %14, %15, %16, %17, %18, %19, %20, %21, %22, %23, %24, %25, %26, %27, %28, %29, %30, %31}, "
    "{%32, %33, %34, %35}, %36, p, 1, 1, 1;\n}\n"
    : "+f"(d[0]), "+f"(d[1]), "+f"(d[2]), "+f"(d[3]), "+f"(d[4]), "+f"(d[5]), "+f"(d[6]), "+f"(d[7]), "+f"(d[8]), "+f"(d[9]), "+f"(d[10]), "+f"(d[11]), "+f"(d[12]), "+f"(d[13]), "+f"(d[14]), "+f"(d[15]), "+f"(d[16]), "+f"(d[17]), "+f"(d[18]), "+f"(d[19]), "+f"(d[20]), "+f"(d[21]), "+f"(d[22]), "+f"(d[23]), "+f"(d[24]), "+f"(d[25]), "+f"(d[26]), "+f"(d[27]), "+f"(d[28]), "+f"(d[29]), "+f"(d[30]), "+f"(d[31])
    : "r"(a[0]), "r"(a[1]), "r"(a[2]), "r"(a[3]), "l"(desc), "r"(scale_d));
}
__device__ __forceinline__ void wgmma_rs_n72(float (&d)[36], const uint32_t* a, uint64_t desc, int scale_d) {
  asm volatile("{\n.reg .pred p;\nsetp.ne.b32 p, %41, 0;\n"
    "wgmma.mma_async.sync.aligned.m64n72k16.f32.bf16.bf16 "
    "{%0, %1, %2, %3, %4, %5, %6, %7, %8, %9, %10, %11, %12, %13, %14, %15, %16, %17, %18, %19, %20, %21, %22, %23, %24, %25, %26, %27, %28, %29, %30, %31, %32, %33, %34, %35}, "
    "{%36, %37, %38, %39}, %40, p, 1, 1, 1;\n}\n"
    : "+f"(d[0]), "+f"(d[1]), "+f"(d[2]), "+f"(d[3]), "+f"(d[4]), "+f"(d[5]), "+f"(d[6]), "+f"(d[7]), "+f"(d[8]), "+f"(d[9]), "+f"(d[10]), "+f"(d[11]), "+f"(d[12]), "+f"(d[13]), "+f"(d[14]), "+f"(d[15]), "+f"(d[16]), "+f"(d[17]), "+f"(d[18]), "+f"(d[19]), "+f"(d[20]), "+f"(d[21]), "+f"(d[22]), "+f"(d[23]), "+f"(d[24]), "+f"(d[25]), "+f"(d[26]), "+f"(d[27]), "+f"(d[28]), "+f"(d[29]), "+f"(d[30]), "+f"(d[31]), "+f"(d[32]), "+f"(d[33]), "+f"(d[34]), "+f"(d[35])
    : "r"(a[0]), "r"(a[1]), "r"(a[2]), "r"(a[3]), "l"(desc), "r"(scale_d));
}
__device__ __forceinline__ void wgmma_rs_n24(float (&d)[12], const uint32_t* a, uint64_t desc, int scale_d) {
  asm volatile("{\n.reg .pred p;\nsetp.ne.b32 p, %17, 0;\n"
    "wgmma.mma_async.sync.aligned.m64n24k16.f32.bf16.bf16 "
    "{%0, %1, %2, %3, %4, %5, %6, %7, %8, %9, %10, %11}, "
    "{%12, %13, %14, %15}, %16, p, 1, 1, 1;\n}\n"
    : "+f"(d[0]), "+f"(d[1]), "+f"(d[2]), "+f"(d[3]), "+f"(d[4]), "+f"(d[5]), "+f"(d[6]), "+f"(d[7]), "+f"(d[8]), "+f"(d[9]), "+f"(d[10]), "+f"(d[11])
    : "r"(a[0]), "r"(a[1]), "r"(a[2]), "r"(a[3]), "l"(desc), "r"(scale_d));
}

__device__ __forceinline__ void mbar_init(uint32_t a, uint32_t c) { asm volatile("mbarrier.init.shared::cta.b64 [%0], %1;" :: "r"(a), "r"(c)); }
__device__ __forceinline__ void mbar_arrive(uint32_t a) { asm volatile("mbarrier.arrive.shared::cta.b64 _, [%0];" :: "r"(a) : "memory"); }
__device__ __forceinline__ void mbar_wait_trap(uint32_t a, uint32_t ph) {
  asm volatile("{\n.reg .pred p;\n.reg .u32 n;\nmov.u32 n, 0;\n"
               "W: mbarrier.try_wait.parity.shared::cta.b64 p, [%0], %1;\n@p bra D;\n"
               "add.u32 n, n, 1;\nsetp.lt.u32 p, n, 4194304;\n@p bra W;\ntrap;\nD:\n}" :: "r"(a), "r"(ph) : "memory");
}
__device__ __forceinline__ void mbar_wait(uint32_t a, uint32_t ph) {
  asm volatile("{\n.reg .pred p;\nW: mbarrier.try_wait.parity.shared::cta.b64 p, [%0], %1;\n@!p bra W;\n}" :: "r"(a), "r"(ph) : "memory");
}
__device__ __forceinline__ uint32_t mbar_peek(uint32_t a, uint32_t ph) {
  uint32_t r;
  asm volatile("{\n.reg .pred p;\nmbarrier.test_wait.parity.shared::cta.b64 p, [%1], %2;\nselp.u32 %0, 1, 0, p;\n}" : "=r"(r) : "r"(a), "r"(ph) : "memory");
  return r;
}
__device__ __forceinline__ void mbar_wait_unless(uint32_t ready, uint32_t a, uint32_t ph) {
  asm volatile("{\n.reg .pred p;\nsetp.ne.u32 p, %2, 0;\n@p bra D;\nW: mbarrier.try_wait.parity.shared::cta.b64 p, [%0], %1;\n@!p bra W;\nD:\n}"
               :: "r"(a), "r"(ph), "r"(ready) : "memory");
}
__device__ __forceinline__ void mbar_wait_sleep(uint32_t a, uint32_t ph) {
  asm volatile("{\n.reg .pred p;\nW: mbarrier.test_wait.parity.shared::cta.b64 p, [%0], %1;\n@p bra D;\nnanosleep.u32 500;\nbra W;\nD:\n}" :: "r"(a), "r"(ph) : "memory");
}
__device__ __forceinline__ void wg_fence() { asm volatile("wgmma.fence.sync.aligned;" ::: "memory"); }
__device__ __forceinline__ void wg_commit() { asm volatile("wgmma.commit_group.sync.aligned;" ::: "memory"); }
template <int N> __device__ __forceinline__ void wg_wait() { asm volatile("wgmma.wait_group.sync.aligned %0;" :: "n"(N) : "memory"); }
__device__ __forceinline__ float tanh_ap(float x) { float y; asm("tanh.approx.f32 %0, %1;" : "=f"(y) : "f"(x)); return y; }
__device__ __forceinline__ float ex2(float x) { float y; asm("ex2.approx.ftz.f32 %0, %1;" : "=f"(y) : "f"(x)); return y; }
__device__ __forceinline__ uint32_t pack_bf16(float lo, float hi) { uint32_t r; asm("cvt.rn.bf16x2.f32 %0, %1, %2;" : "=r"(r) : "f"(hi), "f"(lo)); return r; }
__device__ __forceinline__ float bf_lo(uint32_t v) { return __uint_as_float(v << 16); }
__device__ __forceinline__ float bf_hi(uint32_t v) { return __uint_as_float(v & 0xffff0000u); }
__device__ __forceinline__ uint32_t sub_bf16x2(uint32_t a, uint32_t b) { uint32_t r; asm("sub.rn.bf16x2 %0, %1, %2;" : "=r"(r) : "r"(a), "r"(b)); return r; }
__device__ __forceinline__ uint32_t mul_bf16x2(uint32_t a, uint32_t b) { uint32_t r; asm("mul.rn.bf16x2 %0, %1, %2;" : "=r"(r) : "r"(a), "r"(b)); return r; }
__device__ __forceinline__ uint32_t diff2(uint32_t a, uint32_t b, uint32_t t) { uint32_t r; asm("lop3.b32 %0, %1, %2, %3, 0x7e;" : "=r"(r) : "r"(a), "r"(b), "r"(t)); return r; }
__device__ __forceinline__ uint32_t or3(uint32_t a, uint32_t b, uint32_t c) { uint32_t r; asm("lop3.b32 %0, %1, %2, %3, 0xfe;" : "=r"(r) : "r"(a), "r"(b), "r"(c)); return r; }
__device__ __forceinline__ uint32_t umin2(uint32_t a, uint32_t b) { uint32_t r; asm("min.u32 %0, %1, %2;" : "=r"(r) : "r"(a), "r"(b)); return r; }
__device__ __forceinline__ uint32_t bitmask(uint32_t v, int bit) { uint32_t r; asm("bfe.s32 %0, %1, %2, 1;" : "=r"(r) : "r"(v), "r"(bit)); return r; }
__device__ __forceinline__ uint32_t nz(uint32_t w) { return w == 0u ? 0x8000u : w; }

__device__ __forceinline__ void ldg4(uint32_t* d, const uint4* p) {
  asm volatile("ld.relaxed.gpu.global.v4.b32 {%0,%1,%2,%3}, [%4];" : "=r"(d[0]), "=r"(d[1]), "=r"(d[2]), "=r"(d[3]) : "l"(p) : "memory");
}
__device__ __forceinline__ void ldg2(uint32_t* d, const void* p) {
  asm volatile("ld.relaxed.gpu.global.v2.b32 {%0,%1}, [%2];" : "=r"(d[0]), "=r"(d[1]) : "l"(p) : "memory");
}
__device__ __forceinline__ void stg4(uint4* p, uint32_t a, uint32_t b, uint32_t c, uint32_t d) {
  asm volatile("st.relaxed.gpu.global.v4.b32 [%0], {%1,%2,%3,%4};" :: "l"(p), "r"(a), "r"(b), "r"(c), "r"(d) : "memory");
}
__device__ __forceinline__ void stg2(void* p, uint32_t a, uint32_t b) {
  asm volatile("st.relaxed.gpu.global.v2.b32 [%0], {%1,%2};" :: "l"(p), "r"(a), "r"(b) : "memory");
}
__device__ __forceinline__ void sts4(uint32_t a, const uint32_t* o) { asm volatile("st.shared.v4.b32 [%0], {%1,%2,%3,%4};" :: "r"(a), "r"(o[0]), "r"(o[1]), "r"(o[2]), "r"(o[3]) : "memory"); }
__device__ __forceinline__ void lds4(uint32_t a, uint32_t* o) { asm volatile("ld.shared.v4.b32 {%0,%1,%2,%3}, [%4];" : "=r"(o[0]), "=r"(o[1]), "=r"(o[2]), "=r"(o[3]) : "r"(a) : "memory"); }
__device__ __forceinline__ void lds2(uint32_t a, uint32_t* o) { asm volatile("ld.shared.v2.b32 {%0,%1}, [%2];" : "=r"(o[0]), "=r"(o[1]) : "r"(a) : "memory"); }
__device__ __forceinline__ float rcp(float x) { float y; asm("rcp.approx.ftz.f32 %0, %1;" : "=f"(y) : "f"(x)); return y; }
__device__ __forceinline__ void sts1(uint32_t a, uint32_t v) { asm volatile("st.shared.b32 [%0], %1;" :: "r"(a), "r"(v) : "memory"); }
__device__ __forceinline__ void ldsm4(uint32_t a, uint32_t& r0, uint32_t& r1, uint32_t& r2, uint32_t& r3) {
  asm volatile("ldmatrix.sync.aligned.m8n8.x4.shared.b16 {%0,%1,%2,%3}, [%4];" : "=r"(r0), "=r"(r1), "=r"(r2), "=r"(r3) : "r"(a) : "memory");
}
__device__ __forceinline__ void ldsm4t(uint32_t a, uint32_t& r0, uint32_t& r1, uint32_t& r2, uint32_t& r3) {
  asm volatile("ldmatrix.sync.aligned.m8n8.x4.trans.shared.b16 {%0,%1,%2,%3}, [%4];" : "=r"(r0), "=r"(r1), "=r"(r2), "=r"(r3) : "r"(a) : "memory");
}
__device__ __forceinline__ void mma16(float* c, uint32_t a0, uint32_t a1, uint32_t a2, uint32_t a3, uint32_t b0, uint32_t b1) {
  asm("mma.sync.aligned.m16n8k16.row.col.f32.bf16.bf16.f32 {%0,%1,%2,%3}, {%4,%5,%6,%7}, {%8,%9}, {%0,%1,%2,%3};"
    : "+f"(c[0]), "+f"(c[1]), "+f"(c[2]), "+f"(c[3]) : "r"(a0), "r"(a1), "r"(a2), "r"(a3), "r"(b0), "r"(b1));
}
__device__ __forceinline__ void mma16c(float* d, const uint32_t* a, uint32_t b0, uint32_t b1, float c01) {
  asm("mma.sync.aligned.m16n8k16.row.col.f32.bf16.bf16.f32 {%0,%1,%2,%3}, {%4,%5,%6,%7}, {%8,%9}, {%10,%10,%10,%10};"
    : "=f"(d[0]), "=f"(d[1]), "=f"(d[2]), "=f"(d[3]) : "r"(a[0]), "r"(a[1]), "r"(a[2]), "r"(a[3]), "r"(b0), "r"(b1), "f"(c01));
}
__device__ __forceinline__ void mma8(float* c, uint32_t a0, uint32_t a1, uint32_t b0) {
  asm("mma.sync.aligned.m16n8k8.row.col.f32.bf16.bf16.f32 {%0,%1,%2,%3}, {%4,%5}, {%6}, {%0,%1,%2,%3};"
    : "+f"(c[0]), "+f"(c[1]), "+f"(c[2]), "+f"(c[3]) : "r"(a0), "r"(a1), "r"(b0));
}
__device__ __forceinline__ uint32_t lane_id() { uint32_t l; asm volatile("mov.u32 %0, %%laneid;" : "=r"(l)); return l; }
__device__ __forceinline__ float quad_sum(float v) { v += __shfl_xor_sync(~0u, v, 1); v += __shfl_xor_sync(~0u, v, 2); return v; }
__device__ __forceinline__ float quad_max(float v) { v = fmaxf(v, __shfl_xor_sync(~0u, v, 1)); v = fmaxf(v, __shfl_xor_sync(~0u, v, 2)); return v; }
template <int N> __device__ __forceinline__ void pin(float (&d)[N]) {
#pragma unroll
  for (int i = 0; i < N; i++) asm volatile("" : "+f"(d[i]) :: "memory");
}
#define SPIN_GUARD(n) if (++(n) > SPIN_MAX) break

template <int NG> __device__ __forceinline__ void publish_stats(uint4* dst, const float* y, uint32_t tag, uint32_t lane) {
  float s0 = 0.f, s1 = 0.f;
#pragma unroll
  for (int g = 0; g < NG; g++) { s0 += y[4 * g] + y[4 * g + 1]; s1 += y[4 * g + 2] + y[4 * g + 3]; }
  s0 = quad_sum(s0); s1 = quad_sum(s1);
  const float m0 = s0 * (1.f / (8 * NG)), m1 = s1 * (1.f / (8 * NG));
  float q0 = 0.f, q1 = 0.f, q2 = 0.f, q3 = 0.f;
#pragma unroll
  for (int g = 0; g < NG; g++) {
    const float a = y[4 * g] - m0, b = y[4 * g + 1] - m0, c = y[4 * g + 2] - m1, d = y[4 * g + 3] - m1;
    q0 = fmaf(a, a, q0); q1 = fmaf(b, b, q1); q2 = fmaf(c, c, q2); q3 = fmaf(d, d, q3);
  }
  q0 = quad_sum(q0 + q1); q2 = quad_sum(q2 + q3);
  if ((lane & 3) == 0)
    stg4(dst, (__float_as_uint(s0) & ~1u) | tag, __float_as_uint(q0), __float_as_uint(s1), __float_as_uint(q2));
}

__device__ __forceinline__ void put4(uint4* p, const uint32_t* v) {
#pragma unroll
  for (int i = 0; i < 4; i++) stg4(p + i * 32, v[4 * i], v[4 * i + 1], v[4 * i + 2], v[4 * i + 3]);
}
__device__ __forceinline__ uint32_t row72(uint32_t k) { return k % 9 == 4 ? 32 + k / 9 : k - (k + 4) / 9; }
__device__ __forceinline__ void zero_share(uint4* slab, uint32_t j, uint32_t lane) {
  uint4* p = slab + j * 144 + lane;
#pragma unroll
  for (int i = 0; i < 4; i++) stg4(p + i * 32, 0u, 0u, 0u, 0u);
  if (lane < 16) stg4(p + 128, 0u, 0u, 0u, 0u);
}

struct Maps { CUtensorMap m[11]; };

struct Ring {
  uint32_t st, ph;
  __device__ __forceinline__ void next() { if (++st == NST) { st = 0; ph ^= 1; } }
};

#define GSTAMP(i) do {} while (0)
#define STAMP(i) do {} while (0)
#define ZSTAMP(m, i) do {} while (0)

__device__ __forceinline__ void tma_box(uint32_t dst, const CUtensorMap* m, int col, int row, uint32_t bar, uint32_t expect) {
  asm volatile("{\n.reg .pred e, h;\nelect.sync _|e, 0xffffffff;\nsetp.ne.and.u32 h, %5, 0, e;\n"
               "@h mbarrier.arrive.expect_tx.shared::cta.b64 _, [%2], %5;\n"
               "@e cp.async.bulk.tensor.2d.shared::cluster.global.mbarrier::complete_tx::bytes [%0], [%1, {%3, %4}], [%2];\n}"
               :: "r"(dst), "l"(m), "r"(bar), "r"(col), "r"(row), "r"(expect) : "memory");
}

__device__ __forceinline__ void bulk_load(uint32_t dst, const void* src, uint32_t bytes, uint32_t bar, bool arm) {
  asm volatile("{\n.reg .pred e, h;\nelect.sync _|e, 0xffffffff;\nsetp.ne.and.u32 h, %4, 0, e;\n"
               "@h mbarrier.arrive.expect_tx.shared::cta.b64 _, [%3], %2;\n"
               "@e cp.async.bulk.shared::cluster.global.mbarrier::complete_tx::bytes [%0], [%1], %2, [%3];\n}"
               :: "r"(dst), "l"(src), "r"(bytes), "r"(bar), "r"((uint32_t)arm) : "memory");
}

__global__ void __launch_bounds__(384, 1) mega_kernel(
    const __grid_constant__ Maps maps, uint4* __restrict__ scratch,
    __nv_bfloat16* __restrict__ out) {
  extern __shared__ __align__(1024) uint8_t smem[];
  const uint32_t sb = (uint32_t)__cvta_generic_to_shared(smem);
  const uint32_t full0 = sb + BARS, empty0 = full0 + 8 * NST, rem_full = empty0 + 8 * NST, park_free = rem_full + 8, kv_free = park_free + 8;
  const uint32_t c8_go = kv_free + 8, c8_done = c8_go + 8, c8_full = c8_done + 8, remo_full = c8_full + 8, piece_full = remo_full + 8, xb_done = piece_full + 8, res_full = xb_done + 8, pbar0 = res_full + 8;
  const uint32_t x_done = pbar0 + 64, x_ring = x_done + 8, xbar0 = x_ring + 8, redo_full = xbar0 + 72;
  const uint32_t w = __shfl_sync(~0u, threadIdx.x >> 5, 0);
  uint32_t pair = blockIdx.x >> 1;
  if (gridDim.x == 132) {
    uint32_t smid;
    asm("mov.u32 %0, %%smid;" : "=r"(smid));
    const uint32_t tpc = smid >> 1;
    if (tpc == 60 || tpc == 61) { if (threadIdx.x == 0) { __nanosleep(20000); } return; }
    pair = tpc < 32 ? tpc : tpc >= 62 ? (tpc - 58) * 8 : 33 + (tpc - 32) / 7 * 8 + (tpc - 32) % 7;
  }
  const uint32_t rank = blockIdx.x & 1, t = (pair & 7) * 2 + rank, j = pair >> 3;
  const uint32_t sd = sb & 0x3ffff;
  const uint32_t odd = j & 1;
  const uint32_t scr = t * TILE;
  uint4* const scp = scratch + t * TILE;
  auto at = [&](uint32_t i) { return scratch + i; };
  auto at8 = [&](uint32_t i) { return (uint2*)scratch + i; };
  auto blk = [&](uint32_t kb) { return kb == 0 ? j : kb - (kb <= j); };
  const uint32_t xs = sb + (NST - 2) * STAGE;
  auto fetch_x = [&](uint32_t dst, uint32_t b, uint32_t bar) {
    asm volatile("{\n.reg .pred e;\nelect.sync _|e, 0xffffffff;\n@e mbarrier.arrive.expect_tx.shared::cta.b64 _, [%2], 16384;\n"
                 "@e cp.async.bulk.tensor.3d.shared::cluster.global.mbarrier::complete_tx::bytes [%0], [%1, {%3, %4, 0}], [%2];\n}"
                 :: "r"(dst), "l"(&maps.m[7]), "r"(bar), "r"(64 * b), "r"(64 * t) : "memory");
  };
  if (threadIdx.x == 256) {
    for (int i = 0; i < 9; i++) mbar_init(xbar0 + 8 * i, 1);
    mbar_init(piece_full, 1);
    asm volatile("fence.mbarrier_init.release.cluster;" ::: "memory");
  }
  if (threadIdx.x == 288) {
    for (int i = 0; i < NST; i++) { mbar_init(full0 + 8 * i, 1); mbar_init(empty0 + 8 * i, 16); }
    mbar_init(x_done, 8); mbar_init(x_ring, 16); mbar_init(redo_full, 1); mbar_init(redo_full + 8, 1);
    asm volatile("fence.mbarrier_init.release.cluster;" ::: "memory");
  }
  if (threadIdx.x == 320) {
    mbar_init(rem_full, 2); mbar_init(park_free, 8); mbar_init(kv_free, 8); mbar_init(c8_go, 8); mbar_init(c8_done, 2); mbar_init(c8_full, 1);
    mbar_init(remo_full, 64); mbar_init(xb_done, 8); mbar_init(res_full, 32);
    for (int i = 0; i < 8; i++) mbar_init(pbar0 + 8 * i, 4);
    asm volatile("fence.mbarrier_init.release.cluster;" ::: "memory");
  }
  if (threadIdx.x == 352) {
    asm volatile("prefetch.tensormap [%0];" :: "l"(&maps.m[7]) : "memory");
    asm volatile("prefetch.tensormap [%0];" :: "l"(&maps.m[0]) : "memory");
  }
  __syncwarp();
  asm volatile("barrier.cluster.arrive.relaxed.aligned;" ::: "memory");
  if (w != 8) asm volatile("barrier.cluster.wait.aligned;" ::: "memory");

  if (w >= 8) {
    asm volatile("setmaxnreg.dec.sync.aligned.u32 24;");
    if (w == 8) {
#pragma unroll 1
      for (uint32_t b = 0; b < 9; b++) fetch_x(xs + b * STAGE, b, xbar0 + 8 * b);
      tma_box(sb + PIECE, &maps.m[t >= 12 ? 6 : 5], 72 * j + (odd ? 0 : 64) + (t < 8 ? 576 * ((t >> 2) + 1) : 0), 144 * (t & 3), piece_full, 2304);
      asm volatile("barrier.cluster.wait.aligned;" ::: "memory");
      const uint32_t sb2 = __shfl_sync(~0u, sb, 0);
      uint32_t dst = sb2, bar = sb2 + BARS, ph = 1;
#pragma unroll 1
      for (int seg = 0; seg < 34; seg++) {
        const int n = seg >= 17 ? seg - 17 : seg;
        int ma, mb, ca, cb;
        if (n == 2) continue;
        if (n < 2) { ma = 0; mb = n; ca = 72 * j + 8 * odd + (n ? 0 : 576); cb = ca + (n ? 0 : 576); }
        else if (n < 12) { ma = 3; mb = 2; ca = cb = 576 * j + 64 * (n - 3); }
        else { ma = mb = 4; ca = n == 12 ? 512 : ((j + 2 * n) & 7) * 64; cb = ((j + 2 * n + 1) & 7) * 64; }
        const bool zip = n == 0 || n == 3, solo = n == 16;
#pragma unroll 1
        for (uint32_t st = 0; st < (solo ? 5 : 9); st++) {
          if (seg == 0 && st == NST - 2) mbar_wait(x_ring, 0);
          const uint32_t b = 2 * st + rank, kb = zip ? st : b >= 9 ? b - 9 : b;
          const bool second = zip ? rank : b >= 9;
          const int m = second ? mb : ma;
          const bool shared = kb == 8 && m > 0 && m < 4;
          const uint32_t ks = m == 4 ? 36 * j + 4 * kb : m == 0 ? 4 * blk(kb) : shared ? 0 : (9 * blk(kb) + 1) >> 1;
          asm volatile("{\n.reg .pred p, e, f;\n.reg .u32 n;\nelect.sync _|e, 0xffffffff;\nsetp.ne.and.u32 f, %8, 0, e;\nmov.u32 n, 0;\n"
                       "W: mbarrier.try_wait.parity.shared::cta.b64 p, [%1+48], %2;\n@p bra D;\n"
                       "add.u32 n, n, 1;\nsetp.lt.u32 p, n, 4194304;\n@p bra W;\ntrap;\n"
                       "D: @e mbarrier.arrive.expect_tx.shared::cta.b64 _, [%1], %7;\n"
                       "@f cp.async.bulk.tensor.3d.shared::cluster.global.mbarrier::complete_tx::bytes.multicast::cluster [%0], [%3, {%4, %5, %6}], [%1], 3;\n}"
                       :: "r"(dst + rank * 8192), "r"(bar), "r"(ph), "l"(&maps.m[m + (shared ? 7 : 0)]), "r"(second ? cb : ca),
                          "r"(shared ? 64 : 0), "r"(ks), "r"(solo && st == 4 ? STAGE / 2 : STAGE), "r"((uint32_t)!(solo && b == 9)) : "memory");
          dst += STAGE; bar += 8;
          if (dst == sb2 + NST * STAGE) { dst = sb2; bar -= 8 * NST; ph ^= 1; }
        }
      }
      {
#pragma unroll 1
        for (int i = 0; i < NST; i++) {
          mbar_wait_trap(bar + 48, ph);
          bar += 8;
          if (bar == full0 + 8 * NST) { bar = full0; ph ^= 1; }
        }
      }
    } else if (w == 9) {
      const uint32_t lane = lane_id();
      const uint32_t stg = sb + HSTG + lane * 16;
      uint32_t fph = 0;
#pragma unroll 1
      for (uint32_t layer = 0; layer < 2; layer++) {
        uint4* xb = scp + OFF_X + ((4 + layer) * 8 + j) * SLAB + 28 * 32;
        mbar_wait_sleep(c8_go, layer);
        int n = 0;
#pragma unroll 1
        while (true) {
          if (lane == 0) asm volatile("mbarrier.arrive.expect_tx.shared::cta.b64 _, [%0], 18432;" :: "r"(c8_full) : "memory");
          __syncwarp();
#pragma unroll 1
          for (uint32_t s = 0; s < 9; s++)
            bulk_load(sb + HSTG + s * 2048, s < 8 ? scp + OFF_P + (j + s * 8) * SLAB + 32 * 32 : xb, 2048, c8_full, false);
          mbar_wait(c8_full, fph); fph ^= 1;
          uint32_t bad = 0;
#pragma unroll 8
          for (int s = 0; s < 32; s++) { uint32_t v; asm volatile("ld.shared.b32 %0, [%1];" : "=r"(v) : "r"(stg + s * 512) : "memory"); bad |= v ^ (1 - layer); }
          if (__all_sync(~0u, (bad & 1u) == 0u)) break;
          __nanosleep(300);
          SPIN_GUARD(n);
        }
        asm volatile("bar.arrive 7, 96;" ::: "memory");
        float s0 = 0.f, s1 = 0.f;
#pragma unroll 1
        for (int g = 0; g < 8; g++) {
          const uint32_t a = stg + (g >> 1) * 512 + (g & 1) * 8;
          float a0 = 0.f, a1 = 0.f, a2 = 0.f, a3 = 0.f;
#pragma unroll 1
          for (int b = 0; b < 3; b++) {
            uint32_t v[6];
#pragma unroll
            for (int s = 0; s < 3; s++) lds2(a + (3 * b + s) * 2048, v + 2 * s);
#pragma unroll
            for (int s = 0; s < 3; s++) { a0 += bf_lo(v[2 * s]); a1 += bf_hi(v[2 * s]); a2 += bf_lo(v[2 * s + 1]); a3 += bf_hi(v[2 * s + 1]); }
          }
          sts1(a + 18432, pack_bf16(a0, a1)); sts1(a + 18436, pack_bf16(a2, a3));
          s0 += a0 + a1; s1 += a2 + a3;
        }
        __syncwarp();
        if (lane == 0) mbar_arrive(c8_done);
        s0 = quad_sum(s0); s1 = quad_sum(s1);
        float q0 = 0.f, q1 = 0.f;
        const uint32_t ln = lane_id();
#pragma unroll 1
        for (uint32_t i = 0; i < 4; i++) {
          uint32_t x[4];
          lds4(stg + 18432 + i * 512, x);
          uint4* z = xb + i * 32 + ln;
          asm volatile("" : "+l"(z));
          stg4(z, 0u, 0u, 0u, 0u);
          if (layer == 0) {
            stg4(z - (3 * 8 * SLAB - 128), nz(x[0]), x[1], nz(x[2]), x[3]);
#pragma unroll
            for (int e = 0; e < 4; e++) {
              const float m = (e & 1) ? s1 : s0, c = fmaf(m, -1.f / 64, bf_lo(x[e])), d = fmaf(m, -1.f / 64, bf_hi(x[e]));
              if (e & 1) q1 = fmaf(c, c, fmaf(d, d, q1)); else q0 = fmaf(c, c, fmaf(d, d, q0));
            }
          } else {
            uint32_t* o = (uint32_t*)(out + (128 * t + 32 * (j >> 1) + 2 * (ln >> 2) + (j & 1)) * 576 + 512 + 16 * i + 2 * (ln & 3));
            o[0] = x[0]; o[8 * 576] = x[1]; o[4] = x[2]; o[8 * 576 + 4] = x[3];
          }
        }
        if (layer == 0) {
          q0 = quad_sum(q0); q1 = quad_sum(q1);
          if ((ln & 3) == 0) stg4(scp + OFF_S + j * 96 + 64 + (ln >> 2), __float_as_uint(s0) | 1u, __float_as_uint(q0), __float_as_uint(s1), __float_as_uint(q1));
        }
      }
    } else {
      auto mark = [&](uint32_t k0, uint32_t v) {
        const uint32_t lane = lane_id();
#pragma unroll 1
        for (uint32_t k = k0; k < 6; k++) stg4(scp + OFF_S + (k * 4 + (lane >> 3)) * 96 + j * 8 + (lane & 7), k < 2 ? 0u : v, 0u, 0u, 0u);
      };
      if (w == 11) mark(2, 0u);
      auto phase2_duties = [&](uint32_t layer) {
        const uint32_t lane = lane_id();
        asm volatile("bar.sync 7, 96;" ::: "memory");
        if (w == 11) {
          if (layer == 0) mark(0, 1u);
          __syncwarp();
          if (lane == 0) mbar_arrive(c8_done);
        }
#pragma unroll 1
        for (uint32_t i = 0; i < 16; i++) {
          const uint32_t sl = (w - 10) * 4 + (i >> 2);
          bulk_load(sb + PARK + sl * 2048 + (i & 3) * 512, scp + OFF_X + ((4 + layer) * 8 + sl) * SLAB + row72(4 * j + (i & 3)) * 32, 512, res_full, true);
        }
        mbar_wait_sleep(res_full, layer);
#pragma unroll 1
        for (uint32_t i = 0; i < 16; i++) {
          stg4(scp + OFF_X + ((4 + layer) * 8 + (w - 10) * 4 + (i >> 2)) * SLAB + row72(4 * j + (i & 3)) * 32 + lane, 0u, 0u, 0u, 0u);
          if ((i & 3) == 3) __nanosleep(200);
        }
      };
      if (w == 10) {
        const uint32_t lane = lane_id();
        uint32_t* fl = (uint32_t*)(scratch + OFF_F + (t * 8 + j) * 8) + (lane & 15);
        uint32_t v;
        asm volatile("ld.relaxed.gpu.global.b32 %0, [%1];" : "=r"(v) : "l"(fl) : "memory");
        mbar_wait(piece_full, 0);
        asm volatile("{\n.reg .pred e;\nelect.sync _|e, 0xffffffff;\n@e cp.async.bulk.global.shared::cta.bulk_group [%0], [%1], 2304;\n}\n"
                     "cp.async.bulk.commit_group;\ncp.async.bulk.wait_group 0;\nfence.proxy.async;"
                     :: "l"(scratch + OFF_R + j * 2304 + t * 144), "r"(sb + PIECE) : "memory");
        __syncwarp();
        if (lane < 16) asm volatile("st.release.gpu.global.b32 [%0], 1;" :: "l"((uint32_t*)(scratch + OFF_F + (lane_id() * 8 + j) * 8) + t) : "memory");
        int n = 0;
#pragma unroll 1
        while (!__all_sync(~0u, v != 0u)) {
          __nanosleep(100);
          SPIN_GUARD(n);
          asm volatile("ld.relaxed.gpu.global.b32 %0, [%1];" : "=r"(v) : "l"(fl) : "memory");
        }
        asm volatile("st.relaxed.gpu.global.b32 [%0], 0;" :: "l"(fl) : "memory");
        mbar_wait(x_done, 0);
      }
#pragma unroll 1
      for (uint32_t layer = 0; layer < 3; layer++) {
        if (w == 10 && layer < 2) {
          if (layer) mbar_wait_sleep(park_free, 0);
          const uint4* img = scratch + OFF_R + j * 2304;
          if (lane_id() == 0) asm volatile("mbarrier.arrive.expect_tx.shared::cta.b64 _, [%0], 27648;\nmbarrier.arrive.expect_tx.shared::cta.b64 _, [%1], 9216;"
                                           :: "r"(rem_full), "r"(piece_full) : "memory");
          __syncwarp();
#pragma unroll 1
          for (uint32_t p = 0; p < 3; p++) {
            bulk_load(sb + REM + p * 9216, img + p * 576 + j * 64, 1024, rem_full, false);
            if (j) bulk_load(sb + REM + p * 9216 + 1024, img + p * 576, j * 1024, rem_full, false);
            bulk_load(sb + REM + p * 9216 + (j + 1) * 1024, img + p * 576 + (j + 1) * 64, (8 - j) * 1024, rem_full, false);
          }
#pragma unroll 1
          for (uint32_t i = 0; i < 12; i++)
            bulk_load(sb + REM + 27648 + (i < 8 ? i * 1024 : 6144 + i * 256), img + 1728 + (i < 8 ? (9 * blk(i) + 1) >> 1 : 9 * i - 68) * 16,
                      i < 8 ? 1024 : 256, piece_full, false);
          if (layer == 0) { fetch_x(sb + PARK, j, xbar0); fetch_x(sb + PARK + STAGE, j + 1, xbar0 + 8); }
        }
        if (w == 11 && layer < 2) {
          if (layer) mbar_wait_sleep(park_free, 0);
          __syncwarp();
          if (lane_id() == 0) mbar_arrive(rem_full);
        }
        if (layer) phase2_duties(layer - 1);
        if (layer == 2) break;
        mbar_wait(kv_free, layer);
        if (t > 0) {
          const uint32_t lane = lane_id(), r = lane >> 2, q = lane & 3;
#pragma unroll 1
          for (uint32_t pc = 0; pc < 3; pc++) {
            uint4* hp = scp + OFF_H + ((layer * 8 + j) * 2 + (w - 10)) * 192 + pc * 64 + lane;
            uint32_t hl[8];
            int n = 0;
            hl[4] = 1u;
#pragma unroll 1
            while (true) {
              ldg4(hl, hp);
              if (pc < 2) ldg4(hl + 4, hp + 32);
              if (__all_sync(~0u, hl[0] != 0u && hl[4] != 0u)) break;
              __nanosleep(100);
              SPIN_GUARD(n);
            }
            const uint32_t dst = sb + KVS + (w - 10) * 10368 + r * 144 + q * 4;
            if (pc < 2) {
#pragma unroll
              for (int g = 0; g < 8; g++) sts1(dst + pc * 20736 + odd * 16 + g * 16, hl[g]);
              stg4(hp + 32, 0u, 0u, 0u, 0u);
            } else {
              sts1(dst + (odd ? 0 : 128), hl[0]); sts1(dst + 20736 + (odd ? 0 : 128), hl[1]);
            }
            stg4(hp, 0u, 0u, 0u, 0u);
          }
        }
        asm volatile("bar.arrive 1, 192;" ::: "memory");
        mbar_wait(rem_full, layer);
        mbar_wait(piece_full, 1 - layer);
#pragma unroll 1
        for (uint32_t b = 0; b < 5; b++) {
          const uint32_t blk = sb + REM + 27648 + b * 2048, k = (w - 10) * 32 + lane_id(), rr = k & 7;
          const uint32_t dst = blk + ((k >> 3) & 1) * 1024 + rr * 128 + (((k >> 4) ^ rr) << 4);
          uint32_t v[8];
          lds4(blk + k * 16, v); lds4(blk + 1024 + k * 16, v + 4);
          asm volatile("bar.sync 3, 64;" ::: "memory");
          sts4(dst, v); sts4(dst ^ 64, v + 4);
        }
        asm volatile("fence.proxy.async.shared::cta;" ::: "memory");
        mbar_arrive(remo_full);
        mbar_wait_sleep(xb_done, layer);
        if (w == 10 && layer == 1) {
          const uint32_t lane = lane_id();
          stg4(scp + OFF_S + (lane >> 3) * 96 + j * 8 + (lane & 7), 0u, 0u, 0u, 0u);
          stg4(scp + OFF_S + (4 + (lane >> 3)) * 96 + j * 8 + (lane & 7), 0u, 0u, 0u, 0u);
          if (lane < 8) stg4(scp + OFF_S + j * 96 + 64 + lane, 0u, 0u, 0u, 0u);
        }
#pragma unroll 1
        for (uint32_t i = 0; i < 8 && (w == 11 || layer == 1); i++) {
          zero_share(scp + OFF_X + ((w - 10) * 16 + layer * 8 + i) * SLAB, j, lane_id());
          __nanosleep(500);
        }
      }
    }
  } else {
    asm volatile("setmaxnreg.inc.sync.aligned.u32 240;");
    const bool lead = lane_id() == 0;
    Ring rg{0, 0};
    uint32_t prev = 0;
    uint32_t X[144];
    float rs0, rs1;
    const bool lead2 = lane_id() < 2;
    uint32_t empty_at;
    asm volatile("mapa.shared::cluster.u32 %0, %1, %2;" : "=r"(empty_at) : "r"(empty0), "r"(lane_id() & 1));
    auto release = [&](uint32_t st) { if (lead2) asm volatile("mbarrier.arrive.shared::cluster.b64 _, [%0];" :: "r"(empty_at + st * 8) : "memory"); };
    auto load_kb = [&](int kb, const uint4* src, const char* lo, uint32_t hoff) {
      const uint4* p;
      asm("{\n.reg .pred p;\n.reg .u64 t;\nsetp.ge.u32 p, %2, %3;\nadd.u64 t, %1, -2048;\nselp.b64 %0, t, %1, p;\n}" : "=l"(p) : "l"(src), "r"(j), "r"(kb));
#pragma unroll
      for (int i = 0; i < 4; i++) {
        if (kb == 8) { ldg2(X + 128 + 4 * i, lo + (32 + i) * 512); ldg2(X + 130 + 4 * i, lo + hoff + (32 + i) * 512); }
        else ldg4(X + 16 * kb + 4 * i, p + kb * 128 + i * 32);
      }
    };
    auto check_kb = [&](bool skip, int kb, const uint4* src, const char* lo, uint32_t hoff) {
      int n = 0;
#pragma unroll 1
      while (true) {
        uint32_t m = umin2(umin2(X[16 * kb], X[16 * kb + 4]), umin2(X[16 * kb + 8], X[16 * kb + 12]));
        if (kb == 8) m = umin2(m, umin2(umin2(X[130], X[134]), umin2(X[138], X[142])));
        if (__all_sync(~0u, m != 0u || skip)) break;
        SPIN_GUARD(n);
        load_kb(kb, src, lo, hoff);
      }
    };
#pragma unroll
    for (int i = 0; i < 16; i++) X[i] = 0u;
#pragma unroll 1
    for (uint32_t hf = 0; hf < 4; hf++) {
      const uint32_t layer = hf >> 1;
      const bool ffn = hf & 1;
      const uint32_t tag = 1 - layer;
      const uint32_t xbase = scr + OFF_X + (layer * 8 + w) * SLAB;
      float aA[32], aB[32];
      {
        const uint32_t lane = lane_id(), r = lane >> 2, q = lane & 3;
        const uint4* src = at(xbase + (ffn ? 32 * SLAB : 0) + lane);
        const char* lo = (const char*)at8(2 * (xbase + (ffn ? 32 * SLAB : 0)) + (ffn ? lane : 2 * lane));
        const uint32_t hoff = ffn ? 256 : 8;
        const uint32_t xoff = (w & 1) * 8192 + (16 * (w >> 1) + (lane & 15)) * 128 + (((lane >> 4) ^ (lane & 7)) << 4);
        auto load_x = [&](uint32_t b, uint32_t* d) {
#pragma unroll
          for (int i = 0; i < 4; i++) ldsm4(xs + b * STAGE + (xoff ^ (32 * i)), d[4 * i], d[4 * i + 1], d[4 * i + 2], d[4 * i + 3]);
        };
        auto load_any = [&](int kb) { if (hf == 0) load_x(blk(kb), X + 16 * kb); else load_kb(kb, src, lo, hoff); };
        float m0, m1, v0, v1;
        STAMP(ffn * 16 + 0);
        if (hf == 0) {
          float sum[2][4] = {}, sq0[4][4] = {}, sq1[4][4] = {};
          uint32_t p0, p1;
          mbar_wait(xbar0, 0);
          ldsm4(xs + xoff, p0, p1, X[0], X[1]);
          p0 = __byte_perm(__shfl_sync(~0u, p0, lane & 28), 0, 0x1010); p1 = __byte_perm(__shfl_sync(~0u, p1, lane & 28), 0, 0x1010);
#pragma unroll 3
          for (uint32_t b = 0; b < 9; b++) {
            uint32_t d[16];
            mbar_wait(xbar0 + 8 * b, 0);
            load_x(b, d);
#pragma unroll
            for (int i = 0; i < 16; i++) d[i] = sub_bf16x2(d[i], (i & 1) ? p1 : p0);
#pragma unroll
            for (int g = 0; g < 8; g++) {
              if (!(g & 1)) mma16(sum[(g >> 1) & 1], d[2 * g], d[2 * g + 1], d[2 * g + 2], d[2 * g + 3], 0x3f803f80u, 0x3f803f80u);
              mma8(sq0[g & 3], d[2 * g], d[2 * g + 1], d[2 * g]); mma8(sq1[g & 3], d[2 * g], d[2 * g + 1], d[2 * g + 1]);
            }
          }
          STAMP(1);
          GSTAMP(14);
#pragma unroll
          for (int kb = 0; kb < GD; kb++) load_x(blk(kb), X + 16 * kb);
          release((x_ring - empty0) / 8);
          auto tot = [](float (&c)[4][4], int e) { return (c[0][e] + c[1][e]) + (c[2][e] + c[3][e]); };
          const float a0 = (sum[0][0] + sum[1][0]) * (1.f / 576), a1 = (sum[0][2] + sum[1][2]) * (1.f / 576);
          const uint32_t dg = (lane & 28) + (r >> 1);
          v0 = fmaxf(fmaf(__shfl_sync(~0u, (r & 1) ? tot(sq0, 1) : tot(sq0, 0), dg), 1.f / 576, -a0 * a0), 0.f);
          v1 = fmaxf(fmaf(__shfl_sync(~0u, (r & 1) ? tot(sq1, 3) : tot(sq1, 2), dg), 1.f / 576, -a1 * a1), 0.f);
          m0 = bf_lo(p0) + a0; m1 = bf_lo(p1) + a1;
        } else {
          uint32_t s[3][4];
          const uint4* p = at(scr + OFF_S + ((ffn ? 16 : 0) + w) * 96 + q * 8 + r);
          const bool third = !ffn && q == 0;
          const uint32_t rdy = ffn ? tag : 1u;
          int n = 0;
          s[2][0] = rdy; s[2][1] = s[2][2] = s[2][3] = 0u;
#pragma unroll 1
          while (true) {
            ldg4(s[0], p); ldg4(s[1], p + 32);
            if (third) ldg4(s[2], p + 64);
            if (__all_sync(~0u, ((diff2(s[0][0], s[1][0], rdy) | diff2(s[1][0], s[2][0], rdy)) & 1u) == 0u)) break;
            SPIN_GUARD(n);
          }
          STAMP(ffn * 16 + 1);
          ZSTAMP(1 + ffn, 0);
          GSTAMP(14 + ffn);
#pragma unroll
          for (int kb = 1; kb < GD; kb++) load_kb(kb, src, lo, hoff);
          float t0 = 0.f, t1 = 0.f;
#pragma unroll
          for (int i = 0; i < 3; i++) { t0 += __uint_as_float(s[i][0]); t1 += __uint_as_float(s[i][2]); }
          m0 = quad_sum(t0) * (1.f / 576); m1 = quad_sum(t1) * (1.f / 576);
          const float cnt = ffn ? 72.f : 64.f, inv = ffn ? 1.f / 72 : 1.f / 64;
          v0 = 0.f; v1 = 0.f;
#pragma unroll
          for (int i = 0; i < 3; i++) {
            const float c = (i < 2 || third) ? cnt : 0.f;
            const float d0 = fmaf(__uint_as_float(s[i][0]), inv, -m0), d1 = fmaf(__uint_as_float(s[i][2]), inv, -m1);
            v0 += fmaf(d0 * d0, c, __uint_as_float(s[i][1])); v1 += fmaf(d1 * d1, c, __uint_as_float(s[i][3]));
          }
          v0 = quad_sum(v0) * (1.f / 576); v1 = quad_sum(v1) * (1.f / 576);
        }
        rs0 = rsqrtf(v0 + 1e-5f); rs1 = rsqrtf(v1 + 1e-5f);
        const uint32_t mean0 = pack_bf16(m0, m0), mean1 = pack_bf16(m1, m1);
#pragma unroll
        for (int kb = 0; kb < 9; kb++) {
          if (kb > 0) check_kb(hf == 0, kb, src, lo, hoff);
          if (kb + GD < 9) load_any(kb + GD);
          if (kb + GD == 8 && hf == 0 && lead) mbar_arrive(x_done);
#pragma unroll
          for (int i = 16 * kb; i < 16 * kb + 16; i++) X[i] = sub_bf16x2(X[i], (i & 1) ? mean1 : mean0);
          ZSTAMP(1 + ffn, 1 + 3 * kb);
          mbar_wait(full0 + rg.st * 8, rg.ph);
          ZSTAMP(1 + ffn, 2 + 3 * kb);
          const uint64_t desc = DESC_HI | ((sd + rg.st * STAGE) >> 4);
          wg_fence();
#pragma unroll
          for (int i = 0; i < 4; i++) wgmma_rs_n64(aA, X + 4 * (4 * kb + i), desc + i * 128, kb + i != 0);
          if (kb == 8) { wg_commit(); wg_wait<1>(); wg_fence(); }
#pragma unroll
          for (int i = 0; i < 4; i++) wgmma_rs_n64(aB, X + 4 * (4 * kb + i), desc + 512 + i * 128, kb + i != 0);
          wg_commit();
          wg_wait<1>();
          ZSTAMP(1 + ffn, 3 + 3 * kb);
          if (kb > 0) release(prev);
          prev = rg.st; rg.next();
        }
        ZSTAMP(1 + ffn, 28);
        ZSTAMP(4, 0);
        STAMP(ffn * 16 + 2);
      }
      if (!ffn) {
      const uint32_t lane = lane_id(), r = lane >> 2, q = lane & 3;
      const uint32_t kvrow = sb + KVS + (w & 1) * 10368 + (16 * (w >> 1)) * 144;
      uint32_t Q[18], Km[3][8], Ke[3][4];
      const bool edge = (t == 0 && w < 2);
      const uint32_t row0 = edge ? sb + KVS + 8 * 144 : kvrow + (lane & 7) * 144, row1 = kvrow + (8 + (lane & 7)) * 144;
      {
        const uint32_t dst = kvrow + (8 + r) * 144 + q * 4 + odd * 16, dstr = dst + (odd ? -16 : 128);
        const bool edge_out = w >= 6 && t < 15;
        uint4* const hp = at(scr + TILE + OFF_H + ((layer * 8 + j) * 2 + (w & 1)) * 192 + lane);
        auto put_kv = [&](float (&a)[32], int part, int half) {
          uint32_t hl[4];
#pragma unroll
          for (int i = 0; i < 16; i++) asm volatile("" : "+f"(a[16 * half + i]) :: "memory");
#pragma unroll
          for (int i = 0; i < 4; i++) {
            const int g = 4 * half + i;
            hl[i] = pack_bf16(a[4 * g + 2] * rs1, a[4 * g + 3] * rs1);
            sts1(dst + part * 20736 + g * 16, pack_bf16(a[4 * g] * rs0, a[4 * g + 1] * rs0)); sts1(dst + part * 20736 + 8 * 144 + g * 16, hl[i]);
          }
          if (edge_out) stg4(hp + part * 64 + half * 32, nz(hl[0]), hl[1], hl[2], hl[3]);
        };
        put_kv(aA, 0, 0); put_kv(aA, 0, 1);
        if (lead) mbar_arrive(kv_free);
        wg_wait<0>();
        release(prev);
        float aR[12];
        mbar_wait(rem_full, layer);
        const uint64_t dr = DESC_REM | ((sd + REM) >> 4);
        wg_fence();
#pragma unroll
        for (int s = 0; s < 36; s++) {
          wgmma_rs_n24(aR, X + 4 * s, dr + s * 16, s != 0);
          if (s == 4) put_kv(aB, 1, 0);
          if (s == 16) put_kv(aB, 1, 1);
        }
        wg_commit();
#pragma unroll
        for (int kb = 0; kb < 9; kb++) {
          if (!(kb & 1)) mbar_wait(full0 + rg.st * 8, rg.ph);
          const uint64_t desc = DESC_HI | ((sd + rg.st * STAGE + (kb & 1) * 8192) >> 4);
          wg_fence();
#pragma unroll
          for (int i = 0; i < 4; i++) wgmma_rs_n64(aB, X + 4 * (4 * kb + i), desc + i * 128, kb + i != 0);
          wg_commit();
          wg_wait<1>();
          if (kb > 0 && !(kb & 1)) release(prev);
          if (kb & 1) { prev = rg.st; rg.next(); }
          if (kb == 0) {
            pin(aR);
            const uint32_t k1 = pack_bf16(aR[2] * rs1, aR[3] * rs1), v1 = pack_bf16(aR[6] * rs1, aR[7] * rs1);
            if (edge_out) stg4(hp + 128, nz(k1), v1, 0u, 0u);
            sts1(dstr, pack_bf16(aR[0] * rs0, aR[1] * rs0)); sts1(dstr + 8 * 144, k1);
            sts1(dstr + 20736, pack_bf16(aR[4] * rs0, aR[5] * rs0)); sts1(dstr + 20736 + 8 * 144, v1);
            Q[16] = pack_bf16(aR[8], aR[9]); Q[17] = pack_bf16(aR[10], aR[11]);
            if (w < 4) asm volatile("bar.arrive 2, 256;" ::: "memory");
          }
          if (kb == 8) {
            if (w < 4) asm volatile("bar.sync 1, 192;" ::: "memory");
            else asm volatile("bar.sync 2, 256;" ::: "memory");
#pragma unroll
            for (int nt = 0; nt < 3; nt++) {
              const uint32_t ra = (nt == 0 ? row0 : row1 + (nt - 1) * 8 * 144);
              ldsm4(ra + odd * 16 + (lane >> 3) * 16, Km[nt][0], Km[nt][1], Km[nt][2], Km[nt][3]);
              ldsm4(ra + odd * 16 + 64 + (lane >> 3) * 16, Km[nt][4], Km[nt][5], Km[nt][6], Km[nt][7]);
              ldsm4(ra + (odd ? 0 : 32) + (lane >> 3) * 32, Ke[nt][0], Ke[nt][1], Ke[nt][2], Ke[nt][3]);
            }
            const uint32_t ge = (2u << q) - 1, le = 0xfu << q, on = edge ? 0u : ~0u;
            const uint32_t bits = odd ? 0xfu | ((le & 0xfu) << 4) | (ge << 8) : ge | 0xf0u | (le << 8);
#pragma unroll
            for (int h = 0; h < 4; h++) {
              const uint32_t ma = bitmask(bits, h), mb = bitmask(bits, 4 + h), mc = bitmask(bits, 8 + h);
              Km[0][2 * h] &= ma & on; Km[0][2 * h + 1] &= mb & on; Ke[0][h] &= mc & on;
#pragma unroll
              for (int nt = 1; nt < 3; nt++) { Km[nt][2 * h] &= ma; Km[nt][2 * h + 1] &= mb; Ke[nt][h] &= mc; }
            }
          }
        }
        wg_wait<0>();
        pin(aB);
        if (w < 4) asm volatile("bar.sync 4, 256;" ::: "memory");
        STAMP(3);
#pragma unroll
        for (int i = 0; i < 16; i++) Q[i] = pack_bf16(aB[2 * i], aB[2 * i + 1]);
      }
      uint32_t res[18] = {};
      if (layer) {
        const uint4* p = at(xbase + ((9 * j + 1) >> 1) * 32 + lane);
#pragma unroll
        for (int i = 0; i < 4; i++) ldg4(res + 4 * i, p + i * 32);
        ldg2(res + 16, at8(2 * (xbase + (9 * (j >> 1) + 4) * 32 + lane) + odd));
      }
      {
        uint32_t V01[12][2], V2[12];
        const uint32_t rv = ((lane & 8) ? row1 : row0) + 20736, rw = row1 + 8 * 144 + 20736;
#pragma unroll
        for (int i = 0; i < 4; i++) ldsm4t(rv + odd * 16 + i * 32 + (lane >> 4) * 16, V01[2 * i][0], V01[2 * i][1], V01[2 * i + 1][0], V01[2 * i + 1][1]);
#pragma unroll
        for (int i = 0; i < 2; i++) ldsm4t(rv + (odd ? 0 : 32) + i * 64 + (lane >> 4) * 32, V01[8 + 2 * i][0], V01[8 + 2 * i][1], V01[9 + 2 * i][0], V01[9 + 2 * i][1]);
        ldsm4t(rw + odd * 16 + (lane >> 3) * 16, V2[0], V2[1], V2[2], V2[3]);
        ldsm4t(rw + odd * 16 + 64 + (lane >> 3) * 16, V2[4], V2[5], V2[6], V2[7]);
        ldsm4t(rw + (odd ? 0 : 32) + (lane >> 3) * 32, V2[8], V2[9], V2[10], V2[11]);
        const bool up0 = 2 * q > r, up1 = 2 * q + 1 > r;
        const uint32_t upm = (up0 ? 0xffffu : 0u) | (up1 ? 0xffff0000u : 0u);
        const float c0 = 0.23570226039551584f * 1.4426950408889634f * rs0, c1 = 0.23570226039551584f * 1.4426950408889634f * rs1;
        const float masked = edge ? -1e9f * 1.4426950408889634f * rcp(c0) : 0.f;
        uint32_t Om[16], Oe[8];
        uint4* const po = at(xbase + 16 * SLAB + 4 * j * 32 + lane);
#pragma unroll
        for (int h = 0; h < 4; h++) {
          const uint32_t e0 = odd ? Q[(4 * h + 16) % 18] : Q[4 * h + 4], e1 = odd ? Q[(4 * h + 17) % 18] : Q[4 * h + 5];
          float S[3][4];
#pragma unroll
          for (int nt = 0; nt < 3; nt++) {
            mma16c(S[nt], Q + 4 * h, Km[nt][2 * h], Km[nt][2 * h + 1], nt == 0 ? masked : 0.f);
            mma8(S[nt], e0, e1, Ke[nt][h]);
          }
          const float s00 = up0 ? S[0][0] : S[1][0], s01 = up1 ? S[0][1] : S[1][1];
          const float s10 = up0 ? S[1][2] : S[2][2], s11 = up1 ? S[1][3] : S[2][3];
          const float m0 = quad_max(fmaxf(s00, s01)) * c0, m1 = quad_max(fmaxf(s10, s11)) * c1;
          const float p00 = ex2(fmaf(s00, c0, -m0)), p01 = ex2(fmaf(s01, c0, -m0)), p10 = ex2(fmaf(s10, c1, -m1)), p11 = ex2(fmaf(s11, c1, -m1));
          const float i0 = rcp(quad_sum(p00 + p01)), i1 = rcp(quad_sum(p10 + p11));
          const uint32_t p0 = pack_bf16(p00 * i0, p01 * i0), p1 = pack_bf16(p10 * i1, p11 * i1);
          const uint32_t pf[4] = {p0 & upm, 0u, p0 & ~upm, p1 & upm};
#pragma unroll
          for (int gi = 0; gi < 3; gi++) {
            const int g = gi < 2 ? 2 * h + gi : 8 + h;
            float o[4];
            mma16c(o, pf, V01[g][0], V01[g][1], 0.f);
            mma8(o, 0u, p1 & ~upm, V2[g]);
            uint32_t* d = gi < 2 ? Om + 2 * g : Oe + 2 * h;
            d[0] = pack_bf16(o[0], o[1]); d[1] = pack_bf16(o[2], o[3]);
          }
          if (h > 0) {
#pragma unroll
            for (int e = 0; e < 2; e++) {
              if (!odd && q < h) Om[4 * h + e] = Oe[2 * h - 2 + e];
              if (odd && q >= h) Om[4 * h - 2 + e] = Oe[2 * h + e];
            }
            Om[4 * h - 4] = nz(Om[4 * h - 4]);
            stg4(po + (h - 1) * 32, Om[4 * h - 4], Om[4 * h - 3], Om[4 * h - 2], Om[4 * h - 1]);
            if (h == 1 && w >= 4) asm volatile("bar.arrive 4, 256;" ::: "memory");
          }
        }
        STAMP(4);
        Om[12] = nz(Om[12]);
        stg4(po + 96, Om[12], Om[13], Om[14], Om[15]);
        stg2(at8(2 * (xbase + 16 * SLAB + 1024 + j * 16) + lane), nz(odd ? Oe[0] : Oe[6]), odd ? Oe[1] : Oe[7]);
#pragma unroll
        for (int i = 0; i < 16; i++) X[i] = Om[i];
      }
      if (lane == 0) asm volatile("st.relaxed.gpu.global.b32 [%0], %1;" :: "l"(at(scr + OFF_S + (8 + w) * 96 + j * 8)), "r"(tag) : "memory");
      {
        if (layer == 0) {
          const uint32_t xrow = (w & 1) * 8192 + (16 * (w >> 1) + (lane & 15)) * 128;
          uint32_t u0, u1;
          mbar_wait(xbar0, 1); mbar_wait(xbar0 + 8, 1);
#pragma unroll
          for (int i = 0; i < 5; i++) {
            const uint32_t g = i < 4 ? j + odd + 2 * i : j + (odd ? 0 : 8);
            const uint32_t a = sb + PARK + (g >> 3) * STAGE + xrow;
            if (i < 4) ldsm4(a + ((((g & 7) + (lane >> 4)) ^ (lane & 7)) << 4), res[4 * i], res[4 * i + 1], res[4 * i + 2], res[4 * i + 3]);
            else ldsm4(a + (((g & 7) ^ (lane & 7)) << 4), res[16], res[17], u0, u1);
          }
        }
        const uint4* src = at(xbase + 16 * SLAB + lane);
        const uint32_t st0 = rg.st;
        auto stage_of = [&](uint32_t i) { const uint32_t x = st0 + i; return x >= NST ? x - NST : x; };
        {
          const uint32_t x = st0 + lane, wrap = x >= NST;
          mbar_wait(lane < 5 ? full0 + (x - wrap * NST) * 8 : remo_full, lane < 5 ? rg.ph ^ wrap : layer);
          __syncwarp();
          if (st0) { rg.st = st0 - 1; rg.ph ^= 1; } else rg.st = 5;
        }
        float acc[36];
        auto block72 = [&](uint32_t kb, uint32_t base, const uint32_t* a) {
          const uint64_t d0 = DESC_HI | ((base >> 4) + (((sd + REM + 27648 + (kb >> 1) * 2048 + (kb & 1) * 64 - base) >> 4) << 16));
          wg_fence();
#pragma unroll
          for (int i = 0; i < 4; i++) wgmma_rs_n72(acc, a + 4 * i, d0 - (uint64_t)(i * ((127u << 16) - 128u)), 1);
          wg_commit();
        };
#pragma unroll
        for (int i = 0; i < 18; i++) { acc[2 * i] = bf_lo(res[i]); acc[2 * i + 1] = bf_hi(res[i]); }
        block72(0, sd + st0 * STAGE + 8192, X);
        {
          const uint4* fp = at(scr + OFF_S + (8 + w) * 96 + (lane & 7) * 8);
          int n = 0;
          STAMP(8);
#pragma unroll 1
          while (true) {
            uint32_t f;
            asm volatile("ld.relaxed.gpu.global.b32 %0, [%1];" : "=r"(f) : "l"(fp) : "memory");
            if (__all_sync(~0u, f == tag)) break;
            SPIN_GUARD(n);
          }
          wg_wait<0>(); release(st0);
          STAMP(9);
        }
#pragma unroll
        for (int kb = 1; kb < GO; kb++) load_kb(kb, src, (const char*)src - lane * 8, 256);
        __syncwarp();
        uint32_t m = ~0u;
#pragma unroll
        for (int kb = 1; kb < 9; kb++) {
          m = umin2(m, umin2(umin2(X[16 * kb], X[16 * kb + 4]), umin2(X[16 * kb + 8], X[16 * kb + 12])));
          if (kb == 8) m = umin2(m, umin2(umin2(X[130], X[134]), umin2(X[138], X[142])));
          if (kb + GO - 1 < 9) {
            const uint4* s2 = src + (m == 0u);
            load_kb(kb + GO - 1, s2, (const char*)s2 - lane * 8, 256);
            __syncwarp();
          }
          block72(kb, sd + stage_of((kb + 1) >> 1) * STAGE + (~kb & 1) * 8192, X + 16 * kb);
          if ((kb & 1) && kb > 1) { wg_wait<1>(); release(stage_of(kb >> 1)); }
        }
        uint32_t redo;
        asm volatile("{\n.reg .pred p;\nsetp.eq.u32 p, %1, 0;\nbar.red.or.pred p, %2, 128, p;\nselp.u32 %0, 1, 0, p;\n}" : "=r"(redo) : "r"(m), "r"(5 + (w >> 2)) : "memory");
        wg_wait<0>();
        release(stage_of(4));
        pin(acc);
        if (__any_sync(~0u, redo || FORCE_REDO)) {
#pragma unroll
          for (int i = 0; i < 18; i++) { res[i] = __shfl_sync(~0u, res[i], lane); acc[2 * i] = bf_lo(res[i]); acc[2 * i + 1] = bf_hi(res[i]); }
          const uint32_t box = PARK + 2 * STAGE + (w >> 2) * 8192, bar = redo_full + (w >> 2) * 8;
#pragma unroll 1
          for (uint32_t kb = 0; kb < 10; kb++) {
            asm volatile("bar.sync %0, 128;" :: "r"(5 + (w >> 2)) : "memory");
            if ((w & 3) == 0)
              asm volatile("{\n.reg .pred e;\nelect.sync _|e, 0xffffffff;\n@e mbarrier.arrive.expect_tx.shared::cta.b64 _, [%2], 8192;\n"
                           "@e cp.async.bulk.tensor.3d.shared::cluster.global.mbarrier::complete_tx::bytes [%0], [%1, {%3, %4, %5}], [%2];\n}"
                           :: "r"(sb + box), "l"(&maps.m[kb >= 8 ? 8 : 1]), "r"(bar), "r"(72 * j + 8 * odd), "r"(kb >= 8 ? 64 : 0),
                              "r"(kb >= 8 ? 0 : (9 * blk(kb) + 1) >> 1) : "memory");
            mbar_wait(bar, kb & 1);
            if (kb == 9) break;
            int n = 0;
#pragma unroll 1
            while (true) {
              const char* l = (const char*)(src + blk(kb) * 128) - (kb == 8 ? lane * 8 : 0);
#pragma unroll
              for (int i = 0; i < 4; i++) ldg2(X + 4 * i, l + i * 512);
              uint32_t mm = umin2(umin2(X[0], X[4]), umin2(X[8], X[12]));
              l += (kb == 8 ? 256 : 8) + (mm == 0u ? 16 : 0);
#pragma unroll
              for (int i = 0; i < 4; i++) ldg2(X + 4 * i + 2, l + i * 512);
              if (kb == 8) mm = umin2(mm, umin2(umin2(X[2], X[6]), umin2(X[10], X[14])));
              if (__all_sync(~0u, mm != 0u)) break;
              SPIN_GUARD(n);
            }
            block72(kb, sd + box, X);
            wg_wait<0>();
            pin(acc);
          }
        }
        STAMP(10);
#pragma unroll
        for (int i = 0; i < 18; i++) { res[i] = pack_bf16(acc[2 * i], acc[2 * i + 1]); if (!(i & 3)) res[i] = nz(res[i]); }
        auto put = [&] {
          put4(at(xbase + 32 * SLAB + 4 * j * 32 + lane), res);
          stg2(at8(2 * (xbase + 32 * SLAB + 1024 + j * 16) + lane), res[16], res[17]);
        };
        if (j < PRI) put();
        publish_stats<9>(at(scr + OFF_S + (16 + w) * 96 + j * 8 + r), acc, tag, lane);
        if (j >= PRI) put();
#pragma unroll
        for (int i = 0; i < 16; i++) X[i] = res[i];
      }
      continue;
      }
      const uint32_t hp = sb + PARK + w * 512 + lane_id() * 16;
      auto pack8 = [&](float (&a)[32], int p, uint32_t* o) {
#pragma unroll
        for (int e = 0; e < 8; e++) asm volatile("" : "+f"(a[8 * p + e]) :: "memory");
#pragma unroll
        for (int e = 0; e < 4; e++) o[e] = pack_bf16(a[8 * p + 2 * e], a[8 * p + 2 * e + 1]);
      };
      const float ka0 = 0.7978845608028654f * rs0, kb0 = 0.044715f * ka0 * rs0 * rs0, ku0 = 0.5f * rs0 * rs0;
      const float ka1 = 0.7978845608028654f * rs1, kb1 = 0.044715f * ka1 * rs1 * rs1, ku1 = 0.5f * rs1 * rs1;
      auto packu8 = [&](int p, uint32_t* o) {
#pragma unroll
        for (int e = 0; e < 8; e++) asm volatile("" : "+f"(aA[8 * p + e]) :: "memory");
#pragma unroll
        for (int e = 0; e < 4; e++) o[e] = pack_bf16(aA[8 * p + 2 * e] * ((e & 1) ? ku1 : ku0), aA[8 * p + 2 * e + 1] * ((e & 1) ? ku1 : ku0));
      };
      auto geglu8 = [&](int p, uint32_t* u) {
#pragma unroll
        for (int e = 0; e < 8; e++) asm volatile("" : "+f"(aB[8 * p + e]) :: "memory");
        float h[8];
#pragma unroll
        for (int e = 0; e < 8; e++) {
          const float g = aB[8 * p + e];
          h[e] = fmaf(g, tanh_ap(g * fmaf(g * g, (e & 2) ? kb1 : kb0, (e & 2) ? ka1 : ka0)), g);
        }
#pragma unroll
        for (int e = 0; e < 4; e++) u[e] = mul_bf16x2(pack_bf16(h[2 * e], h[2 * e + 1]), u[e]);
      };
      uint32_t ready = 0;
      auto box = [&](int b, auto&& filler) {
        const int kb = b < 9 ? b : b - 9;
        if (b == 0) mbar_wait_trap(full0 + rg.st * 8, rg.ph);
        else if (!(b & 1)) mbar_wait_unless(ready, full0 + rg.st * 8, rg.ph);
        const uint64_t desc = DESC_HI | ((sd + rg.st * STAGE + (b & 1) * 8192) >> 4);
        if (b & 1) { prev = rg.st; rg.next(); }
        wg_fence();
#pragma unroll
        for (int i = 0; i < 4; i++) {
          if (b < 9) wgmma_rs_n64(aA, X + 4 * (4 * kb + i), desc + i * 128, kb + i != 0);
          else wgmma_rs_n64(aB, X + 4 * (4 * kb + i), desc + i * 128, kb + i != 0);
          if ((b & 1) && b < 17 && i == 0) ready = mbar_peek(full0 + rg.st * 8, rg.ph);
          if (i == 1) filler();
        }
        wg_commit();
        if (!(b & 1)) { wg_wait<1>(); release(prev); }
      };
      auto nop = [] {};
#pragma unroll
      for (int p = 0; p < 4; p++) { uint32_t o[4]; packu8(p, o); sts4(hp + p * 4096, o); }
      box(0, nop);
      if (lead) mbar_arrive(xb_done);
#pragma unroll 1
      for (int c = 1;; c++) {
        const uint32_t hc = hp + c * 4 * 4096;
#pragma unroll
        for (int b = 1; b < 18; b++) box(b, [&] {
          if ((b & 1) && b < 8) { uint32_t o[4]; const uint32_t a = hc - (4 - (b >> 1)) * 4096; lds4(a, o); geglu8(b >> 1, o); sts4(a, o); }
          if ((b & 1) && b > 10) { uint32_t o[4]; packu8((b - 11) >> 1, o); if (c < 8) sts4(hc + ((b - 11) >> 1) * 4096, o); } });
        ZSTAMP(4, c);
        if (c == 8) break;
        box(0, nop);
      }
      wg_wait<0>();
      STAMP(21);
      GSTAMP(19);
      auto unpark = [&](int kb) {
#pragma unroll
        for (int s = 4 * kb; s < 4 * kb + 4; s++) lds4(hp + s * 4096, X + 4 * s);
      };
      unpark(0);
      uint32_t U[16];
#pragma unroll
      for (int p = 0; p < 4; p++) packu8(p, U + 4 * p);
#pragma unroll
      for (int b = 0; b < 8; b++) box(b, [&] {
        if (b < 7) unpark(b + 1);
        if (b & 1) {
          geglu8(b >> 1, U + 2 * (b - 1));
          if (rg.ph > 1) sts4(hp, U + 2 * (b - 1));
#pragma unroll
          for (int i = 0; i < 4; i++) X[128 + 2 * (b - 1) + i] = U[2 * (b - 1) + i];
        } });
      STAMP(24);
      if (layer == 0 && lead) mbar_arrive(park_free);
      const uint32_t lane2 = lane_id();
      uint4* const pw = scp + OFF_P + (j * 8 + w) * SLAB + lane2;
      const uint32_t pr = scr + OFF_P + w * SLAB + 4 * j * 32 + lane2;
      auto put_part = [&](float (&a)[32], int p, uint32_t chunk) {
        uint32_t o[4];
        pack8(a, p, o);
        stg4(pw + (chunk * 4 + p) * 32, (o[0] & ~1u) | tag, o[1], o[2], o[3]);
      };
      auto slot = [&](int p) { return sb + w * 2048 + (p < 3 ? PARK + p * 16384 : KVS + (p - 3) * 16384); };
      auto fetch = [&](int p) {
        bulk_load(slot(p), at(scr + OFF_P + (((j - p) & 7) * 8 + w) * SLAB + 4 * j * 32), 2048, pbar0 + w * 8, true);
      };
#pragma unroll 1
      for (int sp = 0;; sp++) {
        const uint32_t ca = sp == 0 ? 8 : ((j + 2 * sp) & 7), cb = (j + 2 * sp + 1) & 7;
        if (sp == 1 && lead) mbar_arrive(c8_go);
#pragma unroll
        for (int b = 8; b < 18; b++) box(b, [&] {
          if (b >= 11 && b < 15) put_part(aA, b - 11, ca);
          if (b == 17 && sp > 1) { if (sp == 3) mbar_wait(c8_done, layer); fetch(2 * sp - 2); } });
        STAMP(25 + sp);
        if (sp == 3) break;
#pragma unroll
        for (int b = 0; b < 8; b++) box(b, [&] {
          if (b >= 1 && b < 5) put_part(aB, b - 1, cb);
          if (b == 7 && sp > 0) fetch(2 * sp - 1); });
      }
      auto load_p = [&](int p, uint32_t* d) {
#pragma unroll
        for (int i = 0; i < 4; i++) ldg4(d + 4 * i, at(pr + ((j - p) & 7) * 8 * SLAB) + i * 32);
      };
      auto bad = [&](const uint32_t* d, uint32_t tg) { return diff2(d[0], d[4], tg) | diff2(d[8], d[12], tg); };
      uint32_t late = 0;
#pragma unroll
      for (int b = 0; b < 9; b++) {
        if (b == 6) { mbar_wait(lane2 & 1 ? res_full : pbar0 + w * 8, layer); __syncwarp(); }
        box(b, [&] {
          if (b == 1) {
#pragma unroll
            for (int p = 0; p < 4; p++) put_part(aB, p, (j + 7) & 7);
          }
          if (b == 3) { load_p(5, X); load_p(6, X + 16); }
          if (b == 7) {
            late = bad(X, tag) | bad(X + 16, tag);
#pragma unroll
            for (int i = 0; i < 4; i++) ldg4(X + 32 + 4 * i, at(pr + ((j - 7) & 7) * 8 * SLAB + (late == 0x7fc12345u)) + i * 32);
          } });
      }
#pragma unroll
      for (int p = 1; p < 5; p++)
#pragma unroll
        for (int i = 0; i < 4; i++) lds4(slot(p) + lane2 * 16 + i * 512, X + 48 + 16 * p + 4 * i);
#pragma unroll
      for (int i = 0; i < 4; i++) {
        const bool split = j == 2 * i + 1;
        const uint32_t a = slot(0) + i * 512 + (split ? lane2 * 8 : lane2 * 16);
        lds2(a, X + 48 + 4 * i); lds2(a + (split ? 256 : 8), X + 50 + 4 * i);
      }
      wg_wait<0>();
      release(rg.st); rg.next();
      pin(aA);
      STAMP(22);
      GSTAMP(20);
      {
        const uint32_t lane = lane2, r = lane >> 2, q = lane & 3;
        const uint32_t eye = r == 2 * q ? 0x3f80u : r == 2 * q + 1 ? 0x3f800000u : 0u;
        auto add = [&](const uint32_t* d) {
#pragma unroll
          for (int g = 0; g < 8; g++) mma8(aA + 4 * g, d[2 * g], d[2 * g + 1], eye);
        };
        int n = 0;
        late = or3(late, bad(X + 64, tag), or3(bad(X + 80, tag), bad(X + 96, tag), bad(X + 112, tag)));
#pragma unroll 1
        while (!__all_sync(~0u, (late & 1u) == 0u)) {
          SPIN_GUARD(n);
          const uint32_t pc = scr + OFF_P + w * SLAB + 4 * j * 32 + lane_id();
          late = 0;
#pragma unroll
          for (int p = 1; p < 8; p++) {
            uint32_t* d = X + (p < 5 ? 48 + 16 * p : 16 * (p - 5));
#pragma unroll
            for (int i = 0; i < 4; i++) ldg4(d + 4 * i, at(pc + ((j - p) & 7) * 8 * SLAB) + i * 32);
            late |= bad(d, tag);
          }
        }
        add(X); add(X + 16);
#pragma unroll
        for (int p = 1; p < 6; p++) add(X + 48 + 16 * (p % 5));
        STAMP(11);
        const uint32_t tg = tag ^ (__float_as_uint(aA[28]) == 0x7fc12345u ? 2u : 0u);
#pragma unroll 1
        while (!__all_sync(~0u, (bad(X + 32, tg) & 1u) == 0u)) { SPIN_GUARD(n); load_p(7, X + 32); }
        add(X + 32);
        STAMP(12);
        uint32_t res[16];
#pragma unroll
        for (int i = 0; i < 16; i++) X[i] = res[i] = pack_bf16(aA[2 * i], aA[2 * i + 1]);
        if (layer == 0) {
#pragma unroll
          for (int i = 0; i < 4; i++) X[4 * i] = nz(X[4 * i]);
          auto put = [&] { put4(at(xbase + 8 * SLAB + 4 * j * 32 + lane), X); };
          if (j < PRI) put();
          publish_stats<8>(at(scr + OFF_S + w * 96 + j * 8 + r), aA, 1u, lane);
          if (j >= PRI) put();
        } else {
          const uint32_t tb = slot(0);
          __syncwarp();
#pragma unroll
          for (int i = 0; i < 4; i++) {
            const uint32_t row = (lane2 & 7) + (lane2 & 8), g = 2 * i + (lane2 >> 4);
            asm volatile("stmatrix.sync.aligned.m8n8.x4.shared.b16 [%0], {%1,%2,%3,%4};"
                         :: "r"(tb + row * 128 + ((g ^ (row & 7)) << 4)), "r"(res[4 * i]), "r"(res[4 * i + 1]), "r"(res[4 * i + 2]), "r"(res[4 * i + 3]) : "memory");
          }
          __syncwarp();
#pragma unroll
          for (int i = 0; i < 4; i++) {
            const uint32_t row = 4 * i + (lane2 >> 3), g = lane2 & 7;
            uint32_t v[4];
            lds4(tb + row * 128 + ((g ^ (row & 7)) << 4), v);
            ((uint4*)out + ((128 * t + 32 * (w >> 1) + 2 * (lane2 >> 3) + (w & 1)) * 72 + 8 * j + g))[i * 576] = make_uint4(v[0], v[1], v[2], v[3]);
          }
        }
      }
      STAMP(23);
    }
  }
}

typedef CUresult (*EncodeFn)(CUtensorMap*, CUtensorMapDataType, cuuint32_t, void*, const cuuint64_t*, const cuuint64_t*,
                             const cuuint32_t*, const cuuint32_t*, CUtensorMapInterleave, CUtensorMapSwizzle,
                             CUtensorMapL2promotion, CUtensorMapFloatOOBfill);

CUtensorMap make_map(EncodeFn f, const void* p, uint64_t cols, uint64_t rows, uint64_t grp) {
  CUtensorMap m;
  cuuint64_t dims[3] = {cols, grp, rows / grp}, str[2] = {cols * 2, cols * 2 * grp};
  cuuint32_t box[3] = {64, 16, 4}, es[3] = {1, 1, 1};
  f(&m, CU_TENSOR_MAP_DATA_TYPE_BFLOAT16, 3, const_cast<void*>(p), dims, str, box, es, CU_TENSOR_MAP_INTERLEAVE_NONE,
    CU_TENSOR_MAP_SWIZZLE_128B, CU_TENSOR_MAP_L2_PROMOTION_NONE, CU_TENSOR_MAP_FLOAT_OOB_FILL_NONE);
  return m;
}
CUtensorMap make_rem_map(EncodeFn f, const void* p, uint64_t cols) {
  CUtensorMap m;
  cuuint64_t dims[2] = {cols, 576}, str[1] = {cols * 2};
  cuuint32_t box[2] = {8, 144}, es[2] = {1, 1};
  f(&m, CU_TENSOR_MAP_DATA_TYPE_BFLOAT16, 2, const_cast<void*>(p), dims, str, box, es, CU_TENSOR_MAP_INTERLEAVE_NONE,
    CU_TENSOR_MAP_SWIZZLE_NONE, CU_TENSOR_MAP_L2_PROMOTION_NONE, CU_TENSOR_MAP_FLOAT_OOB_FILL_NONE);
  return m;
}

}

extern "C" void kernel_launch(void* const* d_in, const int* in_sizes, int n_in, void* d_out, int out_size) {
  void* fn = nullptr;
  cudaDriverEntryPointQueryResult qr;
  cudaGetDriverEntryPoint("cuTensorMapEncodeTiled", &fn, cudaEnableDefault, &qr);
  EncodeFn enc = (EncodeFn)fn;
  Maps maps;
  maps.m[0] = make_map(enc, d_in[1], 1728, 576, 16); maps.m[1] = make_map(enc, d_in[2], 576, 576, 16);
  maps.m[2] = make_map(enc, d_in[4], 4608, 576, 16); maps.m[3] = make_map(enc, d_in[5], 4608, 576, 16);
  maps.m[4] = make_map(enc, d_in[6], 576, 4608, 16);
  maps.m[5] = make_rem_map(enc, d_in[1], 1728); maps.m[6] = make_rem_map(enc, d_in[2], 576);
  maps.m[8] = make_map(enc, d_in[2], 576, 576, 144); maps.m[9] = make_map(enc, d_in[4], 4608, 576, 144);
  maps.m[10] = make_map(enc, d_in[5], 4608, 576, 144);
  {
    cuuint64_t dims[3] = {576, 1024, 2}, str[2] = {2304, 1152};
    cuuint32_t box[3] = {64, 64, 2}, es[3] = {1, 1, 1};
    enc(&maps.m[7], CU_TENSOR_MAP_DATA_TYPE_BFLOAT16, 3, d_in[0], dims, str, box, es, CU_TENSOR_MAP_INTERLEAVE_NONE,
        CU_TENSOR_MAP_SWIZZLE_128B, CU_TENSOR_MAP_L2_PROMOTION_NONE, CU_TENSOR_MAP_FLOAT_OOB_FILL_NONE);
  }
  void* scr = nullptr;
  cudaGetSymbolAddress(&scr, g_scratch);
  cudaFuncSetAttribute(mega_kernel, cudaFuncAttributeMaxDynamicSharedMemorySize, SMEM_BYTES);
  cudaLaunchConfig_t cfg = {};
  cfg.gridDim = dim3(128); cfg.blockDim = dim3(384); cfg.dynamicSmemBytes = SMEM_BYTES; cfg.stream = cudaStreamPerThread;
  cudaLaunchAttribute at[1];
  at[0].id = cudaLaunchAttributeClusterDimension; at[0].val.clusterDim.x = 2; at[0].val.clusterDim.y = 1; at[0].val.clusterDim.z = 1;
  cfg.attrs = at; cfg.numAttrs = 1;
  int dev = 0, sms = 0, clusters = 0;
  cudaGetDevice(&dev);
  cudaDeviceGetAttribute(&sms, cudaDevAttrMultiProcessorCount, dev);
  cudaOccupancyMaxActiveClusters(&clusters, mega_kernel, &cfg);
  if (sms == 132 && clusters == 66) cfg.gridDim = dim3(132);
  cudaLaunchKernelEx(&cfg, mega_kernel, maps, (uint4*)scr, (__nv_bfloat16*)d_out);
}
```

```cpp
#include <cuda_runtime.h>
#include <cuda.h>
#include <cuda_bf16.h>
#include <stdint.h>

#define TRACE 0
#define GUARD 0
#define FORCE_REDO 0
#define ZT 0

namespace {

constexpr int NST = 6;
constexpr int STAGE = 16384;
constexpr int PARK = NST * STAGE;
constexpr int REM = PARK + 49152;
constexpr int KVS = REM + 40960;
constexpr int PIECE = PARK + 7 * STAGE;
constexpr int HSTG = KVS + 16384;
constexpr int BARS = KVS + 41472;
constexpr int TRC = BARS + 512;
constexpr int SMEM_BYTES = TRC + (TRACE ? 512 : 0);
static_assert(NST == 6, "the producer addresses empty barriers as full + 48");
static_assert(BARS >= PARK + 131072, "barriers overlap park");
static_assert(SMEM_BYTES <= 232448, "smem");

constexpr int SLAB = 36 * 32;
constexpr int SPIN_MAX = 1 << 17;
constexpr uint32_t PRI = 4;
constexpr int GD = 3, GO = 5;
constexpr int OFF_S = 0;
constexpr int OFF_H = OFF_S + 3 * 8 * 96;
constexpr int OFF_X = OFF_H + 2 * 8 * 384;
constexpr int OFF_P = OFF_X + 6 * 8 * SLAB;
constexpr int TILE = OFF_P + 8 * 8 * SLAB;
constexpr int OFF_R = 16 * TILE;
constexpr int OFF_F = OFF_R + 8 * 2304;
constexpr int SCRATCH = OFF_F + 128 * 8;

}

__device__ uint4 g_scratch[SCRATCH];

namespace {

constexpr uint64_t DESC_HI = 0x4000004000000000ull;
constexpr uint64_t DESC_REM = (576ull << 32) | (8u << 16);
__device__ __forceinline__ void wgmma_rs_n64(float (&d)[32], const uint32_t* a, uint64_t desc, int scale_d) {
  asm volatile("{\n.reg .pred p;\nsetp.ne.b32 p, %37, 0;\n"
    "wgmma.mma_async.sync.aligned.m64n64k16.f32.bf16.bf16 "
    "{%0, %1, %2, %3, %4, %5, %6, %7, %8, %9, %10, %11, %12, %13, %14, %15, %16, %17, %18, %19, %20, %21, %22, %23, %24, %25, %26, %27, %28, %29, %30, %31}, "
    "{%32, %33, %34, %35}, %36, p, 1, 1, 1;\n}\n"
    : "+f"(d[0]), "+f"(d[1]), "+f"(d[2]), "+f"(d[3]), "+f"(d[4]), "+f"(d[5]), "+f"(d[6]), "+f"(d[7]), "+f"(d[8]), "+f"(d[9]), "+f"(d[10]), "+f"(d[11]), "+f"(d[12]), "+f"(d[13]), "+f"(d[14]), "+f"(d[15]), "+f"(d[16]), "+f"(d[17]), "+f"(d[18]), "+f"(d[19]), "+f"(d[20]), "+f"(d[21]), "+f"(d[22]), "+f"(d[23]), "+f"(d[24]), "+f"(d[25]), "+f"(d[26]), "+f"(d[27]), "+f"(d[28]), "+f"(d[29]), "+f"(d[30]), "+f"(d[31])
    : "r"(a[0]), "r"(a[1]), "r"(a[2]), "r"(a[3]), "l"(desc), "r"(scale_d));
}
__device__ __forceinline__ void wgmma_rs_n72(float (&d)[36], const uint32_t* a, uint64_t desc, int scale_d) {
  asm volatile("{\n.reg .pred p;\nsetp.ne.b32 p, %41, 0;\n"
    "wgmma.mma_async.sync.aligned.m64n72k16.f32.bf16.bf16 "
    "{%0, %1, %2, %3, %4, %5, %6, %7, %8, %9, %10, %11, %12, %13, %14, %15, %16, %17, %18, %19, %20, %21, %22, %23, %24, %25, %26, %27, %28, %29, %30, %31, %32, %33, %34, %35}, "
    "{%36, %37, %38, %39}, %40, p, 1, 1, 1;\n}\n"
    : "+f"(d[0]), "+f"(d[1]), "+f"(d[2]), "+f"(d[3]), "+f"(d[4]), "+f"(d[5]), "+f"(d[6]), "+f"(d[7]), "+f"(d[8]), "+f"(d[9]), "+f"(d[10]), "+f"(d[11]), "+f"(d[12]), "+f"(d[13]), "+f"(d[14]), "+f"(d[15]), "+f"(d[16]), "+f"(d[17]), "+f"(d[18]), "+f"(d[19]), "+f"(d[20]), "+f"(d[21]), "+f"(d[22]), "+f"(d[23]), "+f"(d[24]), "+f"(d[25]), "+f"(d[26]), "+f"(d[27]), "+f"(d[28]), "+f"(d[29]), "+f"(d[30]), "+f"(d[31]), "+f"(d[32]), "+f"(d[33]), "+f"(d[34]), "+f"(d[35])
    : "r"(a[0]), "r"(a[1]), "r"(a[2]), "r"(a[3]), "l"(desc), "r"(scale_d));
}
__device__ __forceinline__ void wgmma_rs_n24(float (&d)[12], const uint32_t* a, uint64_t desc, int scale_d) {
  asm volatile("{\n.reg .pred p;\nsetp.ne.b32 p, %17, 0;\n"
    "wgmma.mma_async.sync.aligned.m64n24k16.f32.bf16.bf16 "
    "{%0, %1, %2, %3, %4, %5, %6, %7, %8, %9, %10, %11}, "
    "{%12, %13, %14, %15}, %16, p, 1, 1, 1;\n}\n"
    : "+f"(d[0]), "+f"(d[1]), "+f"(d[2]), "+f"(d[3]), "+f"(d[4]), "+f"(d[5]), "+f"(d[6]), "+f"(d[7]), "+f"(d[8]), "+f"(d[9]), "+f"(d[10]), "+f"(d[11])
    : "r"(a[0]), "r"(a[1]), "r"(a[2]), "r"(a[3]), "l"(desc), "r"(scale_d));
}

__device__ __forceinline__ void mbar_init(uint32_t a, uint32_t c) { asm volatile("mbarrier.init.shared::cta.b64 [%0], %1;" :: "r"(a), "r"(c)); }
__device__ __forceinline__ void mbar_arrive(uint32_t a) { asm volatile("mbarrier.arrive.shared::cta.b64 _, [%0];" :: "r"(a) : "memory"); }
__device__ __forceinline__ void mbar_wait_trap(uint32_t a, uint32_t ph) {
  asm volatile("{\n.reg .pred p;\n.reg .u32 n;\nmov.u32 n, 0;\n"
               "W: mbarrier.try_wait.parity.shared::cta.b64 p, [%0], %1;\n@p bra D;\n"
               "add.u32 n, n, 1;\nsetp.lt.u32 p, n, 4194304;\n@p bra W;\ntrap;\nD:\n}" :: "r"(a), "r"(ph) : "memory");
}
__device__ __forceinline__ void mbar_wait(uint32_t a, uint32_t ph) {
  asm volatile("{\n.reg .pred p;\nW: mbarrier.try_wait.parity.shared::cta.b64 p, [%0], %1;\n@!p bra W;\n}" :: "r"(a), "r"(ph) : "memory");
}
__device__ __forceinline__ uint32_t mbar_peek(uint32_t a, uint32_t ph) {
  uint32_t r;
  asm volatile("{\n.reg .pred p;\nmbarrier.test_wait.parity.shared::cta.b64 p, [%1], %2;\nselp.u32 %0, 1, 0, p;\n}" : "=r"(r) : "r"(a), "r"(ph) : "memory");
  return r;
}
__device__ __forceinline__ void mbar_wait_unless(uint32_t ready, uint32_t a, uint32_t ph) {
  asm volatile("{\n.reg .pred p;\nsetp.ne.u32 p, %2, 0;\n@p bra D;\nW: mbarrier.try_wait.parity.shared::cta.b64 p, [%0], %1;\n@!p bra W;\nD:\n}"
               :: "r"(a), "r"(ph), "r"(ready) : "memory");
}
__device__ __forceinline__ void mbar_wait_sleep(uint32_t a, uint32_t ph) {
  asm volatile("{\n.reg .pred p;\nW: mbarrier.test_wait.parity.shared::cta.b64 p, [%0], %1;\n@p bra D;\nnanosleep.u32 500;\nbra W;\nD:\n}" :: "r"(a), "r"(ph) : "memory");
}
__device__ __forceinline__ void wg_fence() { asm volatile("wgmma.fence.sync.aligned;" ::: "memory"); }
__device__ __forceinline__ void wg_commit() { asm volatile("wgmma.commit_group.sync.aligned;" ::: "memory"); }
template <int N> __device__ __forceinline__ void wg_wait() { asm volatile("wgmma.wait_group.sync.aligned %0;" :: "n"(N) : "memory"); }
__device__ __forceinline__ float tanh_ap(float x) { float y; asm("tanh.approx.f32 %0, %1;" : "=f"(y) : "f"(x)); return y; }
__device__ __forceinline__ float ex2(float x) { float y; asm("ex2.approx.ftz.f32 %0, %1;" : "=f"(y) : "f"(x)); return y; }
__device__ __forceinline__ uint32_t pack_bf16(float lo, float hi) { uint32_t r; asm("cvt.rn.bf16x2.f32 %0, %1, %2;" : "=r"(r) : "f"(hi), "f"(lo)); return r; }
__device__ __forceinline__ float bf_lo(uint32_t v) { return __uint_as_float(v << 16); }
__device__ __forceinline__ float bf_hi(uint32_t v) { return __uint_as_float(v & 0xffff0000u); }
__device__ __forceinline__ uint32_t sub_bf16x2(uint32_t a, uint32_t b) { uint32_t r; asm("sub.rn.bf16x2 %0, %1, %2;" : "=r"(r) : "r"(a), "r"(b)); return r; }
__device__ __forceinline__ uint32_t mul_bf16x2(uint32_t a, uint32_t b) { uint32_t r; asm("mul.rn.bf16x2 %0, %1, %2;" : "=r"(r) : "r"(a), "r"(b)); return r; }
__device__ __forceinline__ uint32_t diff2(uint32_t a, uint32_t b, uint32_t t) { uint32_t r; asm("lop3.b32 %0, %1, %2, %3, 0x7e;" : "=r"(r) : "r"(a), "r"(b), "r"(t)); return r; }
__device__ __forceinline__ uint32_t or3(uint32_t a, uint32_t b, uint32_t c) { uint32_t r; asm("lop3.b32 %0, %1, %2, %3, 0xfe;" : "=r"(r) : "r"(a), "r"(b), "r"(c)); return r; }
__device__ __forceinline__ uint32_t umin2(uint32_t a, uint32_t b) { uint32_t r; asm("min.u32 %0, %1, %2;" : "=r"(r) : "r"(a), "r"(b)); return r; }
__device__ __forceinline__ uint32_t nz(uint32_t w) { return w == 0u ? 0x8000u : w; }

__device__ __forceinline__ void ldg4(uint32_t* d, const uint4* p) {
  asm volatile("ld.relaxed.gpu.global.v4.b32 {%0,%1,%2,%3}, [%4];" : "=r"(d[0]), "=r"(d[1]), "=r"(d[2]), "=r"(d[3]) : "l"(p) : "memory");
}
__device__ __forceinline__ void ldg2(uint32_t* d, const void* p) {
  asm volatile("ld.relaxed.gpu.global.v2.b32 {%0,%1}, [%2];" : "=r"(d[0]), "=r"(d[1]) : "l"(p) : "memory");
}
__device__ __forceinline__ void stg4(uint4* p, uint32_t a, uint32_t b, uint32_t c, uint32_t d) {
  asm volatile("st.relaxed.gpu.global.v4.b32 [%0], {%1,%2,%3,%4};" :: "l"(p), "r"(a), "r"(b), "r"(c), "r"(d) : "memory");
}
__device__ __forceinline__ void stg2(void* p, uint32_t a, uint32_t b) {
  asm volatile("st.relaxed.gpu.global.v2.b32 [%0], {%1,%2};" :: "l"(p), "r"(a), "r"(b) : "memory");
}
__device__ __forceinline__ void sts4(uint32_t a, const uint32_t* o) { asm volatile("st.shared.v4.b32 [%0], {%1,%2,%3,%4};" :: "r"(a), "r"(o[0]), "r"(o[1]), "r"(o[2]), "r"(o[3]) : "memory"); }
__device__ __forceinline__ void lds4(uint32_t a, uint32_t* o) { asm volatile("ld.shared.v4.b32 {%0,%1,%2,%3}, [%4];" : "=r"(o[0]), "=r"(o[1]), "=r"(o[2]), "=r"(o[3]) : "r"(a) : "memory"); }
__device__ __forceinline__ void lds2(uint32_t a, uint32_t* o) { asm volatile("ld.shared.v2.b32 {%0,%1}, [%2];" : "=r"(o[0]), "=r"(o[1]) : "r"(a) : "memory"); }
__device__ __forceinline__ float rcp(float x) { float y; asm("rcp.approx.ftz.f32 %0, %1;" : "=f"(y) : "f"(x)); return y; }
__device__ __forceinline__ void sts1(uint32_t a, uint32_t v) { asm volatile("st.shared.b32 [%0], %1;" :: "r"(a), "r"(v) : "memory"); }
__device__ __forceinline__ void ldsm4(uint32_t a, uint32_t& r0, uint32_t& r1, uint32_t& r2, uint32_t& r3) {
  asm volatile("ldmatrix.sync.aligned.m8n8.x4.shared.b16 {%0,%1,%2,%3}, [%4];" : "=r"(r0), "=r"(r1), "=r"(r2), "=r"(r3) : "r"(a) : "memory");
}
__device__ __forceinline__ void ldsm4t(uint32_t a, uint32_t& r0, uint32_t& r1, uint32_t& r2, uint32_t& r3) {
  asm volatile("ldmatrix.sync.aligned.m8n8.x4.trans.shared.b16 {%0,%1,%2,%3}, [%4];" : "=r"(r0), "=r"(r1), "=r"(r2), "=r"(r3) : "r"(a) : "memory");
}
__device__ __forceinline__ void mma16(float* c, uint32_t a0, uint32_t a1, uint32_t a2, uint32_t a3, uint32_t b0, uint32_t b1) {
  asm("mma.sync.aligned.m16n8k16.row.col.f32.bf16.bf16.f32 {%0,%1,%2,%3}, {%4,%5,%6,%7}, {%8,%9}, {%0,%1,%2,%3};"
    : "+f"(c[0]), "+f"(c[1]), "+f"(c[2]), "+f"(c[3]) : "r"(a0), "r"(a1), "r"(a2), "r"(a3), "r"(b0), "r"(b1));
}
__device__ __forceinline__ void mma16z(float* d, const uint32_t* a, uint32_t b0, uint32_t b1) {
  asm("mma.sync.aligned.m16n8k16.row.col.f32.bf16.bf16.f32 {%0,%1,%2,%3}, {%4,%5,%6,%7}, {%8,%9}, {%10,%10,%10,%10};"
    : "=f"(d[0]), "=f"(d[1]), "=f"(d[2]), "=f"(d[3]) : "r"(a[0]), "r"(a[1]), "r"(a[2]), "r"(a[3]), "r"(b0), "r"(b1), "f"(0.f));
}
__device__ __forceinline__ void mma8(float* c, uint32_t a0, uint32_t a1, uint32_t b0) {
  asm("mma.sync.aligned.m16n8k8.row.col.f32.bf16.bf16.f32 {%0,%1,%2,%3}, {%4,%5}, {%6}, {%0,%1,%2,%3};"
    : "+f"(c[0]), "+f"(c[1]), "+f"(c[2]), "+f"(c[3]) : "r"(a0), "r"(a1), "r"(b0));
}
__device__ __forceinline__ uint32_t lane_id() { uint32_t l; asm volatile("mov.u32 %0, %%laneid;" : "=r"(l)); return l; }
__device__ __forceinline__ float quad_sum(float v) { v += __shfl_xor_sync(~0u, v, 1); v += __shfl_xor_sync(~0u, v, 2); return v; }
template <int N> __device__ __forceinline__ void pin(float (&d)[N]) {
#pragma unroll
  for (int i = 0; i < N; i++) asm volatile("" : "+f"(d[i]) :: "memory");
}
#define SPIN_GUARD(n) if (++(n) > SPIN_MAX) break

template <int NG> __device__ __forceinline__ void publish_stats(uint4* dst, const float* y, uint32_t tag, uint32_t lane) {
  float s0 = 0.f, s1 = 0.f;
#pragma unroll
  for (int g = 0; g < NG; g++) { s0 += y[4 * g] + y[4 * g + 1]; s1 += y[4 * g + 2] + y[4 * g + 3]; }
  s0 = quad_sum(s0); s1 = quad_sum(s1);
  const float m0 = s0 * (1.f / (8 * NG)), m1 = s1 * (1.f / (8 * NG));
  float q0 = 0.f, q1 = 0.f, q2 = 0.f, q3 = 0.f;
#pragma unroll
  for (int g = 0; g < NG; g++) {
    const float a = y[4 * g] - m0, b = y[4 * g + 1] - m0, c = y[4 * g + 2] - m1, d = y[4 * g + 3] - m1;
    q0 = fmaf(a, a, q0); q1 = fmaf(b, b, q1); q2 = fmaf(c, c, q2); q3 = fmaf(d, d, q3);
  }
  q0 = quad_sum(q0 + q1); q2 = quad_sum(q2 + q3);
  if ((lane & 3) == 0)
    stg4(dst, (__float_as_uint(s0) & ~1u) | tag, __float_as_uint(q0), __float_as_uint(s1), __float_as_uint(q2));
}

__device__ __forceinline__ void put4(uint4* p, const uint32_t* v) {
#pragma unroll
  for (int i = 0; i < 4; i++) stg4(p + i * 32, v[4 * i], v[4 * i + 1], v[4 * i + 2], v[4 * i + 3]);
}
__device__ __forceinline__ uint32_t row72(uint32_t k) { return k % 9 == 4 ? 32 + k / 9 : k - (k + 4) / 9; }
__device__ __forceinline__ void zero_share(uint4* slab, uint32_t j, uint32_t lane) {
  uint4* p = slab + j * 144 + lane;
#pragma unroll
  for (int i = 0; i < 4; i++) stg4(p + i * 32, 0u, 0u, 0u, 0u);
  if (lane < 16) stg4(p + 128, 0u, 0u, 0u, 0u);
}

struct Maps { CUtensorMap m[11]; };

struct Ring {
  uint32_t st, ph;
  __device__ __forceinline__ void next() { if (++st == NST) { st = 0; ph ^= 1; } }
};

#define GSTAMP(i) do {} while (0)
#define STAMP(i) do {} while (0)
#define ZSTAMP(m, i) do {} while (0)

__device__ __forceinline__ void tma_box(uint32_t dst, const CUtensorMap* m, int col, int row, uint32_t bar, uint32_t expect) {
  asm volatile("{\n.reg .pred e, h;\nelect.sync _|e, 0xffffffff;\nsetp.ne.and.u32 h, %5, 0, e;\n"
               "@h mbarrier.arrive.expect_tx.shared::cta.b64 _, [%2], %5;\n"
               "@e cp.async.bulk.tensor.2d.shared::cluster.global.mbarrier::complete_tx::bytes [%0], [%1, {%3, %4}], [%2];\n}"
               :: "r"(dst), "l"(m), "r"(bar), "r"(col), "r"(row), "r"(expect) : "memory");
}

__device__ __forceinline__ void bulk_load(uint32_t dst, const void* src, uint32_t bytes, uint32_t bar, bool arm) {
  asm volatile("{\n.reg .pred e, h;\nelect.sync _|e, 0xffffffff;\nsetp.ne.and.u32 h, %4, 0, e;\n"
               "@h mbarrier.arrive.expect_tx.shared::cta.b64 _, [%3], %2;\n"
               "@e cp.async.bulk.shared::cluster.global.mbarrier::complete_tx::bytes [%0], [%1], %2, [%3];\n}"
               :: "r"(dst), "l"(src), "r"(bytes), "r"(bar), "r"((uint32_t)arm) : "memory");
}

__global__ void __launch_bounds__(384, 1) mega_kernel(
    const __grid_constant__ Maps maps, uint4* __restrict__ scratch,
    __nv_bfloat16* __restrict__ out) {
  extern __shared__ __align__(1024) uint8_t smem[];
  const uint32_t sb = (uint32_t)__cvta_generic_to_shared(smem);
  const uint32_t full0 = sb + BARS, empty0 = full0 + 8 * NST, rem_full = empty0 + 8 * NST, park_free = rem_full + 8, kv_free = park_free + 8;
  const uint32_t c8_go = kv_free + 8, c8_done = c8_go + 8, c8_full = c8_done + 8, remo_full = c8_full + 8, piece_full = remo_full + 8, xb_done = piece_full + 8, res_full = xb_done + 8, pbar0 = res_full + 8;
  const uint32_t x_done = pbar0 + 64, x_ring = x_done + 8, xbar0 = x_ring + 8, redo_full = xbar0 + 72, att_done = redo_full + 16;
  const uint32_t w = __shfl_sync(~0u, threadIdx.x >> 5, 0);
  uint32_t pair = blockIdx.x >> 1;
  if (gridDim.x == 132) {
    uint32_t smid;
    asm("mov.u32 %0, %%smid;" : "=r"(smid));
    const uint32_t tpc = smid >> 1;
    if (tpc == 60 || tpc == 61) { if (threadIdx.x == 0) { __nanosleep(20000); } return; }
    pair = tpc < 32 ? tpc : tpc >= 62 ? (tpc - 58) * 8 : 33 + (tpc - 32) / 7 * 8 + (tpc - 32) % 7;
  }
  const uint32_t rank = blockIdx.x & 1, t = (pair & 7) * 2 + rank, j = pair >> 3;
  const uint32_t sd = sb & 0x3ffff;
  const uint32_t odd = j & 1;
  const uint32_t scr = t * TILE;
  uint4* const scp = scratch + t * TILE;
  auto at = [&](uint32_t i) { return scratch + i; };
  auto at8 = [&](uint32_t i) { return (uint2*)scratch + i; };
  auto blk = [&](uint32_t kb) { return kb == 0 ? j : kb - (kb <= j); };
  const uint32_t xs = sb + (NST - 2) * STAGE;
  auto fetch_x = [&](uint32_t dst, uint32_t b, uint32_t bar) {
    asm volatile("{\n.reg .pred e;\nelect.sync _|e, 0xffffffff;\n@e mbarrier.arrive.expect_tx.shared::cta.b64 _, [%2], 16384;\n"
                 "@e cp.async.bulk.tensor.3d.shared::cluster.global.mbarrier::complete_tx::bytes [%0], [%1, {%3, %4, 0}], [%2];\n}"
                 :: "r"(dst), "l"(&maps.m[7]), "r"(bar), "r"(64 * b), "r"(64 * t) : "memory");
  };
  if (threadIdx.x == 256) {
    for (int i = 0; i < 9; i++) mbar_init(xbar0 + 8 * i, 1);
    mbar_init(piece_full, 1);
    asm volatile("fence.mbarrier_init.release.cluster;" ::: "memory");
  }
  if (threadIdx.x == 288) {
    for (int i = 0; i < NST; i++) { mbar_init(full0 + 8 * i, 1); mbar_init(empty0 + 8 * i, 16); }
    mbar_init(x_done, 8); mbar_init(x_ring, 16); mbar_init(redo_full, 1); mbar_init(redo_full + 8, 1); mbar_init(att_done, 4);
    asm volatile("fence.mbarrier_init.release.cluster;" ::: "memory");
  }
  if (threadIdx.x == 320) {
    mbar_init(rem_full, 2); mbar_init(park_free, 8); mbar_init(kv_free, 8); mbar_init(c8_go, 8); mbar_init(c8_done, 2); mbar_init(c8_full, 1);
    mbar_init(remo_full, 64); mbar_init(xb_done, 8); mbar_init(res_full, 32);
    for (int i = 0; i < 8; i++) mbar_init(pbar0 + 8 * i, 4);
    asm volatile("fence.mbarrier_init.release.cluster;" ::: "memory");
  }
  if (threadIdx.x == 352) {
    asm volatile("prefetch.tensormap [%0];" :: "l"(&maps.m[7]) : "memory");
    asm volatile("prefetch.tensormap [%0];" :: "l"(&maps.m[0]) : "memory");
  }
  __syncwarp();
  asm volatile("barrier.cluster.arrive.relaxed.aligned;" ::: "memory");
  if (w != 8) asm volatile("barrier.cluster.wait.aligned;" ::: "memory");

  if (w >= 8) {
    asm volatile("setmaxnreg.dec.sync.aligned.u32 24;");
    if (w == 8) {
#pragma unroll 1
      for (uint32_t b = 0; b < 9; b++) fetch_x(xs + b * STAGE, b, xbar0 + 8 * b);
      tma_box(sb + PIECE, &maps.m[t >= 12 ? 6 : 5], 72 * j + (odd ? 0 : 64) + (t < 8 ? 576 * ((t >> 2) + 1) : 0), 144 * (t & 3), piece_full, 2304);
      asm volatile("barrier.cluster.wait.aligned;" ::: "memory");
      const uint32_t sb2 = __shfl_sync(~0u, sb, 0);
      uint32_t dst = sb2, bar = sb2 + BARS, ph = 1;
#pragma unroll 1
      for (int seg = 0; seg < 34; seg++) {
        const int n = seg >= 17 ? seg - 17 : seg;
        int ma, mb, ca, cb;
        if (n == 2) continue;
        if (n < 2) { ma = 0; mb = n; ca = 72 * j + 8 * odd + (n ? 0 : 576); cb = ca + (n ? 0 : 576); }
        else if (n < 12) { ma = 3; mb = 2; ca = cb = 576 * j + 64 * (n - 3); }
        else { ma = mb = 4; ca = n == 12 ? 512 : ((j + 2 * n) & 7) * 64; cb = ((j + 2 * n + 1) & 7) * 64; }
        const bool zip = n == 0 || n == 3, solo = n == 16;
#pragma unroll 1
        for (uint32_t st = 0; st < (solo ? 5 : 9); st++) {
          if (seg == 0 && st == NST - 2) mbar_wait(x_ring, 0);
          const uint32_t b = 2 * st + rank, kb = zip ? st : b >= 9 ? b - 9 : b;
          const bool second = zip ? rank : b >= 9;
          const int m = second ? mb : ma;
          const bool shared = kb == 8 && m > 0 && m < 4;
          const uint32_t ks = m == 4 ? 36 * j + 4 * kb : m == 0 ? 4 * blk(kb) : shared ? 0 : (9 * blk(kb) + 1) >> 1;
          asm volatile("{\n.reg .pred p, e, f;\n.reg .u32 n;\nelect.sync _|e, 0xffffffff;\nsetp.ne.and.u32 f, %8, 0, e;\nmov.u32 n, 0;\n"
                       "W: mbarrier.try_wait.parity.shared::cta.b64 p, [%1+48], %2;\n@p bra D;\n"
                       "add.u32 n, n, 1;\nsetp.lt.u32 p, n, 4194304;\n@p bra W;\ntrap;\n"
                       "D: @e mbarrier.arrive.expect_tx.shared::cta.b64 _, [%1], %7;\n"
                       "@f cp.async.bulk.tensor.3d.shared::cluster.global.mbarrier::complete_tx::bytes.multicast::cluster [%0], [%3, {%4, %5, %6}], [%1], 3;\n}"
                       :: "r"(dst + rank * 8192), "r"(bar), "r"(ph), "l"(&maps.m[m + (shared ? 7 : 0)]), "r"(second ? cb : ca),
                          "r"(shared ? 64 : 0), "r"(ks), "r"(solo && st == 4 ? STAGE / 2 : STAGE), "r"((uint32_t)!(solo && b == 9)) : "memory");
          dst += STAGE; bar += 8;
          if (dst == sb2 + NST * STAGE) { dst = sb2; bar -= 8 * NST; ph ^= 1; }
        }
      }
      {
#pragma unroll 1
        for (int i = 0; i < NST; i++) {
          mbar_wait_trap(bar + 48, ph);
          bar += 8;
          if (bar == full0 + 8 * NST) { bar = full0; ph ^= 1; }
        }
      }
    } else if (w == 9) {
      const uint32_t lane = lane_id();
      const uint32_t stg = sb + HSTG + lane * 16;
      uint32_t fph = 0;
#pragma unroll 1
      for (uint32_t layer = 0; layer < 2; layer++) {
        uint4* xb = scp + OFF_X + ((4 + layer) * 8 + j) * SLAB + 28 * 32;
        mbar_wait_sleep(c8_go, layer);
        int n = 0;
#pragma unroll 1
        while (true) {
          if (lane == 0) asm volatile("mbarrier.arrive.expect_tx.shared::cta.b64 _, [%0], 18432;" :: "r"(c8_full) : "memory");
          __syncwarp();
#pragma unroll 1
          for (uint32_t s = 0; s < 9; s++)
            bulk_load(sb + HSTG + s * 2048, s < 8 ? scp + OFF_P + (j + s * 8) * SLAB + 32 * 32 : xb, 2048, c8_full, false);
          mbar_wait(c8_full, fph); fph ^= 1;
          uint32_t bad = 0;
#pragma unroll 8
          for (int s = 0; s < 32; s++) { uint32_t v; asm volatile("ld.shared.b32 %0, [%1];" : "=r"(v) : "r"(stg + s * 512) : "memory"); bad |= v ^ (1 - layer); }
          if (__all_sync(~0u, (bad & 1u) == 0u)) break;
          __nanosleep(300);
          SPIN_GUARD(n);
        }
        asm volatile("bar.arrive 7, 96;" ::: "memory");
        float s0 = 0.f, s1 = 0.f;
#pragma unroll 1
        for (int g = 0; g < 8; g++) {
          const uint32_t a = stg + (g >> 1) * 512 + (g & 1) * 8;
          float a0 = 0.f, a1 = 0.f, a2 = 0.f, a3 = 0.f;
#pragma unroll 1
          for (int b = 0; b < 3; b++) {
            uint32_t v[6];
#pragma unroll
            for (int s = 0; s < 3; s++) lds2(a + (3 * b + s) * 2048, v + 2 * s);
#pragma unroll
            for (int s = 0; s < 3; s++) { a0 += bf_lo(v[2 * s]); a1 += bf_hi(v[2 * s]); a2 += bf_lo(v[2 * s + 1]); a3 += bf_hi(v[2 * s + 1]); }
          }
          sts1(a + 18432, pack_bf16(a0, a1)); sts1(a + 18436, pack_bf16(a2, a3));
          s0 += a0 + a1; s1 += a2 + a3;
        }
        __syncwarp();
        if (lane == 0) mbar_arrive(c8_done);
        s0 = quad_sum(s0); s1 = quad_sum(s1);
        float q0 = 0.f, q1 = 0.f;
        const uint32_t ln = lane_id();
#pragma unroll 1
        for (uint32_t i = 0; i < 4; i++) {
          uint32_t x[4];
          lds4(stg + 18432 + i * 512, x);
          uint4* z = xb + i * 32 + ln;
          asm volatile("" : "+l"(z));
          stg4(z, 0u, 0u, 0u, 0u);
          if (layer == 0) {
            stg4(z - (3 * 8 * SLAB - 128), nz(x[0]), x[1], nz(x[2]), x[3]);
#pragma unroll
            for (int e = 0; e < 4; e++) {
              const float m = (e & 1) ? s1 : s0, c = fmaf(m, -1.f / 64, bf_lo(x[e])), d = fmaf(m, -1.f / 64, bf_hi(x[e]));
              if (e & 1) q1 = fmaf(c, c, fmaf(d, d, q1)); else q0 = fmaf(c, c, fmaf(d, d, q0));
            }
          } else {
            uint32_t* o = (uint32_t*)(out + (128 * t + 32 * (j >> 1) + 2 * (ln >> 2) + (j & 1)) * 576 + 512 + 16 * i + 2 * (ln & 3));
            o[0] = x[0]; o[8 * 576] = x[1]; o[4] = x[2]; o[8 * 576 + 4] = x[3];
          }
        }
        if (layer == 0) {
          q0 = quad_sum(q0); q1 = quad_sum(q1);
          if ((ln & 3) == 0) stg4(scp + OFF_S + j * 96 + 64 + (ln >> 2), __float_as_uint(s0) | 1u, __float_as_uint(q0), __float_as_uint(s1), __float_as_uint(q1));
        }
      }
    } else {
      auto mark = [&](uint32_t k0, uint32_t v) {
        const uint32_t lane = lane_id();
#pragma unroll 1
        for (uint32_t k = k0; k < 6; k++) stg4(scp + OFF_S + (k * 4 + (lane >> 3)) * 96 + j * 8 + (lane & 7), k < 2 ? 0u : v, 0u, 0u, 0u);
      };
      if (w == 11) mark(2, 0u);
      auto phase2_duties = [&](uint32_t layer) {
        const uint32_t lane = lane_id();
        asm volatile("bar.sync 7, 96;" ::: "memory");
        if (w == 11) {
          if (layer == 0) mark(0, 1u);
          __syncwarp();
          if (lane == 0) mbar_arrive(c8_done);
        }
#pragma unroll 1
        for (uint32_t i = 0; i < 16; i++) {
          const uint32_t sl = (w - 10) * 4 + (i >> 2);
          bulk_load(sb + PARK + sl * 2048 + (i & 3) * 512, scp + OFF_X + ((4 + layer) * 8 + sl) * SLAB + row72(4 * j + (i & 3)) * 32, 512, res_full, true);
        }
        mbar_wait_sleep(res_full, layer);
#pragma unroll 1
        for (uint32_t i = 0; i < 16; i++) {
          stg4(scp + OFF_X + ((4 + layer) * 8 + (w - 10) * 4 + (i >> 2)) * SLAB + row72(4 * j + (i & 3)) * 32 + lane, 0u, 0u, 0u, 0u);
          if ((i & 3) == 3) __nanosleep(200);
        }
      };
      if (w == 10) {
        const uint32_t lane = lane_id();
        uint32_t* fl = (uint32_t*)(scratch + OFF_F + (t * 8 + j) * 8) + (lane & 15);
        uint32_t v;
        asm volatile("ld.relaxed.gpu.global.b32 %0, [%1];" : "=r"(v) : "l"(fl) : "memory");
        mbar_wait(piece_full, 0);
        asm volatile("{\n.reg .pred e;\nelect.sync _|e, 0xffffffff;\n@e cp.async.bulk.global.shared::cta.bulk_group [%0], [%1], 2304;\n}\n"
                     "cp.async.bulk.commit_group;\ncp.async.bulk.wait_group 0;\nfence.proxy.async;"
                     :: "l"(scratch + OFF_R + j * 2304 + t * 144), "r"(sb + PIECE) : "memory");
        __syncwarp();
        if (lane < 16) asm volatile("st.release.gpu.global.b32 [%0], 1;" :: "l"((uint32_t*)(scratch + OFF_F + (lane_id() * 8 + j) * 8) + t) : "memory");
        int n = 0;
#pragma unroll 1
        while (!__all_sync(~0u, v != 0u)) {
          __nanosleep(100);
          SPIN_GUARD(n);
          asm volatile("ld.relaxed.gpu.global.b32 %0, [%1];" : "=r"(v) : "l"(fl) : "memory");
        }
        asm volatile("st.relaxed.gpu.global.b32 [%0], 0;" :: "l"(fl) : "memory");
        mbar_wait(x_done, 0);
      }
#pragma unroll 1
      for (uint32_t layer = 0; layer < 3; layer++) {
        if (w == 10 && layer < 2) {
          if (layer) mbar_wait_sleep(park_free, 0);
          const uint4* img = scratch + OFF_R + j * 2304;
          if (lane_id() == 0) asm volatile("mbarrier.arrive.expect_tx.shared::cta.b64 _, [%0], 27648;\nmbarrier.arrive.expect_tx.shared::cta.b64 _, [%1], 9216;"
                                           :: "r"(rem_full), "r"(piece_full) : "memory");
          __syncwarp();
#pragma unroll 1
          for (uint32_t p = 0; p < 3; p++) {
            bulk_load(sb + REM + p * 9216, img + p * 576 + j * 64, 1024, rem_full, false);
            if (j) bulk_load(sb + REM + p * 9216 + 1024, img + p * 576, j * 1024, rem_full, false);
            bulk_load(sb + REM + p * 9216 + (j + 1) * 1024, img + p * 576 + (j + 1) * 64, (8 - j) * 1024, rem_full, false);
          }
#pragma unroll 1
          for (uint32_t i = 0; i < 12; i++)
            bulk_load(sb + REM + 27648 + (i < 8 ? i * 1024 : 6144 + i * 256), img + 1728 + (i < 8 ? (9 * blk(i) + 1) >> 1 : 9 * i - 68) * 16,
                      i < 8 ? 1024 : 256, piece_full, false);
          if (layer == 0) { fetch_x(sb + PARK, j, xbar0); fetch_x(sb + PARK + STAGE, j + 1, xbar0 + 8); }
        }
        if (w == 11 && layer < 2) {
          if (layer) mbar_wait_sleep(park_free, 0);
          __syncwarp();
          if (lane_id() == 0) mbar_arrive(rem_full);
        }
        if (layer) phase2_duties(layer - 1);
        if (layer == 2) break;
        mbar_wait(kv_free, layer);
        if (t > 0) {
          const uint32_t lane = lane_id(), r = lane >> 2, q = lane & 3;
#pragma unroll 1
          for (uint32_t pc = 0; pc < 3; pc++) {
            uint4* hp = scp + OFF_H + ((layer * 8 + j) * 2 + (w - 10)) * 192 + pc * 64 + lane;
            uint32_t hl[8];
            int n = 0;
            hl[4] = 1u;
#pragma unroll 1
            while (true) {
              ldg4(hl, hp);
              if (pc < 2) ldg4(hl + 4, hp + 32);
              if (__all_sync(~0u, hl[0] != 0u && hl[4] != 0u)) break;
              __nanosleep(100);
              SPIN_GUARD(n);
            }
            const uint32_t dst = sb + KVS + (w - 10) * 10368 + r * 144 + q * 4;
            if (pc < 2) {
#pragma unroll
              for (int g = 0; g < 8; g++) sts1(dst + pc * 20736 + odd * 16 + g * 16, hl[g]);
              stg4(hp + 32, 0u, 0u, 0u, 0u);
            } else {
              sts1(dst + (odd ? 0 : 128), hl[0]); sts1(dst + 20736 + (odd ? 0 : 128), hl[1]);
            }
            stg4(hp, 0u, 0u, 0u, 0u);
          }
        }
        asm volatile("bar.arrive 1, 192;" ::: "memory");
        mbar_wait(rem_full, layer);
        mbar_wait(piece_full, 1 - layer);
#pragma unroll 1
        for (uint32_t b = 0; b < 5; b++) {
          const uint32_t blk = sb + REM + 27648 + b * 2048, k = (w - 10) * 32 + lane_id(), rr = k & 7;
          const uint32_t dst = blk + ((k >> 3) & 1) * 1024 + rr * 128 + (((k >> 4) ^ rr) << 4);
          uint32_t v[8];
          lds4(blk + k * 16, v); lds4(blk + 1024 + k * 16, v + 4);
          asm volatile("bar.sync 3, 64;" ::: "memory");
          sts4(dst, v); sts4(dst ^ 64, v + 4);
        }
        asm volatile("fence.proxy.async.shared::cta;" ::: "memory");
        mbar_arrive(remo_full);
        mbar_wait_sleep(xb_done, layer);
        if (w == 10 && layer == 1) {
          const uint32_t lane = lane_id();
          stg4(scp + OFF_S + (lane >> 3) * 96 + j * 8 + (lane & 7), 0u, 0u, 0u, 0u);
          stg4(scp + OFF_S + (4 + (lane >> 3)) * 96 + j * 8 + (lane & 7), 0u, 0u, 0u, 0u);
          if (lane < 8) stg4(scp + OFF_S + j * 96 + 64 + lane, 0u, 0u, 0u, 0u);
        }
#pragma unroll 1
        for (uint32_t i = 0; i < 8 && (w == 11 || layer == 1); i++) {
          zero_share(scp + OFF_X + ((w - 10) * 16 + layer * 8 + i) * SLAB, j, lane_id());
          __nanosleep(500);
        }
      }
    }
  } else {
    asm volatile("setmaxnreg.inc.sync.aligned.u32 240;");
    const bool lead = lane_id() == 0;
    Ring rg{0, 0};
    uint32_t prev = 0;
    uint32_t X[144];
    float rs0, rs1;
    const bool lead2 = lane_id() < 2;
    uint32_t empty_at;
    asm volatile("mapa.shared::cluster.u32 %0, %1, %2;" : "=r"(empty_at) : "r"(empty0), "r"(lane_id() & 1));
    auto release = [&](uint32_t st) { if (lead2) asm volatile("mbarrier.arrive.shared::cluster.b64 _, [%0];" :: "r"(empty_at + st * 8) : "memory"); };
    auto load_kb = [&](int kb, const uint4* src, const char* lo, uint32_t hoff) {
      const uint4* p;
      asm("{\n.reg .pred p;\n.reg .u64 t;\nsetp.ge.u32 p, %2, %3;\nadd.u64 t, %1, -2048;\nselp.b64 %0, t, %1, p;\n}" : "=l"(p) : "l"(src), "r"(j), "r"(kb));
#pragma unroll
      for (int i = 0; i < 4; i++) {
        if (kb == 8) { ldg2(X + 128 + 4 * i, lo + (32 + i) * 512); ldg2(X + 130 + 4 * i, lo + hoff + (32 + i) * 512); }
        else ldg4(X + 16 * kb + 4 * i, p + kb * 128 + i * 32);
      }
    };
    auto check_kb = [&](bool skip, int kb, const uint4* src, const char* lo, uint32_t hoff) {
      int n = 0;
#pragma unroll 1
      while (true) {
        uint32_t m = umin2(umin2(X[16 * kb], X[16 * kb + 4]), umin2(X[16 * kb + 8], X[16 * kb + 12]));
        if (kb == 8) m = umin2(m, umin2(umin2(X[130], X[134]), umin2(X[138], X[142])));
        if (__all_sync(~0u, m != 0u || skip)) break;
        SPIN_GUARD(n);
        load_kb(kb, src, lo, hoff);
      }
    };
#pragma unroll
    for (int i = 0; i < 16; i++) X[i] = 0u;
#pragma unroll 1
    for (uint32_t hf = 0; hf < 4; hf++) {
      const uint32_t layer = hf >> 1;
      const bool ffn = hf & 1;
      const uint32_t tag = 1 - layer;
      const uint32_t xbase = scr + OFF_X + (layer * 8 + w) * SLAB;
      float aA[32], aB[32];
      {
        const uint32_t lane = lane_id(), r = lane >> 2, q = lane & 3;
        const uint4* src = at(xbase + (ffn ? 32 * SLAB : 0) + lane);
        const char* lo = (const char*)at8(2 * (xbase + (ffn ? 32 * SLAB : 0)) + (ffn ? lane : 2 * lane));
        const uint32_t hoff = ffn ? 256 : 8;
        const uint32_t xoff = (w & 1) * 8192 + (16 * (w >> 1) + (lane & 15)) * 128 + (((lane >> 4) ^ (lane & 7)) << 4);
        auto load_x = [&](uint32_t b, uint32_t* d) {
#pragma unroll
          for (int i = 0; i < 4; i++) ldsm4(xs + b * STAGE + (xoff ^ (32 * i)), d[4 * i], d[4 * i + 1], d[4 * i + 2], d[4 * i + 3]);
        };
        auto load_any = [&](int kb) { if (hf == 0) load_x(blk(kb), X + 16 * kb); else load_kb(kb, src, lo, hoff); };
        float m0, m1, v0, v1;
        STAMP(ffn * 16 + 0);
        if (hf == 0) {
          float sum[2][4] = {}, sq0[4][4] = {}, sq1[4][4] = {};
          uint32_t p0, p1;
          mbar_wait(xbar0, 0);
          ldsm4(xs + xoff, p0, p1, X[0], X[1]);
          p0 = __byte_perm(__shfl_sync(~0u, p0, lane & 28), 0, 0x1010); p1 = __byte_perm(__shfl_sync(~0u, p1, lane & 28), 0, 0x1010);
#pragma unroll 3
          for (uint32_t b = 0; b < 9; b++) {
            uint32_t d[16];
            mbar_wait(xbar0 + 8 * b, 0);
            load_x(b, d);
#pragma unroll
            for (int i = 0; i < 16; i++) d[i] = sub_bf16x2(d[i], (i & 1) ? p1 : p0);
#pragma unroll
            for (int g = 0; g < 8; g++) {
              if (!(g & 1)) mma16(sum[(g >> 1) & 1], d[2 * g], d[2 * g + 1], d[2 * g + 2], d[2 * g + 3], 0x3f803f80u, 0x3f803f80u);
              mma8(sq0[g & 3], d[2 * g], d[2 * g + 1], d[2 * g]); mma8(sq1[g & 3], d[2 * g], d[2 * g + 1], d[2 * g + 1]);
            }
          }
          STAMP(1);
          GSTAMP(14);
#pragma unroll
          for (int kb = 0; kb < GD; kb++) load_x(blk(kb), X + 16 * kb);
          release((x_ring - empty0) / 8);
          auto tot = [](float (&c)[4][4], int e) { return (c[0][e] + c[1][e]) + (c[2][e] + c[3][e]); };
          const float a0 = (sum[0][0] + sum[1][0]) * (1.f / 576), a1 = (sum[0][2] + sum[1][2]) * (1.f / 576);
          const uint32_t dg = (lane & 28) + (r >> 1);
          v0 = fmaxf(fmaf(__shfl_sync(~0u, (r & 1) ? tot(sq0, 1) : tot(sq0, 0), dg), 1.f / 576, -a0 * a0), 0.f);
          v1 = fmaxf(fmaf(__shfl_sync(~0u, (r & 1) ? tot(sq1, 3) : tot(sq1, 2), dg), 1.f / 576, -a1 * a1), 0.f);
          m0 = bf_lo(p0) + a0; m1 = bf_lo(p1) + a1;
        } else {
          uint32_t s[3][4];
          const uint4* p = at(scr + OFF_S + ((ffn ? 16 : 0) + w) * 96 + q * 8 + r);
          const bool third = !ffn && q == 0;
          const uint32_t rdy = ffn ? tag : 1u;
          int n = 0;
          s[2][0] = rdy; s[2][1] = s[2][2] = s[2][3] = 0u;
#pragma unroll 1
          while (true) {
            ldg4(s[0], p); ldg4(s[1], p + 32);
            if (third) ldg4(s[2], p + 64);
            if (__all_sync(~0u, ((diff2(s[0][0], s[1][0], rdy) | diff2(s[1][0], s[2][0], rdy)) & 1u) == 0u)) break;
            SPIN_GUARD(n);
          }
          STAMP(ffn * 16 + 1);
          ZSTAMP(1 + ffn, 0);
          GSTAMP(14 + ffn);
#pragma unroll
          for (int kb = 1; kb < GD; kb++) load_kb(kb, src, lo, hoff);
          float t0 = 0.f, t1 = 0.f;
#pragma unroll
          for (int i = 0; i < 3; i++) { t0 += __uint_as_float(s[i][0]); t1 += __uint_as_float(s[i][2]); }
          m0 = quad_sum(t0) * (1.f / 576); m1 = quad_sum(t1) * (1.f / 576);
          const float cnt = ffn ? 72.f : 64.f, inv = ffn ? 1.f / 72 : 1.f / 64;
          v0 = 0.f; v1 = 0.f;
#pragma unroll
          for (int i = 0; i < 3; i++) {
            const float c = (i < 2 || third) ? cnt : 0.f;
            const float d0 = fmaf(__uint_as_float(s[i][0]), inv, -m0), d1 = fmaf(__uint_as_float(s[i][2]), inv, -m1);
            v0 += fmaf(d0 * d0, c, __uint_as_float(s[i][1])); v1 += fmaf(d1 * d1, c, __uint_as_float(s[i][3]));
          }
          v0 = quad_sum(v0) * (1.f / 576); v1 = quad_sum(v1) * (1.f / 576);
        }
        rs0 = rsqrtf(v0 + 1e-5f); rs1 = rsqrtf(v1 + 1e-5f);
        const uint32_t mean0 = pack_bf16(m0, m0), mean1 = pack_bf16(m1, m1);
#pragma unroll
        for (int kb = 0; kb < 9; kb++) {
          if (kb > 0) check_kb(hf == 0, kb, src, lo, hoff);
          if (kb + GD < 9) load_any(kb + GD);
          if (kb + GD == 8 && hf == 0 && lead) mbar_arrive(x_done);
#pragma unroll
          for (int i = 16 * kb; i < 16 * kb + 16; i++) X[i] = sub_bf16x2(X[i], (i & 1) ? mean1 : mean0);
          ZSTAMP(1 + ffn, 1 + 3 * kb);
          mbar_wait(full0 + rg.st * 8, rg.ph);
          ZSTAMP(1 + ffn, 2 + 3 * kb);
          const uint64_t desc = DESC_HI | ((sd + rg.st * STAGE) >> 4);
          wg_fence();
#pragma unroll
          for (int i = 0; i < 4; i++) wgmma_rs_n64(aA, X + 4 * (4 * kb + i), desc + i * 128, kb + i != 0);
          if (kb == 8) { wg_commit(); wg_wait<1>(); wg_fence(); }
#pragma unroll
          for (int i = 0; i < 4; i++) wgmma_rs_n64(aB, X + 4 * (4 * kb + i), desc + 512 + i * 128, kb + i != 0);
          wg_commit();
          wg_wait<1>();
          ZSTAMP(1 + ffn, 3 + 3 * kb);
          if (kb > 0) release(prev);
          prev = rg.st; rg.next();
        }
        ZSTAMP(1 + ffn, 28);
        ZSTAMP(4, 0);
        STAMP(ffn * 16 + 2);
      }
      if (!ffn) {
      const uint32_t lane = lane_id(), r = lane >> 2, q = lane & 3;
      const uint32_t kvrow = sb + KVS + (w & 1) * 10368 + (16 * (w >> 1)) * 144;
      uint32_t Q[18], Km[3][8], Ke[3][4];
      const bool edge = (t == 0 && w < 2);
      const uint32_t row0 = edge ? sb + KVS + 8 * 144 : kvrow + (lane & 7) * 144, row1 = kvrow + (8 + (lane & 7)) * 144;
      {
        const uint32_t dst = kvrow + (8 + r) * 144 + q * 4 + odd * 16, dstr = dst + (odd ? -16 : 128);
        const bool edge_out = w >= 6 && t < 15;
        uint4* const hp = at(scr + TILE + OFF_H + ((layer * 8 + j) * 2 + (w & 1)) * 192 + lane);
        auto put_kv = [&](float (&a)[32], int part, int half) {
          uint32_t hl[4];
#pragma unroll
          for (int i = 0; i < 16; i++) asm volatile("" : "+f"(a[16 * half + i]) :: "memory");
#pragma unroll
          for (int i = 0; i < 4; i++) {
            const int g = 4 * half + i;
            hl[i] = pack_bf16(a[4 * g + 2] * rs1, a[4 * g + 3] * rs1);
            sts1(dst + part * 20736 + g * 16, pack_bf16(a[4 * g] * rs0, a[4 * g + 1] * rs0)); sts1(dst + part * 20736 + 8 * 144 + g * 16, hl[i]);
          }
          if (edge_out) stg4(hp + part * 64 + half * 32, nz(hl[0]), hl[1], hl[2], hl[3]);
        };
        put_kv(aA, 0, 0); put_kv(aA, 0, 1);
        if (lead) mbar_arrive(kv_free);
        wg_wait<0>();
        release(prev);
        float aR[12];
        mbar_wait(rem_full, layer);
        const uint64_t dr = DESC_REM | ((sd + REM) >> 4);
        wg_fence();
#pragma unroll
        for (int s = 0; s < 36; s++) {
          wgmma_rs_n24(aR, X + 4 * s, dr + s * 16, s != 0);
          if (s == 4) put_kv(aB, 1, 0);
          if (s == 16) put_kv(aB, 1, 1);
        }
        wg_commit();
#pragma unroll
        for (int kb = 0; kb < 9; kb++) {
          if (!(kb & 1)) mbar_wait(full0 + rg.st * 8, rg.ph);
          const uint64_t desc = DESC_HI | ((sd + rg.st * STAGE + (kb & 1) * 8192) >> 4);
          wg_fence();
#pragma unroll
          for (int i = 0; i < 4; i++) wgmma_rs_n64(aB, X + 4 * (4 * kb + i), desc + i * 128, kb + i != 0);
          wg_commit();
          wg_wait<1>();
          if (kb > 0 && !(kb & 1)) release(prev);
          if (kb & 1) { prev = rg.st; rg.next(); }
          if (kb == 0) {
            pin(aR);
            const uint32_t k1 = pack_bf16(aR[2] * rs1, aR[3] * rs1), v1 = pack_bf16(aR[6] * rs1, aR[7] * rs1);
            if (edge_out) stg4(hp + 128, nz(k1), v1, 0u, 0u);
            sts1(dstr, pack_bf16(aR[0] * rs0, aR[1] * rs0)); sts1(dstr + 8 * 144, k1);
            sts1(dstr + 20736, pack_bf16(aR[4] * rs0, aR[5] * rs0)); sts1(dstr + 20736 + 8 * 144, v1);
            Q[16] = pack_bf16(aR[8], aR[9]); Q[17] = pack_bf16(aR[10], aR[11]);
            if (w < 4) asm volatile("bar.arrive 2, 256;" ::: "memory");
          }
          if (kb == 8) {
            if (w < 4) asm volatile("bar.sync 1, 192;" ::: "memory");
            else asm volatile("bar.sync 2, 256;" ::: "memory");
#pragma unroll
            for (int nt = 0; nt < 3; nt++) {
              const uint32_t ra = (nt == 0 ? row0 : row1 + (nt - 1) * 8 * 144);
              ldsm4(ra + odd * 16 + (lane >> 3) * 16, Km[nt][0], Km[nt][1], Km[nt][2], Km[nt][3]);
              ldsm4(ra + odd * 16 + 64 + (lane >> 3) * 16, Km[nt][4], Km[nt][5], Km[nt][6], Km[nt][7]);
              ldsm4(ra + (odd ? 0 : 32) + (lane >> 3) * 32, Ke[nt][0], Ke[nt][1], Ke[nt][2], Ke[nt][3]);
            }
          }
        }
        wg_wait<0>();
        pin(aB);
        mbar_wait(att_done, layer ^ (w >> 2));
        STAMP(3);
#pragma unroll
        for (int i = 0; i < 16; i++) Q[i] = pack_bf16(aB[2 * i], aB[2 * i + 1]);
      }
      uint32_t res[18] = {};
      if (layer) {
        const uint4* p = at(xbase + ((9 * j + 1) >> 1) * 32 + lane);
#pragma unroll
        for (int i = 0; i < 4; i++) ldg4(res + 4 * i, p + i * 32);
        ldg2(res + 16, at8(2 * (xbase + (9 * (j >> 1) + 4) * 32 + lane) + odd));
      }
      {
        uint32_t V01[12][2], V2[12];
        const uint32_t rv = ((lane & 8) ? row1 : row0) + 20736, rw = row1 + 8 * 144 + 20736;
#pragma unroll
        for (int i = 0; i < 4; i++) ldsm4t(rv + odd * 16 + i * 32 + (lane >> 4) * 16, V01[2 * i][0], V01[2 * i][1], V01[2 * i + 1][0], V01[2 * i + 1][1]);
#pragma unroll
        for (int i = 0; i < 2; i++) ldsm4t(rv + (odd ? 0 : 32) + i * 64 + (lane >> 4) * 32, V01[8 + 2 * i][0], V01[8 + 2 * i][1], V01[9 + 2 * i][0], V01[9 + 2 * i][1]);
        ldsm4t(rw + odd * 16 + (lane >> 3) * 16, V2[0], V2[1], V2[2], V2[3]);
        ldsm4t(rw + odd * 16 + 64 + (lane >> 3) * 16, V2[4], V2[5], V2[6], V2[7]);
        ldsm4t(rw + (odd ? 0 : 32) + (lane >> 3) * 32, V2[8], V2[9], V2[10], V2[11]);
        const bool up0 = 2 * q > r, up1 = 2 * q + 1 > r;
        const uint32_t upm = (up0 ? 0xffffu : 0u) | (up1 ? 0xffff0000u : 0u);
        const float c0 = 0.23570226039551584f * 1.4426950408889634f * rs0, c1 = 0.23570226039551584f * 1.4426950408889634f * rs1;
        const float masked = -1e9f * 1.4426950408889634f * rcp(c0);
        const int qe = odd ? 9 : q, qo = odd ? q : -1;
        uint32_t Qe[8];
#pragma unroll
        for (int h = 0; h < 4; h++)
#pragma unroll
          for (int e = 0; e < 2; e++) Qe[2 * h + e] = qe <= h ? Q[4 * h + 4 + e] : qo >= h ? Q[(4 * h + 16 + e) % 18] : 0u;
#pragma unroll
        for (int h = 1; h < 4; h++)
#pragma unroll
          for (int e = 0; e < 2; e++) { if (qe < h) Q[4 * h + e] = 0u; if (qo >= h) Q[4 * h - 2 + e] = 0u; }
        uint32_t Om[16], Oe[8];
        uint4* const po = at(xbase + 16 * SLAB + 4 * j * 32 + lane);
        float sv[4][4], mx[4][2];
#pragma unroll
        for (int h = 0; h < 4; h++) {
          float S[3][4];
#pragma unroll
          for (int nt = 0; nt < 3; nt++) {
            mma16z(S[nt], Q + 4 * h, Km[nt][2 * h], Km[nt][2 * h + 1]);
            mma8(S[nt], Qe[2 * h], Qe[2 * h + 1], Ke[nt][h]);
          }
          if (edge) S[0][0] = S[0][1] = masked;
          sv[h][0] = up0 ? S[0][0] : S[1][0]; sv[h][1] = up1 ? S[0][1] : S[1][1];
          sv[h][2] = up0 ? S[1][2] : S[2][2]; sv[h][3] = up1 ? S[1][3] : S[2][3];
        }
        auto quad8 = [&](auto&& op) {
#pragma unroll
          for (int d = 1; d < 3; d++) {
            float o[8];
#pragma unroll
            for (int i = 0; i < 8; i++) o[i] = __shfl_xor_sync(~0u, mx[i >> 1][i & 1], d);
#pragma unroll
            for (int i = 0; i < 8; i++) mx[i >> 1][i & 1] = op(mx[i >> 1][i & 1], o[i]);
          }
        };
#pragma unroll
        for (int i = 0; i < 8; i++) mx[i >> 1][i & 1] = fmaxf(sv[i >> 1][2 * (i & 1)], sv[i >> 1][2 * (i & 1) + 1]);
        quad8([](float x, float y) { return fmaxf(x, y); });
#pragma unroll
        for (int i = 0; i < 8; i++) {
          const float c = (i & 1) ? c1 : c0, m = mx[i >> 1][i & 1] * c;
          float* p = sv[i >> 1] + 2 * (i & 1);
          p[0] = ex2(fmaf(p[0], c, -m)); p[1] = ex2(fmaf(p[1], c, -m));
          mx[i >> 1][i & 1] = p[0] + p[1];
        }
        quad8([](float x, float y) { return x + y; });
        auto u = [&](int i) { return __float_as_uint(mx[i >> 1][i & 1]); };
        const uint32_t none = or3(or3(u(0), u(1), u(2)), or3(u(3), u(4), u(5)), u(6) | u(7)) & (rg.ph >> 1);
#pragma unroll
        for (int h = 0; h < 4; h++) {
          const float i0 = rcp(mx[h][0]), i1 = rcp(mx[h][1]);
          const uint32_t p0 = pack_bf16(sv[h][0] * i0, sv[h][1] * i0), p1 = pack_bf16(sv[h][2] * i1, sv[h][3] * i1);
          const uint32_t pf[6] = {p0 & upm, p0 & none, p0 & ~upm, p1 & upm, p1 & none, p1 & ~upm};
#pragma unroll
          for (int gi = 0; gi < 3; gi++) {
            const int g = gi < 2 ? 2 * h + gi : 8 + h;
            float o[4];
            mma16z(o, pf, V01[g][0], V01[g][1]);
            mma8(o, pf[4], pf[5], V2[g]);
            uint32_t* d = gi < 2 ? Om + 2 * g : Oe + 2 * h;
            d[0] = pack_bf16(o[0], o[1]); d[1] = pack_bf16(o[2], o[3]);
          }
          if (h > 0) {
#pragma unroll
            for (int e = 0; e < 2; e++) {
              if (qe < h) Om[4 * h + e] = Oe[2 * h - 2 + e];
              if (qo >= h) Om[4 * h - 2 + e] = Oe[2 * h + e];
            }
            Om[4 * h - 4] = nz(Om[4 * h - 4]);
            stg4(po + (h - 1) * 32, Om[4 * h - 4], Om[4 * h - 3], Om[4 * h - 2], Om[4 * h - 1]);
            if (h == 3 && w >= 4 && lead) mbar_arrive(att_done);
          }
        }
        STAMP(4);
        Om[12] = nz(Om[12]);
        stg4(po + 96, Om[12], Om[13], Om[14], Om[15]);
        stg2(at8(2 * (xbase + 16 * SLAB + 1024 + j * 16) + lane), nz(odd ? Oe[0] : Oe[6]), odd ? Oe[1] : Oe[7]);
#pragma unroll
        for (int i = 0; i < 16; i++) X[i] = Om[i];
      }
      if (lane == 0) asm volatile("st.relaxed.gpu.global.b32 [%0], %1;" :: "l"(at(scr + OFF_S + (8 + w) * 96 + j * 8)), "r"(tag) : "memory");
      {
        if (layer == 0) {
          const uint32_t xrow = (w & 1) * 8192 + (16 * (w >> 1) + (lane & 15)) * 128;
          uint32_t u0, u1;
          mbar_wait(xbar0, 1); mbar_wait(xbar0 + 8, 1);
#pragma unroll
          for (int i = 0; i < 5; i++) {
            const uint32_t g = i < 4 ? j + odd + 2 * i : j + (odd ? 0 : 8);
            const uint32_t a = sb + PARK + (g >> 3) * STAGE + xrow;
            if (i < 4) ldsm4(a + ((((g & 7) + (lane >> 4)) ^ (lane & 7)) << 4), res[4 * i], res[4 * i + 1], res[4 * i + 2], res[4 * i + 3]);
            else ldsm4(a + (((g & 7) ^ (lane & 7)) << 4), res[16], res[17], u0, u1);
          }
        }
        const uint4* src = at(xbase + 16 * SLAB + lane);
        const uint32_t st0 = rg.st;
        auto stage_of = [&](uint32_t i) { const uint32_t x = st0 + i; return x >= NST ? x - NST : x; };
        {
          const uint32_t x = st0 + lane, wrap = x >= NST;
          mbar_wait(lane < 5 ? full0 + (x - wrap * NST) * 8 : remo_full, lane < 5 ? rg.ph ^ wrap : layer);
          __syncwarp();
          if (st0) { rg.st = st0 - 1; rg.ph ^= 1; } else rg.st = 5;
        }
        float acc[36];
        auto block72 = [&](uint32_t kb, uint32_t base, const uint32_t* a) {
          const uint64_t d0 = DESC_HI | ((base >> 4) + (((sd + REM + 27648 + (kb >> 1) * 2048 + (kb & 1) * 64 - base) >> 4) << 16));
          wg_fence();
#pragma unroll
          for (int i = 0; i < 4; i++) wgmma_rs_n72(acc, a + 4 * i, d0 - (uint64_t)(i * ((127u << 16) - 128u)), 1);
          wg_commit();
        };
#pragma unroll
        for (int i = 0; i < 18; i++) { acc[2 * i] = bf_lo(res[i]); acc[2 * i + 1] = bf_hi(res[i]); }
        block72(0, sd + st0 * STAGE + 8192, X);
        {
          const uint4* fp = at(scr + OFF_S + (8 + w) * 96 + (lane & 7) * 8);
          int n = 0;
          STAMP(8);
#pragma unroll 1
          while (true) {
            uint32_t f;
            asm volatile("ld.relaxed.gpu.global.b32 %0, [%1];" : "=r"(f) : "l"(fp) : "memory");
            if (__all_sync(~0u, f == tag)) break;
            SPIN_GUARD(n);
          }
          wg_wait<0>(); release(st0);
          STAMP(9);
        }
#pragma unroll
        for (int kb = 1; kb < GO; kb++) load_kb(kb, src, (const char*)src - lane * 8, 256);
        __syncwarp();
        uint32_t m = ~0u;
#pragma unroll
        for (int kb = 1; kb < 9; kb++) {
          m = umin2(m, umin2(umin2(X[16 * kb], X[16 * kb + 4]), umin2(X[16 * kb + 8], X[16 * kb + 12])));
          if (kb == 8) m = umin2(m, umin2(umin2(X[130], X[134]), umin2(X[138], X[142])));
          if (kb + GO - 1 < 9) {
            const uint4* s2 = src + (m == 0u);
            load_kb(kb + GO - 1, s2, (const char*)s2 - lane * 8, 256);
            __syncwarp();
          }
          block72(kb, sd + stage_of((kb + 1) >> 1) * STAGE + (~kb & 1) * 8192, X + 16 * kb);
          if ((kb & 1) && kb > 1) { wg_wait<1>(); release(stage_of(kb >> 1)); }
        }
        uint32_t redo;
        asm volatile("{\n.reg .pred p;\nsetp.eq.u32 p, %1, 0;\nbar.red.or.pred p, %2, 128, p;\nselp.u32 %0, 1, 0, p;\n}" : "=r"(redo) : "r"(m), "r"(5 + (w >> 2)) : "memory");
        wg_wait<0>();
        release(stage_of(4));
        pin(acc);
        if (__any_sync(~0u, redo || FORCE_REDO)) {
#pragma unroll
          for (int i = 0; i < 18; i++) { res[i] = __shfl_sync(~0u, res[i], lane); acc[2 * i] = bf_lo(res[i]); acc[2 * i + 1] = bf_hi(res[i]); }
          const uint32_t box = PARK + 2 * STAGE + (w >> 2) * 8192, bar = redo_full + (w >> 2) * 8;
#pragma unroll 1
          for (uint32_t kb = 0; kb < 10; kb++) {
            asm volatile("bar.sync %0, 128;" :: "r"(5 + (w >> 2)) : "memory");
            if ((w & 3) == 0)
              asm volatile("{\n.reg .pred e;\nelect.sync _|e, 0xffffffff;\n@e mbarrier.arrive.expect_tx.shared::cta.b64 _, [%2], 8192;\n"
                           "@e cp.async.bulk.tensor.3d.shared::cluster.global.mbarrier::complete_tx::bytes [%0], [%1, {%3, %4, %5}], [%2];\n}"
                           :: "r"(sb + box), "l"(&maps.m[kb >= 8 ? 8 : 1]), "r"(bar), "r"(72 * j + 8 * odd), "r"(kb >= 8 ? 64 : 0),
                              "r"(kb >= 8 ? 0 : (9 * blk(kb) + 1) >> 1) : "memory");
            mbar_wait(bar, kb & 1);
            if (kb == 9) break;
            int n = 0;
#pragma unroll 1
            while (true) {
              const char* l = (const char*)(src + blk(kb) * 128) - (kb == 8 ? lane * 8 : 0);
#pragma unroll
              for (int i = 0; i < 4; i++) ldg2(X + 4 * i, l + i * 512);
              uint32_t mm = umin2(umin2(X[0], X[4]), umin2(X[8], X[12]));
              l += (kb == 8 ? 256 : 8) + (mm == 0u ? 16 : 0);
#pragma unroll
              for (int i = 0; i < 4; i++) ldg2(X + 4 * i + 2, l + i * 512);
              if (kb == 8) mm = umin2(mm, umin2(umin2(X[2], X[6]), umin2(X[10], X[14])));
              if (__all_sync(~0u, mm != 0u)) break;
              SPIN_GUARD(n);
            }
            block72(kb, sd + box, X);
            wg_wait<0>();
            pin(acc);
          }
        }
        STAMP(10);
#pragma unroll
        for (int i = 0; i < 18; i++) { res[i] = pack_bf16(acc[2 * i], acc[2 * i + 1]); if (!(i & 3)) res[i] = nz(res[i]); }
        auto put = [&] {
          put4(at(xbase + 32 * SLAB + 4 * j * 32 + lane), res);
          stg2(at8(2 * (xbase + 32 * SLAB + 1024 + j * 16) + lane), res[16], res[17]);
        };
        if (j < PRI) put();
        publish_stats<9>(at(scr + OFF_S + (16 + w) * 96 + j * 8 + r), acc, tag, lane);
        if (j >= PRI) put();
#pragma unroll
        for (int i = 0; i < 16; i++) X[i] = res[i];
      }
      continue;
      }
      const uint32_t hp = sb + PARK + w * 512 + lane_id() * 16;
      auto pack8 = [&](float (&a)[32], int p, uint32_t* o) {
#pragma unroll
        for (int e = 0; e < 8; e++) asm volatile("" : "+f"(a[8 * p + e]) :: "memory");
#pragma unroll
        for (int e = 0; e < 4; e++) o[e] = pack_bf16(a[8 * p + 2 * e], a[8 * p + 2 * e + 1]);
      };
      const float ka0 = 0.7978845608028654f * rs0, kb0 = 0.044715f * ka0 * rs0 * rs0, ku0 = 0.5f * rs0 * rs0;
      const float ka1 = 0.7978845608028654f * rs1, kb1 = 0.044715f * ka1 * rs1 * rs1, ku1 = 0.5f * rs1 * rs1;
      auto packu8 = [&](int p, uint32_t* o) {
#pragma unroll
        for (int e = 0; e < 8; e++) asm volatile("" : "+f"(aA[8 * p + e]) :: "memory");
#pragma unroll
        for (int e = 0; e < 4; e++) o[e] = pack_bf16(aA[8 * p + 2 * e] * ((e & 1) ? ku1 : ku0), aA[8 * p + 2 * e + 1] * ((e & 1) ? ku1 : ku0));
      };
      auto geglu8 = [&](int p, uint32_t* u) {
#pragma unroll
        for (int e = 0; e < 8; e++) asm volatile("" : "+f"(aB[8 * p + e]) :: "memory");
        float h[8];
#pragma unroll
        for (int e = 0; e < 8; e++) {
          const float g = aB[8 * p + e];
          h[e] = fmaf(g, tanh_ap(g * fmaf(g * g, (e & 2) ? kb1 : kb0, (e & 2) ? ka1 : ka0)), g);
        }
#pragma unroll
        for (int e = 0; e < 4; e++) u[e] = mul_bf16x2(pack_bf16(h[2 * e], h[2 * e + 1]), u[e]);
      };
      uint32_t ready = 0;
      auto box = [&](int b, auto&& filler) {
        const int kb = b < 9 ? b : b - 9;
        if (b == 0) mbar_wait_trap(full0 + rg.st * 8, rg.ph);
        else if (!(b & 1)) mbar_wait_unless(ready, full0 + rg.st * 8, rg.ph);
        const uint64_t desc = DESC_HI | ((sd + rg.st * STAGE + (b & 1) * 8192) >> 4);
        if (b & 1) { prev = rg.st; rg.next(); }
        wg_fence();
#pragma unroll
        for (int i = 0; i < 4; i++) {
          if (b < 9) wgmma_rs_n64(aA, X + 4 * (4 * kb + i), desc + i * 128, kb + i != 0);
          else wgmma_rs_n64(aB, X + 4 * (4 * kb + i), desc + i * 128, kb + i != 0);
          if ((b & 1) && b < 17 && i == 0) ready = mbar_peek(full0 + rg.st * 8, rg.ph);
          if (i == 1) filler();
        }
        wg_commit();
        if (!(b & 1)) { wg_wait<1>(); release(prev); }
      };
      auto nop = [] {};
#pragma unroll
      for (int p = 0; p < 4; p++) { uint32_t o[4]; packu8(p, o); sts4(hp + p * 4096, o); }
      box(0, nop);
      if (lead) mbar_arrive(xb_done);
#pragma unroll 1
      for (int c = 1;; c++) {
        const uint32_t hc = hp + c * 4 * 4096;
#pragma unroll
        for (int b = 1; b < 18; b++) box(b, [&] {
          if ((b & 1) && b < 8) { uint32_t o[4]; const uint32_t a = hc - (4 - (b >> 1)) * 4096; lds4(a, o); geglu8(b >> 1, o); sts4(a, o); }
          if ((b & 1) && b > 10) { uint32_t o[4]; packu8((b - 11) >> 1, o); if (c < 8) sts4(hc + ((b - 11) >> 1) * 4096, o); } });
        ZSTAMP(4, c);
        if (c == 8) break;
        box(0, nop);
      }
      wg_wait<0>();
      STAMP(21);
      GSTAMP(19);
      auto unpark = [&](int kb) {
#pragma unroll
        for (int s = 4 * kb; s < 4 * kb + 4; s++) lds4(hp + s * 4096, X + 4 * s);
      };
      unpark(0);
      uint32_t U[16];
#pragma unroll
      for (int p = 0; p < 4; p++) packu8(p, U + 4 * p);
#pragma unroll
      for (int b = 0; b < 8; b++) box(b, [&] {
        if (b < 7) unpark(b + 1);
        if (b & 1) {
          geglu8(b >> 1, U + 2 * (b - 1));
          if (rg.ph > 1) sts4(hp, U + 2 * (b - 1));
#pragma unroll
          for (int i = 0; i < 4; i++) X[128 + 2 * (b - 1) + i] = U[2 * (b - 1) + i];
        } });
      STAMP(24);
      if (layer == 0 && lead) mbar_arrive(park_free);
      const uint32_t lane2 = lane_id();
      uint4* const pw = scp + OFF_P + (j * 8 + w) * SLAB + lane2;
      const uint32_t pr = scr + OFF_P + w * SLAB + 4 * j * 32 + lane2;
      auto put_part = [&](float (&a)[32], int p, uint32_t chunk) {
        uint32_t o[4];
        pack8(a, p, o);
        stg4(pw + (chunk * 4 + p) * 32, (o[0] & ~1u) | tag, o[1], o[2], o[3]);
      };
      auto slot = [&](int p) { return sb + w * 2048 + (p < 3 ? PARK + p * 16384 : KVS + (p - 3) * 16384); };
      auto fetch = [&](int p) {
        bulk_load(slot(p), at(scr + OFF_P + (((j - p) & 7) * 8 + w) * SLAB + 4 * j * 32), 2048, pbar0 + w * 8, true);
      };
#pragma unroll 1
      for (int sp = 0;; sp++) {
        const uint32_t ca = sp == 0 ? 8 : ((j + 2 * sp) & 7), cb = (j + 2 * sp + 1) & 7;
        if (sp == 1 && lead) mbar_arrive(c8_go);
#pragma unroll
        for (int b = 8; b < 18; b++) box(b, [&] {
          if (b >= 11 && b < 15) put_part(aA, b - 11, ca);
          if (b == 17 && sp > 1) { if (sp == 3) mbar_wait(c8_done, layer); fetch(2 * sp - 2); } });
        STAMP(25 + sp);
        if (sp == 3) break;
#pragma unroll
        for (int b = 0; b < 8; b++) box(b, [&] {
          if (b >= 1 && b < 5) put_part(aB, b - 1, cb);
          if (b == 7 && sp > 0) fetch(2 * sp - 1); });
      }
      auto load_p = [&](int p, uint32_t* d) {
#pragma unroll
        for (int i = 0; i < 4; i++) ldg4(d + 4 * i, at(pr + ((j - p) & 7) * 8 * SLAB) + i * 32);
      };
      auto bad = [&](const uint32_t* d, uint32_t tg) { return diff2(d[0], d[4], tg) | diff2(d[8], d[12], tg); };
      uint32_t late = 0;
#pragma unroll
      for (int b = 0; b < 9; b++) {
        if (b == 6) { mbar_wait(lane2 & 1 ? res_full : pbar0 + w * 8, layer); __syncwarp(); }
        box(b, [&] {
          if (b == 1) {
#pragma unroll
            for (int p = 0; p < 4; p++) put_part(aB, p, (j + 7) & 7);
          }
          if (b == 3) { load_p(5, X); load_p(6, X + 16); }
          if (b == 7) {
            late = bad(X, tag) | bad(X + 16, tag);
#pragma unroll
            for (int i = 0; i < 4; i++) ldg4(X + 32 + 4 * i, at(pr + ((j - 7) & 7) * 8 * SLAB + (late == 0x7fc12345u)) + i * 32);
          } });
      }
#pragma unroll
      for (int p = 1; p < 5; p++)
#pragma unroll
        for (int i = 0; i < 4; i++) lds4(slot(p) + lane2 * 16 + i * 512, X + 48 + 16 * p + 4 * i);
#pragma unroll
      for (int i = 0; i < 4; i++) {
        const bool split = j == 2 * i + 1;
        const uint32_t a = slot(0) + i * 512 + (split ? lane2 * 8 : lane2 * 16);
        lds2(a, X + 48 + 4 * i); lds2(a + (split ? 256 : 8), X + 50 + 4 * i);
      }
      wg_wait<0>();
      release(rg.st); rg.next();
      pin(aA);
      STAMP(22);
      GSTAMP(20);
      {
        const uint32_t lane = lane2, r = lane >> 2, q = lane & 3;
        const uint32_t eye = r == 2 * q ? 0x3f80u : r == 2 * q + 1 ? 0x3f800000u : 0u;
        auto add = [&](const uint32_t* d) {
#pragma unroll
          for (int g = 0; g < 8; g++) mma8(aA + 4 * g, d[2 * g], d[2 * g + 1], eye);
        };
        int n = 0;
        late = or3(late, bad(X + 64, tag), or3(bad(X + 80, tag), bad(X + 96, tag), bad(X + 112, tag)));
#pragma unroll 1
        while (!__all_sync(~0u, (late & 1u) == 0u)) {
          SPIN_GUARD(n);
          const uint32_t pc = scr + OFF_P + w * SLAB + 4 * j * 32 + lane_id();
          late = 0;
#pragma unroll
          for (int p = 1; p < 8; p++) {
            uint32_t* d = X + (p < 5 ? 48 + 16 * p : 16 * (p - 5));
#pragma unroll
            for (int i = 0; i < 4; i++) ldg4(d + 4 * i, at(pc + ((j - p) & 7) * 8 * SLAB) + i * 32);
            late |= bad(d, tag);
          }
        }
        add(X); add(X + 16);
#pragma unroll
        for (int p = 1; p < 6; p++) add(X + 48 + 16 * (p % 5));
        STAMP(11);
        const uint32_t tg = tag ^ (__float_as_uint(aA[28]) == 0x7fc12345u ? 2u : 0u);
#pragma unroll 1
        while (!__all_sync(~0u, (bad(X + 32, tg) & 1u) == 0u)) { SPIN_GUARD(n); load_p(7, X + 32); }
        add(X + 32);
        STAMP(12);
        uint32_t res[16];
#pragma unroll
        for (int i = 0; i < 16; i++) X[i] = res[i] = pack_bf16(aA[2 * i], aA[2 * i + 1]);
        if (layer == 0) {
#pragma unroll
          for (int i = 0; i < 4; i++) X[4 * i] = nz(X[4 * i]);
          auto put = [&] { put4(at(xbase + 8 * SLAB + 4 * j * 32 + lane), X); };
          if (j < PRI) put();
          publish_stats<8>(at(scr + OFF_S + w * 96 + j * 8 + r), aA, 1u, lane);
          if (j >= PRI) put();
        } else {
          const uint32_t tb = slot(0);
          __syncwarp();
#pragma unroll
          for (int i = 0; i < 4; i++) {
            const uint32_t row = (lane2 & 7) + (lane2 & 8), g = 2 * i + (lane2 >> 4);
            asm volatile("stmatrix.sync.aligned.m8n8.x4.shared.b16 [%0], {%1,%2,%3,%4};"
                         :: "r"(tb + row * 128 + ((g ^ (row & 7)) << 4)), "r"(res[4 * i]), "r"(res[4 * i + 1]), "r"(res[4 * i + 2]), "r"(res[4 * i + 3]) : "memory");
          }
          __syncwarp();
#pragma unroll
          for (int i = 0; i < 4; i++) {
            const uint32_t row = 4 * i + (lane2 >> 3), g = lane2 & 7;
            uint32_t v[4];
            lds4(tb + row * 128 + ((g ^ (row & 7)) << 4), v);
            ((uint4*)out + ((128 * t + 32 * (w >> 1) + 2 * (lane2 >> 3) + (w & 1)) * 72 + 8 * j + g))[i * 576] = make_uint4(v[0], v[1], v[2], v[3]);
          }
        }
      }
      STAMP(23);
    }
  }
}

typedef CUresult (*EncodeFn)(CUtensorMap*, CUtensorMapDataType, cuuint32_t, void*, const cuuint64_t*, const cuuint64_t*,
                             const cuuint32_t*, const cuuint32_t*, CUtensorMapInterleave, CUtensorMapSwizzle,
                             CUtensorMapL2promotion, CUtensorMapFloatOOBfill);

CUtensorMap make_map(EncodeFn f, const void* p, uint64_t cols, uint64_t rows, uint64_t grp) {
  CUtensorMap m;
  cuuint64_t dims[3] = {cols, grp, rows / grp}, str[2] = {cols * 2, cols * 2 * grp};
  cuuint32_t box[3] = {64, 16, 4}, es[3] = {1, 1, 1};
  f(&m, CU_TENSOR_MAP_DATA_TYPE_BFLOAT16, 3, const_cast<void*>(p), dims, str, box, es, CU_TENSOR_MAP_INTERLEAVE_NONE,
    CU_TENSOR_MAP_SWIZZLE_128B, CU_TENSOR_MAP_L2_PROMOTION_NONE, CU_TENSOR_MAP_FLOAT_OOB_FILL_NONE);
  return m;
}
CUtensorMap make_rem_map(EncodeFn f, const void* p, uint64_t cols) {
  CUtensorMap m;
  cuuint64_t dims[2] = {cols, 576}, str[1] = {cols * 2};
  cuuint32_t box[2] = {8, 144}, es[2] = {1, 1};
  f(&m, CU_TENSOR_MAP_DATA_TYPE_BFLOAT16, 2, const_cast<void*>(p), dims, str, box, es, CU_TENSOR_MAP_INTERLEAVE_NONE,
    CU_TENSOR_MAP_SWIZZLE_NONE, CU_TENSOR_MAP_L2_PROMOTION_NONE, CU_TENSOR_MAP_FLOAT_OOB_FILL_NONE);
  return m;
}

}

extern "C" void kernel_launch(void* const* d_in, const int* in_sizes, int n_in, void* d_out, int out_size) {
  void* fn = nullptr;
  cudaDriverEntryPointQueryResult qr;
  cudaGetDriverEntryPoint("cuTensorMapEncodeTiled", &fn, cudaEnableDefault, &qr);
  EncodeFn enc = (EncodeFn)fn;
  Maps maps;
  maps.m[0] = make_map(enc, d_in[1], 1728, 576, 16); maps.m[1] = make_map(enc, d_in[2], 576, 576, 16);
  maps.m[2] = make_map(enc, d_in[4], 4608, 576, 16); maps.m[3] = make_map(enc, d_in[5], 4608, 576, 16);
  maps.m[4] = make_map(enc, d_in[6], 576, 4608, 16);
  maps.m[5] = make_rem_map(enc, d_in[1], 1728); maps.m[6] = make_rem_map(enc, d_in[2], 576);
  maps.m[8] = make_map(enc, d_in[2], 576, 576, 144); maps.m[9] = make_map(enc, d_in[4], 4608, 576, 144);
  maps.m[10] = make_map(enc, d_in[5], 4608, 576, 144);
  {
    cuuint64_t dims[3] = {576, 1024, 2}, str[2] = {2304, 1152};
    cuuint32_t box[3] = {64, 64, 2}, es[3] = {1, 1, 1};
    enc(&maps.m[7], CU_TENSOR_MAP_DATA_TYPE_BFLOAT16, 3, d_in[0], dims, str, box, es, CU_TENSOR_MAP_INTERLEAVE_NONE,
        CU_TENSOR_MAP_SWIZZLE_128B, CU_TENSOR_MAP_L2_PROMOTION_NONE, CU_TENSOR_MAP_FLOAT_OOB_FILL_NONE);
  }
  void* scr = nullptr;
  cudaGetSymbolAddress(&scr, g_scratch);
  cudaFuncSetAttribute(mega_kernel, cudaFuncAttributeMaxDynamicSharedMemorySize, SMEM_BYTES);
  cudaLaunchConfig_t cfg = {};
  cfg.gridDim = dim3(128); cfg.blockDim = dim3(384); cfg.dynamicSmemBytes = SMEM_BYTES; cfg.stream = cudaStreamPerThread;
  cudaLaunchAttribute at[1];
  at[0].id = cudaLaunchAttributeClusterDimension; at[0].val.clusterDim.x = 2; at[0].val.clusterDim.y = 1; at[0].val.clusterDim.z = 1;
  cfg.attrs = at; cfg.numAttrs = 1;
  int dev = 0, sms = 0, clusters = 0;
  cudaGetDevice(&dev);
  cudaDeviceGetAttribute(&sms, cudaDevAttrMultiProcessorCount, dev);
  cudaOccupancyMaxActiveClusters(&clusters, mega_kernel, &cfg);
  if (sms == 132 && clusters == 66) cfg.gridDim = dim3(132);
  cudaLaunchKernelEx(&cfg, mega_kernel, maps, (uint4*)scr, (__nv_bfloat16*)d_out);
}
```

```cpp
#include <cuda_runtime.h>
#include <cuda.h>
#include <cuda_bf16.h>
#include <stdint.h>

#define TRACE 0
#define GUARD 0
#define FORCE_REDO 0
#define ZT 0

namespace {

constexpr int NST = 6;
constexpr int STAGE = 16384;
constexpr int PARK = NST * STAGE;
constexpr int REM = PARK + 49152;
constexpr int KVS = REM + 40960;
constexpr int PIECE = PARK + 7 * STAGE;
constexpr int HSTG = KVS + 16384;
constexpr int BARS = KVS + 41472;
constexpr int TRC = BARS + 512;
constexpr int SMEM_BYTES = TRC + (TRACE ? 512 : 0);
static_assert(NST == 6, "the producer addresses empty barriers as full + 48");
static_assert(BARS >= PARK + 131072, "barriers overlap park");
static_assert(SMEM_BYTES <= 232448, "smem");

constexpr int SLAB = 36 * 32;
constexpr int SPIN_MAX = 1 << 17;
constexpr uint32_t PRI = 3;
constexpr int GD = 3, GO = 5;
constexpr int OFF_S = 0;
constexpr int OFF_H = OFF_S + 3 * 8 * 96;
constexpr int OFF_X = OFF_H + 2 * 8 * 384 - 8 * SLAB;
constexpr int OFF_P = OFF_X + 6 * 8 * SLAB;
constexpr int TILE = OFF_P + 8 * 8 * SLAB;
constexpr int OFF_R = 16 * TILE;
constexpr int OFF_F = OFF_R + 8 * 2304;
constexpr int SCRATCH = OFF_F + 128 * 8;

}

__device__ uint4 g_scratch[SCRATCH];

namespace {

constexpr uint64_t DESC_HI = 0x4000004000000000ull;
constexpr uint64_t DESC_REM = (576ull << 32) | (8u << 16);
__device__ __forceinline__ void wgmma_rs_n64(float (&d)[32], const uint32_t* a, uint64_t desc, int scale_d) {
  asm volatile("{\n.reg .pred p;\nsetp.ne.b32 p, %37, 0;\n"
    "wgmma.mma_async.sync.aligned.m64n64k16.f32.bf16.bf16 "
    "{%0, %1, %2, %3, %4, %5, %6, %7, %8, %9, %10, %11, %12, %13, %14, %15, %16, %17, %18, %19, %20, %21, %22, %23, %24, %25, %26, %27, %28, %29, %30, %31}, "
    "{%32, %33, %34, %35}, %36, p, 1, 1, 1;\n}\n"
    : "+f"(d[0]), "+f"(d[1]), "+f"(d[2]), "+f"(d[3]), "+f"(d[4]), "+f"(d[5]), "+f"(d[6]), "+f"(d[7]), "+f"(d[8]), "+f"(d[9]), "+f"(d[10]), "+f"(d[11]), "+f"(d[12]), "+f"(d[13]), "+f"(d[14]), "+f"(d[15]), "+f"(d[16]), "+f"(d[17]), "+f"(d[18]), "+f"(d[19]), "+f"(d[20]), "+f"(d[21]), "+f"(d[22]), "+f"(d[23]), "+f"(d[24]), "+f"(d[25]), "+f"(d[26]), "+f"(d[27]), "+f"(d[28]), "+f"(d[29]), "+f"(d[30]), "+f"(d[31])
    : "r"(a[0]), "r"(a[1]), "r"(a[2]), "r"(a[3]), "l"(desc), "r"(scale_d));
}
__device__ __forceinline__ void wgmma_rs_n72(float (&d)[36], const uint32_t* a, uint64_t desc, int scale_d) {
  asm volatile("{\n.reg .pred p;\nsetp.ne.b32 p, %41, 0;\n"
    "wgmma.mma_async.sync.aligned.m64n72k16.f32.bf16.bf16 "
    "{%0, %1, %2, %3, %4, %5, %6, %7, %8, %9, %10, %11, %12, %13, %14, %15, %16, %17, %18, %19, %20, %21, %22, %23, %24, %25, %26, %27, %28, %29, %30, %31, %32, %33, %34, %35}, "
    "{%36, %37, %38, %39}, %40, p, 1, 1, 1;\n}\n"
    : "+f"(d[0]), "+f"(d[1]), "+f"(d[2]), "+f"(d[3]), "+f"(d[4]), "+f"(d[5]), "+f"(d[6]), "+f"(d[7]), "+f"(d[8]), "+f"(d[9]), "+f"(d[10]), "+f"(d[11]), "+f"(d[12]), "+f"(d[13]), "+f"(d[14]), "+f"(d[15]), "+f"(d[16]), "+f"(d[17]), "+f"(d[18]), "+f"(d[19]), "+f"(d[20]), "+f"(d[21]), "+f"(d[22]), "+f"(d[23]), "+f"(d[24]), "+f"(d[25]), "+f"(d[26]), "+f"(d[27]), "+f"(d[28]), "+f"(d[29]), "+f"(d[30]), "+f"(d[31]), "+f"(d[32]), "+f"(d[33]), "+f"(d[34]), "+f"(d[35])
    : "r"(a[0]), "r"(a[1]), "r"(a[2]), "r"(a[3]), "l"(desc), "r"(scale_d));
}
__device__ __forceinline__ void wgmma_rs_n24(float (&d)[12], const uint32_t* a, uint64_t desc, int scale_d) {
  asm volatile("{\n.reg .pred p;\nsetp.ne.b32 p, %17, 0;\n"
    "wgmma.mma_async.sync.aligned.m64n24k16.f32.bf16.bf16 "
    "{%0, %1, %2, %3, %4, %5, %6, %7, %8, %9, %10, %11}, "
    "{%12, %13, %14, %15}, %16, p, 1, 1, 1;\n}\n"
    : "+f"(d[0]), "+f"(d[1]), "+f"(d[2]), "+f"(d[3]), "+f"(d[4]), "+f"(d[5]), "+f"(d[6]), "+f"(d[7]), "+f"(d[8]), "+f"(d[9]), "+f"(d[10]), "+f"(d[11])
    : "r"(a[0]), "r"(a[1]), "r"(a[2]), "r"(a[3]), "l"(desc), "r"(scale_d));
}

__device__ __forceinline__ void mbar_init(uint32_t a, uint32_t c) { asm volatile("mbarrier.init.shared::cta.b64 [%0], %1;" :: "r"(a), "r"(c)); }
__device__ __forceinline__ void mbar_arrive(uint32_t a) { asm volatile("mbarrier.arrive.shared::cta.b64 _, [%0];" :: "r"(a) : "memory"); }
__device__ __forceinline__ void mbar_wait_trap(uint32_t a, uint32_t ph) {
  asm volatile("{\n.reg .pred p;\n.reg .u32 n;\nmov.u32 n, 0;\n"
               "W: mbarrier.try_wait.parity.shared::cta.b64 p, [%0], %1;\n@p bra D;\n"
               "add.u32 n, n, 1;\nsetp.lt.u32 p, n, 4194304;\n@p bra W;\ntrap;\nD:\n}" :: "r"(a), "r"(ph) : "memory");
}
__device__ __forceinline__ void mbar_wait(uint32_t a, uint32_t ph) {
  asm volatile("{\n.reg .pred p;\nW: mbarrier.try_wait.parity.shared::cta.b64 p, [%0], %1;\n@!p bra W;\n}" :: "r"(a), "r"(ph) : "memory");
}
__device__ __forceinline__ uint32_t mbar_peek(uint32_t a, uint32_t ph) {
  uint32_t r;
  asm volatile("{\n.reg .pred p;\nmbarrier.test_wait.parity.shared::cta.b64 p, [%1], %2;\nselp.u32 %0, 1, 0, p;\n}" : "=r"(r) : "r"(a), "r"(ph) : "memory");
  return r;
}
__device__ __forceinline__ void mbar_wait_unless(uint32_t ready, uint32_t a, uint32_t ph) {
  asm volatile("{\n.reg .pred p;\nsetp.ne.u32 p, %2, 0;\n@p bra D;\nW: mbarrier.try_wait.parity.shared::cta.b64 p, [%0], %1;\n@!p bra W;\nD:\n}"
               :: "r"(a), "r"(ph), "r"(ready) : "memory");
}
__device__ __forceinline__ void mbar_wait_sleep(uint32_t a, uint32_t ph) {
  asm volatile("{\n.reg .pred p;\nW: mbarrier.test_wait.parity.shared::cta.b64 p, [%0], %1;\n@p bra D;\nnanosleep.u32 500;\nbra W;\nD:\n}" :: "r"(a), "r"(ph) : "memory");
}
__device__ __forceinline__ void wg_fence() { asm volatile("wgmma.fence.sync.aligned;" ::: "memory"); }
__device__ __forceinline__ void wg_commit() { asm volatile("wgmma.commit_group.sync.aligned;" ::: "memory"); }
template <int N> __device__ __forceinline__ void wg_wait() { asm volatile("wgmma.wait_group.sync.aligned %0;" :: "n"(N) : "memory"); }
__device__ __forceinline__ float tanh_ap(float x) { float y; asm("tanh.approx.f32 %0, %1;" : "=f"(y) : "f"(x)); return y; }
__device__ __forceinline__ float ex2(float x) { float y; asm("ex2.approx.ftz.f32 %0, %1;" : "=f"(y) : "f"(x)); return y; }
__device__ __forceinline__ uint32_t pack_bf16(float lo, float hi) { uint32_t r; asm("cvt.rn.bf16x2.f32 %0, %1, %2;" : "=r"(r) : "f"(hi), "f"(lo)); return r; }
__device__ __forceinline__ float bf_lo(uint32_t v) { return __uint_as_float(v << 16); }
__device__ __forceinline__ float bf_hi(uint32_t v) { return __uint_as_float(v & 0xffff0000u); }
__device__ __forceinline__ uint32_t sub_bf16x2(uint32_t a, uint32_t b) { uint32_t r; asm("sub.rn.bf16x2 %0, %1, %2;" : "=r"(r) : "r"(a), "r"(b)); return r; }
__device__ __forceinline__ uint32_t mul_bf16x2(uint32_t a, uint32_t b) { uint32_t r; asm("mul.rn.bf16x2 %0, %1, %2;" : "=r"(r) : "r"(a), "r"(b)); return r; }
__device__ __forceinline__ uint32_t diff2(uint32_t a, uint32_t b, uint32_t t) { uint32_t r; asm("lop3.b32 %0, %1, %2, %3, 0x7e;" : "=r"(r) : "r"(a), "r"(b), "r"(t)); return r; }
__device__ __forceinline__ uint32_t or3(uint32_t a, uint32_t b, uint32_t c) { uint32_t r; asm("lop3.b32 %0, %1, %2, %3, 0xfe;" : "=r"(r) : "r"(a), "r"(b), "r"(c)); return r; }
__device__ __forceinline__ uint32_t umin2(uint32_t a, uint32_t b) { uint32_t r; asm("min.u32 %0, %1, %2;" : "=r"(r) : "r"(a), "r"(b)); return r; }
__device__ __forceinline__ uint32_t nz(uint32_t w) { return w == 0u ? 0x8000u : w; }

__device__ __forceinline__ void ldg4(uint32_t* d, const uint4* p) {
  asm volatile("ld.relaxed.gpu.global.v4.b32 {%0,%1,%2,%3}, [%4];" : "=r"(d[0]), "=r"(d[1]), "=r"(d[2]), "=r"(d[3]) : "l"(p) : "memory");
}
__device__ __forceinline__ void ldg2(uint32_t* d, const void* p) {
  asm volatile("ld.relaxed.gpu.global.v2.b32 {%0,%1}, [%2];" : "=r"(d[0]), "=r"(d[1]) : "l"(p) : "memory");
}
__device__ __forceinline__ void stg4(uint4* p, uint32_t a, uint32_t b, uint32_t c, uint32_t d) {
  asm volatile("st.relaxed.gpu.global.v4.b32 [%0], {%1,%2,%3,%4};" :: "l"(p), "r"(a), "r"(b), "r"(c), "r"(d) : "memory");
}
__device__ __forceinline__ void stg2(void* p, uint32_t a, uint32_t b) {
  asm volatile("st.relaxed.gpu.global.v2.b32 [%0], {%1,%2};" :: "l"(p), "r"(a), "r"(b) : "memory");
}
__device__ __forceinline__ void sts4(uint32_t a, const uint32_t* o) { asm volatile("st.shared.v4.b32 [%0], {%1,%2,%3,%4};" :: "r"(a), "r"(o[0]), "r"(o[1]), "r"(o[2]), "r"(o[3]) : "memory"); }
__device__ __forceinline__ void lds4(uint32_t a, uint32_t* o) { asm volatile("ld.shared.v4.b32 {%0,%1,%2,%3}, [%4];" : "=r"(o[0]), "=r"(o[1]), "=r"(o[2]), "=r"(o[3]) : "r"(a) : "memory"); }
__device__ __forceinline__ void lds2(uint32_t a, uint32_t* o) { asm volatile("ld.shared.v2.b32 {%0,%1}, [%2];" : "=r"(o[0]), "=r"(o[1]) : "r"(a) : "memory"); }
__device__ __forceinline__ float rcp(float x) { float y; asm("rcp.approx.ftz.f32 %0, %1;" : "=f"(y) : "f"(x)); return y; }
__device__ __forceinline__ void sts1(uint32_t a, uint32_t v) { asm volatile("st.shared.b32 [%0], %1;" :: "r"(a), "r"(v) : "memory"); }
__device__ __forceinline__ void ldsm4(uint32_t a, uint32_t& r0, uint32_t& r1, uint32_t& r2, uint32_t& r3) {
  asm volatile("ldmatrix.sync.aligned.m8n8.x4.shared.b16 {%0,%1,%2,%3}, [%4];" : "=r"(r0), "=r"(r1), "=r"(r2), "=r"(r3) : "r"(a) : "memory");
}
__device__ __forceinline__ void ldsm4t(uint32_t a, uint32_t& r0, uint32_t& r1, uint32_t& r2, uint32_t& r3) {
  asm volatile("ldmatrix.sync.aligned.m8n8.x4.trans.shared.b16 {%0,%1,%2,%3}, [%4];" : "=r"(r0), "=r"(r1), "=r"(r2), "=r"(r3) : "r"(a) : "memory");
}
__device__ __forceinline__ void mma16(float* c, uint32_t a0, uint32_t a1, uint32_t a2, uint32_t a3, uint32_t b0, uint32_t b1) {
  asm("mma.sync.aligned.m16n8k16.row.col.f32.bf16.bf16.f32 {%0,%1,%2,%3}, {%4,%5,%6,%7}, {%8,%9}, {%0,%1,%2,%3};"
    : "+f"(c[0]), "+f"(c[1]), "+f"(c[2]), "+f"(c[3]) : "r"(a0), "r"(a1), "r"(a2), "r"(a3), "r"(b0), "r"(b1));
}
__device__ __forceinline__ void mma16z(float* d, const uint32_t* a, uint32_t b0, uint32_t b1) {
  asm("mma.sync.aligned.m16n8k16.row.col.f32.bf16.bf16.f32 {%0,%1,%2,%3}, {%4,%5,%6,%7}, {%8,%9}, {%10,%10,%10,%10};"
    : "=f"(d[0]), "=f"(d[1]), "=f"(d[2]), "=f"(d[3]) : "r"(a[0]), "r"(a[1]), "r"(a[2]), "r"(a[3]), "r"(b0), "r"(b1), "f"(0.f));
}
__device__ __forceinline__ void mma8(float* c, uint32_t a0, uint32_t a1, uint32_t b0) {
  asm("mma.sync.aligned.m16n8k8.row.col.f32.bf16.bf16.f32 {%0,%1,%2,%3}, {%4,%5}, {%6}, {%0,%1,%2,%3};"
    : "+f"(c[0]), "+f"(c[1]), "+f"(c[2]), "+f"(c[3]) : "r"(a0), "r"(a1), "r"(b0));
}
__device__ __forceinline__ uint32_t lane_id() { uint32_t l; asm volatile("mov.u32 %0, %%laneid;" : "=r"(l)); return l; }
__device__ __forceinline__ float quad_sum(float v) { v += __shfl_xor_sync(~0u, v, 1); v += __shfl_xor_sync(~0u, v, 2); return v; }
template <int N> __device__ __forceinline__ void pin(float (&d)[N]) {
#pragma unroll
  for (int i = 0; i < N; i++) asm volatile("" : "+f"(d[i]) :: "memory");
}
#define SPIN_GUARD(n) if (++(n) > SPIN_MAX) break

template <int NG> __device__ __forceinline__ void publish_stats(uint4* dst, const float* y, uint32_t tag, uint32_t lane) {
  float s0 = 0.f, s1 = 0.f;
#pragma unroll
  for (int g = 0; g < NG; g++) { s0 += y[4 * g] + y[4 * g + 1]; s1 += y[4 * g + 2] + y[4 * g + 3]; }
  s0 = quad_sum(s0); s1 = quad_sum(s1);
  const float m0 = s0 * (1.f / (8 * NG)), m1 = s1 * (1.f / (8 * NG));
  float q0 = 0.f, q1 = 0.f, q2 = 0.f, q3 = 0.f;
#pragma unroll
  for (int g = 0; g < NG; g++) {
    const float a = y[4 * g] - m0, b = y[4 * g + 1] - m0, c = y[4 * g + 2] - m1, d = y[4 * g + 3] - m1;
    q0 = fmaf(a, a, q0); q1 = fmaf(b, b, q1); q2 = fmaf(c, c, q2); q3 = fmaf(d, d, q3);
  }
  q0 = quad_sum(q0 + q1); q2 = quad_sum(q2 + q3);
  if ((lane & 3) == 0)
    stg4(dst, (__float_as_uint(s0) & ~1u) | tag, __float_as_uint(q0), __float_as_uint(s1), __float_as_uint(q2));
}

__device__ __forceinline__ void put4(uint4* p, const uint32_t* v) {
#pragma unroll
  for (int i = 0; i < 4; i++) stg4(p + i * 32, v[4 * i], v[4 * i + 1], v[4 * i + 2], v[4 * i + 3]);
}
__device__ __forceinline__ uint32_t row72(uint32_t k) { return k % 9 == 4 ? 32 + k / 9 : k - (k + 4) / 9; }
__device__ __forceinline__ void zero_share(uint4* slab, uint32_t j, uint32_t lane) {
  uint4* p = slab + j * 144 + lane;
#pragma unroll
  for (int i = 0; i < 4; i++) stg4(p + i * 32, 0u, 0u, 0u, 0u);
  if (lane < 16) stg4(p + 128, 0u, 0u, 0u, 0u);
}

struct Maps { CUtensorMap m[12]; };

struct Ring {
  uint32_t st, ph;
  __device__ __forceinline__ void next() { if (++st == NST) { st = 0; ph ^= 1; } }
};

#define GSTAMP(i) do {} while (0)
#define STAMP(i) do {} while (0)
#define ZSTAMP(m, i) do {} while (0)

__device__ __forceinline__ void tma_box(uint32_t dst, const CUtensorMap* m, int col, int row, uint32_t bar, uint32_t expect) {
  asm volatile("{\n.reg .pred e, h;\nelect.sync _|e, 0xffffffff;\nsetp.ne.and.u32 h, %5, 0, e;\n"
               "@h mbarrier.arrive.expect_tx.shared::cta.b64 _, [%2], %5;\n"
               "@e cp.async.bulk.tensor.2d.shared::cluster.global.mbarrier::complete_tx::bytes [%0], [%1, {%3, %4}], [%2];\n}"
               :: "r"(dst), "l"(m), "r"(bar), "r"(col), "r"(row), "r"(expect) : "memory");
}

__device__ __forceinline__ void bulk_load(uint32_t dst, const void* src, uint32_t bytes, uint32_t bar, bool arm) {
  asm volatile("{\n.reg .pred e, h;\nelect.sync _|e, 0xffffffff;\nsetp.ne.and.u32 h, %4, 0, e;\n"
               "@h mbarrier.arrive.expect_tx.shared::cta.b64 _, [%3], %2;\n"
               "@e cp.async.bulk.shared::cluster.global.mbarrier::complete_tx::bytes [%0], [%1], %2, [%3];\n}"
               :: "r"(dst), "l"(src), "r"(bytes), "r"(bar), "r"((uint32_t)arm) : "memory");
}

__global__ void __launch_bounds__(384, 1) mega_kernel(
    const __grid_constant__ Maps maps, uint4* __restrict__ scratch,
    __nv_bfloat16* __restrict__ out) {
  extern __shared__ __align__(1024) uint8_t smem[];
  const uint32_t sb = (uint32_t)__cvta_generic_to_shared(smem);
  const uint32_t full0 = sb + BARS, empty0 = full0 + 8 * NST, rem_full = empty0 + 8 * NST, park_free = rem_full + 8, kv_free = park_free + 8;
  const uint32_t c8_go = kv_free + 8, c8_done = c8_go + 8, c8_full = c8_done + 8, remo_full = c8_full + 8, piece_full = remo_full + 8, xb_done = piece_full + 8, res_full = xb_done + 8, pbar0 = res_full + 8;
  const uint32_t x_done = pbar0 + 64, x_ring = x_done + 8, xbar0 = x_ring + 8, redo_full = xbar0 + 72, att_done = redo_full + 16;
  const uint32_t side_full = att_done + 8;
  const uint32_t w = __shfl_sync(~0u, threadIdx.x >> 5, 0);
  uint32_t pair = blockIdx.x >> 1;
  if (gridDim.x == 132) {
    uint32_t smid;
    asm("mov.u32 %0, %%smid;" : "=r"(smid));
    const uint32_t tpc = smid >> 1;
    if (tpc == 60 || tpc == 61) { if (threadIdx.x == 0) { __nanosleep(20000); } return; }
    pair = tpc < 32 ? tpc : tpc >= 62 ? (tpc - 58) * 8 : 33 + (tpc - 32) / 7 * 8 + (tpc - 32) % 7;
  }
  const uint32_t rank = blockIdx.x & 1, t = (pair & 7) * 2 + rank, j = pair >> 3;
  const uint32_t sd = sb & 0x3ffff;
  const uint32_t odd = j & 1;
  const uint32_t scr = t * TILE;
  uint4* const scp = scratch + t * TILE;
  auto at = [&](uint32_t i) { return scratch + i; };
  auto at8 = [&](uint32_t i) { return (uint2*)scratch + i; };
  auto blk = [&](uint32_t kb) { return kb == 0 ? j : kb - (kb <= j); };
  const uint32_t xs = sb + (NST - 2) * STAGE;
  auto fetch_x = [&](uint32_t dst, uint32_t col, uint32_t bar, bool narrow) {
    asm volatile("{\n.reg .pred e;\nelect.sync _|e, 0xffffffff;\n@e mbarrier.arrive.expect_tx.shared::cta.b64 _, [%2], %5;\n"
                 "@e cp.async.bulk.tensor.3d.shared::cluster.global.mbarrier::complete_tx::bytes [%0], [%1, {%3, %4, 0}], [%2];\n}"
                 :: "r"(dst), "l"(&maps.m[narrow ? 11 : 7]), "r"(bar), "r"(col), "r"(64 * t), "r"(narrow ? 2048 : 16384) : "memory");
  };
  if (threadIdx.x == 256) {
    for (int i = 0; i < 9; i++) mbar_init(xbar0 + 8 * i, 1);
    mbar_init(piece_full, 1);
    asm volatile("fence.mbarrier_init.release.cluster;" ::: "memory");
  }
  if (threadIdx.x == 288) {
    for (int i = 0; i < NST; i++) { mbar_init(full0 + 8 * i, 1); mbar_init(empty0 + 8 * i, 16); }
    mbar_init(x_done, 8); mbar_init(x_ring, 16); mbar_init(redo_full, 1); mbar_init(redo_full + 8, 1); mbar_init(att_done, 4);
    mbar_init(side_full, 1); mbar_init(side_full + 8, 1); mbar_init(side_full + 48, 16); mbar_init(side_full + 56, 16);
    asm volatile("fence.mbarrier_init.release.cluster;" ::: "memory");
  }
  if (threadIdx.x == 320) {
    mbar_init(rem_full, 2); mbar_init(park_free, 8); mbar_init(kv_free, 8); mbar_init(c8_go, 8); mbar_init(c8_done, 2); mbar_init(c8_full, 1);
    mbar_init(remo_full, 64); mbar_init(xb_done, 8); mbar_init(res_full, 32);
    for (int i = 0; i < 8; i++) mbar_init(pbar0 + 8 * i, 4);
    asm volatile("fence.mbarrier_init.release.cluster;" ::: "memory");
  }
  if (threadIdx.x == 352) {
    asm volatile("prefetch.tensormap [%0];" :: "l"(&maps.m[7]) : "memory");
    asm volatile("prefetch.tensormap [%0];" :: "l"(&maps.m[0]) : "memory");
  }
  __syncwarp();
  asm volatile("barrier.cluster.arrive.relaxed.aligned;" ::: "memory");
  if (w != 8) asm volatile("barrier.cluster.wait.aligned;" ::: "memory");

  if (w >= 8) {
    asm volatile("setmaxnreg.dec.sync.aligned.u32 24;");
    if (w == 8) {
#pragma unroll 1
      for (uint32_t b = 0; b < 9; b++) fetch_x(xs + b * STAGE, 64 * b, xbar0 + 8 * b, false);
      tma_box(sb + PIECE, &maps.m[t >= 12 ? 6 : 5], 72 * j + (odd ? 0 : 64) + (t < 8 ? 576 * ((t >> 2) + 1) : 0), 144 * (t & 3), piece_full, 2304);
      asm volatile("barrier.cluster.wait.aligned;" ::: "memory");
      const uint32_t sb2 = __shfl_sync(~0u, sb, 0);
      uint32_t dst = sb2, bar = sb2 + BARS, ph = 1;
#pragma unroll 1
      for (int seg = 0; seg < 34; seg++) {
        const int n = seg >= 17 ? seg - 17 : seg;
        int ma, mb, ca, cb;
        if (n == 2) continue;
        if (n < 2) { ma = 0; mb = n; ca = 72 * j + 8 * odd + (n ? 0 : 576); cb = ca + (n ? 0 : 576); }
        else if (n < 12) { ma = 3; mb = 2; ca = cb = 576 * j + 64 * (n - 3); }
        else { ma = mb = 4; ca = n == 12 ? 512 : ((j + 2 * n) & 7) * 64; cb = ((j + 2 * n + 1) & 7) * 64; }
        const bool zip = n == 0 || n == 3, solo = n == 16;
#pragma unroll 1
        for (uint32_t st = 0; st < (solo ? 5 : 9); st++) {
          if (seg == 0 && st == NST - 2) mbar_wait(x_ring, 0);
          const uint32_t b = 2 * st + rank, kb = zip ? st : b >= 9 ? b - 9 : b;
          const bool second = zip ? rank : b >= 9;
          const int m = second ? mb : ma;
          const bool shared = kb == 8 && m > 0 && m < 4;
          const uint32_t ks = m == 4 ? 36 * j + 4 * kb : m == 0 ? 4 * blk(kb) : shared ? 0 : (9 * blk(kb) + 1) >> 1;
          const bool side = n == 1 && st >= 7;
          asm volatile("{\n.reg .pred p, e, f;\n.reg .u32 n;\nelect.sync _|e, 0xffffffff;\nsetp.ne.and.u32 f, %8, 0, e;\nmov.u32 n, 0;\n"
                       "W: mbarrier.try_wait.parity.shared::cta.b64 p, [%1+48], %2;\n@p bra D;\n"
                       "add.u32 n, n, 1;\nsetp.lt.u32 p, n, 4194304;\n@p bra W;\ntrap;\n"
                       "D: @e mbarrier.arrive.expect_tx.shared::cta.b64 _, [%1], %7;\n"
                       "@f cp.async.bulk.tensor.3d.shared::cluster.global.mbarrier::complete_tx::bytes.multicast::cluster [%0], [%3, {%4, %5, %6}], [%1], 3;\n}"
                       :: "r"((side ? sb2 + (st - 1) * STAGE : dst) + rank * 8192), "r"(side ? sb2 + (side_full - sb) + (st - 7) * 8 : bar), "r"(side ? seg >= 17 : ph), "l"(&maps.m[m + (shared ? 7 : 0)]), "r"(second ? cb : ca),
                          "r"(shared ? 64 : 0), "r"(ks), "r"(solo && st == 4 ? STAGE / 2 : STAGE), "r"((uint32_t)!(solo && b == 9)) : "memory");
          if (!side) { dst += STAGE; bar += 8; }
          if (dst == sb2 + NST * STAGE) { dst = sb2; bar -= 8 * NST; ph ^= 1; }
        }
      }
      {
#pragma unroll 1
        for (int i = 0; i < NST; i++) {
          mbar_wait_trap(bar + 48, ph);
          bar += 8;
          if (bar == full0 + 8 * NST) { bar = full0; ph ^= 1; }
        }
      }
    } else if (w == 9) {
      const uint32_t lane = lane_id();
      const uint32_t stg = sb + HSTG + lane * 16;
      uint32_t fph = 0;
#pragma unroll 1
      for (uint32_t layer = 0; layer < 2; layer++) {
        uint4* xb = scp + OFF_X + ((4 + layer) * 8 + j) * SLAB + 28 * 32;
        mbar_wait_sleep(c8_go, layer);
        int n = 0;
#pragma unroll 1
        while (true) {
          if (lane == 0) asm volatile("mbarrier.arrive.expect_tx.shared::cta.b64 _, [%0], 18432;" :: "r"(c8_full) : "memory");
          __syncwarp();
#pragma unroll 1
          for (uint32_t s = 0; s < 9; s++)
            bulk_load(sb + HSTG + s * 2048, s < 8 ? scp + OFF_P + (j + s * 8) * SLAB + 32 * 32 : xb, 2048, c8_full, false);
          mbar_wait(c8_full, fph); fph ^= 1;
          uint32_t bad = 0;
#pragma unroll 8
          for (int s = 0; s < 32; s++) { uint32_t v; asm volatile("ld.shared.b32 %0, [%1];" : "=r"(v) : "r"(stg + s * 512) : "memory"); bad |= v ^ (1 - layer); }
          if (__all_sync(~0u, (bad & 1u) == 0u)) break;
          __nanosleep(300);
          SPIN_GUARD(n);
        }
        asm volatile("bar.arrive 7, 96;" ::: "memory");
        float s0 = 0.f, s1 = 0.f;
#pragma unroll 1
        for (int g = 0; g < 8; g++) {
          const uint32_t a = stg + (g >> 1) * 512 + (g & 1) * 8;
          float a0 = 0.f, a1 = 0.f, a2 = 0.f, a3 = 0.f;
#pragma unroll 1
          for (int b = 0; b < 3; b++) {
            uint32_t v[6];
#pragma unroll
            for (int s = 0; s < 3; s++) lds2(a + (3 * b + s) * 2048, v + 2 * s);
#pragma unroll
            for (int s = 0; s < 3; s++) { a0 += bf_lo(v[2 * s]); a1 += bf_hi(v[2 * s]); a2 += bf_lo(v[2 * s + 1]); a3 += bf_hi(v[2 * s + 1]); }
          }
          sts1(a + 18432, pack_bf16(a0, a1)); sts1(a + 18436, pack_bf16(a2, a3));
          s0 += a0 + a1; s1 += a2 + a3;
        }
        __syncwarp();
        if (lane == 0) mbar_arrive(c8_done);
        s0 = quad_sum(s0); s1 = quad_sum(s1);
        float q0 = 0.f, q1 = 0.f;
        const uint32_t ln = lane_id();
#pragma unroll 1
        for (uint32_t i = 0; i < 4; i++) {
          uint32_t x[4];
          lds4(stg + 18432 + i * 512, x);
          uint4* z = xb + i * 32 + ln;
          asm volatile("" : "+l"(z));
          stg4(z, 0u, 0u, 0u, 0u);
          if (layer == 0) {
            stg4(z - (3 * 8 * SLAB - 128), nz(x[0]), x[1], nz(x[2]), x[3]);
#pragma unroll
            for (int e = 0; e < 4; e++) {
              const float m = (e & 1) ? s1 : s0, c = fmaf(m, -1.f / 64, bf_lo(x[e])), d = fmaf(m, -1.f / 64, bf_hi(x[e]));
              if (e & 1) q1 = fmaf(c, c, fmaf(d, d, q1)); else q0 = fmaf(c, c, fmaf(d, d, q0));
            }
          } else {
            uint32_t* o = (uint32_t*)(out + (128 * t + 32 * (j >> 1) + 2 * (ln >> 2) + (j & 1)) * 576 + 512 + 16 * i + 2 * (ln & 3));
            o[0] = x[0]; o[8 * 576] = x[1]; o[4] = x[2]; o[8 * 576 + 4] = x[3];
          }
        }
        if (layer == 0) {
          q0 = quad_sum(q0); q1 = quad_sum(q1);
          if ((ln & 3) == 0) stg4(scp + OFF_S + j * 96 + 64 + (ln >> 2), __float_as_uint(s0) | 1u, __float_as_uint(q0), __float_as_uint(s1), __float_as_uint(q1));
        }
      }
    } else {
      auto mark = [&](uint32_t k0, uint32_t v) {
        const uint32_t lane = lane_id();
#pragma unroll 1
        for (uint32_t k = k0; k < 6; k++) stg4(scp + OFF_S + (k * 4 + (lane >> 3)) * 96 + j * 8 + (lane & 7), k < 2 ? 0u : v, 0u, 0u, 0u);
      };
      if (w == 11) mark(2, 0u);
      auto phase2_duties = [&](uint32_t layer) {
        const uint32_t lane = lane_id();
        asm volatile("bar.sync 7, 96;" ::: "memory");
        if (w == 11) {
          if (layer == 0) mark(0, 1u);
          __syncwarp();
          if (lane == 0) mbar_arrive(c8_done);
        }
#pragma unroll 1
        for (uint32_t i = 0; i < 16; i++) {
          const uint32_t sl = (w - 10) * 4 + (i >> 2);
          bulk_load(sb + PARK + sl * 2048 + (i & 3) * 512, scp + OFF_X + ((4 + layer) * 8 + sl) * SLAB + row72(4 * j + (i & 3)) * 32, 512, res_full, true);
        }
        mbar_wait_sleep(res_full, layer);
#pragma unroll 1
        for (uint32_t i = 0; i < 16; i++) {
          stg4(scp + OFF_X + ((4 + layer) * 8 + (w - 10) * 4 + (i >> 2)) * SLAB + row72(4 * j + (i & 3)) * 32 + lane, 0u, 0u, 0u, 0u);
          if ((i & 3) == 3) __nanosleep(200);
        }
      };
      if (w == 10) {
        const uint32_t lane = lane_id();
        uint32_t* fl = (uint32_t*)(scratch + OFF_F + (t * 8 + j) * 8) + (lane & 15);
        uint32_t v;
        asm volatile("ld.relaxed.gpu.global.b32 %0, [%1];" : "=r"(v) : "l"(fl) : "memory");
        mbar_wait(piece_full, 0);
        asm volatile("{\n.reg .pred e;\nelect.sync _|e, 0xffffffff;\n@e cp.async.bulk.global.shared::cta.bulk_group [%0], [%1], 2304;\n}\n"
                     "cp.async.bulk.commit_group;\ncp.async.bulk.wait_group 0;\nfence.proxy.async;"
                     :: "l"(scratch + OFF_R + j * 2304 + t * 144), "r"(sb + PIECE) : "memory");
        __syncwarp();
        if (lane < 16) asm volatile("st.release.gpu.global.b32 [%0], 1;" :: "l"((uint32_t*)(scratch + OFF_F + (lane_id() * 8 + j) * 8) + t) : "memory");
        int n = 0;
#pragma unroll 1
        while (!__all_sync(~0u, v != 0u)) {
          __nanosleep(100);
          SPIN_GUARD(n);
          asm volatile("ld.relaxed.gpu.global.b32 %0, [%1];" : "=r"(v) : "l"(fl) : "memory");
        }
        asm volatile("st.relaxed.gpu.global.b32 [%0], 0;" :: "l"(fl) : "memory");
        mbar_wait(x_done, 0);
      }
#pragma unroll 1
      for (uint32_t layer = 0; layer < 3; layer++) {
        if (w == 10 && layer < 2) {
          if (layer) mbar_wait_sleep(park_free, 0);
          const uint4* img = scratch + OFF_R + j * 2304;
          if (lane_id() == 0) asm volatile("mbarrier.arrive.expect_tx.shared::cta.b64 _, [%0], 27648;\nmbarrier.arrive.expect_tx.shared::cta.b64 _, [%1], 9216;"
                                           :: "r"(rem_full), "r"(piece_full) : "memory");
          __syncwarp();
#pragma unroll 1
          for (uint32_t p = 0; p < 3; p++) {
            bulk_load(sb + REM + p * 9216, img + p * 576 + j * 64, 1024, rem_full, false);
            if (j) bulk_load(sb + REM + p * 9216 + 1024, img + p * 576, j * 1024, rem_full, false);
            bulk_load(sb + REM + p * 9216 + (j + 1) * 1024, img + p * 576 + (j + 1) * 64, (8 - j) * 1024, rem_full, false);
          }
#pragma unroll 1
          for (uint32_t i = 0; i < 12; i++)
            bulk_load(sb + REM + 27648 + (i < 8 ? i * 1024 : 6144 + i * 256), img + 1728 + (i < 8 ? (9 * blk(i) + 1) >> 1 : 9 * i - 68) * 16,
                      i < 8 ? 1024 : 256, piece_full, false);
          if (layer == 0) { fetch_x(sb + PARK + 2 * STAGE, 72 * j + 8 * odd, xbar0, false); fetch_x(sb + REM + 37888, 72 * j + (odd ? 0 : 64), xbar0 + 8, true); }
        }
        if (w == 11 && layer < 2) {
          if (layer) mbar_wait_sleep(park_free, 0);
          __syncwarp();
          if (lane_id() == 0) mbar_arrive(rem_full);
        }
        if (layer) phase2_duties(layer - 1);
        if (layer == 2) break;
        mbar_wait(kv_free, layer);
        if (t > 0) {
          const uint32_t lane = lane_id(), r = lane >> 2, q = lane & 3;
#pragma unroll 1
          for (uint32_t pc = 0; pc < 3; pc++) {
            uint4* hp = scp + OFF_H + ((layer * 8 + j) * 2 + (w - 10)) * 192 + pc * 64 + lane;
            uint32_t hl[8];
            int n = 0;
            hl[4] = 1u;
#pragma unroll 1
            while (true) {
              ldg4(hl, hp);
              if (pc < 2) ldg4(hl + 4, hp + 32);
              if (__all_sync(~0u, hl[0] != 0u && hl[4] != 0u)) break;
              __nanosleep(100);
              SPIN_GUARD(n);
            }
            const uint32_t dst = sb + KVS + (w - 10) * 10368 + r * 144 + q * 4;
            if (pc < 2) {
#pragma unroll
              for (int g = 0; g < 8; g++) sts1(dst + pc * 20736 + odd * 16 + g * 16, hl[g]);
              stg4(hp + 32, 0u, 0u, 0u, 0u);
            } else {
              sts1(dst + (odd ? 0 : 128), hl[0]); sts1(dst + 20736 + (odd ? 0 : 128), hl[1]);
            }
            stg4(hp, 0u, 0u, 0u, 0u);
          }
        }
        asm volatile("bar.arrive 1, 192;" ::: "memory");
        mbar_wait(rem_full, layer);
        mbar_wait(piece_full, 1 - layer);
#pragma unroll 1
        for (uint32_t b = 0; b < 5; b++) {
          const uint32_t blk = sb + REM + 27648 + b * 2048, k = (w - 10) * 32 + lane_id(), rr = k & 7;
          const uint32_t dst = blk + ((k >> 3) & 1) * 1024 + rr * 128 + (((k >> 4) ^ rr) << 4);
          uint32_t v[8];
          lds4(blk + k * 16, v); lds4(blk + 1024 + k * 16, v + 4);
          asm volatile("bar.sync 3, 64;" ::: "memory");
          sts4(dst, v); sts4(dst ^ 64, v + 4);
        }
        asm volatile("fence.proxy.async.shared::cta;" ::: "memory");
        mbar_arrive(remo_full);
        mbar_wait_sleep(xb_done, layer);
        if (w == 10 && layer == 1) {
          const uint32_t lane = lane_id();
          stg4(scp + OFF_S + (lane >> 3) * 96 + j * 8 + (lane & 7), 0u, 0u, 0u, 0u);
          stg4(scp + OFF_S + (4 + (lane >> 3)) * 96 + j * 8 + (lane & 7), 0u, 0u, 0u, 0u);
          if (lane < 8) stg4(scp + OFF_S + j * 96 + 64 + lane, 0u, 0u, 0u, 0u);
        }
#pragma unroll 1
        for (uint32_t i = 0; i < 8 && (w == 11 || layer == 1); i++) {
          zero_share(scp + OFF_X + ((w - 10) * 16 + layer * 8 + i) * SLAB, j, lane_id());
          __nanosleep(500);
        }
      }
    }
  } else {
    asm volatile("setmaxnreg.inc.sync.aligned.u32 240;");
    const bool lead = lane_id() == 0;
    Ring rg{0, 0};
    uint32_t prev = 0;
    uint32_t X[144];
    float rs0, rs1;
    const bool lead2 = lane_id() < 2;
    uint32_t empty_at;
    asm volatile("mapa.shared::cluster.u32 %0, %1, %2;" : "=r"(empty_at) : "r"(empty0), "r"(lane_id() & 1));
    auto release = [&](uint32_t st) { if (lead2) asm volatile("mbarrier.arrive.shared::cluster.b64 _, [%0];" :: "r"(empty_at + st * 8) : "memory"); };
    auto load_kb = [&](int kb, const uint4* src, const char* lo, uint32_t hoff) {
      const uint4* p;
      asm("{\n.reg .pred p;\n.reg .u64 t;\nsetp.ge.u32 p, %2, %3;\nadd.u64 t, %1, -2048;\nselp.b64 %0, t, %1, p;\n}" : "=l"(p) : "l"(src), "r"(j), "r"(kb));
#pragma unroll
      for (int i = 0; i < 4; i++) {
        if (kb == 8) { ldg2(X + 128 + 4 * i, lo + (32 + i) * 512); ldg2(X + 130 + 4 * i, lo + hoff + (32 + i) * 512); }
        else ldg4(X + 16 * kb + 4 * i, p + kb * 128 + i * 32);
      }
    };
    auto check_kb = [&](bool skip, int kb, const uint4* src, const char* lo, uint32_t hoff) {
      int n = 0;
#pragma unroll 1
      while (true) {
        uint32_t m = umin2(umin2(X[16 * kb], X[16 * kb + 4]), umin2(X[16 * kb + 8], X[16 * kb + 12]));
        if (kb == 8) m = umin2(m, umin2(umin2(X[130], X[134]), umin2(X[138], X[142])));
        if (__all_sync(~0u, m != 0u || skip)) break;
        SPIN_GUARD(n);
        load_kb(kb, src, lo, hoff);
      }
    };
#pragma unroll
    for (int i = 0; i < 16; i++) X[i] = 0u;
#pragma unroll 1
    for (uint32_t hf = 0; hf < 4; hf++) {
      const uint32_t layer = hf >> 1;
      const bool ffn = hf & 1;
      const uint32_t tag = 1 - layer;
      const uint32_t xbase = scr + OFF_X + (layer * 8 + w) * SLAB;
      float aA[32], aB[32];
      {
        const uint32_t lane = lane_id(), r = lane >> 2, q = lane & 3;
        const uint4* src = at(xbase + (ffn ? 32 * SLAB : 0) + lane);
        const char* lo = (const char*)at8(2 * (xbase + (ffn ? 32 * SLAB : 0)) + (ffn ? lane : 2 * lane));
        const uint32_t hoff = ffn ? 256 : 8;
        const uint32_t xoff = (w & 1) * 8192 + (16 * (w >> 1) + (lane & 15)) * 128 + (((lane >> 4) ^ (lane & 7)) << 4);
        auto load_x = [&](uint32_t b, uint32_t* d) {
#pragma unroll
          for (int i = 0; i < 4; i++) ldsm4(xs + b * STAGE + (xoff ^ (32 * i)), d[4 * i], d[4 * i + 1], d[4 * i + 2], d[4 * i + 3]);
        };
        auto load_any = [&](int kb) { if (hf == 0) load_x(blk(kb), X + 16 * kb); else load_kb(kb, src, lo, hoff); };
        float m0, m1, v0, v1;
        STAMP(ffn * 16 + 0);
        if (hf == 0) {
          float sum[2][4] = {}, sq0[4][4] = {}, sq1[4][4] = {};
          uint32_t p0, p1;
          mbar_wait(xbar0, 0);
          ldsm4(xs + xoff, p0, p1, X[0], X[1]);
          p0 = __byte_perm(__shfl_sync(~0u, p0, lane & 28), 0, 0x1010); p1 = __byte_perm(__shfl_sync(~0u, p1, lane & 28), 0, 0x1010);
#pragma unroll 3
          for (uint32_t b = 0; b < 9; b++) {
            uint32_t d[16];
            mbar_wait(xbar0 + 8 * b, 0);
            load_x(b, d);
#pragma unroll
            for (int i = 0; i < 16; i++) d[i] = sub_bf16x2(d[i], (i & 1) ? p1 : p0);
#pragma unroll
            for (int g = 0; g < 8; g++) {
              if (!(g & 1)) mma16(sum[(g >> 1) & 1], d[2 * g], d[2 * g + 1], d[2 * g + 2], d[2 * g + 3], 0x3f803f80u, 0x3f803f80u);
              mma8(sq0[g & 3], d[2 * g], d[2 * g + 1], d[2 * g]); mma8(sq1[g & 3], d[2 * g], d[2 * g + 1], d[2 * g + 1]);
            }
          }
          STAMP(1);
          GSTAMP(14);
#pragma unroll
          for (int kb = 0; kb < GD; kb++) load_x(blk(kb), X + 16 * kb);
          release((x_ring - empty0) / 8);
          auto tot = [](float (&c)[4][4], int e) { return (c[0][e] + c[1][e]) + (c[2][e] + c[3][e]); };
          const float a0 = (sum[0][0] + sum[1][0]) * (1.f / 576), a1 = (sum[0][2] + sum[1][2]) * (1.f / 576);
          const uint32_t dg = (lane & 28) + (r >> 1);
          v0 = fmaxf(fmaf(__shfl_sync(~0u, (r & 1) ? tot(sq0, 1) : tot(sq0, 0), dg), 1.f / 576, -a0 * a0), 0.f);
          v1 = fmaxf(fmaf(__shfl_sync(~0u, (r & 1) ? tot(sq1, 3) : tot(sq1, 2), dg), 1.f / 576, -a1 * a1), 0.f);
          m0 = bf_lo(p0) + a0; m1 = bf_lo(p1) + a1;
        } else {
          uint32_t s[3][4];
          const uint4* p = at(scr + OFF_S + ((ffn ? 16 : 0) + w) * 96 + q * 8 + r);
          const bool third = !ffn && q == 0;
          const uint32_t rdy = ffn ? tag : 1u;
          int n = 0;
          s[2][0] = rdy; s[2][1] = s[2][2] = s[2][3] = 0u;
#pragma unroll 1
          while (true) {
            ldg4(s[0], p); ldg4(s[1], p + 32);
            if (third) ldg4(s[2], p + 64);
            if (__all_sync(~0u, ((diff2(s[0][0], s[1][0], rdy) | diff2(s[1][0], s[2][0], rdy)) & 1u) == 0u)) break;
            SPIN_GUARD(n);
          }
          STAMP(ffn * 16 + 1);
          ZSTAMP(1 + ffn, 0);
          GSTAMP(14 + ffn);
#pragma unroll
          for (int kb = 1; kb < GD; kb++) load_kb(kb, src, lo, hoff);
          float t0 = 0.f, t1 = 0.f;
#pragma unroll
          for (int i = 0; i < 3; i++) { t0 += __uint_as_float(s[i][0]); t1 += __uint_as_float(s[i][2]); }
          m0 = quad_sum(t0) * (1.f / 576); m1 = quad_sum(t1) * (1.f / 576);
          const float cnt = ffn ? 72.f : 64.f, inv = ffn ? 1.f / 72 : 1.f / 64;
          v0 = 0.f; v1 = 0.f;
#pragma unroll
          for (int i = 0; i < 3; i++) {
            const float c = (i < 2 || third) ? cnt : 0.f;
            const float d0 = fmaf(__uint_as_float(s[i][0]), inv, -m0), d1 = fmaf(__uint_as_float(s[i][2]), inv, -m1);
            v0 += fmaf(d0 * d0, c, __uint_as_float(s[i][1])); v1 += fmaf(d1 * d1, c, __uint_as_float(s[i][3]));
          }
          v0 = quad_sum(v0) * (1.f / 576); v1 = quad_sum(v1) * (1.f / 576);
        }
        rs0 = rsqrtf(v0 + 1e-5f); rs1 = rsqrtf(v1 + 1e-5f);
        const uint32_t mean0 = pack_bf16(m0, m0), mean1 = pack_bf16(m1, m1);
#pragma unroll
        for (int kb = 0; kb < 9; kb++) {
          if (kb > 0) check_kb(hf == 0, kb, src, lo, hoff);
          if (kb + GD < 9) load_any(kb + GD);
          if (kb + GD == 8 && hf == 0 && lead) mbar_arrive(x_done);
#pragma unroll
          for (int i = 16 * kb; i < 16 * kb + 16; i++) X[i] = sub_bf16x2(X[i], (i & 1) ? mean1 : mean0);
          ZSTAMP(1 + ffn, 1 + 3 * kb);
          mbar_wait(full0 + rg.st * 8, rg.ph);
          ZSTAMP(1 + ffn, 2 + 3 * kb);
          const uint64_t desc = DESC_HI | ((sd + rg.st * STAGE) >> 4);
          wg_fence();
#pragma unroll
          for (int i = 0; i < 4; i++) wgmma_rs_n64(aA, X + 4 * (4 * kb + i), desc + i * 128, kb + i != 0);
          if (kb == 8) { wg_commit(); wg_wait<1>(); wg_fence(); }
#pragma unroll
          for (int i = 0; i < 4; i++) wgmma_rs_n64(aB, X + 4 * (4 * kb + i), desc + 512 + i * 128, kb + i != 0);
          wg_commit();
          wg_wait<1>();
          ZSTAMP(1 + ffn, 3 + 3 * kb);
          if (kb > 0) release(prev);
          prev = rg.st; rg.next();
        }
        ZSTAMP(1 + ffn, 28);
        ZSTAMP(4, 0);
        STAMP(ffn * 16 + 2);
      }
      if (!ffn) {
      const uint32_t lane = lane_id(), r = lane >> 2, q = lane & 3;
      const uint32_t kvrow = sb + KVS + (w & 1) * 10368 + (16 * (w >> 1)) * 144;
      uint32_t Q[18], Km[3][8], Ke[3][4];
      const bool edge = (t == 0 && w < 2);
      const uint32_t row0 = edge ? sb + KVS + 8 * 144 : kvrow + (lane & 7) * 144, row1 = kvrow + (8 + (lane & 7)) * 144;
      {
        const uint32_t dst = kvrow + (8 + r) * 144 + q * 4 + odd * 16, dstr = dst + (odd ? -16 : 128);
        const bool edge_out = w >= 6 && t < 15;
        uint4* const hp = at(scr + TILE + OFF_H + ((layer * 8 + j) * 2 + (w & 1)) * 192 + lane);
        auto put_kv = [&](float (&a)[32], int part, int half) {
          uint32_t hl[4];
#pragma unroll
          for (int i = 0; i < 16; i++) asm volatile("" : "+f"(a[16 * half + i]) :: "memory");
#pragma unroll
          for (int i = 0; i < 4; i++) {
            const int g = 4 * half + i;
            hl[i] = pack_bf16(a[4 * g + 2] * rs1, a[4 * g + 3] * rs1);
            sts1(dst + part * 20736 + g * 16, pack_bf16(a[4 * g] * rs0, a[4 * g + 1] * rs0)); sts1(dst + part * 20736 + 8 * 144 + g * 16, hl[i]);
          }
          if (edge_out) stg4(hp + part * 64 + half * 32, nz(hl[0]), hl[1], hl[2], hl[3]);
        };
        put_kv(aA, 0, 0); put_kv(aA, 0, 1);
        if (lead) mbar_arrive(kv_free);
        wg_wait<0>();
        release(prev);
        release((side_full + 48 - empty0) / 8); release((side_full + 56 - empty0) / 8);
        float aR[12];
        mbar_wait(rem_full, layer);
        const uint64_t dr = DESC_REM | ((sd + REM) >> 4);
        wg_fence();
#pragma unroll
        for (int s = 0; s < 36; s++) {
          wgmma_rs_n24(aR, X + 4 * s, dr + s * 16, s != 0);
          if (s == 4) put_kv(aB, 1, 0);
          if (s == 16) put_kv(aB, 1, 1);
        }
        wg_commit();
#pragma unroll
        for (int kb = 0; kb < 9; kb++) {
          if (!(kb & 1)) mbar_wait(full0 + rg.st * 8, rg.ph);
          const uint64_t desc = DESC_HI | ((sd + rg.st * STAGE + (kb & 1) * 8192) >> 4);
          wg_fence();
#pragma unroll
          for (int i = 0; i < 4; i++) wgmma_rs_n64(aB, X + 4 * (4 * kb + i), desc + i * 128, kb + i != 0);
          wg_commit();
          wg_wait<1>();
          if (kb > 0 && !(kb & 1)) release(prev);
          if (kb & 1) { prev = rg.st; rg.next(); }
          if (kb == 0) {
            pin(aR);
            const uint32_t k1 = pack_bf16(aR[2] * rs1, aR[3] * rs1), v1 = pack_bf16(aR[6] * rs1, aR[7] * rs1);
            if (edge_out) stg4(hp + 128, nz(k1), v1, 0u, 0u);
            sts1(dstr, pack_bf16(aR[0] * rs0, aR[1] * rs0)); sts1(dstr + 8 * 144, k1);
            sts1(dstr + 20736, pack_bf16(aR[4] * rs0, aR[5] * rs0)); sts1(dstr + 20736 + 8 * 144, v1);
            Q[16] = pack_bf16(aR[8], aR[9]); Q[17] = pack_bf16(aR[10], aR[11]);
            if (w < 4) asm volatile("bar.arrive 2, 256;" ::: "memory");
          }
          if (kb == 8) {
            if (w < 4) asm volatile("bar.sync 1, 192;" ::: "memory");
            else asm volatile("bar.sync 2, 256;" ::: "memory");
#pragma unroll
            for (int nt = 0; nt < 3; nt++) {
              const uint32_t ra = (nt == 0 ? row0 : row1 + (nt - 1) * 8 * 144);
              ldsm4(ra + odd * 16 + (lane >> 3) * 16, Km[nt][0], Km[nt][1], Km[nt][2], Km[nt][3]);
              ldsm4(ra + odd * 16 + 64 + (lane >> 3) * 16, Km[nt][4], Km[nt][5], Km[nt][6], Km[nt][7]);
              ldsm4(ra + (odd ? 0 : 32) + (lane >> 3) * 32, Ke[nt][0], Ke[nt][1], Ke[nt][2], Ke[nt][3]);
            }
          }
        }
        wg_wait<0>();
        pin(aB);
        mbar_wait(att_done, layer ^ (w >> 2));
        STAMP(3);
#pragma unroll
        for (int i = 0; i < 16; i++) Q[i] = pack_bf16(aB[2 * i], aB[2 * i + 1]);
      }
      uint32_t res[18] = {};
      if (layer) {
        const uint4* p = at(xbase + ((9 * j + 1) >> 1) * 32 + lane);
#pragma unroll
        for (int i = 0; i < 4; i++) ldg4(res + 4 * i, p + i * 32);
        ldg2(res + 16, at8(2 * (xbase + (9 * (j >> 1) + 4) * 32 + lane) + odd));
      }
      {
        uint32_t V01[12][2], V2[12];
        const uint32_t rv = ((lane & 8) ? row1 : row0) + 20736, rw = row1 + 8 * 144 + 20736;
#pragma unroll
        for (int i = 0; i < 4; i++) ldsm4t(rv + odd * 16 + i * 32 + (lane >> 4) * 16, V01[2 * i][0], V01[2 * i][1], V01[2 * i + 1][0], V01[2 * i + 1][1]);
#pragma unroll
        for (int i = 0; i < 2; i++) ldsm4t(rv + (odd ? 0 : 32) + i * 64 + (lane >> 4) * 32, V01[8 + 2 * i][0], V01[8 + 2 * i][1], V01[9 + 2 * i][0], V01[9 + 2 * i][1]);
        ldsm4t(rw + odd * 16 + (lane >> 3) * 16, V2[0], V2[1], V2[2], V2[3]);
        ldsm4t(rw + odd * 16 + 64 + (lane >> 3) * 16, V2[4], V2[5], V2[6], V2[7]);
        ldsm4t(rw + (odd ? 0 : 32) + (lane >> 3) * 32, V2[8], V2[9], V2[10], V2[11]);
        const bool up0 = 2 * q > r, up1 = 2 * q + 1 > r;
        const uint32_t upm = (up0 ? 0xffffu : 0u) | (up1 ? 0xffff0000u : 0u);
        const float c0 = 0.23570226039551584f * 1.4426950408889634f * rs0, c1 = 0.23570226039551584f * 1.4426950408889634f * rs1;
        const float masked = -1e9f * 1.4426950408889634f * rcp(c0);
        const int qe = odd ? 9 : q, qo = odd ? q : -1;
        uint32_t Qe[8];
#pragma unroll
        for (int h = 0; h < 4; h++)
#pragma unroll
          for (int e = 0; e < 2; e++) Qe[2 * h + e] = qe <= h ? Q[4 * h + 4 + e] : qo >= h ? Q[(4 * h + 16 + e) % 18] : 0u;
#pragma unroll
        for (int h = 1; h < 4; h++)
#pragma unroll
          for (int e = 0; e < 2; e++) { if (qe < h) Q[4 * h + e] = 0u; if (qo >= h) Q[4 * h - 2 + e] = 0u; }
        uint32_t Om[16], Oe[8];
        uint4* const po = at(xbase + 16 * SLAB + 4 * j * 32 + lane);
        float sv[4][4], mx[4][2];
#pragma unroll
        for (int h = 0; h < 4; h++) {
          float S[3][4];
#pragma unroll
          for (int nt = 0; nt < 3; nt++) {
            mma16z(S[nt], Q + 4 * h, Km[nt][2 * h], Km[nt][2 * h + 1]);
            mma8(S[nt], Qe[2 * h], Qe[2 * h + 1], Ke[nt][h]);
          }
          if (edge) S[0][0] = S[0][1] = masked;
          sv[h][0] = up0 ? S[0][0] : S[1][0]; sv[h][1] = up1 ? S[0][1] : S[1][1];
          sv[h][2] = up0 ? S[1][2] : S[2][2]; sv[h][3] = up1 ? S[1][3] : S[2][3];
        }
        auto quad8 = [&](auto&& op) {
#pragma unroll
          for (int d = 1; d < 3; d++) {
            float o[8];
#pragma unroll
            for (int i = 0; i < 8; i++) o[i] = __shfl_xor_sync(~0u, mx[i >> 1][i & 1], d);
#pragma unroll
            for (int i = 0; i < 8; i++) mx[i >> 1][i & 1] = op(mx[i >> 1][i & 1], o[i]);
          }
        };
#pragma unroll
        for (int i = 0; i < 8; i++) mx[i >> 1][i & 1] = fmaxf(sv[i >> 1][2 * (i & 1)], sv[i >> 1][2 * (i & 1) + 1]);
        quad8([](float x, float y) { return fmaxf(x, y); });
#pragma unroll
        for (int i = 0; i < 8; i++) {
          const float c = (i & 1) ? c1 : c0, m = mx[i >> 1][i & 1] * c;
          float* p = sv[i >> 1] + 2 * (i & 1);
          p[0] = ex2(fmaf(p[0], c, -m)); p[1] = ex2(fmaf(p[1], c, -m));
          mx[i >> 1][i & 1] = p[0] + p[1];
        }
        if (w >= 4 && lead) mbar_arrive(att_done + ((__float_as_uint(mx[0][0]) | __float_as_uint(mx[3][1])) & (rg.ph >> 1)));
        quad8([](float x, float y) { return x + y; });
        auto u = [&](int i) { return __float_as_uint(mx[i >> 1][i & 1]); };
        const uint32_t none = or3(or3(u(0), u(1), u(2)), or3(u(3), u(4), u(5)), u(6) | u(7)) & (rg.ph >> 1);
#pragma unroll
        for (int h = 0; h < 4; h++) {
          const float i0 = rcp(mx[h][0]), i1 = rcp(mx[h][1]);
          const uint32_t p0 = pack_bf16(sv[h][0] * i0, sv[h][1] * i0), p1 = pack_bf16(sv[h][2] * i1, sv[h][3] * i1);
          const uint32_t pf[6] = {p0 & upm, p0 & none, p0 & ~upm, p1 & upm, p1 & none, p1 & ~upm};
#pragma unroll
          for (int gi = 0; gi < 3; gi++) {
            const int g = gi < 2 ? 2 * h + gi : 8 + h;
            float o[4];
            mma16z(o, pf, V01[g][0], V01[g][1]);
            mma8(o, pf[4], pf[5], V2[g]);
            uint32_t* d = gi < 2 ? Om + 2 * g : Oe + 2 * h;
            d[0] = pack_bf16(o[0], o[1]); d[1] = pack_bf16(o[2], o[3]);
          }
          if (h > 0) {
#pragma unroll
            for (int e = 0; e < 2; e++) {
              if (qe < h) Om[4 * h + e] = Oe[2 * h - 2 + e];
              if (qo >= h) Om[4 * h - 2 + e] = Oe[2 * h + e];
            }
            Om[4 * h - 4] = nz(Om[4 * h - 4]);
            stg4(po + (h - 1) * 32, Om[4 * h - 4], Om[4 * h - 3], Om[4 * h - 2], Om[4 * h - 1]);
          }
        }
        STAMP(4);
        Om[12] = nz(Om[12]);
        stg4(po + 96, Om[12], Om[13], Om[14], Om[15]);
        stg2(at8(2 * (xbase + 16 * SLAB + 1024 + j * 16) + lane), nz(odd ? Oe[0] : Oe[6]), odd ? Oe[1] : Oe[7]);
#pragma unroll
        for (int i = 0; i < 16; i++) X[i] = Om[i];
      }
      if (lane == 0) asm volatile("st.relaxed.gpu.global.b32 [%0], %1;" :: "l"(at(scr + OFF_S + (8 + w) * 96 + j * 8)), "r"(tag) : "memory");
      {
        if (layer == 0) {
          const uint32_t xrow = (w & 1) * 8192 + (16 * (w >> 1) + (lane & 15)) * 128;
          uint32_t u0, u1;
          mbar_wait(xbar0, 1); mbar_wait(xbar0 + 8, 1);
#pragma unroll
          for (int i = 0; i < 4; i++)
            ldsm4(sb + PARK + 2 * STAGE + xrow + (((2 * i + (lane >> 4)) ^ (lane & 7)) << 4), res[4 * i], res[4 * i + 1], res[4 * i + 2], res[4 * i + 3]);
          ldsm4(sb + REM + 37888 + (xrow >> 3), res[16], res[17], u0, u1);
        }
        const uint4* src = at(xbase + 16 * SLAB + lane);
        const uint32_t st0 = rg.st;
        auto stage_of = [&](uint32_t i) { const uint32_t x = st0 + i; return i >= 3 ? NST - 3 + i : x >= NST ? x - NST : x; };
        {
          const uint32_t x = st0 + lane, wrap = x >= NST;
          mbar_wait(lane < 3 ? full0 + (x - wrap * NST) * 8 : lane < 5 ? side_full - 24 + lane * 8 : remo_full, lane < 3 ? rg.ph ^ wrap : layer);
          __syncwarp();
          if (st0 >= 3) { rg.st = st0 - 3; rg.ph ^= 1; } else rg.st = st0 + 3;
        }
        float acc[36];
        auto block72 = [&](uint32_t kb, uint32_t base, const uint32_t* a) {
          const uint64_t d0 = DESC_HI | ((base >> 4) + (((sd + REM + 27648 + (kb >> 1) * 2048 + (kb & 1) * 64 - base) >> 4) << 16));
          wg_fence();
#pragma unroll
          for (int i = 0; i < 4; i++) wgmma_rs_n72(acc, a + 4 * i, d0 - (uint64_t)(i * ((127u << 16) - 128u)), 1);
          wg_commit();
        };
#pragma unroll
        for (int i = 0; i < 18; i++) { acc[2 * i] = bf_lo(res[i]); acc[2 * i + 1] = bf_hi(res[i]); }
        block72(0, sd + st0 * STAGE + 8192, X);
        {
          const uint4* fp = at(scr + OFF_S + (8 + w) * 96 + (lane & 7) * 8);
          int n = 0;
          STAMP(8);
#pragma unroll 1
          while (true) {
            uint32_t f;
            asm volatile("ld.relaxed.gpu.global.b32 %0, [%1];" : "=r"(f) : "l"(fp) : "memory");
            if (__all_sync(~0u, f == tag)) break;
            SPIN_GUARD(n);
          }
          wg_wait<0>(); release(st0);
          STAMP(9);
        }
#pragma unroll
        for (int kb = 1; kb < GO; kb++) load_kb(kb, src, (const char*)src - lane * 8, 256);
        __syncwarp();
        uint32_t m = ~0u;
#pragma unroll
        for (int kb = 1; kb < 9; kb++) {
          m = umin2(m, umin2(umin2(X[16 * kb], X[16 * kb + 4]), umin2(X[16 * kb + 8], X[16 * kb + 12])));
          if (kb == 8) m = umin2(m, umin2(umin2(X[130], X[134]), umin2(X[138], X[142])));
          if (kb + GO - 1 < 9) {
            const uint4* s2 = src + (m == 0u);
            load_kb(kb + GO - 1, s2, (const char*)s2 - lane * 8, 256);
            __syncwarp();
          }
          block72(kb, sd + stage_of((kb + 1) >> 1) * STAGE + (~kb & 1) * 8192, X + 16 * kb);
          if (kb == 3 || kb == 5) { wg_wait<1>(); release(stage_of(kb >> 1)); }
        }
        uint32_t redo;
        asm volatile("{\n.reg .pred p;\nsetp.eq.u32 p, %1, 0;\nbar.red.or.pred p, %2, 128, p;\nselp.u32 %0, 1, 0, p;\n}" : "=r"(redo) : "r"(m), "r"(5 + (w >> 2)) : "memory");
        wg_wait<0>();
        pin(acc);
        if (__any_sync(~0u, redo || FORCE_REDO)) {
#pragma unroll
          for (int i = 0; i < 18; i++) { res[i] = __shfl_sync(~0u, res[i], lane); acc[2 * i] = bf_lo(res[i]); acc[2 * i + 1] = bf_hi(res[i]); }
          const uint32_t box = REM + (w >> 2) * 8192, bar = redo_full + (w >> 2) * 8;
#pragma unroll 1
          for (uint32_t kb = 0; kb < 10; kb++) {
            asm volatile("bar.sync %0, 128;" :: "r"(5 + (w >> 2)) : "memory");
            if ((w & 3) == 0)
              asm volatile("{\n.reg .pred e;\nelect.sync _|e, 0xffffffff;\n@e mbarrier.arrive.expect_tx.shared::cta.b64 _, [%2], 8192;\n"
                           "@e cp.async.bulk.tensor.3d.shared::cluster.global.mbarrier::complete_tx::bytes [%0], [%1, {%3, %4, %5}], [%2];\n}"
                           :: "r"(sb + box), "l"(&maps.m[kb >= 8 ? 8 : 1]), "r"(bar), "r"(72 * j + 8 * odd), "r"(kb >= 8 ? 64 : 0),
                              "r"(kb >= 8 ? 0 : (9 * blk(kb) + 1) >> 1) : "memory");
            mbar_wait(bar, kb & 1);
            if (kb == 9) break;
            int n = 0;
#pragma unroll 1
            while (true) {
              const char* l = (const char*)(src + blk(kb) * 128) - (kb == 8 ? lane * 8 : 0);
#pragma unroll
              for (int i = 0; i < 4; i++) ldg2(X + 4 * i, l + i * 512);
              uint32_t mm = umin2(umin2(X[0], X[4]), umin2(X[8], X[12]));
              l += (kb == 8 ? 256 : 8) + (mm == 0u ? 16 : 0);
#pragma unroll
              for (int i = 0; i < 4; i++) ldg2(X + 4 * i + 2, l + i * 512);
              if (kb == 8) mm = umin2(mm, umin2(umin2(X[2], X[6]), umin2(X[10], X[14])));
              if (__all_sync(~0u, mm != 0u)) break;
              SPIN_GUARD(n);
            }
            block72(kb, sd + box, X);
            wg_wait<0>();
            pin(acc);
          }
        }
        STAMP(10);
#pragma unroll
        for (int i = 0; i < 18; i++) { res[i] = pack_bf16(acc[2 * i], acc[2 * i + 1]); if (!(i & 3)) res[i] = nz(res[i]); }
        auto put = [&] {
          put4(at(xbase + 32 * SLAB + 4 * j * 32 + lane), res);
          stg2(at8(2 * (xbase + 32 * SLAB + 1024 + j * 16) + lane), res[16], res[17]);
        };
        if (j < PRI) put();
        publish_stats<9>(at(scr + OFF_S + (16 + w) * 96 + j * 8 + r), acc, tag, lane);
        if (j >= PRI) put();
#pragma unroll
        for (int i = 0; i < 16; i++) X[i] = res[i];
      }
      continue;
      }
      const uint32_t hp = sb + PARK + w * 512 + lane_id() * 16;
      auto pack8 = [&](float (&a)[32], int p, uint32_t* o) {
#pragma unroll
        for (int e = 0; e < 8; e++) asm volatile("" : "+f"(a[8 * p + e]) :: "memory");
#pragma unroll
        for (int e = 0; e < 4; e++) o[e] = pack_bf16(a[8 * p + 2 * e], a[8 * p + 2 * e + 1]);
      };
      const float ka0 = 0.7978845608028654f * rs0, kb0 = 0.044715f * ka0 * rs0 * rs0, ku0 = 0.5f * rs0 * rs0;
      const float ka1 = 0.7978845608028654f * rs1, kb1 = 0.044715f * ka1 * rs1 * rs1, ku1 = 0.5f * rs1 * rs1;
      auto packu8 = [&](int p, uint32_t* o) {
#pragma unroll
        for (int e = 0; e < 8; e++) asm volatile("" : "+f"(aA[8 * p + e]) :: "memory");
#pragma unroll
        for (int e = 0; e < 4; e++) o[e] = pack_bf16(aA[8 * p + 2 * e] * ((e & 1) ? ku1 : ku0), aA[8 * p + 2 * e + 1] * ((e & 1) ? ku1 : ku0));
      };
      auto geglu8 = [&](int p, uint32_t* u) {
#pragma unroll
        for (int e = 0; e < 8; e++) asm volatile("" : "+f"(aB[8 * p + e]) :: "memory");
        float h[8];
#pragma unroll
        for (int e = 0; e < 8; e++) {
          const float g = aB[8 * p + e];
          h[e] = fmaf(g, tanh_ap(g * fmaf(g * g, (e & 2) ? kb1 : kb0, (e & 2) ? ka1 : ka0)), g);
        }
#pragma unroll
        for (int e = 0; e < 4; e++) u[e] = mul_bf16x2(pack_bf16(h[2 * e], h[2 * e + 1]), u[e]);
      };
      uint32_t ready = 0;
      auto box = [&](int b, auto&& filler) {
        const int kb = b < 9 ? b : b - 9;
        if (b == 0) mbar_wait_trap(full0 + rg.st * 8, rg.ph);
        else if (!(b & 1)) mbar_wait_unless(ready, full0 + rg.st * 8, rg.ph);
        const uint64_t desc = DESC_HI | ((sd + rg.st * STAGE + (b & 1) * 8192) >> 4);
        if (b & 1) { prev = rg.st; rg.next(); }
        wg_fence();
#pragma unroll
        for (int i = 0; i < 4; i++) {
          if (b < 9) wgmma_rs_n64(aA, X + 4 * (4 * kb + i), desc + i * 128, kb + i != 0);
          else wgmma_rs_n64(aB, X + 4 * (4 * kb + i), desc + i * 128, kb + i != 0);
          if ((b & 1) && b < 17 && i == 0) ready = mbar_peek(full0 + rg.st * 8, rg.ph);
          if (i == 1) filler();
        }
        wg_commit();
        if (!(b & 1)) { wg_wait<1>(); release(prev); }
      };
      auto nop = [] {};
#pragma unroll
      for (int p = 0; p < 4; p++) { uint32_t o[4]; packu8(p, o); sts4(hp + p * 4096, o); }
      box(0, nop);
      if (lead) mbar_arrive(xb_done);
#pragma unroll 1
      for (int c = 1;; c++) {
        const uint32_t hc = hp + c * 4 * 4096;
#pragma unroll
        for (int b = 1; b < 18; b++) box(b, [&] {
          if ((b & 1) && b < 8) { uint32_t o[4]; const uint32_t a = hc - (4 - (b >> 1)) * 4096; lds4(a, o); geglu8(b >> 1, o); sts4(a, o); }
          if ((b & 1) && b > 10) { uint32_t o[4]; packu8((b - 11) >> 1, o); if (c < 8) sts4(hc + ((b - 11) >> 1) * 4096, o); } });
        ZSTAMP(4, c);
        if (c == 8) break;
        box(0, nop);
      }
      wg_wait<0>();
      STAMP(21);
      GSTAMP(19);
      auto unpark = [&](int kb) {
#pragma unroll
        for (int s = 4 * kb; s < 4 * kb + 4; s++) lds4(hp + s * 4096, X + 4 * s);
      };
      unpark(0);
      uint32_t U[16];
#pragma unroll
      for (int p = 0; p < 4; p++) packu8(p, U + 4 * p);
#pragma unroll
      for (int b = 0; b < 8; b++) box(b, [&] {
        if (b < 7) unpark(b + 1);
        if (b & 1) {
          geglu8(b >> 1, U + 2 * (b - 1));
          if (rg.ph > 1) sts4(hp, U + 2 * (b - 1));
#pragma unroll
          for (int i = 0; i < 4; i++) X[128 + 2 * (b - 1) + i] = U[2 * (b - 1) + i];
        } });
      STAMP(24);
      if (layer == 0 && lead) mbar_arrive(park_free);
      const uint32_t lane2 = lane_id();
      uint4* const pw = scp + OFF_P + (j * 8 + w) * SLAB + lane2;
      const uint32_t pr = scr + OFF_P + w * SLAB + 4 * j * 32 + lane2;
      auto put_part = [&](float (&a)[32], int p, uint32_t chunk) {
        uint32_t o[4];
        pack8(a, p, o);
        stg4(pw + (chunk * 4 + p) * 32, (o[0] & ~1u) | tag, o[1], o[2], o[3]);
      };
      auto slot = [&](int p) { return sb + w * 2048 + (p < 3 ? PARK + p * 16384 : KVS + (p - 3) * 16384); };
      auto fetch = [&](int p) {
        bulk_load(slot(p), at(scr + OFF_P + (((j - p) & 7) * 8 + w) * SLAB + 4 * j * 32), 2048, pbar0 + w * 8, true);
      };
#pragma unroll 1
      for (int sp = 0;; sp++) {
        const uint32_t ca = sp == 0 ? 8 : ((j + 2 * sp) & 7), cb = (j + 2 * sp + 1) & 7;
        if (sp == 1 && lead) mbar_arrive(c8_go);
#pragma unroll
        for (int b = 8; b < 18; b++) box(b, [&] {
          if (b >= 11 && b < 15) put_part(aA, b - 11, ca);
          if (b == 17 && sp > 1) { if (sp == 3) mbar_wait(c8_done, layer); fetch(2 * sp - 2); } });
        STAMP(25 + sp);
        if (sp == 3) break;
#pragma unroll
        for (int b = 0; b < 8; b++) box(b, [&] {
          if (b >= 1 && b < 5) put_part(aB, b - 1, cb);
          if (b == 7 && sp > 0) fetch(2 * sp - 1); });
      }
      auto load_p = [&](int p, uint32_t* d) {
#pragma unroll
        for (int i = 0; i < 4; i++) ldg4(d + 4 * i, at(pr + ((j - p) & 7) * 8 * SLAB) + i * 32);
      };
      auto bad = [&](const uint32_t* d, uint32_t tg) { return diff2(d[0], d[4], tg) | diff2(d[8], d[12], tg); };
      uint32_t late = 0;
#pragma unroll
      for (int b = 0; b < 9; b++) {
        if (b == 6) { mbar_wait(lane2 & 1 ? res_full : pbar0 + w * 8, layer); __syncwarp(); }
        box(b, [&] {
          if (b == 1) {
#pragma unroll
            for (int p = 0; p < 4; p++) put_part(aB, p, (j + 7) & 7);
          }
          if (b == 3) { load_p(5, X); load_p(6, X + 16); }
          if (b == 7) {
            late = bad(X, tag) | bad(X + 16, tag);
#pragma unroll
            for (int i = 0; i < 4; i++) ldg4(X + 32 + 4 * i, at(pr + ((j - 7) & 7) * 8 * SLAB + (late == 0x7fc12345u)) + i * 32);
          } });
      }
#pragma unroll
      for (int p = 1; p < 5; p++)
#pragma unroll
        for (int i = 0; i < 4; i++) lds4(slot(p) + lane2 * 16 + i * 512, X + 48 + 16 * p + 4 * i);
#pragma unroll
      for (int i = 0; i < 4; i++) {
        const bool split = j == 2 * i + 1;
        const uint32_t a = slot(0) + i * 512 + (split ? lane2 * 8 : lane2 * 16);
        lds2(a, X + 48 + 4 * i); lds2(a + (split ? 256 : 8), X + 50 + 4 * i);
      }
      wg_wait<0>();
      release(rg.st); rg.next();
      pin(aA);
      STAMP(22);
      GSTAMP(20);
      {
        const uint32_t lane = lane2, r = lane >> 2, q = lane & 3;
        const uint32_t eye = r == 2 * q ? 0x3f80u : r == 2 * q + 1 ? 0x3f800000u : 0u;
        auto add = [&](const uint32_t* d) {
#pragma unroll
          for (int g = 0; g < 8; g++) mma8(aA + 4 * g, d[2 * g], d[2 * g + 1], eye);
        };
        int n = 0;
        late = or3(late, bad(X + 64, tag), or3(bad(X + 80, tag), bad(X + 96, tag), bad(X + 112, tag)));
#pragma unroll 1
        while (!__all_sync(~0u, (late & 1u) == 0u)) {
          SPIN_GUARD(n);
          const uint32_t pc = scr + OFF_P + w * SLAB + 4 * j * 32 + lane_id();
          late = 0;
#pragma unroll
          for (int p = 1; p < 8; p++) {
            uint32_t* d = X + (p < 5 ? 48 + 16 * p : 16 * (p - 5));
#pragma unroll
            for (int i = 0; i < 4; i++) ldg4(d + 4 * i, at(pc + ((j - p) & 7) * 8 * SLAB) + i * 32);
            late |= bad(d, tag);
          }
        }
        add(X); add(X + 16);
#pragma unroll
        for (int p = 1; p < 6; p++) add(X + 48 + 16 * (p % 5));
        STAMP(11);
        const uint32_t tg = tag ^ (__float_as_uint(aA[28]) == 0x7fc12345u ? 2u : 0u);
#pragma unroll 1
        while (!__all_sync(~0u, (bad(X + 32, tg) & 1u) == 0u)) { SPIN_GUARD(n); load_p(7, X + 32); }
        add(X + 32);
        STAMP(12);
        uint32_t res[16];
#pragma unroll
        for (int i = 0; i < 16; i++) X[i] = res[i] = pack_bf16(aA[2 * i], aA[2 * i + 1]);
        if (layer == 0) {
#pragma unroll
          for (int i = 0; i < 4; i++) X[4 * i] = nz(X[4 * i]);
          auto put = [&] { put4(at(xbase + 8 * SLAB + 4 * j * 32 + lane), X); };
          if (j < PRI) put();
          publish_stats<8>(at(scr + OFF_S + w * 96 + j * 8 + r), aA, 1u, lane);
          if (j >= PRI) put();
        } else {
          const uint32_t tb = slot(0);
          __syncwarp();
#pragma unroll
          for (int i = 0; i < 4; i++) {
            const uint32_t row = (lane2 & 7) + (lane2 & 8), g = 2 * i + (lane2 >> 4);
            asm volatile("stmatrix.sync.aligned.m8n8.x4.shared.b16 [%0], {%1,%2,%3,%4};"
                         :: "r"(tb + row * 128 + ((g ^ (row & 7)) << 4)), "r"(res[4 * i]), "r"(res[4 * i + 1]), "r"(res[4 * i + 2]), "r"(res[4 * i + 3]) : "memory");
          }
          __syncwarp();
#pragma unroll
          for (int i = 0; i < 4; i++) {
            const uint32_t row = 4 * i + (lane2 >> 3), g = lane2 & 7;
            uint32_t v[4];
            lds4(tb + row * 128 + ((g ^ (row & 7)) << 4), v);
            ((uint4*)out + ((128 * t + 32 * (w >> 1) + 2 * (lane2 >> 3) + (w & 1)) * 72 + 8 * j + g))[i * 576] = make_uint4(v[0], v[1], v[2], v[3]);
          }
        }
      }
      STAMP(23);
    }
  }
}

typedef CUresult (*EncodeFn)(CUtensorMap*, CUtensorMapDataType, cuuint32_t, void*, const cuuint64_t*, const cuuint64_t*,
                             const cuuint32_t*, const cuuint32_t*, CUtensorMapInterleave, CUtensorMapSwizzle,
                             CUtensorMapL2promotion, CUtensorMapFloatOOBfill);

CUtensorMap make_map(EncodeFn f, const void* p, uint64_t cols, uint64_t rows, uint64_t grp) {
  CUtensorMap m;
  cuuint64_t dims[3] = {cols, grp, rows / grp}, str[2] = {cols * 2, cols * 2 * grp};
  cuuint32_t box[3] = {64, 16, 4}, es[3] = {1, 1, 1};
  f(&m, CU_TENSOR_MAP_DATA_TYPE_BFLOAT16, 3, const_cast<void*>(p), dims, str, box, es, CU_TENSOR_MAP_INTERLEAVE_NONE,
    CU_TENSOR_MAP_SWIZZLE_128B, CU_TENSOR_MAP_L2_PROMOTION_NONE, CU_TENSOR_MAP_FLOAT_OOB_FILL_NONE);
  return m;
}
CUtensorMap make_rem_map(EncodeFn f, const void* p, uint64_t cols) {
  CUtensorMap m;
  cuuint64_t dims[2] = {cols, 576}, str[1] = {cols * 2};
  cuuint32_t box[2] = {8, 144}, es[2] = {1, 1};
  f(&m, CU_TENSOR_MAP_DATA_TYPE_BFLOAT16, 2, const_cast<void*>(p), dims, str, box, es, CU_TENSOR_MAP_INTERLEAVE_NONE,
    CU_TENSOR_MAP_SWIZZLE_NONE, CU_TENSOR_MAP_L2_PROMOTION_NONE, CU_TENSOR_MAP_FLOAT_OOB_FILL_NONE);
  return m;
}

}

extern "C" void kernel_launch(void* const* d_in, const int* in_sizes, int n_in, void* d_out, int out_size) {
  void* fn = nullptr;
  cudaDriverEntryPointQueryResult qr;
  cudaGetDriverEntryPoint("cuTensorMapEncodeTiled", &fn, cudaEnableDefault, &qr);
  EncodeFn enc = (EncodeFn)fn;
  Maps maps;
  maps.m[0] = make_map(enc, d_in[1], 1728, 576, 16); maps.m[1] = make_map(enc, d_in[2], 576, 576, 16);
  maps.m[2] = make_map(enc, d_in[4], 4608, 576, 16); maps.m[3] = make_map(enc, d_in[5], 4608, 576, 16);
  maps.m[4] = make_map(enc, d_in[6], 576, 4608, 16);
  maps.m[5] = make_rem_map(enc, d_in[1], 1728); maps.m[6] = make_rem_map(enc, d_in[2], 576);
  maps.m[8] = make_map(enc, d_in[2], 576, 576, 144); maps.m[9] = make_map(enc, d_in[4], 4608, 576, 144);
  maps.m[10] = make_map(enc, d_in[5], 4608, 576, 144);
  {
    cuuint64_t dims[3] = {576, 1024, 2}, str[2] = {2304, 1152};
    cuuint32_t box[3] = {64, 64, 2}, es[3] = {1, 1, 1};
    enc(&maps.m[7], CU_TENSOR_MAP_DATA_TYPE_BFLOAT16, 3, d_in[0], dims, str, box, es, CU_TENSOR_MAP_INTERLEAVE_NONE,
        CU_TENSOR_MAP_SWIZZLE_128B, CU_TENSOR_MAP_L2_PROMOTION_NONE, CU_TENSOR_MAP_FLOAT_OOB_FILL_NONE);
    box[0] = 8;
    enc(&maps.m[11], CU_TENSOR_MAP_DATA_TYPE_BFLOAT16, 3, d_in[0], dims, str, box, es, CU_TENSOR_MAP_INTERLEAVE_NONE,
        CU_TENSOR_MAP_SWIZZLE_NONE, CU_TENSOR_MAP_L2_PROMOTION_NONE, CU_TENSOR_MAP_FLOAT_OOB_FILL_NONE);
  }
  void* scr = nullptr;
  cudaGetSymbolAddress(&scr, g_scratch);
  cudaFuncSetAttribute(mega_kernel, cudaFuncAttributeMaxDynamicSharedMemorySize, SMEM_BYTES);
  cudaLaunchConfig_t cfg = {};
  cfg.gridDim = dim3(128); cfg.blockDim = dim3(384); cfg.dynamicSmemBytes = SMEM_BYTES; cfg.stream = cudaStreamPerThread;
  cudaLaunchAttribute at[1];
  at[0].id = cudaLaunchAttributeClusterDimension; at[0].val.clusterDim.x = 2; at[0].val.clusterDim.y = 1; at[0].val.clusterDim.z = 1;
  cfg.attrs = at; cfg.numAttrs = 1;
  int dev = 0, sms = 0, clusters = 0;
  cudaGetDevice(&dev);
  cudaDeviceGetAttribute(&sms, cudaDevAttrMultiProcessorCount, dev);
  cudaOccupancyMaxActiveClusters(&clusters, mega_kernel, &cfg);
  if (sms == 132 && clusters == 66) cfg.gridDim = dim3(132);
  cudaLaunchKernelEx(&cfg, mega_kernel, maps, (uint4*)scr, (__nv_bfloat16*)d_out);
}
```

```cpp
#include <cuda_runtime.h>
#include <cuda.h>
#include <cuda_bf16.h>
#include <stdint.h>

#define TRACE 0
#define GUARD 0
#define FORCE_REDO 0
#define ZT 0

namespace {

constexpr int NST = 6;
constexpr int STAGE = 16384;
constexpr int PARK = NST * STAGE;
constexpr int REM = PARK + 49152;
constexpr int KVS = REM + 40960;
constexpr int PIECE = PARK + 7 * STAGE;
constexpr int HSTG = KVS + 16384;
constexpr int BARS = KVS + 41472;
constexpr int TRC = BARS + 512;
constexpr int SMEM_BYTES = TRC + (TRACE ? 512 : 0);
static_assert(NST == 6, "the producer addresses empty barriers as full + 48");
static_assert(BARS >= PARK + 131072, "barriers overlap park");
static_assert(SMEM_BYTES <= 232448, "smem");

constexpr int SLAB = 36 * 32;
constexpr int SPIN_MAX = 1 << 17;
constexpr uint32_t PRI = 3;
constexpr int GD = 3, GO = 5;
constexpr int OFF_S = 0;
constexpr int OFF_H = OFF_S + 3 * 8 * 96;
constexpr int OFF_X = OFF_H + 2 * 8 * 384 - 8 * SLAB;
constexpr int OFF_P = OFF_X + 6 * 8 * SLAB;
constexpr int TILE = OFF_P + 8 * 8 * SLAB;
constexpr int OFF_R = 16 * TILE;
constexpr int OFF_F = OFF_R + 8 * 2304;
constexpr int SCRATCH = OFF_F + 128 * 8;

}

__device__ uint4 g_scratch[SCRATCH];

namespace {

constexpr uint64_t DESC_HI = 0x4000004000000000ull;
constexpr uint64_t DESC_REM = (576ull << 32) | (8u << 16);
__device__ __forceinline__ void wgmma_rs_n64(float (&d)[32], const uint32_t* a, uint64_t desc, int scale_d) {
  asm volatile("{\n.reg .pred p;\nsetp.ne.b32 p, %37, 0;\n"
    "wgmma.mma_async.sync.aligned.m64n64k16.f32.bf16.bf16 "
    "{%0, %1, %2, %3, %4, %5, %6, %7, %8, %9, %10, %11, %12, %13, %14, %15, %16, %17, %18, %19, %20, %21, %22, %23, %24, %25, %26, %27, %28, %29, %30, %31}, "
    "{%32, %33, %34, %35}, %36, p, 1, 1, 1;\n}\n"
    : "+f"(d[0]), "+f"(d[1]), "+f"(d[2]), "+f"(d[3]), "+f"(d[4]), "+f"(d[5]), "+f"(d[6]), "+f"(d[7]), "+f"(d[8]), "+f"(d[9]), "+f"(d[10]), "+f"(d[11]), "+f"(d[12]), "+f"(d[13]), "+f"(d[14]), "+f"(d[15]), "+f"(d[16]), "+f"(d[17]), "+f"(d[18]), "+f"(d[19]), "+f"(d[20]), "+f"(d[21]), "+f"(d[22]), "+f"(d[23]), "+f"(d[24]), "+f"(d[25]), "+f"(d[26]), "+f"(d[27]), "+f"(d[28]), "+f"(d[29]), "+f"(d[30]), "+f"(d[31])
    : "r"(a[0]), "r"(a[1]), "r"(a[2]), "r"(a[3]), "l"(desc), "r"(scale_d));
}
__device__ __forceinline__ void wgmma_rs_n72(float (&d)[36], const uint32_t* a, uint64_t desc, int scale_d) {
  asm volatile("{\n.reg .pred p;\nsetp.ne.b32 p, %41, 0;\n"
    "wgmma.mma_async.sync.aligned.m64n72k16.f32.bf16.bf16 "
    "{%0, %1, %2, %3, %4, %5, %6, %7, %8, %9, %10, %11, %12, %13, %14, %15, %16, %17, %18, %19, %20, %21, %22, %23, %24, %25, %26, %27, %28, %29, %30, %31, %32, %33, %34, %35}, "
    "{%36, %37, %38, %39}, %40, p, 1, 1, 1;\n}\n"
    : "+f"(d[0]), "+f"(d[1]), "+f"(d[2]), "+f"(d[3]), "+f"(d[4]), "+f"(d[5]), "+f"(d[6]), "+f"(d[7]), "+f"(d[8]), "+f"(d[9]), "+f"(d[10]), "+f"(d[11]), "+f"(d[12]), "+f"(d[13]), "+f"(d[14]), "+f"(d[15]), "+f"(d[16]), "+f"(d[17]), "+f"(d[18]), "+f"(d[19]), "+f"(d[20]), "+f"(d[21]), "+f"(d[22]), "+f"(d[23]), "+f"(d[24]), "+f"(d[25]), "+f"(d[26]), "+f"(d[27]), "+f"(d[28]), "+f"(d[29]), "+f"(d[30]), "+f"(d[31]), "+f"(d[32]), "+f"(d[33]), "+f"(d[34]), "+f"(d[35])
    : "r"(a[0]), "r"(a[1]), "r"(a[2]), "r"(a[3]), "l"(desc), "r"(scale_d));
}
__device__ __forceinline__ void wgmma_rs_n24(float (&d)[12], const uint32_t* a, uint64_t desc, int scale_d) {
  asm volatile("{\n.reg .pred p;\nsetp.ne.b32 p, %17, 0;\n"
    "wgmma.mma_async.sync.aligned.m64n24k16.f32.bf16.bf16 "
    "{%0, %1, %2, %3, %4, %5, %6, %7, %8, %9, %10, %11}, "
    "{%12, %13, %14, %15}, %16, p, 1, 1, 1;\n}\n"
    : "+f"(d[0]), "+f"(d[1]), "+f"(d[2]), "+f"(d[3]), "+f"(d[4]), "+f"(d[5]), "+f"(d[6]), "+f"(d[7]), "+f"(d[8]), "+f"(d[9]), "+f"(d[10]), "+f"(d[11])
    : "r"(a[0]), "r"(a[1]), "r"(a[2]), "r"(a[3]), "l"(desc), "r"(scale_d));
}

__device__ __forceinline__ void mbar_init(uint32_t a, uint32_t c) { asm volatile("mbarrier.init.shared::cta.b64 [%0], %1;" :: "r"(a), "r"(c)); }
__device__ __forceinline__ void mbar_arrive(uint32_t a) { asm volatile("mbarrier.arrive.shared::cta.b64 _, [%0];" :: "r"(a) : "memory"); }
__device__ __forceinline__ void mbar_wait_trap(uint32_t a, uint32_t ph) {
  asm volatile("{\n.reg .pred p;\n.reg .u32 n;\nmov.u32 n, 0;\n"
               "W: mbarrier.try_wait.parity.shared::cta.b64 p, [%0], %1;\n@p bra D;\n"
               "add.u32 n, n, 1;\nsetp.lt.u32 p, n, 4194304;\n@p bra W;\ntrap;\nD:\n}" :: "r"(a), "r"(ph) : "memory");
}
__device__ __forceinline__ void mbar_wait(uint32_t a, uint32_t ph) {
  asm volatile("{\n.reg .pred p;\nW: mbarrier.try_wait.parity.shared::cta.b64 p, [%0], %1;\n@!p bra W;\n}" :: "r"(a), "r"(ph) : "memory");
}
__device__ __forceinline__ uint32_t mbar_peek(uint32_t a, uint32_t ph) {
  uint32_t r;
  asm volatile("{\n.reg .pred p;\nmbarrier.test_wait.parity.shared::cta.b64 p, [%1], %2;\nselp.u32 %0, 1, 0, p;\n}" : "=r"(r) : "r"(a), "r"(ph) : "memory");
  return r;
}
__device__ __forceinline__ void mbar_wait_unless(uint32_t ready, uint32_t a, uint32_t ph) {
  asm volatile("{\n.reg .pred p;\nsetp.ne.u32 p, %2, 0;\n@p bra D;\nW: mbarrier.try_wait.parity.shared::cta.b64 p, [%0], %1;\n@!p bra W;\nD:\n}"
               :: "r"(a), "r"(ph), "r"(ready) : "memory");
}
__device__ __forceinline__ void mbar_wait_sleep(uint32_t a, uint32_t ph) {
  asm volatile("{\n.reg .pred p;\nW: mbarrier.test_wait.parity.shared::cta.b64 p, [%0], %1;\n@p bra D;\nnanosleep.u32 500;\nbra W;\nD:\n}" :: "r"(a), "r"(ph) : "memory");
}
__device__ __forceinline__ void wg_fence() { asm volatile("wgmma.fence.sync.aligned;" ::: "memory"); }
__device__ __forceinline__ void wg_commit() { asm volatile("wgmma.commit_group.sync.aligned;" ::: "memory"); }
template <int N> __device__ __forceinline__ void wg_wait() { asm volatile("wgmma.wait_group.sync.aligned %0;" :: "n"(N) : "memory"); }
__device__ __forceinline__ float tanh_ap(float x) { float y; asm("tanh.approx.f32 %0, %1;" : "=f"(y) : "f"(x)); return y; }
__device__ __forceinline__ float ex2(float x) { float y; asm("ex2.approx.ftz.f32 %0, %1;" : "=f"(y) : "f"(x)); return y; }
__device__ __forceinline__ uint32_t pack_bf16(float lo, float hi) { uint32_t r; asm("cvt.rn.bf16x2.f32 %0, %1, %2;" : "=r"(r) : "f"(hi), "f"(lo)); return r; }
__device__ __forceinline__ float bf_lo(uint32_t v) { return __uint_as_float(v << 16); }
__device__ __forceinline__ float bf_hi(uint32_t v) { return __uint_as_float(v & 0xffff0000u); }
__device__ __forceinline__ uint32_t sub_bf16x2(uint32_t a, uint32_t b) { uint32_t r; asm("sub.rn.bf16x2 %0, %1, %2;" : "=r"(r) : "r"(a), "r"(b)); return r; }
__device__ __forceinline__ uint32_t mul_bf16x2(uint32_t a, uint32_t b) { uint32_t r; asm("mul.rn.bf16x2 %0, %1, %2;" : "=r"(r) : "r"(a), "r"(b)); return r; }
__device__ __forceinline__ uint32_t diff2(uint32_t a, uint32_t b, uint32_t t) { uint32_t r; asm("lop3.b32 %0, %1, %2, %3, 0x7e;" : "=r"(r) : "r"(a), "r"(b), "r"(t)); return r; }
__device__ __forceinline__ uint32_t or3(uint32_t a, uint32_t b, uint32_t c) { uint32_t r; asm("lop3.b32 %0, %1, %2, %3, 0xfe;" : "=r"(r) : "r"(a), "r"(b), "r"(c)); return r; }
__device__ __forceinline__ uint32_t umin2(uint32_t a, uint32_t b) { uint32_t r; asm("min.u32 %0, %1, %2;" : "=r"(r) : "r"(a), "r"(b)); return r; }
__device__ __forceinline__ uint32_t nz(uint32_t w) { return w == 0u ? 0x8000u : w; }

__device__ __forceinline__ void ldg4(uint32_t* d, const uint4* p) {
  asm volatile("ld.relaxed.gpu.global.v4.b32 {%0,%1,%2,%3}, [%4];" : "=r"(d[0]), "=r"(d[1]), "=r"(d[2]), "=r"(d[3]) : "l"(p) : "memory");
}
__device__ __forceinline__ void ldg2(uint32_t* d, const void* p) {
  asm volatile("ld.relaxed.gpu.global.v2.b32 {%0,%1}, [%2];" : "=r"(d[0]), "=r"(d[1]) : "l"(p) : "memory");
}
__device__ __forceinline__ void stg4(uint4* p, uint32_t a, uint32_t b, uint32_t c, uint32_t d) {
  asm volatile("st.relaxed.gpu.global.v4.b32 [%0], {%1,%2,%3,%4};" :: "l"(p), "r"(a), "r"(b), "r"(c), "r"(d) : "memory");
}
__device__ __forceinline__ void stg2(void* p, uint32_t a, uint32_t b) {
  asm volatile("st.relaxed.gpu.global.v2.b32 [%0], {%1,%2};" :: "l"(p), "r"(a), "r"(b) : "memory");
}
__device__ __forceinline__ void sts4(uint32_t a, const uint32_t* o) { asm volatile("st.shared.v4.b32 [%0], {%1,%2,%3,%4};" :: "r"(a), "r"(o[0]), "r"(o[1]), "r"(o[2]), "r"(o[3]) : "memory"); }
__device__ __forceinline__ void lds4(uint32_t a, uint32_t* o) { asm volatile("ld.shared.v4.b32 {%0,%1,%2,%3}, [%4];" : "=r"(o[0]), "=r"(o[1]), "=r"(o[2]), "=r"(o[3]) : "r"(a) : "memory"); }
__device__ __forceinline__ void lds2(uint32_t a, uint32_t* o) { asm volatile("ld.shared.v2.b32 {%0,%1}, [%2];" : "=r"(o[0]), "=r"(o[1]) : "r"(a) : "memory"); }
__device__ __forceinline__ float rcp(float x) { float y; asm("rcp.approx.ftz.f32 %0, %1;" : "=f"(y) : "f"(x)); return y; }
__device__ __forceinline__ void sts1(uint32_t a, uint32_t v) { asm volatile("st.shared.b32 [%0], %1;" :: "r"(a), "r"(v) : "memory"); }
__device__ __forceinline__ void ldsm4(uint32_t a, uint32_t& r0, uint32_t& r1, uint32_t& r2, uint32_t& r3) {
  asm volatile("ldmatrix.sync.aligned.m8n8.x4.shared.b16 {%0,%1,%2,%3}, [%4];" : "=r"(r0), "=r"(r1), "=r"(r2), "=r"(r3) : "r"(a) : "memory");
}
__device__ __forceinline__ void ldsm4t(uint32_t a, uint32_t& r0, uint32_t& r1, uint32_t& r2, uint32_t& r3) {
  asm volatile("ldmatrix.sync.aligned.m8n8.x4.trans.shared.b16 {%0,%1,%2,%3}, [%4];" : "=r"(r0), "=r"(r1), "=r"(r2), "=r"(r3) : "r"(a) : "memory");
}
__device__ __forceinline__ void mma16(float* c, uint32_t a0, uint32_t a1, uint32_t a2, uint32_t a3, uint32_t b0, uint32_t b1) {
  asm("mma.sync.aligned.m16n8k16.row.col.f32.bf16.bf16.f32 {%0,%1,%2,%3}, {%4,%5,%6,%7}, {%8,%9}, {%0,%1,%2,%3};"
    : "+f"(c[0]), "+f"(c[1]), "+f"(c[2]), "+f"(c[3]) : "r"(a0), "r"(a1), "r"(a2), "r"(a3), "r"(b0), "r"(b1));
}
__device__ __forceinline__ void mma16z(float* d, const uint32_t* a, uint32_t b0, uint32_t b1) {
  asm("mma.sync.aligned.m16n8k16.row.col.f32.bf16.bf16.f32 {%0,%1,%2,%3}, {%4,%5,%6,%7}, {%8,%9}, {%10,%10,%10,%10};"
    : "=f"(d[0]), "=f"(d[1]), "=f"(d[2]), "=f"(d[3]) : "r"(a[0]), "r"(a[1]), "r"(a[2]), "r"(a[3]), "r"(b0), "r"(b1), "f"(0.f));
}
__device__ __forceinline__ void mma8(float* c, uint32_t a0, uint32_t a1, uint32_t b0) {
  asm("mma.sync.aligned.m16n8k8.row.col.f32.bf16.bf16.f32 {%0,%1,%2,%3}, {%4,%5}, {%6}, {%0,%1,%2,%3};"
    : "+f"(c[0]), "+f"(c[1]), "+f"(c[2]), "+f"(c[3]) : "r"(a0), "r"(a1), "r"(b0));
}
__device__ __forceinline__ uint32_t lane_id() { uint32_t l; asm volatile("mov.u32 %0, %%laneid;" : "=r"(l)); return l; }
__device__ __forceinline__ float quad_sum(float v) { v += __shfl_xor_sync(~0u, v, 1); v += __shfl_xor_sync(~0u, v, 2); return v; }
template <int N> __device__ __forceinline__ void pin(float (&d)[N]) {
#pragma unroll
  for (int i = 0; i < N; i++) asm volatile("" : "+f"(d[i]) :: "memory");
}
#define SPIN_GUARD(n) if (++(n) > SPIN_MAX) break

template <int NG> __device__ __forceinline__ void publish_stats(uint4* dst, const float* y, uint32_t tag, uint32_t lane) {
  float s0 = 0.f, s1 = 0.f;
#pragma unroll
  for (int g = 0; g < NG; g++) { s0 += y[4 * g] + y[4 * g + 1]; s1 += y[4 * g + 2] + y[4 * g + 3]; }
  s0 = quad_sum(s0); s1 = quad_sum(s1);
  const float m0 = s0 * (1.f / (8 * NG)), m1 = s1 * (1.f / (8 * NG));
  float q0 = 0.f, q1 = 0.f, q2 = 0.f, q3 = 0.f;
#pragma unroll
  for (int g = 0; g < NG; g++) {
    const float a = y[4 * g] - m0, b = y[4 * g + 1] - m0, c = y[4 * g + 2] - m1, d = y[4 * g + 3] - m1;
    q0 = fmaf(a, a, q0); q1 = fmaf(b, b, q1); q2 = fmaf(c, c, q2); q3 = fmaf(d, d, q3);
  }
  q0 = quad_sum(q0 + q1); q2 = quad_sum(q2 + q3);
  if ((lane & 3) == 0)
    stg4(dst, (__float_as_uint(s0) & ~1u) | tag, __float_as_uint(q0), __float_as_uint(s1), __float_as_uint(q2));
}

__device__ __forceinline__ void put4(uint4* p, const uint32_t* v) {
#pragma unroll
  for (int i = 0; i < 4; i++) stg4(p + i * 32, v[4 * i], v[4 * i + 1], v[4 * i + 2], v[4 * i + 3]);
}
__device__ __forceinline__ uint32_t row72(uint32_t k) { return k % 9 == 4 ? 32 + k / 9 : k - (k + 4) / 9; }
__device__ __forceinline__ void zero_share(uint4* slab, uint32_t j, uint32_t lane) {
  uint4* p = slab + j * 144 + lane;
#pragma unroll
  for (int i = 0; i < 4; i++) stg4(p + i * 32, 0u, 0u, 0u, 0u);
  if (lane < 16) stg4(p + 128, 0u, 0u, 0u, 0u);
}

struct Maps { CUtensorMap m[12]; };

struct Ring {
  uint32_t st, ph;
  __device__ __forceinline__ void next() { if (++st == NST) { st = 0; ph ^= 1; } }
};

#define GSTAMP(i) do {} while (0)
#define STAMP(i) do {} while (0)
#define ZSTAMP(m, i) do {} while (0)

__device__ __forceinline__ void tma_box(uint32_t dst, const CUtensorMap* m, int col, int row, uint32_t bar, uint32_t expect) {
  asm volatile("{\n.reg .pred e, h;\nelect.sync _|e, 0xffffffff;\nsetp.ne.and.u32 h, %5, 0, e;\n"
               "@h mbarrier.arrive.expect_tx.shared::cta.b64 _, [%2], %5;\n"
               "@e cp.async.bulk.tensor.2d.shared::cluster.global.mbarrier::complete_tx::bytes [%0], [%1, {%3, %4}], [%2];\n}"
               :: "r"(dst), "l"(m), "r"(bar), "r"(col), "r"(row), "r"(expect) : "memory");
}

__device__ __forceinline__ void bulk_load(uint32_t dst, const void* src, uint32_t bytes, uint32_t bar, bool arm) {
  asm volatile("{\n.reg .pred e, h;\nelect.sync _|e, 0xffffffff;\nsetp.ne.and.u32 h, %4, 0, e;\n"
               "@h mbarrier.arrive.expect_tx.shared::cta.b64 _, [%3], %2;\n"
               "@e cp.async.bulk.shared::cluster.global.mbarrier::complete_tx::bytes [%0], [%1], %2, [%3];\n}"
               :: "r"(dst), "l"(src), "r"(bytes), "r"(bar), "r"((uint32_t)arm) : "memory");
}

__global__ void __launch_bounds__(384, 1) mega_kernel(
    const __grid_constant__ Maps maps, uint4* __restrict__ scratch,
    __nv_bfloat16* __restrict__ out) {
  extern __shared__ __align__(1024) uint8_t smem[];
  const uint32_t sb = (uint32_t)__cvta_generic_to_shared(smem);
  const uint32_t full0 = sb + BARS, empty0 = full0 + 8 * NST, rem_full = empty0 + 8 * NST, park_free = rem_full + 8, kv_free = park_free + 8;
  const uint32_t c8_go = kv_free + 8, c8_done = c8_go + 8, c8_full = c8_done + 8, remo_full = c8_full + 8, piece_full = remo_full + 8, xb_done = piece_full + 8, res_full = xb_done + 8, pbar0 = res_full + 8;
  const uint32_t x_done = pbar0 + 64, x_ring = x_done + 8, xbar0 = x_ring + 8, redo_full = xbar0 + 72, att_done = redo_full + 16;
  const uint32_t side_full = att_done + 8;
  const uint32_t w = __shfl_sync(~0u, threadIdx.x >> 5, 0);
  uint32_t pair = blockIdx.x >> 1;
  if (gridDim.x == 132) {
    uint32_t smid;
    asm("mov.u32 %0, %%smid;" : "=r"(smid));
    const uint32_t tpc = smid >> 1;
    if (tpc == 60 || tpc == 61) {
      if (threadIdx.x == 0) { const long long c0 = clock64(); while (clock64() - c0 < 40000) __nanosleep(1000); }
      return;
    }
    pair = tpc < 32 ? tpc : tpc >= 62 ? (tpc - 58) * 8 : 33 + (tpc - 32) / 7 * 8 + (tpc - 32) % 7;
  }
  const uint32_t rank = blockIdx.x & 1, t = (pair & 7) * 2 + rank, j = pair >> 3;
  const uint32_t sd = sb & 0x3ffff;
  const uint32_t odd = j & 1;
  const uint32_t scr = t * TILE;
  uint4* const scp = scratch + t * TILE;
  auto at = [&](uint32_t i) { return scratch + i; };
  auto at8 = [&](uint32_t i) { return (uint2*)scratch + i; };
  auto blk = [&](uint32_t kb) { return kb == 0 ? j : kb - (kb <= j); };
  const uint32_t xs = sb + (NST - 2) * STAGE;
  auto fetch_x = [&](uint32_t dst, uint32_t col, uint32_t bar, bool narrow) {
    asm volatile("{\n.reg .pred e;\nelect.sync _|e, 0xffffffff;\n@e mbarrier.arrive.expect_tx.shared::cta.b64 _, [%2], %5;\n"
                 "@e cp.async.bulk.tensor.3d.shared::cluster.global.mbarrier::complete_tx::bytes [%0], [%1, {%3, %4, 0}], [%2];\n}"
                 :: "r"(dst), "l"(&maps.m[narrow ? 11 : 7]), "r"(bar), "r"(col), "r"(64 * t), "r"(narrow ? 2048 : 16384) : "memory");
  };
  if (threadIdx.x == 256) {
    for (int i = 0; i < 9; i++) mbar_init(xbar0 + 8 * i, 1);
    mbar_init(piece_full, 1);
    asm volatile("fence.mbarrier_init.release.cluster;" ::: "memory");
  }
  if (threadIdx.x == 288) {
    for (int i = 0; i < NST; i++) { mbar_init(full0 + 8 * i, 1); mbar_init(empty0 + 8 * i, 16); }
    mbar_init(x_done, 8); mbar_init(x_ring, 16); mbar_init(redo_full, 1); mbar_init(redo_full + 8, 1); mbar_init(att_done, 4);
    mbar_init(side_full, 1); mbar_init(side_full + 8, 1); mbar_init(side_full + 48, 16); mbar_init(side_full + 56, 16);
    asm volatile("fence.mbarrier_init.release.cluster;" ::: "memory");
  }
  if (threadIdx.x == 320) {
    mbar_init(rem_full, 2); mbar_init(park_free, 8); mbar_init(kv_free, 8); mbar_init(c8_go, 8); mbar_init(c8_done, 2); mbar_init(c8_full, 1);
    mbar_init(remo_full, 64); mbar_init(xb_done, 8); mbar_init(res_full, 32);
    for (int i = 0; i < 8; i++) mbar_init(pbar0 + 8 * i, 4);
    asm volatile("fence.mbarrier_init.release.cluster;" ::: "memory");
  }
  if (threadIdx.x == 352) {
    asm volatile("prefetch.tensormap [%0];" :: "l"(&maps.m[7]) : "memory");
    asm volatile("prefetch.tensormap [%0];" :: "l"(&maps.m[0]) : "memory");
  }
  __syncwarp();
  asm volatile("barrier.cluster.arrive.relaxed.aligned;" ::: "memory");
  if (w != 8) asm volatile("barrier.cluster.wait.aligned;" ::: "memory");

  if (w >= 8) {
    asm volatile("setmaxnreg.dec.sync.aligned.u32 24;");
    if (w == 8) {
#pragma unroll 1
      for (uint32_t b = 0; b < 9; b++) fetch_x(xs + b * STAGE, 64 * b, xbar0 + 8 * b, false);
      tma_box(sb + PIECE, &maps.m[t >= 12 ? 6 : 5], 72 * j + (odd ? 0 : 64) + (t < 8 ? 576 * ((t >> 2) + 1) : 0), 144 * (t & 3), piece_full, 2304);
      asm volatile("barrier.cluster.wait.aligned;" ::: "memory");
      const uint32_t sb2 = __shfl_sync(~0u, sb, 0);
      uint32_t dst = sb2, bar = sb2 + BARS, ph = 1;
#pragma unroll 1
      for (int seg = 0; seg < 34; seg++) {
        const int n = seg >= 17 ? seg - 17 : seg;
        int ma, mb, ca, cb;
        if (n == 2) continue;
        if (n < 2) { ma = 0; mb = n; ca = 72 * j + 8 * odd + (n ? 0 : 576); cb = ca + (n ? 0 : 576); }
        else if (n < 12) { ma = 3; mb = 2; ca = cb = 576 * j + 64 * (n - 3); }
        else { ma = mb = 4; ca = n == 12 ? 512 : ((j + 2 * n) & 7) * 64; cb = ((j + 2 * n + 1) & 7) * 64; }
        const bool zip = n == 0 || n == 3, solo = n == 16;
#pragma unroll 1
        for (uint32_t st = 0; st < (solo ? 5 : 9); st++) {
          if (seg == 0 && st == NST - 2) mbar_wait(x_ring, 0);
          const uint32_t b = 2 * st + rank, kb = zip ? st : b >= 9 ? b - 9 : b;
          const bool second = zip ? rank : b >= 9;
          const int m = second ? mb : ma;
          const bool shared = kb == 8 && m > 0 && m < 4;
          const uint32_t ks = m == 4 ? 36 * j + 4 * kb : m == 0 ? 4 * blk(kb) : shared ? 0 : (9 * blk(kb) + 1) >> 1;
          const bool side = n == 1 && st >= 7;
          asm volatile("{\n.reg .pred p, e, f;\n.reg .u32 n;\nelect.sync _|e, 0xffffffff;\nsetp.ne.and.u32 f, %8, 0, e;\nmov.u32 n, 0;\n"
                       "W: mbarrier.try_wait.parity.shared::cta.b64 p, [%1+48], %2;\n@p bra D;\n"
                       "add.u32 n, n, 1;\nsetp.lt.u32 p, n, 4194304;\n@p bra W;\ntrap;\n"
                       "D: @e mbarrier.arrive.expect_tx.shared::cta.b64 _, [%1], %7;\n"
                       "@f cp.async.bulk.tensor.3d.shared::cluster.global.mbarrier::complete_tx::bytes.multicast::cluster [%0], [%3, {%4, %5, %6}], [%1], 3;\n}"
                       :: "r"((side ? sb2 + (st - 1) * STAGE : dst) + rank * 8192), "r"(side ? sb2 + (side_full - sb) + (st - 7) * 8 : bar), "r"(side ? seg >= 17 : ph), "l"(&maps.m[m + (shared ? 7 : 0)]), "r"(second ? cb : ca),
                          "r"(shared ? 64 : 0), "r"(ks), "r"(solo && st == 4 ? STAGE / 2 : STAGE), "r"((uint32_t)!(solo && b == 9)) : "memory");
          if (!side) { dst += STAGE; bar += 8; }
          if (dst == sb2 + NST * STAGE) { dst = sb2; bar -= 8 * NST; ph ^= 1; }
        }
      }
      {
#pragma unroll 1
        for (int i = 0; i < NST; i++) {
          mbar_wait_trap(bar + 48, ph);
          bar += 8;
          if (bar == full0 + 8 * NST) { bar = full0; ph ^= 1; }
        }
      }
    } else if (w == 9) {
      const uint32_t lane = lane_id();
      const uint32_t stg = sb + HSTG + lane * 16;
      uint32_t fph = 0;
#pragma unroll 1
      for (uint32_t layer = 0; layer < 2; layer++) {
        uint4* xb = scp + OFF_X + ((4 + layer) * 8 + j) * SLAB + 28 * 32;
        mbar_wait_sleep(c8_go, layer);
        int n = 0;
#pragma unroll 1
        while (true) {
          if (lane == 0) asm volatile("mbarrier.arrive.expect_tx.shared::cta.b64 _, [%0], 18432;" :: "r"(c8_full) : "memory");
          __syncwarp();
#pragma unroll 1
          for (uint32_t s = 0; s < 9; s++)
            bulk_load(sb + HSTG + s * 2048, s < 8 ? scp + OFF_P + (j + s * 8) * SLAB + 32 * 32 : xb, 2048, c8_full, false);
          mbar_wait(c8_full, fph); fph ^= 1;
          uint32_t bad = 0;
#pragma unroll 8
          for (int s = 0; s < 32; s++) { uint32_t v; asm volatile("ld.shared.b32 %0, [%1];" : "=r"(v) : "r"(stg + s * 512) : "memory"); bad |= v ^ (1 - layer); }
          if (__all_sync(~0u, (bad & 1u) == 0u)) break;
          __nanosleep(300);
          SPIN_GUARD(n);
        }
        asm volatile("bar.arrive 7, 96;" ::: "memory");
        float s0 = 0.f, s1 = 0.f;
#pragma unroll 1
        for (int g = 0; g < 8; g++) {
          const uint32_t a = stg + (g >> 1) * 512 + (g & 1) * 8;
          float a0 = 0.f, a1 = 0.f, a2 = 0.f, a3 = 0.f;
#pragma unroll 1
          for (int b = 0; b < 3; b++) {
            uint32_t v[6];
#pragma unroll
            for (int s = 0; s < 3; s++) lds2(a + (3 * b + s) * 2048, v + 2 * s);
#pragma unroll
            for (int s = 0; s < 3; s++) { a0 += bf_lo(v[2 * s]); a1 += bf_hi(v[2 * s]); a2 += bf_lo(v[2 * s + 1]); a3 += bf_hi(v[2 * s + 1]); }
          }
          sts1(a + 18432, pack_bf16(a0, a1)); sts1(a + 18436, pack_bf16(a2, a3));
          s0 += a0 + a1; s1 += a2 + a3;
        }
        __syncwarp();
        if (lane == 0) mbar_arrive(c8_done);
        s0 = quad_sum(s0); s1 = quad_sum(s1);
        float q0 = 0.f, q1 = 0.f;
        const uint32_t ln = lane_id();
#pragma unroll 1
        for (uint32_t i = 0; i < 4; i++) {
          uint32_t x[4];
          lds4(stg + 18432 + i * 512, x);
          uint4* z = xb + i * 32 + ln;
          asm volatile("" : "+l"(z));
          stg4(z, 0u, 0u, 0u, 0u);
          if (layer == 0) {
            stg4(z - (3 * 8 * SLAB - 128), nz(x[0]), x[1], nz(x[2]), x[3]);
#pragma unroll
            for (int e = 0; e < 4; e++) {
              const float m = (e & 1) ? s1 : s0, c = fmaf(m, -1.f / 64, bf_lo(x[e])), d = fmaf(m, -1.f / 64, bf_hi(x[e]));
              if (e & 1) q1 = fmaf(c, c, fmaf(d, d, q1)); else q0 = fmaf(c, c, fmaf(d, d, q0));
            }
          } else {
            uint32_t* o = (uint32_t*)(out + (128 * t + 32 * (j >> 1) + 2 * (ln >> 2) + (j & 1)) * 576 + 512 + 16 * i + 2 * (ln & 3));
            o[0] = x[0]; o[8 * 576] = x[1]; o[4] = x[2]; o[8 * 576 + 4] = x[3];
          }
        }
        if (layer == 0) {
          q0 = quad_sum(q0); q1 = quad_sum(q1);
          if ((ln & 3) == 0) stg4(scp + OFF_S + j * 96 + 64 + (ln >> 2), __float_as_uint(s0) | 1u, __float_as_uint(q0), __float_as_uint(s1), __float_as_uint(q1));
        }
      }
    } else {
      auto mark = [&](uint32_t k0, uint32_t v) {
        const uint32_t lane = lane_id();
#pragma unroll 1
        for (uint32_t k = k0; k < 6; k++) stg4(scp + OFF_S + (k * 4 + (lane >> 3)) * 96 + j * 8 + (lane & 7), k < 2 ? 0u : v, 0u, 0u, 0u);
      };
      if (w == 11) mark(2, 0u);
      auto phase2_duties = [&](uint32_t layer) {
        const uint32_t lane = lane_id();
        asm volatile("bar.sync 7, 96;" ::: "memory");
        if (w == 11) {
          if (layer == 0) mark(0, 1u);
          __syncwarp();
          if (lane == 0) mbar_arrive(c8_done);
        }
#pragma unroll 1
        for (uint32_t i = 0; i < 16; i++) {
          const uint32_t sl = (w - 10) * 4 + (i >> 2);
          bulk_load(sb + PARK + sl * 2048 + (i & 3) * 512, scp + OFF_X + ((4 + layer) * 8 + sl) * SLAB + row72(4 * j + (i & 3)) * 32, 512, res_full, true);
        }
        mbar_wait_sleep(res_full, layer);
#pragma unroll 1
        for (uint32_t i = 0; i < 16; i++) {
          stg4(scp + OFF_X + ((4 + layer) * 8 + (w - 10) * 4 + (i >> 2)) * SLAB + row72(4 * j + (i & 3)) * 32 + lane, 0u, 0u, 0u, 0u);
          if ((i & 3) == 3) __nanosleep(200);
        }
      };
      if (w == 10) {
        const uint32_t lane = lane_id();
        uint32_t* fl = (uint32_t*)(scratch + OFF_F + (t * 8 + j) * 8) + (lane & 15);
        uint32_t v;
        asm volatile("ld.relaxed.gpu.global.b32 %0, [%1];" : "=r"(v) : "l"(fl) : "memory");
        mbar_wait(piece_full, 0);
        asm volatile("{\n.reg .pred e;\nelect.sync _|e, 0xffffffff;\n@e cp.async.bulk.global.shared::cta.bulk_group [%0], [%1], 2304;\n}\n"
                     "cp.async.bulk.commit_group;\ncp.async.bulk.wait_group 0;\nfence.proxy.async;"
                     :: "l"(scratch + OFF_R + j * 2304 + t * 144), "r"(sb + PIECE) : "memory");
        __syncwarp();
        if (lane < 16) asm volatile("st.release.gpu.global.b32 [%0], 1;" :: "l"((uint32_t*)(scratch + OFF_F + (lane_id() * 8 + j) * 8) + t) : "memory");
        int n = 0;
#pragma unroll 1
        while (!__all_sync(~0u, v != 0u)) {
          __nanosleep(100);
          SPIN_GUARD(n);
          asm volatile("ld.relaxed.gpu.global.b32 %0, [%1];" : "=r"(v) : "l"(fl) : "memory");
        }
        asm volatile("st.relaxed.gpu.global.b32 [%0], 0;" :: "l"(fl) : "memory");
        mbar_wait(x_done, 0);
      }
#pragma unroll 1
      for (uint32_t layer = 0; layer < 3; layer++) {
        if (w == 10 && layer < 2) {
          if (layer) mbar_wait_sleep(park_free, 0);
          const uint4* img = scratch + OFF_R + j * 2304;
          if (lane_id() == 0) asm volatile("mbarrier.arrive.expect_tx.shared::cta.b64 _, [%0], 27648;\nmbarrier.arrive.expect_tx.shared::cta.b64 _, [%1], 9216;"
                                           :: "r"(rem_full), "r"(piece_full) : "memory");
          __syncwarp();
#pragma unroll 1
          for (uint32_t p = 0; p < 3; p++) {
            bulk_load(sb + REM + p * 9216, img + p * 576 + j * 64, 1024, rem_full, false);
            if (j) bulk_load(sb + REM + p * 9216 + 1024, img + p * 576, j * 1024, rem_full, false);
            bulk_load(sb + REM + p * 9216 + (j + 1) * 1024, img + p * 576 + (j + 1) * 64, (8 - j) * 1024, rem_full, false);
          }
#pragma unroll 1
          for (uint32_t i = 0; i < 12; i++)
            bulk_load(sb + REM + 27648 + (i < 8 ? i * 1024 : 6144 + i * 256), img + 1728 + (i < 8 ? (9 * blk(i) + 1) >> 1 : 9 * i - 68) * 16,
                      i < 8 ? 1024 : 256, piece_full, false);
          if (layer == 0) { fetch_x(sb + PARK + 2 * STAGE, 72 * j + 8 * odd, xbar0, false); fetch_x(sb + REM + 37888, 72 * j + (odd ? 0 : 64), xbar0 + 8, true); }
        }
        if (w == 11 && layer < 2) {
          if (layer) mbar_wait_sleep(park_free, 0);
          __syncwarp();
          if (lane_id() == 0) mbar_arrive(rem_full);
        }
        if (layer) phase2_duties(layer - 1);
        if (layer == 2) break;
        mbar_wait(kv_free, layer);
        if (t > 0) {
          const uint32_t lane = lane_id(), r = lane >> 2, q = lane & 3;
#pragma unroll 1
          for (uint32_t pc = 0; pc < 3; pc++) {
            uint4* hp = scp + OFF_H + ((layer * 8 + j) * 2 + (w - 10)) * 192 + pc * 64 + lane;
            uint32_t hl[8];
            int n = 0;
            hl[4] = 1u;
#pragma unroll 1
            while (true) {
              ldg4(hl, hp);
              if (pc < 2) ldg4(hl + 4, hp + 32);
              if (__all_sync(~0u, hl[0] != 0u && hl[4] != 0u)) break;
              __nanosleep(100);
              SPIN_GUARD(n);
            }
            const uint32_t dst = sb + KVS + (w - 10) * 10368 + r * 144 + q * 4;
            if (pc < 2) {
#pragma unroll
              for (int g = 0; g < 8; g++) sts1(dst + pc * 20736 + odd * 16 + g * 16, hl[g]);
              stg4(hp + 32, 0u, 0u, 0u, 0u);
            } else {
              sts1(dst + (odd ? 0 : 128), hl[0]); sts1(dst + 20736 + (odd ? 0 : 128), hl[1]);
            }
            stg4(hp, 0u, 0u, 0u, 0u);
          }
        }
        asm volatile("bar.arrive 1, 192;" ::: "memory");
        mbar_wait(rem_full, layer);
        mbar_wait(piece_full, 1 - layer);
#pragma unroll 1
        for (uint32_t b = 0; b < 5; b++) {
          const uint32_t blk = sb + REM + 27648 + b * 2048, k = (w - 10) * 32 + lane_id(), rr = k & 7;
          const uint32_t dst = blk + ((k >> 3) & 1) * 1024 + rr * 128 + (((k >> 4) ^ rr) << 4);
          uint32_t v[8];
          lds4(blk + k * 16, v); lds4(blk + 1024 + k * 16, v + 4);
          asm volatile("bar.sync 3, 64;" ::: "memory");
          sts4(dst, v); sts4(dst ^ 64, v + 4);
        }
        asm volatile("fence.proxy.async.shared::cta;" ::: "memory");
        mbar_arrive(remo_full);
        mbar_wait_sleep(xb_done, layer);
        if (w == 10 && layer == 1) {
          const uint32_t lane = lane_id();
          stg4(scp + OFF_S + (lane >> 3) * 96 + j * 8 + (lane & 7), 0u, 0u, 0u, 0u);
          stg4(scp + OFF_S + (4 + (lane >> 3)) * 96 + j * 8 + (lane & 7), 0u, 0u, 0u, 0u);
          if (lane < 8) stg4(scp + OFF_S + j * 96 + 64 + lane, 0u, 0u, 0u, 0u);
        }
#pragma unroll 1
        for (uint32_t i = 0; i < 8 && (w == 11 || layer == 1); i++) {
          zero_share(scp + OFF_X + ((w - 10) * 16 + layer * 8 + i) * SLAB, j, lane_id());
          __nanosleep(500);
        }
      }
    }
  } else {
    asm volatile("setmaxnreg.inc.sync.aligned.u32 240;");
    const bool lead = lane_id() == 0;
    Ring rg{0, 0};
    uint32_t prev = 0;
    uint32_t X[144];
    float rs0, rs1;
    const bool lead2 = lane_id() < 2;
    uint32_t empty_at;
    asm volatile("mapa.shared::cluster.u32 %0, %1, %2;" : "=r"(empty_at) : "r"(empty0), "r"(lane_id() & 1));
    auto release = [&](uint32_t st) { if (lead2) asm volatile("mbarrier.arrive.shared::cluster.b64 _, [%0];" :: "r"(empty_at + st * 8) : "memory"); };
    auto load_kb = [&](int kb, const uint4* src, const char* lo, uint32_t hoff) {
      const uint4* p;
      asm("{\n.reg .pred p;\n.reg .u64 t;\nsetp.ge.u32 p, %2, %3;\nadd.u64 t, %1, -2048;\nselp.b64 %0, t, %1, p;\n}" : "=l"(p) : "l"(src), "r"(j), "r"(kb));
#pragma unroll
      for (int i = 0; i < 4; i++) {
        if (kb == 8) { ldg2(X + 128 + 4 * i, lo + (32 + i) * 512); ldg2(X + 130 + 4 * i, lo + hoff + (32 + i) * 512); }
        else ldg4(X + 16 * kb + 4 * i, p + kb * 128 + i * 32);
      }
    };
    auto check_kb = [&](bool skip, int kb, const uint4* src, const char* lo, uint32_t hoff) {
      int n = 0;
#pragma unroll 1
      while (true) {
        uint32_t m = umin2(umin2(X[16 * kb], X[16 * kb + 4]), umin2(X[16 * kb + 8], X[16 * kb + 12]));
        if (kb == 8) m = umin2(m, umin2(umin2(X[130], X[134]), umin2(X[138], X[142])));
        if (__all_sync(~0u, m != 0u || skip)) break;
        SPIN_GUARD(n);
        load_kb(kb, src, lo, hoff);
      }
    };
#pragma unroll
    for (int i = 0; i < 16; i++) X[i] = 0u;
#pragma unroll 1
    for (uint32_t hf = 0; hf < 4; hf++) {
      const uint32_t layer = hf >> 1;
      const bool ffn = hf & 1;
      const uint32_t tag = 1 - layer;
      const uint32_t xbase = scr + OFF_X + (layer * 8 + w) * SLAB;
      float aA[32], aB[32];
      {
        const uint32_t lane = lane_id(), r = lane >> 2, q = lane & 3;
        const uint4* src = at(xbase + (ffn ? 32 * SLAB : 0) + lane);
        const char* lo = (const char*)at8(2 * (xbase + (ffn ? 32 * SLAB : 0)) + (ffn ? lane : 2 * lane));
        const uint32_t hoff = ffn ? 256 : 8;
        const uint32_t xoff = (w & 1) * 8192 + (16 * (w >> 1) + (lane & 15)) * 128 + (((lane >> 4) ^ (lane & 7)) << 4);
        auto load_x = [&](uint32_t b, uint32_t* d) {
#pragma unroll
          for (int i = 0; i < 4; i++) ldsm4(xs + b * STAGE + (xoff ^ (32 * i)), d[4 * i], d[4 * i + 1], d[4 * i + 2], d[4 * i + 3]);
        };
        auto load_any = [&](int kb) { if (hf == 0) load_x(blk(kb), X + 16 * kb); else load_kb(kb, src, lo, hoff); };
        float m0, m1, v0, v1;
        STAMP(ffn * 16 + 0);
        if (hf == 0) {
          float sum[2][4] = {}, sq0[4][4] = {}, sq1[4][4] = {};
          uint32_t p0, p1;
          mbar_wait(xbar0, 0);
          ldsm4(xs + xoff, p0, p1, X[0], X[1]);
          p0 = __byte_perm(__shfl_sync(~0u, p0, lane & 28), 0, 0x1010); p1 = __byte_perm(__shfl_sync(~0u, p1, lane & 28), 0, 0x1010);
#pragma unroll 3
          for (uint32_t b = 0; b < 9; b++) {
            uint32_t d[16];
            mbar_wait(xbar0 + 8 * b, 0);
            load_x(b, d);
#pragma unroll
            for (int i = 0; i < 16; i++) d[i] = sub_bf16x2(d[i], (i & 1) ? p1 : p0);
#pragma unroll
            for (int g = 0; g < 8; g++) {
              if (!(g & 1)) mma16(sum[(g >> 1) & 1], d[2 * g], d[2 * g + 1], d[2 * g + 2], d[2 * g + 3], 0x3f803f80u, 0x3f803f80u);
              mma8(sq0[g & 3], d[2 * g], d[2 * g + 1], d[2 * g]); mma8(sq1[g & 3], d[2 * g], d[2 * g + 1], d[2 * g + 1]);
            }
          }
          STAMP(1);
          GSTAMP(14);
#pragma unroll
          for (int kb = 0; kb < GD; kb++) load_x(blk(kb), X + 16 * kb);
          release((x_ring - empty0) / 8);
          auto tot = [](float (&c)[4][4], int e) { return (c[0][e] + c[1][e]) + (c[2][e] + c[3][e]); };
          const float a0 = (sum[0][0] + sum[1][0]) * (1.f / 576), a1 = (sum[0][2] + sum[1][2]) * (1.f / 576);
          const uint32_t dg = (lane & 28) + (r >> 1);
          v0 = fmaxf(fmaf(__shfl_sync(~0u, (r & 1) ? tot(sq0, 1) : tot(sq0, 0), dg), 1.f / 576, -a0 * a0), 0.f);
          v1 = fmaxf(fmaf(__shfl_sync(~0u, (r & 1) ? tot(sq1, 3) : tot(sq1, 2), dg), 1.f / 576, -a1 * a1), 0.f);
          m0 = bf_lo(p0) + a0; m1 = bf_lo(p1) + a1;
        } else {
          uint32_t s[3][4];
          const uint4* p = at(scr + OFF_S + ((ffn ? 16 : 0) + w) * 96 + q * 8 + r);
          const bool third = !ffn && q == 0;
          const uint32_t rdy = ffn ? tag : 1u;
          int n = 0;
          s[2][0] = rdy; s[2][1] = s[2][2] = s[2][3] = 0u;
#pragma unroll 1
          while (true) {
            ldg4(s[0], p); ldg4(s[1], p + 32);
            if (third) ldg4(s[2], p + 64);
            if (__all_sync(~0u, ((diff2(s[0][0], s[1][0], rdy) | diff2(s[1][0], s[2][0], rdy)) & 1u) == 0u)) break;
            SPIN_GUARD(n);
          }
          STAMP(ffn * 16 + 1);
          ZSTAMP(1 + ffn, 0);
          GSTAMP(14 + ffn);
#pragma unroll
          for (int kb = 1; kb < GD; kb++) load_kb(kb, src, lo, hoff);
          float t0 = 0.f, t1 = 0.f;
#pragma unroll
          for (int i = 0; i < 3; i++) { t0 += __uint_as_float(s[i][0]); t1 += __uint_as_float(s[i][2]); }
          m0 = quad_sum(t0) * (1.f / 576); m1 = quad_sum(t1) * (1.f / 576);
          const float cnt = ffn ? 72.f : 64.f, inv = ffn ? 1.f / 72 : 1.f / 64;
          v0 = 0.f; v1 = 0.f;
#pragma unroll
          for (int i = 0; i < 3; i++) {
            const float c = (i < 2 || third) ? cnt : 0.f;
            const float d0 = fmaf(__uint_as_float(s[i][0]), inv, -m0), d1 = fmaf(__uint_as_float(s[i][2]), inv, -m1);
            v0 += fmaf(d0 * d0, c, __uint_as_float(s[i][1])); v1 += fmaf(d1 * d1, c, __uint_as_float(s[i][3]));
          }
          v0 = quad_sum(v0) * (1.f / 576); v1 = quad_sum(v1) * (1.f / 576);
        }
        rs0 = rsqrtf(v0 + 1e-5f); rs1 = rsqrtf(v1 + 1e-5f);
        const uint32_t mean0 = pack_bf16(m0, m0), mean1 = pack_bf16(m1, m1);
#pragma unroll
        for (int kb = 0; kb < 9; kb++) {
          if (kb > 0) check_kb(hf == 0, kb, src, lo, hoff);
          if (kb + GD < 9) load_any(kb + GD);
          if (kb + GD == 8 && hf == 0 && lead) mbar_arrive(x_done);
          if (kb == 8) mbar_wait(x_done, 0);
#pragma unroll
          for (int i = 16 * kb; i < 16 * kb + 16; i++) X[i] = sub_bf16x2(X[i], (i & 1) ? mean1 : mean0);
          ZSTAMP(1 + ffn, 1 + 3 * kb);
          mbar_wait(full0 + rg.st * 8, rg.ph);
          ZSTAMP(1 + ffn, 2 + 3 * kb);
          const uint64_t desc = DESC_HI | ((sd + rg.st * STAGE) >> 4);
          wg_fence();
#pragma unroll
          for (int i = 0; i < 4; i++) wgmma_rs_n64(aA, X + 4 * (4 * kb + i), desc + i * 128, kb + i != 0);
          if (kb == 8) { wg_commit(); wg_wait<1>(); wg_fence(); }
#pragma unroll
          for (int i = 0; i < 4; i++) wgmma_rs_n64(aB, X + 4 * (4 * kb + i), desc + 512 + i * 128, kb + i != 0);
          wg_commit();
          wg_wait<1>();
          ZSTAMP(1 + ffn, 3 + 3 * kb);
          if (kb > 0) release(prev);
          prev = rg.st; rg.next();
        }
        ZSTAMP(1 + ffn, 28);
        ZSTAMP(4, 0);
        STAMP(ffn * 16 + 2);
      }
      if (!ffn) {
      const uint32_t lane = lane_id(), r = lane >> 2, q = lane & 3;
      const uint32_t kvrow = sb + KVS + (w & 1) * 10368 + (16 * (w >> 1)) * 144;
      uint32_t Q[18], Km[3][8], Ke[3][4];
      const bool edge = (t == 0 && w < 2);
      const uint32_t row0 = edge ? sb + KVS + 8 * 144 : kvrow + (lane & 7) * 144, row1 = kvrow + (8 + (lane & 7)) * 144;
      {
        const uint32_t dst = kvrow + (8 + r) * 144 + q * 4 + odd * 16, dstr = dst + (odd ? -16 : 128);
        const bool edge_out = w >= 6 && t < 15;
        uint4* const hp = at(scr + TILE + OFF_H + ((layer * 8 + j) * 2 + (w & 1)) * 192 + lane);
        auto put_kv = [&](float (&a)[32], int part, int half) {
          uint32_t hl[4];
#pragma unroll
          for (int i = 0; i < 16; i++) asm volatile("" : "+f"(a[16 * half + i]) :: "memory");
#pragma unroll
          for (int i = 0; i < 4; i++) {
            const int g = 4 * half + i;
            hl[i] = pack_bf16(a[4 * g + 2] * rs1, a[4 * g + 3] * rs1);
            sts1(dst + part * 20736 + g * 16, pack_bf16(a[4 * g] * rs0, a[4 * g + 1] * rs0)); sts1(dst + part * 20736 + 8 * 144 + g * 16, hl[i]);
          }
          if (edge_out) stg4(hp + part * 64 + half * 32, nz(hl[0]), hl[1], hl[2], hl[3]);
        };
        put_kv(aA, 0, 0); put_kv(aA, 0, 1);
        if (lead) mbar_arrive(kv_free);
        wg_wait<0>();
        release(prev);
        release((side_full + 48 - empty0) / 8); release((side_full + 56 - empty0) / 8);
        float aR[12];
        mbar_wait(rem_full, layer);
        const uint64_t dr = DESC_REM | ((sd + REM) >> 4);
        wg_fence();
#pragma unroll
        for (int s = 0; s < 36; s++) {
          wgmma_rs_n24(aR, X + 4 * s, dr + s * 16, s != 0);
          if (s == 4) put_kv(aB, 1, 0);
          if (s == 16) put_kv(aB, 1, 1);
        }
        wg_commit();
#pragma unroll
        for (int kb = 0; kb < 9; kb++) {
          if (!(kb & 1)) mbar_wait(full0 + rg.st * 8, rg.ph);
          const uint64_t desc = DESC_HI | ((sd + rg.st * STAGE + (kb & 1) * 8192) >> 4);
          wg_fence();
#pragma unroll
          for (int i = 0; i < 4; i++) wgmma_rs_n64(aB, X + 4 * (4 * kb + i), desc + i * 128, kb + i != 0);
          wg_commit();
          wg_wait<1>();
          if (kb > 0 && !(kb & 1)) release(prev);
          if (kb & 1) { prev = rg.st; rg.next(); }
          if (kb == 0) {
            pin(aR);
            const uint32_t k1 = pack_bf16(aR[2] * rs1, aR[3] * rs1), v1 = pack_bf16(aR[6] * rs1, aR[7] * rs1);
            if (edge_out) stg4(hp + 128, nz(k1), v1, 0u, 0u);
            sts1(dstr, pack_bf16(aR[0] * rs0, aR[1] * rs0)); sts1(dstr + 8 * 144, k1);
            sts1(dstr + 20736, pack_bf16(aR[4] * rs0, aR[5] * rs0)); sts1(dstr + 20736 + 8 * 144, v1);
            Q[16] = pack_bf16(aR[8], aR[9]); Q[17] = pack_bf16(aR[10], aR[11]);
            if (w < 4) asm volatile("bar.arrive 2, 256;" ::: "memory");
          }
          if (kb == 8) {
            if (w < 4) asm volatile("bar.sync 1, 192;" ::: "memory");
            else asm volatile("bar.sync 2, 256;" ::: "memory");
#pragma unroll
            for (int nt = 0; nt < 3; nt++) {
              const uint32_t ra = (nt == 0 ? row0 : row1 + (nt - 1) * 8 * 144);
              ldsm4(ra + odd * 16 + (lane >> 3) * 16, Km[nt][0], Km[nt][1], Km[nt][2], Km[nt][3]);
              ldsm4(ra + odd * 16 + 64 + (lane >> 3) * 16, Km[nt][4], Km[nt][5], Km[nt][6], Km[nt][7]);
              ldsm4(ra + (odd ? 0 : 32) + (lane >> 3) * 32, Ke[nt][0], Ke[nt][1], Ke[nt][2], Ke[nt][3]);
            }
          }
        }
        wg_wait<0>();
        pin(aB);
        mbar_wait(att_done, layer ^ (w >> 2));
        STAMP(3);
#pragma unroll
        for (int i = 0; i < 16; i++) Q[i] = pack_bf16(aB[2 * i], aB[2 * i + 1]);
      }
      uint32_t res[18] = {};
      if (layer) {
        const uint4* p = at(xbase + ((9 * j + 1) >> 1) * 32 + lane);
#pragma unroll
        for (int i = 0; i < 4; i++) ldg4(res + 4 * i, p + i * 32);
        ldg2(res + 16, at8(2 * (xbase + (9 * (j >> 1) + 4) * 32 + lane) + odd));
      }
      {
        uint32_t V01[12][2], V2[12];
        const uint32_t rv = ((lane & 8) ? row1 : row0) + 20736, rw = row1 + 8 * 144 + 20736;
#pragma unroll
        for (int i = 0; i < 4; i++) ldsm4t(rv + odd * 16 + i * 32 + (lane >> 4) * 16, V01[2 * i][0], V01[2 * i][1], V01[2 * i + 1][0], V01[2 * i + 1][1]);
#pragma unroll
        for (int i = 0; i < 2; i++) ldsm4t(rv + (odd ? 0 : 32) + i * 64 + (lane >> 4) * 32, V01[8 + 2 * i][0], V01[8 + 2 * i][1], V01[9 + 2 * i][0], V01[9 + 2 * i][1]);
        ldsm4t(rw + odd * 16 + (lane >> 3) * 16, V2[0], V2[1], V2[2], V2[3]);
        ldsm4t(rw + odd * 16 + 64 + (lane >> 3) * 16, V2[4], V2[5], V2[6], V2[7]);
        ldsm4t(rw + (odd ? 0 : 32) + (lane >> 3) * 32, V2[8], V2[9], V2[10], V2[11]);
        const bool up0 = 2 * q > r, up1 = 2 * q + 1 > r;
        const uint32_t upm = (up0 ? 0xffffu : 0u) | (up1 ? 0xffff0000u : 0u);
        const float c0 = 0.23570226039551584f * 1.4426950408889634f * rs0, c1 = 0.23570226039551584f * 1.4426950408889634f * rs1;
        const float masked = -1e9f * 1.4426950408889634f * rcp(c0);
        const int qe = odd ? 9 : q, qo = odd ? q : -1;
        uint32_t Qe[8];
#pragma unroll
        for (int h = 0; h < 4; h++)
#pragma unroll
          for (int e = 0; e < 2; e++) Qe[2 * h + e] = qe <= h ? Q[4 * h + 4 + e] : qo >= h ? Q[(4 * h + 16 + e) % 18] : 0u;
#pragma unroll
        for (int h = 1; h < 4; h++)
#pragma unroll
          for (int e = 0; e < 2; e++) { if (qe < h) Q[4 * h + e] = 0u; if (qo >= h) Q[4 * h - 2 + e] = 0u; }
        uint32_t Om[16], Oe[8];
        uint4* const po = at(xbase + 16 * SLAB + 4 * j * 32 + lane);
        float sv[4][4], mx[4][2];
#pragma unroll
        for (int h = 0; h < 4; h++) {
          float S[3][4];
#pragma unroll
          for (int nt = 0; nt < 3; nt++) {
            mma16z(S[nt], Q + 4 * h, Km[nt][2 * h], Km[nt][2 * h + 1]);
            mma8(S[nt], Qe[2 * h], Qe[2 * h + 1], Ke[nt][h]);
          }
          if (edge) S[0][0] = S[0][1] = masked;
          sv[h][0] = up0 ? S[0][0] : S[1][0]; sv[h][1] = up1 ? S[0][1] : S[1][1];
          sv[h][2] = up0 ? S[1][2] : S[2][2]; sv[h][3] = up1 ? S[1][3] : S[2][3];
        }
        auto quad8 = [&](auto&& op) {
#pragma unroll
          for (int d = 1; d < 3; d++) {
            float o[8];
#pragma unroll
            for (int i = 0; i < 8; i++) o[i] = __shfl_xor_sync(~0u, mx[i >> 1][i & 1], d);
#pragma unroll
            for (int i = 0; i < 8; i++) mx[i >> 1][i & 1] = op(mx[i >> 1][i & 1], o[i]);
          }
        };
#pragma unroll
        for (int i = 0; i < 8; i++) mx[i >> 1][i & 1] = fmaxf(sv[i >> 1][2 * (i & 1)], sv[i >> 1][2 * (i & 1) + 1]);
        quad8([](float x, float y) { return fmaxf(x, y); });
#pragma unroll
        for (int i = 0; i < 8; i++) {
          const float c = (i & 1) ? c1 : c0, m = mx[i >> 1][i & 1] * c;
          float* p = sv[i >> 1] + 2 * (i & 1);
          p[0] = ex2(fmaf(p[0], c, -m)); p[1] = ex2(fmaf(p[1], c, -m));
          mx[i >> 1][i & 1] = p[0] + p[1];
        }
        if (w >= 4 && lead) mbar_arrive(att_done + ((__float_as_uint(mx[0][0]) | __float_as_uint(mx[3][1])) & (rg.ph >> 1)));
        quad8([](float x, float y) { return x + y; });
        auto u = [&](int i) { return __float_as_uint(mx[i >> 1][i & 1]); };
        const uint32_t none = or3(or3(u(0), u(1), u(2)), or3(u(3), u(4), u(5)), u(6) | u(7)) & (rg.ph >> 1);
#pragma unroll
        for (int h = 0; h < 4; h++) {
          const float i0 = rcp(mx[h][0]), i1 = rcp(mx[h][1]);
          const uint32_t p0 = pack_bf16(sv[h][0] * i0, sv[h][1] * i0), p1 = pack_bf16(sv[h][2] * i1, sv[h][3] * i1);
          const uint32_t pf[6] = {p0 & upm, p0 & none, p0 & ~upm, p1 & upm, p1 & none, p1 & ~upm};
#pragma unroll
          for (int gi = 0; gi < 3; gi++) {
            const int g = gi < 2 ? 2 * h + gi : 8 + h;
            float o[4];
            mma16z(o, pf, V01[g][0], V01[g][1]);
            mma8(o, pf[4], pf[5], V2[g]);
            uint32_t* d = gi < 2 ? Om + 2 * g : Oe + 2 * h;
            d[0] = pack_bf16(o[0], o[1]); d[1] = pack_bf16(o[2], o[3]);
          }
          if (h > 0) {
#pragma unroll
            for (int e = 0; e < 2; e++) {
              if (qe < h) Om[4 * h + e] = Oe[2 * h - 2 + e];
              if (qo >= h) Om[4 * h - 2 + e] = Oe[2 * h + e];
            }
            Om[4 * h - 4] = nz(Om[4 * h - 4]);
            stg4(po + (h - 1) * 32, Om[4 * h - 4], Om[4 * h - 3], Om[4 * h - 2], Om[4 * h - 1]);
          }
        }
        STAMP(4);
        Om[12] = nz(Om[12]);
        stg4(po + 96, Om[12], Om[13], Om[14], Om[15]);
        stg2(at8(2 * (xbase + 16 * SLAB + 1024 + j * 16) + lane), nz(odd ? Oe[0] : Oe[6]), odd ? Oe[1] : Oe[7]);
#pragma unroll
        for (int i = 0; i < 16; i++) X[i] = Om[i];
      }
      if (lane == 0) asm volatile("st.relaxed.gpu.global.b32 [%0], %1;" :: "l"(at(scr + OFF_S + (8 + w) * 96 + j * 8)), "r"(tag) : "memory");
      {
        if (layer == 0) {
          const uint32_t xrow = (w & 1) * 8192 + (16 * (w >> 1) + (lane & 15)) * 128;
          uint32_t u0, u1;
          mbar_wait(xbar0, 1); mbar_wait(xbar0 + 8, 1);
#pragma unroll
          for (int i = 0; i < 4; i++)
            ldsm4(sb + PARK + 2 * STAGE + xrow + (((2 * i + (lane >> 4)) ^ (lane & 7)) << 4), res[4 * i], res[4 * i + 1], res[4 * i + 2], res[4 * i + 3]);
          ldsm4(sb + REM + 37888 + (xrow >> 3), res[16], res[17], u0, u1);
        }
        const uint4* src = at(xbase + 16 * SLAB + lane);
        const uint32_t st0 = rg.st;
        auto stage_of = [&](uint32_t i) { const uint32_t x = st0 + i; return i >= 3 ? NST - 3 + i : x >= NST ? x - NST : x; };
        {
          const uint32_t x = st0 + lane, wrap = x >= NST;
          mbar_wait(lane < 3 ? full0 + (x - wrap * NST) * 8 : lane < 5 ? side_full - 24 + lane * 8 : remo_full, lane < 3 ? rg.ph ^ wrap : layer);
          __syncwarp();
          if (st0 >= 3) { rg.st = st0 - 3; rg.ph ^= 1; } else rg.st = st0 + 3;
        }
        float acc[36];
        auto block72 = [&](uint32_t kb, uint32_t base, const uint32_t* a) {
          const uint64_t d0 = DESC_HI | ((base >> 4) + (((sd + REM + 27648 + (kb >> 1) * 2048 + (kb & 1) * 64 - base) >> 4) << 16));
          wg_fence();
#pragma unroll
          for (int i = 0; i < 4; i++) wgmma_rs_n72(acc, a + 4 * i, d0 - (uint64_t)(i * ((127u << 16) - 128u)), 1);
          wg_commit();
        };
#pragma unroll
        for (int i = 0; i < 18; i++) { acc[2 * i] = bf_lo(res[i]); acc[2 * i + 1] = bf_hi(res[i]); }
        block72(0, sd + st0 * STAGE + 8192, X);
        {
          const uint4* fp = at(scr + OFF_S + (8 + w) * 96 + (lane & 7) * 8);
          int n = 0;
          STAMP(8);
#pragma unroll 1
          while (true) {
            uint32_t f;
            asm volatile("ld.relaxed.gpu.global.b32 %0, [%1];" : "=r"(f) : "l"(fp) : "memory");
            if (__all_sync(~0u, f == tag)) break;
            SPIN_GUARD(n);
          }
          wg_wait<0>(); release(st0);
          STAMP(9);
        }
#pragma unroll
        for (int kb = 1; kb < GO; kb++) load_kb(kb, src, (const char*)src - lane * 8, 256);
        __syncwarp();
        uint32_t m = ~0u;
#pragma unroll
        for (int kb = 1; kb < 9; kb++) {
          m = umin2(m, umin2(umin2(X[16 * kb], X[16 * kb + 4]), umin2(X[16 * kb + 8], X[16 * kb + 12])));
          if (kb == 8) m = umin2(m, umin2(umin2(X[130], X[134]), umin2(X[138], X[142])));
          if (kb + GO - 1 < 9) {
            const uint4* s2 = src + (m == 0u);
            load_kb(kb + GO - 1, s2, (const char*)s2 - lane * 8, 256);
            __syncwarp();
          }
          block72(kb, sd + stage_of((kb + 1) >> 1) * STAGE + (~kb & 1) * 8192, X + 16 * kb);
          if (kb == 3 || kb == 5) { wg_wait<1>(); release(stage_of(kb >> 1)); }
        }
        uint32_t redo;
        asm volatile("{\n.reg .pred p;\nsetp.eq.u32 p, %1, 0;\nbar.red.or.pred p, %2, 128, p;\nselp.u32 %0, 1, 0, p;\n}" : "=r"(redo) : "r"(m), "r"(5 + (w >> 2)) : "memory");
        wg_wait<0>();
        pin(acc);
        if (__any_sync(~0u, redo || FORCE_REDO)) {
#pragma unroll
          for (int i = 0; i < 18; i++) { res[i] = __shfl_sync(~0u, res[i], lane); acc[2 * i] = bf_lo(res[i]); acc[2 * i + 1] = bf_hi(res[i]); }
          const uint32_t box = REM + (w >> 2) * 8192, bar = redo_full + (w >> 2) * 8;
#pragma unroll 1
          for (uint32_t kb = 0; kb < 10; kb++) {
            asm volatile("bar.sync %0, 128;" :: "r"(5 + (w >> 2)) : "memory");
            if ((w & 3) == 0)
              asm volatile("{\n.reg .pred e;\nelect.sync _|e, 0xffffffff;\n@e mbarrier.arrive.expect_tx.shared::cta.b64 _, [%2], 8192;\n"
                           "@e cp.async.bulk.tensor.3d.shared::cluster.global.mbarrier::complete_tx::bytes [%0], [%1, {%3, %4, %5}], [%2];\n}"
                           :: "r"(sb + box), "l"(&maps.m[kb >= 8 ? 8 : 1]), "r"(bar), "r"(72 * j + 8 * odd), "r"(kb >= 8 ? 64 : 0),
                              "r"(kb >= 8 ? 0 : (9 * blk(kb) + 1) >> 1) : "memory");
            mbar_wait(bar, kb & 1);
            if (kb == 9) break;
            int n = 0;
#pragma unroll 1
            while (true) {
              const char* l = (const char*)(src + blk(kb) * 128) - (kb == 8 ? lane * 8 : 0);
#pragma unroll
              for (int i = 0; i < 4; i++) ldg2(X + 4 * i, l + i * 512);
              uint32_t mm = umin2(umin2(X[0], X[4]), umin2(X[8], X[12]));
              l += (kb == 8 ? 256 : 8) + (mm == 0u ? 16 : 0);
#pragma unroll
              for (int i = 0; i < 4; i++) ldg2(X + 4 * i + 2, l + i * 512);
              if (kb == 8) mm = umin2(mm, umin2(umin2(X[2], X[6]), umin2(X[10], X[14])));
              if (__all_sync(~0u, mm != 0u)) break;
              SPIN_GUARD(n);
            }
            block72(kb, sd + box, X);
            wg_wait<0>();
            pin(acc);
          }
        }
        STAMP(10);
#pragma unroll
        for (int i = 0; i < 18; i++) { res[i] = pack_bf16(acc[2 * i], acc[2 * i + 1]); if (!(i & 3)) res[i] = nz(res[i]); }
        auto put = [&] {
          put4(at(xbase + 32 * SLAB + 4 * j * 32 + lane), res);
          stg2(at8(2 * (xbase + 32 * SLAB + 1024 + j * 16) + lane), res[16], res[17]);
        };
        if (j < PRI) put();
        publish_stats<9>(at(scr + OFF_S + (16 + w) * 96 + j * 8 + r), acc, tag, lane);
        if (j >= PRI) put();
#pragma unroll
        for (int i = 0; i < 16; i++) X[i] = res[i];
      }
      continue;
      }
      const uint32_t hp = sb + PARK + w * 512 + lane_id() * 16;
      auto pack8 = [&](float (&a)[32], int p, uint32_t* o) {
#pragma unroll
        for (int e = 0; e < 8; e++) asm volatile("" : "+f"(a[8 * p + e]) :: "memory");
#pragma unroll
        for (int e = 0; e < 4; e++) o[e] = pack_bf16(a[8 * p + 2 * e], a[8 * p + 2 * e + 1]);
      };
      const float ka0 = 0.7978845608028654f * rs0, kb0 = 0.044715f * ka0 * rs0 * rs0, ku0 = 0.5f * rs0 * rs0;
      const float ka1 = 0.7978845608028654f * rs1, kb1 = 0.044715f * ka1 * rs1 * rs1, ku1 = 0.5f * rs1 * rs1;
      auto packu8 = [&](int p, uint32_t* o) {
#pragma unroll
        for (int e = 0; e < 8; e++) asm volatile("" : "+f"(aA[8 * p + e]) :: "memory");
#pragma unroll
        for (int e = 0; e < 4; e++) o[e] = pack_bf16(aA[8 * p + 2 * e] * ((e & 1) ? ku1 : ku0), aA[8 * p + 2 * e + 1] * ((e & 1) ? ku1 : ku0));
      };
      auto geglu8 = [&](int p, uint32_t* u) {
#pragma unroll
        for (int e = 0; e < 8; e++) asm volatile("" : "+f"(aB[8 * p + e]) :: "memory");
        float h[8];
#pragma unroll
        for (int e = 0; e < 8; e++) {
          const float g = aB[8 * p + e];
          h[e] = fmaf(g, tanh_ap(g * fmaf(g * g, (e & 2) ? kb1 : kb0, (e & 2) ? ka1 : ka0)), g);
        }
#pragma unroll
        for (int e = 0; e < 4; e++) u[e] = mul_bf16x2(pack_bf16(h[2 * e], h[2 * e + 1]), u[e]);
      };
      uint32_t ready = 0;
      auto box = [&](int b, auto&& filler) {
        const int kb = b < 9 ? b : b - 9;
        if (b == 0) mbar_wait_trap(full0 + rg.st * 8, rg.ph);
        else if (!(b & 1)) mbar_wait_unless(ready, full0 + rg.st * 8, rg.ph);
        const uint64_t desc = DESC_HI | ((sd + rg.st * STAGE + (b & 1) * 8192) >> 4);
        if (b & 1) { prev = rg.st; rg.next(); }
        wg_fence();
#pragma unroll
        for (int i = 0; i < 4; i++) {
          if (b < 9) wgmma_rs_n64(aA, X + 4 * (4 * kb + i), desc + i * 128, kb + i != 0);
          else wgmma_rs_n64(aB, X + 4 * (4 * kb + i), desc + i * 128, kb + i != 0);
          if ((b & 1) && b < 17 && i == 0) ready = mbar_peek(full0 + rg.st * 8, rg.ph);
          if (i == 1) filler();
        }
        wg_commit();
        if (!(b & 1)) { wg_wait<1>(); release(prev); }
      };
      auto nop = [] {};
#pragma unroll
      for (int p = 0; p < 4; p++) { uint32_t o[4]; packu8(p, o); sts4(hp + p * 4096, o); }
      box(0, nop);
      if (lead) mbar_arrive(xb_done);
#pragma unroll 1
      for (int c = 1;; c++) {
        const uint32_t hc = hp + c * 4 * 4096;
#pragma unroll
        for (int b = 1; b < 18; b++) box(b, [&] {
          if ((b & 1) && b < 8) { uint32_t o[4]; const uint32_t a = hc - (4 - (b >> 1)) * 4096; lds4(a, o); geglu8(b >> 1, o); sts4(a, o); }
          if ((b & 1) && b > 10) { uint32_t o[4]; packu8((b - 11) >> 1, o); if (c < 8) sts4(hc + ((b - 11) >> 1) * 4096, o); } });
        ZSTAMP(4, c);
        if (c == 8) break;
        box(0, nop);
      }
      wg_wait<0>();
      STAMP(21);
      GSTAMP(19);
      auto unpark = [&](int kb) {
#pragma unroll
        for (int s = 4 * kb; s < 4 * kb + 4; s++) lds4(hp + s * 4096, X + 4 * s);
      };
      unpark(0);
      uint32_t U[16];
#pragma unroll
      for (int p = 0; p < 4; p++) packu8(p, U + 4 * p);
#pragma unroll
      for (int b = 0; b < 8; b++) box(b, [&] {
        if (b < 7) unpark(b + 1);
        if (b & 1) {
          geglu8(b >> 1, U + 2 * (b - 1));
          if (rg.ph > 1) sts4(hp, U + 2 * (b - 1));
#pragma unroll
          for (int i = 0; i < 4; i++) X[128 + 2 * (b - 1) + i] = U[2 * (b - 1) + i];
        } });
      STAMP(24);
      if (layer == 0 && lead) mbar_arrive(park_free);
      const uint32_t lane2 = lane_id();
      uint4* const pw = scp + OFF_P + (j * 8 + w) * SLAB + lane2;
      const uint32_t pr = scr + OFF_P + w * SLAB + 4 * j * 32 + lane2;
      auto put_part = [&](float (&a)[32], int p, uint32_t chunk) {
        uint32_t o[4];
        pack8(a, p, o);
        stg4(pw + (chunk * 4 + p) * 32, (o[0] & ~1u) | tag, o[1], o[2], o[3]);
      };
      auto slot = [&](int p) { return sb + w * 2048 + (p < 3 ? PARK + p * 16384 : KVS + (p - 3) * 16384); };
      auto fetch = [&](int p) {
        bulk_load(slot(p), at(scr + OFF_P + (((j - p) & 7) * 8 + w) * SLAB + 4 * j * 32), 2048, pbar0 + w * 8, true);
      };
#pragma unroll 1
      for (int sp = 0;; sp++) {
        const uint32_t ca = sp == 0 ? 8 : ((j + 2 * sp) & 7), cb = (j + 2 * sp + 1) & 7;
        if (sp == 1 && lead) mbar_arrive(c8_go);
#pragma unroll
        for (int b = 8; b < 18; b++) box(b, [&] {
          if (b >= 11 && b < 15) put_part(aA, b - 11, ca);
          if (b == 17 && sp > 1) { if (sp == 3) mbar_wait(c8_done, layer); fetch(2 * sp - 2); } });
        STAMP(25 + sp);
        if (sp == 3) break;
#pragma unroll
        for (int b = 0; b < 8; b++) box(b, [&] {
          if (b >= 1 && b < 5) put_part(aB, b - 1, cb);
          if (b == 7 && sp > 0) fetch(2 * sp - 1); });
      }
      auto load_p = [&](int p, uint32_t* d) {
#pragma unroll
        for (int i = 0; i < 4; i++) ldg4(d + 4 * i, at(pr + ((j - p) & 7) * 8 * SLAB) + i * 32);
      };
      auto bad = [&](const uint32_t* d, uint32_t tg) { return diff2(d[0], d[4], tg) | diff2(d[8], d[12], tg); };
      uint32_t late = 0;
#pragma unroll
      for (int b = 0; b < 9; b++) {
        if (b == 6) { mbar_wait(lane2 & 1 ? res_full : pbar0 + w * 8, layer); __syncwarp(); }
        box(b, [&] {
          if (b == 1) {
#pragma unroll
            for (int p = 0; p < 4; p++) put_part(aB, p, (j + 7) & 7);
          }
          if (b == 3) { load_p(5, X); load_p(6, X + 16); }
          if (b == 7) {
            late = bad(X, tag) | bad(X + 16, tag);
#pragma unroll
            for (int i = 0; i < 4; i++) ldg4(X + 32 + 4 * i, at(pr + ((j - 7) & 7) * 8 * SLAB + (late == 0x7fc12345u)) + i * 32);
          } });
      }
#pragma unroll
      for (int p = 1; p < 5; p++)
#pragma unroll
        for (int i = 0; i < 4; i++) lds4(slot(p) + lane2 * 16 + i * 512, X + 48 + 16 * p + 4 * i);
#pragma unroll
      for (int i = 0; i < 4; i++) {
        const bool split = j == 2 * i + 1;
        const uint32_t a = slot(0) + i * 512 + (split ? lane2 * 8 : lane2 * 16);
        lds2(a, X + 48 + 4 * i); lds2(a + (split ? 256 : 8), X + 50 + 4 * i);
      }
      wg_wait<0>();
      release(rg.st); rg.next();
      pin(aA);
      STAMP(22);
      GSTAMP(20);
      {
        const uint32_t lane = lane2, r = lane >> 2, q = lane & 3;
        const uint32_t eye = r == 2 * q ? 0x3f80u : r == 2 * q + 1 ? 0x3f800000u : 0u;
        auto add = [&](const uint32_t* d) {
#pragma unroll
          for (int g = 0; g < 8; g++) mma8(aA + 4 * g, d[2 * g], d[2 * g + 1], eye);
        };
        int n = 0;
        late = or3(late, bad(X + 64, tag), or3(bad(X + 80, tag), bad(X + 96, tag), bad(X + 112, tag)));
#pragma unroll 1
        while (!__all_sync(~0u, (late & 1u) == 0u)) {
          SPIN_GUARD(n);
          const uint32_t pc = scr + OFF_P + w * SLAB + 4 * j * 32 + lane_id();
          late = 0;
#pragma unroll
          for (int p = 1; p < 8; p++) {
            uint32_t* d = X + (p < 5 ? 48 + 16 * p : 16 * (p - 5));
#pragma unroll
            for (int i = 0; i < 4; i++) ldg4(d + 4 * i, at(pc + ((j - p) & 7) * 8 * SLAB) + i * 32);
            late |= bad(d, tag);
          }
        }
        add(X); add(X + 16);
#pragma unroll
        for (int p = 1; p < 6; p++) add(X + 48 + 16 * (p % 5));
        STAMP(11);
        const uint32_t tg = tag ^ (__float_as_uint(aA[28]) == 0x7fc12345u ? 2u : 0u);
#pragma unroll 1
        while (!__all_sync(~0u, (bad(X + 32, tg) & 1u) == 0u)) { SPIN_GUARD(n); load_p(7, X + 32); }
        add(X + 32);
        STAMP(12);
        uint32_t res[16];
#pragma unroll
        for (int i = 0; i < 16; i++) X[i] = res[i] = pack_bf16(aA[2 * i], aA[2 * i + 1]);
        if (layer == 0) {
#pragma unroll
          for (int i = 0; i < 4; i++) X[4 * i] = nz(X[4 * i]);
          auto put = [&] { put4(at(xbase + 8 * SLAB + 4 * j * 32 + lane), X); };
          if (j < PRI) put();
          publish_stats<8>(at(scr + OFF_S + w * 96 + j * 8 + r), aA, 1u, lane);
          if (j >= PRI) put();
        } else {
          const uint32_t tb = slot(0);
          __syncwarp();
#pragma unroll
          for (int i = 0; i < 4; i++) {
            const uint32_t row = (lane2 & 7) + (lane2 & 8), g = 2 * i + (lane2 >> 4);
            asm volatile("stmatrix.sync.aligned.m8n8.x4.shared.b16 [%0], {%1,%2,%3,%4};"
                         :: "r"(tb + row * 128 + ((g ^ (row & 7)) << 4)), "r"(res[4 * i]), "r"(res[4 * i + 1]), "r"(res[4 * i + 2]), "r"(res[4 * i + 3]) : "memory");
          }
          __syncwarp();
#pragma unroll
          for (int i = 0; i < 4; i++) {
            const uint32_t row = 4 * i + (lane2 >> 3), g = lane2 & 7;
            uint32_t v[4];
            lds4(tb + row * 128 + ((g ^ (row & 7)) << 4), v);
            ((uint4*)out + ((128 * t + 32 * (w >> 1) + 2 * (lane2 >> 3) + (w & 1)) * 72 + 8 * j + g))[i * 576] = make_uint4(v[0], v[1], v[2], v[3]);
          }
        }
      }
      STAMP(23);
    }
  }
}

typedef CUresult (*EncodeFn)(CUtensorMap*, CUtensorMapDataType, cuuint32_t, void*, const cuuint64_t*, const cuuint64_t*,
                             const cuuint32_t*, const cuuint32_t*, CUtensorMapInterleave, CUtensorMapSwizzle,
                             CUtensorMapL2promotion, CUtensorMapFloatOOBfill);

CUtensorMap make_map(EncodeFn f, const void* p, uint64_t cols, uint64_t rows, uint64_t grp) {
  CUtensorMap m;
  cuuint64_t dims[3] = {cols, grp, rows / grp}, str[2] = {cols * 2, cols * 2 * grp};
  cuuint32_t box[3] = {64, 16, 4}, es[3] = {1, 1, 1};
  f(&m, CU_TENSOR_MAP_DATA_TYPE_BFLOAT16, 3, const_cast<void*>(p), dims, str, box, es, CU_TENSOR_MAP_INTERLEAVE_NONE,
    CU_TENSOR_MAP_SWIZZLE_128B, CU_TENSOR_MAP_L2_PROMOTION_NONE, CU_TENSOR_MAP_FLOAT_OOB_FILL_NONE);
  return m;
}
CUtensorMap make_rem_map(EncodeFn f, const void* p, uint64_t cols) {
  CUtensorMap m;
  cuuint64_t dims[2] = {cols, 576}, str[1] = {cols * 2};
  cuuint32_t box[2] = {8, 144}, es[2] = {1, 1};
  f(&m, CU_TENSOR_MAP_DATA_TYPE_BFLOAT16, 2, const_cast<void*>(p), dims, str, box, es, CU_TENSOR_MAP_INTERLEAVE_NONE,
    CU_TENSOR_MAP_SWIZZLE_NONE, CU_TENSOR_MAP_L2_PROMOTION_NONE, CU_TENSOR_MAP_FLOAT_OOB_FILL_NONE);
  return m;
}

}

extern "C" void kernel_launch(void* const* d_in, const int* in_sizes, int n_in, void* d_out, int out_size) {
  void* fn = nullptr;
  cudaDriverEntryPointQueryResult qr;
  cudaGetDriverEntryPoint("cuTensorMapEncodeTiled", &fn, cudaEnableDefault, &qr);
  EncodeFn enc = (EncodeFn)fn;
  Maps maps;
  maps.m[0] = make_map(enc, d_in[1], 1728, 576, 16); maps.m[1] = make_map(enc, d_in[2], 576, 576, 16);
  maps.m[2] = make_map(enc, d_in[4], 4608, 576, 16); maps.m[3] = make_map(enc, d_in[5], 4608, 576, 16);
  maps.m[4] = make_map(enc, d_in[6], 576, 4608, 16);
  maps.m[5] = make_rem_map(enc, d_in[1], 1728); maps.m[6] = make_rem_map(enc, d_in[2], 576);
  maps.m[8] = make_map(enc, d_in[2], 576, 576, 144); maps.m[9] = make_map(enc, d_in[4], 4608, 576, 144);
  maps.m[10] = make_map(enc, d_in[5], 4608, 576, 144);
  {
    cuuint64_t dims[3] = {576, 1024, 2}, str[2] = {2304, 1152};
    cuuint32_t box[3] = {64, 64, 2}, es[3] = {1, 1, 1};
    enc(&maps.m[7], CU_TENSOR_MAP_DATA_TYPE_BFLOAT16, 3, d_in[0], dims, str, box, es, CU_TENSOR_MAP_INTERLEAVE_NONE,
        CU_TENSOR_MAP_SWIZZLE_128B, CU_TENSOR_MAP_L2_PROMOTION_NONE, CU_TENSOR_MAP_FLOAT_OOB_FILL_NONE);
    box[0] = 8;
    enc(&maps.m[11], CU_TENSOR_MAP_DATA_TYPE_BFLOAT16, 3, d_in[0], dims, str, box, es, CU_TENSOR_MAP_INTERLEAVE_NONE,
        CU_TENSOR_MAP_SWIZZLE_NONE, CU_TENSOR_MAP_L2_PROMOTION_NONE, CU_TENSOR_MAP_FLOAT_OOB_FILL_NONE);
  }
  void* scr = nullptr;
  cudaGetSymbolAddress(&scr, g_scratch);
  cudaFuncSetAttribute(mega_kernel, cudaFuncAttributeMaxDynamicSharedMemorySize, SMEM_BYTES);
  cudaLaunchConfig_t cfg = {};
  cfg.gridDim = dim3(128); cfg.blockDim = dim3(384); cfg.dynamicSmemBytes = SMEM_BYTES; cfg.stream = cudaStreamPerThread;
  cudaLaunchAttribute at[1];
  at[0].id = cudaLaunchAttributeClusterDimension; at[0].val.clusterDim.x = 2; at[0].val.clusterDim.y = 1; at[0].val.clusterDim.z = 1;
  cfg.attrs = at; cfg.numAttrs = 1;
  int dev = 0, sms = 0, clusters = 0;
  cudaGetDevice(&dev);
  cudaDeviceGetAttribute(&sms, cudaDevAttrMultiProcessorCount, dev);
  cudaOccupancyMaxActiveClusters(&clusters, mega_kernel, &cfg);
  if (sms == 132 && clusters == 66) cfg.gridDim = dim3(132);
  cudaLaunchKernelEx(&cfg, mega_kernel, maps, (uint4*)scr, (__nv_bfloat16*)d_out);
}
```
